```python
import torch

def _softmax(x, axis=-1):
    return torch.softmax(x, dim=axis)
def _gelu(x):
    return torch.nn.functional.gelu(x, approximate="tanh")
def _silu(x):
    return torch.nn.functional.silu(x)
def _sigmoid(x):
    return torch.sigmoid(x)
def _layernorm(x, axis=-1, eps=1e-5):
    m = x.mean(dim=axis, keepdim=True)
    v = x.var(dim=axis, keepdim=True, unbiased=False)
    return (x - m) / torch.sqrt(v + eps)
def _scatter_add(tgt, idx, src, axis=0):
    return tgt.clone().index_add_(axis, idx, src)
def _segment_sum(src, seg, n):
    out = torch.zeros((n,) + src.shape[1:], dtype=src.dtype)
    return out.index_add_(0, seg, src)
def _pad(x, pw):
    flat = tuple(v for pair in reversed(pw) for v in pair)
    return torch.nn.functional.pad(x, flat)

kernel_name = 'recurrent_scan__ssm_conv_s4d__moe_arch_mod__prompt'

def setup_inputs():

    _w = (lambda a: (lambda t: t.to(torch.bfloat16) if t.is_floating_point() else t)(torch.as_tensor(a)))
    def _A_setup():
        Bsz, L, D, N = 1, 2048, 1024, 128
        return {
            "u": _w((lambda *s: torch.randn(*s, dtype=torch.bfloat16) * 0.05)(Bsz, L, D)),
            "log_A_real": _w((lambda *s: torch.randn(*s, dtype=torch.bfloat16) * 6.4)(D, N) * 0.5),
            "A_imag": _w((lambda *s: torch.randn(*s, dtype=torch.bfloat16) * 0.05)(D, N) * 3.14),
            "C_real": _w((lambda *s: torch.randn(*s, dtype=torch.bfloat16) * 0.05)(D, N) / N ** 0.5),
            "C_imag": _w((lambda *s: torch.randn(*s, dtype=torch.bfloat16) * 0.05)(D, N) / N ** 0.5),
            "log_dt": _w((lambda *s: torch.randn(*s, dtype=torch.bfloat16) * 0.05)(D) * 0.5 - 4.0),
            "D_skip": _w((lambda *s: torch.randn(*s, dtype=torch.bfloat16) * 0.05)(D)),
        }
    _A_in = _A_setup()

    def _B_setup():
        B, S, D, F, C = 1, 2048, 1024, 3584, 2
        return {
            "x": _w((lambda *s: torch.randn(*s, dtype=torch.bfloat16) * 0.05)(B, S, D)),
            "w_r": _w((lambda *s: torch.randn(*s, dtype=torch.bfloat16) * 0.05)(D)),
            "w_gate": _w((lambda *s: torch.randn(*s, dtype=torch.bfloat16) * 0.05)(D, F)),
            "w_up": _w((lambda *s: torch.randn(*s, dtype=torch.bfloat16) * 0.05)(D, F)),
            "w_down": _w((lambda *s: torch.randn(*s, dtype=torch.bfloat16) * 0.05)(F, D)),
        }
    _B_in = _B_setup()

    return {
        "A_u": _A_in["u"],
        "A_log_A_real": _A_in["log_A_real"],
        "A_A_imag": _A_in["A_imag"],
        "A_C_real": _A_in["C_real"],
        "A_C_imag": _A_in["C_imag"],
        "A_log_dt": _A_in["log_dt"],
        "A_D_skip": _A_in["D_skip"],
        "B_x": _B_in["x"],
        "B_w_r": _B_in["w_r"],
        "B_w_gate": _B_in["w_gate"],
        "B_w_up": _B_in["w_up"],
        "B_w_down": _B_in["w_down"],
    }

def reference(A_u, A_log_A_real, A_A_imag, A_C_real, A_C_imag, A_log_dt, A_D_skip, B_x, B_w_r, B_w_gate, B_w_up, B_w_down):
    def _A_ref(u, log_A_real, A_imag, C_real, C_imag, log_dt, D_skip):
        L = u.shape[1]
        dt = torch.exp(log_dt)
        A = -torch.exp(log_A_real) + 1j * A_imag
        C = (C_real + 1j * C_imag) * dt[:, None]
        pos = (lambda x, dt: x.to(dt))(torch.arange(L), log_dt.dtype)
        P = torch.exp((A * dt[:, None])[:, :, None] * pos[None, None, :])
        K = 2.0 * torch.einsum("dn,dnl->dl", C, P).real
        L2 = 2 * L
        u_t = (lambda x, *d: x.permute(*d))(u, 0, 2, 1)
        Kf = (lambda x, *a, **k: torch.fft.rfft(x.float(), *a, **k))(K, L2)
        Uf = (lambda x, *a, **k: torch.fft.rfft(x.float(), *a, **k))(u_t, L2)
        y = (lambda x, *a, **k: torch.fft.irfft(x, *a, **k).to(torch.bfloat16))(Uf * Kf[None, :, :], L2)[:, :, :L]
        y = (lambda x, *d: x.permute(*d))(y, 0, 2, 1)
        return y + u * D_skip[None, None, :]

    def _B_ref(x, w_r, w_gate, w_up, w_down):
        B, S, D = x.shape
        C = 2
        r = x @ w_r
        idx = torch.argsort(-r, axis=-1)[:, :C]
        idx_e = (lambda x, n, axis: torch.repeat_interleave(x, n, dim=axis))(idx.reshape(B, C, 1), D, axis=2)
        x_sel = (lambda x, i, axis: torch.take_along_dim(x, i, dim=axis))(x, idx_e, axis=1)
        g = _silu(x_sel @ w_gate)
        u = x_sel @ w_up
        y = (g * u) @ w_down
        r_sel = _sigmoid((lambda x, i, axis: torch.take_along_dim(x, i, dim=axis))(r, idx, axis=1))
        y = y * r_sel.reshape(B, C, 1)
        b_off = (torch.arange(B) * S).reshape(B, 1)
        flat_idx = (idx + b_off).reshape(B * C)
        zero = (x * 0.0).reshape(B * S, D)
        upd = _scatter_add(zero, flat_idx, y.reshape(B * C, D), axis=0)
        return x + upd.reshape(B, S, D)

    x = A_u
    xn = _layernorm(x, axis=-1)
    s = _A_ref(xn, A_log_A_real, A_A_imag, A_C_real, A_C_imag, A_log_dt, A_D_skip)
    g = _silu(_B_ref(xn, B_w_r, B_w_gate, B_w_up, B_w_down))
    return x + s * g
```

```cpp
#include <cuda_runtime.h>
#include <cuda.h>
#include <cuda_bf16.h>
#include <cuda_fp16.h>
#include <stdint.h>

#define TS(i)
#define TSL(i)

#define NSLOT 7
#define DEPTH 4

namespace {

constexpr int NTHREADS = 640;
constexpr int SPIN_LIMIT = 1 << 22;

constexpr int SM_SLAB = 0;
constexpr int SM_RING = 65536;
constexpr int SM_WB   = SM_RING + NSLOT * 8192;
constexpr int WB_SZ   = 7680;
constexpr int SM_U    = SM_WB + 8 * WB_SZ;
constexpr int U_HI    = 2240;
constexpr int U_SZ    = 4416;
constexpr int SM_XSEL = SM_U + 8 * U_SZ;
constexpr int XSEL_T  = 2112;
constexpr int SM_PAIR = SM_XSEL + 2 * XSEL_T;
constexpr int SM_H    = SM_PAIR + 1024;
constexpr int H_T     = 192;
constexpr int SM_KEYS = SM_H + 2 * H_T;
constexpr int SM_TOK  = SM_KEYS + 128;
constexpr int SM_FIX  = SM_TOK + 16;
constexpr int SM_BAR  = SM_FIX + 64;
constexpr int B_SLAB = 0, B_FULL = 1, B_EMPTY = B_FULL + NSLOT, B_KDONE = B_EMPTY + NSLOT, B_STG = B_KDONE + 1,
              B_FIX = B_STG + 8, B_PAIR = B_FIX + 1, B_TOK = B_PAIR + 4, NBAR = B_TOK + 1;
constexpr int SM_TOTAL = SM_BAR + NBAR * 8;
static_assert(SM_TOTAL <= 232448, "smem");
constexpr int KA_DP = 0;
constexpr int KA_O2 = 544;
constexpr int KA_E2 = 640;
constexpr int KA_O3 = 736;
constexpr int KA_E3 = 816;

struct Params {
    const __nv_bfloat16 *x, *lar, *aim, *cr, *ci, *logdt, *dskip, *wr;
    __nv_bfloat16* out;
};

__device__ uint4 g_stats[1024];
__device__ uint32_t g_part[128 * 56 * 16];
__device__ uint32_t g_epoch;

__device__ __forceinline__ uint4 ldg128(const void* p) {
    uint4 v; asm volatile("ld.global.nc.v4.u32 {%0,%1,%2,%3}, [%4];" : "=r"(v.x), "=r"(v.y), "=r"(v.z), "=r"(v.w) : "l"(p)); return v;
}
__device__ __forceinline__ uint4 ld_relaxed128(const void* p) {
    uint4 v;
    asm volatile("{ .reg .b128 t; ld.relaxed.gpu.global.b128 t, [%4]; mov.b128 {%0,%1,%2,%3}, t; }"
                 : "=r"(v.x), "=r"(v.y), "=r"(v.z), "=r"(v.w) : "l"(p) : "memory");
    return v;
}
__device__ __forceinline__ void st_relaxed128(void* p, uint4 v) {
    asm volatile("{ .reg .b128 t; mov.b128 t, {%1,%2,%3,%4}; st.relaxed.gpu.global.b128 [%0], t; }"
                 :: "l"(p), "r"(v.x), "r"(v.y), "r"(v.z), "r"(v.w) : "memory");
}
__device__ __forceinline__ void st_relaxed32(void* p, uint32_t v) {
    asm volatile("st.relaxed.gpu.global.u32 [%0], %1;" :: "l"(p), "r"(v) : "memory");
}
__device__ __forceinline__ uint32_t lds32(uint32_t a) { uint32_t v; asm volatile("ld.shared.u32 %0, [%1];" : "=r"(v) : "r"(a)); return v; }
__device__ __forceinline__ uint32_t lds16(uint32_t a) { uint32_t v; asm volatile("ld.shared.u16 %0, [%1];" : "=r"(v) : "r"(a)); return v; }
__device__ __forceinline__ uint2 lds64(uint32_t a) { uint2 v; asm volatile("ld.shared.v2.u32 {%0,%1}, [%2];" : "=r"(v.x), "=r"(v.y) : "r"(a)); return v; }
__device__ __forceinline__ uint4 lds128(uint32_t a) {
    uint4 v; asm volatile("ld.shared.v4.u32 {%0,%1,%2,%3}, [%4];" : "=r"(v.x), "=r"(v.y), "=r"(v.z), "=r"(v.w) : "r"(a)); return v;
}
__device__ __forceinline__ void sts16(uint32_t a, uint32_t v) { asm volatile("st.shared.u16 [%0], %1;" :: "r"(a), "h"((uint16_t)v) : "memory"); }
__device__ __forceinline__ void sts32(uint32_t a, uint32_t v) { asm volatile("st.shared.u32 [%0], %1;" :: "r"(a), "r"(v) : "memory"); }
__device__ __forceinline__ void sts128(uint32_t a, uint32_t x, uint32_t y, uint32_t z, uint32_t w) {
    asm volatile("st.shared.v4.u32 [%0], {%1,%2,%3,%4};" :: "r"(a), "r"(x), "r"(y), "r"(z), "r"(w) : "memory");
}
__device__ __forceinline__ void ldsm4(uint32_t a, uint32_t& r0, uint32_t& r1, uint32_t& r2, uint32_t& r3) {
    asm volatile("ldmatrix.sync.aligned.m8n8.x4.shared.b16 {%0,%1,%2,%3}, [%4];" : "=r"(r0), "=r"(r1), "=r"(r2), "=r"(r3) : "r"(a));
}
__device__ __forceinline__ void ldsm4t(uint32_t a, uint32_t& r0, uint32_t& r1, uint32_t& r2, uint32_t& r3) {
    asm volatile("ldmatrix.sync.aligned.m8n8.x4.trans.shared.b16 {%0,%1,%2,%3}, [%4];" : "=r"(r0), "=r"(r1), "=r"(r2), "=r"(r3) : "r"(a));
}
__device__ __forceinline__ void ldsm2(uint32_t a, uint32_t& r0, uint32_t& r1) {
    asm volatile("ldmatrix.sync.aligned.m8n8.x2.shared.b16 {%0,%1}, [%2];" : "=r"(r0), "=r"(r1) : "r"(a));
}
__device__ __forceinline__ void mma_f16(float (&d)[4], uint32_t a0, uint32_t a1, uint32_t a2, uint32_t a3, uint32_t b0, uint32_t b1) {
    asm("mma.sync.aligned.m16n8k16.row.col.f32.f16.f16.f32 {%0,%1,%2,%3}, {%4,%5,%6,%7}, {%8,%9}, {%0,%1,%2,%3};"
        : "+f"(d[0]), "+f"(d[1]), "+f"(d[2]), "+f"(d[3]) : "r"(a0), "r"(a1), "r"(a2), "r"(a3), "r"(b0), "r"(b1));
}
__device__ __forceinline__ void mma_bf16(float (&d)[4], uint32_t a0, uint32_t a1, uint32_t a2, uint32_t a3, uint32_t b0, uint32_t b1) {
    asm("mma.sync.aligned.m16n8k16.row.col.f32.bf16.bf16.f32 {%0,%1,%2,%3}, {%4,%5,%6,%7}, {%8,%9}, {%0,%1,%2,%3};"
        : "+f"(d[0]), "+f"(d[1]), "+f"(d[2]), "+f"(d[3]) : "r"(a0), "r"(a1), "r"(a2), "r"(a3), "r"(b0), "r"(b1));
}
__device__ __forceinline__ void mma_h(uint32_t& d0, uint32_t& d1, const uint32_t (&a)[4], uint32_t b0, uint32_t b1) {
    asm("mma.sync.aligned.m16n8k16.row.col.f16.f16.f16.f16 {%0,%1}, {%2,%3,%4,%5}, {%6,%7}, {%8,%8};"
        : "=r"(d0), "=r"(d1) : "r"(a[0]), "r"(a[1]), "r"(a[2]), "r"(a[3]), "r"(b0), "r"(b1), "r"(0u));
}
__device__ __forceinline__ uint32_t prmt(uint32_t a, uint32_t b, uint32_t s) { uint32_t d; asm("prmt.b32 %0, %1, %2, %3;" : "=r"(d) : "r"(a), "r"(b), "r"(s)); return d; }
__device__ __forceinline__ uint32_t pack_h(float lo, float hi) { uint32_t d; asm("cvt.rn.f16x2.f32 %0, %1, %2;" : "=r"(d) : "f"(hi), "f"(lo)); return d; }
__device__ __forceinline__ uint32_t pack_b(float lo, float hi) { uint32_t d; asm("cvt.rn.bf16x2.f32 %0, %1, %2;" : "=r"(d) : "f"(hi), "f"(lo)); return d; }
__device__ __forceinline__ float blo(uint32_t v) { return __uint_as_float(v << 16); }
__device__ __forceinline__ float bhi(uint32_t v) { return __uint_as_float(v & 0xFFFF0000u); }
__device__ __forceinline__ float rb(float v) { return blo(pack_b(v, v)); }
__device__ __forceinline__ uint32_t bsub2(uint32_t a, uint32_t b) { uint32_t d; asm("sub.rn.bf16x2 %0, %1, %2;" : "=r"(d) : "r"(a), "r"(b)); return d; }
__device__ __forceinline__ uint32_t badd2(uint32_t a, uint32_t b) { uint32_t d; asm("add.rn.bf16x2 %0, %1, %2;" : "=r"(d) : "r"(a), "r"(b)); return d; }
__device__ __forceinline__ uint32_t bmul2(uint32_t a, uint32_t b) { uint32_t d; asm("mul.rn.bf16x2 %0, %1, %2;" : "=r"(d) : "r"(a), "r"(b)); return d; }
__device__ __forceinline__ uint32_t bfma2(uint32_t a, uint32_t b, uint32_t c) { uint32_t d; asm("fma.rn.bf16x2 %0, %1, %2, %3;" : "=r"(d) : "r"(a), "r"(b), "r"(c)); return d; }
__device__ __forceinline__ uint32_t norm2(uint32_t x, uint32_t m, uint32_t hi, uint32_t lo) {
    uint32_t a = bsub2(x, m);
    return bfma2(a, hi, bmul2(a, lo));
}
__device__ __forceinline__ float ex2(float v) { float d; asm("ex2.approx.ftz.f32 %0, %1;" : "=f"(d) : "f"(v)); return d; }
__device__ __forceinline__ float rcp(float v) { float d; asm("rcp.approx.ftz.f32 %0, %1;" : "=f"(d) : "f"(v)); return d; }
__device__ __forceinline__ float sigmoidf_(float v) { return rcp(1.0f + ex2(-1.4426950408889634f * v)); }
__device__ __forceinline__ float siluf_(float v) { return v * sigmoidf_(v); }

__device__ __forceinline__ void mbar_init(uint32_t a, int n) { asm volatile("mbarrier.init.shared::cta.b64 [%0], %1;" :: "r"(a), "r"(n) : "memory"); }
__device__ __forceinline__ void mbar_expect(uint32_t a, int tx) { asm volatile("mbarrier.arrive.expect_tx.shared::cta.b64 _, [%0], %1;" :: "r"(a), "r"(tx) : "memory"); }
__device__ __forceinline__ void mbar_arrive(uint32_t a) { asm volatile("mbarrier.arrive.shared::cta.b64 _, [%0];" :: "r"(a) : "memory"); }
__device__ __forceinline__ void mbar_arrive_cluster(uint32_t a) { asm volatile("mbarrier.arrive.release.cluster.shared::cluster.b64 _, [%0];" :: "r"(a) : "memory"); }
__device__ __forceinline__ void mbar_wait(uint32_t a, int parity) {
    uint32_t done; int it = 0;
    do {
        asm volatile("{ .reg .pred p; mbarrier.try_wait.parity.acquire.cluster.shared::cta.b64 p, [%1], %2; selp.u32 %0, 1, 0, p; }"
                     : "=r"(done) : "r"(a), "r"(parity) : "memory");
    } while (!done && ++it < SPIN_LIMIT);
}
__device__ __forceinline__ uint32_t mapa(uint32_t a, uint32_t rank) { uint32_t d; asm("mapa.shared::cluster.u32 %0, %1, %2;" : "=r"(d) : "r"(a), "r"(rank)); return d; }
__device__ __forceinline__ void st_async2(uint32_t a, uint32_t x, uint32_t y, uint32_t bar) {
    asm volatile("st.async.weak.shared::cluster.mbarrier::complete_tx::bytes.v2.b32 [%0], {%1,%2}, [%3];" :: "r"(a), "r"(x), "r"(y), "r"(bar) : "memory");
}
__device__ __forceinline__ void bar_sync(int id, int n) { asm volatile("bar.sync %0, %1;" :: "r"(id), "r"(n) : "memory"); }
__device__ __forceinline__ void bar_arrive(int id, int n) { asm volatile("bar.arrive %0, %1;" :: "r"(id), "r"(n) : "memory"); }
__device__ __forceinline__ void cluster_arrive() { asm volatile("barrier.cluster.arrive.relaxed.aligned;" ::: "memory"); }
__device__ __forceinline__ void cluster_wait() { asm volatile("barrier.cluster.wait.aligned;" ::: "memory"); }
__device__ __forceinline__ void tma2d(uint32_t dst, const CUtensorMap* tm, int c0, int c1, uint32_t bar, uint64_t pol) {
    asm volatile("cp.async.bulk.tensor.2d.shared::cluster.global.mbarrier::complete_tx::bytes.L2::cache_hint [%0], [%1, {%3, %4}], [%2], %5;"
                 :: "r"(dst), "l"(tm), "r"(bar), "r"(c0), "r"(c1), "l"(pol) : "memory");
}

struct cf { float r, i; };
__device__ __forceinline__ cf cmul(cf a, cf b) { return {a.r * b.r - a.i * b.i, a.r * b.i + a.i * b.r}; }
__device__ __forceinline__ cf csq(cf a) { return {a.r * a.r - a.i * a.i, (a.r + a.r) * a.i}; }
__device__ __forceinline__ cf cexp_(float a2, float b) { float m = ex2(a2); return {m * __cosf(b), m * __sinf(b)}; }
__device__ __forceinline__ uint32_t pk(cf a) { return pack_h(a.r, a.i); }
__device__ __forceinline__ uint32_t pkj(cf a) { return pack_h(-a.i, a.r); }
__device__ __forceinline__ uint32_t hprod(uint32_t x, uint32_t y, uint32_t yj) {
    __half2 X = *reinterpret_cast<__half2*>(&x), Y = *reinterpret_cast<__half2*>(&y), J = *reinterpret_cast<__half2*>(&yj);
    __half2 R = __hfma2(__high2half2(X), J, __hmul2(__low2half2(X), Y));
    return *reinterpret_cast<uint32_t*>(&R);
}
__device__ __forceinline__ float pick(uint2 v, int s) { uint32_t w = (s & 2) ? v.y : v.x; return (s & 1) ? bhi(w) : blo(w); }
__device__ __forceinline__ uint32_t band(int k0, int lo, int hi) {
    return ((k0 >= lo && k0 <= hi) ? 0x3C00u : 0u) | ((k0 + 1 >= lo && k0 + 1 <= hi) ? 0x3C000000u : 0u);
}

__global__ void __cluster_dims__(2, 1, 1) __launch_bounds__(NTHREADS, 1)
fused_kernel(const Params p, const __grid_constant__ CUtensorMap tm_x, const __grid_constant__ CUtensorMap tm_g,
             const __grid_constant__ CUtensorMap tm_u, const __grid_constant__ CUtensorMap tm_d)
{
    extern __shared__ __align__(1024) uint8_t smem_raw[];
    const uint32_t sm = (uint32_t)__cvta_generic_to_shared(smem_raw);
    const uint32_t bars = sm + SM_BAR;
    const int tid = threadIdx.x, warp = tid >> 5, lane = tid & 31;
    const int g = lane >> 2, q = lane & 3;
    const int c = blockIdx.x, rank = c & 1, G = c >> 1;

    if (warp < 8) {
        const int ch = c * 8 + warp;
        const uint2 lar4 = __ldg(reinterpret_cast<const uint2*>(p.lar + ch * 128) + lane);
        const uint2 aim4 = __ldg(reinterpret_cast<const uint2*>(p.aim + ch * 128) + lane);
        const uint2 cr4 = __ldg(reinterpret_cast<const uint2*>(p.cr + ch * 128) + lane);
        const uint2 ci4 = __ldg(reinterpret_cast<const uint2*>(p.ci + ch * 128) + lane);
        const float logdt = __bfloat162float(p.logdt[ch]);
        const float dsk = __bfloat162float(p.dskip[ch]);
        cluster_arrive();
        const uint32_t wb = sm + SM_WB + warp * WB_SZ;
        const uint32_t ub = sm + SM_U + warp * U_SZ;
        if (lane < 16) sts128(ub + (lane >> 3) * U_HI + (lane & 7) * 16, 0, 0, 0, 0);
        sts32(wb + lane * 4, 0x00003C00u);

        const float dt = rb(expf(logdt));
        float outscale, cs;
        {
            uint32_t m0 = __vmaxu2(__vmaxu2(cr4.x & 0x7FFF7FFFu, cr4.y & 0x7FFF7FFFu), __vmaxu2(ci4.x & 0x7FFF7FFFu, ci4.y & 0x7FFF7FFFu));
            uint32_t m1 = max(m0 & 0xFFFFu, m0 >> 16);
            float cmax = blo(__reduce_max_sync(0xFFFFFFFFu, m1));
            outscale = fmaxf(fmaxf(2.0f * dt * cmax, fabsf(dsk) * (1.0f / 1024.0f)), 1e-30f);
            cs = 2.0f * dt / outscale;
        }
        TSL(0);
        float kacc[2][3][4];
#pragma unroll
        for (int i = 0; i < 2; i++)
#pragma unroll
            for (int j = 0; j < 3; j++) kacc[i][j][0] = kacc[i][j][1] = kacc[i][j][2] = kacc[i][j][3] = 0.f;
        {
            const uint32_t st = wb + lane * 4;
            const uint32_t la = wb + ((lane & 7) + (lane & 8)) * 144 + (lane >> 4) * 16;
            const uint32_t lb = wb + (32 + (lane & 7)) * 144 + (lane >> 3) * 16;
            const uint32_t lb2 = wb + (48 + min(lane & 7, 4)) * 144 + (lane >> 3) * 16;
#pragma unroll 1
            for (int s = 0; s < 4; s++) {
                const float ea = rb(ex2(pick(lar4, s) * 1.4426950408889634f));
                const float a2 = -(ea * dt) * 1.4426950408889634f;
                const float b = pick(aim4, s) * dt;
                {
                    cf z8 = cexp_(a2 * 8.f, b * 8.f);
                    cf z16 = csq(z8), z24 = cmul(z16, z8), z32 = csq(z16), z64 = csq(z32), z96 = cmul(z64, z32), z128 = csq(z64);
                    uint32_t r[16];
                    r[1] = pk(z8); r[2] = pk(z16); r[3] = pk(z24); r[4] = pk(z32); r[8] = pk(z64); r[12] = pk(z96);
                    const uint32_t j4 = pkj(z32), j8 = pkj(z64), j12 = pkj(z96), h = pk(z128), hj = pkj(z128);
#pragma unroll
                    for (int i = 1; i < 4; i++) { r[4 + i] = hprod(r[i], r[4], j4); r[8 + i] = hprod(r[i], r[8], j8); r[12 + i] = hprod(r[i], r[12], j12); }
                    sts32(st + 16 * 144, h);
#pragma unroll
                    for (int i = 1; i < 16; i++) { sts32(st + i * 144, r[i]); sts32(st + (16 + i) * 144, hprod(r[i], h, hj)); }
                }
                {
                    cf C = {pick(cr4, s) * cs, -pick(ci4, s) * cs};
                    cf z = cexp_(a2, -b), v = cexp_(a2 * 256.f, -b * 256.f);
                    cf z4 = csq(csq(z)), v4 = csq(csq(v));
                    cf c1 = cmul(C, z), c2 = cmul(c1, z), c3 = cmul(c2, z);
                    cf d1 = cmul(C, v), d2 = cmul(d1, v), d3 = cmul(d2, v);
                    const uint32_t l0 = pk(C), l1 = pk(c1), l2 = pk(c2), l3 = pk(c3), e1 = pk(d1), e2 = pk(d2), e3 = pk(d3);
                    const uint32_t f = pk(z4), fj = pkj(z4), w = pk(v), wj = pkj(v), y = pk(v4), yj = pkj(v4);
                    const uint32_t l4 = hprod(l0, f, fj), l6 = hprod(l2, f, fj), e4 = hprod(l0, y, yj);
                    sts32(st + 32 * 144, l0); sts32(st + 33 * 144, l1); sts32(st + 34 * 144, l2); sts32(st + 35 * 144, l3);
                    sts32(st + 36 * 144, l4); sts32(st + 37 * 144, hprod(l1, f, fj)); sts32(st + 38 * 144, l6); sts32(st + 39 * 144, hprod(l3, f, fj));
                    sts32(st + 40 * 144, e1);
                    sts32(st + 41 * 144, hprod(l2, w, wj));
                    sts32(st + 42 * 144, hprod(e1, f, fj));
                    sts32(st + 43 * 144, hprod(l6, w, wj));
                    sts32(st + 44 * 144, e2);
                    sts32(st + 45 * 144, hprod(e2, f, fj));
                    sts32(st + 46 * 144, e3);
                    sts32(st + 47 * 144, hprod(e3, f, fj));
                    sts32(st + 48 * 144, e4);
                    sts32(st + 49 * 144, hprod(e1, y, yj));
                    sts32(st + 50 * 144, hprod(e2, y, yj));
                    sts32(st + 51 * 144, hprod(e3, y, yj));
                    sts32(st + 52 * 144, hprod(e4, y, yj));
                }
                __syncwarp();
#pragma unroll
                for (int kp = 0; kp < 2; kp++) {
                    uint32_t bb[3][4];
                    ldsm4(lb + kp * 64, bb[0][0], bb[0][1], bb[0][2], bb[0][3]);
                    ldsm4(lb + 8 * 144 + kp * 64, bb[1][0], bb[1][1], bb[1][2], bb[1][3]);
                    ldsm4(lb2 + kp * 64, bb[2][0], bb[2][1], bb[2][2], bb[2][3]);
#pragma unroll
                    for (int k2 = 0; k2 < 2; k2++)
#pragma unroll
                        for (int mt = 0; mt < 2; mt++) {
                            uint32_t a0, a1, a2r, a3;
                            ldsm4(la + mt * 16 * 144 + (kp * 2 + k2) * 32, a0, a1, a2r, a3);
#pragma unroll
                            for (int nt = 0; nt < 3; nt++) mma_f16(kacc[mt][nt], a0, a1, a2r, a3, bb[nt][2 * k2], bb[nt][2 * k2 + 1]);
                        }
                }
                __syncwarp();
            }
        }
        TSL(1);
        const uint32_t ka = wb + 4096;
        if (lane == 0) kacc[0][0][0] += dsk / outscale;
#pragma unroll
        for (int i = 0; i < 7; i++) sts128(ka + (i * 32 + lane) * 16, 0, 0, 0, 0);
#pragma unroll
        for (int mt = 0; mt < 2; mt++)
#pragma unroll
            for (int hi = 0; hi < 2; hi++) {
                const int R = 16 * mt + 8 * hi + g;
                sts32(wb + (8 * R + 2 * q) * 2, pack_h(kacc[mt][0][2 * hi], kacc[mt][0][2 * hi + 1]));
                const int i1 = q < 2 ? 256 + 4 * R + 2 * q : 256 + 64 * q + 2 * R;
                sts32(wb + i1 * 2, pack_h(kacc[mt][1][2 * hi], kacc[mt][1][2 * hi + 1]));
                const uint32_t v2 = pack_h(kacc[mt][2][2 * hi], kacc[mt][2][2 * hi + 1]);
                if (q < 2 || (q == 2 && R == 0)) sts16(wb + (512 + 64 * q + R) * 2, v2);
                if (q < 2) sts16(wb + (544 + 64 * q + R) * 2, v2 >> 16);
            }
        __syncwarp();
        {
            const uint32_t dp = ka + (KA_DP + 8 + lane) * 4;
            const int o = (lane + ((lane >> 1) & 1)) >> 1;
#pragma unroll
            for (int it = 0; it < 17; it++) {
                const uint32_t v = lds16(wb + (it < 8 ? 32 * it + lane : it < 16 ? 256 + 16 * (it - 8) + o : 384) * 2);
                if (it < 16 || lane < 3) { sts16(dp + it * 128, v); sts16(dp + it * 128 + 6, v); }
            }
#pragma unroll
            for (int it = 0; it < 4; it++) {
                const int i = 32 * it + lane;
                const uint32_t v = lds16(wb + (385 + i) * 2), w = lds16(wb + (513 + i) * 2);
                const uint32_t a2a = ka + (((i & 1) ? KA_E2 : KA_O2) + 14 + (i >> 1)) * 4;
                sts16(a2a, v); sts16(a2a + 10, v);
                const uint32_t a3a = ka + (((i & 1) ? KA_E3 + 1 : KA_O3) + 8 + (i >> 1)) * 4;
                sts16(a3a, w); sts16(a3a + 6, w);
            }
        }
        uint32_t xb0, xb1;
        {
            const uint32_t v = lds16(wb + 512 * 2), v2 = v | (v << 16);
            xb0 = v2 & ((band(2 * q, g + 4, g + 5) >> 10 & 0x00010001u) * 0xFFFFu);
            xb1 = v2 & ((band(2 * q + 8, g + 4, g + 5) >> 10 & 0x00010001u) * 0xFFFFu);
        }
        __syncwarp();
        cluster_wait();
        if (lane < 2) mbar_arrive_cluster(mapa(bars + B_KDONE * 8, lane));
        TSL(2);
        bar_sync(2, 512);
        asm volatile("setmaxnreg.inc.sync.aligned.u32 168;");
        TSL(3);

        float acc[16][4];
        {
            const uint32_t se = ub + (q < 2 ? U_HI + (g + 7) * 16 + 8 + q * 4 : (g + 8) * 16 + (q - 2) * 4);
            const uint32_t so = ub + (q < 2 ? (g + 8) * 16 + 8 + q * 4 : U_HI + (g + 8) * 16 + (q - 2) * 4);
            const uint32_t A3[4] = {band(2 * q, g, g + 8), band(2 * q, g + 1, g + 7), band(2 * q + 8, g, g + 8), band(2 * q + 8, g + 1, g + 7)};
            uint32_t w9[8][2], w7[8][2];
#pragma unroll
            for (int y = 0; y < 8; y++) {
                const uint32_t sm1 = lds32(so + y * 128 - 16), s0 = lds32(se + y * 128), s1 = lds32(so + y * 128);
                mma_h(w9[y][0], w7[y][0], A3, s0, s1);
                mma_h(w9[y][1], w7[y][1], A3, sm1, s0);
            }
            float a3[4][2][4];
#pragma unroll
            for (int i = 0; i < 4; i++)
#pragma unroll
                for (int j = 0; j < 2; j++) a3[i][j][0] = a3[i][j][1] = a3[i][j][2] = a3[i][j][3] = 0.f;
            const uint32_t ko = ka + (KA_O3 - 56 + g - 2 * q) * 4, ke = ka + (KA_E3 - 56 + g - 2 * q) * 4;
            uint32_t po = 0, pe0 = 0, pe1 = 0;
#pragma unroll
            for (int cc = 7; cc <= 14; cc++) {
                const uint32_t no = lds32(ko + (cc + 1) * 32), ne0 = lds32(ke + (cc + 1) * 32), ne1 = lds32(ke + (cc + 1) * 32 + 4);
#pragma unroll
                for (int T = 4; T < 8; T++) {
                    const int y = 2 * T - cc;
                    if (y >= 0) {
                        mma_f16(a3[T - 4][0], pe0, ne0, po, no, w9[y][0], w7[y][1]);
                        mma_f16(a3[T - 4][1], pe1, ne1, po, no, w9[y][1], w7[y][0]);
                    }
                }
                po = no; pe0 = ne0; pe1 = ne1;
            }
#pragma unroll
            for (int t = 0; t < 8; t++) acc[t][0] = acc[t][1] = acc[t][2] = acc[t][3] = 0.f;
#pragma unroll
            for (int T = 4; T < 8; T++)
#pragma unroll
                for (int b7 = 0; b7 < 2; b7++) {
                    acc[2 * T + b7][0] = a3[T - 4][0][2 * b7]; acc[2 * T + b7][1] = a3[T - 4][0][2 * b7 + 1];
                    acc[2 * T + b7][2] = a3[T - 4][1][2 * b7]; acc[2 * T + b7][3] = a3[T - 4][1][2 * b7 + 1];
                }
        }
        TSL(4);
        {
            const uint32_t se = ub + (q < 1 ? U_HI + (g + 7) * 16 + 12 : (g + 8) * 16 + (q - 1) * 4);
            const uint32_t so = ub + (q < 1 ? (g + 8) * 16 + 12 : U_HI + (g + 8) * 16 + (q - 1) * 4);
            const uint32_t A2[4] = {band(2 * q, g + 5, g + 7), band(2 * q, g, g + 4), band(2 * q + 8, g + 5, g + 7), band(2 * q + 8, g, g + 4)};
            const uint32_t ko = ka + (KA_O2 - 50 + 2 * g - 4 * q) * 4, ke = ka + (KA_E2 - 50 + 2 * g - 4 * q) * 4;
            uint32_t ro[5][3], re[5][3];
#pragma unroll
            for (int cc = 4; cc <= 8; cc++) {
                ro[cc - 4][0] = lds32(ko + cc * 64 - 4); re[cc - 4][0] = lds32(ke + cc * 64 - 4);
                const uint2 o2 = lds64(ko + cc * 64), e2 = lds64(ke + cc * 64);
                ro[cc - 4][1] = o2.x; ro[cc - 4][2] = o2.y; re[cc - 4][1] = e2.x; re[cc - 4][2] = e2.y;
            }
            uint32_t gw[2][2][2];
            {
                const uint32_t sm1 = lds32(so - 16), s0 = lds32(se), s1 = lds32(so);
                mma_h(gw[0][0][0], gw[0][0][1], A2, sm1, s0);
                mma_h(gw[0][1][0], gw[0][1][1], A2, s0, s1);
            }
#pragma unroll
            for (int y = 0; y < 12; y++) {
                if (y + 1 < 12) {
                    const uint32_t sm1 = lds32(so + (y + 1) * 128 - 16), s0 = lds32(se + (y + 1) * 128), s1 = lds32(so + (y + 1) * 128);
                    mma_h(gw[(y + 1) & 1][0][0], gw[(y + 1) & 1][0][1], A2, sm1, s0);
                    mma_h(gw[(y + 1) & 1][1][0], gw[(y + 1) & 1][1][1], A2, s0, s1);
                }
#pragma unroll
                for (int be = 0; be < 2; be++)
#pragma unroll
                    for (int cc = 4; cc <= 8; cc++)
                        if (y + cc < 16)
                            mma_f16(acc[y + cc], ro[cc - 4][1 - be], ro[cc - 4][2 - be], re[cc - 4][1 - be], re[cc - 4][2 - be],
                                    gw[y & 1][be][0], gw[y & 1][be][1]);
            }
        }
        TSL(5);
        {
            uint32_t kb[66];
            const uint32_t kd = ka + (KA_DP + 8 + g - 2 * q) * 4;
#pragma unroll
            for (int z = 0; z < 66; z++) kb[z] = lds32(kd + z * 32);
            mbar_wait(bars + B_KDONE * 8, 0);
            mbar_wait(bars + B_TOK * 8, 0);
            int tk[2]; uint32_t sel[2], fixa[2];
#pragma unroll
            for (int k = 0; k < 2; k++) {
                const int t = 0xFFFF - (lds32(sm + SM_TOK + 4 * k) & 0xFFFF);
                tk[k] = (((t >> 4) & 7) == g && ((t >> 1) & 3) == q) ? (t >> 7) : -1;
                sel[k] = 0x10 + 0x22 * (t & 1) + 0x44 * ((t >> 3) & 1);
                fixa[k] = mapa(sm, k);
            }
            const int chl = rank * 8 + warp;
            const uint32_t stg_off = SM_WB + chl * 256 + (((lane >> 1) ^ ((chl & 1) + 4 * (chl >> 3))) * 16) + (lane & 1) * 8;
            const uint32_t lu = ub + ((lane >> 3) & 1) * U_HI + ((lane & 7) + 8) * 16;
            constexpr int PF = 2;
            uint32_t sq[PF + 1][2];
            uint32_t prev = 0;
#pragma unroll
            for (int i = 0; i < PF; i++) ldsm2(lu + (i - 7) * 16, sq[i][0], sq[i][1]);
#pragma unroll
            for (int xi = 0; xi < 128; xi++) {
                const int x = xi - 7;
                if (xi + PF < 128) ldsm2(lu + (x + PF) * 16, sq[(xi + PF) % (PF + 1)][0], sq[(xi + PF) % (PF + 1)][1]);
                const uint32_t s0 = sq[xi % (PF + 1)][0], s1 = sq[xi % (PF + 1)][1];
#pragma unroll
                for (int t = 0; t < 16; t++) {
                    const int cc = 8 * t - x;
                    if (cc >= 0 && cc <= 32) mma_f16(acc[t], prev, s0, s0, s1, kb[2 * cc + 1], kb[2 * cc]);
                    if (cc == 64) mma_f16(acc[t], prev, s0, s0, s1, xb0, xb1);
                }
                prev = s1;
                if (x >= 0 && (x & 7) == 0) {
                    const int t = x >> 3;
                    const uint32_t sa = pack_b(acc[t][0] * outscale, acc[t][1] * outscale);
                    const uint32_t sb = pack_b(acc[t][2] * outscale, acc[t][3] * outscale);
                    const float2 ua = __half22float2(*reinterpret_cast<const __half2*>(&s0));
                    const float2 uc = __half22float2(*reinterpret_cast<const __half2*>(&s1));
                    const uint32_t pa = bmul2(sa, pack_b(siluf_(ua.x), siluf_(ua.y)));
                    const uint32_t pb = bmul2(sb, pack_b(siluf_(uc.x), siluf_(uc.y)));
                    st_async2(fixa[t & 1] + stg_off + (t >> 1) * WB_SZ, pa, pb, fixa[t & 1] + SM_BAR + (B_STG + (t >> 1)) * 8);
#pragma unroll
                    for (int k = 0; k < 2; k++)
                        asm volatile("{ .reg .pred p; setp.eq.s32 p, %0, %1;\n"
                                     "@p st.async.weak.shared::cluster.mbarrier::complete_tx::bytes.b32 [%2], %3, [%4]; }"
                                     :: "r"(tk[k]), "r"(t), "r"(fixa[k] + SM_FIX + chl * 4), "r"(prmt(sa, sb, sel[k])),
                                        "r"(fixa[k] + SM_BAR + B_FIX * 8) : "memory");
                }
            }
        }
        TSL(6);
    } else if (warp < 16) {
        const int v = warp - 8, j = tid - 256;
        uint4 xa[4], xc[4], w4[4];
        {
            const uint4* ra = reinterpret_cast<const uint4*>(p.x + (size_t)(16 * c + 2 * v) * 1024) + lane;
#pragma unroll
            for (int k = 0; k < 4; k++) { xa[k] = ldg128(ra + 32 * k); xc[k] = ldg128(ra + 128 + 32 * k); }
#pragma unroll
            for (int k = 0; k < 4; k++) w4[k] = ldg128(reinterpret_cast<const uint4*>(p.wr) + 32 * k + lane);
        }
        uint32_t tag;
        asm volatile("ld.relaxed.gpu.global.u32 %0, [%1];" : "=r"(tag) : "l"(&g_epoch) : "memory");
        cluster_arrive();
        uint4* const my_stats = g_stats + (c >> 4) * 128 + (v & 3) * 32 + ((2 * c) & 31);
        if (v < 4 && lane < 2) st_relaxed128(my_stats + lane, make_uint4(0, 0, 0, 0));
        uint32_t* const my_part = g_part + ((2 * (32 * rank + v) + (q & 1)) * 56 + G) * 16 + g + 8 * (q >> 1);
        if (v < 4 && G < 56) {
#pragma unroll
            for (int n = 0; n < 8; n++) st_relaxed32(my_part + n * 8 * 56 * 16, 0);
        }
        bar_sync(1, 256);
        tag = tag % 3 + 1;
        {
            constexpr uint32_t ONE = 0x3F803F80u;
            float sw[4] = {0, 0, 0, 0}, sA[4] = {0, 0, 0, 0}, sB[4] = {0, 0, 0, 0};
            float qA[2][4] = {{0, 0, 0, 0}, {0, 0, 0, 0}}, qB[2][4] = {{0, 0, 0, 0}, {0, 0, 0, 0}};
#pragma unroll
            for (int k = 0; k < 4; k++) mma_bf16(sw, w4[k].x, w4[k].y, w4[k].z, w4[k].w, ONE, ONE);
#pragma unroll
            for (int k = 0; k < 4; k++) {
                mma_bf16(sA, xa[k].x, xa[k].y, xa[k].z, xa[k].w, ONE, ONE);
                mma_bf16(qA[0], xa[k].x, w4[k].x, xa[k].y, w4[k].y, xa[k].x, xa[k].y);
                mma_bf16(qA[1], xa[k].z, w4[k].z, xa[k].w, w4[k].w, xa[k].z, xa[k].w);
                mma_bf16(sB, xc[k].x, xc[k].y, xc[k].z, xc[k].w, ONE, ONE);
                mma_bf16(qB[0], xc[k].x, w4[k].x, xc[k].y, w4[k].y, xc[k].x, xc[k].y);
                mma_bf16(qB[1], xc[k].z, w4[k].z, xc[k].w, w4[k].w, xc[k].z, xc[k].w);
            }
            TSL(8);
            const bool dg = q == (g >> 1), od = g & 1;
            float r0 = dg ? (od ? qA[0][1] + qA[1][1] : qA[0][0] + qA[1][0]) : 0.f;
            float r1 = dg ? (od ? qA[0][3] + qA[1][3] : qA[0][2] + qA[1][2]) : 0.f;
            float r2 = dg ? (od ? qB[0][1] + qB[1][1] : qB[0][0] + qB[1][0]) : 0.f;
            float r3 = dg ? (od ? qB[0][3] + qB[1][3] : qB[0][2] + qB[1][2]) : 0.f;
            const bool rowb = lane & 1;
            float ss = (rowb ? r2 : r0) + __shfl_xor_sync(0xFFFFFFFFu, rowb ? r0 : r2, 1);
            float dw = (rowb ? r3 : r1) + __shfl_xor_sync(0xFFFFFFFFu, rowb ? r1 : r3, 1);
            float sx = rowb ? sB[0] + sB[2] : sA[0] + sA[2];
            float ws = sw[0] + sw[2];
            ss += __shfl_xor_sync(0xFFFFFFFFu, ss, 2); dw += __shfl_xor_sync(0xFFFFFFFFu, dw, 2);
#pragma unroll
            for (int o = 4; o < 32; o <<= 1) {
                ss += __shfl_xor_sync(0xFFFFFFFFu, ss, o); dw += __shfl_xor_sync(0xFFFFFFFFu, dw, o);
                sx += __shfl_xor_sync(0xFFFFFFFFu, sx, o); ws += __shfl_xor_sync(0xFFFFFFFFu, ws, o);
            }
            const float mean = sx * (1.0f / 1024.0f);
            const float var = fmaxf(ss * (1.0f / 1024.0f) - mean * mean, 0.f);
            const float m = rb(mean);
            float sd; asm("sqrt.approx.f32 %0, %1;" : "=f"(sd) : "f"(rb(rb(var) + 1e-5f)));
            const float rs = rcp(rb(sd));
            const float hi = rb(rs);
            const uint32_t p0 = pack_b(m, hi), p1 = pack_b(rs - hi, rs * (dw - m * ws));
            const uint32_t o0 = __shfl_xor_sync(0xFFFFFFFFu, p0, 1), o1 = __shfl_xor_sync(0xFFFFFFFFu, p1, 1);
            if (lane == 0) {
                const uint32_t tb = ((tag & 1) << 15) | ((tag >> 1) << 31);
                st_relaxed128(my_stats + (v >> 2), make_uint4(prmt(p0, o0, 0x5410), (prmt(p0, o0, 0x7632) & 0x7FFF7FFFu) | tb,
                                                              prmt(p1, o1, 0x5410), prmt(p1, o1, 0x7632)));
            }
        }
        TSL(9);
        cluster_wait();
        mbar_wait(bars + B_SLAB * 8, 0);
        TSL(10);
        uint32_t xt[8][4];
        {
            const uint32_t a = sm + SM_SLAB + j * 32 + ((rank ^ ((j >> 2) & 1)) * 16);
#pragma unroll
            for (int pp = 0; pp < 4; pp++) {
                const uint4 e = lds128(a + (2 * pp) * 8192), o = lds128(a + (2 * pp + 1) * 8192);
                xt[0][pp] = prmt(e.x, o.x, 0x5410); xt[1][pp] = prmt(e.x, o.x, 0x7632);
                xt[2][pp] = prmt(e.y, o.y, 0x5410); xt[3][pp] = prmt(e.y, o.y, 0x7632);
                xt[4][pp] = prmt(e.z, o.z, 0x5410); xt[5][pp] = prmt(e.z, o.z, 0x7632);
                xt[6][pp] = prmt(e.w, o.w, 0x5410); xt[7][pp] = prmt(e.w, o.w, 0x7632);
            }
        }
        uint4 st[4];
        {
            const uint32_t tb = ((tag & 1) << 15) | ((tag >> 1) << 31);
            const uint4* src = g_stats + v * 128 + lane;
            int it = 0;
            bool ok;
            do {
#pragma unroll
                for (int i = 0; i < 4; i++) st[i] = ld_relaxed128(src + 32 * i);
                const uint32_t bad = ((st[0].y ^ tb) | (st[1].y ^ tb) | (st[2].y ^ tb) | (st[3].y ^ tb)) & 0x80008000u;
                ok = __all_sync(0xFFFFFFFFu, bad == 0);
            } while (!ok && ++it < SPIN_LIMIT);
        }
        TSL(11);
        {
            uint32_t h1[4], h2[4];
#pragma unroll
            for (int i = 0; i < 4; i++) {
                const uint32_t o2 = st[i].w ^ (prmt(st[i].w, 0, 0xBB99) | 0x80008000u);
                const uint32_t id = 0xFFFF - 8 * j - 2 * i;
                const uint32_t k0 = prmt(o2, id, 0x1054), k1 = prmt(o2, id - 1, 0x3254);
                h1[i] = max(k0, k1); h2[i] = min(k0, k1);
            }
            const uint32_t a1 = max(h1[0], h1[1]), a2 = __vimax3_u32(min(h1[0], h1[1]), h2[0], h2[1]);
            const uint32_t b1 = max(h1[2], h1[3]), b2 = __vimax3_u32(min(h1[2], h1[3]), h2[2], h2[3]);
            const uint32_t k1 = max(a1, b1), k2 = __vimax3_u32(min(a1, b1), a2, b2);
            const uint32_t m1 = __reduce_max_sync(0xFFFFFFFFu, k1);
            const uint32_t m2 = __reduce_max_sync(0xFFFFFFFFu, k1 == m1 ? k2 : k1);
            if (lane < 3) sts32(sm + SM_KEYS + (lane == 2 ? 64 : v * 8 + lane * 4), lane == 0 ? m1 : lane == 1 ? m2 : tag);
            bar_arrive(3, 320);
        }
        {
            const uint32_t a = sm + SM_U + (j & 1) * U_HI + ((j >> 1) + 8) * 16;
#pragma unroll
            for (int i = 0; i < 4; i++) st[i].y &= 0x7FFF7FFFu;
#pragma unroll
            for (int cc = 0; cc < 8; cc++) {
                uint32_t o[4];
#pragma unroll
                for (int i = 0; i < 4; i++) { const uint32_t n = norm2(xt[cc][i], st[i].x, st[i].y, st[i].z); o[i] = pack_h(blo(n), bhi(n)); }
                sts128(a + cc * U_SZ, o[0], o[1], o[2], o[3]);
            }
        }
        bar_arrive(2, 512);
        TSL(12);
        if (warp < 12) {
            asm volatile("setmaxnreg.dec.sync.aligned.u32 64;");
            if (G < 56) {
                mbar_wait(bars + B_TOK * 8, 0);
                TSL(13);
                const uint32_t lrow = (lane & 7) + 8 * (lane >> 4);
                const uint32_t la = sm + SM_RING + lrow * 128 + (((2 * v + ((lane >> 3) & 1)) ^ (lane & 7)) * 16);
                const uint32_t xs = sm + SM_XSEL + (g & 1) * XSEL_T + rank * 1024 + q * 16;
                float ag[2][4] = {{0, 0, 0, 0}, {0, 0, 0, 0}}, au[2][4] = {{0, 0, 0, 0}, {0, 0, 0, 0}};
                int slot = 0, ph = 0;
#pragma unroll 1
                for (int n = 0; n < 16; n++) {
                    const uint4 xb = lds128(xs + n * 64);
                    mbar_wait(bars + (B_FULL + slot) * 8, ph);
                    uint32_t a[4][4];
#pragma unroll
                    for (int i = 0; i < 4; i++) ldsm4t(la + slot * 8192 + i * 2048, a[i][0], a[i][1], a[i][2], a[i][3]);
                    mma_bf16(ag[0], a[0][0], a[0][1], a[0][2], a[0][3], xb.x, xb.y);
                    mma_bf16(ag[1], a[1][0], a[1][1], a[1][2], a[1][3], xb.z, xb.w);
                    mma_bf16(au[0], a[2][0], a[2][1], a[2][2], a[2][3], xb.x, xb.y);
                    mma_bf16(au[1], a[3][0], a[3][1], a[3][2], a[3][3], xb.z, xb.w);
                    __syncwarp();
                    if (lane == 0) mbar_arrive(bars + (B_EMPTY + slot) * 8);
                    if (++slot == NSLOT) { slot = 0; ph ^= 1; }
                }
                TSL(14);
                float gs = q == 0 ? ag[0][0] + ag[1][0] : q == 1 ? ag[0][1] + ag[1][1] : q == 2 ? ag[0][2] + ag[1][2] : ag[0][3] + ag[1][3];
                float us = q == 0 ? au[0][0] + au[1][0] : q == 1 ? au[0][1] + au[1][1] : q == 2 ? au[0][2] + au[1][2] : au[0][3] + au[1][3];
                const uint32_t rem = mapa(sm, rank ^ 1);
                st_async2(rem + SM_PAIR + v * 256 + lane * 8, __float_as_uint(gs), __float_as_uint(us), rem + SM_BAR + (B_PAIR + v) * 8);
                mbar_wait(bars + (B_PAIR + v) * 8, 0);
                const uint2 oth = lds64(sm + SM_PAIR + v * 256 + lane * 8);
                gs = rb(gs + __uint_as_float(oth.x)); us = rb(us + __uint_as_float(oth.y));
                const float hv = rb(siluf_(gs)) * us;
                sts16(sm + SM_H + (q & 1) * H_T + (v >> 1) * 64 + (g >> 1) * 16 + (2 * (v & 1) + (q >> 1)) * 4 + (g & 1) * 2, pack_b(hv, hv));
                bar_sync(4, 128);
                const uint4 h0 = lds128(sm + SM_H + (g & 1) * H_T + q * 16), h1 = lds128(sm + SM_H + (g & 1) * H_T + 64 + q * 16);
                TSL(15);
#pragma unroll 1
                for (int n = 0; n < 8; n++) {
                    mbar_wait(bars + (B_FULL + slot) * 8, ph);
                    uint32_t a[4][4];
#pragma unroll
                    for (int i = 0; i < 4; i++) ldsm4t(la + slot * 8192 + i * 2048, a[i][0], a[i][1], a[i][2], a[i][3]);
                    float d0[4] = {0, 0, 0, 0}, d1[4] = {0, 0, 0, 0};
                    mma_bf16(d0, a[0][0], a[0][1], a[0][2], a[0][3], h0.x, h0.y);
                    mma_bf16(d1, a[1][0], a[1][1], a[1][2], a[1][3], h0.z, h0.w);
                    mma_bf16(d0, a[2][0], a[2][1], a[2][2], a[2][3], h1.x, h1.y);
                    mma_bf16(d1, a[3][0], a[3][1], a[3][2], a[3][3], h1.z, h1.w);
                    __syncwarp();
                    if (lane == 0) mbar_arrive(bars + (B_EMPTY + slot) * 8);
                    const float o = q == 0 ? d0[0] + d1[0] : q == 1 ? d0[1] + d1[1] : q == 2 ? d0[2] + d1[2] : d0[3] + d1[3];
                    st_relaxed32(my_part + n * 8 * 56 * 16, (__float_as_uint(o) & ~3u) | tag);
                    if (++slot == NSLOT) { slot = 0; ph ^= 1; }
                }
                TSL(16);
            }
        } else {
            asm volatile("setmaxnreg.dec.sync.aligned.u32 40;");
            const int sw = warp - 12;
            mbar_wait(bars + B_TOK * 8, 0);
            const int t0 = 0xFFFF - (lds32(sm + SM_TOK) & 0xFFFF), t1 = 0xFFFF - (lds32(sm + SM_TOK + 4) & 0xFFFF);
            uint32_t la[2];
            {
                const int chl = 8 * ((lane >> 1) & 1) + 2 * (lane >> 3) + (lane & 1);
                const int gam = 4 * sw + 2 * ((lane >> 2) & 1), sz = (chl & 1) + 4 * (chl >> 3);
                la[0] = sm + SM_WB + chl * 256 + ((gam ^ sz) * 16);
                la[1] = sm + SM_WB + chl * 256 + (((gam + 1) ^ sz) * 16);
            }
            const int tl = 128 * rank + 32 * sw + 16 * (q >> 1) + 2 * (g >> 2) + 8 * ((g >> 1) & 1) + (g & 1);
            const uint32_t xa0 = sm + SM_SLAB + (tl & 7) * 8192 + (tl >> 3) * 32 + (((q & 1) ^ (sw & 1)) * 16);
            __nv_bfloat16* const op = p.out + (size_t)tl * 1024 + G * 16 + (q & 1) * 8;
#pragma unroll 1
            for (int s = 0; s < 8; s++) {
                const uint4 x0 = lds128(xa0 + s * 1024), x1 = lds128(xa0 + s * 1024 + 4 * 8192);
                mbar_wait(bars + (B_STG + s) * 8, 0);
                uint32_t a[4], b[4];
                ldsm4t(la[0] + s * WB_SZ, a[0], a[1], a[2], a[3]);
                ldsm4t(la[1] + s * WB_SZ, b[0], b[1], b[2], b[3]);
                const int t = tl + 256 * s;
                if (t != t0 && t != t1)
                    *reinterpret_cast<uint4*>(op + (size_t)s * 256 * 1024) = make_uint4(badd2(x0.x, a[0]), badd2(x0.y, a[1]), badd2(x0.z, a[2]), badd2(x0.w, a[3]));
                if (t + 4 != t0 && t + 4 != t1)
                    *reinterpret_cast<uint4*>(op + (size_t)(s * 256 + 4) * 1024) = make_uint4(badd2(x1.x, b[0]), badd2(x1.y, b[1]), badd2(x1.z, b[2]), badd2(x1.w, b[3]));
            }
            TSL(17);
        }
    } else {
        if (warp == 16 && lane == 0) {
            mbar_init(bars + B_SLAB * 8, 1);
            for (int i = 0; i < NSLOT; i++) { mbar_init(bars + (B_FULL + i) * 8, 1); mbar_init(bars + (B_EMPTY + i) * 8, 4); }
            mbar_init(bars + B_KDONE * 8, 16);
            for (int i = 0; i < 8; i++) mbar_init(bars + (B_STG + i) * 8, 1);
            mbar_init(bars + B_FIX * 8, 1);
            for (int i = 0; i < 4; i++) mbar_init(bars + (B_PAIR + i) * 8, 1);
            mbar_init(bars + B_TOK * 8, 2);
            asm volatile("fence.mbarrier_init.release.cluster;" ::: "memory");
        } else if (warp == 17 && lane < 4) {
            const CUtensorMap* tm = lane == 0 ? &tm_x : lane == 1 ? &tm_g : lane == 2 ? &tm_u : &tm_d;
            asm volatile("prefetch.tensormap [%0];" :: "l"(tm) : "memory");
        }
        __syncwarp();
        cluster_arrive();
        asm volatile("setmaxnreg.dec.sync.aligned.u32 40;");
        cluster_wait();
        if (warp == 16) {
            if (lane == 0) {
                mbar_expect(bars + B_SLAB * 8, 65536);
                for (int i = 4 * rank; i < 4 * rank + 4; i++)
                    asm volatile("cp.async.bulk.tensor.3d.shared::cluster.global.mbarrier::complete_tx::bytes.multicast::cluster"
                                 " [%0], [%1, {%3, %4, %5}], [%2], %6;"
                                 :: "r"(sm + SM_SLAB + i * 8192), "l"(&tm_x), "r"(bars + B_SLAB * 8), "r"(G * 16), "r"(i), "r"(0), "h"((uint16_t)3) : "memory");
                for (int i = 0; i < 8; i++) mbar_expect(bars + (B_STG + i) * 8, 4096);
                mbar_expect(bars + B_FIX * 8, 64);
                if (G < 56) {
                    for (int i = 0; i < 4; i++) mbar_expect(bars + (B_PAIR + i) * 8, 256);
                    uint64_t pol; asm volatile("createpolicy.fractional.L2::evict_first.b64 %0, 1.0;" : "=l"(pol));
                    TS(20);
#pragma unroll 1
                    for (int n = 0; n < 24; n++) {
                        const int slot = n % NSLOT;
                        if (n >= DEPTH) mbar_wait(bars + (B_FULL + (n - DEPTH) % NSLOT) * 8, ((n - DEPTH) / NSLOT) & 1);
                        if (n >= NSLOT) mbar_wait(bars + (B_EMPTY + slot) * 8, (n / NSLOT - 1) & 1);
                        const uint32_t fb = bars + (B_FULL + slot) * 8, dst = sm + SM_RING + slot * 8192;
                        mbar_expect(fb, 8192);
                        if (n < 16) {
                            tma2d(dst, &tm_g, G * 64, rank * 512 + n * 32, fb, pol);
                            tma2d(dst + 4096, &tm_u, G * 64, rank * 512 + n * 32, fb, pol);
                        } else {
                            tma2d(dst, &tm_d, rank * 512 + (n - 16) * 64, G * 64, fb, pol);
                        }
                    }
                    TS(23);
                }
            }
        } else if (warp >= 18) {
            const int k = warp - 18;
            bar_sync(3, 320);
            const uint32_t key = lane < 16 ? lds32(sm + SM_KEYS + lane * 4) : 0u;
            const uint32_t m1 = __reduce_max_sync(0xFFFFFFFFu, key);
            const uint32_t m2 = __reduce_max_sync(0xFFFFFFFFu, key == m1 ? 0u : key);
            const uint32_t mk = k ? m2 : m1;
            const int t = (0xFFFF - (mk & 0xFFFF)) & 2047;
            const uint4* row = reinterpret_cast<const uint4*>(p.x + (size_t)t * 1024) + lane;
            uint4 xr[4];
#pragma unroll
            for (int i = 0; i < 4; i++) xr[i] = ldg128(row + 32 * i);
            const uint4 st = ld_relaxed128(g_stats + (t >> 8) * 128 + ((t >> 1) & 3) * 32 + ((t >> 3) & 31));
            if (lane == 0) {
                sts32(sm + SM_TOK + 4 * k, (mk & 0xFFFF0000u) | (0xFFFF - t));
                if (c == 0 && k == 0) st_relaxed32(&g_epoch, lds32(sm + SM_KEYS + 64));
            }
            const uint32_t se = (t & 1) ? 0x3232 : 0x1010;
            const uint32_t m = prmt(st.x, 0, se), hi = prmt(st.y, 0, se) & 0x7FFF7FFFu, lo = prmt(st.z, 0, se);
            const uint32_t a = sm + SM_XSEL + k * XSEL_T + (lane >> 2) * 64 + (lane & 3) * 4;
#pragma unroll
            for (int i = 0; i < 4; i++) {
                sts32(a + i * 512, norm2(xr[i].x, m, hi, lo)); sts32(a + i * 512 + 16, norm2(xr[i].y, m, hi, lo));
                sts32(a + i * 512 + 32, norm2(xr[i].z, m, hi, lo)); sts32(a + i * 512 + 48, norm2(xr[i].w, m, hi, lo));
            }
            __syncwarp();
            if (lane == 0) mbar_arrive(bars + B_TOK * 8);
        } else {
            mbar_wait(bars + B_TOK * 8, 0);
            const uint32_t tag = lds32(sm + SM_KEYS + 64), key = lds32(sm + SM_TOK + 4 * rank);
            const int t = 0xFFFF - (key & 0xFFFF);
            const int col = 4 * q + 2 * (lane >> 4) + ((lane >> 3) & 1), d = G * 16 + col;
            const float r = __uint_as_float((key & 0x80000000u) ? (key & 0x7FFF0000u) : (~key & 0xFFFF0000u));
            const float sg = rb(sigmoidf_(r));
            const float xn = blo(lds16(sm + SM_XSEL + rank * XSEL_T + (d >> 5) * 64 + ((d >> 1) & 3) * 16 + ((d >> 3) & 3) * 4 + (d & 1) * 2));
            mbar_wait(bars + B_SLAB * 8, 0);
            const float xv = blo(lds16(sm + SM_SLAB + (t & 7) * 8192 + (t >> 3) * 32 + (((col >> 3) ^ ((t >> 5) & 1)) * 16) + (col & 7) * 2));
            mbar_wait(bars + B_FIX * 8, 0);
            const float s = blo(lds32(sm + SM_FIX + col * 4));
            if (G < 56) mbar_wait(bars + (B_PAIR + 0) * 8, 0);
            TSL(24);
            const uint4* src = reinterpret_cast<const uint4*>(g_part) + c * 224 + lane;
            float s0 = 0, s1 = 0, s2 = 0, s3 = 0;
            {
                uint4 pv[7];
                int it = 0;
                bool ok;
                do {
                    uint32_t bad = 0;
#pragma unroll
                    for (int i = 0; i < 7; i++) pv[i] = ld_relaxed128(src + 32 * i);
#pragma unroll
                    for (int i = 0; i < 7; i++) bad |= (pv[i].x ^ tag) | (pv[i].y ^ tag) | (pv[i].z ^ tag) | (pv[i].w ^ tag);
                    ok = __all_sync(0xFFFFFFFFu, (bad & 3) == 0);
                } while (!ok && ++it < SPIN_LIMIT);
#pragma unroll
                for (int i = 0; i < 7; i++) {
                    s0 += __uint_as_float(pv[i].x); s1 += __uint_as_float(pv[i].y); s2 += __uint_as_float(pv[i].z); s3 += __uint_as_float(pv[i].w);
                }
            }
            TSL(25);
            const bool u16 = lane & 16, u8 = lane & 8;
            const float y0 = (u16 ? s2 : s0) + __shfl_xor_sync(0xFFFFFFFFu, u16 ? s0 : s2, 16);
            const float y1 = (u16 ? s3 : s1) + __shfl_xor_sync(0xFFFFFFFFu, u16 ? s1 : s3, 16);
            float y = (u8 ? y1 : y0) + __shfl_xor_sync(0xFFFFFFFFu, u8 ? y0 : y1, 8);
            y += __shfl_xor_sync(0xFFFFFFFFu, y, 4);
            const float z = rb(xn + rb(rb(y) * sg));
            const float o = xv + rb(s * rb(siluf_(z)));
            if (!(lane & 4)) p.out[(size_t)t * 1024 + d] = __float2bfloat16(o);
            TSL(26);
        }
    }
}

typedef CUresult (*EncodeFn)(CUtensorMap*, CUtensorMapDataType, cuuint32_t, void*, const cuuint64_t*, const cuuint64_t*,
                             const cuuint32_t*, const cuuint32_t*, CUtensorMapInterleave, CUtensorMapSwizzle,
                             CUtensorMapL2promotion, CUtensorMapFloatOOBfill);

}

extern "C" void kernel_launch(void* const* d_in, const int* in_sizes, int n_in, void* d_out, int out_size) {
    Params p;
    p.x = (const __nv_bfloat16*)d_in[0];
    p.lar = (const __nv_bfloat16*)d_in[1];
    p.aim = (const __nv_bfloat16*)d_in[2];
    p.cr = (const __nv_bfloat16*)d_in[3];
    p.ci = (const __nv_bfloat16*)d_in[4];
    p.logdt = (const __nv_bfloat16*)d_in[5];
    p.dskip = (const __nv_bfloat16*)d_in[6];
    p.wr = (const __nv_bfloat16*)d_in[8];
    p.out = (__nv_bfloat16*)d_out;

    void* fn = nullptr;
    cudaDriverEntryPointQueryResult qr;
    cudaGetDriverEntryPoint("cuTensorMapEncodeTiled", &fn, cudaEnableDefault, &qr);
    EncodeFn enc = (EncodeFn)fn;
    CUtensorMap tm_x, tm_g, tm_u, tm_d;
    const cuuint32_t es[3] = {1, 1, 1};
    {
        const cuuint64_t gd[3] = {1024, 8, 256}, gs[2] = {2048, 16384};
        const cuuint32_t bx[3] = {16, 1, 256};
        enc(&tm_x, CU_TENSOR_MAP_DATA_TYPE_BFLOAT16, 3, d_in[0], gd, gs, bx, es, CU_TENSOR_MAP_INTERLEAVE_NONE,
            CU_TENSOR_MAP_SWIZZLE_32B, CU_TENSOR_MAP_L2_PROMOTION_NONE, CU_TENSOR_MAP_FLOAT_OOB_FILL_NONE);
    }
    {
        const cuuint64_t gd[2] = {3584, 1024}, gs[1] = {7168};
        const cuuint32_t bx[2] = {64, 32};
        enc(&tm_g, CU_TENSOR_MAP_DATA_TYPE_BFLOAT16, 2, d_in[9], gd, gs, bx, es, CU_TENSOR_MAP_INTERLEAVE_NONE,
            CU_TENSOR_MAP_SWIZZLE_128B, CU_TENSOR_MAP_L2_PROMOTION_NONE, CU_TENSOR_MAP_FLOAT_OOB_FILL_NONE);
        enc(&tm_u, CU_TENSOR_MAP_DATA_TYPE_BFLOAT16, 2, d_in[10], gd, gs, bx, es, CU_TENSOR_MAP_INTERLEAVE_NONE,
            CU_TENSOR_MAP_SWIZZLE_128B, CU_TENSOR_MAP_L2_PROMOTION_NONE, CU_TENSOR_MAP_FLOAT_OOB_FILL_NONE);
    }
    {
        const cuuint64_t gd[2] = {1024, 3584}, gs[1] = {2048};
        const cuuint32_t bx[2] = {64, 64};
        enc(&tm_d, CU_TENSOR_MAP_DATA_TYPE_BFLOAT16, 2, d_in[11], gd, gs, bx, es, CU_TENSOR_MAP_INTERLEAVE_NONE,
            CU_TENSOR_MAP_SWIZZLE_128B, CU_TENSOR_MAP_L2_PROMOTION_NONE, CU_TENSOR_MAP_FLOAT_OOB_FILL_NONE);
    }
    cudaFuncSetAttribute(fused_kernel, cudaFuncAttributeMaxDynamicSharedMemorySize, SM_TOTAL);
    fused_kernel<<<128, NTHREADS, SM_TOTAL>>>(p, tm_x, tm_g, tm_u, tm_d);
}
```

```cpp
#include <cuda_runtime.h>
#include <cuda.h>
#include <cuda_bf16.h>
#include <cuda_fp16.h>
#include <stdint.h>

#define TG(i)
#define TS(i)
#define TSL(i)

#define EPI_R 4
#define QPF 4
#define FENCE_EVERY 4
#define TSW 0
#define NSLOT 7
#define DEPTH 4

namespace {

constexpr int NTHREADS = 512;
constexpr int SPIN_LIMIT = 1 << 16;

constexpr int SM_SLAB = 0;
constexpr int SM_RING = 65536;
constexpr int SM_WB   = SM_RING + NSLOT * 8192;
constexpr int WB_SZ   = 8448;
constexpr int SM_U    = SM_WB + 8 * WB_SZ;
constexpr int U_HI    = 2240;
constexpr int U_SZ    = 4416;
constexpr int SM_XSEL = SM_U + 8 * U_SZ;
constexpr int XSEL_T  = 2112;
constexpr int SM_PAIR = SM_XSEL + 2 * XSEL_T;
constexpr int SM_H    = SM_PAIR + 1024;
constexpr int H_T     = 192;
constexpr int SM_KEYS = SM_H + 2 * H_T;
constexpr int SM_TOK  = SM_KEYS + 128;
constexpr int SM_FIX  = SM_TOK + 16;
constexpr int SM_SCL  = SM_FIX + 64;
constexpr int SM_BAR  = SM_SCL + 64;
constexpr int B_FULL = 0, B_EMPTY = 8, B_STG = 16, B_MISC = 24, NBAR = 32;
constexpr int B_KDONE = B_MISC, B_TOK = B_MISC + 1, B_FIX = B_MISC + 2, B_PAIR = B_MISC + 3, B_SLAB = B_MISC + 4;
constexpr int SM_TOTAL = SM_BAR + NBAR * 8;
static_assert(SM_TOTAL <= 232448 && NSLOT < 8, "smem");
__host__ __device__ constexpr int full_bar(int n) { return B_FULL + (n == 23 ? 7 : n % NSLOT); }
__host__ __device__ constexpr int full_par(int n) { return n == 23 ? 0 : (n / NSLOT) & 1; }
constexpr int KP = 272;
constexpr int KA_DE = 4;
constexpr int KA_DO = 276;
constexpr int KA_O2 = 544;
constexpr int KA_E2 = 640;
constexpr int KA_O3 = 736;
constexpr int KA_E3 = 816;

struct Params {
    const __nv_bfloat16 *x, *lar, *aim, *cr, *ci, *logdt, *dskip, *wr;
    __nv_bfloat16* out;
    uint4* stats;
    uint32_t *part, *epoch;
    int up_first;
};

__device__ uint4 g_stats[1024];
__device__ uint32_t g_part[128 * 56 * 16];
__device__ uint32_t g_epoch;

__device__ __forceinline__ uint4 ldg128(const void* p) {
    uint4 v; asm volatile("ld.global.nc.v4.u32 {%0,%1,%2,%3}, [%4];" : "=r"(v.x), "=r"(v.y), "=r"(v.z), "=r"(v.w) : "l"(p)); return v;
}
__device__ __forceinline__ uint4 ld_relaxed128(const void* p) {
    uint4 v;
    asm volatile("{ .reg .b128 t; ld.relaxed.gpu.global.b128 t, [%4]; mov.b128 {%0,%1,%2,%3}, t; }"
                 : "=r"(v.x), "=r"(v.y), "=r"(v.z), "=r"(v.w) : "l"(p) : "memory");
    return v;
}
__device__ __forceinline__ void st_relaxed128(void* p, uint4 v) {
    asm volatile("{ .reg .b128 t; mov.b128 t, {%1,%2,%3,%4}; st.relaxed.gpu.global.b128 [%0], t; }"
                 :: "l"(p), "r"(v.x), "r"(v.y), "r"(v.z), "r"(v.w) : "memory");
}
__device__ __forceinline__ void st_relaxed32(void* p, uint32_t v) {
    asm volatile("st.relaxed.gpu.global.u32 [%0], %1;" :: "l"(p), "r"(v) : "memory");
}
__device__ __forceinline__ uint32_t lds32(uint32_t a) { uint32_t v; asm volatile("ld.shared.u32 %0, [%1];" : "=r"(v) : "r"(a)); return v; }
__device__ __forceinline__ uint32_t lds16(uint32_t a) { uint32_t v; asm volatile("ld.shared.u16 %0, [%1];" : "=r"(v) : "r"(a)); return v; }
__device__ __forceinline__ uint2 lds64(uint32_t a) { uint2 v; asm volatile("ld.shared.v2.u32 {%0,%1}, [%2];" : "=r"(v.x), "=r"(v.y) : "r"(a)); return v; }
__device__ __forceinline__ uint4 lds128(uint32_t a) {
    uint4 v; asm volatile("ld.shared.v4.u32 {%0,%1,%2,%3}, [%4];" : "=r"(v.x), "=r"(v.y), "=r"(v.z), "=r"(v.w) : "r"(a)); return v;
}
__device__ __forceinline__ void sts16(uint32_t a, uint32_t v) { asm volatile("st.shared.u16 [%0], %1;" :: "r"(a), "h"((uint16_t)v) : "memory"); }
__device__ __forceinline__ void sts32(uint32_t a, uint32_t v) { asm volatile("st.shared.u32 [%0], %1;" :: "r"(a), "r"(v) : "memory"); }
__device__ __forceinline__ void sts64(uint32_t a, uint32_t x, uint32_t y) { asm volatile("st.shared.v2.u32 [%0], {%1,%2};" :: "r"(a), "r"(x), "r"(y) : "memory"); }
__device__ __forceinline__ void sts128(uint32_t a, uint32_t x, uint32_t y, uint32_t z, uint32_t w) {
    asm volatile("st.shared.v4.u32 [%0], {%1,%2,%3,%4};" :: "r"(a), "r"(x), "r"(y), "r"(z), "r"(w) : "memory");
}
__device__ __forceinline__ void ldsm4(uint32_t a, uint32_t& r0, uint32_t& r1, uint32_t& r2, uint32_t& r3) {
    asm volatile("ldmatrix.sync.aligned.m8n8.x4.shared.b16 {%0,%1,%2,%3}, [%4];" : "=r"(r0), "=r"(r1), "=r"(r2), "=r"(r3) : "r"(a));
}
__device__ __forceinline__ void ldsm4t(uint32_t a, uint32_t& r0, uint32_t& r1, uint32_t& r2, uint32_t& r3) {
    asm volatile("ldmatrix.sync.aligned.m8n8.x4.trans.shared.b16 {%0,%1,%2,%3}, [%4];" : "=r"(r0), "=r"(r1), "=r"(r2), "=r"(r3) : "r"(a));
}
__device__ __forceinline__ void mma_f16(float (&d)[4], uint32_t a0, uint32_t a1, uint32_t a2, uint32_t a3, uint32_t b0, uint32_t b1) {
    asm("mma.sync.aligned.m16n8k16.row.col.f32.f16.f16.f32 {%0,%1,%2,%3}, {%4,%5,%6,%7}, {%8,%9}, {%0,%1,%2,%3};"
        : "+f"(d[0]), "+f"(d[1]), "+f"(d[2]), "+f"(d[3]) : "r"(a0), "r"(a1), "r"(a2), "r"(a3), "r"(b0), "r"(b1));
}
__device__ __forceinline__ void mma_bf16(float (&d)[4], uint32_t a0, uint32_t a1, uint32_t a2, uint32_t a3, uint32_t b0, uint32_t b1) {
    asm("mma.sync.aligned.m16n8k16.row.col.f32.bf16.bf16.f32 {%0,%1,%2,%3}, {%4,%5,%6,%7}, {%8,%9}, {%0,%1,%2,%3};"
        : "+f"(d[0]), "+f"(d[1]), "+f"(d[2]), "+f"(d[3]) : "r"(a0), "r"(a1), "r"(a2), "r"(a3), "r"(b0), "r"(b1));
}
__device__ __forceinline__ void mma_h(uint32_t& d0, uint32_t& d1, const uint32_t (&a)[4], uint32_t b0, uint32_t b1) {
    asm("mma.sync.aligned.m16n8k16.row.col.f16.f16.f16.f16 {%0,%1}, {%2,%3,%4,%5}, {%6,%7}, {%8,%8};"
        : "=r"(d0), "=r"(d1) : "r"(a[0]), "r"(a[1]), "r"(a[2]), "r"(a[3]), "r"(b0), "r"(b1), "r"(0u));
}
__device__ __forceinline__ uint32_t prmt(uint32_t a, uint32_t b, uint32_t s) { uint32_t d; asm("prmt.b32 %0, %1, %2, %3;" : "=r"(d) : "r"(a), "r"(b), "r"(s)); return d; }
__device__ __forceinline__ uint32_t pack_h(float lo, float hi) { uint32_t d; asm("cvt.rn.f16x2.f32 %0, %1, %2;" : "=r"(d) : "f"(hi), "f"(lo)); return d; }
__device__ __forceinline__ uint32_t pack_b(float lo, float hi) { uint32_t d; asm("cvt.rn.bf16x2.f32 %0, %1, %2;" : "=r"(d) : "f"(hi), "f"(lo)); return d; }
__device__ __forceinline__ float blo(uint32_t v) { return __uint_as_float(v << 16); }
__device__ __forceinline__ float bhi(uint32_t v) { return __uint_as_float(v & 0xFFFF0000u); }
__device__ __forceinline__ float rb(float v) { return blo(pack_b(v, v)); }
__device__ __forceinline__ uint32_t bsub2(uint32_t a, uint32_t b) { uint32_t d; asm("sub.rn.bf16x2 %0, %1, %2;" : "=r"(d) : "r"(a), "r"(b)); return d; }
__device__ __forceinline__ uint32_t bmul2(uint32_t a, uint32_t b) { uint32_t d; asm("mul.rn.bf16x2 %0, %1, %2;" : "=r"(d) : "r"(a), "r"(b)); return d; }
__device__ __forceinline__ uint32_t bfma2(uint32_t a, uint32_t b, uint32_t c) { uint32_t d; asm("fma.rn.bf16x2 %0, %1, %2, %3;" : "=r"(d) : "r"(a), "r"(b), "r"(c)); return d; }
__device__ __forceinline__ uint32_t norm2(uint32_t x, uint32_t m, uint32_t hi, uint32_t lo) {
    uint32_t a = bsub2(x, m);
    return bfma2(a, hi, bmul2(a, lo));
}
__device__ __forceinline__ float ex2(float v) { float d; asm("ex2.approx.ftz.f32 %0, %1;" : "=f"(d) : "f"(v)); return d; }
__device__ __forceinline__ float rcp(float v) { float d; asm("rcp.approx.ftz.f32 %0, %1;" : "=f"(d) : "f"(v)); return d; }
__device__ __forceinline__ float sigmoidf_(float v) { return rcp(1.0f + ex2(-1.4426950408889634f * v)); }
__device__ __forceinline__ float siluf_(float v) { return v * sigmoidf_(v); }

__device__ __forceinline__ void mbar_init(uint32_t a, int n) { asm volatile("mbarrier.init.shared::cta.b64 [%0], %1;" :: "r"(a), "r"(n) : "memory"); }
__device__ __forceinline__ void mbar_expect(uint32_t a, int tx) { asm volatile("mbarrier.arrive.expect_tx.shared::cta.b64 _, [%0], %1;" :: "r"(a), "r"(tx) : "memory"); }
__device__ __forceinline__ void mbar_arrive(uint32_t a) { asm volatile("mbarrier.arrive.shared::cta.b64 _, [%0];" :: "r"(a) : "memory"); }
__device__ __forceinline__ void mbar_wait(uint32_t a, int parity) {
    asm volatile("{ .reg .pred p;\n"
                 "W: mbarrier.try_wait.parity.shared::cta.b64 p, [%0], %1;\n"
                 "@!p bra.uni W; }" :: "r"(a), "r"(parity) : "memory");
}
__device__ __forceinline__ uint32_t mapa(uint32_t a, uint32_t rank) { uint32_t d; asm("mapa.shared::cluster.u32 %0, %1, %2;" : "=r"(d) : "r"(a), "r"(rank)); return d; }
__device__ __forceinline__ void st_async2(uint32_t a, uint32_t x, uint32_t y, uint32_t bar) {
    asm volatile("st.async.weak.shared::cluster.mbarrier::complete_tx::bytes.v2.b32 [%0], {%1,%2}, [%3];" :: "r"(a), "r"(x), "r"(y), "r"(bar) : "memory");
}
__device__ __forceinline__ void st_async1(uint32_t a, uint32_t x, uint32_t bar) {
    asm volatile("st.async.weak.shared::cluster.mbarrier::complete_tx::bytes.b32 [%0], %1, [%2];" :: "r"(a), "r"(x), "r"(bar) : "memory");
}
__device__ __forceinline__ void bar_sync(int id, int n) { asm volatile("bar.sync %0, %1;" :: "r"(id), "r"(n) : "memory"); }
__device__ __forceinline__ void bar_arrive(int id, int n) { asm volatile("bar.arrive %0, %1;" :: "r"(id), "r"(n) : "memory"); }
__device__ __forceinline__ void cluster_arrive() { asm volatile("barrier.cluster.arrive.relaxed.aligned;" ::: "memory"); }
__device__ __forceinline__ void cluster_wait() { asm volatile("barrier.cluster.wait.aligned;" ::: "memory"); }
__device__ __forceinline__ void tma3d(uint32_t dst, const CUtensorMap* tm, int c0, int c1, uint32_t bar, uint64_t pol) {
    asm volatile("cp.async.bulk.tensor.3d.shared::cluster.global.mbarrier::complete_tx::bytes.L2::cache_hint [%0], [%1, {%3, %4, %6}], [%2], %5;"
                 :: "r"(dst), "l"(tm), "r"(bar), "r"(c0), "r"(c1), "l"(pol), "r"(0) : "memory");
}
__device__ __forceinline__ bool elect() {
    uint32_t p; asm volatile("{ .reg .pred p; elect.sync _|p, 0xFFFFFFFF; selp.u32 %0, 1, 0, p; }" : "=r"(p)); return p;
}

struct cf { float r, i; };
__device__ __forceinline__ cf cmul(cf a, cf b) { return {a.r * b.r - a.i * b.i, a.r * b.i + a.i * b.r}; }
__device__ __forceinline__ cf csq(cf a) { return {a.r * a.r - a.i * a.i, (a.r + a.r) * a.i}; }
__device__ __forceinline__ cf cexp_(float a2, float b) { float m = ex2(a2); return {m * __cosf(b), m * __sinf(b)}; }
struct hc { uint32_t r, i; };
__device__ __forceinline__ hc pk(cf a, cf b) { return {pack_h(a.r, b.r), pack_h(a.i, b.i)}; }
__device__ __forceinline__ hc hmulc(hc a, hc b) {
    const __half2 ar = *reinterpret_cast<__half2*>(&a.r), ai = *reinterpret_cast<__half2*>(&a.i);
    const __half2 br = *reinterpret_cast<__half2*>(&b.r), bi = *reinterpret_cast<__half2*>(&b.i);
    const __half2 r = __hfma2(ar, br, __hneg2(__hmul2_rn(ai, bi))), i = __hfma2(ar, bi, __hmul2_rn(ai, br));
    return {*reinterpret_cast<const uint32_t*>(&r), *reinterpret_cast<const uint32_t*>(&i)};
}
__device__ __forceinline__ void sth(uint32_t a, hc v) { sts32(a, v.r); sts32(a + 128, v.i); }
__device__ __forceinline__ uint32_t cpy(uint32_t v, uint32_t z) { uint32_t d; asm("xor.b32 %0, %1, %2;" : "=r"(d) : "r"(v), "r"(z)); return d; }
__device__ __forceinline__ void sched_fence() { asm volatile("pmevent 0;" ::: "memory"); }
__device__ __forceinline__ uint32_t pin(uint32_t v) { return __shfl_sync(0xFFFFFFFFu, v, threadIdx.x & 31); }
__device__ __forceinline__ void mma4(float (&d)[4], const uint32_t (&a)[4], uint32_t b0, uint32_t b1) { mma_f16(d, a[0], a[1], a[2], a[3], b0, b1); }
__device__ __forceinline__ float tanh_(float v) { float d; asm("tanh.approx.f32 %0, %1;" : "=f"(d) : "f"(v)); return d; }
__device__ __forceinline__ uint32_t band(int k0, int lo, int hi) {
    return ((k0 >= lo && k0 <= hi) ? 0x3C00u : 0u) | ((k0 + 1 >= lo && k0 + 1 <= hi) ? 0x3C000000u : 0u);
}

__global__ void __cluster_dims__(2, 1, 1) __launch_bounds__(NTHREADS, 1)
fused_kernel(const Params p, const __grid_constant__ CUtensorMap tm_x, const __grid_constant__ CUtensorMap tm_g,
             const __grid_constant__ CUtensorMap tm_d)
{
    extern __shared__ __align__(1024) uint8_t smem_raw[];
    const uint32_t sm = (uint32_t)__cvta_generic_to_shared(smem_raw);
    const uint32_t bars = sm + SM_BAR;
    const int tid = threadIdx.x, warp = __shfl_sync(0xFFFFFFFFu, tid >> 5, 0), lane = tid & 31;
    const int g = lane >> 2, q = lane & 3;
    const int c = blockIdx.x, rank = c & 1, G = c >> 1;

    if (lane == 0 && warp >= 8) {
        const int v = warp - 8;
        mbar_init(bars + (B_STG + v) * 8, 1);
        mbar_init(bars + (B_EMPTY + v) * 8, 4);
        mbar_init(bars + (B_FULL + v) * 8, 1);
        mbar_init(bars + (B_MISC + v) * 8, v == 1 ? 2 : 1);
        mbar_expect(bars + (B_STG + v) * 8, 4096);
        if (v < DEPTH) mbar_expect(bars + (B_FULL + v) * 8, 8192);
        if (v != 1) mbar_expect(bars + (B_MISC + v) * 8, v <= 2 ? 64 : v == 3 ? 1024 : 65536);
        asm volatile("fence.mbarrier_init.release.cluster;" ::: "memory");
    }
    __syncwarp();
    cluster_arrive();

    if (warp < 8) {
        TSL(32);
        const int ch = c * 8 + warp;
        const uint2 lar4 = __ldg(reinterpret_cast<const uint2*>(p.lar + ch * 128) + lane);
        const uint2 aim4 = __ldg(reinterpret_cast<const uint2*>(p.aim + ch * 128) + lane);
        const uint2 cr4 = __ldg(reinterpret_cast<const uint2*>(p.cr + ch * 128) + lane);
        const uint2 ci4 = __ldg(reinterpret_cast<const uint2*>(p.ci + ch * 128) + lane);
        uint32_t ldt_raw, dsk_raw;
        asm volatile("ld.global.nc.u16 %0, [%1];" : "=r"(ldt_raw) : "l"(p.logdt + ch));
        asm volatile("ld.global.nc.u16 %0, [%1];" : "=r"(dsk_raw) : "l"(p.dskip + ch));
        const float logdt = blo(ldt_raw), dsk = blo(dsk_raw);
        const uint32_t wb = sm + SM_WB + warp * WB_SZ;
        const uint32_t ub = sm + SM_U + warp * U_SZ;
        if (lane < 16) sts128(ub + (lane >> 3) * U_HI + (lane & 7) * 16, 0, 0, 0, 0);
        sth(wb + lane * 4, hc{0x3C003C00u, 0u});

        const float dt = rb(expf(logdt));
        float outscale, cs, dn;
        {
            uint32_t m0 = __vmaxu2(__vmaxu2(cr4.x & 0x7FFF7FFFu, cr4.y & 0x7FFF7FFFu), __vmaxu2(ci4.x & 0x7FFF7FFFu, ci4.y & 0x7FFF7FFFu));
            uint32_t m1 = max(m0 & 0xFFFFu, m0 >> 16);
            float cmax = blo(__reduce_max_sync(0xFFFFFFFFu, m1));
            const float sc = fminf(fmaxf(fmaxf(2.0f * dt * cmax, fabsf(dsk) * (1.0f / 1024.0f)), 1e-30f), 1e30f);
            outscale = __uint_as_float(__float_as_uint(sc) & 0x7F800000u);
            const float inv = __uint_as_float(0x7F000000u - __float_as_uint(outscale));
            cs = 2.0f * dt * inv;
            dn = dsk * inv;
        }
        TSL(0);
        float kacc[2][3][4];
#pragma unroll
        for (int i = 0; i < 2; i++)
#pragma unroll
            for (int j = 0; j < 3; j++) kacc[i][j][0] = kacc[i][j][1] = kacc[i][j][2] = kacc[i][j][3] = 0.f;
        if (lane == 0) kacc[0][0][0] = dn;
        {
            const uint32_t st = wb + lane * 4;
            const uint32_t la = wb + ((lane & 8) ? 29 : (lane & 7)) * KP + (lane >> 4) * 128;
            const uint32_t lo = wb + ((lane >> 3) & 1) * 128 + (lane >> 4) * 16;
            const uint32_t lb = lo + (8 + (lane & 7)) * KP, lb2 = lo + (24 + min(lane & 7, 4)) * KP, lm = lo + 30 * KP;
#pragma unroll 1
            for (int s = 0; s < 2; s++) {
                const uint32_t wl = s ? lar4.y : lar4.x, wa = s ? aim4.y : aim4.x, wr_ = s ? cr4.y : cr4.x, wi = s ? ci4.y : ci4.x;
                const uint32_t ea = pack_b(ex2(blo(wl) * 1.4426950408889634f), ex2(bhi(wl) * 1.4426950408889634f));
                const float a2[2] = {-(blo(ea) * dt) * 1.4426950408889634f, -(bhi(ea) * dt) * 1.4426950408889634f};
                const float b[2] = {blo(wa) * dt, bhi(wa) * dt};
                {
                    cf z8[2], z16[2], z24[2], z32[2], z64[2], z128[2];
#pragma unroll
                    for (int e = 0; e < 2; e++) {
                        z8[e] = cexp_(a2[e] * 8.f, b[e] * 8.f);
                        z16[e] = csq(z8[e]); z24[e] = cmul(z16[e], z8[e]); z32[e] = csq(z16[e]); z64[e] = csq(z32[e]); z128[e] = csq(z64[e]);
                    }
                    const hc r1 = pk(z8[0], z8[1]), r2 = pk(z16[0], z16[1]), r3 = pk(z24[0], z24[1]), r4 = pk(z32[0], z32[1]);
                    sth(st + 1 * KP, r1); sth(st + 2 * KP, r2); sth(st + 3 * KP, r3); sth(st + 4 * KP, r4);
                    sth(st + 5 * KP, hmulc(r1, r4)); sth(st + 6 * KP, hmulc(r2, r4)); sth(st + 7 * KP, hmulc(r3, r4));
                    sth(st + 29 * KP, pk(z64[0], z64[1])); sth(st + 30 * KP, pk(z128[0], z128[1]));
                }
                {
                    cf C[2], z4[2], v[2], v4[2], c1[2], c2[2], c3[2], d1[2], d2[2], d3[2];
#pragma unroll
                    for (int e = 0; e < 2; e++) {
                        C[e] = {(e ? bhi(wr_) : blo(wr_)) * cs, (e ? bhi(wi) : blo(wi)) * -cs};
                        const cf z = cexp_(a2[e], -b[e]);
                        v[e] = cexp_(a2[e] * 256.f, b[e] * -256.f);
                        z4[e] = csq(csq(z)); v4[e] = csq(csq(v[e]));
                        c1[e] = cmul(C[e], z); c2[e] = cmul(c1[e], z); c3[e] = cmul(c2[e], z);
                        d1[e] = cmul(C[e], v[e]); d2[e] = cmul(d1[e], v[e]); d3[e] = cmul(d2[e], v[e]);
                    }
                    const hc l0 = pk(C[0], C[1]), l1 = pk(c1[0], c1[1]), l2 = pk(c2[0], c2[1]), l3 = pk(c3[0], c3[1]);
                    const hc e1 = pk(d1[0], d1[1]), e2 = pk(d2[0], d2[1]), e3 = pk(d3[0], d3[1]);
                    const hc f = pk(z4[0], z4[1]), w = pk(v[0], v[1]), y = pk(v4[0], v4[1]);
                    const hc l6 = hmulc(l2, f), e4 = hmulc(l0, y);
                    sth(st + 8 * KP, l0); sth(st + 9 * KP, l1); sth(st + 10 * KP, l2); sth(st + 11 * KP, l3);
                    sth(st + 12 * KP, hmulc(l0, f)); sth(st + 13 * KP, hmulc(l1, f)); sth(st + 14 * KP, l6); sth(st + 15 * KP, hmulc(l3, f));
                    sth(st + 16 * KP, e1);
                    sth(st + 17 * KP, hmulc(l2, w));
                    sth(st + 18 * KP, hmulc(e1, f));
                    sth(st + 19 * KP, hmulc(l6, w));
                    sth(st + 20 * KP, e2);
                    sth(st + 21 * KP, hmulc(e2, f));
                    sth(st + 22 * KP, e3);
                    sth(st + 23 * KP, hmulc(e3, f));
                    sth(st + 24 * KP, e4);
                    sth(st + 25 * KP, hmulc(e1, y));
                    sth(st + 26 * KP, hmulc(e2, y));
                    sth(st + 27 * KP, hmulc(e3, y));
                    sth(st + 28 * KP, hmulc(e4, y));
                }
                __syncwarp();
                TSL(s ? 34 : 27);
#pragma unroll
                for (int kp = 0; kp < 4; kp++) {
                    uint32_t bb[3][4], m2[4];
                    ldsm4(lm + kp * 32, m2[0], m2[1], m2[2], m2[3]);
                    ldsm4(lb + kp * 32, bb[0][0], bb[0][1], bb[0][2], bb[0][3]);
                    ldsm4(lb + 8 * KP + kp * 32, bb[1][0], bb[1][1], bb[1][2], bb[1][3]);
                    ldsm4(lb2 + kp * 32, bb[2][0], bb[2][1], bb[2][2], bb[2][3]);
#pragma unroll
                    for (int k2 = 0; k2 < 2; k2++) {
                        hc v0, m1;
                        ldsm4(la + kp * 32 + k2 * 16, v0.r, m1.r, v0.i, m1.i);
                        const hc mm = {m2[2 * k2], m2[2 * k2 + 1]};
                        const hc v1 = hmulc(v0, m1), v2 = hmulc(v0, mm), v3 = hmulc(v1, mm);
#pragma unroll
                        for (int nt = 0; nt < 3; nt++) {
                            mma_f16(kacc[0][nt], v0.r, v1.r, v0.i, v1.i, bb[nt][2 * k2], bb[nt][2 * k2 + 1]);
                            mma_f16(kacc[1][nt], v2.r, v3.r, v2.i, v3.i, bb[nt][2 * k2], bb[nt][2 * k2 + 1]);
                        }
                    }
                }
                __syncwarp();
                if (s == 0) TSL(33);
            }
        }
        TSL(1);
        const uint32_t ka = wb + 4096;
        uint32_t xb0, xb1;
        {
            sts128(ka + (lane < 2 ? lane : lane < 7 ? 63 + lane : 126 + lane) * 16, 0, 0, 0, 0);
            sts128(ka + (158 + lane) * 16, 0, 0, 0, 0);
            sts128(ka + (190 + lane) * 16, 0, 0, 0, 0);
            __syncwarp();
            uint32_t v1[4], v2[4];
#pragma unroll
            for (int m = 0; m < 4; m++) {
                v1[m] = pack_h(kacc[m >> 1][1][2 * (m & 1) + 1], kacc[m >> 1][1][2 * (m & 1)]);
                v2[m] = pack_h(kacc[m >> 1][2][2 * (m & 1)], kacc[m >> 1][2][2 * (m & 1) + 1]);
            }
            if (q < 2) {
                const uint32_t a = ka + (128 + 4 * g + 2 * q) * 4;
                const uint32_t a3 = ka + (((g & 1) ? KA_O3 : KA_E3) + 8 + 32 * q + (g >> 1)) * 4;
                const uint32_t a30 = lane == 0 ? ka + (KA_E2 + 77) * 4 : a3;
#pragma unroll
                for (int m = 0; m < 4; m++) {
                    const uint32_t ee = prmt(v1[m], 0, 0x3232);
                    sts64(a + (KA_DE + 32 * m) * 4, ee, v1[m]);
                    sts32(a + (KA_DO + 32 * m) * 4, ee);
                    sts16(a + (KA_DO + 32 * m + 1) * 4 + 2, v1[m]);
                    sts16(a + (KA_DO + 32 * m - 1) * 4, ee);
                    if (m == 0) { sts16(a30, v2[0]); sts16(a30 + (lane == 0 ? 10 : 6), v2[0]); }
                    else { sts16(a3 + m * 16, v2[m]); sts16(a3 + m * 16 + 6, v2[m]); }
                    sts16(a3 + 64 + m * 16, v2[m] >> 16); sts16(a3 + 64 + m * 16 + 6, v2[m] >> 16);
                }
            } else {
                const uint32_t a = ka + (32 * q + g - 50) * 4;
#pragma unroll
                for (int m = 0; m < 4; m++) {
                    const uint32_t ve = v1[m] >> 16;
                    sts16(a + (KA_O2 + 8 * m) * 4, v1[m]); sts16(a + (KA_O2 + 8 * m) * 4 + 10, v1[m]);
                    if (m || lane != 2) { sts16(a + (KA_E2 + 8 * m - 1) * 4, ve); sts16(a + (KA_E2 + 8 * m - 1) * 4 + 10, ve); }
                }
                if (lane == 2) {
                    const uint32_t ee = prmt(v1[0], 0, 0x3232);
                    sts64(ka + (KA_DE + 256) * 4, ee, ee);
                    sts32(ka + (KA_DO + 256) * 4, ee);
                    sts16(ka + (KA_DO + 257) * 4 + 2, ee);
                    sts16(ka + (KA_DO + 255) * 4, ee);
                    sts16(ka + (KA_E3 + 72) * 4, v2[0]);
                }
            }
            __syncwarp();
#pragma unroll
            for (int m = 0; m < 4; m++) {
                const uint32_t v0 = pack_h(kacc[m >> 1][0][2 * (m & 1) + 1], kacc[m >> 1][0][2 * (m & 1)]);
                const uint32_t a = ka + (lane + 32 * m) * 4;
                sts32(a + KA_DO * 4, v0); sts16(a + (KA_DE + 1) * 4 + 2, v0); sts16(a + KA_DE * 4, v0 >> 16);
            }
            const uint32_t vv = prmt(__shfl_sync(0xFFFFFFFFu, v2[0], 0), 0, 0x1010);
            xb0 = vv & ((band(2 * q, g + 4, g + 5) >> 10 & 0x00010001u) * 0xFFFFu);
            xb1 = vv & ((band(2 * q + 8, g + 4, g + 5) >> 10 & 0x00010001u) * 0xFFFFu);
            __syncwarp();
        }
        TSL(2);
        cluster_wait();
        const int chl = rank * 8 + warp;
        if (lane < 2) st_async1(mapa(sm + SM_SCL + chl * 4, lane), __float_as_uint(2.0f * outscale) >> 16, mapa(bars + B_KDONE * 8, lane));
        bar_sync(5, 288);
        asm volatile("setmaxnreg.inc.sync.aligned.u32 200;");
        uint32_t kb[66], q2[10][4];
        const uint32_t zr = lds32(ub);
        const uint32_t A3[4] = {pin(band(2 * q, g, g + 8)), pin(band(2 * q, g + 1, g + 7)), pin(band(2 * q + 8, g, g + 8)), pin(band(2 * q + 8, g + 1, g + 7))};
        const uint32_t A2[4] = {pin(band(2 * q, g + 5, g + 7)), pin(band(2 * q, g, g + 4)), pin(band(2 * q + 8, g + 5, g + 7)), pin(band(2 * q + 8, g, g + 4))};
        xb0 = pin(xb0); xb1 = pin(xb1);
        {
            const uint32_t tag = lds32(sm + SM_KEYS + 64);
            uint4 st[4];
            const uint4* src = p.stats + warp * 128 + lane;
#pragma unroll
            for (int i = 0; i < 4; i++) st[i] = ld_relaxed128(src + 32 * i);
            mbar_wait(bars + B_SLAB * 8, 0);
            TSL(10);
            uint32_t xt[8][4];
            const uint32_t a = sm + SM_SLAB + tid * 32 + ((rank ^ ((tid >> 2) & 1)) * 16);
#pragma unroll
            for (int pp = 0; pp < 4; pp++) {
                const uint4 e = lds128(a + (2 * pp) * 8192), o = lds128(a + (2 * pp + 1) * 8192);
                xt[0][pp] = prmt(e.x, o.x, 0x5410); xt[1][pp] = prmt(e.x, o.x, 0x7632);
                xt[2][pp] = prmt(e.y, o.y, 0x5410); xt[3][pp] = prmt(e.y, o.y, 0x7632);
                xt[4][pp] = prmt(e.z, o.z, 0x5410); xt[5][pp] = prmt(e.z, o.z, 0x7632);
                xt[6][pp] = prmt(e.w, o.w, 0x5410); xt[7][pp] = prmt(e.w, o.w, 0x7632);
            }
            const uint32_t kd = ka + (((g & 1) ? KA_DO : KA_DE) + (g >> 1) - q) * 4;
#pragma unroll
            for (int z = 0; z < 66; z++) kb[z] = lds32(kd + z * 16);
            const uint32_t k2o = ka + (KA_O2 - 50 + 2 * g - 4 * q) * 4, k2e = ka + (KA_E2 - 50 + 2 * g - 4 * q) * 4;
#pragma unroll
            for (int cc = 4; cc <= 8; cc++) {
                const uint2 o2 = lds64(k2o + cc * 64), e2 = lds64(k2e + cc * 64);
                q2[cc - 4][0] = o2.x; q2[cc - 4][1] = o2.y; q2[cc - 4][2] = e2.x; q2[cc - 4][3] = e2.y;
                q2[cc + 1][0] = lds32(k2o + cc * 64 - 4); q2[cc + 1][1] = cpy(o2.x, zr);
                q2[cc + 1][2] = lds32(k2e + cc * 64 - 4); q2[cc + 1][3] = cpy(e2.x, zr);
            }
            const uint32_t tb = ((tag & 1) << 15) | ((tag >> 1) << 31);
            int it = 0;
            TSL(7);
            while (true) {
                const uint32_t bad = ((st[0].y ^ tb) | (st[1].y ^ tb) | (st[2].y ^ tb) | (st[3].y ^ tb)) & 0x80008000u;
                if (__all_sync(0xFFFFFFFFu, bad == 0) || ++it >= SPIN_LIMIT) break;
#pragma unroll
                for (int i = 0; i < 4; i++) st[i] = ld_relaxed128(src + 32 * i);
            }
            TSL(11); TG(31);
            uint32_t h1[4], h2[4];
#pragma unroll
            for (int i = 0; i < 4; i++) {
                const uint32_t o2 = st[i].w ^ (prmt(st[i].w, 0, 0xBB99) | 0x80008000u);
                const uint32_t id = 0xFFFF - 8 * tid - 2 * i;
                const uint32_t k0 = prmt(o2, id, 0x1054), k1 = prmt(o2, id - 1, 0x3254);
                h1[i] = max(k0, k1); h2[i] = min(k0, k1);
            }
            const uint32_t a1 = max(h1[0], h1[1]), a2 = __vimax3_u32(min(h1[0], h1[1]), h2[0], h2[1]);
            const uint32_t b1 = max(h1[2], h1[3]), b2 = __vimax3_u32(min(h1[2], h1[3]), h2[2], h2[3]);
            const uint32_t k1 = max(a1, b1), k2 = __vimax3_u32(min(a1, b1), a2, b2);
            const uint32_t m1 = __reduce_max_sync(0xFFFFFFFFu, k1);
            const uint32_t m2 = __reduce_max_sync(0xFFFFFFFFu, k1 == m1 ? k2 : k1);
            if (lane == 0) sts64(sm + SM_KEYS + warp * 8, m1, m2);
            bar_arrive(3, 320);
            const uint32_t ua = sm + SM_U + (tid & 1) * U_HI + ((tid >> 1) + 8) * 16;
#pragma unroll
            for (int i = 0; i < 4; i++) { st[i].y = bmul2(st[i].y & 0x7FFF7FFFu, 0x3F003F00u); st[i].z = bmul2(st[i].z, 0x3F003F00u); }
#pragma unroll
            for (int cc = 0; cc < 8; cc++) {
                uint32_t o[4];
#pragma unroll
                for (int i = 0; i < 4; i++) { const uint32_t n = norm2(xt[cc][i], st[i].x, st[i].y, st[i].z); o[i] = pack_h(blo(n), bhi(n)); }
                sts128(ua + cc * U_SZ, o[0], o[1], o[2], o[3]);
            }
        }
        TSL(12);
        bar_sync(2, 256);
        TSL(3);

        float acc[16][4];
        {
            const uint32_t se = ub + (q < 2 ? U_HI + (g + 7) * 16 + 8 + q * 4 : (g + 8) * 16 + (q - 2) * 4);
            const uint32_t so = ub + (q < 2 ? (g + 8) * 16 + 8 + q * 4 : U_HI + (g + 8) * 16 + (q - 2) * 4);
            float a3[4][2][4];
#pragma unroll
            for (int i = 0; i < 4; i++)
#pragma unroll
                for (int j = 0; j < 2; j++) a3[i][j][0] = a3[i][j][1] = a3[i][j][2] = a3[i][j][3] = 0.f;
            const uint32_t ko = ka + (KA_O3 - 56 + g - 2 * q) * 4, ke = ka + (KA_E3 - 56 + g - 2 * q) * 4;
#pragma unroll
            for (int par = 0; par < 2; par++) {
                if (par) __syncwarp();
                uint32_t w9[4][2], w7[4][2];
#pragma unroll
                for (int yy = 0; yy < 4; yy++) {
                    const int y = 2 * yy + par;
                    const uint32_t sm1 = lds32(so + y * 128 - 16), s0 = lds32(se + y * 128), s1 = lds32(so + y * 128);
                    uint32_t t0, t1;
                    mma_h(w9[yy][0], t0, A3, s0, s1);
                    mma_h(w9[yy][1], t1, A3, sm1, cpy(s0, zr));
                    w7[yy][0] = cpy(t1, zr); w7[yy][1] = cpy(t0, zr);
                }
#pragma unroll
                for (int cc = 8 - par; cc <= 14; cc += 2) {
                    const uint32_t f0 = cc == 7 ? zr : lds32(ke + cc * 32), f1 = lds32(ke + cc * 32 + 32);
                    const uint32_t f2 = cc == 7 ? cpy(zr, zr) : lds32(ko + cc * 32), f3 = lds32(ko + cc * 32 + 32);
                    const uint32_t g0 = cc == 7 ? zr + zr : lds32(ke + cc * 32 + 4), g1 = lds32(ke + cc * 32 + 36), g2 = cpy(f2, zr), g3 = cpy(f3, zr);
#pragma unroll
                    for (int T = 4; T < 8; T++) {
                        const int y = 2 * T - cc;
                        if (y >= 0) {
                            mma_f16(a3[T - 4][0], f0, f1, f2, f3, w9[y >> 1][0], w7[y >> 1][0]);
                            mma_f16(a3[T - 4][1], g0, g1, g2, g3, w9[y >> 1][1], w7[y >> 1][1]);
                        }
                    }
                }
            }
            __syncwarp();
#pragma unroll
            for (int T = 0; T < 4; T++)
#pragma unroll
                for (int b3 = 0; b3 < 2; b3++)
#pragma unroll
                    for (int b7 = 0; b7 < 2; b7++)
                        sts64(ka + (2 * T + b7) * 512 + b3 * 8 + lane * 16, __float_as_uint(a3[T][b3][2 * b7]), __float_as_uint(a3[T][b3][2 * b7 + 1]));
        }
        TSL(4);
        {
            const uint32_t lq = ub + (lane < 8 ? U_HI - 16 : lane < 24 ? 0 : U_HI) + ((lane & 7) + 8) * 16;
            const uint32_t se = ub + (q < 1 ? U_HI + (g + 7) * 16 + 12 : (g + 8) * 16 + (q - 1) * 4);
            const uint32_t so = ub + (q < 1 ? (g + 8) * 16 + 12 : U_HI + (g + 8) * 16 + (q - 1) * 4);
            const uint32_t stg = SM_WB + chl * 256 + (((lane >> 1) ^ ((chl & 1) + 4 * (chl >> 3))) * 16) + (lane & 1) * 8;
            const uint32_t cta[2] = {mapa(sm, 0), mapa(sm, 1)};
#pragma unroll
            for (int t = 0; t < 8; t++) acc[t][0] = acc[t][1] = acc[t][2] = acc[t][3] = 0.f;
            constexpr int PF = QPF;
            constexpr int NQ = PF + FENCE_EVERY;
            uint32_t Q[NQ][4], X[4], sm1, s0, s1;
#pragma unroll
            for (int i = 0; i < PF; i++) ldsm4(lq + (i - 7) * 16, Q[i][0], Q[i][1], Q[i][2], Q[i][3]);
            mbar_wait(bars + B_KDONE * 8, 0);
            mbar_wait(bars + B_TOK * 8, 0);
            const int t0 = 0xFFFF - (lds32(sm + SM_TOK) & 0xFFFF), t1 = 0xFFFF - (lds32(sm + SM_TOK + 4) & 0xFFFF);
            const int l0 = ((t0 >> 4) & 7) * 4 + ((t0 >> 1) & 3), l1 = ((t1 >> 4) & 7) * 4 + ((t1 >> 1) & 3);
            const uint32_t tmask = (lane == l0 ? 1u << (t0 >> 7) : 0u) | (lane == l1 ? 1u << (t1 >> 7) : 0u);
            uint32_t keep = ka + 4096 + (lane == l0 ? 0 : 16);
            float2 ua, uc;
            TSL(5);
            if (warp == TSW) TSL(38);
#pragma unroll
            for (int k = 0; k < 16; k++) {
                uint32_t gw[2][2];
                if (k == 4 && warp == TSW) TSL(35);
                if (k == 12 && warp == TSW) TSL(36);
#pragma unroll
                for (int r = 0; r < 8; r++) {
                    const int xi = 8 * k + r;
                    const uint32_t (&A)[4] = Q[xi % NQ];
                    if (xi % FENCE_EVERY == 0) {
                        sched_fence();
#pragma unroll
                        for (int n = xi + PF; n < xi + PF + FENCE_EVERY && n < 128; n++) ldsm4(lq + (n - 7) * 16, Q[n % NQ][0], Q[n % NQ][1], Q[n % NQ][2], Q[n % NQ][3]);
                    }
                    if (r == 4 && k >= 3 && k < 15) {
                        sm1 = lds32(so + (k - 3) * 128 - 16); s0 = lds32(se + (k - 3) * 128); s1 = lds32(so + (k - 3) * 128);
                    }
                    if (r == 0 && k >= 4) {
                        mma_h(gw[0][0], gw[0][1], A2, sm1, cpy(s0, zr));
                        mma_h(gw[1][0], gw[1][1], A2, s0, s1);
                        if (k < 12) {
                            const uint4 v = lds128(ka + (k - 4) * 512 + lane * 16);
                            acc[k + 4][0] = __uint_as_float(v.x); acc[k + 4][1] = __uint_as_float(v.y);
                            acc[k + 4][2] = __uint_as_float(v.z); acc[k + 4][3] = __uint_as_float(v.w);
                            ldsm4(lq + (k - 4) * 128, X[0], X[1], X[2], X[3]);
                        }
                    }
#pragma unroll
                    for (int i = 0; i < 4; i++)
                        if (k + i < 16) mma4(acc[k + i], A, kb[16 * i + 15 - 2 * r], kb[16 * i + 14 - 2 * r]);
                    if (k >= 4 && (r == 2 || r == 4)) {
#pragma unroll
                        for (int i = 0; i < 4; i++)
                            if (k + i < 16) mma4(acc[k + i], q2[(r >> 2) * 5 + i], gw[r >> 2][0], gw[r >> 2][1]);
                    }
                    if (k >= 4 && k < 12) {
                        if (r == 4) mma4(acc[k + 4], X, xb0, xb1);
                        if (r == 5 || r == 6) mma4(acc[k + 4], q2[(r - 5) * 5 + 4], gw[r - 5][0], gw[r - 5][1]);
                    }
                    if (r == 7) {
                        if (k + 4 < 16) mma4(acc[k + 4], A, kb[65], kb[64]);
                        ua = __half22float2(*reinterpret_cast<const __half2*>(&A[2]));
                        uc = __half22float2(*reinterpret_cast<const __half2*>(&A[3]));
                    }
                    if ((k > 0 && r == EPI_R) || xi == 127) {
                        const int t = xi == 127 ? 15 : k - 1;
                        const float w0 = acc[t][0] * ua.x, w1 = acc[t][1] * ua.y, w2 = acc[t][2] * uc.x, w3 = acc[t][3] * uc.y;
                        const uint32_t pa = pack_b(fmaf(w0, tanh_(ua.x), w0), fmaf(w1, tanh_(ua.y), w1));
                        const uint32_t pb = pack_b(fmaf(w2, tanh_(uc.x), w2), fmaf(w3, tanh_(uc.y), w3));
                        st_async2(cta[t & 1] + stg + (t >> 1) * WB_SZ, pa, pb, cta[t & 1] + SM_BAR + (B_STG + (t >> 1)) * 8);
                        asm volatile("{ .reg .pred p; setp.ne.u32 p, %1, 0; @p st.shared.v4.f32 [%0], {%2,%3,%4,%5}; @p add.u32 %0, %0, 16; }"
                                     : "+r"(keep) : "r"(tmask & (1u << t)), "f"(acc[t][0]), "f"(acc[t][1]), "f"(acc[t][2]), "f"(acc[t][3]) : "memory");
                    }
                }
            }
            if (warp == TSW) TSL(37);
            __syncwarp();
            if (lane < 2) {
                const int t = lane ? t1 : t0, to = lane ? t0 : t1;
                const uint32_t v = lds32(ka + 4096 + (l0 == l1 ? (t >> 7) > (to >> 7) : lane) * 16 + ((t >> 3) & 1) * 8 + (t & 1) * 4);
                const uint32_t dst = lane ? cta[1] : cta[0];
                st_async1(dst + SM_FIX + chl * 4, v, dst + SM_BAR + B_FIX * 8);
            }
        }
        TSL(6);
    } else {
        const int v = warp - 8;
        uint64_t pol = 0;
        cluster_wait();
        TSL(19);
        uint4 xa[4], xc[4], w4[4];
        {
            const uint4* ra = reinterpret_cast<const uint4*>(p.x + (size_t)(16 * c + 2 * v) * 1024) + lane;
#pragma unroll
            for (int k = 0; k < 4; k++) { xa[k] = ldg128(ra + 32 * k); xc[k] = ldg128(ra + 128 + 32 * k); }
#pragma unroll
            for (int k = 0; k < 4; k++) w4[k] = ldg128(reinterpret_cast<const uint4*>(p.wr) + 32 * k + lane);
        }
        uint32_t tag;
        asm volatile("ld.relaxed.gpu.global.u32 %0, [%1];" : "=r"(tag) : "l"(p.epoch) : "memory");
        if (warp == 12) {
            TG(28);
            asm volatile("createpolicy.fractional.L2::evict_first.b64 %0, 1.0;" : "=l"(pol));
            if (elect()) {
#pragma unroll 1
                for (int i = 4 * rank; i < 4 * rank + 4; i++)
                    asm volatile("cp.async.bulk.tensor.3d.shared::cluster.global.mbarrier::complete_tx::bytes.multicast::cluster"
                                 " [%0], [%1, {%3, %4, %5}], [%2], %6;"
                                 :: "r"(sm + SM_SLAB + i * 8192), "l"(&tm_x), "r"(bars + B_SLAB * 8), "r"(G * 16), "r"(i), "r"(0), "h"((uint16_t)3) : "memory");
                if (G < 56) {
#pragma unroll 1
                    for (int n = 0; n < DEPTH; n++)
                        tma3d(sm + SM_RING + n * 8192, &tm_g, G * 64, rank * 512 + n * 32, bars + (B_FULL + n) * 8, pol);
                }
            }
            __syncwarp();
            TSL(20);
        }
        uint4* const my_stats = p.stats + (c >> 4) * 128 + (v & 3) * 32 + ((2 * c) & 31);
        uint32_t* const my_part = p.part + ((2 * (32 * rank + v) + (q & 1)) * 56 + G) * 16 + g + 8 * (q >> 1);
        if (v < 4) {
            if (lane < 2) st_relaxed128(my_stats + lane, make_uint4(0, 0, 0, 0));
            if (G < 56) {
#pragma unroll
                for (int n = 0; n < 8; n++) st_relaxed32(my_part + n * 8 * 56 * 16, 0);
            }
            bar_arrive(6 + v, 64);
        } else {
            bar_sync(2 + v, 64);
        }
        tag = tag % 3 + 1;
        if (warp == 8) { sts32(sm + SM_KEYS + 64, tag); bar_arrive(5, 288); }
        {
            constexpr uint32_t ONE = 0x3F803F80u;
            float sw[4] = {0, 0, 0, 0}, sA[4] = {0, 0, 0, 0}, sB[4] = {0, 0, 0, 0};
            float qA[2][4] = {{0, 0, 0, 0}, {0, 0, 0, 0}}, qB[2][4] = {{0, 0, 0, 0}, {0, 0, 0, 0}};
#pragma unroll
            for (int k = 0; k < 4; k++) mma_bf16(sw, w4[k].x, w4[k].y, w4[k].z, w4[k].w, ONE, ONE);
#pragma unroll
            for (int k = 0; k < 4; k++) {
                mma_bf16(sA, xa[k].x, xa[k].y, xa[k].z, xa[k].w, ONE, ONE);
                mma_bf16(qA[0], xa[k].x, w4[k].x, xa[k].y, w4[k].y, xa[k].x, xa[k].y);
                mma_bf16(qA[1], xa[k].z, w4[k].z, xa[k].w, w4[k].w, xa[k].z, xa[k].w);
                mma_bf16(sB, xc[k].x, xc[k].y, xc[k].z, xc[k].w, ONE, ONE);
                mma_bf16(qB[0], xc[k].x, w4[k].x, xc[k].y, w4[k].y, xc[k].x, xc[k].y);
                mma_bf16(qB[1], xc[k].z, w4[k].z, xc[k].w, w4[k].w, xc[k].z, xc[k].w);
            }
            TSL(8);
            const bool dg = q == (g >> 1), od = g & 1;
            float r0 = dg ? (od ? qA[0][1] + qA[1][1] : qA[0][0] + qA[1][0]) : 0.f;
            float r1 = dg ? (od ? qA[0][3] + qA[1][3] : qA[0][2] + qA[1][2]) : 0.f;
            float r2 = dg ? (od ? qB[0][1] + qB[1][1] : qB[0][0] + qB[1][0]) : 0.f;
            float r3 = dg ? (od ? qB[0][3] + qB[1][3] : qB[0][2] + qB[1][2]) : 0.f;
            const bool rowb = lane & 1;
            float ss = (rowb ? r2 : r0) + __shfl_xor_sync(0xFFFFFFFFu, rowb ? r0 : r2, 1);
            float dw = (rowb ? r3 : r1) + __shfl_xor_sync(0xFFFFFFFFu, rowb ? r1 : r3, 1);
            float sx = rowb ? sB[0] + sB[2] : sA[0] + sA[2];
            float ws = sw[0] + sw[2];
            ss += __shfl_xor_sync(0xFFFFFFFFu, ss, 2); dw += __shfl_xor_sync(0xFFFFFFFFu, dw, 2);
#pragma unroll
            for (int o = 4; o < 32; o <<= 1) {
                ss += __shfl_xor_sync(0xFFFFFFFFu, ss, o); dw += __shfl_xor_sync(0xFFFFFFFFu, dw, o);
                sx += __shfl_xor_sync(0xFFFFFFFFu, sx, o); ws += __shfl_xor_sync(0xFFFFFFFFu, ws, o);
            }
            const float mean = sx * (1.0f / 1024.0f);
            const float var = fmaxf(ss * (1.0f / 1024.0f) - mean * mean, 0.f);
            const float m = rb(mean);
            float sd; asm("sqrt.approx.ftz.f32 %0, %1;" : "=f"(sd) : "f"(rb(rb(var) + 1e-5f)));
            const float rs = rcp(rb(sd));
            const float hi = rb(rs);
            const uint32_t p0 = pack_b(m, hi), p1 = pack_b(rs - hi, rs * (dw - m * ws));
            const uint32_t o0 = __shfl_xor_sync(0xFFFFFFFFu, p0, 1), o1 = __shfl_xor_sync(0xFFFFFFFFu, p1, 1);
            if (lane == 0) {
                const uint32_t tb = ((tag & 1) << 15) | ((tag >> 1) << 31);
                st_relaxed128(my_stats + (v >> 2), make_uint4(prmt(p0, o0, 0x5410), (prmt(p0, o0, 0x7632) & 0x7FFF7FFFu) | tb,
                                                              prmt(p1, o1, 0x5410), prmt(p1, o1, 0x7632)));
            }
        }
        TSL(9);
        if (warp < 12) {
            asm volatile("setmaxnreg.dec.sync.aligned.u32 56;");
            if (G < 56) {
                const uint32_t la = pin(sm + SM_RING + ((lane & 7) + 8 * (lane >> 4)) * 128 + (((2 * v + ((lane >> 3) & 1)) ^ (lane & 7)) * 16));
                const uint32_t xs = pin(sm + SM_XSEL + ((g >> 1) & 1) * XSEL_T + rank * 1024 + q * 16);
                const uint32_t hs = pin(sm + SM_H + ((g >> 1) & 1) * H_T + q * 16);
                const uint32_t hd = pin(sm + SM_H + (q & 1) * H_T + (v >> 1) * 64 + (g >> 1) * 16 + (2 * (v & 1) + (q >> 1)) * 4 + (g & 1) * 2);
                const uint32_t pr = pin(SM_PAIR + v * 256 + lane * 8), rem = mapa(sm, rank ^ 1);
                float ag[4] = {0, 0, 0, 0}, au[4] = {0, 0, 0, 0};
                mbar_wait(bars + B_TOK * 8, 0);
                TSL(13);
#pragma unroll
                for (int n = 0; n < 16; n++) {
                    const uint4 xb = lds128(xs + n * 64);
                    mbar_wait(bars + full_bar(n) * 8, full_par(n));
                    uint32_t a[4][4];
#pragma unroll
                    for (int i = 0; i < 4; i++) ldsm4t(la + (n % NSLOT) * 8192 + i * 2048, a[i][0], a[i][1], a[i][2], a[i][3]);
                    __syncwarp();
                    if (lane == 0) mbar_arrive(bars + (B_EMPTY + n % NSLOT) * 8);
                    mma_bf16(ag, a[0][0], a[0][1], a[0][2], a[0][3], xb.x, xb.y);
                    mma_bf16(au, a[2][0], a[2][1], a[2][2], a[2][3], xb.x, xb.y);
                    mma_bf16(ag, a[1][0], a[1][1], a[1][2], a[1][3], xb.z, xb.w);
                    mma_bf16(au, a[3][0], a[3][1], a[3][2], a[3][3], xb.z, xb.w);
                }
                TSL(14);
                float gs = (q & 2) ? ag[2] : ag[0], us = (q & 2) ? au[2] : au[0];
                st_async2(rem + pr, __float_as_uint(gs), __float_as_uint(us), rem + SM_BAR + B_PAIR * 8);
                mbar_wait(bars + B_PAIR * 8, 0);
                const uint2 oth = lds64(sm + pr);
                const uint32_t gu = pack_b(gs + __uint_as_float(oth.x), us + __uint_as_float(oth.y));
                gs = p.up_first ? bhi(gu) : blo(gu); us = p.up_first ? blo(gu) : bhi(gu);
                const float hv = rb(siluf_(gs)) * us;
                sts16(hd, pack_b(hv, hv));
                bar_sync(4, 128);
                const uint4 h0 = lds128(hs), h1 = lds128(hs + 64);
                TSL(15);
#pragma unroll
                for (int n = 16; n < 24; n++) {
                    mbar_wait(bars + full_bar(n) * 8, full_par(n));
                    uint32_t a[4][4];
#pragma unroll
                    for (int i = 0; i < 4; i++) ldsm4t(la + (n % NSLOT) * 8192 + i * 2048, a[i][0], a[i][1], a[i][2], a[i][3]);
                    if (n + NSLOT < 24) {
                        __syncwarp();
                        if (lane == 0) mbar_arrive(bars + (B_EMPTY + n % NSLOT) * 8);
                    }
                    float d[4] = {0, 0, 0, 0};
                    mma_bf16(d, a[0][0], a[0][1], a[0][2], a[0][3], h0.x, h0.y);
                    mma_bf16(d, a[1][0], a[1][1], a[1][2], a[1][3], h0.z, h0.w);
                    mma_bf16(d, a[2][0], a[2][1], a[2][2], a[2][3], h1.x, h1.y);
                    mma_bf16(d, a[3][0], a[3][1], a[3][2], a[3][3], h1.z, h1.w);
                    st_relaxed32(my_part + (n - 16) * 8 * 56 * 16, (__float_as_uint((q & 2) ? d[2] : d[0]) & ~3u) | tag);
                }
                TSL(16);
            }
        } else {
            asm volatile("setmaxnreg.dec.sync.aligned.u32 56;");
            if (warp == 12) {
                if (G < 56) {
                    const bool lead = elect();
#pragma unroll
                    for (int n = DEPTH; n < 24; n++) {
                        mbar_wait(bars + full_bar(n - DEPTH) * 8, full_par(n - DEPTH));
                        if (n >= NSLOT) mbar_wait(bars + (B_EMPTY + n % NSLOT) * 8, (n / NSLOT - 1) & 1);
                        if (lead) {
                            const uint32_t fb = bars + full_bar(n) * 8;
                            mbar_expect(fb, 8192);
                            if (n < 16) tma3d(sm + SM_RING + (n % NSLOT) * 8192, &tm_g, G * 64, rank * 512 + n * 32, fb, pol);
                            else tma3d(sm + SM_RING + (n % NSLOT) * 8192, &tm_d, rank * 512 + (n - 16) * 64, G * 64, fb, pol);
                        }
                    }
                    TSL(23);
                }
            } else if (warp >= 14) {
                const int sw = warp - 14;
                bar_sync(3, 320);
                const uint32_t key = lane < 16 ? lds32(sm + SM_KEYS + lane * 4) : 0u;
                const uint32_t m1 = __reduce_max_sync(0xFFFFFFFFu, key);
                const uint32_t m2 = __reduce_max_sync(0xFFFFFFFFu, key == m1 ? 0u : key);
                const int t0 = (0xFFFF - (m1 & 0xFFFF)) & 2047, t1 = (0xFFFF - (m2 & 0xFFFF)) & 2047;
                {
                    const int t = sw ? t1 : t0;
                    const uint4* row = reinterpret_cast<const uint4*>(p.x + (size_t)t * 1024) + lane;
                    uint4 xr[4];
#pragma unroll
                    for (int i = 0; i < 4; i++) xr[i] = ldg128(row + 32 * i);
                    const uint4 st = ld_relaxed128(p.stats + (t >> 8) * 128 + ((t >> 1) & 3) * 32 + ((t >> 3) & 31));
                    if (lane == 0) {
                        sts32(sm + SM_TOK + 4 * sw, ((sw ? m2 : m1) & 0xFFFF0000u) | (0xFFFF - t));
                        if (c == 0 && sw == 0) st_relaxed32(p.epoch, tag);
                    }
                    const uint32_t se = (t & 1) ? 0x3232 : 0x1010;
                    const uint32_t m = prmt(st.x, 0, se), hi = prmt(st.y, 0, se) & 0x7FFF7FFFu, lo = prmt(st.z, 0, se);
                    const uint32_t a = sm + SM_XSEL + sw * XSEL_T + (lane >> 2) * 64 + (lane & 3) * 4;
#pragma unroll
                    for (int i = 0; i < 4; i++) {
                        sts32(a + i * 512, norm2(xr[i].x, m, hi, lo)); sts32(a + i * 512 + 16, norm2(xr[i].y, m, hi, lo));
                        sts32(a + i * 512 + 32, norm2(xr[i].z, m, hi, lo)); sts32(a + i * 512 + 48, norm2(xr[i].w, m, hi, lo));
                    }
                    __syncwarp();
                    if (lane == 0) mbar_arrive(bars + B_TOK * 8);
                }
                const int chl = 8 * ((lane >> 1) & 1) + 2 * (lane >> 3) + (lane & 1);
                const uint32_t la = sm + SM_WB + chl * 256 + (((8 * sw + 2 * ((lane >> 2) & 1)) ^ ((chl & 1) + 4 * (chl >> 3))) * 16);
                const int tl = 128 * rank + 64 * sw + 16 * (q >> 1) + 2 * (g >> 2) + 8 * ((g >> 1) & 1) + (g & 1);
                const uint32_t xa0 = sm + SM_SLAB + (tl & 7) * 8192 + (tl >> 3) * 32 + (q & 1) * 16;
                __nv_bfloat16* const op = p.out + (size_t)tl * 1024 + G * 16 + (q & 1) * 8;
                mbar_wait(bars + B_KDONE * 8, 0);
                uint32_t sc[4];
                {
                    const uint4 s0 = lds128(sm + SM_SCL + (q & 1) * 32), s1 = lds128(sm + SM_SCL + (q & 1) * 32 + 16);
                    sc[0] = prmt(s0.x, s0.y, 0x5410); sc[1] = prmt(s0.z, s0.w, 0x5410); sc[2] = prmt(s1.x, s1.y, 0x5410); sc[3] = prmt(s1.z, s1.w, 0x5410);
                }
                uint32_t skip = 0;
#pragma unroll
                for (int k = 0; k < 2; k++) {
                    const int d = (k ? t1 : t0) - tl;
                    if ((d & ~0x724) == 0) skip |= 1u << ((d >> 8) * 4 + ((d >> 5) & 1) * 2 + ((d >> 2) & 1));
                }
                const uint32_t lb[4] = {pin(la), pin(la ^ 16), pin(la ^ 64), pin(la ^ 80)}, xb[2] = {pin(xa0), pin(xa0 ^ 144)};
#pragma unroll
                for (int s = 0; s < 8; s++) {
                    uint4 xv[4];
#pragma unroll
                    for (int i = 0; i < 4; i++) xv[i] = lds128(xb[i >> 1] + s * 1024 + (i & 1) * 4 * 8192);
                    mbar_wait(bars + (B_STG + s) * 8, 0);
#pragma unroll
                    for (int i = 0; i < 4; i++) {
                        uint32_t a[4];
                        ldsm4t(lb[i] + s * WB_SZ, a[0], a[1], a[2], a[3]);
                        asm volatile("{ .reg .pred p; setp.eq.u32 p, %5, 0; @p st.global.v4.u32 [%0], {%1,%2,%3,%4}; }"
                                     :: "l"(op + (size_t)(256 * s + (i & 1) * 4 + (i >> 1) * 32) * 1024),
                                        "r"(bfma2(a[0], sc[0], xv[i].x)), "r"(bfma2(a[1], sc[1], xv[i].y)),
                                        "r"(bfma2(a[2], sc[2], xv[i].z)), "r"(bfma2(a[3], sc[3], xv[i].w)), "r"(skip & (1u << (4 * s + i))) : "memory");
                    }
                }
                TSL(17); TG(30);
            } else {
                mbar_wait(bars + B_TOK * 8, 0);
                const uint32_t key = lds32(sm + SM_TOK + 4 * rank);
                const int t = 0xFFFF - (key & 0xFFFF);
                const int col = 4 * q + 2 * (lane >> 4) + ((lane >> 3) & 1), d = G * 16 + col;
                const float r = __uint_as_float((key & 0x80000000u) ? (key & 0x7FFF0000u) : (~key & 0xFFFF0000u));
                const float sg = rb(sigmoidf_(r));
                const float xn = blo(lds16(sm + SM_XSEL + rank * XSEL_T + (d >> 5) * 64 + ((d >> 1) & 3) * 16 + ((d >> 3) & 3) * 4 + (d & 1) * 2));
                mbar_wait(bars + B_KDONE * 8, 0);
                const float scl = blo(lds32(sm + SM_SCL + col * 4));
                const float xv = blo(lds16(sm + SM_SLAB + (t & 7) * 8192 + (t >> 3) * 32 + (((col >> 3) ^ ((t >> 5) & 1)) * 16) + (col & 7) * 2));
                mbar_wait(bars + (G < 56 ? full_bar(23) : B_FIX) * 8, 0);
                TSL(24);
                const uint4* src = reinterpret_cast<const uint4*>(p.part) + c * 224 + lane;
                float s0 = 0, s1 = 0, s2 = 0, s3 = 0;
                {
                    uint4 pv[7];
                    int it = 0;
                    bool ok;
                    do {
                        uint32_t bad = 0;
#pragma unroll
                        for (int i = 0; i < 7; i++) pv[i] = ld_relaxed128(src + 32 * i);
#pragma unroll
                        for (int i = 0; i < 7; i++) bad |= (pv[i].x ^ tag) | (pv[i].y ^ tag) | (pv[i].z ^ tag) | (pv[i].w ^ tag);
                        ok = __all_sync(0xFFFFFFFFu, (bad & 3) == 0);
                    } while (!ok && ++it < SPIN_LIMIT);
#pragma unroll
                    for (int i = 0; i < 7; i++) {
                        s0 += __uint_as_float(pv[i].x); s1 += __uint_as_float(pv[i].y); s2 += __uint_as_float(pv[i].z); s3 += __uint_as_float(pv[i].w);
                    }
                }
                TSL(25);
                const bool u16 = lane & 16, u8 = lane & 8;
                const float y0 = (u16 ? s2 : s0) + __shfl_xor_sync(0xFFFFFFFFu, u16 ? s0 : s2, 16);
                const float y1 = (u16 ? s3 : s1) + __shfl_xor_sync(0xFFFFFFFFu, u16 ? s1 : s3, 16);
                float y = (u8 ? y1 : y0) + __shfl_xor_sync(0xFFFFFFFFu, u8 ? y0 : y1, 8);
                y += __shfl_xor_sync(0xFFFFFFFFu, y, 4);
                const float z = rb(xn + rb(rb(y) * sg));
                const float gt = rb(siluf_(z));
                mbar_wait(bars + B_FIX * 8, 0);
                const float o = xv + rb(rb(__uint_as_float(lds32(sm + SM_FIX + col * 4)) * scl) * gt);
                if (!(lane & 4)) p.out[(size_t)t * 1024 + d] = __float2bfloat16(o);
                TSL(26); TG(29);
            }
        }
    }
}

typedef CUresult (*EncodeFn)(CUtensorMap*, CUtensorMapDataType, cuuint32_t, void*, const cuuint64_t*, const cuuint64_t*,
                             const cuuint32_t*, const cuuint32_t*, CUtensorMapInterleave, CUtensorMapSwizzle,
                             CUtensorMapL2promotion, CUtensorMapFloatOOBfill);

}

extern "C" void kernel_launch(void* const* d_in, const int* in_sizes, int n_in, void* d_out, int out_size) {
    Params p;
    p.x = (const __nv_bfloat16*)d_in[0];
    p.lar = (const __nv_bfloat16*)d_in[1];
    p.aim = (const __nv_bfloat16*)d_in[2];
    p.cr = (const __nv_bfloat16*)d_in[3];
    p.ci = (const __nv_bfloat16*)d_in[4];
    p.logdt = (const __nv_bfloat16*)d_in[5];
    p.dskip = (const __nv_bfloat16*)d_in[6];
    p.wr = (const __nv_bfloat16*)d_in[8];
    p.out = (__nv_bfloat16*)d_out;
    cudaGetSymbolAddress((void**)&p.stats, g_stats);
    cudaGetSymbolAddress((void**)&p.part, g_part);
    cudaGetSymbolAddress((void**)&p.epoch, g_epoch);

    void* fn = nullptr;
    cudaDriverEntryPointQueryResult qr;
    cudaGetDriverEntryPoint("cuTensorMapEncodeTiled", &fn, cudaEnableDefault, &qr);
    EncodeFn enc = (EncodeFn)fn;
    CUtensorMap tm_x, tm_g, tm_d;
    const cuuint32_t es[3] = {1, 1, 1};
    {
        const cuuint64_t gd[3] = {1024, 8, 256}, gs[2] = {2048, 16384};
        const cuuint32_t bx[3] = {16, 1, 256};
        enc(&tm_x, CU_TENSOR_MAP_DATA_TYPE_BFLOAT16, 3, d_in[0], gd, gs, bx, es, CU_TENSOR_MAP_INTERLEAVE_NONE,
            CU_TENSOR_MAP_SWIZZLE_32B, CU_TENSOR_MAP_L2_PROMOTION_NONE, CU_TENSOR_MAP_FLOAT_OOB_FILL_NONE);
    }
    {
        char *wg = (char*)d_in[9], *wu = (char*)d_in[10];
        p.up_first = wu < wg;
        const cuuint64_t gd[3] = {3584, 1024, 2}, gs[2] = {7168, (cuuint64_t)(p.up_first ? wg - wu : wu - wg)};
        const cuuint32_t bx[3] = {64, 32, 2};
        enc(&tm_g, CU_TENSOR_MAP_DATA_TYPE_BFLOAT16, 3, p.up_first ? wu : wg, gd, gs, bx, es, CU_TENSOR_MAP_INTERLEAVE_NONE,
            CU_TENSOR_MAP_SWIZZLE_128B, CU_TENSOR_MAP_L2_PROMOTION_NONE, CU_TENSOR_MAP_FLOAT_OOB_FILL_NONE);
    }
    {
        const cuuint64_t gd[3] = {1024, 3584, 1}, gs[2] = {2048, 2048 * 3584};
        const cuuint32_t bx[3] = {64, 64, 1};
        enc(&tm_d, CU_TENSOR_MAP_DATA_TYPE_BFLOAT16, 3, d_in[11], gd, gs, bx, es, CU_TENSOR_MAP_INTERLEAVE_NONE,
            CU_TENSOR_MAP_SWIZZLE_128B, CU_TENSOR_MAP_L2_PROMOTION_NONE, CU_TENSOR_MAP_FLOAT_OOB_FILL_NONE);
    }
    cudaFuncSetAttribute(fused_kernel, cudaFuncAttributeMaxDynamicSharedMemorySize, SM_TOTAL);
    fused_kernel<<<128, NTHREADS, SM_TOTAL>>>(p, tm_x, tm_g, tm_d);
}
```

```cpp
#include <cuda_runtime.h>
#include <cuda.h>
#include <cuda_bf16.h>
#include <cuda_fp16.h>
#include <stdint.h>

#define TG(i)
#define TS(i)
#define TSL(i)

#define EPI_R 4
#define QPF 4
#define FENCE_EVERY 4
#define TSW 0
#define NSLOT 7
#define DEPTH 4

namespace {

constexpr int NTHREADS = 512;
constexpr int SPIN_LIMIT = 1 << 16;

constexpr int SM_SLAB = 0;
constexpr int SM_RING = 65536;
constexpr int SM_WB   = SM_RING + NSLOT * 8192;
constexpr int WB_SZ   = 8448;
constexpr int SM_U    = SM_WB + 8 * WB_SZ;
constexpr int U_HI    = 2240;
constexpr int U_SZ    = 4416;
constexpr int SM_XSEL = SM_U + 8 * U_SZ;
constexpr int XSEL_T  = 2112;
constexpr int SM_PAIR = SM_XSEL + 2 * XSEL_T;
constexpr int SM_H    = SM_PAIR + 1024;
constexpr int H_T     = 192;
constexpr int SM_KEYS = SM_H + 2 * H_T;
constexpr int SM_TOK  = SM_KEYS + 128;
constexpr int SM_FIX  = SM_TOK + 16;
constexpr int SM_SCL  = SM_FIX + 64;
constexpr int SM_BAR  = SM_SCL + 64;
constexpr int B_FULL = 0, B_EMPTY = 8, B_STG = 16, B_MISC = 24, NBAR = 32;
constexpr int B_KDONE = B_MISC, B_TOK = B_MISC + 1, B_FIX = B_MISC + 2, B_PAIR = B_MISC + 3, B_SLAB = B_MISC + 4;
constexpr int SM_TOTAL = SM_BAR + NBAR * 8;
static_assert(SM_TOTAL <= 232448 && NSLOT < 8, "smem");
__host__ __device__ constexpr int full_bar(int n) { return B_FULL + (n == 23 ? 7 : n % NSLOT); }
__host__ __device__ constexpr int full_par(int n) { return n == 23 ? 0 : (n / NSLOT) & 1; }
constexpr int KP = 272;
constexpr int KA_DE = 4;
constexpr int KA_DO = 276;
constexpr int KA_O2 = 544;
constexpr int KA_E2 = 640;
constexpr int KA_O3 = 736;
constexpr int KA_E3 = 816;

struct Params {
    const __nv_bfloat16 *lar, *aim, *cr, *ci, *logdt, *dskip;
    const __nv_bfloat16 *x, *wr;
    __nv_bfloat16* out;
    uint4* stats;
    uint32_t *part, *epoch;
    int up_first;
};

__device__ uint4 g_stats[1024];
__device__ uint32_t g_part[128 * 56 * 16];
__device__ uint32_t g_epoch;

__device__ __forceinline__ uint4 ldg128(const void* p) {
    uint4 v; asm volatile("ld.global.nc.v4.u32 {%0,%1,%2,%3}, [%4];" : "=r"(v.x), "=r"(v.y), "=r"(v.z), "=r"(v.w) : "l"(p)); return v;
}
__device__ __forceinline__ uint4 ld_relaxed128(const void* p) {
    uint4 v;
    asm volatile("{ .reg .b128 t; ld.relaxed.gpu.global.b128 t, [%4]; mov.b128 {%0,%1,%2,%3}, t; }"
                 : "=r"(v.x), "=r"(v.y), "=r"(v.z), "=r"(v.w) : "l"(p) : "memory");
    return v;
}
__device__ __forceinline__ void st_relaxed128(void* p, uint4 v) {
    asm volatile("{ .reg .b128 t; mov.b128 t, {%1,%2,%3,%4}; st.relaxed.gpu.global.b128 [%0], t; }"
                 :: "l"(p), "r"(v.x), "r"(v.y), "r"(v.z), "r"(v.w) : "memory");
}
__device__ __forceinline__ void st_relaxed32(void* p, uint32_t v) {
    asm volatile("st.relaxed.gpu.global.u32 [%0], %1;" :: "l"(p), "r"(v) : "memory");
}
__device__ __forceinline__ uint32_t lds32(uint32_t a) { uint32_t v; asm volatile("ld.shared.u32 %0, [%1];" : "=r"(v) : "r"(a)); return v; }
__device__ __forceinline__ uint32_t lds16(uint32_t a) { uint32_t v; asm volatile("ld.shared.u16 %0, [%1];" : "=r"(v) : "r"(a)); return v; }
__device__ __forceinline__ uint2 lds64(uint32_t a) { uint2 v; asm volatile("ld.shared.v2.u32 {%0,%1}, [%2];" : "=r"(v.x), "=r"(v.y) : "r"(a)); return v; }
__device__ __forceinline__ uint4 lds128(uint32_t a) {
    uint4 v; asm volatile("ld.shared.v4.u32 {%0,%1,%2,%3}, [%4];" : "=r"(v.x), "=r"(v.y), "=r"(v.z), "=r"(v.w) : "r"(a)); return v;
}
__device__ __forceinline__ void sts16(uint32_t a, uint32_t v) { asm volatile("st.shared.u16 [%0], %1;" :: "r"(a), "h"((uint16_t)v) : "memory"); }
__device__ __forceinline__ void sts32(uint32_t a, uint32_t v) { asm volatile("st.shared.u32 [%0], %1;" :: "r"(a), "r"(v) : "memory"); }
__device__ __forceinline__ void sts64(uint32_t a, uint32_t x, uint32_t y) { asm volatile("st.shared.v2.u32 [%0], {%1,%2};" :: "r"(a), "r"(x), "r"(y) : "memory"); }
__device__ __forceinline__ void sts128(uint32_t a, uint32_t x, uint32_t y, uint32_t z, uint32_t w) {
    asm volatile("st.shared.v4.u32 [%0], {%1,%2,%3,%4};" :: "r"(a), "r"(x), "r"(y), "r"(z), "r"(w) : "memory");
}
__device__ __forceinline__ void ldsm4(uint32_t a, uint32_t& r0, uint32_t& r1, uint32_t& r2, uint32_t& r3) {
    asm volatile("ldmatrix.sync.aligned.m8n8.x4.shared.b16 {%0,%1,%2,%3}, [%4];" : "=r"(r0), "=r"(r1), "=r"(r2), "=r"(r3) : "r"(a));
}
__device__ __forceinline__ void ldsm4t(uint32_t a, uint32_t& r0, uint32_t& r1, uint32_t& r2, uint32_t& r3) {
    asm volatile("ldmatrix.sync.aligned.m8n8.x4.trans.shared.b16 {%0,%1,%2,%3}, [%4];" : "=r"(r0), "=r"(r1), "=r"(r2), "=r"(r3) : "r"(a));
}
__device__ __forceinline__ void mma_f16(float (&d)[4], uint32_t a0, uint32_t a1, uint32_t a2, uint32_t a3, uint32_t b0, uint32_t b1) {
    asm("mma.sync.aligned.m16n8k16.row.col.f32.f16.f16.f32 {%0,%1,%2,%3}, {%4,%5,%6,%7}, {%8,%9}, {%0,%1,%2,%3};"
        : "+f"(d[0]), "+f"(d[1]), "+f"(d[2]), "+f"(d[3]) : "r"(a0), "r"(a1), "r"(a2), "r"(a3), "r"(b0), "r"(b1));
}
__device__ __forceinline__ void mma_bf16(float (&d)[4], uint32_t a0, uint32_t a1, uint32_t a2, uint32_t a3, uint32_t b0, uint32_t b1) {
    asm("mma.sync.aligned.m16n8k16.row.col.f32.bf16.bf16.f32 {%0,%1,%2,%3}, {%4,%5,%6,%7}, {%8,%9}, {%0,%1,%2,%3};"
        : "+f"(d[0]), "+f"(d[1]), "+f"(d[2]), "+f"(d[3]) : "r"(a0), "r"(a1), "r"(a2), "r"(a3), "r"(b0), "r"(b1));
}
__device__ __forceinline__ void mma_h(uint32_t& d0, uint32_t& d1, const uint32_t (&a)[4], uint32_t b0, uint32_t b1) {
    asm("mma.sync.aligned.m16n8k16.row.col.f16.f16.f16.f16 {%0,%1}, {%2,%3,%4,%5}, {%6,%7}, {%8,%8};"
        : "=r"(d0), "=r"(d1) : "r"(a[0]), "r"(a[1]), "r"(a[2]), "r"(a[3]), "r"(b0), "r"(b1), "r"(0u));
}
__device__ __forceinline__ uint32_t prmt(uint32_t a, uint32_t b, uint32_t s) { uint32_t d; asm("prmt.b32 %0, %1, %2, %3;" : "=r"(d) : "r"(a), "r"(b), "r"(s)); return d; }
__device__ __forceinline__ uint32_t pack_h(float lo, float hi) { uint32_t d; asm("cvt.rn.f16x2.f32 %0, %1, %2;" : "=r"(d) : "f"(hi), "f"(lo)); return d; }
__device__ __forceinline__ uint32_t pack_b(float lo, float hi) { uint32_t d; asm("cvt.rn.bf16x2.f32 %0, %1, %2;" : "=r"(d) : "f"(hi), "f"(lo)); return d; }
__device__ __forceinline__ float blo(uint32_t v) { return __uint_as_float(v << 16); }
__device__ __forceinline__ float bhi(uint32_t v) { return __uint_as_float(v & 0xFFFF0000u); }
__device__ __forceinline__ float rb(float v) { return blo(pack_b(v, v)); }
__device__ __forceinline__ uint32_t bsub2(uint32_t a, uint32_t b) { uint32_t d; asm("sub.rn.bf16x2 %0, %1, %2;" : "=r"(d) : "r"(a), "r"(b)); return d; }
__device__ __forceinline__ uint32_t bmul2(uint32_t a, uint32_t b) { uint32_t d; asm("mul.rn.bf16x2 %0, %1, %2;" : "=r"(d) : "r"(a), "r"(b)); return d; }
__device__ __forceinline__ uint32_t bfma2(uint32_t a, uint32_t b, uint32_t c) { uint32_t d; asm("fma.rn.bf16x2 %0, %1, %2, %3;" : "=r"(d) : "r"(a), "r"(b), "r"(c)); return d; }
__device__ __forceinline__ uint32_t norm2(uint32_t x, uint32_t m, uint32_t hi, uint32_t lo) {
    uint32_t a = bsub2(x, m);
    return bfma2(a, hi, bmul2(a, lo));
}
__device__ __forceinline__ float ex2(float v) { float d; asm("ex2.approx.ftz.f32 %0, %1;" : "=f"(d) : "f"(v)); return d; }
__device__ __forceinline__ float rcp(float v) { float d; asm("rcp.approx.ftz.f32 %0, %1;" : "=f"(d) : "f"(v)); return d; }
__device__ __forceinline__ float sigmoidf_(float v) { return rcp(1.0f + ex2(-1.4426950408889634f * v)); }
__device__ __forceinline__ float siluf_(float v) { return v * sigmoidf_(v); }

__device__ __forceinline__ void mbar_init(uint32_t a, int n) { asm volatile("mbarrier.init.shared::cta.b64 [%0], %1;" :: "r"(a), "r"(n) : "memory"); }
__device__ __forceinline__ void mbar_expect(uint32_t a, int tx) { asm volatile("mbarrier.arrive.expect_tx.shared::cta.b64 _, [%0], %1;" :: "r"(a), "r"(tx) : "memory"); }
__device__ __forceinline__ void mbar_arrive(uint32_t a) { asm volatile("mbarrier.arrive.shared::cta.b64 _, [%0];" :: "r"(a) : "memory"); }
__device__ __forceinline__ void mbar_wait(uint32_t a, int parity) {
    asm volatile("{ .reg .pred p;\n"
                 "W: mbarrier.try_wait.parity.shared::cta.b64 p, [%0], %1;\n"
                 "@!p bra.uni W; }" :: "r"(a), "r"(parity) : "memory");
}
__device__ __forceinline__ uint32_t mapa(uint32_t a, uint32_t rank) { uint32_t d; asm("mapa.shared::cluster.u32 %0, %1, %2;" : "=r"(d) : "r"(a), "r"(rank)); return d; }
__device__ __forceinline__ void st_async2(uint32_t a, uint32_t x, uint32_t y, uint32_t bar) {
    asm volatile("st.async.weak.shared::cluster.mbarrier::complete_tx::bytes.v2.b32 [%0], {%1,%2}, [%3];" :: "r"(a), "r"(x), "r"(y), "r"(bar) : "memory");
}
__device__ __forceinline__ void st_async1(uint32_t a, uint32_t x, uint32_t bar) {
    asm volatile("st.async.weak.shared::cluster.mbarrier::complete_tx::bytes.b32 [%0], %1, [%2];" :: "r"(a), "r"(x), "r"(bar) : "memory");
}
__device__ __forceinline__ void bar_sync(int id, int n) { asm volatile("bar.sync %0, %1;" :: "r"(id), "r"(n) : "memory"); }
__device__ __forceinline__ void bar_arrive(int id, int n) { asm volatile("bar.arrive %0, %1;" :: "r"(id), "r"(n) : "memory"); }
__device__ __forceinline__ void cluster_arrive() { asm volatile("barrier.cluster.arrive.relaxed.aligned;" ::: "memory"); }
__device__ __forceinline__ void cluster_wait() { asm volatile("barrier.cluster.wait.aligned;" ::: "memory"); }
__device__ __forceinline__ void tma3d(uint32_t dst, const CUtensorMap* tm, int c0, int c1, uint32_t bar, uint64_t pol) {
    asm volatile("cp.async.bulk.tensor.3d.shared::cluster.global.mbarrier::complete_tx::bytes.L2::cache_hint [%0], [%1, {%3, %4, %6}], [%2], %5;"
                 :: "r"(dst), "l"(tm), "r"(bar), "r"(c0), "r"(c1), "l"(pol), "r"(0) : "memory");
}
__device__ __forceinline__ bool elect() {
    uint32_t p; asm volatile("{ .reg .pred p; elect.sync _|p, 0xFFFFFFFF; selp.u32 %0, 1, 0, p; }" : "=r"(p)); return p;
}

struct cf { float r, i; };
__device__ __forceinline__ cf cmul(cf a, cf b) { return {a.r * b.r - a.i * b.i, a.r * b.i + a.i * b.r}; }
__device__ __forceinline__ cf csq(cf a) { return {a.r * a.r - a.i * a.i, (a.r + a.r) * a.i}; }
__device__ __forceinline__ cf cexp_(float a2, float b) { float m = ex2(a2); return {m * __cosf(b), m * __sinf(b)}; }
struct hc { uint32_t r, i; };
__device__ __forceinline__ hc pk(cf a, cf b) { return {pack_h(a.r, b.r), pack_h(a.i, b.i)}; }
__device__ __forceinline__ hc hmulc(hc a, hc b) {
    const __half2 ar = *reinterpret_cast<__half2*>(&a.r), ai = *reinterpret_cast<__half2*>(&a.i);
    const __half2 br = *reinterpret_cast<__half2*>(&b.r), bi = *reinterpret_cast<__half2*>(&b.i);
    const __half2 r = __hfma2(ar, br, __hneg2(__hmul2_rn(ai, bi))), i = __hfma2(ar, bi, __hmul2_rn(ai, br));
    return {*reinterpret_cast<const uint32_t*>(&r), *reinterpret_cast<const uint32_t*>(&i)};
}
__device__ __forceinline__ void sth(uint32_t a, hc v) { sts32(a, v.r); sts32(a + 128, v.i); }
__device__ __forceinline__ uint32_t cpy(uint32_t v, uint32_t z) { uint32_t d; asm("xor.b32 %0, %1, %2;" : "=r"(d) : "r"(v), "r"(z)); return d; }
__device__ __forceinline__ void sched_fence() { asm volatile("pmevent 0;" ::: "memory"); }
__device__ __forceinline__ uint32_t pin(uint32_t v) { return __shfl_sync(0xFFFFFFFFu, v, threadIdx.x & 31); }
__device__ __forceinline__ void mma4(float (&d)[4], const uint32_t (&a)[4], uint32_t b0, uint32_t b1) { mma_f16(d, a[0], a[1], a[2], a[3], b0, b1); }
__device__ __forceinline__ float tanh_(float v) { float d; asm("tanh.approx.f32 %0, %1;" : "=f"(d) : "f"(v)); return d; }
__device__ __forceinline__ uint32_t band(int k0, int lo, int hi) {
    return ((k0 >= lo && k0 <= hi) ? 0x3C00u : 0u) | ((k0 + 1 >= lo && k0 + 1 <= hi) ? 0x3C000000u : 0u);
}

__global__ void __cluster_dims__(2, 1, 1) __launch_bounds__(NTHREADS, 1)
fused_kernel(const Params p, const __grid_constant__ CUtensorMap tm_x, const __grid_constant__ CUtensorMap tm_g,
             const __grid_constant__ CUtensorMap tm_d)
{
    extern __shared__ __align__(1024) uint8_t smem_raw[];
    const uint32_t sm = (uint32_t)__cvta_generic_to_shared(smem_raw);
    const uint32_t bars = sm + SM_BAR;
    const int tid = threadIdx.x, warp = __shfl_sync(0xFFFFFFFFu, tid >> 5, 0), lane = tid & 31;
    const int g = lane >> 2, q = lane & 3;
    const int c = blockIdx.x, rank = c & 1, G = c >> 1;

    if (lane == 0 && warp >= 8) {
        const int v = warp - 8;
        mbar_init(bars + (B_STG + v) * 8, 1);
        mbar_init(bars + (B_EMPTY + v) * 8, 4);
        mbar_init(bars + (B_FULL + v) * 8, 1);
        mbar_init(bars + (B_MISC + v) * 8, v == 1 ? 2 : 1);
        mbar_expect(bars + (B_STG + v) * 8, 4096);
        if (v < DEPTH) mbar_expect(bars + (B_FULL + v) * 8, 8192);
        if (v != 1) mbar_expect(bars + (B_MISC + v) * 8, v <= 2 ? 64 : v == 3 ? 1024 : 65536);
        asm volatile("fence.mbarrier_init.release.cluster;" ::: "memory");
    }
    __syncwarp();
    cluster_arrive();

    if (warp < 8) {
        TSL(32);
        const int ch = c * 8 + warp;
        const uint2 lar4 = __ldg(reinterpret_cast<const uint2*>(p.lar + ch * 128) + lane);
        const uint2 aim4 = __ldg(reinterpret_cast<const uint2*>(p.aim + ch * 128) + lane);
        const uint2 cr4 = __ldg(reinterpret_cast<const uint2*>(p.cr + ch * 128) + lane);
        const uint2 ci4 = __ldg(reinterpret_cast<const uint2*>(p.ci + ch * 128) + lane);
        uint32_t ldt_raw, dsk_raw;
        asm volatile("ld.global.nc.u16 %0, [%1];" : "=r"(ldt_raw) : "l"(p.logdt + ch));
        asm volatile("ld.global.nc.u16 %0, [%1];" : "=r"(dsk_raw) : "l"(p.dskip + ch));
        const float logdt = blo(ldt_raw), dsk = blo(dsk_raw);
        const uint32_t wb = sm + SM_WB + warp * WB_SZ;
        const uint32_t ub = sm + SM_U + warp * U_SZ;
        if (lane < 16) sts128(ub + (lane >> 3) * U_HI + (lane & 7) * 16, 0, 0, 0, 0);
        sth(wb + lane * 4, hc{0x3C003C00u, 0u});

        const float dt = rb(expf(logdt));
        float outscale, cs, dn;
        {
            uint32_t m0 = __vmaxu2(__vmaxu2(cr4.x & 0x7FFF7FFFu, cr4.y & 0x7FFF7FFFu), __vmaxu2(ci4.x & 0x7FFF7FFFu, ci4.y & 0x7FFF7FFFu));
            uint32_t m1 = max(m0 & 0xFFFFu, m0 >> 16);
            float cmax = blo(__reduce_max_sync(0xFFFFFFFFu, m1));
            const float sc = fminf(fmaxf(fmaxf(2.0f * dt * cmax, fabsf(dsk) * (1.0f / 1024.0f)), 1e-30f), 1e30f);
            outscale = __uint_as_float(__float_as_uint(sc) & 0x7F800000u);
            const float inv = __uint_as_float(0x7F000000u - __float_as_uint(outscale));
            cs = 2.0f * dt * inv;
            dn = dsk * inv;
        }
        TSL(0);
        if (warp == TSW) TSL(39);
        float kacc[2][3][4];
#pragma unroll
        for (int i = 0; i < 2; i++)
#pragma unroll
            for (int j = 0; j < 3; j++) kacc[i][j][0] = kacc[i][j][1] = kacc[i][j][2] = kacc[i][j][3] = 0.f;
        if (lane == 0) kacc[0][0][0] = dn;
        {
            const uint32_t st = wb + lane * 4;
            const uint32_t zk = lds32(wb + 128);
            const uint32_t la = wb + ((lane & 8) ? 29 : (lane & 7)) * KP + (lane >> 4) * 128;
            const uint32_t lo = wb + ((lane >> 3) & 1) * 128 + (lane >> 4) * 16;
            const uint32_t lb = lo + (8 + (lane & 7)) * KP, lb2 = lo + (24 + min(lane & 7, 4)) * KP, lm = lo + 30 * KP;
#pragma unroll 1
            for (int s = 0; s < 2; s++) {
                const uint32_t wl = s ? lar4.y : lar4.x, wa = s ? aim4.y : aim4.x, wr_ = s ? cr4.y : cr4.x, wi = s ? ci4.y : ci4.x;
                const uint32_t ea = pack_b(ex2(blo(wl) * 1.4426950408889634f), ex2(bhi(wl) * 1.4426950408889634f));
                const float a2[2] = {-(blo(ea) * dt) * 1.4426950408889634f, -(bhi(ea) * dt) * 1.4426950408889634f};
                const float b[2] = {blo(wa) * dt, bhi(wa) * dt};
                {
                    cf z8[2], z16[2], z32[2], z64[2], z128[2];
#pragma unroll
                    for (int e = 0; e < 2; e++) {
                        z8[e] = cexp_(a2[e] * 8.f, b[e] * 8.f);
                        z16[e] = csq(z8[e]); z32[e] = csq(z16[e]); z64[e] = csq(z32[e]); z128[e] = csq(z64[e]);
                    }
                    const hc r1 = pk(z8[0], z8[1]), r2 = pk(z16[0], z16[1]), r3 = hmulc(r1, r2), r4 = pk(z32[0], z32[1]);
                    sth(st + 1 * KP, r1); sth(st + 2 * KP, r2); sth(st + 3 * KP, r3); sth(st + 4 * KP, r4);
                    sth(st + 5 * KP, hmulc(r1, r4)); sth(st + 6 * KP, hmulc(r2, r4)); sth(st + 7 * KP, hmulc(r3, r4));
                    sth(st + 29 * KP, pk(z64[0], z64[1])); sth(st + 30 * KP, pk(z128[0], z128[1]));
                }
                {
                    cf C[2], z2[2], z4[2], v2[2], v4[2], c1[2], d1[2];
#pragma unroll
                    for (int e = 0; e < 2; e++) {
                        C[e] = {(e ? bhi(wr_) : blo(wr_)) * cs, (e ? bhi(wi) : blo(wi)) * -cs};
                        const cf z = cexp_(a2[e], -b[e]);
                        const cf v = cexp_(a2[e] * 256.f, b[e] * -256.f);
                        z2[e] = csq(z); z4[e] = csq(z2[e]); v2[e] = csq(v); v4[e] = csq(v2[e]);
                        c1[e] = cmul(C[e], z); d1[e] = cmul(C[e], v);
                    }
                    const hc l0 = pk(C[0], C[1]), l1 = pk(c1[0], c1[1]), e1 = pk(d1[0], d1[1]);
                    const hc h = pk(z2[0], z2[1]), f = pk(z4[0], z4[1]), w = pk(v2[0], v2[1]), y = pk(v4[0], v4[1]);
                    const hc l2 = hmulc(l0, h), l3 = hmulc(l1, h), e2 = hmulc(l0, w), e3 = hmulc(e1, w), e4 = hmulc(l0, y), g2 = hmulc(e1, h);
                    sth(st + 8 * KP, l0); sth(st + 9 * KP, l1); sth(st + 10 * KP, l2); sth(st + 11 * KP, l3);
                    sth(st + 12 * KP, hmulc(l0, f)); sth(st + 13 * KP, hmulc(l1, f)); sth(st + 14 * KP, hmulc(l2, f)); sth(st + 15 * KP, hmulc(l3, f));
                    sth(st + 16 * KP, e1);
                    sth(st + 17 * KP, g2);
                    sth(st + 18 * KP, hmulc(e1, f));
                    sth(st + 19 * KP, hmulc(g2, f));
                    sth(st + 20 * KP, e2);
                    sth(st + 21 * KP, hmulc(e2, f));
                    sth(st + 22 * KP, e3);
                    sth(st + 23 * KP, hmulc(e3, f));
                    sth(st + 24 * KP, e4);
                    sth(st + 25 * KP, hmulc(e1, y));
                    sth(st + 26 * KP, hmulc(e2, y));
                    sth(st + 27 * KP, hmulc(e3, y));
                    sth(st + 28 * KP, hmulc(e4, y));
                }
                __syncwarp();
                if (warp == TSW) TSL(s ? 34 : 27);
#pragma unroll
                for (int kp = 0; kp < 4; kp++) {
                    uint32_t bb[3][4], m2[4];
                    ldsm4(lm + kp * 32, m2[0], m2[1], m2[2], m2[3]);
                    ldsm4(lb + kp * 32, bb[0][0], bb[0][1], bb[0][2], bb[0][3]);
                    ldsm4(lb + 8 * KP + kp * 32, bb[1][0], bb[1][1], bb[1][2], bb[1][3]);
                    ldsm4(lb2 + kp * 32, bb[2][0], bb[2][1], bb[2][2], bb[2][3]);
#pragma unroll
                    for (int k2 = 0; k2 < 2; k2++) {
                        hc v0, m1;
                        ldsm4(la + kp * 32 + k2 * 16, v0.r, m1.r, v0.i, m1.i);
                        const hc mm = {m2[2 * k2], m2[2 * k2 + 1]};
                        const hc v1 = hmulc(v0, m1), v2 = hmulc(v0, mm), v3 = hmulc(v1, mm);
#pragma unroll
                        for (int nt = 0; nt < 3; nt++) {
                            mma_f16(kacc[0][nt], v0.r, v1.r, v0.i, v1.i, bb[nt][2 * k2], bb[nt][2 * k2 + 1]);
                            mma_f16(kacc[1][nt], v2.r, v3.r, v2.i, v3.i, bb[nt][2 * k2], bb[nt][2 * k2 + 1]);
                        }
                    }
                }
                __syncwarp();
                if (warp == TSW) TSL(s ? 40 : 33);
            }
        }
        TSL(1);
        const uint32_t ka = wb + 4096;
        uint32_t xb0, xb1;
        {
            sts128(ka + (lane < 2 ? lane : lane < 7 ? 63 + lane : 126 + lane) * 16, 0, 0, 0, 0);
            sts128(ka + (158 + lane) * 16, 0, 0, 0, 0);
            sts128(ka + (190 + lane) * 16, 0, 0, 0, 0);
            __syncwarp();
            uint32_t v1[4], v2[4];
#pragma unroll
            for (int m = 0; m < 4; m++) {
                v1[m] = pack_h(kacc[m >> 1][1][2 * (m & 1) + 1], kacc[m >> 1][1][2 * (m & 1)]);
                v2[m] = pack_h(kacc[m >> 1][2][2 * (m & 1)], kacc[m >> 1][2][2 * (m & 1) + 1]);
            }
            if (q < 2) {
                const uint32_t a = ka + (128 + 4 * g + 2 * q) * 4;
                const uint32_t a3 = ka + (((g & 1) ? KA_O3 : KA_E3) + 8 + 32 * q + (g >> 1)) * 4;
                const uint32_t a30 = lane == 0 ? ka + (KA_E2 + 77) * 4 : a3;
#pragma unroll
                for (int m = 0; m < 4; m++) {
                    const uint32_t ee = prmt(v1[m], 0, 0x3232);
                    sts64(a + (KA_DE + 32 * m) * 4, ee, v1[m]);
                    sts32(a + (KA_DO + 32 * m) * 4, ee);
                    sts16(a + (KA_DO + 32 * m + 1) * 4 + 2, v1[m]);
                    sts16(a + (KA_DO + 32 * m - 1) * 4, ee);
                    if (m == 0) { sts16(a30, v2[0]); sts16(a30 + (lane == 0 ? 10 : 6), v2[0]); }
                    else { sts16(a3 + m * 16, v2[m]); sts16(a3 + m * 16 + 6, v2[m]); }
                    sts16(a3 + 64 + m * 16, v2[m] >> 16); sts16(a3 + 64 + m * 16 + 6, v2[m] >> 16);
                }
            } else {
                const uint32_t a = ka + (32 * q + g - 50) * 4;
#pragma unroll
                for (int m = 0; m < 4; m++) {
                    const uint32_t ve = v1[m] >> 16;
                    sts16(a + (KA_O2 + 8 * m) * 4, v1[m]); sts16(a + (KA_O2 + 8 * m) * 4 + 10, v1[m]);
                    if (m || lane != 2) { sts16(a + (KA_E2 + 8 * m - 1) * 4, ve); sts16(a + (KA_E2 + 8 * m - 1) * 4 + 10, ve); }
                }
                if (lane == 2) {
                    const uint32_t ee = prmt(v1[0], 0, 0x3232);
                    sts64(ka + (KA_DE + 256) * 4, ee, ee);
                    sts32(ka + (KA_DO + 256) * 4, ee);
                    sts16(ka + (KA_DO + 257) * 4 + 2, ee);
                    sts16(ka + (KA_DO + 255) * 4, ee);
                    sts16(ka + (KA_E3 + 72) * 4, v2[0]);
                }
            }
            __syncwarp();
#pragma unroll
            for (int m = 0; m < 4; m++) {
                const uint32_t v0 = pack_h(kacc[m >> 1][0][2 * (m & 1) + 1], kacc[m >> 1][0][2 * (m & 1)]);
                const uint32_t a = ka + (lane + 32 * m) * 4;
                sts32(a + KA_DO * 4, v0); sts16(a + (KA_DE + 1) * 4 + 2, v0); sts16(a + KA_DE * 4, v0 >> 16);
            }
            const uint32_t vv = prmt(__shfl_sync(0xFFFFFFFFu, v2[0], 0), 0, 0x1010);
            xb0 = vv & ((band(2 * q, g + 4, g + 5) >> 10 & 0x00010001u) * 0xFFFFu);
            xb1 = vv & ((band(2 * q + 8, g + 4, g + 5) >> 10 & 0x00010001u) * 0xFFFFu);
            __syncwarp();
        }
        TSL(2);
        cluster_wait();
        const int chl = rank * 8 + warp;
        if (lane < 2) st_async1(mapa(sm + SM_SCL + chl * 4, lane), __float_as_uint(2.0f * outscale) >> 16, mapa(bars + B_KDONE * 8, lane));
        bar_sync(5, 288);
        asm volatile("setmaxnreg.inc.sync.aligned.u32 200;");
        uint32_t kb[66], q2[10][4];
        const uint32_t zr = lds32(ub);
        const uint32_t A3[4] = {pin(band(2 * q, g, g + 8)), pin(band(2 * q, g + 1, g + 7)), pin(band(2 * q + 8, g, g + 8)), pin(band(2 * q + 8, g + 1, g + 7))};
        const uint32_t A2[4] = {pin(band(2 * q, g + 5, g + 7)), pin(band(2 * q, g, g + 4)), pin(band(2 * q + 8, g + 5, g + 7)), pin(band(2 * q + 8, g, g + 4))};
        xb0 = pin(xb0); xb1 = pin(xb1);
        {
            const uint32_t tag = lds32(sm + SM_KEYS + 64);
            uint4 st[4];
            const uint4* src = p.stats + warp * 128 + lane;
#pragma unroll
            for (int i = 0; i < 4; i++) st[i] = ld_relaxed128(src + 32 * i);
            mbar_wait(bars + B_SLAB * 8, 0);
            TSL(10);
            uint32_t xt[8][4];
            const uint32_t a = sm + SM_SLAB + tid * 32 + ((rank ^ ((tid >> 2) & 1)) * 16);
#pragma unroll
            for (int pp = 0; pp < 4; pp++) {
                const uint4 e = lds128(a + (2 * pp) * 8192), o = lds128(a + (2 * pp + 1) * 8192);
                xt[0][pp] = prmt(e.x, o.x, 0x5410); xt[1][pp] = prmt(e.x, o.x, 0x7632);
                xt[2][pp] = prmt(e.y, o.y, 0x5410); xt[3][pp] = prmt(e.y, o.y, 0x7632);
                xt[4][pp] = prmt(e.z, o.z, 0x5410); xt[5][pp] = prmt(e.z, o.z, 0x7632);
                xt[6][pp] = prmt(e.w, o.w, 0x5410); xt[7][pp] = prmt(e.w, o.w, 0x7632);
            }
            const uint32_t kd = ka + (((g & 1) ? KA_DO : KA_DE) + (g >> 1) - q) * 4;
#pragma unroll
            for (int z = 0; z < 66; z++) kb[z] = lds32(kd + z * 16);
            const uint32_t k2o = ka + (KA_O2 - 50 + 2 * g - 4 * q) * 4, k2e = ka + (KA_E2 - 50 + 2 * g - 4 * q) * 4;
#pragma unroll
            for (int cc = 4; cc <= 8; cc++) {
                const uint2 o2 = lds64(k2o + cc * 64), e2 = lds64(k2e + cc * 64);
                q2[cc - 4][0] = o2.x; q2[cc - 4][1] = o2.y; q2[cc - 4][2] = e2.x; q2[cc - 4][3] = e2.y;
                q2[cc + 1][0] = lds32(k2o + cc * 64 - 4); q2[cc + 1][1] = cpy(o2.x, zr);
                q2[cc + 1][2] = lds32(k2e + cc * 64 - 4); q2[cc + 1][3] = cpy(e2.x, zr);
            }
            const uint32_t tb = ((tag & 1) << 15) | ((tag >> 1) << 31);
            int it = 0;
            TSL(7);
            while (true) {
                const uint32_t bad = ((st[0].y ^ tb) | (st[1].y ^ tb) | (st[2].y ^ tb) | (st[3].y ^ tb)) & 0x80008000u;
                if (__all_sync(0xFFFFFFFFu, bad == 0) || ++it >= SPIN_LIMIT) break;
#pragma unroll
                for (int i = 0; i < 4; i++) st[i] = ld_relaxed128(src + 32 * i);
            }
            TSL(11); TG(31);
            uint32_t h1[4], h2[4];
#pragma unroll
            for (int i = 0; i < 4; i++) {
                const uint32_t o2 = st[i].w ^ (prmt(st[i].w, 0, 0xBB99) | 0x80008000u);
                const uint32_t id = 0xFFFF - 8 * tid - 2 * i;
                const uint32_t k0 = prmt(o2, id, 0x1054), k1 = prmt(o2, id - 1, 0x3254);
                h1[i] = max(k0, k1); h2[i] = min(k0, k1);
            }
            const uint32_t a1 = max(h1[0], h1[1]), a2 = __vimax3_u32(min(h1[0], h1[1]), h2[0], h2[1]);
            const uint32_t b1 = max(h1[2], h1[3]), b2 = __vimax3_u32(min(h1[2], h1[3]), h2[2], h2[3]);
            const uint32_t k1 = max(a1, b1), k2 = __vimax3_u32(min(a1, b1), a2, b2);
            const uint32_t m1 = __reduce_max_sync(0xFFFFFFFFu, k1);
            const uint32_t m2 = __reduce_max_sync(0xFFFFFFFFu, k1 == m1 ? k2 : k1);
            if (lane == 0) sts64(sm + SM_KEYS + warp * 8, m1, m2);
            bar_arrive(3, 320);
            const uint32_t ua = sm + SM_U + (tid & 1) * U_HI + ((tid >> 1) + 8) * 16;
#pragma unroll
            for (int i = 0; i < 4; i++) { st[i].y = bmul2(st[i].y & 0x7FFF7FFFu, 0x3F003F00u); st[i].z = bmul2(st[i].z, 0x3F003F00u); }
#pragma unroll
            for (int cc = 0; cc < 8; cc++) {
                uint32_t o[4];
#pragma unroll
                for (int i = 0; i < 4; i++) { const uint32_t n = norm2(xt[cc][i], st[i].x, st[i].y, st[i].z); o[i] = pack_h(blo(n), bhi(n)); }
                sts128(ua + cc * U_SZ, o[0], o[1], o[2], o[3]);
            }
        }
        TSL(12);
        bar_sync(2, 256);
        TSL(3);

        float acc[16][4];
        {
            const uint32_t se = ub + (q < 2 ? U_HI + (g + 7) * 16 + 8 + q * 4 : (g + 8) * 16 + (q - 2) * 4);
            const uint32_t so = ub + (q < 2 ? (g + 8) * 16 + 8 + q * 4 : U_HI + (g + 8) * 16 + (q - 2) * 4);
            float a3[4][2][4];
#pragma unroll
            for (int i = 0; i < 4; i++)
#pragma unroll
                for (int j = 0; j < 2; j++) a3[i][j][0] = a3[i][j][1] = a3[i][j][2] = a3[i][j][3] = 0.f;
            const uint32_t ko = ka + (KA_O3 - 56 + g - 2 * q) * 4, ke = ka + (KA_E3 - 56 + g - 2 * q) * 4;
#pragma unroll
            for (int par = 0; par < 2; par++) {
                if (par) __syncwarp();
                uint32_t w9[4][2], w7[4][2];
#pragma unroll
                for (int yy = 0; yy < 4; yy++) {
                    const int y = 2 * yy + par;
                    const uint32_t sm1 = lds32(so + y * 128 - 16), s0 = lds32(se + y * 128), s1 = lds32(so + y * 128);
                    uint32_t t0, t1;
                    mma_h(w9[yy][0], t0, A3, s0, s1);
                    mma_h(w9[yy][1], t1, A3, sm1, cpy(s0, zr));
                    w7[yy][0] = cpy(t1, zr); w7[yy][1] = cpy(t0, zr);
                }
#pragma unroll
                for (int cc = 8 - par; cc <= 14; cc += 2) {
                    const uint32_t f0 = cc == 7 ? zr : lds32(ke + cc * 32), f1 = lds32(ke + cc * 32 + 32);
                    const uint32_t f2 = cc == 7 ? cpy(zr, zr) : lds32(ko + cc * 32), f3 = lds32(ko + cc * 32 + 32);
                    const uint32_t g0 = cc == 7 ? zr + zr : lds32(ke + cc * 32 + 4), g1 = lds32(ke + cc * 32 + 36), g2 = cpy(f2, zr), g3 = cpy(f3, zr);
#pragma unroll
                    for (int T = 4; T < 8; T++) {
                        const int y = 2 * T - cc;
                        if (y >= 0) {
                            mma_f16(a3[T - 4][0], f0, f1, f2, f3, w9[y >> 1][0], w7[y >> 1][0]);
                            mma_f16(a3[T - 4][1], g0, g1, g2, g3, w9[y >> 1][1], w7[y >> 1][1]);
                        }
                    }
                }
            }
            __syncwarp();
#pragma unroll
            for (int T = 0; T < 4; T++)
#pragma unroll
                for (int b3 = 0; b3 < 2; b3++)
#pragma unroll
                    for (int b7 = 0; b7 < 2; b7++)
                        sts64(ka + (2 * T + b7) * 512 + b3 * 8 + lane * 16, __float_as_uint(a3[T][b3][2 * b7]), __float_as_uint(a3[T][b3][2 * b7 + 1]));
        }
        TSL(4);
        {
            const uint32_t lq = ub + (lane < 8 ? U_HI - 16 : lane < 24 ? 0 : U_HI) + ((lane & 7) + 8) * 16;
            const uint32_t se = ub + (q < 1 ? U_HI + (g + 7) * 16 + 12 : (g + 8) * 16 + (q - 1) * 4);
            const uint32_t so = ub + (q < 1 ? (g + 8) * 16 + 12 : U_HI + (g + 8) * 16 + (q - 1) * 4);
            const uint32_t stg = SM_WB + chl * 256 + (((lane >> 1) ^ ((chl & 1) + 4 * (chl >> 3))) * 16) + (lane & 1) * 8;
            const uint32_t cta[2] = {mapa(sm, 0), mapa(sm, 1)};
#pragma unroll
            for (int t = 0; t < 8; t++) acc[t][0] = acc[t][1] = acc[t][2] = acc[t][3] = 0.f;
            constexpr int PF = QPF;
            constexpr int NQ = PF + FENCE_EVERY;
            uint32_t Q[NQ][4], X[4], sm1, s0, s1;
#pragma unroll
            for (int i = 0; i < PF; i++) ldsm4(lq + (i - 7) * 16, Q[i][0], Q[i][1], Q[i][2], Q[i][3]);
            mbar_wait(bars + B_KDONE * 8, 0);
            mbar_wait(bars + B_TOK * 8, 0);
            const int t0 = 0xFFFF - (lds32(sm + SM_TOK) & 0xFFFF), t1 = 0xFFFF - (lds32(sm + SM_TOK + 4) & 0xFFFF);
            const int l0 = ((t0 >> 4) & 7) * 4 + ((t0 >> 1) & 3), l1 = ((t1 >> 4) & 7) * 4 + ((t1 >> 1) & 3);
            const uint32_t tmask = (lane == l0 ? 1u << (t0 >> 7) : 0u) | (lane == l1 ? 1u << (t1 >> 7) : 0u);
            const uint32_t keep = ka + 4096 + (l0 == l1 ? 0 : lane == l0 ? -16 * (t0 >> 7) : 16 - 16 * (t1 >> 7));
            float2 ua, uc;
            TSL(5);
            if (warp == TSW) TSL(38);
#pragma unroll
            for (int k = 0; k < 16; k++) {
                uint32_t gw[2][2];
                if (k == 4 && warp == TSW) TSL(35);
                if (k == 12 && warp == TSW) TSL(36);
#pragma unroll
                for (int r = 0; r < 8; r++) {
                    const int xi = 8 * k + r;
                    const uint32_t (&A)[4] = Q[xi % NQ];
                    if (xi % FENCE_EVERY == 0) {
                        sched_fence();
#pragma unroll
                        for (int n = xi + PF; n < xi + PF + FENCE_EVERY && n < 128; n++) ldsm4(lq + (n - 7) * 16, Q[n % NQ][0], Q[n % NQ][1], Q[n % NQ][2], Q[n % NQ][3]);
                    }
                    if (r == 4 && k >= 3 && k < 15) {
                        sm1 = lds32(so + (k - 3) * 128 - 16); s0 = lds32(se + (k - 3) * 128); s1 = lds32(so + (k - 3) * 128);
                    }
                    if (r == 0 && k >= 4) {
                        mma_h(gw[0][0], gw[0][1], A2, sm1, cpy(s0, zr));
                        mma_h(gw[1][0], gw[1][1], A2, s0, s1);
                        if (k < 12) {
                            const uint4 v = lds128(ka + (k - 4) * 512 + lane * 16);
                            acc[k + 4][0] = __uint_as_float(v.x); acc[k + 4][1] = __uint_as_float(v.y);
                            acc[k + 4][2] = __uint_as_float(v.z); acc[k + 4][3] = __uint_as_float(v.w);
                            ldsm4(lq + (k - 4) * 128, X[0], X[1], X[2], X[3]);
                        }
                    }
#pragma unroll
                    for (int i = 0; i < 4; i++)
                        if (k + i < 16) mma4(acc[k + i], A, kb[16 * i + 15 - 2 * r], kb[16 * i + 14 - 2 * r]);
                    if (k >= 4 && (r == 2 || r == 4)) {
#pragma unroll
                        for (int i = 0; i < 4; i++)
                            if (k + i < 16) mma4(acc[k + i], q2[(r >> 2) * 5 + i], gw[r >> 2][0], gw[r >> 2][1]);
                    }
                    if (k >= 4 && k < 12) {
                        if (r == 4) mma4(acc[k + 4], X, xb0, xb1);
                        if (r == 5 || r == 6) mma4(acc[k + 4], q2[(r - 5) * 5 + 4], gw[r - 5][0], gw[r - 5][1]);
                    }
                    if (r == 7) {
                        if (k + 4 < 16) mma4(acc[k + 4], A, kb[65], kb[64]);
                        ua = __half22float2(*reinterpret_cast<const __half2*>(&A[2]));
                        uc = __half22float2(*reinterpret_cast<const __half2*>(&A[3]));
                    }
                    if ((k > 0 && r == EPI_R) || xi == 127) {
                        const int t = xi == 127 ? 15 : k - 1;
                        const float w0 = acc[t][0] * ua.x, w1 = acc[t][1] * ua.y, w2 = acc[t][2] * uc.x, w3 = acc[t][3] * uc.y;
                        const uint32_t pa = pack_b(fmaf(w0, tanh_(ua.x), w0), fmaf(w1, tanh_(ua.y), w1));
                        const uint32_t pb = pack_b(fmaf(w2, tanh_(uc.x), w2), fmaf(w3, tanh_(uc.y), w3));
                        st_async2(cta[t & 1] + stg + (t >> 1) * WB_SZ, pa, pb, cta[t & 1] + SM_BAR + (B_STG + (t >> 1)) * 8);
                        asm volatile("{ .reg .pred p; setp.ne.u32 p, %1, 0; @p st.shared.v4.f32 [%0], {%2,%3,%4,%5}; }"
                                     :: "r"(keep + 16 * t), "r"(tmask & (1u << t)), "f"(acc[t][0]), "f"(acc[t][1]), "f"(acc[t][2]), "f"(acc[t][3]) : "memory");
                    }
                }
            }
            if (warp == TSW) TSL(37);
            __syncwarp();
            if (lane < 2) {
                const int t = lane ? t1 : t0;
                const uint32_t v = lds32(ka + 4096 + (l0 == l1 ? t >> 7 : lane) * 16 + ((t >> 3) & 1) * 8 + (t & 1) * 4);
                const uint32_t dst = lane ? cta[1] : cta[0];
                st_async1(dst + SM_FIX + chl * 4, v, dst + SM_BAR + B_FIX * 8);
            }
        }
        TSL(6);
    } else {
        const int v = warp - 8;
        uint64_t pol = 0;
        cluster_wait();
        TSL(19);
        if (warp == 12) {
            TG(28);
            asm volatile("createpolicy.fractional.L2::evict_first.b64 %0, 1.0;" : "=l"(pol));
            if (elect()) {
                asm volatile("cp.async.bulk.tensor.3d.shared::cluster.global.mbarrier::complete_tx::bytes.multicast::cluster"
                             " [%0], [%1, {%3, %4, %5}], [%2], %6;"
                             :: "r"(sm + SM_SLAB + rank * 32768), "l"(&tm_x), "r"(bars + B_SLAB * 8), "r"(G * 16), "r"(0), "r"(4 * rank), "h"((uint16_t)3) : "memory");
                TS(18);
                if (G < 56) {
#pragma unroll 1
                    for (int n = 0; n < DEPTH; n++)
                        tma3d(sm + SM_RING + n * 8192, &tm_g, G * 64, rank * 512 + n * 32, bars + (B_FULL + n) * 8, pol);
                }
            }
            __syncwarp();
            TSL(20);
        }
        uint4* const my_stats = p.stats + (c >> 4) * 128 + (v & 3) * 32 + ((2 * c) & 31);
        uint32_t* const my_part = p.part + ((2 * (32 * rank + v) + (q & 1)) * 56 + G) * 16 + g + 8 * (q >> 1);
        if (v < 4) {
            if (lane < 2) st_relaxed128(my_stats + lane, make_uint4(0, 0, 0, 0));
            if (G < 56) {
#pragma unroll
                for (int n = 0; n < 8; n++) st_relaxed32(my_part + n * 8 * 56 * 16, 0);
            }
            bar_arrive(6 + v, 64);
        } else {
            bar_sync(2 + v, 64);
        }
        uint4 xa[4], xc[4], w4[4];
        {
            const uint4* ra = reinterpret_cast<const uint4*>(p.x + (size_t)(16 * c + 2 * v) * 1024) + lane;
#pragma unroll
            for (int k = 0; k < 4; k++) { xa[k] = ldg128(ra + 32 * k); xc[k] = ldg128(ra + 128 + 32 * k); }
#pragma unroll
            for (int k = 0; k < 4; k++) w4[k] = ldg128(reinterpret_cast<const uint4*>(p.wr) + 32 * k + lane);
        }
        uint32_t tag;
        asm volatile("ld.relaxed.gpu.global.u32 %0, [%1];" : "=r"(tag) : "l"(p.epoch) : "memory");
        tag = tag % 3 + 1;
        {
            constexpr uint32_t ONE = 0x3F803F80u;
            float sw[4] = {0, 0, 0, 0}, sA[4] = {0, 0, 0, 0}, sB[4] = {0, 0, 0, 0};
            float qA[2][4] = {{0, 0, 0, 0}, {0, 0, 0, 0}}, qB[2][4] = {{0, 0, 0, 0}, {0, 0, 0, 0}};
#pragma unroll
            for (int k = 0; k < 4; k++) mma_bf16(sw, w4[k].x, w4[k].y, w4[k].z, w4[k].w, ONE, ONE);
#pragma unroll
            for (int k = 0; k < 4; k++) {
                mma_bf16(sA, xa[k].x, xa[k].y, xa[k].z, xa[k].w, ONE, ONE);
                mma_bf16(qA[0], xa[k].x, w4[k].x, xa[k].y, w4[k].y, xa[k].x, xa[k].y);
                mma_bf16(qA[1], xa[k].z, w4[k].z, xa[k].w, w4[k].w, xa[k].z, xa[k].w);
                mma_bf16(sB, xc[k].x, xc[k].y, xc[k].z, xc[k].w, ONE, ONE);
                mma_bf16(qB[0], xc[k].x, w4[k].x, xc[k].y, w4[k].y, xc[k].x, xc[k].y);
                mma_bf16(qB[1], xc[k].z, w4[k].z, xc[k].w, w4[k].w, xc[k].z, xc[k].w);
            }
            TSL(8);
            const bool dg = q == (g >> 1), od = g & 1;
            float r0 = dg ? (od ? qA[0][1] + qA[1][1] : qA[0][0] + qA[1][0]) : 0.f;
            float r1 = dg ? (od ? qA[0][3] + qA[1][3] : qA[0][2] + qA[1][2]) : 0.f;
            float r2 = dg ? (od ? qB[0][1] + qB[1][1] : qB[0][0] + qB[1][0]) : 0.f;
            float r3 = dg ? (od ? qB[0][3] + qB[1][3] : qB[0][2] + qB[1][2]) : 0.f;
            const bool rowb = lane & 1;
            float ss = (rowb ? r2 : r0) + __shfl_xor_sync(0xFFFFFFFFu, rowb ? r0 : r2, 1);
            float dw = (rowb ? r3 : r1) + __shfl_xor_sync(0xFFFFFFFFu, rowb ? r1 : r3, 1);
            float sx = rowb ? sB[0] + sB[2] : sA[0] + sA[2];
            float ws = sw[0] + sw[2];
            ss += __shfl_xor_sync(0xFFFFFFFFu, ss, 2); dw += __shfl_xor_sync(0xFFFFFFFFu, dw, 2);
#pragma unroll
            for (int o = 4; o < 32; o <<= 1) {
                ss += __shfl_xor_sync(0xFFFFFFFFu, ss, o); dw += __shfl_xor_sync(0xFFFFFFFFu, dw, o);
                sx += __shfl_xor_sync(0xFFFFFFFFu, sx, o); ws += __shfl_xor_sync(0xFFFFFFFFu, ws, o);
            }
            const float mean = sx * (1.0f / 1024.0f);
            const float var = fmaxf(ss * (1.0f / 1024.0f) - mean * mean, 0.f);
            const float m = rb(mean);
            float sd; asm("sqrt.approx.ftz.f32 %0, %1;" : "=f"(sd) : "f"(rb(rb(var) + 1e-5f)));
            const float rs = rcp(rb(sd));
            const float hi = rb(rs);
            const uint32_t p0 = pack_b(m, hi), p1 = pack_b(rs - hi, rs * (dw - m * ws));
            const uint32_t o0 = __shfl_xor_sync(0xFFFFFFFFu, p0, 1), o1 = __shfl_xor_sync(0xFFFFFFFFu, p1, 1);
            if (lane == 0) {
                const uint32_t tb = ((tag & 1) << 15) | ((tag >> 1) << 31);
                st_relaxed128(my_stats + (v >> 2), make_uint4(prmt(p0, o0, 0x5410), (prmt(p0, o0, 0x7632) & 0x7FFF7FFFu) | tb,
                                                              prmt(p1, o1, 0x5410), prmt(p1, o1, 0x7632)));
            }
        }
        TSL(9);
        if (warp == 8) { sts32(sm + SM_KEYS + 64, tag); bar_arrive(5, 288); }
        if (warp < 12) {
            asm volatile("setmaxnreg.dec.sync.aligned.u32 56;");
            if (G < 56) {
                const uint32_t la = pin(sm + SM_RING + ((lane & 7) + 8 * (lane >> 4)) * 128 + (((2 * v + ((lane >> 3) & 1)) ^ (lane & 7)) * 16));
                const uint32_t xs = pin(sm + SM_XSEL + ((g >> 1) & 1) * XSEL_T + rank * 1024 + q * 16);
                const uint32_t hs = pin(sm + SM_H + ((g >> 1) & 1) * H_T + q * 16);
                const uint32_t hd = pin(sm + SM_H + (q & 1) * H_T + (v >> 1) * 64 + (g >> 1) * 16 + (2 * (v & 1) + (q >> 1)) * 4 + (g & 1) * 2);
                const uint32_t pr = pin(SM_PAIR + v * 256 + lane * 8), rem = mapa(sm, rank ^ 1);
                float ag[4] = {0, 0, 0, 0}, au[4] = {0, 0, 0, 0};
                mbar_wait(bars + B_TOK * 8, 0);
                TSL(13);
#pragma unroll
                for (int n = 0; n < 16; n++) {
                    const uint4 xb = lds128(xs + n * 64);
                    mbar_wait(bars + full_bar(n) * 8, full_par(n));
                    uint32_t a[4][4];
#pragma unroll
                    for (int i = 0; i < 4; i++) ldsm4t(la + (n % NSLOT) * 8192 + i * 2048, a[i][0], a[i][1], a[i][2], a[i][3]);
                    __syncwarp();
                    if (lane == 0) mbar_arrive(bars + (B_EMPTY + n % NSLOT) * 8);
                    mma_bf16(ag, a[0][0], a[0][1], a[0][2], a[0][3], xb.x, xb.y);
                    mma_bf16(au, a[2][0], a[2][1], a[2][2], a[2][3], xb.x, xb.y);
                    mma_bf16(ag, a[1][0], a[1][1], a[1][2], a[1][3], xb.z, xb.w);
                    mma_bf16(au, a[3][0], a[3][1], a[3][2], a[3][3], xb.z, xb.w);
                }
                TSL(14);
                float gs = (q & 2) ? ag[2] : ag[0], us = (q & 2) ? au[2] : au[0];
                st_async2(rem + pr, __float_as_uint(gs), __float_as_uint(us), rem + SM_BAR + B_PAIR * 8);
                mbar_wait(bars + B_PAIR * 8, 0);
                const uint2 oth = lds64(sm + pr);
                const uint32_t gu = pack_b(gs + __uint_as_float(oth.x), us + __uint_as_float(oth.y));
                gs = p.up_first ? bhi(gu) : blo(gu); us = p.up_first ? blo(gu) : bhi(gu);
                const float hv = rb(siluf_(gs)) * us;
                sts16(hd, pack_b(hv, hv));
                bar_sync(4, 128);
                const uint4 h0 = lds128(hs), h1 = lds128(hs + 64);
                TSL(15);
#pragma unroll
                for (int n = 16; n < 24; n++) {
                    mbar_wait(bars + full_bar(n) * 8, full_par(n));
                    uint32_t a[4][4];
#pragma unroll
                    for (int i = 0; i < 4; i++) ldsm4t(la + (n % NSLOT) * 8192 + i * 2048, a[i][0], a[i][1], a[i][2], a[i][3]);
                    if (n + NSLOT < 24) {
                        __syncwarp();
                        if (lane == 0) mbar_arrive(bars + (B_EMPTY + n % NSLOT) * 8);
                    }
                    float d[4] = {0, 0, 0, 0};
                    mma_bf16(d, a[0][0], a[0][1], a[0][2], a[0][3], h0.x, h0.y);
                    mma_bf16(d, a[1][0], a[1][1], a[1][2], a[1][3], h0.z, h0.w);
                    mma_bf16(d, a[2][0], a[2][1], a[2][2], a[2][3], h1.x, h1.y);
                    mma_bf16(d, a[3][0], a[3][1], a[3][2], a[3][3], h1.z, h1.w);
                    st_relaxed32(my_part + (n - 16) * 8 * 56 * 16, (__float_as_uint((q & 2) ? d[2] : d[0]) & ~3u) | tag);
                }
                TSL(16);
            }
        } else {
            asm volatile("setmaxnreg.dec.sync.aligned.u32 56;");
            if (warp == 12) {
                if (G < 56) {
                    const bool lead = elect();
#pragma unroll
                    for (int n = DEPTH; n < 24; n++) {
                        mbar_wait(bars + full_bar(n - DEPTH) * 8, full_par(n - DEPTH));
                        if (n >= NSLOT) mbar_wait(bars + (B_EMPTY + n % NSLOT) * 8, (n / NSLOT - 1) & 1);
                        if (lead) {
                            const uint32_t fb = bars + full_bar(n) * 8;
                            mbar_expect(fb, 8192);
                            if (n < 16) tma3d(sm + SM_RING + (n % NSLOT) * 8192, &tm_g, G * 64, rank * 512 + n * 32, fb, pol);
                            else tma3d(sm + SM_RING + (n % NSLOT) * 8192, &tm_d, rank * 512 + (n - 16) * 64, G * 64, fb, pol);
                        }
                    }
                    TSL(23);
                }
            } else if (warp >= 14) {
                const int sw = warp - 14;
                bar_sync(3, 320);
                const uint32_t key = lane < 16 ? lds32(sm + SM_KEYS + lane * 4) : 0u;
                const uint32_t m1 = __reduce_max_sync(0xFFFFFFFFu, key);
                const uint32_t m2 = __reduce_max_sync(0xFFFFFFFFu, key == m1 ? 0u : key);
                const int t0 = (0xFFFF - (m1 & 0xFFFF)) & 2047, t1 = (0xFFFF - (m2 & 0xFFFF)) & 2047;
                {
                    const int t = sw ? t1 : t0;
                    const uint4* row = reinterpret_cast<const uint4*>(p.x + (size_t)t * 1024) + lane;
                    uint4 xr[4];
#pragma unroll
                    for (int i = 0; i < 4; i++) xr[i] = ldg128(row + 32 * i);
                    const uint4 st = ld_relaxed128(p.stats + (t >> 8) * 128 + ((t >> 1) & 3) * 32 + ((t >> 3) & 31));
                    if (lane == 0) {
                        sts32(sm + SM_TOK + 4 * sw, ((sw ? m2 : m1) & 0xFFFF0000u) | (0xFFFF - t));
                        if (c == 0 && sw == 0) st_relaxed32(p.epoch, tag);
                    }
                    const uint32_t se = (t & 1) ? 0x3232 : 0x1010;
                    const uint32_t m = prmt(st.x, 0, se), hi = prmt(st.y, 0, se) & 0x7FFF7FFFu, lo = prmt(st.z, 0, se);
                    const uint32_t a = sm + SM_XSEL + sw * XSEL_T + (lane >> 2) * 64 + (lane & 3) * 4;
#pragma unroll
                    for (int i = 0; i < 4; i++) {
                        sts32(a + i * 512, norm2(xr[i].x, m, hi, lo)); sts32(a + i * 512 + 16, norm2(xr[i].y, m, hi, lo));
                        sts32(a + i * 512 + 32, norm2(xr[i].z, m, hi, lo)); sts32(a + i * 512 + 48, norm2(xr[i].w, m, hi, lo));
                    }
                    __syncwarp();
                    if (lane == 0) mbar_arrive(bars + B_TOK * 8);
                }
                const int chl = 8 * ((lane >> 1) & 1) + 2 * (lane >> 3) + (lane & 1);
                const uint32_t la = sm + SM_WB + chl * 256 + (((8 * sw + 2 * ((lane >> 2) & 1)) ^ ((chl & 1) + 4 * (chl >> 3))) * 16);
                const int tl = 128 * rank + 64 * sw + 16 * (q >> 1) + 2 * (g >> 2) + 8 * ((g >> 1) & 1) + (g & 1);
                const uint32_t xa0 = sm + SM_SLAB + (tl & 7) * 8192 + (tl >> 3) * 32 + (q & 1) * 16;
                __nv_bfloat16* const op = p.out + (size_t)tl * 1024 + G * 16 + (q & 1) * 8;
                mbar_wait(bars + B_KDONE * 8, 0);
                uint32_t sc[4];
                {
                    const uint4 s0 = lds128(sm + SM_SCL + (q & 1) * 32), s1 = lds128(sm + SM_SCL + (q & 1) * 32 + 16);
                    sc[0] = prmt(s0.x, s0.y, 0x5410); sc[1] = prmt(s0.z, s0.w, 0x5410); sc[2] = prmt(s1.x, s1.y, 0x5410); sc[3] = prmt(s1.z, s1.w, 0x5410);
                }
                uint32_t skip = 0;
#pragma unroll
                for (int k = 0; k < 2; k++) {
                    const int d = (k ? t1 : t0) - tl;
                    if ((d & ~0x724) == 0) skip |= 1u << ((d >> 8) * 4 + ((d >> 5) & 1) * 2 + ((d >> 2) & 1));
                }
                const uint32_t lb[4] = {pin(la), pin(la ^ 16), pin(la ^ 64), pin(la ^ 80)}, xb[2] = {pin(xa0), pin(xa0 ^ 144)};
#pragma unroll
                for (int s = 0; s < 8; s++) {
                    uint4 xv[4];
#pragma unroll
                    for (int i = 0; i < 4; i++) xv[i] = lds128(xb[i >> 1] + s * 1024 + (i & 1) * 4 * 8192);
                    mbar_wait(bars + (B_STG + s) * 8, 0);
#pragma unroll
                    for (int i = 0; i < 4; i++) {
                        uint32_t a[4];
                        ldsm4t(lb[i] + s * WB_SZ, a[0], a[1], a[2], a[3]);
                        asm volatile("{ .reg .pred p; setp.eq.u32 p, %5, 0; @p st.global.v4.u32 [%0], {%1,%2,%3,%4}; }"
                                     :: "l"(op + (size_t)(256 * s + (i & 1) * 4 + (i >> 1) * 32) * 1024),
                                        "r"(bfma2(a[0], sc[0], xv[i].x)), "r"(bfma2(a[1], sc[1], xv[i].y)),
                                        "r"(bfma2(a[2], sc[2], xv[i].z)), "r"(bfma2(a[3], sc[3], xv[i].w)), "r"(skip & (1u << (4 * s + i))) : "memory");
                    }
                }
                TSL(17); TG(30);
            } else {
                mbar_wait(bars + B_TOK * 8, 0);
                const uint32_t key = lds32(sm + SM_TOK + 4 * rank);
                const int t = 0xFFFF - (key & 0xFFFF);
                const int col = 4 * q + 2 * (lane >> 4) + ((lane >> 3) & 1), d = G * 16 + col;
                const float r = __uint_as_float((key & 0x80000000u) ? (key & 0x7FFF0000u) : (~key & 0xFFFF0000u));
                const float sg = rb(sigmoidf_(r));
                const float xn = blo(lds16(sm + SM_XSEL + rank * XSEL_T + (d >> 5) * 64 + ((d >> 1) & 3) * 16 + ((d >> 3) & 3) * 4 + (d & 1) * 2));
                mbar_wait(bars + B_KDONE * 8, 0);
                const float scl = blo(lds32(sm + SM_SCL + col * 4));
                const float xv = blo(lds16(sm + SM_SLAB + (t & 7) * 8192 + (t >> 3) * 32 + (((col >> 3) ^ ((t >> 5) & 1)) * 16) + (col & 7) * 2));
                mbar_wait(bars + (G < 56 ? full_bar(23) : B_FIX) * 8, 0);
                TSL(24);
                const uint4* src = reinterpret_cast<const uint4*>(p.part) + c * 224 + lane;
                float s0 = 0, s1 = 0, s2 = 0, s3 = 0;
                {
                    uint4 pv[7];
                    int it = 0;
                    bool ok;
                    do {
                        uint32_t bad = 0;
#pragma unroll
                        for (int i = 0; i < 7; i++) pv[i] = ld_relaxed128(src + 32 * i);
#pragma unroll
                        for (int i = 0; i < 7; i++) bad |= (pv[i].x ^ tag) | (pv[i].y ^ tag) | (pv[i].z ^ tag) | (pv[i].w ^ tag);
                        ok = __all_sync(0xFFFFFFFFu, (bad & 3) == 0);
                    } while (!ok && ++it < SPIN_LIMIT);
#pragma unroll
                    for (int i = 0; i < 7; i++) {
                        s0 += __uint_as_float(pv[i].x); s1 += __uint_as_float(pv[i].y); s2 += __uint_as_float(pv[i].z); s3 += __uint_as_float(pv[i].w);
                    }
                }
                TSL(25);
                const bool u16 = lane & 16, u8 = lane & 8;
                const float y0 = (u16 ? s2 : s0) + __shfl_xor_sync(0xFFFFFFFFu, u16 ? s0 : s2, 16);
                const float y1 = (u16 ? s3 : s1) + __shfl_xor_sync(0xFFFFFFFFu, u16 ? s1 : s3, 16);
                float y = (u8 ? y1 : y0) + __shfl_xor_sync(0xFFFFFFFFu, u8 ? y0 : y1, 8);
                y += __shfl_xor_sync(0xFFFFFFFFu, y, 4);
                const float z = rb(xn + rb(rb(y) * sg));
                const float gt = rb(siluf_(z));
                mbar_wait(bars + B_FIX * 8, 0);
                const float o = xv + rb(rb(__uint_as_float(lds32(sm + SM_FIX + col * 4)) * scl) * gt);
                if (!(lane & 4)) p.out[(size_t)t * 1024 + d] = __float2bfloat16(o);
                TSL(26); TG(29);
            }
        }
    }
}

typedef CUresult (*EncodeFn)(CUtensorMap*, CUtensorMapDataType, cuuint32_t, void*, const cuuint64_t*, const cuuint64_t*,
                             const cuuint32_t*, const cuuint32_t*, CUtensorMapInterleave, CUtensorMapSwizzle,
                             CUtensorMapL2promotion, CUtensorMapFloatOOBfill);

}

extern "C" void kernel_launch(void* const* d_in, const int* in_sizes, int n_in, void* d_out, int out_size) {
    Params p;
    p.x = (const __nv_bfloat16*)d_in[0];
    p.lar = (const __nv_bfloat16*)d_in[1];
    p.aim = (const __nv_bfloat16*)d_in[2];
    p.cr = (const __nv_bfloat16*)d_in[3];
    p.ci = (const __nv_bfloat16*)d_in[4];
    p.logdt = (const __nv_bfloat16*)d_in[5];
    p.dskip = (const __nv_bfloat16*)d_in[6];
    p.wr = (const __nv_bfloat16*)d_in[8];
    p.out = (__nv_bfloat16*)d_out;
    cudaGetSymbolAddress((void**)&p.stats, g_stats);
    cudaGetSymbolAddress((void**)&p.part, g_part);
    cudaGetSymbolAddress((void**)&p.epoch, g_epoch);

    void* fn = nullptr;
    cudaDriverEntryPointQueryResult qr;
    cudaGetDriverEntryPoint("cuTensorMapEncodeTiled", &fn, cudaEnableDefault, &qr);
    EncodeFn enc = (EncodeFn)fn;
    CUtensorMap tm_x, tm_g, tm_d;
    const cuuint32_t es[3] = {1, 1, 1};
    {
        const cuuint64_t gd[3] = {1024, 256, 8}, gs[2] = {16384, 2048};
        const cuuint32_t bx[3] = {16, 256, 4};
        enc(&tm_x, CU_TENSOR_MAP_DATA_TYPE_BFLOAT16, 3, d_in[0], gd, gs, bx, es, CU_TENSOR_MAP_INTERLEAVE_NONE,
            CU_TENSOR_MAP_SWIZZLE_32B, CU_TENSOR_MAP_L2_PROMOTION_NONE, CU_TENSOR_MAP_FLOAT_OOB_FILL_NONE);
    }
    {
        char *wg = (char*)d_in[9], *wu = (char*)d_in[10];
        p.up_first = wu < wg;
        const cuuint64_t gd[3] = {3584, 1024, 2}, gs[2] = {7168, (cuuint64_t)(p.up_first ? wg - wu : wu - wg)};
        const cuuint32_t bx[3] = {64, 32, 2};
        enc(&tm_g, CU_TENSOR_MAP_DATA_TYPE_BFLOAT16, 3, p.up_first ? wu : wg, gd, gs, bx, es, CU_TENSOR_MAP_INTERLEAVE_NONE,
            CU_TENSOR_MAP_SWIZZLE_128B, CU_TENSOR_MAP_L2_PROMOTION_NONE, CU_TENSOR_MAP_FLOAT_OOB_FILL_NONE);
    }
    {
        const cuuint64_t gd[3] = {1024, 3584, 1}, gs[2] = {2048, 2048 * 3584};
        const cuuint32_t bx[3] = {64, 64, 1};
        enc(&tm_d, CU_TENSOR_MAP_DATA_TYPE_BFLOAT16, 3, d_in[11], gd, gs, bx, es, CU_TENSOR_MAP_INTERLEAVE_NONE,
            CU_TENSOR_MAP_SWIZZLE_128B, CU_TENSOR_MAP_L2_PROMOTION_NONE, CU_TENSOR_MAP_FLOAT_OOB_FILL_NONE);
    }
    cudaFuncSetAttribute(fused_kernel, cudaFuncAttributeMaxDynamicSharedMemorySize, SM_TOTAL);
    fused_kernel<<<128, NTHREADS, SM_TOTAL>>>(p, tm_x, tm_g, tm_d);
}
```

```cpp
#include <cuda_runtime.h>
#include <cuda.h>
#include <cuda_bf16.h>
#include <cuda_fp16.h>
#include <stdint.h>

#define TG(i)
#define TS(i)
#define TSL(i)

#define TSW 0
#define NSLOT 6
#define DEPTH 4

namespace {

constexpr int NTHREADS = 512;
constexpr int SPIN_LIMIT = 1 << 16;

constexpr int SM_SLAB = 0;
constexpr int SM_RING = 65536;
constexpr int SM_F2   = SM_RING + NSLOT * 8192;
constexpr int SM_CH   = SM_F2 + 6144;
constexpr int SUB     = 1056;
constexpr int CH_SZ   = 12 * SUB;
constexpr int SM_XSEL = SM_CH + 8 * CH_SZ;
constexpr int SM_PAIR = SM_XSEL + 4096;
constexpr int SM_H    = SM_PAIR + 2048;
constexpr int SM_KEYS = SM_H + 1024;
constexpr int SM_TOK  = SM_KEYS + 64;
constexpr int SM_FIX  = SM_TOK + 16;
constexpr int SM_XRAW = SM_FIX + 32;
constexpr int SM_SCL  = SM_XRAW + 32;
constexpr int SM_BAR  = SM_SCL + 16;
constexpr int B_FULL = 0, B_EMPTY = 8, B_STG = 16, B_MISC = 24, NBAR = 32;
constexpr int B_PEER = B_MISC, B_TOK = B_MISC + 1, B_FIX = B_MISC + 2, B_PAIR = B_MISC + 3, B_SLAB = B_MISC + 4;
constexpr int SM_TOTAL = SM_BAR + NBAR * 8;
static_assert(SM_TOTAL <= 232448 && NSLOT < 8 && DEPTH + 2 <= NSLOT, "smem");
__host__ __device__ constexpr int full_bar(int n) { return B_FULL + (n == 23 ? 7 : n % NSLOT); }
__host__ __device__ constexpr int full_par(int n) { return n == 23 ? 0 : (n / NSLOT) & 1; }
constexpr int KP = 272;

struct Scratch {
    uint4 stats[1024];
    uint32_t part[128 * 56 * 16];
    uint32_t epoch;
};
__device__ Scratch g_scratch;

struct Params {
    const __nv_bfloat16 *lar, *aim, *cr, *ci, *logdt, *dskip;
    const __nv_bfloat16 *x, *wr;
    __nv_bfloat16* out;
    Scratch* sc;
    const uint4* tab;
    int up_first;
};

__device__ __forceinline__ uint4 ldg128(const void* p) {
    uint4 v; asm volatile("ld.global.nc.v4.u32 {%0,%1,%2,%3}, [%4];" : "=r"(v.x), "=r"(v.y), "=r"(v.z), "=r"(v.w) : "l"(p)); return v;
}
__device__ __forceinline__ uint4 ld_relaxed128(const void* p) {
    uint4 v;
    asm volatile("{ .reg .b128 t; ld.relaxed.gpu.global.b128 t, [%4]; mov.b128 {%0,%1,%2,%3}, t; }"
                 : "=r"(v.x), "=r"(v.y), "=r"(v.z), "=r"(v.w) : "l"(p) : "memory");
    return v;
}
__device__ __forceinline__ void st_relaxed128(void* p, uint4 v) {
    asm volatile("{ .reg .b128 t; mov.b128 t, {%1,%2,%3,%4}; st.relaxed.gpu.global.b128 [%0], t; }"
                 :: "l"(p), "r"(v.x), "r"(v.y), "r"(v.z), "r"(v.w) : "memory");
}
__device__ __forceinline__ void st_relaxed32(void* p, uint32_t v) {
    asm volatile("st.relaxed.gpu.global.u32 [%0], %1;" :: "l"(p), "r"(v) : "memory");
}
__device__ __forceinline__ uint32_t lds32(uint32_t a) { uint32_t v; asm volatile("ld.shared.u32 %0, [%1];" : "=r"(v) : "r"(a)); return v; }
__device__ __forceinline__ uint32_t lds16(uint32_t a) { uint32_t v; asm volatile("ld.shared.u16 %0, [%1];" : "=r"(v) : "r"(a)); return v; }
__device__ __forceinline__ uint2 lds64(uint32_t a) { uint2 v; asm volatile("ld.shared.v2.u32 {%0,%1}, [%2];" : "=r"(v.x), "=r"(v.y) : "r"(a)); return v; }
__device__ __forceinline__ uint4 lds128(uint32_t a) {
    uint4 v; asm volatile("ld.shared.v4.u32 {%0,%1,%2,%3}, [%4];" : "=r"(v.x), "=r"(v.y), "=r"(v.z), "=r"(v.w) : "r"(a)); return v;
}
__device__ __forceinline__ void sts16(uint32_t a, uint32_t v) { asm volatile("st.shared.u16 [%0], %1;" :: "r"(a), "h"((uint16_t)v) : "memory"); }
__device__ __forceinline__ void sts32(uint32_t a, uint32_t v) { asm volatile("st.shared.u32 [%0], %1;" :: "r"(a), "r"(v) : "memory"); }
__device__ __forceinline__ void sts64(uint32_t a, uint32_t x, uint32_t y) { asm volatile("st.shared.v2.u32 [%0], {%1,%2};" :: "r"(a), "r"(x), "r"(y) : "memory"); }
__device__ __forceinline__ void sts128(uint32_t a, uint32_t x, uint32_t y, uint32_t z, uint32_t w) {
    asm volatile("st.shared.v4.u32 [%0], {%1,%2,%3,%4};" :: "r"(a), "r"(x), "r"(y), "r"(z), "r"(w) : "memory");
}
__device__ __forceinline__ void ldsm4(uint32_t a, uint32_t& r0, uint32_t& r1, uint32_t& r2, uint32_t& r3) {
    asm volatile("ldmatrix.sync.aligned.m8n8.x4.shared.b16 {%0,%1,%2,%3}, [%4];" : "=r"(r0), "=r"(r1), "=r"(r2), "=r"(r3) : "r"(a));
}
__device__ __forceinline__ void mma_f16(float (&d)[4], uint32_t a0, uint32_t a1, uint32_t a2, uint32_t a3, uint32_t b0, uint32_t b1) {
    asm("mma.sync.aligned.m16n8k16.row.col.f32.f16.f16.f32 {%0,%1,%2,%3}, {%4,%5,%6,%7}, {%8,%9}, {%0,%1,%2,%3};"
        : "+f"(d[0]), "+f"(d[1]), "+f"(d[2]), "+f"(d[3]) : "r"(a0), "r"(a1), "r"(a2), "r"(a3), "r"(b0), "r"(b1));
}
__device__ __forceinline__ void mma_bf16(float (&d)[4], uint32_t a0, uint32_t a1, uint32_t a2, uint32_t a3, uint32_t b0, uint32_t b1) {
    asm("mma.sync.aligned.m16n8k16.row.col.f32.bf16.bf16.f32 {%0,%1,%2,%3}, {%4,%5,%6,%7}, {%8,%9}, {%0,%1,%2,%3};"
        : "+f"(d[0]), "+f"(d[1]), "+f"(d[2]), "+f"(d[3]) : "r"(a0), "r"(a1), "r"(a2), "r"(a3), "r"(b0), "r"(b1));
}
__device__ __forceinline__ uint32_t prmt(uint32_t a, uint32_t b, uint32_t s) { uint32_t d; asm("prmt.b32 %0, %1, %2, %3;" : "=r"(d) : "r"(a), "r"(b), "r"(s)); return d; }
__device__ __forceinline__ uint32_t pack_h(float lo, float hi) { uint32_t d; asm("cvt.rn.f16x2.f32 %0, %1, %2;" : "=r"(d) : "f"(hi), "f"(lo)); return d; }
__device__ __forceinline__ uint32_t pack_b(float lo, float hi) { uint32_t d; asm("cvt.rn.bf16x2.f32 %0, %1, %2;" : "=r"(d) : "f"(hi), "f"(lo)); return d; }
__device__ __forceinline__ float blo(uint32_t v) { return __uint_as_float(v << 16); }
__device__ __forceinline__ float bhi(uint32_t v) { return __uint_as_float(v & 0xFFFF0000u); }
__device__ __forceinline__ float rb(float v) { return blo(pack_b(v, v)); }
__device__ __forceinline__ uint32_t bsub2(uint32_t a, uint32_t b) { uint32_t d; asm("sub.rn.bf16x2 %0, %1, %2;" : "=r"(d) : "r"(a), "r"(b)); return d; }
__device__ __forceinline__ uint32_t bmul2(uint32_t a, uint32_t b) { uint32_t d; asm("mul.rn.bf16x2 %0, %1, %2;" : "=r"(d) : "r"(a), "r"(b)); return d; }
__device__ __forceinline__ uint32_t bfma2(uint32_t a, uint32_t b, uint32_t c) { uint32_t d; asm("fma.rn.bf16x2 %0, %1, %2, %3;" : "=r"(d) : "r"(a), "r"(b), "r"(c)); return d; }
__device__ __forceinline__ uint32_t norm2(uint32_t x, uint32_t m, uint32_t hi, uint32_t lo) {
    uint32_t a = bsub2(x, m);
    return bfma2(a, hi, bmul2(a, lo));
}
__device__ __forceinline__ float ex2(float v) { float d; asm("ex2.approx.ftz.f32 %0, %1;" : "=f"(d) : "f"(v)); return d; }
__device__ __forceinline__ float rcp(float v) { float d; asm("rcp.approx.ftz.f32 %0, %1;" : "=f"(d) : "f"(v)); return d; }
__device__ __forceinline__ float sigmoidf_(float v) { return rcp(1.0f + ex2(-1.4426950408889634f * v)); }
__device__ __forceinline__ float siluf_(float v) { return v * sigmoidf_(v); }

__device__ __forceinline__ void mbar_init(uint32_t a, int n) { asm volatile("mbarrier.init.shared::cta.b64 [%0], %1;" :: "r"(a), "r"(n) : "memory"); }
__device__ __forceinline__ void mbar_expect(uint32_t a, int tx) { asm volatile("mbarrier.arrive.expect_tx.shared::cta.b64 _, [%0], %1;" :: "r"(a), "r"(tx) : "memory"); }
__device__ __forceinline__ void mbar_arrive(uint32_t a) { asm volatile("mbarrier.arrive.shared::cta.b64 _, [%0];" :: "r"(a) : "memory"); }
__device__ __forceinline__ void mbar_wait(uint32_t a, int parity) {
    asm volatile("{ .reg .pred p;\n"
                 "W: mbarrier.try_wait.parity.shared::cta.b64 p, [%0], %1;\n"
                 "@!p bra.uni W; }" :: "r"(a), "r"(parity) : "memory");
}
__device__ __forceinline__ uint32_t mapa(uint32_t a, uint32_t rank) { uint32_t d; asm("mapa.shared::cluster.u32 %0, %1, %2;" : "=r"(d) : "r"(a), "r"(rank)); return d; }
__device__ __forceinline__ void st_async4(uint32_t a, uint32_t x, uint32_t y, uint32_t z, uint32_t w, uint32_t bar) {
    asm volatile("st.async.weak.shared::cluster.mbarrier::complete_tx::bytes.v4.b32 [%0], {%1,%2,%3,%4}, [%5];"
                 :: "r"(a), "r"(x), "r"(y), "r"(z), "r"(w), "r"(bar) : "memory");
}
__device__ __forceinline__ void stsm4(uint32_t a, uint32_t r0, uint32_t r1, uint32_t r2, uint32_t r3) {
    asm volatile("stmatrix.sync.aligned.m8n8.x4.shared.b16 [%0], {%1,%2,%3,%4};" :: "r"(a), "r"(r0), "r"(r1), "r"(r2), "r"(r3) : "memory");
}
__device__ __forceinline__ void proxy_fence() { asm volatile("fence.proxy.async.shared::cta;" ::: "memory"); }
__device__ __forceinline__ void bar_sync(int id, int n) { asm volatile("bar.sync %0, %1;" :: "r"(id), "r"(n) : "memory"); }
__device__ __forceinline__ void bar_arrive(int id, int n) { asm volatile("bar.arrive %0, %1;" :: "r"(id), "r"(n) : "memory"); }
__device__ __forceinline__ void cluster_arrive() { asm volatile("barrier.cluster.arrive.relaxed.aligned;" ::: "memory"); }
__device__ __forceinline__ void cluster_wait() { asm volatile("barrier.cluster.wait.aligned;" ::: "memory"); }
__device__ __forceinline__ void tma3d(uint32_t dst, const CUtensorMap* tm, int c0, int c1, uint32_t bar, uint64_t pol) {
    asm volatile("cp.async.bulk.tensor.3d.shared::cluster.global.mbarrier::complete_tx::bytes.L2::cache_hint [%0], [%1, {%3, %4, %6}], [%2], %5;"
                 :: "r"(dst), "l"(tm), "r"(bar), "r"(c0), "r"(c1), "l"(pol), "r"(0) : "memory");
}
__device__ __forceinline__ bool elect() {
    uint32_t p; asm volatile("{ .reg .pred p; elect.sync _|p, 0xFFFFFFFF; selp.u32 %0, 1, 0, p; }" : "=r"(p)); return p;
}

struct cf { float r, i; };
__device__ __forceinline__ cf cmul(cf a, cf b) { return {a.r * b.r - a.i * b.i, a.r * b.i + a.i * b.r}; }
__device__ __forceinline__ cf csq(cf a) { return {a.r * a.r - a.i * a.i, (a.r + a.r) * a.i}; }
__device__ __forceinline__ cf cexp_(float a2, float b) { float m = ex2(a2); return {m * __cosf(b), m * __sinf(b)}; }
struct hc { uint32_t r, i; };
__device__ __forceinline__ hc pk(cf a, cf b) { return {pack_h(a.r, b.r), pack_h(a.i, b.i)}; }
__device__ __forceinline__ hc hmulc(hc a, hc b) {
    const __half2 ar = *reinterpret_cast<__half2*>(&a.r), ai = *reinterpret_cast<__half2*>(&a.i);
    const __half2 br = *reinterpret_cast<__half2*>(&b.r), bi = *reinterpret_cast<__half2*>(&b.i);
    const __half2 r = __hfma2(ar, br, __hneg2(__hmul2_rn(ai, bi))), i = __hfma2(ar, bi, __hmul2_rn(ai, br));
    return {*reinterpret_cast<const uint32_t*>(&r), *reinterpret_cast<const uint32_t*>(&i)};
}
__device__ __forceinline__ void sth(uint32_t a, hc v) { sts32(a, v.r); sts32(a + 128, v.i); }
__device__ __forceinline__ uint32_t cpy(uint32_t v, uint32_t z) { uint32_t d; asm("xor.b32 %0, %1, %2;" : "=r"(d) : "r"(v), "r"(z)); return d; }
__device__ __forceinline__ void sched_fence() { asm volatile("pmevent 0;" ::: "memory"); }
__device__ __forceinline__ float tanh_(float v) { float d; asm("tanh.approx.f32 %0, %1;" : "=f"(d) : "f"(v)); return d; }
__device__ __forceinline__ float silu2(float h) {
    return h * rcp(fmaf(ex2(-2.8853900817779268f * h), 0.5f, 0.5f));
}
__device__ __forceinline__ uint32_t hfma2_(uint32_t a, uint32_t b, uint32_t c) { uint32_t d; asm("fma.rn.f16x2 %0, %1, %2, %3;" : "=r"(d) : "r"(a), "r"(b), "r"(c)); return d; }
__device__ __forceinline__ uint32_t hfms2_(uint32_t a, uint32_t b, uint32_t c) {
    uint32_t d; asm("{ .reg .b32 t; neg.f16x2 t, %1; fma.rn.f16x2 %0, t, %2, %3; }" : "=r"(d) : "r"(a), "r"(b), "r"(c)); return d;
}

__device__ __forceinline__ uint64_t bdesc(uint32_t addr, uint32_t sbo) {
    return (uint64_t)((addr & 0x3FFFFu) >> 4) | ((uint64_t)(128 >> 4) << 16) | ((uint64_t)(sbo >> 4) << 32);
}
__device__ __forceinline__ void wg_h(uint32_t (&d)[16], const uint32_t* a, const uint32_t* b, uint64_t d0, uint64_t d1, uint64_t d2, uint64_t d3) {
    asm volatile(
        "wgmma.mma_async.sync.aligned.m64n64k16.f16.f16.f16 {%0,%1,%2,%3,%4,%5,%6,%7,%8,%9,%10,%11,%12,%13,%14,%15}, {%16,%17,%18,%19}, %32, 0, 1, 1, 1;\n"
        "wgmma.mma_async.sync.aligned.m64n64k16.f16.f16.f16 {%0,%1,%2,%3,%4,%5,%6,%7,%8,%9,%10,%11,%12,%13,%14,%15}, {%20,%21,%22,%23}, %33, 1, 1, 1, 1;\n"
        "wgmma.mma_async.sync.aligned.m64n64k16.f16.f16.f16 {%0,%1,%2,%3,%4,%5,%6,%7,%8,%9,%10,%11,%12,%13,%14,%15}, {%24,%25,%26,%27}, %34, 1, 1, 1, 1;\n"
        "wgmma.mma_async.sync.aligned.m64n64k16.f16.f16.f16 {%0,%1,%2,%3,%4,%5,%6,%7,%8,%9,%10,%11,%12,%13,%14,%15}, {%28,%29,%30,%31}, %35, 1, 1, 1, 1;\n"
        : "=r"(d[0]), "=r"(d[1]), "=r"(d[2]), "=r"(d[3]), "=r"(d[4]), "=r"(d[5]), "=r"(d[6]), "=r"(d[7]), "=r"(d[8]), "=r"(d[9]), "=r"(d[10]), "=r"(d[11]), "=r"(d[12]), "=r"(d[13]), "=r"(d[14]), "=r"(d[15])
        : "r"(a[0]), "r"(a[1]), "r"(a[2]), "r"(a[3]), "r"(a[4]), "r"(a[5]), "r"(a[6]), "r"(a[7]), "r"(b[0]), "r"(b[1]), "r"(b[2]), "r"(b[3]), "r"(b[4]), "r"(b[5]), "r"(b[6]), "r"(b[7]), "l"(d0), "l"(d1), "l"(d2), "l"(d3));
}
__device__ __forceinline__ void wg_f0(float (&d)[32], const uint32_t* a, const uint32_t* b, uint64_t d0, uint64_t d1, uint64_t d2, uint64_t d3) {
    asm volatile(
        "wgmma.mma_async.sync.aligned.m64n64k16.f32.f16.f16 {%0,%1,%2,%3,%4,%5,%6,%7,%8,%9,%10,%11,%12,%13,%14,%15,%16,%17,%18,%19,%20,%21,%22,%23,%24,%25,%26,%27,%28,%29,%30,%31}, {%32,%33,%34,%35}, %48, 0, 1, 1, 1;\n"
        "wgmma.mma_async.sync.aligned.m64n64k16.f32.f16.f16 {%0,%1,%2,%3,%4,%5,%6,%7,%8,%9,%10,%11,%12,%13,%14,%15,%16,%17,%18,%19,%20,%21,%22,%23,%24,%25,%26,%27,%28,%29,%30,%31}, {%36,%37,%38,%39}, %49, 1, 1, 1, 1;\n"
        "wgmma.mma_async.sync.aligned.m64n64k16.f32.f16.f16 {%0,%1,%2,%3,%4,%5,%6,%7,%8,%9,%10,%11,%12,%13,%14,%15,%16,%17,%18,%19,%20,%21,%22,%23,%24,%25,%26,%27,%28,%29,%30,%31}, {%40,%41,%42,%43}, %50, 1, 1, 1, 1;\n"
        "wgmma.mma_async.sync.aligned.m64n64k16.f32.f16.f16 {%0,%1,%2,%3,%4,%5,%6,%7,%8,%9,%10,%11,%12,%13,%14,%15,%16,%17,%18,%19,%20,%21,%22,%23,%24,%25,%26,%27,%28,%29,%30,%31}, {%44,%45,%46,%47}, %51, 1, 1, 1, 1;\n"
        : "=f"(d[0]), "=f"(d[1]), "=f"(d[2]), "=f"(d[3]), "=f"(d[4]), "=f"(d[5]), "=f"(d[6]), "=f"(d[7]), "=f"(d[8]), "=f"(d[9]), "=f"(d[10]), "=f"(d[11]), "=f"(d[12]), "=f"(d[13]), "=f"(d[14]), "=f"(d[15]), "=f"(d[16]), "=f"(d[17]), "=f"(d[18]), "=f"(d[19]), "=f"(d[20]), "=f"(d[21]), "=f"(d[22]), "=f"(d[23]), "=f"(d[24]), "=f"(d[25]), "=f"(d[26]), "=f"(d[27]), "=f"(d[28]), "=f"(d[29]), "=f"(d[30]), "=f"(d[31])
        : "r"(a[0]), "r"(a[1]), "r"(a[2]), "r"(a[3]), "r"(a[4]), "r"(a[5]), "r"(a[6]), "r"(a[7]), "r"(b[0]), "r"(b[1]), "r"(b[2]), "r"(b[3]), "r"(b[4]), "r"(b[5]), "r"(b[6]), "r"(b[7]), "l"(d0), "l"(d1), "l"(d2), "l"(d3));
}
__device__ __forceinline__ void wg_f1(float (&d)[32], const uint32_t* a, const uint32_t* b, uint64_t d0, uint64_t d1, uint64_t d2, uint64_t d3) {
    asm volatile(
        "wgmma.mma_async.sync.aligned.m64n64k16.f32.f16.f16 {%0,%1,%2,%3,%4,%5,%6,%7,%8,%9,%10,%11,%12,%13,%14,%15,%16,%17,%18,%19,%20,%21,%22,%23,%24,%25,%26,%27,%28,%29,%30,%31}, {%32,%33,%34,%35}, %48, 1, 1, 1, 1;\n"
        "wgmma.mma_async.sync.aligned.m64n64k16.f32.f16.f16 {%0,%1,%2,%3,%4,%5,%6,%7,%8,%9,%10,%11,%12,%13,%14,%15,%16,%17,%18,%19,%20,%21,%22,%23,%24,%25,%26,%27,%28,%29,%30,%31}, {%36,%37,%38,%39}, %49, 1, 1, 1, 1;\n"
        "wgmma.mma_async.sync.aligned.m64n64k16.f32.f16.f16 {%0,%1,%2,%3,%4,%5,%6,%7,%8,%9,%10,%11,%12,%13,%14,%15,%16,%17,%18,%19,%20,%21,%22,%23,%24,%25,%26,%27,%28,%29,%30,%31}, {%40,%41,%42,%43}, %50, 1, 1, 1, 1;\n"
        "wgmma.mma_async.sync.aligned.m64n64k16.f32.f16.f16 {%0,%1,%2,%3,%4,%5,%6,%7,%8,%9,%10,%11,%12,%13,%14,%15,%16,%17,%18,%19,%20,%21,%22,%23,%24,%25,%26,%27,%28,%29,%30,%31}, {%44,%45,%46,%47}, %51, 1, 1, 1, 1;\n"
        : "+f"(d[0]), "+f"(d[1]), "+f"(d[2]), "+f"(d[3]), "+f"(d[4]), "+f"(d[5]), "+f"(d[6]), "+f"(d[7]), "+f"(d[8]), "+f"(d[9]), "+f"(d[10]), "+f"(d[11]), "+f"(d[12]), "+f"(d[13]), "+f"(d[14]), "+f"(d[15]), "+f"(d[16]), "+f"(d[17]), "+f"(d[18]), "+f"(d[19]), "+f"(d[20]), "+f"(d[21]), "+f"(d[22]), "+f"(d[23]), "+f"(d[24]), "+f"(d[25]), "+f"(d[26]), "+f"(d[27]), "+f"(d[28]), "+f"(d[29]), "+f"(d[30]), "+f"(d[31])
        : "r"(a[0]), "r"(a[1]), "r"(a[2]), "r"(a[3]), "r"(a[4]), "r"(a[5]), "r"(a[6]), "r"(a[7]), "r"(b[0]), "r"(b[1]), "r"(b[2]), "r"(b[3]), "r"(b[4]), "r"(b[5]), "r"(b[6]), "r"(b[7]), "l"(d0), "l"(d1), "l"(d2), "l"(d3));
}
template <int ACC> __device__ __forceinline__ void wg_w(float (&d)[4], uint64_t da, uint64_t db) {
    asm volatile("wgmma.mma_async.sync.aligned.m64n8k16.f32.bf16.bf16 {%0,%1,%2,%3}, %4, %5, %6, 1, 1, 1, 0;"
                 : "+f"(d[0]), "+f"(d[1]), "+f"(d[2]), "+f"(d[3]) : "l"(da), "l"(db), "n"(ACC));
}
__device__ __forceinline__ void wg_w0(float (&d)[4], uint64_t da, uint64_t db) {
    asm volatile("wgmma.mma_async.sync.aligned.m64n8k16.f32.bf16.bf16 {%0,%1,%2,%3}, %4, %5, 0, 1, 1, 1, 0;"
                 : "=f"(d[0]), "=f"(d[1]), "=f"(d[2]), "=f"(d[3]) : "l"(da), "l"(db));
}
__device__ __forceinline__ void wg_fence() { asm volatile("wgmma.fence.sync.aligned;" ::: "memory"); }
__device__ __forceinline__ void wg_commit() { asm volatile("wgmma.commit_group.sync.aligned;" ::: "memory"); }
template <int N> __device__ __forceinline__ void wg_wait() { asm volatile("wgmma.wait_group.sync.aligned %0;" :: "n"(N) : "memory"); }
__device__ __forceinline__ void touch(uint32_t& r) { asm volatile("" : "+r"(r) :: "memory"); }
__device__ __forceinline__ void touch(float& r) { asm volatile("" : "+f"(r) :: "memory"); }
template <class T, int N> __device__ __forceinline__ void touch(T (&r)[N]) {
#pragma unroll
    for (int i = 0; i < N; i++) touch(r[i]);
}

__global__ void __cluster_dims__(2, 1, 1) __launch_bounds__(NTHREADS, 1)
fused_kernel(const Params p, const __grid_constant__ CUtensorMap tm_x, const __grid_constant__ CUtensorMap tm_g,
             const __grid_constant__ CUtensorMap tm_d)
{
    extern __shared__ __align__(1024) uint8_t smem_raw[];
    const uint32_t sm = (uint32_t)__cvta_generic_to_shared(smem_raw);
    const uint32_t bars = sm + SM_BAR;
    const int tid = threadIdx.x, warp = __shfl_sync(0xFFFFFFFFu, tid >> 5, 0), lane = tid & 31;
    const int g = lane >> 2, q = lane & 3;
    const int c = blockIdx.x, rank = c & 1, G = c >> 1;

    if (lane == 0 && warp >= 8) {
        const int v = warp - 8;
        mbar_init(bars + (B_STG + v) * 8, 5);
        mbar_init(bars + (B_EMPTY + v) * 8, 4);
        mbar_init(bars + (B_FULL + v) * 8, 1);
        mbar_init(bars + (B_MISC + v) * 8, v == 1 ? 2 : 1);
        mbar_expect(bars + (B_STG + v) * 8, 4096);
        if (v < DEPTH + 2) mbar_expect(bars + (B_FULL + v) * 8, 8192);
        if (v >= 2) mbar_expect(bars + (B_MISC + v) * 8, v == 2 ? 32 : v == 3 ? 2048 : 65536 + 6144);
        asm volatile("fence.mbarrier_init.release.cluster;" ::: "memory");
    }
    __syncwarp();
    cluster_arrive();

    if (warp < 8) {
        TSL(32);
        const int ch = c * 8 + warp;
        const uint2 lar4 = __ldg(reinterpret_cast<const uint2*>(p.lar + ch * 128) + lane);
        const uint2 aim4 = __ldg(reinterpret_cast<const uint2*>(p.aim + ch * 128) + lane);
        const uint2 cr4 = __ldg(reinterpret_cast<const uint2*>(p.cr + ch * 128) + lane);
        const uint2 ci4 = __ldg(reinterpret_cast<const uint2*>(p.ci + ch * 128) + lane);
        uint32_t ldt_raw, dsk_raw;
        asm volatile("ld.global.nc.u16 %0, [%1];" : "=r"(ldt_raw) : "l"(p.logdt + ch));
        asm volatile("ld.global.nc.u16 %0, [%1];" : "=r"(dsk_raw) : "l"(p.dskip + ch));
        const float logdt = blo(ldt_raw), dsk = blo(dsk_raw);
        const uint32_t wb = sm + SM_CH + warp * CH_SZ + 4 * SUB;
        sth(wb + lane * 4, hc{0x3C003C00u, 0u});

        const float dt = rb(expf(logdt));
        float outscale, cs, dn;
        {
            uint32_t m0 = __vmaxu2(__vmaxu2(cr4.x & 0x7FFF7FFFu, cr4.y & 0x7FFF7FFFu), __vmaxu2(ci4.x & 0x7FFF7FFFu, ci4.y & 0x7FFF7FFFu));
            uint32_t m1 = max(m0 & 0xFFFFu, m0 >> 16);
            float cmax = blo(__reduce_max_sync(0xFFFFFFFFu, m1));
            const float sc = fminf(fmaxf(fmaxf(2.0f * dt * cmax, fabsf(dsk) * (1.0f / 1024.0f)), 1e-30f), 1e30f);
            outscale = __uint_as_float(__float_as_uint(sc) & 0x7F800000u);
            const float inv = __uint_as_float(0x7F000000u - __float_as_uint(outscale));
            cs = 2.0f * dt * inv;
            dn = dsk * inv;
        }
        TSL(0);
        if (warp == TSW) TSL(39);
        float kacc[2][3][4];
#pragma unroll
        for (int i = 0; i < 2; i++)
#pragma unroll
            for (int j = 0; j < 3; j++) kacc[i][j][0] = kacc[i][j][1] = kacc[i][j][2] = kacc[i][j][3] = 0.f;
        if (lane == 0) kacc[0][0][0] = dn;
        {
            const uint32_t st = wb + lane * 4;
            const uint32_t zk = lds32(wb + 128);
            const uint32_t la = wb + ((lane & 8) ? 29 : (lane & 7)) * KP + (lane >> 4) * 128;
            const uint32_t lo = wb + ((lane >> 3) & 1) * 128 + (lane >> 4) * 16;
            const uint32_t lb = lo + (8 + (lane & 7)) * KP, lb2 = lo + (24 + min(lane & 7, 4)) * KP, lm = lo + 30 * KP;
#pragma unroll 1
            for (int s = 0; s < 2; s++) {
                const uint32_t wl = s ? lar4.y : lar4.x, wa = s ? aim4.y : aim4.x, wr_ = s ? cr4.y : cr4.x, wi = s ? ci4.y : ci4.x;
                const uint32_t ea = pack_b(ex2(blo(wl) * 1.4426950408889634f), ex2(bhi(wl) * 1.4426950408889634f));
                const float a2[2] = {-(blo(ea) * dt) * 1.4426950408889634f, -(bhi(ea) * dt) * 1.4426950408889634f};
                const float b[2] = {blo(wa) * dt, bhi(wa) * dt};
                {
                    cf z8[2], z16[2], z32[2], z64[2], z128[2];
#pragma unroll
                    for (int e = 0; e < 2; e++) {
                        z8[e] = cexp_(a2[e] * 8.f, b[e] * 8.f);
                        z16[e] = csq(z8[e]); z32[e] = csq(z16[e]); z64[e] = csq(z32[e]); z128[e] = csq(z64[e]);
                    }
                    const hc r1 = pk(z8[0], z8[1]), r2 = pk(z16[0], z16[1]), r3 = hmulc(r1, r2), r4 = pk(z32[0], z32[1]);
                    sth(st + 1 * KP, r1); sth(st + 2 * KP, r2); sth(st + 3 * KP, r3); sth(st + 4 * KP, r4);
                    sth(st + 5 * KP, hmulc(r1, r4)); sth(st + 6 * KP, hmulc(r2, r4)); sth(st + 7 * KP, hmulc(r3, r4));
                    sth(st + 29 * KP, pk(z64[0], z64[1])); sth(st + 30 * KP, pk(z128[0], z128[1]));
                }
                {
                    cf C[2], z2[2], z4[2], v2[2], v4[2], c1[2], d1[2];
#pragma unroll
                    for (int e = 0; e < 2; e++) {
                        C[e] = {(e ? bhi(wr_) : blo(wr_)) * cs, (e ? bhi(wi) : blo(wi)) * -cs};
                        const cf z = cexp_(a2[e], -b[e]);
                        const cf v = cexp_(a2[e] * 256.f, b[e] * -256.f);
                        z2[e] = csq(z); z4[e] = csq(z2[e]); v2[e] = csq(v); v4[e] = csq(v2[e]);
                        c1[e] = cmul(C[e], z); d1[e] = cmul(C[e], v);
                    }
                    const hc l0 = pk(C[0], C[1]), l1 = pk(c1[0], c1[1]), e1 = pk(d1[0], d1[1]);
                    const hc h = pk(z2[0], z2[1]), f = pk(z4[0], z4[1]), w = pk(v2[0], v2[1]), y = pk(v4[0], v4[1]);
                    const hc l2 = hmulc(l0, h), l3 = hmulc(l1, h), e2 = hmulc(l0, w), e3 = hmulc(e1, w), e4 = hmulc(l0, y), g2 = hmulc(e1, h);
                    sth(st + 8 * KP, l0); sth(st + 9 * KP, l1); sth(st + 10 * KP, l2); sth(st + 11 * KP, l3);
                    sth(st + 12 * KP, hmulc(l0, f)); sth(st + 13 * KP, hmulc(l1, f)); sth(st + 14 * KP, hmulc(l2, f)); sth(st + 15 * KP, hmulc(l3, f));
                    sth(st + 16 * KP, e1);
                    sth(st + 17 * KP, g2);
                    sth(st + 18 * KP, hmulc(e1, f));
                    sth(st + 19 * KP, hmulc(g2, f));
                    sth(st + 20 * KP, e2);
                    sth(st + 21 * KP, hmulc(e2, f));
                    sth(st + 22 * KP, e3);
                    sth(st + 23 * KP, hmulc(e3, f));
                    sth(st + 24 * KP, e4);
                    sth(st + 25 * KP, hmulc(e1, y));
                    sth(st + 26 * KP, hmulc(e2, y));
                    sth(st + 27 * KP, hmulc(e3, y));
                    sth(st + 28 * KP, hmulc(e4, y));
                }
                __syncwarp();
                if (warp == TSW) TSL(s ? 34 : 27);
#pragma unroll
                for (int kp = 0; kp < 4; kp++) {
                    uint32_t bb[3][4], m2[4];
                    ldsm4(lm + kp * 32, m2[0], m2[1], m2[2], m2[3]);
                    ldsm4(lb + kp * 32, bb[0][0], bb[0][1], bb[0][2], bb[0][3]);
                    ldsm4(lb + 8 * KP + kp * 32, bb[1][0], bb[1][1], bb[1][2], bb[1][3]);
                    ldsm4(lb2 + kp * 32, bb[2][0], bb[2][1], bb[2][2], bb[2][3]);
#pragma unroll
                    for (int k2 = 0; k2 < 2; k2++) {
                        hc v0, m1;
                        ldsm4(la + kp * 32 + k2 * 16, v0.r, m1.r, v0.i, m1.i);
                        const hc mm = {m2[2 * k2], m2[2 * k2 + 1]};
                        const hc v1 = hmulc(v0, m1), v2 = hmulc(v0, mm), v3 = hmulc(v1, mm);
                        v0.r = cpy(v0.r, zk); v0.i = cpy(v0.i, zk);
#pragma unroll
                        for (int nt = 0; nt < 3; nt++) {
                            mma_f16(kacc[0][nt], v0.r, v1.r, v0.i, v1.i, bb[nt][2 * k2], bb[nt][2 * k2 + 1]);
                            mma_f16(kacc[1][nt], v2.r, v3.r, v2.i, v3.i, bb[nt][2 * k2], bb[nt][2 * k2 + 1]);
                        }
                    }
                }
                __syncwarp();
                if (warp == TSW) TSL(s ? 40 : 33);
            }
        }
        TSL(1);
        uint32_t fc[16], fs[16], ta[8], tb[8];
        {
            const uint4* tp = p.tab + (tid & 127);
#pragma unroll
            for (int i = 0; i < 4; i++) {
                const uint4 u = ldg128(tp + i * 128), v = ldg128(tp + (4 + i) * 128), w = ldg128(tp + (8 + i) * 128);
                fc[4 * i] = u.x; fc[4 * i + 1] = u.y; fc[4 * i + 2] = u.z; fc[4 * i + 3] = u.w;
                fs[4 * i] = v.x; fs[4 * i + 1] = v.y; fs[4 * i + 2] = v.z; fs[4 * i + 3] = v.w;
                uint32_t* t = i < 2 ? ta + 4 * i : tb + 4 * (i - 2);
                t[0] = w.x; t[1] = w.y; t[2] = w.z; t[3] = w.w;
            }
        }
        {
            const uint32_t tb_ = wb + 4 * SUB;
            const uint32_t seg = wb + (lane & 3) * SUB + (lane >> 2) * 16;
            uint32_t v0[4];
#pragma unroll
            for (int m = 0; m < 4; m++) {
                constexpr float S = 1.0f / 512.0f;
                const float (&k0)[4] = kacc[m >> 1][0], (&k1)[4] = kacc[m >> 1][1], (&k2)[4] = kacc[m >> 1][2];
                const int R = 8 * m + g, o = 2 * (m & 1);
                v0[m] = pack_h(k0[o] * S, k0[o + 1] * S);
                sts32(tb_ + (q < 2 ? 4 * R + 2 * q : 64 * q + 2 * R) * 2, pack_h(k1[o] * S, k1[o + 1] * S));
                const uint32_t v2 = pack_h(k2[o] * S, k2[o + 1] * S);
                if (q < 2 || (m == 0 && lane == 2)) sts16(tb_ + (256 + 64 * q + R) * 2, v2);
                if (q < 2) sts16(tb_ + (288 + 64 * q + R) * 2, v2 >> 16);
            }
            stsm4(seg, v0[0], v0[1], v0[2], v0[3]);
            if (lane == 0) sts16(sm + SM_SCL + warp * 2, __float_as_uint(16384.0f * outscale) >> 16);
            __syncwarp();
            const uint2 l1 = lds64(tb_ + lane * 8);
            const uint32_t l1n = lds16(tb_ + lane * 8 + 8);
            uint32_t l2[2], l2n[2], l3[4], l3n[4];
#pragma unroll
            for (int i = 0; i < 2; i++) { l2[i] = lds32(tb_ + 256 + i * 128 + lane * 4); l2n[i] = lds16(tb_ + 260 + i * 128 + lane * 4); }
#pragma unroll
            for (int i = 0; i < 4; i++) { l3[i] = lds16(tb_ + 512 + i * 64 + lane * 2); l3n[i] = lds16(tb_ + 514 + i * 64 + lane * 2); }
            sts128(seg + 128, prmt(l1.x, 0, 0x1010), prmt(l1.x, l1.y, 0x5432), prmt(l1.y, 0, 0x1010), prmt(l1.y, l1n, 0x5432));
#pragma unroll
            for (int i = 0; i < 2; i++) sts128(seg + 256 + i * 128, prmt(l2[i], 0, 0x1010), l2[i], prmt(l2[i], 0, 0x3232), prmt(l2n[i], 0, 0x1010));
            const uint32_t s3 = (lane & 1) ? 0x5454 : 0x5410;
#pragma unroll
            for (int i = 0; i < 4; i++) {
                const uint32_t vv = prmt(l3[i], 0, 0x1010);
                sts128(seg + 512 + i * 128, vv, vv, prmt(l3[i], l3n[i], s3), prmt(l3n[i], 0, 0x1010));
            }
        }
        proxy_fence();
        TSL(2);
        cluster_wait();
        bar_sync(2, 512);
        asm volatile("setmaxnreg.inc.sync.aligned.u32 200;");
        TSL(3);
        const int wgi = warp >> 2, w = warp & 3;
        uint32_t gt[2][4][4];
        {
            const uint64_t dre = bdesc(sm + SM_F2 + 2048, 512), dim = bdesc(sm + SM_F2, 512);
            const uint32_t zst = 4 * SUB + (lane >> 4) * SUB + (16 * w + (lane & 15)) * 16;
            const uint32_t hl = sm + SM_CH + (lane >> 4) * CH_SZ + wgi * SUB + (16 * w + (lane & 15)) * 16;
#pragma unroll
            for (int ci = 0; ci < 4; ci++) {
                const uint32_t cb = sm + SM_CH + (4 * wgi + ci) * CH_SZ;
                const uint64_t d1 = bdesc(cb, SUB);
                uint32_t re[16], im[16];
                wg_fence();
                wg_h(re, fc, fc + 8, d1, d1 + 16, d1 + 32, d1 + 48);
                wg_h(im, fs, fs + 8, d1, d1 + 16, d1 + 32, d1 + 48);
                wg_commit();
                {
                    uint32_t h[4];
                    ldsm4(hl + 2 * ci * CH_SZ + 2 * 0 * SUB, h[0], h[1], h[2], h[3]);
                    sched_fence();
#pragma unroll
                    for (int i = 0; i < 2; i++) {
                        const float2 f0 = __half22float2(*reinterpret_cast<const __half2*>(&h[i])), f1 = __half22float2(*reinterpret_cast<const __half2*>(&h[2 + i]));
                        gt[0][2 * i][ci] = pack_b(silu2(f0.x), silu2(f1.x)); gt[0][2 * i + 1][ci] = pack_b(silu2(f0.y), silu2(f1.y));
                        touch(gt[0][2 * i][ci]); touch(gt[0][2 * i + 1][ci]);
                    }
                    sched_fence();
                }
                wg_wait<0>();
                touch(re); touch(im);
#pragma unroll
                for (int i = 0; i < 16; i++) {
                    re[i] = hfma2_(ta[i & 7], im[i], re[i]); im[i] = hfms2_(tb[i & 7], re[i], im[i]); re[i] = hfma2_(ta[i & 7], im[i], re[i]);
                }
                uint32_t su[16], sk[16];
                wg_fence();
                wg_h(su, re, im, dre, dre + 16, dim, dim + 16);
                wg_h(sk, re + 8, im + 8, dre, dre + 16, dim, dim + 16);
                wg_commit();
                {
                    uint32_t h[4];
                    ldsm4(hl + 2 * ci * CH_SZ + 2 * 1 * SUB, h[0], h[1], h[2], h[3]);
                    sched_fence();
#pragma unroll
                    for (int i = 0; i < 2; i++) {
                        const float2 f0 = __half22float2(*reinterpret_cast<const __half2*>(&h[i])), f1 = __half22float2(*reinterpret_cast<const __half2*>(&h[2 + i]));
                        gt[1][2 * i][ci] = pack_b(silu2(f0.x), silu2(f1.x)); gt[1][2 * i + 1][ci] = pack_b(silu2(f0.y), silu2(f1.y));
                        touch(gt[1][2 * i][ci]); touch(gt[1][2 * i + 1][ci]);
                    }
                    sched_fence();
                }
                wg_wait<0>();
                touch(su); touch(sk);
                uint32_t zr[8], zi[8];
#pragma unroll
                for (int i = 0; i < 8; i++) {
                    const hc z = hmulc(hc{su[i], su[8 + i]}, hc{sk[i], sk[8 + i]});
                    zr[i] = z.r; zi[i] = z.i;
                }
                uint32_t y[16];
                wg_fence();
                wg_h(y, zi, zr, dre, dre + 16, dim, dim + 16);
                wg_commit();
                wg_wait<0>();
                touch(y);
#pragma unroll
                for (int i = 0; i < 8; i++) {
                    y[8 + i] = hfms2_(ta[i], y[i], y[8 + i]); y[i] = hfma2_(tb[i], y[8 + i], y[i]); y[8 + i] = hfms2_(ta[i], y[i], y[8 + i]);
                }
                bar_sync(10 + wgi, 128);
                stsm4(cb + zst, y[8], y[9], y[10], y[11]);
                stsm4(cb + zst + 2 * SUB, y[12], y[13], y[14], y[15]);
                stsm4(cb + zst + 4 * SUB, y[0], y[1], y[2], y[3]);
                stsm4(cb + zst + 6 * SUB, y[4], y[5], y[6], y[7]);
                if (warp == TSW) TSL(35 + ci);
            }
        }
        proxy_fence();
        mbar_wait(bars + B_TOK * 8, 0);
        bar_sync(1, 256);
        if (tid == 0) asm volatile("mbarrier.arrive.relaxed.cluster.shared::cluster.b64 _, [%0];" :: "r"(mapa(bars + B_PEER * 8, rank ^ 1)) : "memory");
        TSL(4);
        {
            float acc[2][32];
            wg_fence();
#pragma unroll
            for (int jj = 0; jj < 2; jj++) {
                const uint64_t d4 = bdesc(sm + SM_CH + (4 + 2 * jj + wgi) * SUB, CH_SZ);
                wg_f0(acc[jj], fc, fc + 8, d4, d4 + 16, d4 + 32, d4 + 48);
                wg_f1(acc[jj], fs, fs + 8, d4 + SUB / 4, d4 + SUB / 4 + 16, d4 + SUB / 4 + 32, d4 + SUB / 4 + 48);
                wg_commit();
            }
            const uint2 tk = lds64(sm + SM_TOK);
            const uint4 sc = lds128(sm + SM_SCL);
            const uint32_t xo = SM_SLAB + wgi * 16384 + (16 * w + g) * 128 + q * 32 + ((rank ^ (g & 1)) * 16);
            const uint32_t peer = mapa(sm, rank ^ 1), so = SM_CH + wgi * CH_SZ + w * 1024 + lane * 16;
            mbar_wait(bars + B_PEER * 8, 0);
#pragma unroll
            for (int jj = 0; jj < 2; jj++) {
                uint4 xv[4];
#pragma unroll
                for (int i = 0; i < 4; i++) xv[i] = lds128(sm + xo + jj * 32768 + (i & 1) * 8192 + (i >> 1) * 1024);
                if (jj == 0) wg_wait<1>(); else wg_wait<0>();
                touch(acc[jj]);
                uint32_t s[4][4], o[4][4];
#pragma unroll
                for (int i = 0; i < 4; i++) {
#pragma unroll
                    for (int j = 0; j < 4; j++) s[i][j] = pack_b(acc[jj][8 * j + i], acc[jj][8 * j + 4 + i]);
                    o[i][0] = bfma2(bmul2(s[i][0], gt[jj][i][0]), sc.x, xv[i].x); o[i][1] = bfma2(bmul2(s[i][1], gt[jj][i][1]), sc.y, xv[i].y);
                    o[i][2] = bfma2(bmul2(s[i][2], gt[jj][i][2]), sc.z, xv[i].z); o[i][3] = bfma2(bmul2(s[i][3], gt[jj][i][3]), sc.w, xv[i].w);
                }
                const uint32_t sb = SM_BAR + (B_STG + 2 * jj + wgi) * 8;
#pragma unroll
                for (int e = 0; e < 2; e++)
                    if (e == rank) {
#pragma unroll
                        for (int hi = 0; hi < 2; hi++) {
                            const uint32_t (&r)[4] = o[2 * hi + 1 - e], (&l)[4] = o[2 * hi + e];
                            st_async4(peer + so + 2 * jj * CH_SZ + hi * 512, r[0], r[1], r[2], r[3], peer + sb);
                            sts128(sm + so + (4 + 2 * jj) * CH_SZ + 64 + hi * 512, l[0], l[1], l[2], l[3]);
                        }
                    }
                __syncwarp();
                if (lane == 0) mbar_arrive(sm + sb);
                if (warp == TSW) TSL(5 + jj);
#pragma unroll
                for (int k = 0; k < 2; k++) {
                    const int t = 0xFFFF - ((k ? tk.y : tk.x) & 0xFFFF);
                    if ((t & ~0x101) == 512 * w + 32 * g + 16 * jj + 8 * wgi + 2 * q) {
                        uint32_t f[4];
#pragma unroll
                        for (int j = 0; j < 4; j++) {
                            const uint32_t lo = (t & 1) ? s[1][j] : s[0][j], hi = (t & 1) ? s[3][j] : s[2][j];
                            f[j] = (t & 256) ? hi : lo;
                        }
                        const uint32_t dst = mapa(sm, k);
                        st_async4(dst + SM_FIX + rank * 16, bmul2(f[0], sc.x), bmul2(f[1], sc.y), bmul2(f[2], sc.z), bmul2(f[3], sc.w),
                                  dst + SM_BAR + B_FIX * 8);
                    }
                }
                __syncwarp();
            }
        }
        TSL(7);
    } else {
        const int v = warp - 8;
        uint64_t pol = 0;
        cluster_wait();
        TSL(19);
        if (warp == 12) {
            TG(28);
            asm volatile("createpolicy.fractional.L2::evict_first.b64 %0, 1.0;" : "=l"(pol));
            if (elect()) {
                asm volatile("cp.async.bulk.shared::cluster.global.mbarrier::complete_tx::bytes [%0], [%1], 6144, [%2];"
                             :: "r"(sm + SM_F2), "l"(p.tab + 1536), "r"(bars + B_SLAB * 8) : "memory");
                asm volatile("cp.async.bulk.tensor.5d.shared::cluster.global.mbarrier::complete_tx::bytes.multicast::cluster"
                             " [%0], [%1, {%3, %4, %4, %4, %5}], [%2], %6;"
                             :: "r"(sm + SM_SLAB + rank * 32768), "l"(&tm_x), "r"(bars + B_SLAB * 8), "r"(G * 16), "r"(0), "r"(2 * rank), "h"((uint16_t)3) : "memory");
                TS(18);
                if (G < 56) {
#pragma unroll 1
                    for (int n = 0; n < DEPTH; n++)
                        tma3d(sm + SM_RING + n * 8192, &tm_g, G * 64, rank * 512 + n * 32, bars + (B_FULL + n) * 8, pol);
                }
            }
            __syncwarp();
            TSL(20);
        }
        if (warp == 13 && lane < 2 && c + 128 * lane < 192) asm volatile("prefetch.global.L2 [%0];" :: "l"(p.tab + (c + 128 * lane) * 8));
        uint4* const my_stats = p.sc->stats + ((2 * (c & 1) + (v >> 2)) * 64 + (c >> 1)) * 4 + (v & 3);
        uint32_t* const my_part = p.sc->part + ((2 * (32 * rank + v) + (q & 1)) * 56 + G) * 16 + g + 8 * (q >> 1);
        if (v < 4 && G < 56) {
#pragma unroll
            for (int n = 0; n < 8; n++) st_relaxed32(my_part + n * 8 * 56 * 16, 0);
        }
        if (v & 1) {
            if (lane < 2) st_relaxed128(my_stats - lane, make_uint4(0, 0, 0, 0));
            bar_arrive(6 + (v >> 1), 64);
        } else {
            bar_sync(6 + (v >> 1), 64);
        }
        uint4 xa[4], xc[4], w4[4];
        {
            const uint4* ra = reinterpret_cast<const uint4*>(p.x + (size_t)(16 * c + 2 * v) * 1024) + lane;
#pragma unroll
            for (int k = 0; k < 4; k++) { xa[k] = ldg128(ra + 32 * k); xc[k] = ldg128(ra + 128 + 32 * k); }
#pragma unroll
            for (int k = 0; k < 4; k++) w4[k] = ldg128(reinterpret_cast<const uint4*>(p.wr) + 32 * k + lane);
        }
        uint32_t tag;
        asm volatile("ld.relaxed.gpu.global.u32 %0, [%1];" : "=r"(tag) : "l"(&p.sc->epoch) : "memory");
        tag = tag % 3 + 1;
        {
            constexpr uint32_t ONE = 0x3F803F80u;
            float sw[4] = {0, 0, 0, 0}, sA[4] = {0, 0, 0, 0}, sB[4] = {0, 0, 0, 0};
            float qA[2][4] = {{0, 0, 0, 0}, {0, 0, 0, 0}}, qB[2][4] = {{0, 0, 0, 0}, {0, 0, 0, 0}};
#pragma unroll
            for (int k = 0; k < 4; k++) mma_bf16(sw, w4[k].x, w4[k].y, w4[k].z, w4[k].w, ONE, ONE);
#pragma unroll
            for (int k = 0; k < 4; k++) {
                mma_bf16(sA, xa[k].x, xa[k].y, xa[k].z, xa[k].w, ONE, ONE);
                mma_bf16(qA[0], xa[k].x, w4[k].x, xa[k].y, w4[k].y, xa[k].x, xa[k].y);
                mma_bf16(qA[1], xa[k].z, w4[k].z, xa[k].w, w4[k].w, xa[k].z, xa[k].w);
                mma_bf16(sB, xc[k].x, xc[k].y, xc[k].z, xc[k].w, ONE, ONE);
                mma_bf16(qB[0], xc[k].x, w4[k].x, xc[k].y, w4[k].y, xc[k].x, xc[k].y);
                mma_bf16(qB[1], xc[k].z, w4[k].z, xc[k].w, w4[k].w, xc[k].z, xc[k].w);
            }
            TSL(8);
            const bool dg = q == (g >> 1), od = g & 1;
            float r0 = dg ? (od ? qA[0][1] + qA[1][1] : qA[0][0] + qA[1][0]) : 0.f;
            float r1 = dg ? (od ? qA[0][3] + qA[1][3] : qA[0][2] + qA[1][2]) : 0.f;
            float r2 = dg ? (od ? qB[0][1] + qB[1][1] : qB[0][0] + qB[1][0]) : 0.f;
            float r3 = dg ? (od ? qB[0][3] + qB[1][3] : qB[0][2] + qB[1][2]) : 0.f;
            const bool rowb = lane & 1;
            float ss = (rowb ? r2 : r0) + __shfl_xor_sync(0xFFFFFFFFu, rowb ? r0 : r2, 1);
            float dw = (rowb ? r3 : r1) + __shfl_xor_sync(0xFFFFFFFFu, rowb ? r1 : r3, 1);
            float sx = rowb ? sB[0] + sB[2] : sA[0] + sA[2];
            float ws = sw[0] + sw[2];
            ss += __shfl_xor_sync(0xFFFFFFFFu, ss, 2); dw += __shfl_xor_sync(0xFFFFFFFFu, dw, 2);
#pragma unroll
            for (int o = 4; o < 32; o <<= 1) {
                ss += __shfl_xor_sync(0xFFFFFFFFu, ss, o); dw += __shfl_xor_sync(0xFFFFFFFFu, dw, o);
                sx += __shfl_xor_sync(0xFFFFFFFFu, sx, o); ws += __shfl_xor_sync(0xFFFFFFFFu, ws, o);
            }
            const float mean = sx * (1.0f / 1024.0f);
            const float var = fmaxf(ss * (1.0f / 1024.0f) - mean * mean, 0.f);
            const float m = rb(mean);
            float sd; asm("sqrt.approx.ftz.f32 %0, %1;" : "=f"(sd) : "f"(rb(rb(var) + 1e-5f)));
            const float rs = rcp(rb(sd));
            const float hi = rb(rs);
            const uint32_t p0 = pack_b(m, hi), p1 = pack_b(rs - hi, rs * (dw - m * ws));
            const uint32_t o0 = __shfl_xor_sync(0xFFFFFFFFu, p0, 1), o1 = __shfl_xor_sync(0xFFFFFFFFu, p1, 1);
            if (lane == 0) {
                const uint32_t tb = ((tag & 1) << 15) | ((tag >> 1) << 31);
                st_relaxed128(my_stats, make_uint4(prmt(p0, o0, 0x5410), (prmt(p0, o0, 0x7632) & 0x7FFF7FFFu) | tb,
                                                              prmt(p1, o1, 0x5410), prmt(p1, o1, 0x7632)));
            }
        }
        TSL(9);
        if (warp == 12 && G < 56 && elect())
            tma3d(sm + SM_RING + DEPTH * 8192, &tm_g, G * 64, rank * 512 + DEPTH * 32, bars + (B_FULL + DEPTH) * 8, pol);
        int t0 = 0, t1 = 0;
        uint32_t mk = 0;
        uint4 xr[4], stk;
        {
            const int wgi = v >> 2, w = v & 3;
            uint4 st[4];
            const uint4* src = p.sc->stats + wgi * 256 + 64 * w + lane;
            mbar_wait(bars + B_SLAB * 8, 0);
            TSL(10);
            uint32_t xt[8][4];
            const uint32_t a = sm + SM_SLAB + wgi * 16384 + (16 * w + g) * 128 + q * 32 + ((rank ^ (g & 1)) * 16);
#pragma unroll
            for (int i = 0; i < 4; i++) {
                const uint4 e = lds128(a + (i >> 1) * 32768 + (i & 1) * 1024), o = lds128(a + (i >> 1) * 32768 + (i & 1) * 1024 + 8192);
                xt[0][i] = prmt(e.x, o.x, 0x5410); xt[1][i] = prmt(e.x, o.x, 0x7632);
                xt[2][i] = prmt(e.y, o.y, 0x5410); xt[3][i] = prmt(e.y, o.y, 0x7632);
                xt[4][i] = prmt(e.z, o.z, 0x5410); xt[5][i] = prmt(e.z, o.z, 0x7632);
                xt[6][i] = prmt(e.w, o.w, 0x5410); xt[7][i] = prmt(e.w, o.w, 0x7632);
            }
            const uint32_t tb = ((tag & 1) << 15) | ((tag >> 1) << 31);
            int it = 0;
            bool ok;
            do {
#pragma unroll
                for (int i = 0; i < 4; i++) st[i] = ld_relaxed128(src + (i >> 1) * 512 + (i & 1) * 32);
                const uint32_t bad = ((st[0].y ^ tb) | (st[1].y ^ tb) | (st[2].y ^ tb) | (st[3].y ^ tb)) & 0x80008000u;
                ok = __all_sync(0xFFFFFFFFu, bad == 0);
            } while (!ok && ++it < SPIN_LIMIT);
            TSL(11); TG(31);
            uint32_t h1[4], h2[4];
#pragma unroll
            for (int i = 0; i < 4; i++) {
                const uint32_t o2 = st[i].w ^ (prmt(st[i].w, 0, 0xBB99) | 0x80008000u);
                const uint32_t id = 0xFFFF - (512 * w + 32 * g + 8 * wgi + 2 * q) - ((i >> 1) * 16 + (i & 1) * 256);
                const uint32_t k0 = prmt(o2, id, 0x1054), k1 = prmt(o2, id - 1, 0x3254);
                h1[i] = max(k0, k1); h2[i] = min(k0, k1);
            }
            const uint32_t a1 = max(h1[0], h1[1]), a2 = __vimax3_u32(min(h1[0], h1[1]), h2[0], h2[1]);
            const uint32_t b1 = max(h1[2], h1[3]), b2 = __vimax3_u32(min(h1[2], h1[3]), h2[2], h2[3]);
            const uint32_t k1 = max(a1, b1), k2 = __vimax3_u32(min(a1, b1), a2, b2);
            const uint32_t w1 = __reduce_max_sync(0xFFFFFFFFu, k1);
            const uint32_t w2 = __reduce_max_sync(0xFFFFFFFFu, k1 == w1 ? k2 : k1);
            if (lane == 0) sts64(sm + SM_KEYS + v * 8, w1, w2);
            if (warp < 14) {
                bar_arrive(3, 256);
                if (warp == 12 && G < 56 && elect())
                    tma3d(sm + SM_RING + (DEPTH + 1) * 8192, &tm_g, G * 64, rank * 512 + (DEPTH + 1) * 32, bars + (B_FULL + DEPTH + 1) * 8, pol);
            } else {
                bar_sync(3, 256);
                const uint32_t key = lane < 16 ? lds32(sm + SM_KEYS + lane * 4) : 0u;
                const uint32_t m1 = __reduce_max_sync(0xFFFFFFFFu, key);
                const uint32_t m2 = __reduce_max_sync(0xFFFFFFFFu, key == m1 ? 0u : key);
                t0 = (0xFFFF - (m1 & 0xFFFF)) & 2047; t1 = (0xFFFF - (m2 & 0xFFFF)) & 2047;
                const int t = warp == 15 ? t1 : t0;
                mk = ((warp == 15 ? m2 : m1) & 0xFFFF0000u) | (0xFFFF - t);
                const uint4* row = reinterpret_cast<const uint4*>(p.x + (size_t)t * 1024) + lane;
#pragma unroll
                for (int i = 0; i < 4; i++) xr[i] = ldg128(row + 32 * i);
                stk = ld_relaxed128(p.sc->stats + (((t >> 3) & 3) * 64 + (t >> 5)) * 4 + ((t >> 1) & 3));
            }
            const uint32_t ua = sm + SM_CH + (2 * (lane >> 4) + wgi) * SUB + (16 * w + (lane & 15)) * 16;
#pragma unroll
            for (int i = 0; i < 4; i++) { st[i].y = bmul2(st[i].y & 0x7FFF7FFFu, 0x3F003F00u); st[i].z = bmul2(st[i].z, 0x3F003F00u); }
#pragma unroll
            for (int cc = 0; cc < 8; cc++) {
                uint32_t o[4];
#pragma unroll
                for (int i = 0; i < 4; i++) { const uint32_t n = norm2(xt[cc][i], st[i].x, st[i].y, st[i].z); o[i] = pack_h(blo(n), bhi(n)); }
                stsm4(ua + cc * CH_SZ, o[0], o[1], o[2], o[3]);
            }
            proxy_fence();
            bar_arrive(2, 512);
        }
        TSL(12);
        if (warp < 12) {
            asm volatile("setmaxnreg.dec.sync.aligned.u32 56;");
            if (G < 56) {
                const uint64_t dw = (uint64_t)(((sm + SM_RING) & 0x3FFFFu) >> 4) | (1ull << 16) | (64ull << 32) | (1ull << 62);
                const uint64_t dx = (uint64_t)(((sm + SM_XSEL + rank * 2048) & 0x3FFFFu) >> 4) | (2ull << 16) | (8ull << 32);
                const uint64_t dh = (uint64_t)(((sm + SM_H) & 0x3FFFFu) >> 4) | (8ull << 16) | (8ull << 32);
                float ag[4] = {0, 0, 0, 0}, au[4] = {0, 0, 0, 0};
                touch(ag); touch(au);
                mbar_wait(bars + B_TOK * 8, 0);
                TSL(13);
                int slot = 0, ph = 0;
#pragma unroll 1
                for (int n = 0; n < 16; n++) {
                    mbar_wait(bars + (B_FULL + slot) * 8, ph);
                    const uint64_t a = dw + slot * 512, b = dx + n * 8;
                    wg_fence();
                    wg_w<1>(ag, a, b); wg_w<1>(au, a + 256, b); wg_w<1>(ag, a + 128, b + 4); wg_w<1>(au, a + 384, b + 4);
                    wg_commit();
                    wg_wait<0>();
                    touch(ag); touch(au);
                    if (lane == 0) mbar_arrive(bars + (B_EMPTY + slot) * 8);
                    if (++slot == NSLOT) { slot = 0; ph ^= 1; }
                }
                TSL(14);
                if (q == 0) {
#pragma unroll
                    for (int r = 0; r < 2; r++) {
                        const uint32_t dst = mapa(sm, r), o = dst + SM_PAIR + rank * 1024 + v * 256 + g * 32;
                        st_async4(o, __float_as_uint(ag[0]), __float_as_uint(ag[1]), __float_as_uint(ag[2]), __float_as_uint(ag[3]), dst + SM_BAR + B_PAIR * 8);
                        st_async4(o + 16, __float_as_uint(au[0]), __float_as_uint(au[1]), __float_as_uint(au[2]), __float_as_uint(au[3]), dst + SM_BAR + B_PAIR * 8);
                    }
                }
                mbar_wait(bars + B_PAIR * 8, 0);
                {
                    const uint32_t o = sm + SM_PAIR + v * 256 + g * 32 + q * 4, og = o + (p.up_first ? 16 : 0), ou = o + (p.up_first ? 0 : 16);
                    const float gs = rb(__uint_as_float(lds32(og)) + __uint_as_float(lds32(og + 1024)));
                    const float us = rb(__uint_as_float(lds32(ou)) + __uint_as_float(lds32(ou + 1024)));
                    const float hv = rb(siluf_(gs)) * us;
                    const uint32_t hd = sm + SM_H + (2 * v + (q >> 1)) * 128 + (q & 1) * 32 + g * 2, hb = pack_b(hv, hv);
                    sts16(hd, hb); sts16(hd + 64, hb);
                }
                proxy_fence();
                bar_sync(4, 128);
                TSL(15);
#pragma unroll 1
                for (int n = 0; n < 8; n++) {
                    mbar_wait(bars + (n == 7 ? full_bar(23) : B_FULL + slot) * 8, n == 7 ? 0 : ph);
                    const uint64_t a = dw + slot * 512;
                    float d[4];
                    wg_fence();
                    wg_w0(d, a, dh); wg_w<1>(d, a + 128, dh + 16); wg_w<1>(d, a + 256, dh + 32); wg_w<1>(d, a + 384, dh + 48);
                    wg_commit();
                    wg_wait<0>();
                    touch(d);
                    st_relaxed32(my_part + n * 8 * 56 * 16, (__float_as_uint((q & 2) ? d[2] : d[0]) & ~3u) | tag);
                    if (lane == 0) mbar_arrive(bars + (B_EMPTY + slot) * 8);
                    if (++slot == NSLOT) { slot = 0; ph ^= 1; }
                }
                TSL(16);
            }
        } else {
            asm volatile("setmaxnreg.dec.sync.aligned.u32 56;");
            if (warp == 12) {
                if (G < 56) {
                    const bool lead = elect();
#pragma unroll
                    for (int n = DEPTH + 2; n < 24; n++) {
                        mbar_wait(bars + full_bar(n - DEPTH) * 8, full_par(n - DEPTH));
                        if (n >= NSLOT) mbar_wait(bars + (B_EMPTY + n % NSLOT) * 8, (n / NSLOT - 1) & 1);
                        if (lead) {
                            const uint32_t fb = bars + full_bar(n) * 8;
                            mbar_expect(fb, 8192);
                            if (n < 16) tma3d(sm + SM_RING + (n % NSLOT) * 8192, &tm_g, G * 64, rank * 512 + n * 32, fb, pol);
                            else tma3d(sm + SM_RING + (n % NSLOT) * 8192, &tm_d, rank * 512 + (n - 16) * 64, G * 64, fb, pol);
                        }
                    }
                    TSL(23);
                }
            } else if (warp >= 14) {
                const int sw = warp - 14;
                {
                    if (lane == 0) {
                        sts32(sm + SM_TOK + 4 * sw, mk);
                        if (c == 0 && sw == 0) st_relaxed32(&p.sc->epoch, tag);
                    }
                    const uint32_t se = (mk & 1) ? 0x1010 : 0x3232;
                    const uint32_t m = prmt(stk.x, 0, se), hi = prmt(stk.y, 0, se) & 0x7FFF7FFFu, lo = prmt(stk.z, 0, se);
                    const uint32_t a = sm + SM_XSEL + lane * 32 + sw * 16;
#pragma unroll
                    for (int i = 0; i < 4; i++) {
                        sts128(a + i * 1024, norm2(xr[i].x, m, hi, lo), norm2(xr[i].y, m, hi, lo), norm2(xr[i].z, m, hi, lo), norm2(xr[i].w, m, hi, lo));
                        if (sw == rank && 16 * i + (lane >> 1) == G) sts128(sm + SM_XRAW + (lane & 1) * 16, xr[i].x, xr[i].y, xr[i].z, xr[i].w);
                    }
                    proxy_fence();
                    __syncwarp();
                    if (lane == 0) mbar_arrive(bars + B_TOK * 8);
                }
                const int tl = 1024 * sw + 32 * (lane >> 3) + (lane & 6) + rank;
                const uint32_t la = sm + SM_CH + ((lane & 1) == rank ? 4 * CH_SZ + 64 : 0) + sw * 2048 + (lane >> 1) * 16;
                __nv_bfloat16* const op = p.out + (size_t)tl * 1024 + G * 16 + (lane & 1) * 8;
                uint32_t skip = 0;
#pragma unroll
                for (int k = 0; k < 2; k++) {
                    const int d = (k ? t1 : t0) - tl;
                    if ((d & ~0x398) == 0) skip |= 1u << ((d & 0x18) + (d >> 7));
                }
#pragma unroll
                for (int jb = 0; jb < 4; jb++) {
                    mbar_wait(bars + (B_STG + jb) * 8, 0);
                    uint4 o[8];
#pragma unroll
                    for (int i = 0; i < 8; i++) o[i] = lds128(la + jb * CH_SZ + i * 256);
#pragma unroll
                    for (int i = 0; i < 8; i++)
                        asm volatile("{ .reg .pred p; setp.eq.u32 p, %5, 0; @p st.global.v4.u32 [%0], {%1,%2,%3,%4}; }"
                                     :: "l"(op + (size_t)(128 * i + 8 * jb) * 1024), "r"(o[i].x), "r"(o[i].y), "r"(o[i].z), "r"(o[i].w),
                                        "r"(skip & (1u << (8 * jb + i))) : "memory");
                }
                TSL(17); TG(30);
            } else {
                mbar_wait(bars + B_TOK * 8, 0);
                const uint32_t key = lds32(sm + SM_TOK + 4 * rank);
                const int t = 0xFFFF - (key & 0xFFFF);
                const int col = 4 * q + 2 * (lane >> 4) + ((lane >> 3) & 1), d = G * 16 + col;
                const float r = __uint_as_float((key & 0x80000000u) ? (key & 0x7FFF0000u) : (~key & 0xFFFF0000u));
                const float sg = rb(sigmoidf_(r));
                const float xn = blo(lds16(sm + SM_XSEL + (d >> 3) * 32 + rank * 16 + (d & 7) * 2));
                const float xv = blo(lds16(sm + SM_XRAW + col * 2));
                mbar_wait(bars + (G < 56 ? full_bar(23) : B_FIX) * 8, 0);
                TSL(24);
                const uint4* src = reinterpret_cast<const uint4*>(p.sc->part) + c * 224 + lane;
                float s0 = 0, s1 = 0, s2 = 0, s3 = 0;
                {
                    uint4 pv[7];
                    int it = 0;
                    bool ok;
                    do {
                        uint32_t bad = 0;
#pragma unroll
                        for (int i = 0; i < 7; i++) pv[i] = ld_relaxed128(src + 32 * i);
#pragma unroll
                        for (int i = 0; i < 7; i++) bad |= (pv[i].x ^ tag) | (pv[i].y ^ tag) | (pv[i].z ^ tag) | (pv[i].w ^ tag);
                        ok = __all_sync(0xFFFFFFFFu, (bad & 3) == 0);
                    } while (!ok && ++it < SPIN_LIMIT);
#pragma unroll
                    for (int i = 0; i < 7; i++) {
                        s0 += __uint_as_float(pv[i].x); s1 += __uint_as_float(pv[i].y); s2 += __uint_as_float(pv[i].z); s3 += __uint_as_float(pv[i].w);
                    }
                }
                TSL(25);
                const bool u16 = lane & 16, u8 = lane & 8;
                const float y0 = (u16 ? s2 : s0) + __shfl_xor_sync(0xFFFFFFFFu, u16 ? s0 : s2, 16);
                const float y1 = (u16 ? s3 : s1) + __shfl_xor_sync(0xFFFFFFFFu, u16 ? s1 : s3, 16);
                float y = (u8 ? y1 : y0) + __shfl_xor_sync(0xFFFFFFFFu, u8 ? y0 : y1, 8);
                y += __shfl_xor_sync(0xFFFFFFFFu, y, 4);
                const float z = rb(xn + rb(rb(y) * sg));
                const float gt = rb(siluf_(z));
                mbar_wait(bars + B_FIX * 8, 0);
                const float o = xv + rb(blo(lds16(sm + SM_FIX + col * 2)) * gt);
                if (!(lane & 4)) p.out[(size_t)t * 1024 + d] = __float2bfloat16(o);
                TSL(26); TG(29);
            }
        }
    }
}

__device__ __align__(128) const uint32_t g_tab[7680] = {
0x2fff3000,0x2e7c2fd4,0x2fc92fd4,0xad72af5a,0x2ff82ffc,0x230e2c07,0x2faf2fbc,0x217ea934,0x2fed2ff4,0xad4da8d5,0x2f912fa0,0x2e5e2bb7,
0x2fdd2fe6,0xb000af46,0x2f6e2f80,0x2fdd2fc9,0x2ff42fff,0x2e1f2fc9,0x2e1f2e7c,0xa875ad72,0x2fbc2fdd,0x9fd92a4e,0x2d4d2dba,0x2cd825db,
0x2f5a2f91,0xaeb5ac07,0x2c5d2cd8,0x30002f30,0x2ed02f1a,0xaf80aff4,0x2aaa2bb7,0x2cb02f1a,0x2fdd2ffc,0x2dba2fbc,0x2a4e2c07,0x25dba934,
0x2f462fa0,0xa7652875,0x25152875,0x2f802d27,0x2e3f2ed0,0xafa0ad72,0xa17e1cb6,0x2e3f2fe6,0x2cd82d96,0xadfeafd4,0xa934a6a1,0xa44e29f1,
0x2fbc2ff8,0x2d4d2faf,0x9fd9230e,0x2cd8217e,0x2e992f46,0xaa4e2515,0xaa4ea765,0x2fd42f80,0x2cb02dba,0xafffae99,0xad72ac5d,0x27652dba,
0x28752b05,0xab5eaee9,0xaf1aae5e,0xae3fa934,0x2f912ff4,0x2cd82fa0,0xac07a8d5,0x2f302bb7,0x2dba2ed0,0xac5d1cb6,0xae99ad72,0x2dba2fe6,
0x29932c5d,0xafc9af6e,0xafe6af6e,0xaaaa25db,0xa17e244e,0xa30ead4d,0xafafaffc,0xaff8aee9,0x2f5a2fed,0x2c5d2f91,0xaeb5ad4d,0x30002e5e,
0x2cb02e3f,0xad72a17e,0xafffafa0,0x27652e3f,0x217e2993,0xaf02afe6,0xaf02afc9,0xaf1aaaaa,0xab05a5db,0x2814aa4e,0xac07adba,0xad4dafdd,
0x2f1a2fe6,0x2bb72f80,0xaff4af46,0x2f1a2fc9,0x2b052d96,0xae5ea6a1,0xaee9afd4,0xa93429f1,0xa5db244e,0xadbaaffc,0xaa4ead4d,0xafddaee9,
0xaddcabb7,0x2cb0a17e,0x2765a17e,0x1cb6ad00,0x2ed02fdd,0x2aaa2f6e,0xaf80b000,0x2cb02fdd,0x28752cd8,0xaf1aa934,0xab5eadfe,0xae3fa44e,
0xab05a17e,0xac07afaf,0x2814a30e,0xad4daff8,0xaf6eaddc,0x2eb52765,0x2eb52cb0,0x2dba1cb6,0x29932f5a,0xa7652e99,0x25152e99,0x2aaaad96,
0xafa0ab05,0xabb7afed,0xaff4acd8,0x28d52ffc,0xa814af02,0x2f912d27,0x9fd9ae1f,0xaee9ae3f,0x2fd42c32,0xaf5a1cb6,0x30002d72,0x2fd42515,
0x28752f46,0xa8d52e7c,0xa8d52c32,0x2e3fa993,0xafedac5d,0xa934b000,0xaf30af5a,0xa8142eb5,0x1648adfe,0x2e992e5e,0x2c87a814,0xa9f1affc,
0x2fe62e1f,0xafffa875,0x2ddc2ff4,0x2ed02e1f,0x26a12f30,0xa9f12e5e,0xad96244e,0x2fd41fd9,0xafffad27,0xa515aff4,0xac32aff4,0xaddc2b5e,
0x2875acb0,0x2d272f46,0x2fa02993,0x2875aed0,0x2ee92f6e,0xaf91ac87,0x1fd92e99,0x28143000,0x244e2f1a,0xab052e3f,0xaf91a875,0x2fbc2b5e,
0xafd4addc,0x1648afc9,0x1648ae7c,0xafdd9cb6,0x2c32aa4e,0x2aaa2fd4,0x2f802e99,0x2e7caa4e,0x2d002ffc,0xae1fae5e,0xad272814,0xabb72dfe,
0x1fd92f02,0xac072e1f,0xafedad27,0x2dfe2e3f,0xaf6eae7c,0x25dbaf80,0x2c5daaaa,0xaf6eac32,0x2ddca5db,0x25153000,0x2c323000,0x2fff26a1,
0x28d52fbc,0xabb7af91,0xaff4ab05,0xafa0244e,0x96482ee9,0xac872dfe,0xae99af30,0x29f12fbc,0xaed0af02,0x2993af1a,0x2f46217e,0xacb0af02,
0x2f1a1cb6,0xa30e2fc9,0xa30e2e7c,0x2e1f2ddc,0x9fd92eb5,0xa44eb000,0xae5eaf5a,0xaf30ac5d,0xa17e2ed0,0xad002ddc,0xabb7afff,0xa17e2fe6,
0xadfeaf6e,0x2c07ae99,0x2fed2c87,0x9fd9b000,0x2fd42814,0xa9f12f30,0xad962934,0x26a12fed,0xaaaa2d00,0x2765afa0,0xa515afa0,0xa993afaf,
0xa5152eb5,0xad722dba,0x9cb6af6e,0xac322eb5,0xad00afbc,0x2d27adfe,0x2e1f2f30,0x2bb7aee9,0x2ffc2b5e,0xacd82e3f,0xafeda875,0xab052f1a,
0xadba2993,0x2c87ae7c,0x2c87ac32,0x2a4eaf46,0xaddc2d96,0xafe62c5d,0xaed02c5d,0x2fffa9f1,0x2e1fad4d,0x2e3f2814,0x2f02ac07,0xad27ab05,
0xae5e2d00,0x9fd9af1a,0xaf302b5e,0xa44e2faf,0x2e99acb0,0xad962f80,0x2f5aaaaa,0x2e99aed0,0xae3f2d72,0xaff82c32,0xaff82515,0x2f021cb6,
0x2ee9ac87,0x2d4d29f1,0x2ffc9648,0xa44eae99,0xaf6e2b05,0x26a1afbc,0xafd4a44e,0xadba2f91,0x2fc9a8d5,0xaf462e3f,0x2f802875,0x2fe6a8d5,
0xae992d4d,0xb0002c07,0xaf6ea814,0x2c872b05,0x2f80ab5e,0x2c322bb7,0x2e7c2bb7,0x2aaaaff8,0xaff42765,0x2b5eafff,0xad27ad72,0xaff42cb0,
0x2fed1648,0xaffc2c5d,0x2b052eb5,0x2cd82a4e,0xaee92d27,0xaffc2bb7,0xad4dad00,0x244e2e1f,0x2fdda993,0x29f12cb0,0x29f12ed0,0x2eb5af46,
0xafe61648,0x2d72afdd,0x9cb6afd4,0xaed01648,0x2f022934,0xafa02814,0xa8d52fed,0xa30e2f30,0xaf302d00,0xafed2b5e,0xa814af1a,0xa9342faf,
0x3000a765,0x26a12d72,0xa5db2fff,0x3000acb0,0xaf46a6a1,0x2ed0af5a,0x2cb0af5a,0xa993ac87,0x2d272cd8,0xae3f9fd9,0xaf022d4d,0xae1f2fbc,
0xaf6e2cd8,0xafd42b05,0x26a1affc,0xadba2fed,0x2fe6a30e,0x1cb62e1f,0xad722f1a,0x2ed0a30e,0xae1faaaa,0x2fafae7c,0x2fafac32,0x28d5af80,
0x29342e99,0xac07a9f1,0xafbc1648,0xaffc2c87,0xafa02cb0,0xafaf2aaa,0x2d00af80,0xafa02ed0,0x2f911648,0xa44e2eb5,0xafbc2c5d,0x2b052a4e,
0xac87acd8,0x3000ad4d,0x2f6e1fd9,0x2e99afbc,0x9cb62faf,0xa515ad27,0xac32ad27,0xad72a30e,0xafc92c87,0xaf802a4e,0x2f46adba,0xafe62c87,
0x2f02244e,0xa8d52f30,0xafa01fd9,0xa30e2e5e,0xa934ae1f,0x2fbcabb7,0x2c072d00,0x2ffcad27,0xaa4e2fff,0x26a1aed0,0x26a1afe6,0x1648addc,
0xaf4629f1,0xac3225db,0xae7c25db,0x29931648,0xab5e2f91,0xafaf2e5e,0xad002fed,0x2f1aad4d,0x2ee9a875,0xaf302ff8,0x2dfea17e,0x2fbcaff4,
0x2c5dafc9,0xa9f12d72,0x2d96afff,0x2c5dae7c,0xaf022993,0xab5e2515,0xab5ea765,0xa30e2aaa,0xacd82fd4,0xaf302dba,0xaf912f6e,0x2c07a6a1,
0x2d969fd9,0xafdd2fed,0x25db2c07,0x2f5aadfe,0x2e7caff8,0xad722f02,0x2fffae3f,0x2fc9aff8,0xaeb52934,0xaa4e244e,0x9648acd8,0xac5d2dfe,
0xaddc2ff8,0xae7c2d00,0xafc92d00,0x9cb628d5,0x2bb72515,0xaff82f80,0xab5e2f46,0x2bb7a765,0x2fbcaf5a,0xaf302fdd,0x2dfea5db,0x2ee9ad96,
0xae5e28d5,0xa934230e,0x2b05af02,0xaee92fa0,0xaeb52fff,0xad962c32,0xad962515,0xac872ddc,0x276529f1,0xaf802eb5,0xaf462fdd,0xa51529f1,
0x2ff4adfe,0xaff82fed,0x217e2c07,0x28759fd9,0xadfe2875,0xa814217e,0x2e5eaff8,0xaffc2ff4,0xaf5a2fe6,0xac872aaa,0xa6a1a993,0xaf5a2fc9,
0x9cb62c87,0xae7c2d96,0xafc92d96,0xaddc2eb5,0x2f1aac07,0xafaf2f30,0xad002f91,0xab5e2cd8,0xad962814,0xa5db1fd9,0x2fddaf91,0xaf5a2ee9,
0xafc92faf,0xaaaa28d5,0x2993ae1f,0xafe62faf,0xa8d52ddc,0xad002c32,0xad002515,0xaff82fff,0x2d4da6a1,0xae5e2dba,0xafed2f6e,0xaf912fd4,
0xad272765,0xa30e1cb6,0x2fafaddc,0xad272cb0,0xaffc2f5a,0xa81425db,0x2e5eafdd,0xadfe2d96,0xac5d2ee9,0xaa4e2934,0x9648ab05,0xaeb52e5e,
0x2993230e,0xac322b5e,0xae7c2b5e,0xaf462f02,0xacb026a1,0x9cb61648,0x2ddcaa4e,0xa76526a1,0xaff42ee9,0xa17e1fd9,0x2ff8af91,0xa8752814,
0xadfe2fa0,0xa44e230e,0x2cd8af02,0xa93428d5,0x96482aaa,0xa5db2515,0xa5dba765,0xa9f12993,0x2f462f5a,0x2c322e99,0x2e7c2e99,0xa993ad96,
0x2f1a2f30,0xa875244e,0x2e3f2e5e,0x2b5e1fd9,0x2ee92f02,0xaf30ad27,0x2dfe2e1f,0x2fbc2e3f,0x2eb52ed0,0xaf6eafff,0x2dba2ddc,0x2eb52fe6,
0x28752993,0xa8d52515,0xa8d5a765,0x2e3f2aaa,0x244e26a1,0xaf91ad96,0xab05a9f1,0x2fbc2fd4,0x96481fd9,0xae99afed,0xac87ac07,0x29f12dfe,
0xa515a17e,0x9cb6abb7,0xad72ad00,0xac32a17e,0xac5dab05,0xaf5aacd8,0xb000afed,0x2eb52ffc,0xaddcad27,0xae7caff4,0xafc9aff4,0x9cb62b5e,
0xaf02ae7c,0x217eaaaa,0xaf1aaf80,0xaf02ac32,0xafbcaf6e,0x2f302c87,0xadfeae99,0xaee9b000,0xafedafa0,0xaf30aff4,0xa934abb7,0xa81428d5,
0xafd4afff,0x1648ac32,0x1648a515,0xafddaddc,0xaed0af6e,0x2f462c5d,0x299325db,0xacb0af6e,0xad00adfe,0x2e1f2fed,0x2d272c07,0x2bb79fd9,
0xadfeaf02,0xa814ae1f,0x2e5e2d27,0xaffcae3f,0xaa4eacb0,0x2e992993,0x2fd42f46,0xaa4eaed0,0x1cb6a5db,0x2e7c3000,0x2fc93000,0x2ddc26a1,
0x2b5e2814,0xa8752934,0x2e3f2f30,0x2f1a2fed,0x1648a814,0x2c879fd9,0x2e992f91,0xa9f1aee9,0x2c322875,0x2f802fa0,0x2aaa2d27,0x2e7c2875,
0x2f1a2ddc,0xa30e2c32,0xa30e2515,0x2e1f2fff,0x2ffc2fd4,0xafedad96,0xacd8a9f1,0xab0526a1,0x2e1f2c32,0x2ff42d72,0xa8751cb6,0x2e1f2515,
0x2ffc2f6e,0x28142e99,0xae5eac87,0x2dfe3000,0x2eb52fbc,0xaf5aab05,0xb000af91,0xac5d244e,0x29932d00,0xac32afa0,0xae7cafa0,0xaf46afaf,
0x2fe62fd4,0x2ddc3000,0xafffaf5a,0x2ed02fd4,0x2d002ee9,0xad271fd9,0xae1faf91,0xabb72814,0x9fd928d5,0xae5eaff4,0xa44eabb7,0xaf30afa0,
0xadbaaaaa,0x2c87a515,0x2c872765,0x2a4ea993,0x9cb62d96,0xacb02c5d,0xa7652c5d,0x2ddca9f1,0xaff8adfe,0xa30eafbc,0xafafaee9,0xa17e2f30,
0x244ead00,0x2dfe2f1a,0x2934ab5e,0xacd8afaf,0x2fdd2e7c,0xb000a993,0x2f6e2f46,0x2fdd2c32,0xae3f9cb6,0xaff8a765,0xaff8acb0,0x2f022ddc,
0xac07afdd,0x2dfeaa4e,0x1fd9adba,0xafeda5db,0x2f6e2934,0xa6a12ee9,0x2fd42e5e,0x2dbaab05,0x27652f1a,0xaaaaaff4,0xa9932bb7,0xa5152f1a,
0xafddadfe,0xadbaaee9,0xaa4eafbc,0xa5db2f30,0x2aaaab5e,0x2fc92bb7,0x2fe62bb7,0xa993aff8,0x2e3f2fc9,0xafa01cb6,0xa17e2ddc,0x2e3f2e7c,
0xae5e9648,0x2d4dac5d,0xaf91aeb5,0xafedaa4e,0xac07aff8,0x1fd9afaf,0x2dfea30e,0xafeda17e,0x2fdd2aaa,0x29f12fe6,0x29f12fc9,0x2eb5a993,
0xa5152dba,0xaddcae99,0xafffac5d,0xac322dba,0xaf02af30,0x2fa02c07,0x28d5acd8,0x230eaf91,0x2934ad00,0x2e5eab5e,0x2ee92f1a,0xab05afaf,
0x2dba2fc9,0xac5d2ddc,0xae991cb6,0x2dba2e7c,0xaf80a6a1,0x2765af5a,0xa515af5a,0xaf46ac87,0x217eae5e,0x230e2ffc,0x2faf2dfe,0x2ff82814,
0x2f6e244e,0x2fd42934,0xa6a12dfe,0x2dbaacd8,0xa5152e3f,0xafffa17e,0xaddcafa0,0xac322e3f,0xae1faf80,0x2fafa515,0x2faf2765,0x28d5af46,
0x2f9125db,0xaee92a4e,0xa8142dba,0x9fd92fdd,0x2f1a2e7c,0x2bb72f46,0xaff4a993,0x2f1a2c32,0xaf309648,0xacd8aeb5,0x2c07ac5d,0xaf91aa4e,
0x25dbae5e,0x2dba2dfe,0x2a4e2ffc,0x2fdd2814,0x2d722faf,0xae7cad27,0xafc9ad27,0xafffa30e,0x27652fdd,0xa9932f6e,0xaaaab000,0xa5152fdd,
0xaf02ae5e,0x28d5af91,0x2fa02d4d,0x230eafed,0x2f91217e,0xa8142faf,0xaee9230e,0x9fd92ff8,0xaa4e2d72,0x26a1afc9,0x26a1ae7c,0x1648afff,
0xaf8029f1,0xafc925db,0xafe625db,0x2f461648,0x2fa0a934,0x2bb72cd8,0x2ff4a44e,0xa8d5adfe,0xafbc2875,0x2934aff8,0xaffc217e,0xac072ff4,
0x2fd4a765,0xaf5a2ddc,0x30009cb6,0x2fd4acb0,0xaf02aaaa,0xab5eacb0,0xab5eaed0,0xa30e2f80,0x2e5e2c5d,0xab053000,0x29342f5a,0x2ee9aeb5,
0xad96ad4d,0x2fddacd8,0xa5dbafbc,0xaf5a1fd9,0x2cb02e1f,0xaddca875,0x1cb62ff4,0x27652e1f,0xa6a1af91,0x29f1afed,0x2d96ae5e,0xafd42d4d,
0x9cb62ff8,0xafe62d00,0xaed02d00,0x2d7228d5,0x2875afe6,0x2d272993,0x2fa0aaaa,0x2875afc9,0xac072f5a,0x2934afdd,0xaffc25db,0xafbc2d96,
0x2cd8af1a,0x2f91ae3f,0x2f302875,0xac07ab5e,0xaeb52d72,0xad96a765,0xad96acb0,0xac872fff,0x2fc9aa4e,0xa9932fd4,0x2aaa2e99,0x2fe6aa4e,
0xaff41fd9,0x2ff8acd8,0xa17eafbc,0xa875ad4d,0x2ffca875,0x2ee9a17e,0xa44e2ff8,0x2d4daff4,0xaf6ea515,0x25dbaf46,0x2c5daf80,0xaf6e2765,
0x2d722c87,0xafe62d96,0xaed02d96,0x9cb62eb5,0xa8d5aee9,0x2bb72b05,0x2ff4a934,0x2fa0ae5e,0x2d962c07,0x25db2d4d,0xafdd2b05,0x2f5aa814,
0xa765af02,0x2f46af1a,0x2f80217e,0x2515af02,0xa8d52fff,0xad00a765,0xad00acb0,0xaff82d72,0x2dfeaeb5,0xacd83000,0x244e2f5a,0x29342c5d,
0xa17e2fc9,0xad002fff,0xabb7ad72,0xa17e2e7c,0x2d4daf5a,0x2ee9a5db,0xa44e2fdd,0x2ffcad96,0xafd42c07,0x29f1af91,0x2d96af30,0xa6a1acd8,
0x2f46230e,0xafc92b5e,0xafe62b5e,0xaf802f02,0xae7c2eb5,0xafff2dba,0x2d72af6e,0xafc92eb5,0x2ff4a814,0x217e2d4d,0xaff82b05,0x28752c07,
0xad4dab5e,0x2fedae3f,0x2e5e2875,0x2f91af1a,0x96482f80,0xa5dbacb0,0xa5dbaed0,0xa9f1aaaa,0xad729648,0xa515a6a1,0xac32a6a1,0x9cb62a4e,
0xae1f2ffc,0xae3f2c07,0xaf022fbc,0x2d27a934,0x2cd8230e,0xaffc2fa0,0x2b0528d5,0x2fedaf02,0x2e99afe6,0xad962f46,0x2f5aaf80,0x2e99afc9,
0x230eaddc,0x2d27aed0,0x2d27afe6,0xafaf2fff,0xafbc2c87,0x1fd9a9f1,0xad4d1648,0xacd82e99,0xaa4e2f30,0xac5d2814,0xaeb52fed,0x96482934,
0x2ed0a8d5,0xaf802e3f,0x2aaa2875,0x2cb0a8d5,0x2e99affc,0x3000afbc,0x2f6eac07,0xac872934,0xa993a8d5,0x2ed0afaf,0x2cb0afaf,0xaf462e1f,
0xaff42ed0,0x2b5ead72,0xad271cb6,0xaff42fe6,0xa44e2dba,0x9fd9a6a1,0xaf302fd4,0xae5e2f6e,0x2fbcad27,0x2d4dabb7,0x9fd92d00,0x2cd8ae1f,
0x2c87af80,0x2f5aae7c,0x2f5aac32,0x26a1aaaa,0xacb01648,0x2fffafdd,0x2d72afd4,0xa7651648,0xafaf2f91,0x2f1aafbc,0xab5ea44e,0xad002b05,
0x2b05230e,0xa44e28d5,0xafbc2fa0,0x2f91af02,0x3000aed0,0x26a19cb6,0xa5db2d72,0x3000afe6,0x2aaaaeb5,0x2c32a9f1,0x2e7ca9f1,0x2f80afdd,
0xad27244e,0x2e3fad4d,0x2f02affc,0x2e1faee9,0xaa4e2e5e,0xaeb52f30,0xac5d1fd9,0x9648244e,0x2cb0a30e,0xad722e1f,0xafff2f1a,0x2765a30e,
0x2ff8af46,0xabb72cb0,0xabb72ed0,0x2b5ea993,0x2b05ae99,0xa81429f1,0x2c079648,0x2d4dac87,0xafa02fe6,0xafaf2f80,0x2d00af46,0xafa02fc9,
0xa9342dba,0xafed2fd4,0xa814a6a1,0xaf302f6e,0x2c87a44e,0xb0002ffc,0xaf6e2d4d,0xae992ee9,0x2fffaf02,0xafe62ff8,0xaed02ff8,0xaddc2e3f,
0xaed02c87,0xaaaa2a4e,0x2f80adba,0xacb02c87,0xafaf2fed,0xab5e2b05,0x2f1aaffc,0xad002cd8,0xab052e1f,0xac072bb7,0x2814ad00,0xad4d2d27,
0x29f11cb6,0xac5d2c32,0xac5d2515,0xad962d72,0x2d722d96,0x25152c5d,0x2c322c5d,0x1cb6a9f1,0x2d272d4d,0xad00a814,0x2bb72c07,0x2e1f2b05,
0x2cd82d00,0xaffcaf1a,0x2b052b5e,0x2fed2faf,0x2c872cb0,0xadbaaf80,0x2a4e2aaa,0x2c872ed0,0xae3faddc,0xaff8aed0,0xaff8afe6,0x2f022fff,
0xaee9ae99,0xad4daf6e,0xaffcb000,0x244e2c87,0xaf6eaf30,0x26a1a814,0xafd4afed,0xadbaa934,0xafc9afa0,0x2f462d00,0xaf80afaf,0xafe6afa0,
0xac87ad4d,0x9648ac07,0x29f12814,0xae99ab05,0xa993ab5e,0x2ed02bb7,0x2cb02bb7,0xaf46aff8,0xa30ea765,0x2f1a2fff,0x2e1f2d72,0xa30eacb0,
0x244e1648,0x1fd92c5d,0x2f302eb5,0x2e5e2a4e,0x2ee92e1f,0x2ffc2f02,0x2d4d2e3f,0xa44ead27,0x2fdd2f80,0x29f12e7c,0x29f12c32,0x2eb52aaa,
0x2fe63000,0xad72a5db,0x1cb626a1,0x2ed03000,0x2f022f91,0xafa0afbc,0xa8d5a44e,0xa30e2b05,0x2b052d00,0xa44e2b5e,0xafbcaf1a,0x2f912faf,
0x16482765,0xafd4ad72,0xafddafff,0x16482cb0,0xaaaaa6a1,0xac32af5a,0xae7caf5a,0xaf80ac87,0xae1facd8,0x2d001fd9,0xabb7ad4d,0xad27afbc,
0xaf6eae5e,0xafd4af30,0x26a19fd9,0xadbaa44e,0xafe6aff4,0x9cb6ad27,0x2d722b5e,0xaed0aff4,0xae1faf46,0x2faf2cb0,0x2faf2ed0,0x28d5a993,
0xa934ac87,0x2c072f6e,0x2fbc3000,0x2ffc2e99,0xa8d5acb0,0x2875aaaa,0x2e3f2f80,0xa8d5aed0,0x29341648,0x2fed2eb5,0x28142c5d,0x2f302a4e,
0x2e992cd8,0x16482d4d,0xa9f19fd9,0x2c872fbc,0x2fff2faf,0xafe6ad27,0xaed0ad27,0xaddca30e,0x2fc92e99,0x2f802f5a,0xaf46ad96,0x2fe62e99,
0x2f022fed,0xa8d52b05,0xafa0affc,0xa30e2cd8,0x29342d27,0xafbcaf02,0xac07ae3f,0xaffcae1f,0xaa4e9cb6,0x26a1ac32,0x26a1a515,0x1648ad72,
0xaaaa29f1,0xaed025db,0xacb025db,0x2f801648,0xaf1aaf91,0x2875ae5e,0xae3fafed,0xab5e2d4d,0x2c07a875,0x2b052ff8,0x2d4da17e,0xa814aff4,
0x2eb52fc9,0xaf6ead72,0x2dba2fff,0x2eb52e7c,0xaf02af80,0xab5eafe6,0xab5eafc9,0xa30e2f46,0x2cd8a6a1,0x2f302d96,0x2f9129f1,0xac07afd4,
0x2d962ffc,0xafdda44e,0x25db2ee9,0x2f5a2d4d,0xae7ca17e,0x2d72abb7,0xafffad00,0xafc9a17e,0x2c5da934,0x2f5aa44e,0x30002cd8,0xaeb5adfe,
0x2d722ff8,0xacb02d00,0xa7652d00,0x2fff28d5,0xaf02a515,0x217eaf80,0xaf1aaf46,0xaf022765,0xa814af5a,0x2b052fdd,0x2d4da5db,0x2c07ad96,
0x2e5e2fa0,0x29342ff4,0xab052bb7,0x2ee9a8d5,0xaeb59cb6,0xad96aed0,0xad96afe6,0xac872d72,0xa765af6e,0x2f802c5d,0x2f4625db,0x2515af6e,
0x2ff42d4d,0xaff8a44e,0x217e2ee9,0x28752ffc,0xad4d2875,0xafbc217e,0xacd8aff8,0x1fd92ff4,0xaa4eafe6,0x2e99aaaa,0x2fd42993,0xaa4eafc9,
0x2fff2c87,0xacb02d96,0xa7652d96,0x2d722eb5,0xab5e2c07,0x2875af30,0xae3faf91,0xaf1aacd8,0xad96afbc,0xa5dbaffc,0x2fdd2934,0xaf5aac07,
0x2fc92875,0x2aaa2fa0,0xa9932d27,0x2fe62875,0xa8d52d72,0xad00aed0,0xad00afe6,0xaff89cb6,0xad4dafd4,0x2e5e2d96,0x2fed29f1,0x2f91a6a1,
0x2e1fa765,0x2ff49cb6,0xa8752ddc,0x2e1facb0,0x1fd92f5a,0xafbc25db,0xacd8afdd,0xad4d2d96,0xaeb5aee9,0x2f5aa934,0x30002b05,0x2c5dae5e,
0x2f80230e,0xaed02b5e,0xacb02b5e,0xaaaa2f02,0x2cb02fd4,0x1cb63000,0xaddcaf5a,0x27652fd4,0xaff4ac07,0xa17eaffc,0x2ff82934,0xa875afbc,
0x2dfea8d5,0x244e2ff4,0xacd82bb7,0x29342fa0,0x96482f46,0xa5dbafe6,0xa5dbafc9,0xa9f1af80,0xafff9648,0xae7ca6a1,0xafc9a6a1,0x2d722a4e,
0x2ff81fd9,0x230e2ee9,0x2faf2814,0x217eaf91,0xafeda30e,0x2d4dafa0,0xaf91a8d5,0xae5e2f02,0x2fdd2515,0xb0002aaa,0x2f6e2993,0x2fdda765,
0x230eafff,0x2d27afc9,0x2d27ae7c,0xafaf2d72,0xa8142fdd,0xaffc2a4e,0xadfe2dba,0x2e5e25db,0x2a4eaf91,0x2c5d2c07,0x2eb5acd8,0x1648af30,
0xac322f1a,0x2993aff4,0xaf462bb7,0xae7c2f1a,0x2fdd1fd9,0x2dba2814,0x2a4e2ee9,0x25dbaf91,0xaf46a8d5,0x2765afaf,0xa515afaf,0xaf802e1f,
0x2e3f2c32,0xafa02ddc,0xa17e2fff,0x2e3f2515,0xacd8adba,0x2dfe26a1,0x2934afd4,0x244eaf6e,0xa8142ff8,0xadfe2faf,0xaffc230e,0x2e5e217e,
0x2c87af46,0x2f5aa515,0x2f5a2765,0x26a1af80,0xae7c2dba,0x9cb6ae99,0xaddcac5d,0xafc92dba,0x2fafab05,0xaf1a2ee9,0x2b5e2e5e,0x2d002934,
0xaf91a30e,0xacd8a8d5,0x2c07afa0,0xaf302f02,0x2dba2c32,0xac5d2fff,0xae992ddc,0x2dba2515,0xa993aeb5,0x2fc9a9f1,0x2fe6a9f1,0x2aaaafdd,
0xa17e2fed,0xa30eadfe,0xafaf9fd9,0xaff82c07,0x2a4eafed,0x2eb5af91,0x2c5d2d4d,0x1648ae5e,0xae7c2e3f,0xaddca17e,0x9cb6afa0,0xafc92e3f,
0x2ff8a993,0xabb72fe6,0xabb72fc9,0x2b5e2aaa,0xaf30a5db,0x2fbcaa4e,0x2ee9adba,0x2dfeafdd,0x2f1a2515,0x2bb72993,0xaff42aaa,0x2f1aa765,
0xab05adba,0x2e5eafd4,0x2ee926a1,0x2934af6e,0xa5db2fed,0xadba9fd9,0xaa4eadfe,0xafdd2c07,0x2ddcaf02,0xacb02ff8,0xa7652ff8,0x9cb62e3f,
0xac322fdd,0xaf462f6e,0x2993b000,0xae7c2fdd,0x2fafacd8,0x2b5e2934,0xaf1a2dfe,0x2d00244e,0xaf30a17e,0x2ee9afaf,0x2fbca30e,0x2dfeaff8,
0x29f12ddc,0xac5da765,0xac5dacb0,0xad969cb6,0xa993aa4e,0x2765ac87,0xa515ac87,0xaaaa2dba,0xafa02f30,0xabb7244e,0xaff42e5e,0x28d51fd9,
0x28142bb7,0xaf912e1f,0x1fd92d27,0x2ee9ad00,0x2fd4aed0,0xaf5a2fff,0x3000addc,0x2fd4afe6,0x2fafaf46,0x2fa0ae7c,0x2fa0ac32,0xad002993,
0xa44eac5d,0x2f91b000,0x2b05af5a,0xafbc2eb5,0xb0002dfe,0x2c87ae5e,0xae992814,0xaf6e2ffc,0xa5152e1f,0x9cb6a875,0xad722ff4,0xac322e1f,
0x26a12b05,0xa9f12cd8,0xad962fed,0x2fd4affc,0x2fffae1f,0x2515230e,0x2c32230e,0x2ddcaf1a,0x2875ae7c,0x2d27aaaa,0x2fa0af80,0x2875ac32,
0xaee929f1,0x2f91ae99,0x9fd9ac87,0xa8149648,0xafed2f1a,0xaf302e3f,0xa934a875,0xa8142b5e,0xa6a12ddc,0xb0002fc9,0xb0002e7c,0x25db1cb6,
0x2ed0aa4e,0xaf462fd4,0xa9932e99,0x2cb0aa4e,0x2e3faffc,0xad272e5e,0x2e1fa814,0x2f02adfe,0x9fd9abb7,0x2c07ad27,0x2fedae1f,0xadfe2d00,
0xaf6e2cb0,0x25dba993,0x2c5daf46,0xaf6e2ed0,0xaddc2fdd,0xa5159648,0xac329648,0xafff2fd4,0x28d52814,0xabb72934,0xaff42f30,0xafa02fed,
0x3000aee9,0x2e99adfe,0xac872f30,0x2f6eafbc,0x2c32af02,0x2f80af1a,0x2aaa217e,0x2e7caf02,0xab5e9cb6,0x2ff4afc9,0x2ff4ae7c,0x2d27addc,
0xaffc2eb5,0x2fedb000,0x2cd8af5a,0x2b05ac5d,0xa17e2c32,0xad002d72,0xabb71cb6,0xa17e2515,0x2dfea9f1,0xac072c87,0xafed2e99,0x1fd91648,
0x2fd4afbc,0xa9f12b05,0xad962f91,0x26a1a44e,0x2aaaae3f,0xa76528d5,0x251528d5,0x2993a875,0xafe62eb5,0xaddc2dba,0x2fffaf6e,0xaed02eb5,
0xae3f2fbc,0xae1f2dfe,0x2d27af30,0xaf022ee9,0x9fd92b5e,0xae5e2e3f,0xa44ea875,0xaf302f1a,0x2d96a993,0xae992e7c,0xae992c32,0xaf5a2f46,
0x299329f1,0xa76525db,0x251525db,0x2aaa1648,0x28d52934,0xaf02acd8,0x230e244e,0x2fa02dfe,0x28142875,0xaf91aff8,0x1fd9217e,0x2ee92ff4,
0x26a12765,0xaa4eaddc,0x16481cb6,0x26a12cb0,0xaf02af46,0xab5eae7c,0xab5eac32,0xa30e2993,0xae5eaeb5,0x2b059648,0xa934aa4e,0xaee9ac5d,
0xad96adfe,0x2fdd2e5e,0xa5dba814,0xaf5aaffc,0xacb0ad27,0x2ddc2faf,0x9cb6a30e,0xa765ad27,0x2fd42f91,0x2f6e2fed,0x2dba2e5e,0xa6a1ad4d,
0x2fff2ff8,0x25152d00,0x2c322d00,0x2ddc28d5,0x2faf2fe6,0xae1fa993,0x28d52aaa,0x2faf2fc9,0x2ee92f5a,0xaf91afdd,0x1fd925db,0x28142d96,
0xacd8ab5e,0xaf91ad00,0xaf30afaf,0x2c072f1a,0xaeb5addc,0xad96afc9,0xad96ae7c,0xac879cb6,0xafc9af5a,0x2993a6a1,0xaaaaac87,0xafe6af5a,
0xaff4affc,0x2ff82e5e,0xa17ea814,0xa875adfe,0x9fd9a875,0x2c07a17e,0x2fed2ff8,0xadfeaff4,0x29f12515,0x2fdd2f46,0x2eb52f80,0x29f1a765,
0x2ddc2c87,0x25152d96,0x2c322d96,0x2fff2eb5,0x2fa02ee9,0xaf02ab05,0x230e2934,0x28d52e5e,0x2d962ee9,0x25db2dfe,0xafddaf30,0x2f5a2fbc,
0x27652bb7,0xaf46ab5e,0xaf80aff8,0xa5152bb7,0xa8d59cb6,0xad00afc9,0xad00ae7c,0xaff8addc,0xadfeac5d,0x2cd89648,0xa44eaa4e,0xa934aeb5,
0xaff8afc9,0xae3fafff,0x2f022d72,0xaff8ae7c,0xadfeaf5a,0x2c07a5db,0x2fed2fdd,0x9fd9ad96,0xa6a1ac07,0x2f6e2f91,0x2dba2f30,0x2fd42cd8,
0x2aaa230e,0xa7652b5e,0x25152b5e,0x29932f02,0x2e7c2c5d,0x2fff2d96,0xad72a9f1,0x2fc92c5d,0x2ff42fbc,0x217e2dfe,0xaff8af30,0x28752ee9,
0x2d4d2f1a,0xafedad00,0xae5eafaf,0xaf91ab5e,0x96482993,0xa5dbae7c,0xa5dbac32,0xa9f1af46,0xaddc9648,0xafe6a6a1,0xaed0a6a1,0x2fff2a4e,
0xad27affc,0x2d00ac07,0xabb7afbc,0xae1f2934,0x2e5e230e,0x1fd92fa0,0x2f3028d5,0x244eaf02,0x2c872fe6,0xadbaaf46,0x2a4e2f80,0x2c872fc9,
0x230ead72,0x2d27ac32,0x2d27a515,0xafaf9cb6,0x2fbc2e99,0x9fd92f6e,0x2d4d3000,0x2cd8ac87,0xaa4e2b05,0xac5dafbc,0xaeb5a44e,0x96482f91,
0xaed0afa0,0x2f802d00,0xaaaaafaf,0xacb0afa0,0x2c872ffc,0x16482fbc,0xa9f12c07,0x2e99a934,0xaf80a8d5,0xac32afaf,0xae7cafaf,0xaaaa2e1f,
0xa30eaed0,0x2f1a2d72,0x2e1f9cb6,0xa30eafe6,0x2fed2dba,0xaffca6a1,0x2b052fd4,0x2cd82f6e,0xafbcae1f,0xad4daf02,0x1fd9ae3f,0xacd82d27,
0x2c87a993,0x2f5a2cb0,0x2f5a2ed0,0x26a1af46,0x2cb03000,0xafffa5db,0xad7226a1,0x27653000,0xafafa934,0x2f1aa814,0xab5eafed,0xad00af30,
0x2f30230e,0x2fed28d5,0x28142fa0,0x2934af02,0x16482ed0,0xafd41cb6,0xafddad72,0x16482fe6,0xaf46aeb5,0x2ed0a9f1,0x2cb0a9f1,0xa993afdd,
0x2e1fa44e,0xad002d4d,0x2bb72ffc,0x2d272ee9,0xaa4e2cd8,0xaeb52b05,0xac5daffc,0x96482fed,0xacb0aff4,0x2d72ad27,0x2fff2b5e,0xa765aff4,
0x2ff82aaa,0xabb72e7c,0xabb72c32,0x2b5e2f80,0xab052c87,0x2814af6e,0xac07b000,0xad4dae99,0xa8d5afe6,0x2875af80,0x2e3f2f46,0xa8d5afc9,
0x2f912dba,0xa44e2fd4,0xafbca6a1,0x2b052f6e,0xae99244e,0x9648affc,0x29f1ad4d,0xac87aee9,0x1cb6af02,0x25152ff8,0x2c322ff8,0x2d722e3f,
0x2ed02e99,0x2aaa2f5a,0xaf80ad96,0x2cb02e99,0xafafa44e,0xab5eaf30,0x2f1a9fd9,0xad00ae5e,0x2b05ad27,0x2c072f02,0xa8142e3f,0x2d4d2e1f,
0x29f12fff,0xac5daed0,0xac5dafe6,0xad96addc,0xaf46aa4e,0xac32ac87,0xae7cac87,0x29932dba,0x2f1a2b05,0xa8752fed,0x2e3f2cd8,0x2b5eaffc,
0xaee9abb7,0x2f30ae1f,0xadfead27,0xafbc2d00,0x2eb52c32,0xaf6e1cb6,0x2dba2d72,0x2eb52515,0x2fafa993,0x2fa0a515,0x2fa02765,0xad00aaaa,
0xafed26a1,0xa934ad96,0xaf30a9f1,0xa8142fd4,0x30009fd9,0xac872fed,0x2e992c07,0x2f6eadfe,0xafe6a17e,0x2fffabb7,0xaddcad00,0xaed0a17e,
0xac5d2f30,0xaf5a2e5e,0xb000244e,0x2eb51fd9,0x2ddcae1f,0x2e7c230e,0x2fc9230e,0x1cb6af1a,0xaf022cb0,0x217eaf46,0xaf1aa993,0xaf022ed0,
0x2fbca9f1,0xaf302e99,0x2dfe2c87,0x2ee91648,0xa44eafa0,0x2b05aff4,0x2f91abb7,0xafbc28d5,0xa6a12fff,0xb0002c32,0xb0002515,0x25db2ddc,
0x2c32af6e,0x2aaa2c5d,0x2f8025db,0x2e7caf6e,0xae3f2dfe,0x2d27afed,0xae1fac07,0xaf021fd9,0x2dfe2bb7,0x28142d27,0xae5e2e1f,0x2ffcad00,
0xaa4eae7c,0x2e99af80,0x2fd4aaaa,0xaa4eac32,0x9cb62fdd,0xae7c9648,0xafc99648,0xaddc2fd4,0x2b5eafbc,0xa8752f91,0x2e3f2b05,0x2f1aa44e,
0xb0002814,0xae991fd9,0x2c87af91,0xaf6e2ee9,0x2ed02875,0xa9932fa0,0xaf462d27,0x2cb02875,0xab5eaddc,0x2ff4ac32,0x2ff4a515,0x2d27afff,
0x9fd92fd4,0xa44ead96,0xae5ea9f1,0xaf3026a1,0x2e1faed0,0x2ff4addc,0xa8752fff,0x2e1fafe6,0xaffc29f1,0xa814ac87,0x2e5eae99,0xadfe9648,
0x2eb52814,0xaf5a2f30,0xb0002934,0xac5d2fed,0xa993ae3f,0x2c3228d5,0x2e7c28d5,0x2f46a875,0xa5152fd4,0xad723000,0x9cb6af5a,0xac322fd4,
0x2e3faee9,0x2e1f9fd9,0xad272f91,0x2f02a814,0xaffc28d5,0x2cd8aff4,0x2fedabb7,0x2b05afa0,0x2d962aaa,0xae992515,0xae99a765,0xaf5a2993,
0x1cb6adba,0x2cb0aeb5,0x2765aeb5,0xaddc2f6e,0xaff82d4d,0xa30ea814,0xafaf2c07,0xa17e2b05,0xa44e2e3f,0xadfe2b5e,0xa9342f1a,0x2cd8a875,
0x2fddacb0,0xb0002f80,0x2f6eaaaa,0x2fddaed0,0x2d001cb6,0x217e2765,0x217e2cb0,0x2bb7addc,0x2ee9afdd,0x2d4daa4e,0x2ffcadba,0xa44ea5db,
0xa9f1a934,0x2fd4aee9,0x26a1ae5e,0xad962b05,0xafc92f1a,0x2f46aff4,0xaf802bb7,0xafe62f1a,0xafdd2d4d,0xadba2c07,0xaa4ea814,0xa5db2b05,
0xaaaa2f1a,0xafc92f02,0xafe62f02,0x2993a17e,0x2e3fa765,0xafa02fff,0xa17e2d72,0x2e3facb0,0x2e5eb000,0xad4d2eb5,0x2f91ac5d,0x2fedaf5a,
0x2ee9aff8,0x2ffcafaf,0x2d4da30e,0xa44ea17e,0xa5dbaaaa,0x2f6eafe6,0x2f6eafc9,0xac5d2993,0xafe62dba,0x2d72ae99,0x9cb6ac5d,0xaed02dba,
0xabb72f30,0x28d5ac07,0xafa02cd8,0xaff42f91,0xa9342e3f,0xae5e2f1a,0xaee92b5e,0x2b05a875,0x2dbaa765,0xac5d2d72,0xae992fff,0x2dbaacb0,
0x2f80afd4,0xa7652a4e,0x25152a4e,0x2f46ae99,0x217eacd8,0x230e1fd9,0x2fafad4d,0x2ff8afbc,0xa9f1a44e,0x26a1a934,0x2fd4adfe,0xad962cd8,
0xafe62e3f,0x9cb6a17e,0x2d72afa0,0xaed02e3f,0xad272f80,0xa8752515,0xa875a765,0xafa02f46,0x293425db,0xac072a4e,0xafbc2dba,0xaffc2fdd,
0x2f1aacb0,0x2bb7aaaa,0xaff42f80,0x2f1aaed0,0x2f30b000,0x2cd8ac5d,0xac072eb5,0x2f91af5a,0x25dbacd8,0x2dbaad4d,0x2a4e1fd9,0x2fddafbc,
0xad722875,0x2e7cae1f,0x2fc9ae1f,0x2fffaff4,0xafc92fdd,0xaf802f6e,0x2f46b000,0xafe62fdd,0xabb72e5e,0xafa02f91,0x28d5ad4d,0xaff42fed,
0x2934217e,0xafbc2faf,0xac07230e,0xaffc2ff8,0x2f5aad72,0xafd42fc9,0xafd42e7c,0xb0002fff,0x9cb69648,0xacb0a6a1,0xa765a6a1,0x2ddc2a4e,
0xa17e9fd9,0xaff4aee9,0xa875a814,0x2ff82f91,0xa44ea30e,0xadfeafa0,0xa934a8d5,0x2cd82f02,0xa5dba515,0x9648aaaa,0xa9f1a993,0xa5db2765,
0xa30e9cb6,0xad27a765,0xad27acb0,0x2faf2ddc,0xa814a5db,0xaffcaf5a,0xadfead96,0x2e5e2fdd,0xaa4ea934,0xac5daee9,0xaeb5ae5e,0x96482b05,
0xac32ab5e,0x2993a30e,0xaf46af02,0xae7cab5e,0xa5db9fd9,0xad96a814,0xaf5aaee9,0x2fdd2f91,0xaaaaa8d5,0xafc9afaf,0xafe6afaf,0x29932e1f,
0xad00ac32,0xa8d5addc,0xaff8afff,0xad00a515,0xae5eadba,0x2d4d26a1,0xaf91afd4,0xafedaf6e,0xa814a17e,0xadfea875,0xaffcaff4,0x2e5e2ff8,
0xac87aaaa,0xaf5aafe6,0xaf5aafc9,0xa6a12993,0xae7cad96,0x9cb6ac87,0xaddcaeb5,0xafc9ad96,0xafafaf30,0x2f1a2c07,0xab5eacd8,0xad00af91,
0xa934a30e,0xae5ea8d5,0xaee9afa0,0x2b052f02,0xad96ac32,0xaeb5afff,0xac87addc,0xad96a515,0xaf80aeb5,0x2765a9f1,0xa515a9f1,0xaf46afdd,
0xaff8afed,0x2ff42dfe,0x28751fd9,0x217eac07,0xaa4ea44e,0xaeb5a934,0xac5dadfe,0x96482cd8,0xae7cad00,0xaddcaff8,0x9cb6a8d5,0xafc9ad00,
0xaff8af80,0x2bb7a515,0x2bb72765,0xab5eaf46,0xaf30afdd,0x2fbc2f5a,0x2ee92d96,0x2dfe25db,0xab5ea515,0xaf02a993,0xa30eaaaa,0xab5e2765,
0xaf30adba,0xacd8afd4,0x2c0726a1,0xaf91af6e,0xafddafed,0x2d961fd9,0x2f5a2dfe,0x25dbac07,0xad72af02,0x2e7c2ff8,0x2fc92ff8,0x2fff2e3f,
0xac32a5db,0xaf46a9f1,0x29939648,0xae7ca5db,0xafafae5e,0xab5eaf91,0x2f1a2d4d,0xad00afed,0xaf30aff8,0x2ee92875,0x2fbc2ff4,0x2dfe217e,
0xa9f1ad72,0x2c5d2fc9,0x2c5d2e7c,0x2d962fff,0xaf80aa4e,0xafc9ac87,0xafe6ac87,0x2f462dba,0xa8d5af30,0x2f02a44e,0xa30eae5e,0xafa09fd9,
0x2fbc2bb7,0xa9342e1f,0x2ffc2d27,0x2c07ad00,0x26a12ed0,0xaa4eafff,0x16482ddc,0x26a12fe6,0xafafaaaa,0xafa0acb0,0xafa0aed0,0x2d002f80,
0xa44eaeb5,0x2f919648,0x2b05aa4e,0xafbcac5d,0x30002d4d,0xac872cd8,0x2e992fbc,0x2f6e9fd9,0xa5152d27,0x9cb6afaf,0xad72230e,0xac322d27,
0xafd4ab05,0xaf6eacd8,0xadbaafed,0x26a12ffc,0x1cb6ae1f,0x2fe6230e,0x2ed0230e,0xad72af1a,0x2faf2e7c,0xae1f2aaa,0x28d52f80,0x2faf2c32,
0xac0729f1,0x2934ae99,0xaffcac87,0xafbc9648,0xafedab5e,0xaf30ad00,0xa934afaf,0xa8142f1a,0x26a1ad72,0x30002765,0x30002cb0,0xa5dbafff,
0x2ed02f5a,0xaf4626a1,0xa9932c87,0x2cb02f5a,0xae3f1fd9,0x2d27acd8,0xae1fafbc,0xaf02ad4d,0xaffcabb7,0xaee9ad27,0x244eae1f,0xad4d2d00,
0x29f1acb0,0x2fdd2993,0x2eb52f46,0x29f1aed0,0x2d722fdd,0xafe69648,0xaed09648,0x9cb62fd4,0xafa0a814,0x2f02a934,0xa30eaf30,0xa8d5afed,
0xb000ac07,0xae99ad4d,0x2c87ab05,0xaf6e2814,0x2c32abb7,0x2f802b5e,0x2aaa2ff8,0x2e7cabb7,0x2b5e2fff,0xaff4a765,0xaff4acb0,0xad272d72,
0xaffcac5d,0x2fed9648,0x2cd8aa4e,0x2b05aeb5,0xaff8ac32,0xae3fad72,0x2f029cb6,0xaff8a515,0x2d4da9f1,0x2ee92c87,0xa44e2e99,0x2ffc1648,
0x26a12fbc,0xaf6eab05,0xadbaaf91,0xafd4244e,0xaf46ae3f,0x2fc928d5,0x2fe628d5,0x2f80a875,0xafe6ac5d,0xaddcad96,0x2fff29f1,0xaed0ac5d,
0x2e3fa814,0x2e1f2d4d,0xad272b05,0x2f022c07,0x9fd92f1a,0xae5ead00,0xa44eafaf,0xaf30ab5e,0xad96af80,0x2e992cb0,0x2e992ed0,0x2f5a2aaa,
0xad72adba,0xa515aeb5,0xac32aeb5,0x9cb62f6e,0x2d272dfe,0xad002fbc,0x2bb72ee9,0x2e1faf30,0xacd8ae3f,0x2ffcab5e,0xab05af1a,0xafed2875,
0x2c872e7c,0xadbaa993,0x2a4e2f46,0x2c872c32,0xad00addc,0xa17eaed0,0xa17eafe6,0xabb72fff,0x2c072e99,0xadfe2f6e,0x9fd93000,0x2fedac87,
0xa9f1af30,0x2fd4a814,0x26a1afed,0xad96a934,0x27652fa0,0xaaaaad00,0xa9932faf,0xa5152fa0,0xac87adfe,0x9648aee9,0x29f1afbc,0xae992f30,
0x29932f1a,0xaed02f02,0xacb02f02,0x2f46a17e,0xa30eafc9,0x2f1a9cb6,0x2e1faddc,0xa30eae7c,0xa44e3000,0x9fd9aeb5,0xaf302c5d,0xae5e2f5a,
0xac07ae1f,0x1fd9af02,0x2dfeae3f,0xafed2d27,0x25db2f80,0xaf6e2e7c,0xaf6e2c32,0x2c5d2aaa,0x2515b000,0x2ddc25db,0x2fffa6a1,0x2c32b000,
0xabb72f91,0x28d5afbc,0xafa0a44e,0xaff42b05,0xab05ae3f,0x244eaf1a,0x2fbcab5e,0xaf912875,0x16482fc9,0xafd42ddc,0xafdd1cb6,0x16482e7c,
0x2aaaafd4,0x2c322a4e,0x2e7c2a4e,0x2f80ae99,0xae1f2e5e,0x2d00affc,0xabb7adfe,0xad27a814,0xa9f1ae5e,0x26a1af30,0x2fd49fd9,0xad96a44e,
0xa5152ff4,0xafff2d27,0xaddcab5e,0xac322ff4,0x2d27af46,0x28752cb0,0x28752ed0,0x2fa0a993,0xaf912c87,0x2ee9af6e,0x2814b000,0x1fd9ae99,
0xa8d5ae7c,0x2875af46,0x2e3f2993,0xa8d5ac32,0xa9343000,0xafed2c5d,0xa814aeb5,0xaf302f5a,0x2e99ae5e,0x16482dfe,0xa9f12ffc,0x2c872814,
0xafff2875,0x2fe6ae1f,0x2ed0ae1f,0x2ddcaff4,0xa765ae99,0x2993af5a,0x2aaa2d96,0x2515ae99,0xabb72fed,0xafa02b05,0x28d5affc,0xaff42cd8,
0x2f91ad27,0xa8142f02,0xaee92e3f,0x9fd92e1f,0xaf5a9cb6,0x2fd4ac32,0x2fd4a515,0x3000ad72,0x2aaaaf6e,0x2ed0afdd,0x2cb0afdd,0xaf803000,
0xaf1a2934,0x2875acd8,0xae3f244e,0xab5e2dfe,0xac072faf,0xab05217e,0xad4d2ff8,0x2814230e,0x2eb5a765,0xaf6e2ddc,0x2dba9cb6,0x2eb5acb0,
0x2bb7af80,0x2f1aafe6,0x2f1aafc9,0xaff42f46,0xae5e26a1,0x2b05ad96,0xa934a9f1,0xaee92fd4,0xadba2ffc,0xa5dba44e,0xafdd2ee9,0xaa4e2d4d,
0x2cb0217e,0xaddc2bb7,0x1cb62d00,0x2765217e,0x2c5daf91,0x2f5aafed,0x3000ae5e,0xaeb52d4d,0xad72217e,0x2cb0ae3f,0x2765ae3f,0xafff2fa0,
0xaf022fe6,0x217ea993,0xaf1a2aaa,0xaf022fc9,0x28142a4e,0xab0525db,0xad4d2fdd,0xac072dba,0x2cd8afa0,0x2f91aff4,0x2f30abb7,0xac0728d5,
0xac5d9cb6,0x2dbaaed0,0x2dbaafe6,0xae992d72,0xafc92f6e,0x2993ac5d,0xaaaaa5db,0xafe62f6e,0xa30e2d4d,0xa17ea44e,0xaff82ee9,0xafaf2ffc,
0x2d4dafaf,0x2fbcaff8,0x2cd8a17e,0x9fd9a30e,0xaa4ea515,0x2e99af46,0x2fd4af80,0xaa4e2765,0xafff2e99,0x2cb0adba,0x2765adba,0xad722c5d,
0xab5e2ee9,0x2875ab05,0xae3f2934,0xaf1a2e5e,0x2dbaafbc,0x2fddaffc,0x25db2934,0x2a4eac07,0xa765a875,0x2f46afa0,0x2f80ad27,0x2515a875,
0xafa02d72,0x2e3faed0,0x2e3fafe6,0xa17e9cb6,0xadfe2fd4,0x2cd8ad96,0xa44ea9f1,0xa93426a1,0x2e1fafc9,0x2ff4afff,0xa8752d72,0x2e1fae7c,
0x9fd9aa4e,0x2fbcafdd,0x2cd8a5db,0x2d4dadba,0xaeb52c07,0x2f5aaf91,0x3000af30,0x2c5dacd8,0xaf802ff4,0x2ed0af1a,0x2cb0af1a,0x2aaaabb7,
0x2e7cafd4,0x2fffb000,0xad722f5a,0x2fc9afd4,0x230eac07,0x2ff8affc,0x217e2934,0x2fafafbc,0xad4d28d5,0x2fedaff4,0x2e5eabb7,0x2f91afa0,
0xb0002f46,0x2fddafe6,0x2fddafc9,0x2f6eaf80,0xaaaaaa4e,0xaed0ac87,0xacb0ac87,0x2f802dba,0xab5eab05,0xafafafed,0xad00acd8,0x2f1a2ffc,
0xac07abb7,0xab05ae1f,0xad4dad27,0x28142d00,0xac5dac32,0x29f19cb6,0xad96ad72,0xac5da515,0xafafaf80,0xafa0afe6,0xafa0afc9,0x2d002f46,
0xafedafd4,0xa934adba,0xaf30af6e,0xa81426a1,0xb000affc,0x2c87244e,0xae99aee9,0xaf6ead4d,0xafe6aff8,0x2fff2f02,0xaddcae3f,0xaed0aff8,
0xaeb5af30,0xaa4eae5e,0x9648a44e,0xac5d9fd9,0xad72ae1f,0x2cb0230e,0x2765230e,0xafffaf1a,0xabb7acb0,0x2ff82f46,0x2b5e2993,0xabb7aed0,
0xa814a9f1,0x2b052e99,0x2d4d2c87,0x2c071648,0xa44ea8d5,0x2b05a30e,0x2f912f02,0xafbcafa0,0x26a11cb6,0x30002ed0,0x30002fe6,0xa5dbad72,
0x2c3229f1,0x2aaa2eb5,0x2f802fdd,0x2e7c29f1,0x2e3f2d4d,0xad27a44e,0x2e1f2ee9,0x2f022ffc,0x2d4d2bb7,0x2fbc2d27,0x2cd82e1f,0x9fd9ad00,
0x2f5a2e7c,0x2c872f80,0x26a12aaa,0x2f5a2c32,0x2fff2fdd,0xacb09648,0xa7659648,0x2d722fd4,0x2f1a2fbc,0xafafaf91,0xad00ab05,0xab5e244e,
0x30002fbc,0x2e992ffc,0xac87a934,0x2f6e2c07,0x2ed02faf,0xa99328d5,0xaf46ae1f,0x2cb02faf,0x2b5e2d72,0xaff4aed0,0xaff4afe6,0xad279cb6,
0x9fd926a1,0xa44eadba,0xae5eaf6e,0xaf30afd4,0x2d272ed0,0x230e2ddc,0xafafafff,0x2d272fe6,0x1fd929f1,0xafbcac87,0xacd8ae99,0xad4d9648,
0xac5da814,0xaa4eaf30,0x9648a934,0xaeb5afed,0xaf80ae3f,0x2ed028d5,0x2cb028d5,0x2aaaa875,0xa51526a1,0xad721648,0x9cb6aa4e,0xac3226a1,
0xae3fac07,0xae1faffc,0x2d272934,0xaf02afbc,0xaffcafa0,0x2cd8a30e,0x2fed2f02,0x2b05a8d5,0xad96af46,0x2e992fe6,0x2e992fc9,0x2f5a2f80,
0xafffadba,0xae7caeb5,0xafc9aeb5,0x2d722f6e,0x217ead4d,0x2ff42814,0x2875ac07,0xaff8ab05,0x2fed2e3f,0xad4d2b5e,0x2f912f1a,0x2e5ea875,
0xa5db2cb0,0x9648af80,0xa9f12aaa,0xa5db2ed0,0xad00afff,0xa17eafc9,0xa17eae7c,0xabb72d72,0x2ee925db,0x2d4d2f5a,0x2ffc2d96,0xa44eafdd,
0x29f12f91,0xafd4ac07,0xa6a12cd8,0x2d962f30,0xafc9ab5e,0x2f46a30e,0xaf80af02,0xafe6ab5e,0x25dbad4d,0x2d96ac07,0x2f5a2814,0xafddab05,
0x2f462f1a,0xa7652f02,0x25152f02,0x2f80a17e,0xad002765,0xa8d5afff,0xaff8ad72,0xad002cb0,0xacd8b000,0x2dfe2eb5,0x2934ac5d,0x244eaf5a,
0x2ee9217e,0x2ffc2875,0x2d4d2ff4,0xa44eaff8,0x25db2f46,0xaf6e2515,0xaf6ea765,0x2c5d2f80,0xafe6ad96,0x2d72ac87,0x9cb6aeb5,0xaed0ad96,
0x2bb7ab05,0xa8d52ee9,0x2fa02e5e,0x2ff42934,0x2f912e3f,0x2cd82f1a,0xac072b5e,0x2f30a875,0xad962765,0xaeb5ad72,0xac87afff,0xad962cb0,
0xa993afd4,0x2fc92a4e,0x2fe62a4e,0x2aaaae99,0x2ff82cd8,0xaff49fd9,0xa8752d4d,0xa17e2fbc,0x29f12fed,0xa6a12f91,0xafd4ad4d,0x2d962e5e,
0xafe6ad00,0x9cb6aff8,0x2d72a8d5,0xaed0ad00,0x2d27a993,0x28752fe6,0x28752fc9,0x2fa02aaa,0x29342fdd,0xac07af5a,0xafbcad96,0xaffca5db,
0xab5e2cb0,0xaf022aaa,0xa30eaf80,0xab5e2ed0,0xab05b000,0x2e5eac5d,0x2ee92eb5,0x2934af5a,0x2fdd2cd8,0xad962d4d,0xaf5a9fd9,0xa5db2fbc,
0xaddc2875,0x2cb0ae1f,0x2765ae1f,0x1cb6aff4,0xafc9a5db,0xaf80a9f1,0x2f469648,0xafe6a5db,0x2bb7acd8,0x2fa02934,0xa8d52dfe,0x2ff4244e,
0x29342ff8,0xafbca875,0xac07aff4,0xaffca17e,0xaf5aaddc,0x2fd42765,0x2fd42cb0,0x30001cb6,0xa993af6e,0x2765afdd,0xa515afdd,0xaaaa3000,
0x28d52f91,0xaf022e5e,0x230e2fed,0x2fa0ad4d,0xa814afaf,0x2f91a17e,0x9fd9aff8,0xaee9a30e,0x26a12fc9,0xaa4ead72,0x16482fff,0x26a12e7c,
0x2bb7af46,0x2f1aae7c,0x2f1aac32,0xaff42993,0xacd82eb5,0xaf301648,0xaf912a4e,0x2c072c5d,0x2dbaadfe,0x25db2e5e,0x2fdda814,0x2a4eaffc,
0xae7c2d27,0x2d72afaf,0xafff230e,0xafc92d27,0x2fd4a934,0x2f6ea44e,0x2dba2cd8,0xa6a1adfe,0xafff217e,0xa515ae3f,0xac32ae3f,0xaddc2fa0,
0x2faf2515,0xae1f2f80,0x28d52f46,0x2fafa765,0xaee9aa4e,0x2f91a5db,0x9fd9afdd,0xa814adba,0x2e5e2b5e,0x29342d00,0xab052faf,0x2ee9af1a,
0xac5daddc,0x2dbaafc9,0x2dbaae7c,0xae999cb6,0x27652f5a,0xaf8026a1,0xaf462c87,0xa5152f5a,0x230eaffc,0x217e2e5e,0x2ff8a814,0x2fafadfe,
0x1fd92faf,0xac072ff8,0xafed217e,0x2dfe230e,0x29f1afe6,0x2fddaaaa,0x2eb52993,0x29f1afc9,0xaddc2e99,0xa515adba,0xac32adba,0xafff2c5d,
0x2fa0ac07,0xaf022f30,0x230e2f91,0x28d52cd8,0xadba2ee9,0xafdd2dfe,0xa5dbaf30,0xaa4e2fbc,0x2fc9abb7,0x2aaa2b5e,0xa9932ff8,0x2fe6abb7,
0xafa09cb6,0x2e3fafc9,0x2e3fae7c,0xa17eaddc,0x2d4d2c5d,0xae5e1648,0xafed2a4e,0xaf912eb5,0xaff82765,0xae3f1cb6,0x2f02addc,0xaff82cb0,
0x2dfe2a4e,0xac072fdd,0xafed25db,0x1fd92dba,0xa6a1aee9,0x2f6ea934,0x2dba2b05,0x2fd4ae5e,0xaaaa2ff4,0x2765af1a,0xa515af1a,0xa993abb7,
0xacb0ac5d,0x9cb6ad96,0x2ddc29f1,0xa765ac5d,0xa30e2fbc,0xaff82dfe,0xa17eaf30,0xafaf2ee9,0x2dfeaf1a,0x244e2d00,0xacd82faf,0x29342b5e,
0xb0002993,0x2fddae7c,0x2fddac32,0x2f6eaf46,0x2ddcb000,0x2fe6afd4,0x2ed0afd4,0xafff2f5a,0xad279fd9,0x2d00aee9,0xabb7a814,0xae1f2f91,
0xae5e2ff4,0x9fd9a8d5,0xaf302fa0,0xa44e2bb7,0x2c872515,0xadba2aaa,0x2a4e2993,0x2c87a765,0x2ff4ad72,0x2e1fac32,0x2e1fa515,0xa8759cb6,
0x2814ae99,0x2ffcaf6e,0x2dfeb000,0xae5e2c87,0xaf5a2b05,0x2eb5afbc,0xac5da44e,0xb0002f91,0xac322fa0,0x2993ad00,0xaf462faf,0xae7c2fa0,
0x2c871fd9,0x16482814,0xa9f12ee9,0x2e99af91,0x2f80afa0,0x2c32a875,0x2e7ca875,0x2aaaad27,0xa30eac32,0x2f1aaddc,0x2e1fafff,0xa30ea515,
0xafed2d96,0x2ffcafd4,0xab05a6a1,0xacd829f1,0xa8142e1f,0xadfe2f02,0xaffc2e3f,0x2e5ead27,0x2e99a993,0xaa4e2cb0,0xaa4e2ed0,0x2fd4af46,
0x2e7cb000,0x1cb625db,0x2ddca6a1,0x2fc9b000,0xa875a934,0x2b5ea814,0x2f1aafed,0x2e3faf30,0xaf302ff4,0xafed2fa0,0xa814a8d5,0xa9342bb7,
0x16482c32,0xafd42fff,0xafdd2ddc,0x16482515,0x2f46ac5d,0xaed02f6e,0xacb02f6e,0x2993a5db,0x2e1fafed,0xad002dfe,0x2bb71fd9,0x2d27ac07,
0xaf5a2cd8,0xac5d2b05,0x2eb5affc,0xb0002fed,0xae7c2ff4,0xaddc2d27,0x9cb6ab5e,0xafc92ff4,0x217e2aaa,0xaf022e7c,0xaf022c32,0xaf1a2f80,
0x2f30ac87,0xafbc2f6e,0xaee93000,0xadfe2e99,0xa8d5a515,0x2875a993,0x2e3faaaa,0xa8d52765,0xaf912d96,0x244ea6a1,0x2fbcafd4,0xab0529f1,
0xae992fed,0x96489fd9,0x29f1adfe,0xac872c07,0x9cb62bb7,0xa515217e,0xac32217e,0xad722d00,0x2c32ae99,0x2f46af5a,0xa9932d96,0x2e7cae99,
0xa875a44e,0x2f1aaf30,0x2b5e9fd9,0x2e3fae5e,0xaf302d27,0x2ee9af02,0x2fbcae3f,0x2dfeae1f,0xaf6e2fff,0x2eb5aed0,0x2eb5afe6,0x2dbaaddc,
0xaddcadba,0xafe6aeb5,0xaed0aeb5,0x2fff2f6e,0xae1fadfe,0xae3fafbc,0xaf02aee9,0x2d272f30,0xae5eae3f,0x9fd9ab5e,0xaf30af1a,0xa44e2875,
0xae99ae7c,0x2d962993,0xaf5aaf46,0xae99ac32,0xad00ad72,0xa17eac32,0xa17ea515,0xabb79cb6,0xac07ac87,0x2dfe29f1,0x1fd99648,0xafedae99,
0xa9f1ab05,0x2fd42fbc,0x26a1244e,0xad96af91,0xa765a8d5,0x2aaa2e3f,0x29932875,0x2515a8d5,0x2e992dfe,0x30002ee9,0x2f6e2fbc,0xac87af30,
0x2f802f1a,0x2c322f02,0x2e7c2f02,0x2aaaa17e,0x2ff42fc9,0xab5e1cb6,0x2d272ddc,0x2ff42e7c,0x2fed3000,0xaffcaeb5,0x2b052c5d,0x2cd82f5a,
0x2c072d27,0x9fd92bb7,0xadfead00,0x2fed2e1f,0x25db2993,0xaf6eacb0,0xaf6eaed0,0x2c5d2f46,0xa5151648,0xaddcafdd,0xafffafd4,0xac321648,
0xabb7a934,0x28d5a814,0xafa0afed,0xaff4af30,0xaf30ae3f,0xafedaf1a,0xa814ab5e,0xa9342875,0xb000afc9,0xa6a1addc,0x25db9cb6,0xb000ae7c,
0xaf46afd4,0x2ed02a4e,0x2cb02a4e,0xa993ae99,0xad27ae5e,0x2e3f2ffc,0x2f022dfe,0x2e1f2814,0xa9f1acd8,0x26a1ab05,0x2fd42ffc,0xad96afed,
0x2515a30e,0x2fff2e1f,0x2ddc2f1a,0x2c32a30e,0x2d272aaa,0x28752e7c,0x28752c32,0x2fa02f80,0x2f912e99,0xaee9a9f1,0xa8141648,0x9fd92c87,
0x2fa02e7c,0x2faf2f46,0xad00a993,0x2fa02c32,0x2f913000,0xa44e2c5d,0xafbcaeb5,0x2b052f5a,0x2c872e5e,0xb000adfe,0xaf6eaffc,0xae99a814,
0x9cb62875,0xa515ae1f,0xac32ae1f,0xad72aff4,0x27652c87,0xa9932a4e,0xaaaaadba,0xa5152c87,0xabb7a44e,0xafa0af30,0x28d59fd9,0xaff4ae5e,
0xaf91ae1f,0x2814abb7,0x2ee92d00,0x1fd9ad27,0xaf5aafff,0x2fd42ed0,0x2fd42fe6,0x30002ddc,0xaf46af6e,0xac32afdd,0xae7cafdd,0x29933000,
0x2b5ea934,0x2faf2cd8,0x2d00a44e,0xaf1aadfe,0x2ee92faf,0xaf30217e,0x2dfe2ff8,0x2fbc230e,0xac5d2765,0x29f1addc,0xad961cb6,0xac5d2cb0,
0x2bb7a993,0x2f1aa515,0x2f1a2765,0xaff4aaaa,0x2e5e2fd4,0xab052dba,0x29342f6e,0x2ee9a6a1,0xadba1fd9,0xa5dbafed,0xafddac07,0xaa4e2dfe,
0xacb0aff8,0x2ddc2f02,0x9cb6ae3f,0xa765aff8,0x2eb52f91,0x2a4e2fed,0x16482e5e,0x2c5dad4d,0xaddc217e,0xae7cae3f,0xafc9ae3f,0x9cb62fa0,
0xabb7afe6,0x2ff82993,0x2b5eaaaa,0xabb7afc9,0x2fbc2a4e,0xaf3025db,0x2dfe2fdd,0x2ee92dba,0xacd828d5,0xaf91230e,0xaf30af02,0x2c072fa0,
0xac5dafff,0x2dbaac32,0x2dbaa515,0xae99addc,0x2fc929f1,0xa9932eb5,0x2aaa2fdd,0x2fe629f1,0xa30e2dfe,0xa17eafed,0xaff8ac07,0xafaf1fd9,
0xadfeafaf,0xa814aff8,0x2e5ea17e,0xaffca30e,0x2f5a2515,0x2c872f46,0x26a12f80,0x2f5aa765,0x9cb62e99,0xae7cadba,0xafc9adba,0xaddc2c5d,
0xaf1aaee9,0x2faf2b05,0x2d00a934,0x2b5eae5e,0x2dbaa814,0x2fdd9fd9,0x25db2f91,0x2a4eaee9,0x27652faf,0xaf4628d5,0xaf80ae1f,0xa5152faf,
0xafa0addc,0x2e3fac32,0x2e3fa515,0xa17eafff,0x2dfea6a1,0xacd82dba,0x244e2f6e,0x29342fd4,0x2d272fc9,0x230e2fff,0xafafad72,0x2d272e7c,
0xaffcaa4e,0xa814afdd,0x2e5ea5db,0xadfeadba,0x2c5dac07,0x2a4e2f91,0x16482f30,0x2eb52cd8,0x29932ff4,0xac32af1a,0xae7caf1a,0xaf46abb7,
0xae7c26a1,0xafff1648,0x2d72aa4e,0xafc926a1,0x230eaee9,0x2ff89fd9,0x217e2f91,0x2fafa814,0x2d4d2fa0,0xafed230e,0xae5eaf02,0xaf9128d5,
0xb000aaaa,0x2fdda515,0x2fdd2765,0x2f6ea993,0x1cb6b000,0x2cb0afd4,0x2765afd4,0xaddc2f5a,0xa17e2ffc,0xaff42c07,0xa8752fbc,0x2ff8a934,
0x244eaff4,0x2dfe28d5,0x2934afa0,0xacd8abb7,0xa5db2fe6,0x9648af46,0xa9f12f80,0xa5db2fc9,0x2ff41cb6,0x2e1f2765,0x2e1f2cb0,0xa875addc,
0xafbca5db,0x1fd9af5a,0xad4dad96,0xacd82fdd,0x2f5a2934,0xaeb52ee9,0x2c5d2e5e,0x3000ab05,0xaed0ab5e,0x2f80a30e,0xaaaaaf02,0xacb0ab5e,
0xa5db2ffc,0xad962fbc,0xaf5a2c07,0x2fdda934,0x2aaaafa0,0x2fc9a875,0x2fe6a875,0xa993ad27,0xad002ed0,0xa8d5ad72,0xaff81cb6,0xad002fe6,
0x2e5ead96,0xad4d2fd4,0x2f9126a1,0x2feda9f1,0xafbca17e,0xad4da875,0x1fd9aff4,0xacd82ff8,0x2e992aaa,0xaa4e2fe6,0xaa4e2fc9,0x2fd4a993,
0xacb0ad96,0x2fffac87,0x2d72aeb5,0xa765ad96,0x28752f30,0xab5eac07,0xaf1a2cd8,0xae3f2f91,0x2934aff4,0x2e5eafa0,0x2ee928d5,0xab05abb7,
0xad962ed0,0xaeb51cb6,0xac87ad72,0xad962fe6,0x2f80ac5d,0xa7652f6e,0x25152f6e,0x2f46a5db,0xaff8244e,0x2ff4ad4d,0x2875affc,0x217eaee9,
0x2f5a244e,0x2c5d2934,0xaeb52dfe,0x3000acd8,0xacb0ad00,0x2d72aff8,0x2fffa8d5,0xa765ad00,0x217e2f80,0xaf022515,0xaf02a765,0xaf1a2f46,
0x2b05afdd,0xa8142f5a,0x2c072d96,0x2d4d25db,0xab5e2fe6,0xaf022f80,0xa30eaf46,0xab5e2fc9,0x2f30ad96,0x2cd826a1,0xac072fd4,0x2f91a9f1,
0xafdd244e,0x2d96affc,0x2f5aad4d,0x25dbaee9,0x2d722bb7,0xae7c217e,0xafc9217e,0xafff2d00,0xaed0a5db,0xaaaaa9f1,0x2f809648,0xacb0a5db,
0x28752e5e,0xaf1a2f91,0xab5ead4d,0xae3f2fed,0x2b05aff8,0x2c072875,0xa8142ff4,0x2d4d217e,0xaf6e2d72,0x2eb5afc9,0x2eb5ae7c,0x2dbaafff,
0x2f80af5a,0x2fc9ae99,0x2fe6ae99,0xaf462d96,0xa8d5ab05,0x2f02afed,0xa30eacd8,0xafa02ffc,0xafbc2f02,0x2934ad27,0xaffc2e1f,0xac072e3f,
0x26a12c32,0xaa4e1cb6,0x16482d72,0x26a12515,0x28752aaa,0xa8d52cb0,0xa8d52ed0,0x2e3faf80,0x2fedaeb5,0x29349648,0x2f30aa4e,0x2814ac5d,
0x1648ad4d,0x2e99acd8,0x2c87afbc,0xa9f11fd9,0xafe62d27,0x2fffafaf,0xaddc230e,0xaed02d27,0xafd42f30,0xaf6e2e5e,0xadba244e,0x26a11fd9,
0x9cb62d27,0xafe62ff4,0xaed02ff4,0x2d72ab5e,0x2fafacb0,0xae1f2f46,0x28d52993,0x2fafaed0,0x2c07af6e,0xa9342c87,0x2ffcae99,0x2fbcb000,
0xa44eab5e,0x2b05ad00,0x2f91afaf,0xafbc2f1a,0xafd42d72,0x1648a765,0x1648acb0,0xafdd2fff,0xac322f5a,0xaaaa26a1,0xaf802c87,0xae7c2f5a,
0x2d009fd9,0xae1f2cd8,0xad272fbc,0xabb72d4d,0x2ffcaf02,0x2ee9ae1f,0xa44e2d27,0x2d4dae3f,0x29f1ae7c,0x2fddaf80,0x2eb5aaaa,0x29f1ac32,
0xad7225db,0x2fe6b000,0x2ed0b000,0x1cb6a6a1,0xafa02fbc,0x2f02af91,0xa30eab05,0xa8d5244e,0x96482c07,0xac872d4d,0xae992b05,0x29f1a814,
0x2ed0abb7,0xa9932b5e,0xaf462ff8,0x2cb0abb7,0x2f1aafff,0xa30e2765,0xa30e2cb0,0x2e1fad72,0x1fd9ac5d,0x244e9648,0x2e5eaa4e,0x2f30aeb5,
0xaff82ed0,0xae3f2ddc,0x2f02afff,0xaff82fe6,0xad4d2f6e,0xaee92e99,0x244eac87,0xaffc3000,0x26a12814,0xaf6e2f30,0xadba2934,0xafd42fed,
0x2f46ad00,0xafc92fa0,0xafe62fa0,0xaf802faf,0x2515ac5d,0x2d72ad96,0x1cb629f1,0x2c32ac5d,0xad002814,0x2d27ad4d,0x2e1fab05,0x2bb7ac07,
0xaffc2f1a,0x2cd8ad00,0x2fedafaf,0x2b05ab5e,0xadba2f80,0x2c87acb0,0x2c87aed0,0x2a4eaaaa,0xaf80af6e,0xafc9afdd,0xafe6afdd,0x2f463000,
0xafa0af91,0xabb7ae5e,0xaff4afed,0x28d52d4d,0xafbcafaf,0x2934a17e,0xaffcaff8,0xac07a30e,0xafd4afc9,0x2f5a2d72,0xb000afff,0xafd4ae7c,
0x2bb72aaa,0x2f1a2cb0,0x2f1a2ed0,0xaff4af80,0x2cd82c5d,0x2f303000,0x2f912f5a,0xac07aeb5,0x2dba2d4d,0x25db2cd8,0x2fdd2fbc,0x2a4e9fd9,
0x2e7c2e1f,0xad72a875,0x2fff2ff4,0x2fc92e1f,0x26a12934,0xa9f1244e,0xad96acd8,0x2fd42dfe,0x9cb6217e,0xafe6ae3f,0xaed0ae3f,0x2d722fa0,
0xa875a515,0xad27af80,0xafa0af46,0xa8752765,0xac07aa4e,0x2934a5db,0xaffcafdd,0xafbcadba,0xae5eaf1a,0xa934ae3f,0x2b052875,0xaee9ab5e,
0xac5dad72,0x2dba2765,0x2dba2cb0,0xae99afff,0xa765aa4e,0x2f802fd4,0x2f462e99,0x2515aa4e,0x230e9fd9,0x217e2cd8,0x2ff82fbc,0x2faf2d4d,
0x2ffc2faf,0x2ee92ff8,0xa44e217e,0x2d4d230e,0x2f6e2fe6,0xa5db2aaa,0xac5da993,0x2f6e2fc9,0x2d722e99,0xafe6adba,0xaed0adba,0x9cb62c5d,
0x28d52c07,0xabb7af30,0xaff4af91,0xafa0acd8,0xadbaac07,0xafddad4d,0xa5dbab05,0xaa4e2814,0xafc9af02,0xaaaaaf1a,0x2993217e,0xafe6af02,
0xafa0afff,0x2e3f2765,0x2e3f2cb0,0xa17ead72,0xad4daeb5,0x2e5e3000,0x2fed2f5a,0x2f912c5d,0x217ea765,0x2d009cb6,0x2bb72ddc,0x217eacb0,
0x2d4d2a4e,0x2ee92fdd,0xa44e25db,0x2ffc2dba,0x2fd42ee9,0xa9f12934,0xad96ab05,0x26a12e5e,0x2f462ff4,0xafc9af1a,0xafe6af1a,0xaf80abb7,
0x2cb02eb5,0x1cb62dba,0xaddcaf6e,0x27652eb5,0xa30e2814,0xaff8ad4d,0xa17eab05,0xafafac07,0xadfeab5e,0xa44eae3f,0x2cd82875,0xa934af1a,
0xb000af80,0x2fdd2cb0,0x2fdd2ed0,0x2f6e2aaa,0xad72b000,0xa515afd4,0xac32afd4,0x9cb62f5a,0x2e1f1fd9,0x2e3f2ee9,0x2f022814,0xad27af91,
0x2cd82ff4,0xaffca8d5,0x2b052fa0,0x2fed2bb7,0xae99a515,0x2d96aaaa,0xaf5aa993,0xae992765,0x2ff42ddc,0x2e1f2ed0,0x2e1f2fe6,0xa875afff,
0xa8142c87,0xaffca9f1,0xadfe1648,0x2e5e2e99,0xaf5aaf30,0x2eb5a814,0xac5dafed,0xb000a934,0x2c32a8d5,0xa9932e3f,0x2f462875,0x2e7ca8d5,
0xae999fd9,0xb000a814,0xaf6eaee9,0x2c872f91,0xa993afa0,0x2ed0a875,0x2cb0a875,0xaf46ad27,0x2ff42c32,0xab5e2ddc,0x2d272fff,0x2ff42515,
0xa44e2d96,0x9fd9afd4,0xaf30a6a1,0xae5e29f1,0x2814ad27,0x2dfeabb7,0x2ffc2d00,0xae5eae1f,0x2e992f80,0xaa4e2e7c,0xaa4e2c32,0x2fd42aaa,
0xae7c1648,0x9cb6afdd,0xaddcafd4,0xafc91648,0xa875af91,0x2b5e2fbc,0x2f1a244e,0x2e3fab05,0x2b052ff4,0xa44e2fa0,0xafbca8d5,0x2f912bb7,
0xb000ac32,0xa6a1afff,0x25dbaddc,0xb000a515,0x2aaaac5d,0x2c322f6e,0x2e7c2f6e,0x2f80a5db,0x2d272fed,0xae3fadfe,0xaf029fd9,0xae1f2c07,
0xaf5aae5e,0xac5daf30,0x2eb59fd9,0xb000a44e,0x2e7ca30e,0x2ddc2e1f,0x1cb62f1a,0x2fc9a30e,0x217e2f46,0xaf02acb0,0xaf02aed0,0xaf1a2993,
0xaf30ae99,0x2fbc29f1,0x2ee99648,0x2dfeac87,0x2fa02515,0x2faf2993,0xad002aaa,0x2fa0a765,0xa9342d96,0xafeda6a1,0xa814afd4,0xaf3029f1,
0xac87afed,0x30001fd9,0x2f6e2dfe,0x2e99ac07,0x2fff2bb7,0xafe6217e,0xaed0217e,0xaddc2d00,0xac322c87,0xaf462a4e,0x2993adba,0xae7c2c87,
0xa875afed,0x2f1aab05,0x2b5e2ffc,0x2e3facd8,0x2f302e1f,0xaee92bb7,0xafbcad00,0xadfe2d27,0xaf6e9cb6,0x2eb5ac32,0x2eb5a515,0x2dbaad72,
0x2aaaaf5a,0x2ed0ae99,0x2cb0ae99,0xaf802d96,0xab5e2f30,0xafaf244e,0xad002e5e,0x2f1a1fd9,0x2c07af02,0x2b052d27,0x2d4dae1f,0xa814ae3f,
0xac5d2ed0,0x29f1afff,0xad962ddc,0xac5d2fe6,0x28752f80,0xa8d52fe6,0xa8d52fc9,0x2e3faf46,0xa44eafd4,0x2f91adba,0x2b05af6e,0xafbc26a1,
0x96482ffc,0xae99a44e,0xac872ee9,0x29f12d4d,0x2515aff8,0x1cb62f02,0x2d72ae3f,0x2c32aff8,0xaeb5ab05,0xaa4eacd8,0x9648afed,0xac5d2ffc,
0x2d722d27,0xacb02ff4,0xa7652ff4,0x2fffab5e,0xabb7ae7c,0x2ff8aaaa,0x2b5eaf80,0xabb7ac32,0x28142f6e,0xab05ac87,0xad4d2e99,0xac073000,
0x2feda8d5,0x2f30a30e,0x29342f02,0x2814afa0,0xafd49cb6,0x1648aed0,0x1648afe6,0xafdd2d72,0x2ed029f1,0xaf462eb5,0xa9932fdd,0x2cb029f1,
0xad00ad4d,0x2e1f244e,0x2d27aee9,0x2bb7affc,0xad4d2f02,0xafbc2e1f,0xacd8ad27,0x1fd92e3f,0x2f5aacb0,0x2c872993,0x26a12f46,0x2f5aaed0,
0xafff25db,0x2cb0b000,0x2765b000,0xad72a6a1,0x2f1a2814,0xafaf2934,0xad002f30,0xab5e2fed,0x1648afbc,0x2c87affc,0x2e992934,0xa9f1ac07,
0xac322faf,0xaf8028d5,0xaaaaae1f,0xae7c2faf,0x2f1aad72,0xa30e2ed0,0xa30e2fe6,0x2e1f1cb6,0xaffc26a1,0x2fedadba,0x2cd8af6e,0x2b05afd4,
0x2d272c32,0x230e2d72,0xafaf1cb6,0x2d272515,0x9fd9af6e,0x2fbcae99,0x2cd82c87,0x2d4db000,0xac5d2fbc,0xaa4eab05,0x9648af91,0xaeb5244e,
0x2f80ad00,0xaed02fa0,0xacb02fa0,0xaaaa2faf,0xafe626a1,0xaddc1648,0x2fffaa4e,0xaed026a1,0x2d002c07,0xad272ffc,0xae1fa934,0xabb72fbc,
0x1fd9afa0,0x2e5ea30e,0x244e2f02,0x2f30a8d5,0xadba2f46,0x2c87afe6,0x2c87afc9,0x2a4eaf80,0x2fffad96,0x2e7cac5d,0x2fc9ac5d,0xad7229f1,
0x217eadfe,0x2ff4afbc,0x2875aee9,0xaff82f30,0xafed2d00,0x2d4daf1a,0xaf912b5e,0xae5e2faf,0xa5db2e7c,0x9648a993,0xa9f12f46,0xa5db2c32,
0xae3f2fff,0xaff82fc9,0xaff82e7c,0x2f02ad72,0x2c0725db,0xadfe2f5a,0x9fd92d96,0x2fedafdd,0x2f6eaf91,0xa6a12c07,0x2fd4acd8,0x2dbaaf30,
0xa765ab5e,0x2aaaa30e,0x2993af02,0x2515ab5e,0x25dbadfe,0x2d96aee9,0x2f5aafbc,0xafdd2f30,0xaf462b5e,0x2765abb7,0xa515abb7,0xaf802ff8,
0xad002fc9,0xa8d51cb6,0xaff82ddc,0xad002e7c,0x2cd81648,0xadfe2c5d,0xa9342eb5,0xa44e2a4e,0x2c07217e,0x9fd92875,0xadfe2ff4,0x2fedaff8,
0x2fddaf46,0x29f1a515,0x29f12765,0x2eb5af80,0x2515ad96,0x2ddcac87,0x2fffaeb5,0x2c32ad96,0xaf022b05,0x2fa0aee9,0x28d5ae5e,0x230ea934,
0xaf912d00,0xacd82b5e,0x2c07af1a,0xaf302faf,0xad962fc9,0xaeb52ddc,0xac871cb6,0xad962e7c,0x299326a1,0xafc92f5a,0xafe62f5a,0xaaaa2c87,
0x2ff8ae5e,0xaff42ffc,0xa8752dfe,0xa17e2814,0x2f6eafed,0x2fd4af91,0xa6a12d4d,0x2dbaae5e,0x2515ad00,0x2fffaff8,0x2ddca8d5,0x2c32ad00,
0xae1f2993,0x2fafafe6,0x2fafafc9,0x28d5aaaa,0xaf912fdd,0x2ee9af5a,0x2814ad96,0x1fd9a5db,0xab5e2e7c,0xaf022f46,0xa30ea993,0xab5e2c32,
0x2b051648,0xae5e2eb5,0xaee92c5d,0xa9342a4e,0x2fddae5e,0xad962dfe,0xaf5a2ffc,0xa5db2814,0x2ddcafaf,0xacb02d27,0xa7652d27,0x9cb6230e,
0xa765a5db,0x2993a9f1,0x2aaa9648,0x2515a5db,0xaf022cd8,0x28d5a934,0x2fa0adfe,0x230ea44e,0xaf912ff8,0x2814a875,0x2ee9aff4,0x1fd9a17e,
0xaa4e2ddc,0x26a1a765,0x26a1acb0,0x16489cb6,0x9de49e49,0xae47aeb3,0x997f9a49,0xa9d8aaaf,0x9d1b9d7f,0xad70addc,0x97db98b6,0xa82da902,
0x9c529cb6,0xac99ad04,0x94b69648,0xa502a6ad,0x9b129bdb,0xab85ac2e,0x8e489248,0x9eada2ad,0xa46ba4b7,0xaf06af7f,0xa020a0b6,0xaa89ab78,
0xa3a9a420,0xae15ae8d,0x9de49f12,0xa8aaa999,0xa27ba312,0xad24ad9c,0x9b129cb6,0xa599a777,0xa14da1e4,0xac34acac,0x94b698b6,0x9f76a376,
0xa75da7db,0xafc5b025,0xa2dfa3db,0xab39ac21,0xa662a6e0,0xaebaaf3f,0xa0e9a1e4,0xa928aa31,0xa567a5e4,0xadafae34,0x9de49fdb,0xa630a820,
0xa46ba4e9,0xaca6ad2a,0x97db9bdb,0xa020a420,0xa928a980,0xb042b08c,0xa4d0a580,0xabeaac86,0xa878a8d0,0xaf5faff2,0xa2dfa420,0xa9a6aac8,
0xa790a820,0xae3baecd,0xa020a17f,0xa6c7a885,0xa630a6e0,0xad17ada9,0x997f9d7f,0xa084a484,0xaaa2ab13,0xb0a2b0f3,0xa630a712,0xac4daceb,
0xa9bfaa31,0xb002b052,0xa46ba54d,0xaa24ab5f,0xa8dda94e,0xaec6af65,0xa14da312,0xa75da8e9,0xa7f4a86b,0xad89ae28,0x9b129f12,0xa0e9a4e9,
0xac0eac54,0xb103b15a,0xa790a852,0xaca6ad50,0xab07ab91,0xb055b0ac,0xa567a67b,0xaaa2abf6,0xa9f2aa7c,0xaf52affe,0xa27ba452,0xa7f4a94e,
0xa8dda967,0xadfbaea7,0x9c52a052,0xa14da54d,0xacccad1e,0xb163b1c1,0xa878a91c,0xacfeadb6,0xac27ac79,0xb0a9b106,0xa662a7a9,0xab20ac47,
0xab07abab,0xafdeb04c,0xa3a9a51b,0xa846a9b3,0xa9bfaa63,0xae6daf26,0x9d1ba11b,0xa1b2a5b2,0xad89ade8,0xb1c5b229,0xa928a9e5,0xad57ae1b,
0xacccad2a,0xb0fcb160,0xa75da86b,0xab9eac93,0xac0eac6d,0xb035b099,0xa46ba5e4,0xa891aa17,0xaaa2ab5f,0xaee0afa5,0x9de4a1e4,0xa216a617,
0xb226b292,0xb4a2b4f6,0xadafae80,0xb03cb0d9,0xb150b1bb,0xb3fab44f,0xac0eacde,0xae08af3f,0xb07cb0e6,0xb2b6b357,0xa8ddaa7c,0xab39acd2,
0xaf52b012,0xb177b216,0xa27ba67b,0xa4d0a8d0,0xb288b2fb,0xb4d5b52d,0xae08aee6,0xb069b10c,0xb1a4b216,0xb428b47e,0xac4dad2a,0xae47af8c,
0xb0c2b133,0xb2feb3a7,0xa928aae1,0xab85ad04,0xafc5b052,0xb1b1b257,0xa2dfa6e0,0xa502a902,0xb2eab364,0xb509b565,0xae61af4c,0xb095b140,
0xb1f8b271,0xb454b4ae,0xac8cad76,0xae87afd8,0xb109b181,0xb347b3f7,0xa974ab46,0xabd1ad37,0xb01cb092,0xb1ebb298,0xa344a744,0xa534a935,
0xb34db3cf,0xb53db59d,0xaebaafb2,0xb0c2b174,0xb24db2cd,0xb480b4de,0xacccadc2,0xaec6b012,0xb150b1ce,0xb390b423,0xa9bfabab,0xac0ead6a,
0xb055b0d2,0xb226b2da,0xa3a9a7a9,0xa567a967,0xb3b1b41d,0xb571b5d6,0xaf13b00c,0xb0efb1a7,0xb2a2b329,0xb4acb50e,0xad0bae0e,0xaf06b039,
0xb197b21c,0xb3d9b44c,0xaa0bac08,0xac34ad9c,0xb08fb113,0xb261b31c,0xa407a807,0xa599a999,0xb40ab453,0xb5a6b60f,0xaf6cb03f,0xb11cb1db,
0xb2f8b386,0xb4d9b53f,0xad4aae5a,0xaf45b05f,0xb1deb26b,0xb411b474,0xaa56ac3a,0xac5aadcf,0xb0c9b153,0xb29cb35e,0xa439a839,0xa5cba9cc,
0xb43db489,0xb5dbb649,0xafc5b072,0xb14ab20f,0xb34db3e3,0xb506b570,0xad89aea7,0xaf85b085,0xb226b2b9,0xb436b49d,0xaaa2ac6d,0xac80ae02,
0xb103b194,0xb2d7b3a0,0xa46ba86b,0xa5fda9fe,0xb46fb4bf,0xb611b683,0xb00fb0a5,0xb177b243,0xb3a3b420,0xb533b5a1,0xadc9aef3,0xafc5b0ac,
0xb26eb308,0xb45bb4c6,0xaaeeac9f,0xaca6ae34,0xb13db1d5,0xb312b3e3,0xa49da89e,0xa630aa31,0xb647b6be,0xb806b857,0xb1a4b278,0xb312b40f,
0xb560b5d2,0xb6d6b76f,0xb002b0d2,0xb103b209,0xb480b4ef,0xb5b1b642,0xacccae67,0xadfbaffe,0xb34db413,0xb498b523,0xa662aa63,0xa7f4abf6,
0xb67eb6fa,0xb824b878,0xb1d2b2ac,0xb340b42a,0xb58db604,0xb707b7a5,0xb022b0f9,0xb123b230,0xb4a6b519,0xb5d8b66d,0xacf1ae9a,0xae21b019,
0xb389b434,0xb4b7b546,0xa694aa95,0xa813ac14,0xb6b5b736,0xb842b899,0xb1ffb2e1,0xb36eb445,0xb5bbb637,0xb738b7db,0xb042b120,0xb143b257,
0xb4cbb542,0xb5ffb699,0xad17aecd,0xae47b032,0xb3c5b456,0xb4d5b569,0xa6c7aac8,0xa82dac2e,0xb6edb773,0xb860b8bb,0xb22db315,0xb39db460,
0xb5eab66a,0xb769b809,0xb062b146,0xb163b27e,0xb4f1b56c,0xb627b6c6,0xad3daf00,0xae6db04c,0xb400b478,0xb4f4b58c,0xa6f9aafa,0xa846ac47,
0xb725b7b0,0xb87fb8dd,0xb25ab34a,0xb3cbb47b,0xb618b69d,0xb79bb825,0xb082b16d,0xb184b2a5,0xb517b596,0xb64eb6f2,0xad63af32,0xae93b065,
0xb41eb49a,0xb513b5af,0xa72bab2d,0xa85fac60,0xb75eb7ee,0xb89eb8ff,0xb288b37f,0xb3fab496,0xb647b6d1,0xb7cdb841,0xb0a2b194,0xb1a4b2cd,
0xb53db5c1,0xb676b71f,0xad89af65,0xaebab07f,0xb43db4bc,0xb533b5d2,0xa75dab5f,0xa878ac79,0xb797b817,0xb8beb923,0xb2b6b3b4,0xb414b4b1,
0xb676b705,0xb800b85d,0xb0c2b1bb,0xb1c5b2f4,0xb563b5eb,0xb69fb74d,0xadafaf98,0xaee0b099,0xb45bb4de,0xb552b5f6,0xa790ab91,0xa891ac93,
0xb7d1b837,0xb8deb946,0xb2e4b3e9,0xb42cb4cd,0xb6a6b73a,0xb81ab87a,0xb0e3b1e2,0xb1e5b31c,0xb58ab616,0xb6c7b77a,0xadd5afcb,0xaf06b0b2,
0xb479b500,0xb571b61a,0xa7c2abc4,0xa8aaacac,0xb8feb96b,0xba15baa6,0xb443b4e8,0xb502b5c8,0xb834b897,0xb90eb98d,0xb205b343,0xb30bb442,
0xb6f0b7a8,0xb822b895,0xaf2cb0cc,0xb02fb19a,0xb591b63e,0xb694b767,0xa8c4acc5,0xa98dad90,0xb91fb990,0xba3abad1,0xb45bb504,0xb51ab5e4,
0xb84eb8b4,0xb92ab9ae,0xb226b36b,0xb32cb456,0xb71ab7d7,0xb838b8ae,0xaf52b0e6,0xb042b1b4,0xb5b1b662,0xb6b5b78d,0xa8ddacde,0xa9a6ada9,
0xb941b9b5,0xba61bafd,0xb473b51f,0xb533b601,0xb868b8d2,0xb947b9cf,0xb247b393,0xb34db46a,0xb743b803,0xb84eb8c7,0xaf78b0ff,0xb055b1ce,
0xb5d1b687,0xb6d6b7b4,0xa8f6acf8,0xa9bfadc2,0xb963b9dc,0xba88bb29,0xb48ab53b,0xb54bb61e,0xb883b8f0,0xb965b9f1,0xb267b3bb,0xb36eb47e,
0xb76db81b,0xb864b8e1,0xaf9fb119,0xb069b1e8,0xb5f1b6ac,0xb6f8b7db,0xa90fad11,0xa9d8addc,0xb985ba02,0xbaafbb57,0xb4a2b557,0xb563b63a,
0xb89eb90f,0xb983ba14,0xb288b3e3,0xb390b493,0xb797b833,0xb87bb8fb,0xafc5b133,0xb07cb202,0xb611b6d1,0xb71ab801,0xa928ad2a,0xa9f2adf5,
0xb9a8ba2a,0xbad8bb86,0xb4bab573,0xb57cb657,0xb8b9b92e,0xb9a1ba37,0xb2a9b405,0xb3b1b4a7,0xb7c2b84b,0xb892b915,0xafebb14d,0xb08fb21c,
0xb631b6f6,0xb73bb815,0xa941ad44,0xaa0bae0e,0xb9ccba53,0xbb01bbb6,0xb4d2b58f,0xb594b675,0xb8d5b94d,0xb9c0ba5a,0xb2cab419,0xb3d2b4bc,
0xb7ecb863,0xb8a9b930,0xb009b167,0xb0a2b236,0xb652b71b,0xb75eb829,0xa95bad5d,0xaa24ae28,0xb9f0ba7c,0xbb2bbbe7,0xb4eab5ab,0xb5adb692,
0xb8f1b96d,0xb9dfba7e,0xb2eab42e,0xb3f3b4d0,0xb80cb87c,0xb8c0b94b,0xb01cb181,0xb0b6b250,0xb673b741,0xb780b83d,0xa974ad76,0xaa3dae41,
0xe480000,0x1ead0000,0x1b121a49,0x2b852aaf,0x14b61248,0x250222ad,0x1c521bdb,0x2c992c2e,0x17db1648,0x282d26ad,0x1d1b1cb6,0x2d702d04,
0x197f18b6,0x29d82902,0x1de41d7f,0x2e472ddc,0x14b60000,0x1f760000,0x214d20b6,0x2c342b78,0x1b1218b6,0x25992376,0x227b21e4,0x2d242cac,
0x1de41cb6,0x28aa2777,0x23a92312,0x2e152d9c,0x20201f12,0x2a892999,0x246b2420,0x2f062e8d,0x17db0000,0x20200000,0x246b23db,0x2ca62c21,
0x1de41bdb,0x26302420,0x256724e9,0x2daf2d2a,0x20e91fdb,0x29282820,0x266225e4,0x2eba2e34,0x22df21e4,0x2b392a31,0x275d26e0,0x2fc52f3f,
0x197f0000,0x20840000,0x26302580,0x2d172c86,0x20201d7f,0x26c72484,0x279026e0,0x2e3b2da9,0x22df217f,0x29a62885,0x28782820,0x2f5f2ecd,
0x24d02420,0x2bea2ac8,0x292828d0,0x30422ff2,0x1b120000,0x20e90000,0x27f42712,0x2d892ceb,0x214d1f12,0x275d24e9,0x28dd286b,0x2ec62e28,
0x246b2312,0x2a2428e9,0x29bf294e,0x30022f65,0x2630254d,0x2c4d2b5f,0x2aa22a31,0x30a23052,0x1c520000,0x214d0000,0x28dd2852,0x2dfb2d50,
0x227b2052,0x27f4254d,0x29f22967,0x2f522ea7,0x25672452,0x2aa2294e,0x2b072a7c,0x30552ffe,0x2790267b,0x2ca62bf6,0x2c0e2b91,0x310330ac,
0x1d1b0000,0x21b20000,0x29bf291c,0x2e6d2db6,0x23a9211b,0x284625b2,0x2b072a63,0x2fde2f26,0x2662251b,0x2b2029b3,0x2c272bab,0x30a9304c,
0x287827a9,0x2cfe2c47,0x2ccc2c79,0x31633106,0x1de40000,0x22160000,0x2aa229e5,0x2ee02e1b,0x246b21e4,0x28912617,0x2c0e2b5f,0x30352fa5,
0x275d25e4,0x2b9e2a17,0x2ccc2c6d,0x30fc3099,0x2928286b,0x2d572c93,0x2d892d2a,0x31c53160,0x227b0000,0x24d00000,0x2f522e80,0x317730d9,
0x28dd267b,0x2b3928d0,0x307c3012,0x32b63216,0x2c0e2a7c,0x2e082cd2,0x315030e6,0x33fa3357,0x2daf2cde,0x303c2f3f,0x322631bb,0x34a2344f,
0x22df0000,0x25020000,0x2fc52ee6,0x31b1310c,0x292826e0,0x2b852902,0x30c23052,0x32fe3257,0x2c4d2ae1,0x2e472d04,0x31a43133,0x342833a7,
0x2e082d2a,0x30692f8c,0x32883216,0x34d5347e,0x23440000,0x25340000,0x301c2f4c,0x31eb3140,0x29742744,0x2bd12935,0x31093092,0x33473298,
0x2c8c2b46,0x2e872d37,0x31f83181,0x345433f7,0x2e612d76,0x30952fd8,0x32ea3271,0x350934ae,0x23a90000,0x25670000,0x30552fb2,0x32263174,
0x29bf27a9,0x2c0e2967,0x315030d2,0x339032da,0x2ccc2bab,0x2ec62d6a,0x324d31ce,0x34803423,0x2eba2dc2,0x30c23012,0x334d32cd,0x353d34de,
0x24070000,0x25990000,0x308f300c,0x326131a7,0x2a0b2807,0x2c342999,0x31973113,0x33d9331c,0x2d0b2c08,0x2f062d9c,0x32a2321c,0x34ac344c,
0x2f132e0e,0x30ef3039,0x33b13329,0x3571350e,0x24390000,0x25cb0000,0x30c9303f,0x329c31db,0x2a562839,0x2c5a29cc,0x31de3153,0x3411335e,
0x2d4a2c3a,0x2f452dcf,0x32f8326b,0x34d93474,0x2f6c2e5a,0x311c305f,0x340a3386,0x35a6353f,0x246b0000,0x25fd0000,0x31033072,0x32d7320f,
0x2aa2286b,0x2c8029fe,0x32263194,0x343633a0,0x2d892c6d,0x2f852e02,0x334d32b9,0x3506349d,0x2fc52ea7,0x314a3085,0x343d33e3,0x35db3570,
0x249d0000,0x26300000,0x313d30a5,0x33123243,0x2aee289e,0x2ca62a31,0x326e31d5,0x345b33e3,0x2dc92c9f,0x2fc52e34,0x33a33308,0x353334c6,
0x300f2ef3,0x317730ac,0x346f3420,0x361135a1,0x26620000,0x27f40000,0x334d3278,0x3498340f,0x2ccc2a63,0x2dfb2bf6,0x34803413,0x35b13523,
0x30022e67,0x31032ffe,0x356034ef,0x36d63642,0x31a430d2,0x33123209,0x364735d2,0x3806376f,0x26940000,0x28130000,0x338932ac,0x34b7342a,
0x2cf12a95,0x2e212c14,0x34a63434,0x35d83546,0x30222e9a,0x31233019,0x358d3519,0x3707366d,0x31d230f9,0x33403230,0x367e3604,0x382437a5,
0x26c70000,0x282d0000,0x33c532e1,0x34d53445,0x2d172ac8,0x2e472c2e,0x34cb3456,0x35ff3569,0x30422ecd,0x31433032,0x35bb3542,0x37383699,
0x31ff3120,0x336e3257,0x36b53637,0x384237db,0x26f90000,0x28460000,0x34003315,0x34f43460,0x2d3d2afa,0x2e6d2c47,0x34f13478,0x3627358c,
0x30622f00,0x3163304c,0x35ea356c,0x376936c6,0x322d3146,0x339d327e,0x36ed366a,0x38603809,0x272b0000,0x285f0000,0x341e334a,0x3513347b,
0x2d632b2d,0x2e932c60,0x3517349a,0x364e35af,0x30822f32,0x31843065,0x36183596,0x379b36f2,0x325a316d,0x33cb32a5,0x3725369d,0x387f3825,
0x275d0000,0x28780000,0x343d337f,0x35333496,0x2d892b5f,0x2eba2c79,0x353d34bc,0x367635d2,0x30a22f65,0x31a4307f,0x364735c1,0x37cd371f,
0x32883194,0x33fa32cd,0x375e36d1,0x389e3841,0x27900000,0x28910000,0x345b33b4,0x355234b1,0x2daf2b91,0x2ee02c93,0x356334de,0x369f35f6,
0x30c22f98,0x31c53099,0x367635eb,0x3800374d,0x32b631bb,0x341432f4,0x37973705,0x38be385d,0x27c20000,0x28aa0000,0x347933e9,0x357134cd,
0x2dd52bc4,0x2f062cac,0x358a3500,0x36c7361a,0x30e32fcb,0x31e530b2,0x36a63616,0x381a377a,0x32e431e2,0x342c331c,0x37d1373a,0x38de387a,
0x28c40000,0x298d0000,0x359134e8,0x369435c8,0x2f2c2cc5,0x302f2d90,0x36f0363e,0x38223767,0x320530cc,0x330b319a,0x383437a8,0x390e3895,
0x34433343,0x35023442,0x38fe3897,0x3a15398d,0x28dd0000,0x29a60000,0x35b13504,0x36b535e4,0x2f522cde,0x30422da9,0x371a3662,0x3838378d,
0x322630e6,0x332c31b4,0x384e37d7,0x392a38ae,0x345b336b,0x351a3456,0x391f38b4,0x3a3a39ae,0x28f60000,0x29bf0000,0x35d1351f,0x36d63601,
0x2f782cf8,0x30552dc2,0x37433687,0x384e37b4,0x324730ff,0x334d31ce,0x38683803,0x394738c7,0x34733393,0x3533346a,0x394138d2,0x3a6139cf,
0x290f0000,0x29d80000,0x35f1353b,0x36f8361e,0x2f9f2d11,0x30692ddc,0x376d36ac,0x386437db,0x32673119,0x336e31e8,0x3883381b,0x396538e1,
0x348a33bb,0x354b347e,0x396338f0,0x3a8839f1,0x29280000,0x29f20000,0x36113557,0x371a363a,0x2fc52d2a,0x307c2df5,0x379736d1,0x387b3801,
0x32883133,0x33903202,0x389e3833,0x398338fb,0x34a233e3,0x35633493,0x3985390f,0x3aaf3a14,0x29410000,0x2a0b0000,0x36313573,0x373b3657,
0x2feb2d44,0x308f2e0e,0x37c236f6,0x38923815,0x32a9314d,0x33b1321c,0x38b9384b,0x39a13915,0x34ba3405,0x357c34a7,0x39a8392e,0x3ad83a37,
0x295b0000,0x2a240000,0x3652358f,0x375e3675,0x30092d5d,0x30a22e28,0x37ec371b,0x38a93829,0x32ca3167,0x33d23236,0x38d53863,0x39c03930,
0x34d23419,0x359434bc,0x39cc394d,0x3b013a5a,0x29740000,0x2a3d0000,0x367335ab,0x37803692,0x301c2d76,0x30b62e41,0x380c3741,0x38c0383d,
0x32ea3181,0x33f33250,0x38f1387c,0x39df394b,0x34ea342e,0x35ad34d0,0x39f0396d,0x3b2b3a7e,0xa1e4a248,0xb238b2a1,0x9d7f9e48,0xadd5aeaa,
0xa11ba17f,0xb166b1cf,0x9bdb9cb6,0xac2bad00,0xa052a0b6,0xb093b0fd,0x98b69a48,0xa901aaac,0x9f129fdb,0xaf7eb029,0x92489648,0xa2ada6ad,
0xa86ba8b6,0xb2f0b365,0xa420a4b6,0xae84af72,0xa7a8a81f,0xb207b27c,0xa1e4a311,0xaca9ad97,0xa67ba711,0xb11cb191,0x9f12a0b6,0xa998ab75,
0xa54da5e4,0xb02fb0a6,0x98b69cb6,0xa376a776,0xab5cabd9,0xb3a8b414,0xa6dfa7da,0xaf33b01d,0xaa61aade,0xb2a7b328,0xa4e9a5e4,0xad26ae2d,
0xa966a9e3,0xb1a4b226,0xa1e4a3db,0xaa2fac1f,0xa86ba8e8,0xb09fb122,0x9bdb9fdb,0xa420a81f,0xad26ad7e,0xb42fb475,0xa8cfa97f,0xafe2b080,
0xac77acce,0xb346b3d3,0xa6dfa81f,0xada3aec3,0xab8eac1f,0xb22cb2b9,0xa420a57f,0xaac5ac83,0xaa2faade,0xb10fb19e,0x9d7fa17f,0xa484a884,
0xae9daf0e,0xb48ab4d5,0xaa2fab11,0xb048b0e4,0xadbcae2d,0xb3e5b43e,0xa86ba94d,0xae20af59,0xacdbad4c,0xb2b3b34c,0xa54da711,0xab5cace7,
0xabf2ac6a,0xb17fb219,0x9f12a311,0xa4e9a8e8,0xb00ab04e,0xb4e4b534,0xab8eac51,0xb09fb147,0xaf01af8b,0xb441b493,0xa966aa7a,0xae9dafef,
0xadeeae78,0xb33ab3df,0xa67ba852,0xabf2ad4c,0xacdbad65,0xb1eeb294,0xa052a452,0xa54da94d,0xb0c5b115,0xb53db593,0xac77ad1a,0xb0f6b1aa,
0xb023b074,0xb490b4e7,0xaa61aba7,0xaf1ab042,0xaf01afa4,0xb3c0b438,0xa7a8a91b,0xac44adb0,0xadbcae5f,0xb25db30f,0xa11ba51b,0xa5b2a9b1,
0xb17fb1db,0xb596b5f1,0xad26ade2,0xb14db20d,0xb0c5b122,0xb4deb53a,0xab5cac6a,0xaf97b08d,0xb00ab067,0xb423b481,0xa86ba9e3,0xac90ae14,
0xae9daf59,0xb2ccb389,0xa1e4a5e4,0xa616aa16,0xb5eeb64e,0xb846b887,0xb1a4b26f,0xb429b4bd,0xb52cb58d,0xb783b805,0xb00ab0d7,0xb1fab328,
0xb466b4c9,0xb66db6f9,0xacdbae78,0xaf33b0cb,0xb33ab402,0xb54fb5df,0xa67baa7a,0xa8cfacce,0xb645b6aa,0xb86eb8b0,0xb1fab2d2,0xb454b4ed,
0xb579b5df,0xb7cab82a,0xb048b122,0xb238b371,0xb4a8b511,0xb6adb73d,0xad26aedc,0xaf7eb0fd,0xb3a8b43e,0xb584b61a,0xa6dfaade,0xa901ad00,
0xb69bb705,0xb895b8d8,0xb251b334,0xb47eb51d,0xb5c5b631,0xb809b850,0xb086b16c,0xb276b3ba,0xb4eab558,0xb6ebb780,0xad71af40,0xafc9b12e,
0xb40bb47b,0xb5b9b654,0xa744ab43,0xa934ad33,0xb6f1b75e,0xb8bbb900,0xb2a7b396,0xb4a8b54c,0xb611b682,0xb82cb874,0xb0c5b1b6,0xb2b3b402,
0xb52cb59f,0xb729b7c2,0xadbcafa4,0xb00ab160,0xb441b4b7,0xb5eeb68d,0xa7a8aba7,0xa966ad65,0xb745b7b7,0xb8e1b927,0xb2fdb3f7,0xb4d2b57c,
0xb65cb6d2,0xb84eb899,0xb103b201,0xb2f0b426,0xb56db5e5,0xb767b802,0xae07b004,0xb02fb191,0xb478b4f3,0xb622b6c6,0xa806ac06,0xa998ad97,
0xb799b807,0xb906b94d,0xb352b42c,0xb4fcb5ab,0xb6a7b721,0xb871b8bc,0xb141b24b,0xb32eb44b,0xb5aeb62b,0xb7a4b822,0xae52b036,0xb055b1c3,
0xb4aeb52f,0xb656b6ff,0xa839ac38,0xa9caadc9,0xb7ebb832,0xb92ab972,0xb3a8b45d,0xb526b5da,0xb6f1b76f,0xb892b8e0,0xb17fb294,0xb36bb46f,
0xb5eeb670,0xb7e0b842,0xae9db067,0xb07ab1f4,0xb4e4b56a,0xb68ab737,0xa86bac6a,0xa9fdadfb,0xb81eb85d,0xb94eb996,0xb3fdb48d,0xb54fb608,
0xb73ab7bd,0xb8b4b902,0xb1bdb2de,0xb3a8b493,0xb62eb6b5,0xb80eb862,0xaee8b099,0xb09fb226,0xb51ab5a5,0xb6beb76f,0xa89dac9c,0xaa2fae2d,
0xb971b9ba,0xba6cbab5,0xb579b637,0xb6beb7a1,0xb8d4b924,0xb9c8ba1d,0xb3e5b4b7,0xb4e4b5d4,0xb82cb881,0xb90db96d,0xb0c5b257,0xb1eeb3df,
0xb6f1b7a6,0xb83eb8a8,0xaa61ae5f,0xabf2afef,0xb993b9dc,0xba88bad0,0xb5a2b665,0xb6e5b7cd,0xb8f5b946,0xb9e4ba39,0xb411b4db,0xb502b5f7,
0xb849b8a0,0xb928b989,0xb0eab288,0xb213b408,0xb724b7dd,0xb856b8c1,0xaa93ae91,0xac12b010,0xb9b4b9fe,0xbaa2bae9,0xb5cbb693,0xb70db7f9,
0xb914b966,0xb9ffba54,0xb42fb4ff,0xb520b61a,0xb866b8bf,0xb942b9a4,0xb10fb2b9,0xb238b420,0xb756b80a,0xb86eb8db,0xaac5aec3,0xac2bb029,
0xb9d5ba1f,0xbabcbb02,0xb5f4b6c1,0xb734b812,0xb934b986,0xba1aba6f,0xb44eb523,0xb53db63c,0xb883b8dd,0xb95cb9be,0xb134b2ea,0xb25db438,
0xb788b825,0xb885b8f3,0xaaf8aef5,0xac44b042,0xb9f5ba3f,0xbad5bb1a,0xb61db6ee,0xb75cb828,0xb953b9a6,0xba34ba89,0xb46cb546,0xb55bb65f,
0xb89fb8fb,0xb975b9d8,0xb15ab31b,0xb282b451,0xb7bab840,0xb89db90c,0xab2aaf27,0xac5eb05b,0xba14ba5e,0xbaedbb30,0xb645b71b,0xb783b83d,
0xb971b9c5,0xba4ebaa2,0xb48ab56a,0xb579b682,0xb8bbb918,0xb98eb9f2,0xb17fb34c,0xb2a7b469,0xb7ebb85a,0xb8b4b924,0xab5caf59,0xac77b074,
0xba32ba7c,0xbb04bb46,0xb66db748,0xb7a9b852,0xb98eb9e3,0xba66baba,0xb4a8b58d,0xb596b6a4,0xb8d7b935,0xb9a7ba0b,0xb1a4b37d,0xb2ccb481,
0xb80eb874,0xb8cab93c,0xab8eaf8b,0xac90b08d,0xba4fba99,0xbb1bbb5a,0xb696b775,0xb7d0b867,0xb9abba00,0xba7fbad1,0xb4c6b5b1,0xb5b3b6c6,
0xb8f2b951,0xb9bfba23,0xb1c9b3ae,0xb2f0b499,0xb826b88e,0xb8e1b954,0xabc0afbd,0xaca9b0a6,0xbb30bb6e,0xbbb5bbdd,0xb7f6b87c,0xb890b91d,
0xba96bae8,0xbb39bb7f,0xb5d1b6e8,0xb6b8b7f3,0xb9d7ba3b,0xba86bae6,0xb315b4b1,0xb41db570,0xb8f7b96b,0xb9a0ba19,0xacc2b0be,0xad8ab185,
0xbb44bb80,0xbbc1bbe6,0xb80eb891,0xb8a2b930,0xbaadbafe,0xbb4bbb8e,0xb5eeb70a,0xb6d4b80a,0xb9efba52,0xba9abaf9,0xb33ab4c9,0xb42fb587,
0xb90db982,0xb9b4ba2d,0xacdbb0d7,0xada3b19e,0xbb57bb91,0xbbcdbbed,0xb821b8a6,0xb8b4b943,0xbac3bb13,0xbb5bbb9c,0xb60bb72c,0xb6f1b81a,
0xba05ba69,0xbaadbb0b,0xb35fb4e1,0xb441b59f,0xb923b999,0xb9c8ba41,0xacf4b0f0,0xadbcb1b6,0xbb69bba0,0xbbd6bbf4,0xb834b8ba,0xb8c5b956,
0xbad9bb27,0xbb6bbba9,0xb628b74e,0xb70db82a,0xba1cba7f,0xbac0bb1d,0xb383b4f9,0xb454b5b6,0xb939b9af,0xb9dbba54,0xad0db109,0xadd5b1cf,
0xbb7bbbaf,0xbbdfbbf8,0xb846b8ce,0xb8d7b969,0xbaedbb3a,0xbb7abbb5,0xb645b76f,0xb729b83a,0xba32ba95,0xbad2bb2e,0xb3a8b511,0xb466b5ce,
0xb94eb9c5,0xb9efba67,0xad26b122,0xadeeb1e8,0xbb8bbbbc,0xbbe7bbfc,0xb859b8e2,0xb8e8b97b,0xbb01bb4c,0xbb88bbc0,0xb662b790,0xb745b84a,
0xba48baaa,0xbae4bb3e,0xb3cdb529,0xb478b5e5,0xb963b9da,0xba01ba7a,0xad3fb13b,0xae07b201,0xbb9abbc9,0xbbeebbff,0xb86bb8f6,0xb8fab98d,
0xbb15bb5e,0xbb95bbcb,0xb67fb7b2,0xb761b85a,0xba5dbabf,0xbaf5bb4e,0xb3f1b540,0xb48ab5fd,0xb978b9f0,0xba14ba8c,0xad58b153,0xae20b219,
0xbba8bbd4,0xbbf4bc00,0xb87eb909,0xb90bb99f,0xbb27bb6f,0xbba2bbd4,0xb69bb7d2,0xb77db86a,0xba72bad3,0xbb06bb5d,0xb40bb558,0xb49cb614,
0xb98cba04,0xba26ba9e,0xad71b16c,0xae39b232,0x12480000,0x22ad0000,0x1f121e48,0x2f7e2eaa,0x18b61648,0x290126ad,0x20521fdb,0x30933029,
0x1bdb1a48,0x2c2b2aac,0x211b20b6,0x316630fd,0x1d7f1cb6,0x2dd52d00,0x21e4217f,0x323831cf,0x18b60000,0x23760000,0x254d24b6,0x302f2f72,
0x1f121cb6,0x29982776,0x267b25e4,0x311c30a6,0x21e420b6,0x2ca92b75,0x27a82711,0x32073191,0x24202311,0x2e842d97,0x286b281f,0x32f0327c,
0x1bdb0000,0x24200000,0x286b27da,0x309f301d,0x21e41fdb,0x2a2f281f,0x296628e8,0x31a43122,0x24e923db,0x2d262c1f,0x2a6129e3,0x32a73226,
0x26df25e4,0x2f332e2d,0x2b5c2ade,0x33a83328,0x1d7f0000,0x24840000,0x2a2f297f,0x310f3080,0x2420217f,0x2ac52884,0x2b8e2ade,0x322c319e,
0x26df257f,0x2da32c83,0x2c772c1f,0x334632b9,0x28cf281f,0x2fe22ec3,0x2d262cce,0x342f33d3,0x1f120000,0x24e90000,0x2bf22b11,0x317f30e4,
0x254d2311,0x2b5c28e8,0x2cdb2c6a,0x32b33219,0x286b2711,0x2e202ce7,0x2dbc2d4c,0x33e5334c,0x2a2f294d,0x30482f59,0x2e9d2e2d,0x348a343e,
0x20520000,0x254d0000,0x2cdb2c51,0x31ee3147,0x267b2452,0x2bf2294d,0x2dee2d65,0x333a3294,0x29662852,0x2e9d2d4c,0x2f012e78,0x344133df,
0x2b8e2a7a,0x309f2fef,0x300a2f8b,0x34e43493,0x211b0000,0x25b20000,0x2dbc2d1a,0x325d31aa,0x27a8251b,0x2c4429b1,0x2f012e5f,0x33c0330f,
0x2a61291b,0x2f1a2db0,0x30232fa4,0x34903438,0x2c772ba7,0x30f63042,0x30c53074,0x353d34e7,0x21e40000,0x26160000,0x2e9d2de2,0x32cc320d,
0x286b25e4,0x2c902a16,0x300a2f59,0x34233389,0x2b5c29e3,0x2f972e14,0x30c53067,0x34de3481,0x2d262c6a,0x314d308d,0x317f3122,0x3596353a,
0x267b0000,0x28cf0000,0x333a326f,0x354f34bd,0x2cdb2a7a,0x2f332cce,0x34663402,0x366d35df,0x300a2e78,0x31fa30cb,0x352c34c9,0x378336f9,
0x31a430d7,0x34293328,0x35ee358d,0x38463805,0x26df0000,0x29010000,0x33a832d2,0x358434ed,0x2d262ade,0x2f7e2d00,0x34a8343e,0x36ad361a,
0x30482edc,0x323830fd,0x35793511,0x37ca373d,0x31fa3122,0x34543371,0x364535df,0x386e382a,0x27440000,0x29340000,0x340b3334,0x35b9351d,
0x2d712b43,0x2fc92d33,0x34ea347b,0x36eb3654,0x30862f40,0x3276312e,0x35c53558,0x38093780,0x3251316c,0x347e33ba,0x369b3631,0x38953850,
0x27a80000,0x29660000,0x34413396,0x35ee354c,0x2dbc2ba7,0x300a2d65,0x352c34b7,0x3729368d,0x30c52fa4,0x32b33160,0x3611359f,0x382c37c2,
0x32a731b6,0x34a83402,0x36f13682,0x38bb3874,0x28060000,0x29980000,0x347833f7,0x3622357c,0x2e072c06,0x302f2d97,0x356d34f3,0x376736c6,
0x31033004,0x32f03191,0x365c35e5,0x384e3802,0x32fd3201,0x34d23426,0x374536d2,0x38e13899,0x28390000,0x29ca0000,0x34ae342c,0x365635ab,
0x2e522c38,0x30552dc9,0x35ae352f,0x37a436ff,0x31413036,0x332e31c3,0x36a7362b,0x38713822,0x3352324b,0x34fc344b,0x37993721,0x390638bc,
0x286b0000,0x29fd0000,0x34e4345d,0x368a35da,0x2e9d2c6a,0x307a2dfb,0x35ee356a,0x37e03737,0x317f3067,0x336b31f4,0x36f13670,0x38923842,
0x33a83294,0x3526346f,0x37eb376f,0x392a38e0,0x289d0000,0x2a2f0000,0x351a348d,0x36be3608,0x2ee82c9c,0x309f2e2d,0x362e35a5,0x380e376f,
0x31bd3099,0x33a83226,0x373a36b5,0x38b43862,0x33fd32de,0x354f3493,0x381e37bd,0x394e3902,0x2a610000,0x2bf20000,0x36f13637,0x383e37a1,
0x30c52e5f,0x31ee2fef,0x382c37a6,0x390d38a8,0x33e53257,0x34e433df,0x38d43881,0x39c8396d,0x357934b7,0x36be35d4,0x39713924,0x3a6c3a1d,
0x2a930000,0x2c120000,0x37243665,0x385637cd,0x30ea2e91,0x32133010,0x384937dd,0x392838c1,0x34113288,0x35023408,0x38f538a0,0x39e43989,
0x35a234db,0x36e535f7,0x39933946,0x3a883a39,0x2ac50000,0x2c2b0000,0x37563693,0x386e37f9,0x310f2ec3,0x32383029,0x3866380a,0x394238db,
0x342f32b9,0x35203420,0x391438bf,0x39ff39a4,0x35cb34ff,0x370d361a,0x39b43966,0x3aa23a54,0x2af80000,0x2c440000,0x378836c1,0x38853812,
0x31342ef5,0x325d3042,0x38833825,0x395c38f3,0x344e32ea,0x353d3438,0x393438dd,0x3a1a39be,0x35f43523,0x3734363c,0x39d53986,0x3abc3a6f,
0x2b2a0000,0x2c5e0000,0x37ba36ee,0x389d3828,0x315a2f27,0x3282305b,0x389f3840,0x3975390c,0x346c331b,0x355b3451,0x395338fb,0x3a3439d8,
0x361d3546,0x375c365f,0x39f539a6,0x3ad53a89,0x2b5c0000,0x2c770000,0x37eb371b,0x38b4383d,0x317f2f59,0x32a73074,0x38bb385a,0x398e3924,
0x348a334c,0x35793469,0x39713918,0x3a4e39f2,0x3645356a,0x37833682,0x3a1439c5,0x3aed3aa2,0x2b8e0000,0x2c900000,0x380e3748,0x38ca3852,
0x31a42f8b,0x32cc308d,0x38d73874,0x39a7393c,0x34a8337d,0x35963481,0x398e3935,0x3a663a0b,0x366d358d,0x37a936a4,0x3a3239e3,0x3b043aba,
0x2bc00000,0x2ca90000,0x38263775,0x38e13867,0x31c92fbd,0x32f030a6,0x38f2388e,0x39bf3954,0x34c633ae,0x35b33499,0x39ab3951,0x3a7f3a23,
0x369635b1,0x37d036c6,0x3a4f3a00,0x3b1b3ad1,0x2cc20000,0x2d8a0000,0x38f7387c,0x39a0391d,0x331530be,0x341d3185,0x39d7396b,0x3a863a19,
0x35d134b1,0x36b83570,0x3a963a3b,0x3b393ae6,0x37f636e8,0x389037f3,0x3b303ae8,0x3bb53b7f,0x2cdb0000,0x2da30000,0x390d3891,0x39b43930,
0x333a30d7,0x342f319e,0x39ef3982,0x3a9a3a2d,0x35ee34c9,0x36d43587,0x3aad3a52,0x3b4b3af9,0x380e370a,0x38a2380a,0x3b443afe,0x3bc13b8e,
0x2cf40000,0x2dbc0000,0x392338a6,0x39c83943,0x335f30f0,0x344131b6,0x3a053999,0x3aad3a41,0x360b34e1,0x36f1359f,0x3ac33a69,0x3b5b3b0b,
0x3821372c,0x38b4381a,0x3b573b13,0x3bcd3b9c,0x2d0d0000,0x2dd50000,0x393938ba,0x39db3956,0x33833109,0x345431cf,0x3a1c39af,0x3ac03a54,
0x362834f9,0x370d35b6,0x3ad93a7f,0x3b6b3b1d,0x3834374e,0x38c5382a,0x3b693b27,0x3bd63ba9,0x2d260000,0x2dee0000,0x394e38ce,0x39ef3969,
0x33a83122,0x346631e8,0x3a3239c5,0x3ad23a67,0x36453511,0x372935ce,0x3aed3a95,0x3b7a3b2e,0x3846376f,0x38d7383a,0x3b7b3b3a,0x3bdf3bb5,
0x2d3f0000,0x2e070000,0x396338e2,0x3a01397b,0x33cd313b,0x34783201,0x3a4839da,0x3ae43a7a,0x36623529,0x374535e5,0x3b013aaa,0x3b883b3e,
0x38593790,0x38e8384a,0x3b8b3b4c,0x3be73bc0,0x2d580000,0x2e200000,0x397838f6,0x3a14398d,0x33f13153,0x348a3219,0x3a5d39f0,0x3af53a8c,
0x367f3540,0x376135fd,0x3b153abf,0x3b953b4e,0x386b37b2,0x38fa385a,0x3b9a3b5e,0x3bee3bcb,0x2d710000,0x2e390000,0x398c3909,0x3a26399f,
0x340b316c,0x349c3232,0x3a723a04,0x3b063a9e,0x369b3558,0x377d3614,0x3b273ad3,0x3ba23b5d,0x387e37d2,0x390b386a,0x3ba83b6f,0x3bf43bd4,
0x0,0x0,0x0,0x0,0x2a3e0000,0x30722e1f,0x32a731a8,0x33d93364,0x2e1f0000,0x336431a8,0x33643400,0x2e1f31a8,
0x30720000,0x33d93364,0x2a3e31a8,0xb2a7ae1f,0x31a80000,0x31a83400,0xb1a80000,0xb1a8b400,0x32a70000,0x2a3e3364,0xb3d9b1a8,0x3072ae1f,
0x33640000,0xae1f31a8,0xae1fb400,0x336431a8,0x33d90000,0xb2a72e1f,0x3072b1a8,0xaa3e3364,0x34000000,0xb4000000,0x34000000,0xb4000000,
0x33d90000,0xb2a7ae1f,0x307231a8,0xaa3eb364,0x33640000,0xae1fb1a8,0xae1f3400,0x3364b1a8,0x32a70000,0x2a3eb364,0xb3d931a8,0x30722e1f,
0x31a80000,0x31a8b400,0xb1a80000,0xb1a83400,0x30720000,0x33d9b364,0x2a3eb1a8,0xb2a72e1f,0x2e1f0000,0x3364b1a8,0x3364b400,0x2e1fb1a8,
0x2a3e0000,0x3072ae1f,0x32a7b1a8,0x33d9b364,0x0,0x0,0x0,0x0,0xaa3e0000,0xb0722e1f,0xb2a731a8,0xb3d93364,
0xae1f0000,0xb36431a8,0xb3643400,0xae1f31a8,0xb0720000,0xb3d93364,0xaa3e31a8,0x32a7ae1f,0xb1a80000,0xb1a83400,0x31a80000,0x31a8b400,
0xb2a70000,0xaa3e3364,0x33d9b1a8,0xb072ae1f,0xb3640000,0x2e1f31a8,0x2e1fb400,0xb36431a8,0xb3d90000,0x32a72e1f,0xb072b1a8,0x2a3e3364,
0xb4000000,0x34000000,0xb4000000,0x34000000,0xb3d90000,0x32a7ae1f,0xb07231a8,0x2a3eb364,0xb3640000,0x2e1fb1a8,0x2e1f3400,0xb364b1a8,
0xb2a70000,0xaa3eb364,0x33d931a8,0xb0722e1f,0xb1a80000,0xb1a8b400,0x31a80000,0x31a83400,0xb0720000,0xb3d9b364,0xaa3eb1a8,0x32a72e1f,
0xae1f0000,0xb364b1a8,0xb364b400,0xae1fb1a8,0xaa3e0000,0xb072ae1f,0xb2a7b1a8,0xb3d9b364,0x0,0x0,0x0,0x0,
0x33d93400,0x32a73364,0x307231a8,0x2a3e2e1f,0xae1f0000,0xb364b1a8,0xb364b400,0xae1fb1a8,0xb2a7b400,0x2a3eae1f,0x33d931a8,0x30723364,
0x31a80000,0x31a83400,0xb1a80000,0xb1a8b400,0x30723400,0xb3d9ae1f,0x2a3eb1a8,0x32a73364,0xb3640000,0x2e1fb1a8,0x2e1f3400,0xb364b1a8,
0xaa3eb400,0x30723364,0xb2a7b1a8,0x33d92e1f,0x34000000,0xb4000000,0x34000000,0xb4000000,0xaa3e3400,0x3072b364,0xb2a731a8,0x33d9ae1f,
0xb3640000,0x2e1f31a8,0x2e1fb400,0xb36431a8,0x3072b400,0xb3d92e1f,0x2a3e31a8,0x32a7b364,0x31a80000,0x31a8b400,0xb1a80000,0xb1a83400,
0xb2a73400,0x2a3e2e1f,0x33d9b1a8,0x3072b364,0xae1f0000,0xb36431a8,0xb3643400,0xae1f31a8,0x33d9b400,0x32a7b364,0x3072b1a8,0x2a3eae1f,
0x0,0x0,0x0,0x0,0xb3d93400,0xb2a73364,0xb07231a8,0xaa3e2e1f,0x2e1f0000,0x3364b1a8,0x3364b400,0x2e1fb1a8,
0x32a7b400,0xaa3eae1f,0xb3d931a8,0xb0723364,0xb1a80000,0xb1a83400,0x31a80000,0x31a8b400,0xb0723400,0x33d9ae1f,0xaa3eb1a8,0xb2a73364,
0x33640000,0xae1fb1a8,0xae1f3400,0x3364b1a8,0x2a3eb400,0xb0723364,0x32a7b1a8,0xb3d92e1f,0xb4000000,0x34000000,0xb4000000,0x34000000,
0x2a3e3400,0xb072b364,0x32a731a8,0xb3d9ae1f,0x33640000,0xae1f31a8,0xae1fb400,0x336431a8,0xb072b400,0x33d92e1f,0xaa3e31a8,0xb2a7b364,
0xb1a80000,0xb1a8b400,0x31a80000,0x31a83400,0x32a73400,0xaa3e2e1f,0xb3d9b1a8,0xb072b364,0x2e1f0000,0x336431a8,0x33643400,0x2e1f31a8,
0xb3d9b400,0xb2a7b364,0xb072b1a8,0xaa3eae1f,0x0,0x0,0x0,0x0,0xaa3e0000,0xb072ae1f,0xb2a7b1a8,0xb3d9b364,
0x2e1f0000,0x336431a8,0x33643400,0x2e1f31a8,0xb0720000,0xb3d9b364,0xaa3eb1a8,0x32a72e1f,0x31a80000,0x31a83400,0xb1a80000,0xb1a8b400,
0xb2a70000,0xaa3eb364,0x33d931a8,0xb0722e1f,0x33640000,0xae1f31a8,0xae1fb400,0x336431a8,0xb3d90000,0x32a7ae1f,0xb07231a8,0x2a3eb364,
0x34000000,0xb4000000,0x34000000,0xb4000000,0xb3d90000,0x32a72e1f,0xb072b1a8,0x2a3e3364,0x33640000,0xae1fb1a8,0xae1f3400,0x3364b1a8,
0xb2a70000,0xaa3e3364,0x33d9b1a8,0xb072ae1f,0x31a80000,0x31a8b400,0xb1a80000,0xb1a83400,0xb0720000,0xb3d93364,0xaa3e31a8,0x32a7ae1f,
0x2e1f0000,0x3364b1a8,0x3364b400,0x2e1fb1a8,0xaa3e0000,0xb0722e1f,0xb2a731a8,0xb3d93364,0x0,0x0,0x0,0x0,
0x2a3e0000,0x3072ae1f,0x32a7b1a8,0x33d9b364,0xae1f0000,0xb36431a8,0xb3643400,0xae1f31a8,0x30720000,0x33d9b364,0x2a3eb1a8,0xb2a72e1f,
0xb1a80000,0xb1a83400,0x31a80000,0x31a8b400,0x32a70000,0x2a3eb364,0xb3d931a8,0x30722e1f,0xb3640000,0x2e1f31a8,0x2e1fb400,0xb36431a8,
0x33d90000,0xb2a7ae1f,0x307231a8,0xaa3eb364,0xb4000000,0x34000000,0xb4000000,0x34000000,0x33d90000,0xb2a72e1f,0x3072b1a8,0xaa3e3364,
0xb3640000,0x2e1fb1a8,0x2e1f3400,0xb364b1a8,0x32a70000,0x2a3e3364,0xb3d9b1a8,0x3072ae1f,0xb1a80000,0xb1a8b400,0x31a80000,0x31a83400,
0x30720000,0x33d93364,0x2a3e31a8,0xb2a7ae1f,0xae1f0000,0xb364b1a8,0xb364b400,0xae1fb1a8,0x2a3e0000,0x30722e1f,0x32a731a8,0x33d93364,
0x0,0x0,0x0,0x0,0xb3d9b400,0xb2a7b364,0xb072b1a8,0xaa3eae1f,0xae1f0000,0xb364b1a8,0xb364b400,0xae1fb1a8,
0x32a73400,0xaa3e2e1f,0xb3d9b1a8,0xb072b364,0x31a80000,0x31a83400,0xb1a80000,0xb1a8b400,0xb072b400,0x33d92e1f,0xaa3e31a8,0xb2a7b364,
0xb3640000,0x2e1fb1a8,0x2e1f3400,0xb364b1a8,0x2a3e3400,0xb072b364,0x32a731a8,0xb3d9ae1f,0x34000000,0xb4000000,0x34000000,0xb4000000,
0x2a3eb400,0xb0723364,0x32a7b1a8,0xb3d92e1f,0xb3640000,0x2e1f31a8,0x2e1fb400,0xb36431a8,0xb0723400,0x33d9ae1f,0xaa3eb1a8,0xb2a73364,
0x31a80000,0x31a8b400,0xb1a80000,0xb1a83400,0x32a7b400,0xaa3eae1f,0xb3d931a8,0xb0723364,0xae1f0000,0xb36431a8,0xb3643400,0xae1f31a8,
0xb3d93400,0xb2a73364,0xb07231a8,0xaa3e2e1f,0x0,0x0,0x0,0x0,0x33d9b400,0x32a7b364,0x3072b1a8,0x2a3eae1f,
0x2e1f0000,0x3364b1a8,0x3364b400,0x2e1fb1a8,0xb2a73400,0x2a3e2e1f,0x33d9b1a8,0x3072b364,0xb1a80000,0xb1a83400,0x31a80000,0x31a8b400,
0x3072b400,0xb3d92e1f,0x2a3e31a8,0x32a7b364,0x33640000,0xae1fb1a8,0xae1f3400,0x3364b1a8,0xaa3e3400,0x3072b364,0xb2a731a8,0x33d9ae1f,
0xb4000000,0x34000000,0xb4000000,0x34000000,0xaa3eb400,0x30723364,0xb2a7b1a8,0x33d92e1f,0x33640000,0xae1f31a8,0xae1fb400,0x336431a8,
0x30723400,0xb3d9ae1f,0x2a3eb1a8,0x32a73364,0xb1a80000,0xb1a8b400,0x31a80000,0x31a83400,0xb2a7b400,0x2a3eae1f,0x33d931a8,0x30723364,
0x2e1f0000,0x336431a8,0x33643400,0x2e1f31a8,0x33d93400,0x32a73364,0x307231a8,0x2a3e2e1f,0x34003400,0x34003400,0x34003400,0x34003400,
0x33d93400,0x32a73364,0x307231a8,0x2a3e2e1f,0x33643400,0x2e1f31a8,0xae1f0000,0xb364b1a8,0x32a73400,0xaa3e2e1f,0xb3d9b1a8,0xb072b364,
0x31a83400,0xb1a80000,0xb1a8b400,0x31a80000,0x30723400,0xb3d9ae1f,0x2a3eb1a8,0x32a73364,0x2e1f3400,0xb364b1a8,0x33640000,0xae1f31a8,
0x2a3e3400,0xb072b364,0x32a731a8,0xb3d9ae1f,0x3400,0xb400,0x3400,0xb400,0xaa3e3400,0x3072b364,0xb2a731a8,0x33d9ae1f,
0xae1f3400,0x3364b1a8,0xb3640000,0x2e1f31a8,0xb0723400,0x33d9ae1f,0xaa3eb1a8,0xb2a73364,0xb1a83400,0x31a80000,0x31a8b400,0xb1a80000,
0xb2a73400,0x2a3e2e1f,0x33d9b1a8,0x3072b364,0xb3643400,0xae1f31a8,0x2e1f0000,0x3364b1a8,0xb3d93400,0xb2a73364,0xb07231a8,0xaa3e2e1f,
0xb4003400,0xb4003400,0xb4003400,0xb4003400,0xb3d93400,0xb2a73364,0xb07231a8,0xaa3e2e1f,0xb3643400,0xae1f31a8,0x2e1f0000,0x3364b1a8,
0xb2a73400,0x2a3e2e1f,0x33d9b1a8,0x3072b364,0xb1a83400,0x31a80000,0x31a8b400,0xb1a80000,0xb0723400,0x33d9ae1f,0xaa3eb1a8,0xb2a73364,
0xae1f3400,0x3364b1a8,0xb3640000,0x2e1f31a8,0xaa3e3400,0x3072b364,0xb2a731a8,0x33d9ae1f,0x3400,0xb400,0x3400,0xb400,
0x2a3e3400,0xb072b364,0x32a731a8,0xb3d9ae1f,0x2e1f3400,0xb364b1a8,0x33640000,0xae1f31a8,0x30723400,0xb3d9ae1f,0x2a3eb1a8,0x32a73364,
0x31a83400,0xb1a80000,0xb1a8b400,0x31a80000,0x32a73400,0xaa3e2e1f,0xb3d9b1a8,0xb072b364,0x33643400,0x2e1f31a8,0xae1f0000,0xb364b1a8,
0x33d93400,0x32a73364,0x307231a8,0x2a3e2e1f,0x34003400,0x34003400,0x34003400,0x34003400,0xaa3e0000,0xb072ae1f,0xb2a7b1a8,0xb3d9b364,
0xb364b400,0xae1fb1a8,0x2e1f0000,0x336431a8,0x30720000,0x33d93364,0x2a3e31a8,0xb2a7ae1f,0x31a83400,0xb1a80000,0xb1a8b400,0x31a80000,
0xb2a70000,0xaa3eb364,0x33d931a8,0xb0722e1f,0xae1fb400,0x336431a8,0xb3640000,0x2e1fb1a8,0x33d90000,0xb2a72e1f,0x3072b1a8,0xaa3e3364,
0x3400,0xb400,0x3400,0xb400,0xb3d90000,0x32a72e1f,0xb072b1a8,0x2a3e3364,0x2e1fb400,0xb36431a8,0x33640000,0xae1fb1a8,
0x32a70000,0x2a3eb364,0xb3d931a8,0x30722e1f,0xb1a83400,0x31a80000,0x31a8b400,0xb1a80000,0xb0720000,0xb3d93364,0xaa3e31a8,0x32a7ae1f,
0x3364b400,0x2e1fb1a8,0xae1f0000,0xb36431a8,0x2a3e0000,0x3072ae1f,0x32a7b1a8,0x33d9b364,0xb4003400,0xb4003400,0xb4003400,0xb4003400,
0x2a3e0000,0x3072ae1f,0x32a7b1a8,0x33d9b364,0x3364b400,0x2e1fb1a8,0xae1f0000,0xb36431a8,0xb0720000,0xb3d93364,0xaa3e31a8,0x32a7ae1f,
0xb1a83400,0x31a80000,0x31a8b400,0xb1a80000,0x32a70000,0x2a3eb364,0xb3d931a8,0x30722e1f,0x2e1fb400,0xb36431a8,0x33640000,0xae1fb1a8,
0xb3d90000,0x32a72e1f,0xb072b1a8,0x2a3e3364,0x3400,0xb400,0x3400,0xb400,0x33d90000,0xb2a72e1f,0x3072b1a8,0xaa3e3364,
0xae1fb400,0x336431a8,0xb3640000,0x2e1fb1a8,0xb2a70000,0xaa3eb364,0x33d931a8,0xb0722e1f,0x31a83400,0xb1a80000,0xb1a8b400,0x31a80000,
0x30720000,0x33d93364,0x2a3e31a8,0xb2a7ae1f,0xb364b400,0xae1fb1a8,0x2e1f0000,0x336431a8,0xaa3e0000,0xb072ae1f,0xb2a7b1a8,0xb3d9b364,
0x34003400,0x34003400,0x34003400,0x34003400,0xb3d9b400,0xb2a7b364,0xb072b1a8,0xaa3eae1f,0x33643400,0x2e1f31a8,0xae1f0000,0xb364b1a8,
0xb2a7b400,0x2a3eae1f,0x33d931a8,0x30723364,0x31a83400,0xb1a80000,0xb1a8b400,0x31a80000,0xb072b400,0x33d92e1f,0xaa3e31a8,0xb2a7b364,
0x2e1f3400,0xb364b1a8,0x33640000,0xae1f31a8,0xaa3eb400,0x30723364,0xb2a7b1a8,0x33d92e1f,0x3400,0xb400,0x3400,0xb400,
0x2a3eb400,0xb0723364,0x32a7b1a8,0xb3d92e1f,0xae1f3400,0x3364b1a8,0xb3640000,0x2e1f31a8,0x3072b400,0xb3d92e1f,0x2a3e31a8,0x32a7b364,
0xb1a83400,0x31a80000,0x31a8b400,0xb1a80000,0x32a7b400,0xaa3eae1f,0xb3d931a8,0xb0723364,0xb3643400,0xae1f31a8,0x2e1f0000,0x3364b1a8,
0x33d9b400,0x32a7b364,0x3072b1a8,0x2a3eae1f,0xb4003400,0xb4003400,0xb4003400,0xb4003400,0x33d9b400,0x32a7b364,0x3072b1a8,0x2a3eae1f,
0xb3643400,0xae1f31a8,0x2e1f0000,0x3364b1a8,0x32a7b400,0xaa3eae1f,0xb3d931a8,0xb0723364,0xb1a83400,0x31a80000,0x31a8b400,0xb1a80000,
0x3072b400,0xb3d92e1f,0x2a3e31a8,0x32a7b364,0xae1f3400,0x3364b1a8,0xb3640000,0x2e1f31a8,0x2a3eb400,0xb0723364,0x32a7b1a8,0xb3d92e1f,
0x3400,0xb400,0x3400,0xb400,0xaa3eb400,0x30723364,0xb2a7b1a8,0x33d92e1f,0x2e1f3400,0xb364b1a8,0x33640000,0xae1f31a8,
0xb072b400,0x33d92e1f,0xaa3e31a8,0xb2a7b364,0x31a83400,0xb1a80000,0xb1a8b400,0x31a80000,0xb2a7b400,0x2a3eae1f,0x33d931a8,0x30723364,
0x33643400,0x2e1f31a8,0xae1f0000,0xb364b1a8,0xb3d9b400,0xb2a7b364,0xb072b1a8,0xaa3eae1f,0x34003400,0x34003400,0x34003400,0x34003400,
0x2a3e0000,0x30722e1f,0x32a731a8,0x33d93364,0xb364b400,0xae1fb1a8,0x2e1f0000,0x336431a8,0xb0720000,0xb3d9b364,0xaa3eb1a8,0x32a72e1f,
0x31a83400,0xb1a80000,0xb1a8b400,0x31a80000,0x32a70000,0x2a3e3364,0xb3d9b1a8,0x3072ae1f,0xae1fb400,0x336431a8,0xb3640000,0x2e1fb1a8,
0xb3d90000,0x32a7ae1f,0xb07231a8,0x2a3eb364,0x3400,0xb400,0x3400,0xb400,0x33d90000,0xb2a7ae1f,0x307231a8,0xaa3eb364,
0x2e1fb400,0xb36431a8,0x33640000,0xae1fb1a8,0xb2a70000,0xaa3e3364,0x33d9b1a8,0xb072ae1f,0xb1a83400,0x31a80000,0x31a8b400,0xb1a80000,
0x30720000,0x33d9b364,0x2a3eb1a8,0xb2a72e1f,0x3364b400,0x2e1fb1a8,0xae1f0000,0xb36431a8,0xaa3e0000,0xb0722e1f,0xb2a731a8,0xb3d93364,
0xb4003400,0xb4003400,0xb4003400,0xb4003400,0xaa3e0000,0xb0722e1f,0xb2a731a8,0xb3d93364,0x3364b400,0x2e1fb1a8,0xae1f0000,0xb36431a8,
0x30720000,0x33d9b364,0x2a3eb1a8,0xb2a72e1f,0xb1a83400,0x31a80000,0x31a8b400,0xb1a80000,0xb2a70000,0xaa3e3364,0x33d9b1a8,0xb072ae1f,
0x2e1fb400,0xb36431a8,0x33640000,0xae1fb1a8,0x33d90000,0xb2a7ae1f,0x307231a8,0xaa3eb364,0x3400,0xb400,0x3400,0xb400,
0xb3d90000,0x32a7ae1f,0xb07231a8,0x2a3eb364,0xae1fb400,0x336431a8,0xb3640000,0x2e1fb1a8,0x32a70000,0x2a3e3364,0xb3d9b1a8,0x3072ae1f,
0x31a83400,0xb1a80000,0xb1a8b400,0x31a80000,0xb0720000,0xb3d9b364,0xaa3eb1a8,0x32a72e1f,0xb364b400,0xae1fb1a8,0x2e1f0000,0x336431a8,
0x2a3e0000,0x30722e1f,0x32a731a8,0x33d93364,0x0,0x0,0x0,0x0,0xaa3e0000,0xb072ae1f,0xb2a7b1a8,0xb3d9b364,
0xae1f0000,0xb364b1a8,0xb364b400,0xae1fb1a8,0xb0720000,0xb3d9b364,0xaa3eb1a8,0x32a72e1f,0xb1a80000,0xb1a8b400,0x31a80000,0x31a83400,
0xb2a70000,0xaa3eb364,0x33d931a8,0xb0722e1f,0xb3640000,0x2e1fb1a8,0x2e1f3400,0xb364b1a8,0xb3d90000,0x32a7ae1f,0xb07231a8,0x2a3eb364,
0xb4000000,0x34000000,0xb4000000,0x34000000,0xb3d90000,0x32a72e1f,0xb072b1a8,0x2a3e3364,0xb3640000,0x2e1f31a8,0x2e1fb400,0xb36431a8,
0xb2a70000,0xaa3e3364,0x33d9b1a8,0xb072ae1f,0xb1a80000,0xb1a83400,0x31a80000,0x31a8b400,0xb0720000,0xb3d93364,0xaa3e31a8,0x32a7ae1f,
0xae1f0000,0xb36431a8,0xb3643400,0xae1f31a8,0xaa3e0000,0xb0722e1f,0xb2a731a8,0xb3d93364,0x0,0x0,0x0,0x0,
0x2a3e0000,0x3072ae1f,0x32a7b1a8,0x33d9b364,0x2e1f0000,0x3364b1a8,0x3364b400,0x2e1fb1a8,0x30720000,0x33d9b364,0x2a3eb1a8,0xb2a72e1f,
0x31a80000,0x31a8b400,0xb1a80000,0xb1a83400,0x32a70000,0x2a3eb364,0xb3d931a8,0x30722e1f,0x33640000,0xae1fb1a8,0xae1f3400,0x3364b1a8,
0x33d90000,0xb2a7ae1f,0x307231a8,0xaa3eb364,0x34000000,0xb4000000,0x34000000,0xb4000000,0x33d90000,0xb2a72e1f,0x3072b1a8,0xaa3e3364,
0x33640000,0xae1f31a8,0xae1fb400,0x336431a8,0x32a70000,0x2a3e3364,0xb3d9b1a8,0x3072ae1f,0x31a80000,0x31a83400,0xb1a80000,0xb1a8b400,
0x30720000,0x33d93364,0x2a3e31a8,0xb2a7ae1f,0x2e1f0000,0x336431a8,0x33643400,0x2e1f31a8,0x2a3e0000,0x30722e1f,0x32a731a8,0x33d93364,
0x0,0x0,0x0,0x0,0xb3d9b400,0xb2a7b364,0xb072b1a8,0xaa3eae1f,0x2e1f0000,0x336431a8,0x33643400,0x2e1f31a8,
0x32a73400,0xaa3e2e1f,0xb3d9b1a8,0xb072b364,0xb1a80000,0xb1a8b400,0x31a80000,0x31a83400,0xb072b400,0x33d92e1f,0xaa3e31a8,0xb2a7b364,
0x33640000,0xae1f31a8,0xae1fb400,0x336431a8,0x2a3e3400,0xb072b364,0x32a731a8,0xb3d9ae1f,0xb4000000,0x34000000,0xb4000000,0x34000000,
0x2a3eb400,0xb0723364,0x32a7b1a8,0xb3d92e1f,0x33640000,0xae1fb1a8,0xae1f3400,0x3364b1a8,0xb0723400,0x33d9ae1f,0xaa3eb1a8,0xb2a73364,
0xb1a80000,0xb1a83400,0x31a80000,0x31a8b400,0x32a7b400,0xaa3eae1f,0xb3d931a8,0xb0723364,0x2e1f0000,0x3364b1a8,0x3364b400,0x2e1fb1a8,
0xb3d93400,0xb2a73364,0xb07231a8,0xaa3e2e1f,0x0,0x0,0x0,0x0,0x33d9b400,0x32a7b364,0x3072b1a8,0x2a3eae1f,
0xae1f0000,0xb36431a8,0xb3643400,0xae1f31a8,0xb2a73400,0x2a3e2e1f,0x33d9b1a8,0x3072b364,0x31a80000,0x31a8b400,0xb1a80000,0xb1a83400,
0x3072b400,0xb3d92e1f,0x2a3e31a8,0x32a7b364,0xb3640000,0x2e1f31a8,0x2e1fb400,0xb36431a8,0xaa3e3400,0x3072b364,0xb2a731a8,0x33d9ae1f,
0x34000000,0xb4000000,0x34000000,0xb4000000,0xaa3eb400,0x30723364,0xb2a7b1a8,0x33d92e1f,0xb3640000,0x2e1fb1a8,0x2e1f3400,0xb364b1a8,
0x30723400,0xb3d9ae1f,0x2a3eb1a8,0x32a73364,0x31a80000,0x31a83400,0xb1a80000,0xb1a8b400,0xb2a7b400,0x2a3eae1f,0x33d931a8,0x30723364,
0xae1f0000,0xb364b1a8,0xb364b400,0xae1fb1a8,0x33d93400,0x32a73364,0x307231a8,0x2a3e2e1f,0x0,0x0,0x0,0x0,
0x2a3e0000,0x30722e1f,0x32a731a8,0x33d93364,0xae1f0000,0xb364b1a8,0xb364b400,0xae1fb1a8,0x30720000,0x33d93364,0x2a3e31a8,0xb2a7ae1f,
0xb1a80000,0xb1a8b400,0x31a80000,0x31a83400,0x32a70000,0x2a3e3364,0xb3d9b1a8,0x3072ae1f,0xb3640000,0x2e1fb1a8,0x2e1f3400,0xb364b1a8,
0x33d90000,0xb2a72e1f,0x3072b1a8,0xaa3e3364,0xb4000000,0x34000000,0xb4000000,0x34000000,0x33d90000,0xb2a7ae1f,0x307231a8,0xaa3eb364,
0xb3640000,0x2e1f31a8,0x2e1fb400,0xb36431a8,0x32a70000,0x2a3eb364,0xb3d931a8,0x30722e1f,0xb1a80000,0xb1a83400,0x31a80000,0x31a8b400,
0x30720000,0x33d9b364,0x2a3eb1a8,0xb2a72e1f,0xae1f0000,0xb36431a8,0xb3643400,0xae1f31a8,0x2a3e0000,0x3072ae1f,0x32a7b1a8,0x33d9b364,
0x0,0x0,0x0,0x0,0xaa3e0000,0xb0722e1f,0xb2a731a8,0xb3d93364,0x2e1f0000,0x3364b1a8,0x3364b400,0x2e1fb1a8,
0xb0720000,0xb3d93364,0xaa3e31a8,0x32a7ae1f,0x31a80000,0x31a8b400,0xb1a80000,0xb1a83400,0xb2a70000,0xaa3e3364,0x33d9b1a8,0xb072ae1f,
0x33640000,0xae1fb1a8,0xae1f3400,0x3364b1a8,0xb3d90000,0x32a72e1f,0xb072b1a8,0x2a3e3364,0x34000000,0xb4000000,0x34000000,0xb4000000,
0xb3d90000,0x32a7ae1f,0xb07231a8,0x2a3eb364,0x33640000,0xae1f31a8,0xae1fb400,0x336431a8,0xb2a70000,0xaa3eb364,0x33d931a8,0xb0722e1f,
0x31a80000,0x31a83400,0xb1a80000,0xb1a8b400,0xb0720000,0xb3d9b364,0xaa3eb1a8,0x32a72e1f,0x2e1f0000,0x336431a8,0x33643400,0x2e1f31a8,
0xaa3e0000,0xb072ae1f,0xb2a7b1a8,0xb3d9b364,0x0,0x0,0x0,0x0,0x33d93400,0x32a73364,0x307231a8,0x2a3e2e1f,
0x2e1f0000,0x336431a8,0x33643400,0x2e1f31a8,0xb2a7b400,0x2a3eae1f,0x33d931a8,0x30723364,0xb1a80000,0xb1a8b400,0x31a80000,0x31a83400,
0x30723400,0xb3d9ae1f,0x2a3eb1a8,0x32a73364,0x33640000,0xae1f31a8,0xae1fb400,0x336431a8,0xaa3eb400,0x30723364,0xb2a7b1a8,0x33d92e1f,
0xb4000000,0x34000000,0xb4000000,0x34000000,0xaa3e3400,0x3072b364,0xb2a731a8,0x33d9ae1f,0x33640000,0xae1fb1a8,0xae1f3400,0x3364b1a8,
0x3072b400,0xb3d92e1f,0x2a3e31a8,0x32a7b364,0xb1a80000,0xb1a83400,0x31a80000,0x31a8b400,0xb2a73400,0x2a3e2e1f,0x33d9b1a8,0x3072b364,
0x2e1f0000,0x3364b1a8,0x3364b400,0x2e1fb1a8,0x33d9b400,0x32a7b364,0x3072b1a8,0x2a3eae1f,0x0,0x0,0x0,0x0,
0xb3d93400,0xb2a73364,0xb07231a8,0xaa3e2e1f,0xae1f0000,0xb36431a8,0xb3643400,0xae1f31a8,0x32a7b400,0xaa3eae1f,0xb3d931a8,0xb0723364,
0x31a80000,0x31a8b400,0xb1a80000,0xb1a83400,0xb0723400,0x33d9ae1f,0xaa3eb1a8,0xb2a73364,0xb3640000,0x2e1f31a8,0x2e1fb400,0xb36431a8,
0x2a3eb400,0xb0723364,0x32a7b1a8,0xb3d92e1f,0x34000000,0xb4000000,0x34000000,0xb4000000,0x2a3e3400,0xb072b364,0x32a731a8,0xb3d9ae1f,
0xb3640000,0x2e1fb1a8,0x2e1f3400,0xb364b1a8,0xb072b400,0x33d92e1f,0xaa3e31a8,0xb2a7b364,0x31a80000,0x31a83400,0xb1a80000,0xb1a8b400,
0x32a73400,0xaa3e2e1f,0xb3d9b1a8,0xb072b364,0xae1f0000,0xb364b1a8,0xb364b400,0xae1fb1a8,0xb3d9b400,0xb2a7b364,0xb072b1a8,0xaa3eae1f,
};

typedef CUresult (*EncodeFn)(CUtensorMap*, CUtensorMapDataType, cuuint32_t, void*, const cuuint64_t*, const cuuint64_t*,
                             const cuuint32_t*, const cuuint32_t*, CUtensorMapInterleave, CUtensorMapSwizzle,
                             CUtensorMapL2promotion, CUtensorMapFloatOOBfill);

}

extern "C" void kernel_launch(void* const* d_in, const int* in_sizes, int n_in, void* d_out, int out_size) {
    Params p;
    p.x = (const __nv_bfloat16*)d_in[0];
    p.lar = (const __nv_bfloat16*)d_in[1];
    p.aim = (const __nv_bfloat16*)d_in[2];
    p.cr = (const __nv_bfloat16*)d_in[3];
    p.ci = (const __nv_bfloat16*)d_in[4];
    p.logdt = (const __nv_bfloat16*)d_in[5];
    p.dskip = (const __nv_bfloat16*)d_in[6];
    p.wr = (const __nv_bfloat16*)d_in[8];
    p.out = (__nv_bfloat16*)d_out;
    cudaGetSymbolAddress((void**)&p.sc, g_scratch);
    cudaGetSymbolAddress((void**)&p.tab, g_tab);

    void* fn = nullptr;
    cudaDriverEntryPointQueryResult qr;
    cudaGetDriverEntryPoint("cuTensorMapEncodeTiled", &fn, cudaEnableDefault, &qr);
    EncodeFn enc = (EncodeFn)fn;
    CUtensorMap tm_x, tm_g, tm_d;
    const cuuint32_t es[5] = {1, 1, 1, 1, 1};
    {
        const cuuint64_t gd[5] = {1024, 4, 64, 2, 4}, gs[4] = {4096, 65536, 2048, 16384};
        const cuuint32_t bx[5] = {16, 4, 64, 2, 2};
        enc(&tm_x, CU_TENSOR_MAP_DATA_TYPE_BFLOAT16, 5, d_in[0], gd, gs, bx, es, CU_TENSOR_MAP_INTERLEAVE_NONE,
            CU_TENSOR_MAP_SWIZZLE_32B, CU_TENSOR_MAP_L2_PROMOTION_NONE, CU_TENSOR_MAP_FLOAT_OOB_FILL_NONE);
    }
    {
        char *wg = (char*)d_in[9], *wu = (char*)d_in[10];
        p.up_first = wu < wg;
        const cuuint64_t gd[3] = {3584, 1024, 2}, gs[2] = {7168, (cuuint64_t)(p.up_first ? wg - wu : wu - wg)};
        const cuuint32_t bx[3] = {64, 32, 2};
        enc(&tm_g, CU_TENSOR_MAP_DATA_TYPE_BFLOAT16, 3, p.up_first ? wu : wg, gd, gs, bx, es, CU_TENSOR_MAP_INTERLEAVE_NONE,
            CU_TENSOR_MAP_SWIZZLE_128B, CU_TENSOR_MAP_L2_PROMOTION_NONE, CU_TENSOR_MAP_FLOAT_OOB_FILL_NONE);
    }
    {
        const cuuint64_t gd[3] = {1024, 3584, 1}, gs[2] = {2048, 2048 * 3584};
        const cuuint32_t bx[3] = {64, 64, 1};
        enc(&tm_d, CU_TENSOR_MAP_DATA_TYPE_BFLOAT16, 3, d_in[11], gd, gs, bx, es, CU_TENSOR_MAP_INTERLEAVE_NONE,
            CU_TENSOR_MAP_SWIZZLE_128B, CU_TENSOR_MAP_L2_PROMOTION_NONE, CU_TENSOR_MAP_FLOAT_OOB_FILL_NONE);
    }
    cudaFuncSetAttribute(fused_kernel, cudaFuncAttributeMaxDynamicSharedMemorySize, SM_TOTAL);
    fused_kernel<<<128, NTHREADS, SM_TOTAL>>>(p, tm_x, tm_g, tm_d);
}
```

```cpp
#include <cuda_runtime.h>
#include <cuda.h>
#include <cuda_bf16.h>
#include <cuda_fp16.h>
#include <stdint.h>

#define TG(i)
#define TS(i)
#define TSL(i)

#define TSW 0
#define XFIRST 8
#define XPROMO 0
#define NSLOT 6
#define DEPTH 4

namespace {

constexpr int NTHREADS = 640;
constexpr int SPIN_LIMIT = 1 << 16;

constexpr int SM_SLAB = 0;
constexpr int SM_RING = 65536;
constexpr int SM_F2   = SM_RING + NSLOT * 8192;
constexpr int SM_CH   = SM_F2 + 6144;
constexpr int SUB     = 1056;
constexpr int CH_SZ   = 12 * SUB;
constexpr int SM_XSEL = SM_CH + 8 * CH_SZ;
constexpr int SM_PAIR = SM_XSEL + 4096;
constexpr int SM_H    = SM_PAIR + 2048;
constexpr int SM_KEYS = SM_H + 1024;
constexpr int SM_TOK  = SM_KEYS + 64;
constexpr int SM_FIX  = SM_TOK + 16;
constexpr int SM_XRAW = SM_FIX + 32;
constexpr int SM_SCL  = SM_XRAW + 32;
constexpr int SM_PROBE = SM_SCL + 16;
constexpr int SM_BAR  = SM_PROBE + 64;
constexpr int SM_RED  = SM_XSEL;
constexpr int B_FULL = 0, B_EMPTY = 8, B_STG = 16, B_PROBE = 20, B_MISC = 24, B_ROW = 32, NBAR = 40;
constexpr int B_PEER = B_MISC, B_TOK = B_MISC + 1, B_FIX = B_MISC + 2, B_PAIR = B_MISC + 3, B_SLAB = B_MISC + 4;
constexpr int SM_TOTAL = SM_BAR + NBAR * 8;
static_assert(SM_TOTAL <= 232448 && NSLOT < 8 && DEPTH <= NSLOT && DEPTH <= 4, "smem");
__host__ __device__ constexpr int full_bar(int n) { return B_FULL + (n == 23 ? 7 : n % NSLOT); }
__host__ __device__ constexpr int full_par(int n) { return n == 23 ? 0 : (n / NSLOT) & 1; }
constexpr int KP = 272;

struct Scratch {
    uint4 stats[1024];
    uint32_t part[128 * 56 * 16];
    uint32_t epoch;
};
__device__ Scratch g_scratch;

struct Params {
    const __nv_bfloat16 *lar, *aim, *cr, *ci, *logdt, *dskip;
    const __nv_bfloat16 *x, *wr;
    __nv_bfloat16* out;
    Scratch* sc;
    const uint4* tab;
    int up_first;
    const __nv_bfloat16 *w2, *wd;
};

__device__ __forceinline__ uint4 ldg128(const void* p) {
    uint4 v; asm volatile("ld.global.nc.v4.u32 {%0,%1,%2,%3}, [%4];" : "=r"(v.x), "=r"(v.y), "=r"(v.z), "=r"(v.w) : "l"(p)); return v;
}
__device__ __forceinline__ uint4 ld_relaxed128(const void* p) {
    uint4 v;
    asm volatile("{ .reg .b128 t; ld.relaxed.gpu.global.b128 t, [%4]; mov.b128 {%0,%1,%2,%3}, t; }"
                 : "=r"(v.x), "=r"(v.y), "=r"(v.z), "=r"(v.w) : "l"(p) : "memory");
    return v;
}
__device__ __forceinline__ void st_relaxed128(void* p, uint4 v) {
    asm volatile("{ .reg .b128 t; mov.b128 t, {%1,%2,%3,%4}; st.relaxed.gpu.global.b128 [%0], t; }"
                 :: "l"(p), "r"(v.x), "r"(v.y), "r"(v.z), "r"(v.w) : "memory");
}
__device__ __forceinline__ void st_relaxed32(void* p, uint32_t v) {
    asm volatile("st.relaxed.gpu.global.u32 [%0], %1;" :: "l"(p), "r"(v) : "memory");
}
__device__ __forceinline__ uint32_t lds32(uint32_t a) { uint32_t v; asm volatile("ld.shared.u32 %0, [%1];" : "=r"(v) : "r"(a)); return v; }
__device__ __forceinline__ uint32_t lds16(uint32_t a) { uint32_t v; asm volatile("ld.shared.u16 %0, [%1];" : "=r"(v) : "r"(a)); return v; }
__device__ __forceinline__ uint2 lds64(uint32_t a) { uint2 v; asm volatile("ld.shared.v2.u32 {%0,%1}, [%2];" : "=r"(v.x), "=r"(v.y) : "r"(a)); return v; }
__device__ __forceinline__ uint4 lds128(uint32_t a) {
    uint4 v; asm volatile("ld.shared.v4.u32 {%0,%1,%2,%3}, [%4];" : "=r"(v.x), "=r"(v.y), "=r"(v.z), "=r"(v.w) : "r"(a)); return v;
}
__device__ __forceinline__ void sts16(uint32_t a, uint32_t v) { asm volatile("st.shared.u16 [%0], %1;" :: "r"(a), "h"((uint16_t)v) : "memory"); }
__device__ __forceinline__ void sts32(uint32_t a, uint32_t v) { asm volatile("st.shared.u32 [%0], %1;" :: "r"(a), "r"(v) : "memory"); }
__device__ __forceinline__ void sts64(uint32_t a, uint32_t x, uint32_t y) { asm volatile("st.shared.v2.u32 [%0], {%1,%2};" :: "r"(a), "r"(x), "r"(y) : "memory"); }
__device__ __forceinline__ void sts128(uint32_t a, uint32_t x, uint32_t y, uint32_t z, uint32_t w) {
    asm volatile("st.shared.v4.u32 [%0], {%1,%2,%3,%4};" :: "r"(a), "r"(x), "r"(y), "r"(z), "r"(w) : "memory");
}
__device__ __forceinline__ void ldsm4(uint32_t a, uint32_t& r0, uint32_t& r1, uint32_t& r2, uint32_t& r3) {
    asm volatile("ldmatrix.sync.aligned.m8n8.x4.shared.b16 {%0,%1,%2,%3}, [%4];" : "=r"(r0), "=r"(r1), "=r"(r2), "=r"(r3) : "r"(a));
}
__device__ __forceinline__ void mma_f16(float (&d)[4], uint32_t a0, uint32_t a1, uint32_t a2, uint32_t a3, uint32_t b0, uint32_t b1) {
    asm("mma.sync.aligned.m16n8k16.row.col.f32.f16.f16.f32 {%0,%1,%2,%3}, {%4,%5,%6,%7}, {%8,%9}, {%0,%1,%2,%3};"
        : "+f"(d[0]), "+f"(d[1]), "+f"(d[2]), "+f"(d[3]) : "r"(a0), "r"(a1), "r"(a2), "r"(a3), "r"(b0), "r"(b1));
}
__device__ __forceinline__ void mma_bf16(float (&d)[4], uint32_t a0, uint32_t a1, uint32_t a2, uint32_t a3, uint32_t b0, uint32_t b1) {
    asm("mma.sync.aligned.m16n8k16.row.col.f32.bf16.bf16.f32 {%0,%1,%2,%3}, {%4,%5,%6,%7}, {%8,%9}, {%0,%1,%2,%3};"
        : "+f"(d[0]), "+f"(d[1]), "+f"(d[2]), "+f"(d[3]) : "r"(a0), "r"(a1), "r"(a2), "r"(a3), "r"(b0), "r"(b1));
}
__device__ __forceinline__ uint32_t prmt(uint32_t a, uint32_t b, uint32_t s) { uint32_t d; asm("prmt.b32 %0, %1, %2, %3;" : "=r"(d) : "r"(a), "r"(b), "r"(s)); return d; }
__device__ __forceinline__ uint32_t pack_h(float lo, float hi) { uint32_t d; asm("cvt.rn.f16x2.f32 %0, %1, %2;" : "=r"(d) : "f"(hi), "f"(lo)); return d; }
__device__ __forceinline__ uint32_t pack_b(float lo, float hi) { uint32_t d; asm("cvt.rn.bf16x2.f32 %0, %1, %2;" : "=r"(d) : "f"(hi), "f"(lo)); return d; }
__device__ __forceinline__ float blo(uint32_t v) { return __uint_as_float(v << 16); }
__device__ __forceinline__ float bhi(uint32_t v) { return __uint_as_float(v & 0xFFFF0000u); }
__device__ __forceinline__ float rb(float v) { return blo(pack_b(v, v)); }
__device__ __forceinline__ uint32_t bsub2(uint32_t a, uint32_t b) { uint32_t d; asm("sub.rn.bf16x2 %0, %1, %2;" : "=r"(d) : "r"(a), "r"(b)); return d; }
__device__ __forceinline__ uint32_t bmul2(uint32_t a, uint32_t b) { uint32_t d; asm("mul.rn.bf16x2 %0, %1, %2;" : "=r"(d) : "r"(a), "r"(b)); return d; }
__device__ __forceinline__ uint32_t bfma2(uint32_t a, uint32_t b, uint32_t c) { uint32_t d; asm("fma.rn.bf16x2 %0, %1, %2, %3;" : "=r"(d) : "r"(a), "r"(b), "r"(c)); return d; }
__device__ __forceinline__ uint32_t norm2(uint32_t x, uint32_t m, uint32_t hi, uint32_t lo) {
    uint32_t a = bsub2(x, m);
    return bfma2(a, hi, bmul2(a, lo));
}
__device__ __forceinline__ float ex2(float v) { float d; asm("ex2.approx.ftz.f32 %0, %1;" : "=f"(d) : "f"(v)); return d; }
__device__ __forceinline__ float rcp(float v) { float d; asm("rcp.approx.ftz.f32 %0, %1;" : "=f"(d) : "f"(v)); return d; }
__device__ __forceinline__ float sigmoidf_(float v) { return rcp(1.0f + ex2(-1.4426950408889634f * v)); }
__device__ __forceinline__ float siluf_(float v) { return v * sigmoidf_(v); }

__device__ __forceinline__ void mbar_init(uint32_t a, int n) { asm volatile("mbarrier.init.shared::cta.b64 [%0], %1;" :: "r"(a), "r"(n) : "memory"); }
__device__ __forceinline__ void mbar_expect(uint32_t a, int tx) { asm volatile("mbarrier.arrive.expect_tx.shared::cta.b64 _, [%0], %1;" :: "r"(a), "r"(tx) : "memory"); }
__device__ __forceinline__ void mbar_arrive(uint32_t a) { asm volatile("mbarrier.arrive.shared::cta.b64 _, [%0];" :: "r"(a) : "memory"); }
__device__ __forceinline__ void mbar_wait(uint32_t a, int parity) {
    asm volatile("{ .reg .pred p;\n"
                 "W: mbarrier.try_wait.parity.shared::cta.b64 p, [%0], %1;\n"
                 "@!p bra.uni W; }" :: "r"(a), "r"(parity) : "memory");
}
__device__ __forceinline__ uint32_t mapa(uint32_t a, uint32_t rank) { uint32_t d; asm("mapa.shared::cluster.u32 %0, %1, %2;" : "=r"(d) : "r"(a), "r"(rank)); return d; }
__device__ __forceinline__ void st_async4(uint32_t a, uint32_t x, uint32_t y, uint32_t z, uint32_t w, uint32_t bar) {
    asm volatile("st.async.weak.shared::cluster.mbarrier::complete_tx::bytes.v4.b32 [%0], {%1,%2,%3,%4}, [%5];"
                 :: "r"(a), "r"(x), "r"(y), "r"(z), "r"(w), "r"(bar) : "memory");
}
__device__ __forceinline__ void stsm4(uint32_t a, uint32_t r0, uint32_t r1, uint32_t r2, uint32_t r3) {
    asm volatile("stmatrix.sync.aligned.m8n8.x4.shared.b16 [%0], {%1,%2,%3,%4};" :: "r"(a), "r"(r0), "r"(r1), "r"(r2), "r"(r3) : "memory");
}
__device__ __forceinline__ void proxy_fence() { asm volatile("fence.proxy.async.shared::cta;" ::: "memory"); }
__device__ __forceinline__ void bar_sync(int id, int n) { asm volatile("bar.sync %0, %1;" :: "r"(id), "r"(n) : "memory"); }
__device__ __forceinline__ void bar_arrive(int id, int n) { asm volatile("bar.arrive %0, %1;" :: "r"(id), "r"(n) : "memory"); }
__device__ __forceinline__ void cluster_arrive() { asm volatile("barrier.cluster.arrive.relaxed.aligned;" ::: "memory"); }
__device__ __forceinline__ void cluster_wait() { asm volatile("barrier.cluster.wait.aligned;" ::: "memory"); }
__device__ __forceinline__ void tma3d(uint32_t dst, const CUtensorMap* tm, int c0, int c1, uint32_t bar, uint64_t pol) {
    asm volatile("cp.async.bulk.tensor.3d.shared::cluster.global.mbarrier::complete_tx::bytes.L2::cache_hint [%0], [%1, {%3, %4, %6}], [%2], %5;"
                 :: "r"(dst), "l"(tm), "r"(bar), "r"(c0), "r"(c1), "l"(pol), "r"(0) : "memory");
}
__device__ __forceinline__ bool elect() {
    uint32_t p; asm volatile("{ .reg .pred p; elect.sync _|p, 0xFFFFFFFF; selp.u32 %0, 1, 0, p; }" : "=r"(p)); return p;
}

struct cf { float r, i; };
__device__ __forceinline__ cf cmul(cf a, cf b) { return {a.r * b.r - a.i * b.i, a.r * b.i + a.i * b.r}; }
__device__ __forceinline__ cf csq(cf a) { return {a.r * a.r - a.i * a.i, (a.r + a.r) * a.i}; }
__device__ __forceinline__ cf cexp_(float a2, float b) { float m = ex2(a2); return {m * __cosf(b), m * __sinf(b)}; }
struct hc { uint32_t r, i; };
__device__ __forceinline__ hc pk(cf a, cf b) { return {pack_h(a.r, b.r), pack_h(a.i, b.i)}; }
__device__ __forceinline__ hc hmulc(hc a, hc b) {
    const __half2 ar = *reinterpret_cast<__half2*>(&a.r), ai = *reinterpret_cast<__half2*>(&a.i);
    const __half2 br = *reinterpret_cast<__half2*>(&b.r), bi = *reinterpret_cast<__half2*>(&b.i);
    const __half2 r = __hfma2(ar, br, __hneg2(__hmul2_rn(ai, bi))), i = __hfma2(ar, bi, __hmul2_rn(ai, br));
    return {*reinterpret_cast<const uint32_t*>(&r), *reinterpret_cast<const uint32_t*>(&i)};
}
__device__ __forceinline__ void sth(uint32_t a, hc v) { sts32(a, v.r); sts32(a + 128, v.i); }
__device__ __forceinline__ uint32_t cpy(uint32_t v, uint32_t z) { uint32_t d; asm("xor.b32 %0, %1, %2;" : "=r"(d) : "r"(v), "r"(z)); return d; }
__device__ __forceinline__ void sched_fence() { asm volatile("pmevent 0;" ::: "memory"); }
__device__ __forceinline__ float tanh_(float v) { float d; asm("tanh.approx.f32 %0, %1;" : "=f"(d) : "f"(v)); return d; }
__device__ __forceinline__ float silu2(float h) {
    return h * rcp(fmaf(ex2(-2.8853900817779268f * h), 0.5f, 0.5f));
}
__device__ __forceinline__ uint32_t hfma2_(uint32_t a, uint32_t b, uint32_t c) { uint32_t d; asm("fma.rn.f16x2 %0, %1, %2, %3;" : "=r"(d) : "r"(a), "r"(b), "r"(c)); return d; }
__device__ __forceinline__ uint32_t hfms2_(uint32_t a, uint32_t b, uint32_t c) {
    uint32_t d; asm("{ .reg .b32 t; neg.f16x2 t, %1; fma.rn.f16x2 %0, t, %2, %3; }" : "=r"(d) : "r"(a), "r"(b), "r"(c)); return d;
}

__device__ __forceinline__ uint64_t bdesc(uint32_t addr, uint32_t sbo) {
    return (uint64_t)((addr & 0x3FFFFu) >> 4) | ((uint64_t)(128 >> 4) << 16) | ((uint64_t)(sbo >> 4) << 32);
}
__device__ __forceinline__ void wg_h(uint32_t (&d)[16], const uint32_t* a, const uint32_t* b, uint64_t d0, uint64_t d1, uint64_t d2, uint64_t d3) {
    asm volatile(
        "wgmma.mma_async.sync.aligned.m64n64k16.f16.f16.f16 {%0,%1,%2,%3,%4,%5,%6,%7,%8,%9,%10,%11,%12,%13,%14,%15}, {%16,%17,%18,%19}, %32, 0, 1, 1, 1;\n"
        "wgmma.mma_async.sync.aligned.m64n64k16.f16.f16.f16 {%0,%1,%2,%3,%4,%5,%6,%7,%8,%9,%10,%11,%12,%13,%14,%15}, {%20,%21,%22,%23}, %33, 1, 1, 1, 1;\n"
        "wgmma.mma_async.sync.aligned.m64n64k16.f16.f16.f16 {%0,%1,%2,%3,%4,%5,%6,%7,%8,%9,%10,%11,%12,%13,%14,%15}, {%24,%25,%26,%27}, %34, 1, 1, 1, 1;\n"
        "wgmma.mma_async.sync.aligned.m64n64k16.f16.f16.f16 {%0,%1,%2,%3,%4,%5,%6,%7,%8,%9,%10,%11,%12,%13,%14,%15}, {%28,%29,%30,%31}, %35, 1, 1, 1, 1;\n"
        : "=r"(d[0]), "=r"(d[1]), "=r"(d[2]), "=r"(d[3]), "=r"(d[4]), "=r"(d[5]), "=r"(d[6]), "=r"(d[7]), "=r"(d[8]), "=r"(d[9]), "=r"(d[10]), "=r"(d[11]), "=r"(d[12]), "=r"(d[13]), "=r"(d[14]), "=r"(d[15])
        : "r"(a[0]), "r"(a[1]), "r"(a[2]), "r"(a[3]), "r"(a[4]), "r"(a[5]), "r"(a[6]), "r"(a[7]), "r"(b[0]), "r"(b[1]), "r"(b[2]), "r"(b[3]), "r"(b[4]), "r"(b[5]), "r"(b[6]), "r"(b[7]), "l"(d0), "l"(d1), "l"(d2), "l"(d3));
}
__device__ __forceinline__ void wg_f0(float (&d)[32], const uint32_t* a, const uint32_t* b, uint64_t d0, uint64_t d1, uint64_t d2, uint64_t d3) {
    asm volatile(
        "wgmma.mma_async.sync.aligned.m64n64k16.f32.f16.f16 {%0,%1,%2,%3,%4,%5,%6,%7,%8,%9,%10,%11,%12,%13,%14,%15,%16,%17,%18,%19,%20,%21,%22,%23,%24,%25,%26,%27,%28,%29,%30,%31}, {%32,%33,%34,%35}, %48, 0, 1, 1, 1;\n"
        "wgmma.mma_async.sync.aligned.m64n64k16.f32.f16.f16 {%0,%1,%2,%3,%4,%5,%6,%7,%8,%9,%10,%11,%12,%13,%14,%15,%16,%17,%18,%19,%20,%21,%22,%23,%24,%25,%26,%27,%28,%29,%30,%31}, {%36,%37,%38,%39}, %49, 1, 1, 1, 1;\n"
        "wgmma.mma_async.sync.aligned.m64n64k16.f32.f16.f16 {%0,%1,%2,%3,%4,%5,%6,%7,%8,%9,%10,%11,%12,%13,%14,%15,%16,%17,%18,%19,%20,%21,%22,%23,%24,%25,%26,%27,%28,%29,%30,%31}, {%40,%41,%42,%43}, %50, 1, 1, 1, 1;\n"
        "wgmma.mma_async.sync.aligned.m64n64k16.f32.f16.f16 {%0,%1,%2,%3,%4,%5,%6,%7,%8,%9,%10,%11,%12,%13,%14,%15,%16,%17,%18,%19,%20,%21,%22,%23,%24,%25,%26,%27,%28,%29,%30,%31}, {%44,%45,%46,%47}, %51, 1, 1, 1, 1;\n"
        : "=f"(d[0]), "=f"(d[1]), "=f"(d[2]), "=f"(d[3]), "=f"(d[4]), "=f"(d[5]), "=f"(d[6]), "=f"(d[7]), "=f"(d[8]), "=f"(d[9]), "=f"(d[10]), "=f"(d[11]), "=f"(d[12]), "=f"(d[13]), "=f"(d[14]), "=f"(d[15]), "=f"(d[16]), "=f"(d[17]), "=f"(d[18]), "=f"(d[19]), "=f"(d[20]), "=f"(d[21]), "=f"(d[22]), "=f"(d[23]), "=f"(d[24]), "=f"(d[25]), "=f"(d[26]), "=f"(d[27]), "=f"(d[28]), "=f"(d[29]), "=f"(d[30]), "=f"(d[31])
        : "r"(a[0]), "r"(a[1]), "r"(a[2]), "r"(a[3]), "r"(a[4]), "r"(a[5]), "r"(a[6]), "r"(a[7]), "r"(b[0]), "r"(b[1]), "r"(b[2]), "r"(b[3]), "r"(b[4]), "r"(b[5]), "r"(b[6]), "r"(b[7]), "l"(d0), "l"(d1), "l"(d2), "l"(d3));
}
__device__ __forceinline__ void wg_f1(float (&d)[32], const uint32_t* a, const uint32_t* b, uint64_t d0, uint64_t d1, uint64_t d2, uint64_t d3) {
    asm volatile(
        "wgmma.mma_async.sync.aligned.m64n64k16.f32.f16.f16 {%0,%1,%2,%3,%4,%5,%6,%7,%8,%9,%10,%11,%12,%13,%14,%15,%16,%17,%18,%19,%20,%21,%22,%23,%24,%25,%26,%27,%28,%29,%30,%31}, {%32,%33,%34,%35}, %48, 1, 1, 1, 1;\n"
        "wgmma.mma_async.sync.aligned.m64n64k16.f32.f16.f16 {%0,%1,%2,%3,%4,%5,%6,%7,%8,%9,%10,%11,%12,%13,%14,%15,%16,%17,%18,%19,%20,%21,%22,%23,%24,%25,%26,%27,%28,%29,%30,%31}, {%36,%37,%38,%39}, %49, 1, 1, 1, 1;\n"
        "wgmma.mma_async.sync.aligned.m64n64k16.f32.f16.f16 {%0,%1,%2,%3,%4,%5,%6,%7,%8,%9,%10,%11,%12,%13,%14,%15,%16,%17,%18,%19,%20,%21,%22,%23,%24,%25,%26,%27,%28,%29,%30,%31}, {%40,%41,%42,%43}, %50, 1, 1, 1, 1;\n"
        "wgmma.mma_async.sync.aligned.m64n64k16.f32.f16.f16 {%0,%1,%2,%3,%4,%5,%6,%7,%8,%9,%10,%11,%12,%13,%14,%15,%16,%17,%18,%19,%20,%21,%22,%23,%24,%25,%26,%27,%28,%29,%30,%31}, {%44,%45,%46,%47}, %51, 1, 1, 1, 1;\n"
        : "+f"(d[0]), "+f"(d[1]), "+f"(d[2]), "+f"(d[3]), "+f"(d[4]), "+f"(d[5]), "+f"(d[6]), "+f"(d[7]), "+f"(d[8]), "+f"(d[9]), "+f"(d[10]), "+f"(d[11]), "+f"(d[12]), "+f"(d[13]), "+f"(d[14]), "+f"(d[15]), "+f"(d[16]), "+f"(d[17]), "+f"(d[18]), "+f"(d[19]), "+f"(d[20]), "+f"(d[21]), "+f"(d[22]), "+f"(d[23]), "+f"(d[24]), "+f"(d[25]), "+f"(d[26]), "+f"(d[27]), "+f"(d[28]), "+f"(d[29]), "+f"(d[30]), "+f"(d[31])
        : "r"(a[0]), "r"(a[1]), "r"(a[2]), "r"(a[3]), "r"(a[4]), "r"(a[5]), "r"(a[6]), "r"(a[7]), "r"(b[0]), "r"(b[1]), "r"(b[2]), "r"(b[3]), "r"(b[4]), "r"(b[5]), "r"(b[6]), "r"(b[7]), "l"(d0), "l"(d1), "l"(d2), "l"(d3));
}
template <int ACC> __device__ __forceinline__ void wg_w(float (&d)[4], uint64_t da, uint64_t db) {
    asm volatile("wgmma.mma_async.sync.aligned.m64n8k16.f32.bf16.bf16 {%0,%1,%2,%3}, %4, %5, %6, 1, 1, 1, 0;"
                 : "+f"(d[0]), "+f"(d[1]), "+f"(d[2]), "+f"(d[3]) : "l"(da), "l"(db), "n"(ACC));
}
__device__ __forceinline__ void wg_w0(float (&d)[4], uint64_t da, uint64_t db) {
    asm volatile("wgmma.mma_async.sync.aligned.m64n8k16.f32.bf16.bf16 {%0,%1,%2,%3}, %4, %5, 0, 1, 1, 1, 0;"
                 : "=f"(d[0]), "=f"(d[1]), "=f"(d[2]), "=f"(d[3]) : "l"(da), "l"(db));
}
__device__ __forceinline__ void wg_fence() { asm volatile("wgmma.fence.sync.aligned;" ::: "memory"); }
__device__ __forceinline__ void wg_commit() { asm volatile("wgmma.commit_group.sync.aligned;" ::: "memory"); }
template <int N> __device__ __forceinline__ void wg_wait() { asm volatile("wgmma.wait_group.sync.aligned %0;" :: "n"(N) : "memory"); }
__device__ __forceinline__ void touch(uint32_t& r) { asm volatile("" : "+r"(r) :: "memory"); }
__device__ __forceinline__ void touch(float& r) { asm volatile("" : "+f"(r) :: "memory"); }
template <class T, int N> __device__ __forceinline__ void touch(T (&r)[N]) {
#pragma unroll
    for (int i = 0; i < N; i++) touch(r[i]);
}

__global__ void __cluster_dims__(2, 1, 1) __launch_bounds__(NTHREADS, 1)
fused_kernel(const Params p, const __grid_constant__ CUtensorMap tm_x, const __grid_constant__ CUtensorMap tm_g,
             const __grid_constant__ CUtensorMap tm_d, const __grid_constant__ CUtensorMap tm_o)
{
    extern __shared__ __align__(1024) uint8_t smem_raw[];
    const uint32_t sm = (uint32_t)__cvta_generic_to_shared(smem_raw);
    const uint32_t bars = sm + SM_BAR;
    const int tid = threadIdx.x, lane = tid & 31;
    const int pw = __shfl_sync(0xFFFFFFFFu, tid >> 5, 0);
    const int warp = pw;
    const int g = lane >> 2, q = lane & 3;
    const int c = blockIdx.x, rank = c & 1, G = c >> 1;

    if (lane == 0 && warp >= 8 && warp < 16) {
        const int v = warp - 8;
        mbar_init(bars + (B_STG + v) * 8, v < 4 ? 5 : 1);
        mbar_init(bars + (B_EMPTY + v) * 8, 4);
        mbar_init(bars + (B_FULL + v) * 8, 1);
        mbar_init(bars + (B_MISC + v) * 8, (v == 1 || v == 2) ? 2 : 1);
        mbar_init(bars + (B_ROW + v) * 8, 1);
        if (v < 4) mbar_expect(bars + (B_STG + v) * 8, 4096);
        if (v >= 2) mbar_expect(bars + (B_MISC + v) * 8, v == 2 ? 32 : v == 3 ? 2048 : 65536 + 6144);
        asm volatile("fence.mbarrier_init.release.cluster;" ::: "memory");
    }
    __syncwarp();
    cluster_arrive();

    if (warp < 8) {
        const int ch = c * 8 + warp;
        const uint2 lar4 = __ldg(reinterpret_cast<const uint2*>(p.lar + ch * 128) + lane);
        const uint2 aim4 = __ldg(reinterpret_cast<const uint2*>(p.aim + ch * 128) + lane);
        const uint2 cr4 = __ldg(reinterpret_cast<const uint2*>(p.cr + ch * 128) + lane);
        const uint2 ci4 = __ldg(reinterpret_cast<const uint2*>(p.ci + ch * 128) + lane);
        uint32_t ldt_raw, dsk_raw;
        asm volatile("ld.global.nc.u16 %0, [%1];" : "=r"(ldt_raw) : "l"(p.logdt + ch));
        asm volatile("ld.global.nc.u16 %0, [%1];" : "=r"(dsk_raw) : "l"(p.dskip + ch));
        const float logdt = blo(ldt_raw), dsk = blo(dsk_raw);
        const uint32_t wb = sm + SM_CH + warp * CH_SZ + 4 * SUB;
        sth(wb + lane * 4, hc{0x3C003C00u, 0u});

        const float dt = rb(expf(logdt));
        float outscale, cs, dn;
        {
            uint32_t m0 = __vmaxu2(__vmaxu2(cr4.x & 0x7FFF7FFFu, cr4.y & 0x7FFF7FFFu), __vmaxu2(ci4.x & 0x7FFF7FFFu, ci4.y & 0x7FFF7FFFu));
            uint32_t m1 = max(m0 & 0xFFFFu, m0 >> 16);
            float cmax = blo(__reduce_max_sync(0xFFFFFFFFu, m1));
            const float sc = fminf(fmaxf(fmaxf(2.0f * dt * cmax, fabsf(dsk) * (1.0f / 1024.0f)), 1e-30f), 1e30f);
            outscale = __uint_as_float(__float_as_uint(sc) & 0x7F800000u);
            const float inv = __uint_as_float(0x7F000000u - __float_as_uint(outscale));
            cs = 2.0f * dt * inv;
            dn = dsk * inv;
        }
        TSL(0);
        if (warp == TSW) TSL(39);
        float kacc[2][3][4];
#pragma unroll
        for (int i = 0; i < 2; i++)
#pragma unroll
            for (int j = 0; j < 3; j++) kacc[i][j][0] = kacc[i][j][1] = kacc[i][j][2] = kacc[i][j][3] = 0.f;
        if (lane == 0) kacc[0][0][0] = dn;
        {
            const uint32_t st = wb + lane * 4;
            const uint32_t zk = lds32(wb + 128);
            const uint32_t la = wb + ((lane & 8) ? 29 : (lane & 7)) * KP + (lane >> 4) * 128;
            const uint32_t lo = wb + ((lane >> 3) & 1) * 128 + (lane >> 4) * 16;
            const uint32_t lb = lo + (8 + (lane & 7)) * KP, lb2 = lo + (24 + min(lane & 7, 4)) * KP, lm = lo + 30 * KP;
#pragma unroll 1
            for (int s = 0; s < 2; s++) {
                const uint32_t wl = s ? lar4.y : lar4.x, wa = s ? aim4.y : aim4.x, wr_ = s ? cr4.y : cr4.x, wi = s ? ci4.y : ci4.x;
                const uint32_t ea = pack_b(ex2(blo(wl) * 1.4426950408889634f), ex2(bhi(wl) * 1.4426950408889634f));
                const float a2[2] = {-(blo(ea) * dt) * 1.4426950408889634f, -(bhi(ea) * dt) * 1.4426950408889634f};
                const float b[2] = {blo(wa) * dt, bhi(wa) * dt};
                {
                    cf z8[2], z16[2], z32[2], z64[2], z128[2];
#pragma unroll
                    for (int e = 0; e < 2; e++) {
                        z8[e] = cexp_(a2[e] * 8.f, b[e] * 8.f);
                        z16[e] = csq(z8[e]); z32[e] = csq(z16[e]); z64[e] = csq(z32[e]); z128[e] = csq(z64[e]);
                    }
                    const hc r1 = pk(z8[0], z8[1]), r2 = pk(z16[0], z16[1]), r3 = hmulc(r1, r2), r4 = pk(z32[0], z32[1]);
                    sth(st + 1 * KP, r1); sth(st + 2 * KP, r2); sth(st + 3 * KP, r3); sth(st + 4 * KP, r4);
                    sth(st + 5 * KP, hmulc(r1, r4)); sth(st + 6 * KP, hmulc(r2, r4)); sth(st + 7 * KP, hmulc(r3, r4));
                    sth(st + 29 * KP, pk(z64[0], z64[1])); sth(st + 30 * KP, pk(z128[0], z128[1]));
                }
                {
                    cf C[2], z2[2], z4[2], v2[2], v4[2], c1[2], d1[2];
#pragma unroll
                    for (int e = 0; e < 2; e++) {
                        C[e] = {(e ? bhi(wr_) : blo(wr_)) * cs, (e ? bhi(wi) : blo(wi)) * -cs};
                        const cf z = cexp_(a2[e], -b[e]);
                        const cf v = cexp_(a2[e] * 256.f, b[e] * -256.f);
                        z2[e] = csq(z); z4[e] = csq(z2[e]); v2[e] = csq(v); v4[e] = csq(v2[e]);
                        c1[e] = cmul(C[e], z); d1[e] = cmul(C[e], v);
                    }
                    const hc l0 = pk(C[0], C[1]), l1 = pk(c1[0], c1[1]), e1 = pk(d1[0], d1[1]);
                    const hc h = pk(z2[0], z2[1]), f = pk(z4[0], z4[1]), w = pk(v2[0], v2[1]), y = pk(v4[0], v4[1]);
                    const hc l2 = hmulc(l0, h), l3 = hmulc(l1, h), e2 = hmulc(l0, w), e3 = hmulc(e1, w), e4 = hmulc(l0, y), g2 = hmulc(e1, h);
                    sth(st + 8 * KP, l0); sth(st + 9 * KP, l1); sth(st + 10 * KP, l2); sth(st + 11 * KP, l3);
                    sth(st + 12 * KP, hmulc(l0, f)); sth(st + 13 * KP, hmulc(l1, f)); sth(st + 14 * KP, hmulc(l2, f)); sth(st + 15 * KP, hmulc(l3, f));
                    sth(st + 16 * KP, e1);
                    sth(st + 17 * KP, g2);
                    sth(st + 18 * KP, hmulc(e1, f));
                    sth(st + 19 * KP, hmulc(g2, f));
                    sth(st + 20 * KP, e2);
                    sth(st + 21 * KP, hmulc(e2, f));
                    sth(st + 22 * KP, e3);
                    sth(st + 23 * KP, hmulc(e3, f));
                    sth(st + 24 * KP, e4);
                    sth(st + 25 * KP, hmulc(e1, y));
                    sth(st + 26 * KP, hmulc(e2, y));
                    sth(st + 27 * KP, hmulc(e3, y));
                    sth(st + 28 * KP, hmulc(e4, y));
                }
                __syncwarp();
                if (warp == TSW) TSL(s ? 34 : 27);
#pragma unroll
                for (int kp = 0; kp < 4; kp++) {
                    uint32_t bb[3][4], m2[4];
                    ldsm4(lm + kp * 32, m2[0], m2[1], m2[2], m2[3]);
                    ldsm4(lb + kp * 32, bb[0][0], bb[0][1], bb[0][2], bb[0][3]);
                    ldsm4(lb + 8 * KP + kp * 32, bb[1][0], bb[1][1], bb[1][2], bb[1][3]);
                    ldsm4(lb2 + kp * 32, bb[2][0], bb[2][1], bb[2][2], bb[2][3]);
#pragma unroll
                    for (int k2 = 0; k2 < 2; k2++) {
                        hc v0, m1;
                        ldsm4(la + kp * 32 + k2 * 16, v0.r, m1.r, v0.i, m1.i);
                        const hc mm = {m2[2 * k2], m2[2 * k2 + 1]};
                        const hc v1 = hmulc(v0, m1), v2 = hmulc(v0, mm), v3 = hmulc(v1, mm);
                        v0.r = cpy(v0.r, zk); v0.i = cpy(v0.i, zk);
#pragma unroll
                        for (int nt = 0; nt < 3; nt++) {
                            mma_f16(kacc[0][nt], v0.r, v1.r, v0.i, v1.i, bb[nt][2 * k2], bb[nt][2 * k2 + 1]);
                            mma_f16(kacc[1][nt], v2.r, v3.r, v2.i, v3.i, bb[nt][2 * k2], bb[nt][2 * k2 + 1]);
                        }
                    }
                }
                __syncwarp();
                if (warp == TSW) TSL(s ? 40 : 33);
            }
        }
        TSL(1);
        asm volatile("setmaxnreg.inc.sync.aligned.u32 120;");
        uint32_t fc[16], fs[16], ta[8], tb[8];
        {
            const uint4* tp = p.tab + (tid & 127);
#pragma unroll
            for (int i = 0; i < 4; i++) {
                const uint4 u = ldg128(tp + i * 128), v = ldg128(tp + (4 + i) * 128), w = ldg128(tp + (8 + i) * 128);
                fc[4 * i] = u.x; fc[4 * i + 1] = u.y; fc[4 * i + 2] = u.z; fc[4 * i + 3] = u.w;
                fs[4 * i] = v.x; fs[4 * i + 1] = v.y; fs[4 * i + 2] = v.z; fs[4 * i + 3] = v.w;
                uint32_t* t = i < 2 ? ta + 4 * i : tb + 4 * (i - 2);
                t[0] = w.x; t[1] = w.y; t[2] = w.z; t[3] = w.w;
            }
        }
        {
            const uint32_t tb_ = wb + 4 * SUB;
            const uint32_t seg = wb + (lane & 3) * SUB + (lane >> 2) * 16;
            uint32_t v0[4];
#pragma unroll
            for (int m = 0; m < 4; m++) {
                constexpr float S = 1.0f / 512.0f;
                const float (&k0)[4] = kacc[m >> 1][0], (&k1)[4] = kacc[m >> 1][1], (&k2)[4] = kacc[m >> 1][2];
                const int R = 8 * m + g, o = 2 * (m & 1);
                v0[m] = pack_h(k0[o] * S, k0[o + 1] * S);
                sts32(tb_ + (q < 2 ? 4 * R + 2 * q : 64 * q + 2 * R) * 2, pack_h(k1[o] * S, k1[o + 1] * S));
                const uint32_t v2 = pack_h(k2[o] * S, k2[o + 1] * S);
                if (q < 2 || (m == 0 && lane == 2)) sts16(tb_ + (256 + 64 * q + R) * 2, v2);
                if (q < 2) sts16(tb_ + (288 + 64 * q + R) * 2, v2 >> 16);
            }
            stsm4(seg, v0[0], v0[1], v0[2], v0[3]);
            if (lane == 0) sts16(sm + SM_SCL + warp * 2, __float_as_uint(16384.0f * outscale) >> 16);
            __syncwarp();
            const uint2 l1 = lds64(tb_ + lane * 8);
            const uint32_t l1n = lds16(tb_ + lane * 8 + 8);
            uint32_t l2[2], l2n[2], l3[4], l3n[4];
#pragma unroll
            for (int i = 0; i < 2; i++) { l2[i] = lds32(tb_ + 256 + i * 128 + lane * 4); l2n[i] = lds16(tb_ + 260 + i * 128 + lane * 4); }
#pragma unroll
            for (int i = 0; i < 4; i++) { l3[i] = lds16(tb_ + 512 + i * 64 + lane * 2); l3n[i] = lds16(tb_ + 514 + i * 64 + lane * 2); }
            sts128(seg + 128, prmt(l1.x, 0, 0x1010), prmt(l1.x, l1.y, 0x5432), prmt(l1.y, 0, 0x1010), prmt(l1.y, l1n, 0x5432));
#pragma unroll
            for (int i = 0; i < 2; i++) sts128(seg + 256 + i * 128, prmt(l2[i], 0, 0x1010), l2[i], prmt(l2[i], 0, 0x3232), prmt(l2n[i], 0, 0x1010));
            const uint32_t s3 = (lane & 1) ? 0x5454 : 0x5410;
#pragma unroll
            for (int i = 0; i < 4; i++) {
                const uint32_t vv = prmt(l3[i], 0, 0x1010);
                sts128(seg + 512 + i * 128, vv, vv, prmt(l3[i], l3n[i], s3), prmt(l3n[i], 0, 0x1010));
            }
        }
        proxy_fence();
        TSL(2);
        cluster_wait();
        bar_sync(2, 512);
        asm volatile("setmaxnreg.inc.sync.aligned.u32 176;");
        TSL(3);
        const int wgi = warp >> 2, w = warp & 3;
        uint32_t gt[2][4][4];
        {
            const uint64_t dre = bdesc(sm + SM_F2 + 2048, 512), dim = bdesc(sm + SM_F2, 512);
            const uint32_t zst = 4 * SUB + (lane >> 4) * SUB + (16 * w + (lane & 15)) * 16;
            const uint32_t hl = sm + SM_CH + (lane >> 4) * CH_SZ + wgi * SUB + (16 * w + (lane & 15)) * 16;
#pragma unroll
            for (int ci = 0; ci < 4; ci++) {
                const uint32_t cb = sm + SM_CH + (4 * wgi + ci) * CH_SZ;
                const uint64_t d1 = bdesc(cb, SUB);
                uint32_t re[16], im[16];
                wg_fence();
                wg_h(re, fc, fc + 8, d1, d1 + 16, d1 + 32, d1 + 48);
                wg_h(im, fs, fs + 8, d1, d1 + 16, d1 + 32, d1 + 48);
                wg_commit();
                {
                    uint32_t h[4];
                    ldsm4(hl + 2 * ci * CH_SZ + 2 * 0 * SUB, h[0], h[1], h[2], h[3]);
                    sched_fence();
#pragma unroll
                    for (int i = 0; i < 2; i++) {
                        const float2 f0 = __half22float2(*reinterpret_cast<const __half2*>(&h[i])), f1 = __half22float2(*reinterpret_cast<const __half2*>(&h[2 + i]));
                        gt[0][2 * i][ci] = pack_b(silu2(f0.x), silu2(f1.x)); gt[0][2 * i + 1][ci] = pack_b(silu2(f0.y), silu2(f1.y));
                        touch(gt[0][2 * i][ci]); touch(gt[0][2 * i + 1][ci]);
                    }
                    sched_fence();
                }
                wg_wait<0>();
                touch(re); touch(im);
#pragma unroll
                for (int i = 0; i < 16; i++) {
                    re[i] = hfma2_(ta[i & 7], im[i], re[i]); im[i] = hfms2_(tb[i & 7], re[i], im[i]); re[i] = hfma2_(ta[i & 7], im[i], re[i]);
                }
                uint32_t su[16], sk[16];
                wg_fence();
                wg_h(su, re, im, dre, dre + 16, dim, dim + 16);
                wg_h(sk, re + 8, im + 8, dre, dre + 16, dim, dim + 16);
                wg_commit();
                {
                    uint32_t h[4];
                    ldsm4(hl + 2 * ci * CH_SZ + 2 * 1 * SUB, h[0], h[1], h[2], h[3]);
                    sched_fence();
#pragma unroll
                    for (int i = 0; i < 2; i++) {
                        const float2 f0 = __half22float2(*reinterpret_cast<const __half2*>(&h[i])), f1 = __half22float2(*reinterpret_cast<const __half2*>(&h[2 + i]));
                        gt[1][2 * i][ci] = pack_b(silu2(f0.x), silu2(f1.x)); gt[1][2 * i + 1][ci] = pack_b(silu2(f0.y), silu2(f1.y));
                        touch(gt[1][2 * i][ci]); touch(gt[1][2 * i + 1][ci]);
                    }
                    sched_fence();
                }
                wg_wait<0>();
                touch(su); touch(sk);
                uint32_t zr[8], zi[8];
#pragma unroll
                for (int i = 0; i < 8; i++) {
                    const hc z = hmulc(hc{su[i], su[8 + i]}, hc{sk[i], sk[8 + i]});
                    zr[i] = z.r; zi[i] = z.i;
                }
                uint32_t y[16];
                wg_fence();
                wg_h(y, zi, zr, dre, dre + 16, dim, dim + 16);
                wg_commit();
                wg_wait<0>();
                touch(y);
#pragma unroll
                for (int i = 0; i < 8; i++) {
                    y[8 + i] = hfms2_(ta[i], y[i], y[8 + i]); y[i] = hfma2_(tb[i], y[8 + i], y[i]); y[8 + i] = hfms2_(ta[i], y[i], y[8 + i]);
                }
                bar_sync(10 + wgi, 128);
                stsm4(cb + zst, y[8], y[9], y[10], y[11]);
                stsm4(cb + zst + 2 * SUB, y[12], y[13], y[14], y[15]);
                stsm4(cb + zst + 4 * SUB, y[0], y[1], y[2], y[3]);
                stsm4(cb + zst + 6 * SUB, y[4], y[5], y[6], y[7]);
                if (warp == TSW) TSL(35 + ci);
            }
        }
        proxy_fence();
        mbar_wait(bars + B_TOK * 8, 0);
        bar_sync(1, 256);
        if (warp == 0 && lane == 0) asm volatile("mbarrier.arrive.relaxed.cluster.shared::cluster.b64 _, [%0];" :: "r"(mapa(bars + B_PEER * 8, rank ^ 1)) : "memory");
        TSL(4);
        {
            const uint2 tk = lds64(sm + SM_TOK);
            const uint4 sc = lds128(sm + SM_SCL);
            const uint32_t xo = SM_SLAB + wgi * 16384 + (16 * w + g) * 128 + q * 32 + ((rank ^ (g & 1)) * 16);
            const uint32_t peer = mapa(sm, rank ^ 1), so = SM_CH + wgi * CH_SZ + w * 1024 + lane * 16;
#pragma unroll
            for (int jj = 0; jj < 2; jj++) {
                uint4 xv[4];
#pragma unroll
                for (int i = 0; i < 4; i++) xv[i] = lds128(sm + xo + jj * 32768 + (i & 1) * 8192 + (i >> 1) * 1024);
                float acc[32];
                const uint64_t d4 = bdesc(sm + SM_CH + (4 + 2 * jj + wgi) * SUB, CH_SZ);
                if (jj == 0 && wgi == 1) bar_sync(5, 256);
                wg_fence();
                wg_f0(acc, fc, fc + 8, d4, d4 + 16, d4 + 32, d4 + 48);
                wg_f1(acc, fs, fs + 8, d4 + SUB / 4, d4 + SUB / 4 + 16, d4 + SUB / 4 + 32, d4 + SUB / 4 + 48);
                wg_commit();
                if (jj == 0) {
                    if (wgi == 0) bar_arrive(5, 256);
                    mbar_wait(bars + B_PEER * 8, 0);
                }
                wg_wait<0>();
                touch(acc);
                uint32_t s[4][4], o[4][4];
#pragma unroll
                for (int i = 0; i < 4; i++) {
#pragma unroll
                    for (int j = 0; j < 4; j++) s[i][j] = pack_b(acc[8 * j + i], acc[8 * j + 4 + i]);
                    o[i][0] = bfma2(bmul2(s[i][0], gt[jj][i][0]), sc.x, xv[i].x); o[i][1] = bfma2(bmul2(s[i][1], gt[jj][i][1]), sc.y, xv[i].y);
                    o[i][2] = bfma2(bmul2(s[i][2], gt[jj][i][2]), sc.z, xv[i].z); o[i][3] = bfma2(bmul2(s[i][3], gt[jj][i][3]), sc.w, xv[i].w);
                }
                const uint32_t sb = SM_BAR + (B_STG + 2 * jj + wgi) * 8;
#pragma unroll
                for (int e = 0; e < 2; e++)
                    if (e == rank) {
#pragma unroll
                        for (int hi = 0; hi < 2; hi++) {
                            const uint32_t (&r)[4] = o[2 * hi + 1 - e], (&l)[4] = o[2 * hi + e];
                            st_async4(peer + so + 2 * jj * CH_SZ + hi * 512, r[0], r[1], r[2], r[3], peer + sb);
                            sts128(sm + so + (4 + 2 * jj) * CH_SZ + 64 + hi * 512, l[0], l[1], l[2], l[3]);
                        }
                    }
                __syncwarp();
                if (lane == 0) mbar_arrive(sm + sb);
                if (warp == TSW) TSL(5 + jj);
#pragma unroll
                for (int k = 0; k < 2; k++) {
                    const int t = k ? tk.y : tk.x;
                    if ((t & ~0x101) == 512 * w + 32 * g + 16 * jj + 8 * wgi + 2 * q) {
                        uint32_t f[4];
#pragma unroll
                        for (int j = 0; j < 4; j++) {
                            const uint32_t lo = (t & 1) ? s[1][j] : s[0][j], hi = (t & 1) ? s[3][j] : s[2][j];
                            f[j] = (t & 256) ? hi : lo;
                        }
                        const uint32_t dst = mapa(sm, k);
                        st_async4(dst + SM_FIX + rank * 16, bmul2(f[0], sc.x), bmul2(f[1], sc.y), bmul2(f[2], sc.z), bmul2(f[3], sc.w),
                                  dst + SM_BAR + B_FIX * 8);
                    }
                }
                __syncwarp();
            }
        }
        TSL(7);
    } else if (warp < 16) {
        const int v = warp - 8;
        const uint32_t xs = sm + SM_CH + v * CH_SZ;
        if (lane == 0) {
            mbar_expect(bars + (B_ROW + v) * 8, 4096);
            asm volatile("cp.async.bulk.shared::cluster.global.mbarrier::complete_tx::bytes [%0], [%1], 4096, [%2];"
                         :: "r"(xs), "l"(p.x + (size_t)(64 * (c & 31) + 32 * (v >> 2) + 8 * (c >> 5) + 2 * (v & 3)) * 1024), "r"(bars + (B_ROW + v) * 8) : "memory");
        }
        uint4 w4[4];
#pragma unroll
        for (int k = 0; k < 4; k++) w4[k] = ldg128(reinterpret_cast<const uint4*>(p.wr) + 32 * k + lane);
        uint32_t* const my_part = p.sc->part + ((2 * (32 * rank + v) + (q & 1)) * 56 + G) * 16 + g + 8 * (q >> 1);
#pragma unroll
        for (int n = 0; n < 8; n++)
            asm volatile("{ .reg .pred p; setp.ne.u32 p, %1, 0; @p st.relaxed.gpu.global.u32 [%0], 0; }" :: "l"(my_part + n * 8 * 56 * 16), "r"((uint32_t)(v < 4 && G < 56)) : "memory");
        {
            constexpr uint32_t ONE = 0x3F803F80u;
            const uint32_t zr = p.up_first >> 1;
#pragma unroll
            for (int k = 0; k < 4; k++) { w4[k].x = cpy(w4[k].x, zr); w4[k].y = cpy(w4[k].y, zr); w4[k].z = cpy(w4[k].z, zr); w4[k].w = cpy(w4[k].w, zr); }
            const bool od = g & 1;
            const uint32_t ra = sm + SM_RED + v * 288 + g * 16;
            sched_fence();
            mbar_wait(bars + (B_ROW + v) * 8, 0);
            TSL(43);
            uint4 xa[4], xc[4];
#pragma unroll
            for (int k = 0; k < 8; k++) (k < 4 ? xa[k] : xc[k - 4]) = lds128(xs + k * 512 + lane * 16);
#pragma unroll
            for (int r = 0; r < 2; r++) {
                if (r) sched_fence();
                const uint4 (&x)[4] = r ? xc : xa;
                float s1[4] = {0, 0, 0, 0}, q0[4] = {0, 0, 0, 0}, q1[4] = {0, 0, 0, 0};
#pragma unroll
                for (int k = 0; k < 4; k++) {
                    mma_bf16(q0, cpy(x[k].x, zr), w4[k].x, cpy(x[k].y, zr), w4[k].y, x[k].x, x[k].y);
                    mma_bf16(q1, cpy(x[k].z, zr), w4[k].z, cpy(x[k].w, zr), w4[k].w, x[k].z, x[k].w);
                    mma_bf16(s1, x[k].x, x[k].y, x[k].z, x[k].w, ONE, ONE);
                }
                const float qq = (od ? q0[1] : q0[0]) + (od ? q1[1] : q1[0]), ww = (od ? q0[3] : q0[2]) + (od ? q1[3] : q1[2]);
                if (q == (g >> 1)) sts128(ra + r * 144, __float_as_uint(qq), __float_as_uint(ww), __float_as_uint(s1[0]), __float_as_uint(s1[2]));
            }
            bar_arrive(7, 288);
        }
        TSL(8);
        bar_sync(6, 320);
        const uint32_t tag = lds32(sm + SM_TOK + 8);
        cluster_wait();
        {
            const int wgi = v >> 2, w = v & 3;
            uint4 st[4] = {};
            const uint4* src = p.sc->stats + wgi * 256 + 64 * w + lane;
            mbar_wait(bars + B_SLAB * 8, 0);
            TSL(10);
            uint32_t xt[8][4];
            const uint32_t a = sm + SM_SLAB + wgi * 16384 + (16 * w + g) * 128 + q * 32 + ((rank ^ (g & 1)) * 16);
#pragma unroll
            for (int i = 0; i < 4; i++) {
                const uint4 e = lds128(a + (i >> 1) * 32768 + (i & 1) * 1024), o = lds128(a + (i >> 1) * 32768 + (i & 1) * 1024 + 8192);
                xt[0][i] = prmt(e.x, o.x, 0x5410); xt[1][i] = prmt(e.x, o.x, 0x7632);
                xt[2][i] = prmt(e.y, o.y, 0x5410); xt[3][i] = prmt(e.y, o.y, 0x7632);
                xt[4][i] = prmt(e.z, o.z, 0x5410); xt[5][i] = prmt(e.z, o.z, 0x7632);
                xt[6][i] = prmt(e.w, o.w, 0x5410); xt[7][i] = prmt(e.w, o.w, 0x7632);
            }
            const uint32_t tb = ((tag & 1) << 15) | ((tag >> 1) << 31);
#pragma unroll
            for (int i = 0; i < 4; i++) st[i].y = ~tb;
            int it = 0;
            bool ok;
            if (warp == 8) TSL(44);
            do {
#pragma unroll
                for (int i = 0; i < 4; i++)
                    asm volatile("{ .reg .pred p; .reg .b128 t; setp.ne.u32 p, %5, 0; mov.b128 t, {%0,%1,%2,%3};\n"
                                 "@p ld.relaxed.gpu.global.b128 t, [%4]; mov.b128 {%0,%1,%2,%3}, t; }"
                                 : "+r"(st[i].x), "+r"(st[i].y), "+r"(st[i].z), "+r"(st[i].w)
                                 : "l"(src + (i >> 1) * 512 + (i & 1) * 32), "r"((st[i].y ^ tb) & 0x80008000u) : "memory");
                const uint32_t bad = ((st[0].y ^ tb) | (st[1].y ^ tb) | (st[2].y ^ tb) | (st[3].y ^ tb)) & 0x80008000u;
                ok = __all_sync(0xFFFFFFFFu, bad == 0);
                if (warp == 8 && it == 0) TSL(45);
            } while (!ok && ++it < SPIN_LIMIT);
            TSL(11); TG(31);
            uint32_t h1[4], h2[4];
#pragma unroll
            for (int i = 0; i < 4; i++) {
                const uint32_t o2 = st[i].w ^ (prmt(st[i].w, 0, 0xBB99) | 0x80008000u);
                const uint32_t id = 0xFFFF - (512 * w + 32 * g + 8 * wgi + 2 * q) - ((i >> 1) * 16 + (i & 1) * 256);
                const uint32_t k0 = prmt(o2, id, 0x1054), k1 = prmt(o2, id - 1, 0x3254);
                h1[i] = max(k0, k1); h2[i] = min(k0, k1);
            }
            const uint32_t a1 = max(h1[0], h1[1]), a2 = __vimax3_u32(min(h1[0], h1[1]), h2[0], h2[1]);
            const uint32_t b1 = max(h1[2], h1[3]), b2 = __vimax3_u32(min(h1[2], h1[3]), h2[2], h2[3]);
            const uint32_t k1 = max(a1, b1), k2 = __vimax3_u32(min(a1, b1), a2, b2);
            const uint32_t w1 = __reduce_max_sync(0xFFFFFFFFu, k1);
            const uint32_t w2 = __reduce_max_sync(0xFFFFFFFFu, k1 == w1 ? k2 : k1);
            if (lane == 0) sts64(sm + SM_KEYS + v * 8, w1, w2);
            bar_arrive(3, 320);
            const uint32_t ua = sm + SM_CH + (2 * (lane >> 4) + wgi) * SUB + (16 * w + (lane & 15)) * 16;
#pragma unroll
            for (int i = 0; i < 4; i++) { st[i].y = bmul2(st[i].y & 0x7FFF7FFFu, 0x3F003F00u); st[i].z = bmul2(st[i].z, 0x3F003F00u); }
#pragma unroll
            for (int cc = 0; cc < 8; cc++) {
                uint32_t o[4];
#pragma unroll
                for (int i = 0; i < 4; i++) { const uint32_t n = norm2(xt[cc][i], st[i].x, st[i].y, st[i].z); o[i] = pack_h(blo(n), bhi(n)); }
                stsm4(ua + cc * CH_SZ, o[0], o[1], o[2], o[3]);
            }
            proxy_fence();
            bar_arrive(2, 512);
        }
        TSL(12);
        if (warp < 12) {
            asm volatile("setmaxnreg.dec.sync.aligned.u32 40;");
            if (G < 56) {
                const uint64_t dw = (uint64_t)(((sm + SM_RING) & 0x3FFFFu) >> 4) | (1ull << 16) | (64ull << 32) | (1ull << 62);
                const uint64_t dx = (uint64_t)(((sm + SM_XSEL + rank * 2048) & 0x3FFFFu) >> 4) | (2ull << 16) | (8ull << 32);
                const uint64_t dh = (uint64_t)(((sm + SM_H) & 0x3FFFFu) >> 4) | (8ull << 16) | (8ull << 32);
                float ag[4] = {0, 0, 0, 0}, au[4] = {0, 0, 0, 0};
                touch(ag); touch(au);
                mbar_wait(bars + B_TOK * 8, 0);
                TSL(13);
                int slot = 0, ph = 0;
#pragma unroll 1
                for (int n = 0; n < 16; n++) {
                    mbar_wait(bars + (B_FULL + slot) * 8, ph);
                    const uint64_t a = dw + slot * 512, b = dx + n * 8;
                    wg_fence();
                    wg_w<1>(ag, a, b); wg_w<1>(au, a + 256, b); wg_w<1>(ag, a + 128, b + 4); wg_w<1>(au, a + 384, b + 4);
                    wg_commit();
                    wg_wait<0>();
                    touch(ag); touch(au);
                    if (lane == 0) mbar_arrive(bars + (B_EMPTY + slot) * 8);
                    if (++slot == NSLOT) { slot = 0; ph ^= 1; }
                }
                TSL(14);
                if (q == 0) {
#pragma unroll
                    for (int r = 0; r < 2; r++) {
                        const uint32_t dst = mapa(sm, r), o = dst + SM_PAIR + rank * 1024 + v * 256 + g * 32;
                        st_async4(o, __float_as_uint(ag[0]), __float_as_uint(ag[1]), __float_as_uint(ag[2]), __float_as_uint(ag[3]), dst + SM_BAR + B_PAIR * 8);
                        st_async4(o + 16, __float_as_uint(au[0]), __float_as_uint(au[1]), __float_as_uint(au[2]), __float_as_uint(au[3]), dst + SM_BAR + B_PAIR * 8);
                    }
                }
                mbar_wait(bars + B_PAIR * 8, 0);
                {
                    const uint32_t o = sm + SM_PAIR + v * 256 + g * 32 + q * 4, og = o + (p.up_first ? 16 : 0), ou = o + (p.up_first ? 0 : 16);
                    const float gs = rb(__uint_as_float(lds32(og)) + __uint_as_float(lds32(og + 1024)));
                    const float us = rb(__uint_as_float(lds32(ou)) + __uint_as_float(lds32(ou + 1024)));
                    const float hv = rb(siluf_(gs)) * us;
                    const uint32_t hd = sm + SM_H + (2 * v + (q >> 1)) * 128 + (q & 1) * 32 + g * 2, hb = pack_b(hv, hv);
                    sts16(hd, hb); sts16(hd + 64, hb);
                }
                proxy_fence();
                bar_sync(4, 128);
                TSL(15);
#pragma unroll 1
                for (int n = 0; n < 8; n++) {
                    mbar_wait(bars + (n == 7 ? full_bar(23) : B_FULL + slot) * 8, n == 7 ? 0 : ph);
                    const uint64_t a = dw + slot * 512;
                    float d[4];
                    wg_fence();
                    wg_w0(d, a, dh); wg_w<1>(d, a + 128, dh + 16); wg_w<1>(d, a + 256, dh + 32); wg_w<1>(d, a + 384, dh + 48);
                    wg_commit();
                    wg_wait<0>();
                    touch(d);
                    st_relaxed32(my_part + n * 8 * 56 * 16, (__float_as_uint((q & 2) ? d[2] : d[0]) & ~3u) | tag);
                    if (lane == 0) mbar_arrive(bars + (B_EMPTY + slot) * 8);
                    if (++slot == NSLOT) { slot = 0; ph ^= 1; }
                }
                TSL(16);
            }
        } else {
            asm volatile("setmaxnreg.dec.sync.aligned.u32 40;");
            const int sw = warp - 12;
            const uint32_t la = sm + SM_CH + ((lane & 1) == rank ? 4 * CH_SZ + 64 : 0) + sw * 1024 + (lane >> 1) * 16;
            const uint32_t sa = sm + SM_SLAB + rank * 8192 + sw * 2048 + (lane ^ ((lane >> 3) & 1)) * 16;
#pragma unroll 1
            for (int jb = 0; jb < 4; jb++) {
                mbar_wait(bars + (B_STG + jb) * 8, 0);
                uint4 o[4];
#pragma unroll
                for (int i = 0; i < 4; i++) o[i] = lds128(la + jb * CH_SZ + i * 256);
#pragma unroll
                for (int i = 0; i < 4; i++) sts128(sa + jb * 16384 + i * 512, o[i].x, o[i].y, o[i].z, o[i].w);
                proxy_fence();
                __syncwarp();
                if (lane == 0) {
                    asm volatile("cp.async.bulk.tensor.5d.global.shared::cta.bulk_group [%0, {%2, %3, %4, %5, %6}], [%1];"
                                 :: "l"(&tm_o), "r"(sm + SM_SLAB + jb * 16384 + rank * 8192 + sw * 2048), "r"(G * 16), "r"(0), "r"(16 * sw), "r"(rank), "r"(jb) : "memory");
                    asm volatile("cp.async.bulk.commit_group;" ::: "memory");
                }
            }
            if (lane == 0) {
                const uint2 tk = lds64(sm + SM_TOK);
#pragma unroll
                for (int jb = 0; jb < 4; jb++) {
                    if (jb == 0) asm volatile("cp.async.bulk.wait_group 3;" ::: "memory");
                    if (jb == 1) asm volatile("cp.async.bulk.wait_group 2;" ::: "memory");
                    if (jb == 2) asm volatile("cp.async.bulk.wait_group 1;" ::: "memory");
                    if (jb == 3) asm volatile("cp.async.bulk.wait_group 0;" ::: "memory");
#pragma unroll
                    for (int k = 0; k < 2; k++)
                        if (((k ? tk.y : tk.x) & 0x619) == 512 * sw + 8 * jb + rank)
                            asm volatile("mbarrier.arrive.release.cluster.shared::cluster.b64 _, [%0];" :: "r"(mapa(bars + B_FIX * 8, k)) : "memory");
                }
            }
            TSL(17); TG(30);
        }
    } else {
        asm volatile("setmaxnreg.dec.sync.aligned.u32 48;");
        cluster_wait();
        if (warp == 16) {
            TSL(19);
            const bool lead = elect();
            if (lead) {
                sts32(sm + SM_TOK + 12, 0);
                asm volatile("cp.async.bulk.shared::cluster.global.mbarrier::complete_tx::bytes [%0], [%1], 6144, [%2];"
                             :: "r"(sm + SM_F2), "l"(p.tab + 1536), "r"(bars + B_SLAB * 8) : "memory");
                asm volatile("cp.async.bulk.tensor.5d.shared::cluster.global.mbarrier::complete_tx::bytes.multicast::cluster"
                             " [%0], [%1, {%3, %4, %4, %4, %5}], [%2], %6;"
                             :: "r"(sm + SM_SLAB + rank * 32768), "l"(&tm_x), "r"(bars + B_SLAB * 8), "r"(G * 16), "r"(0), "r"(2 * rank), "h"((uint16_t)3) : "memory");
            }
            TSL(20);
            if (G < 56) {
                uint64_t pol; asm volatile("createpolicy.fractional.L2::evict_first.b64 %0, 1.0;" : "=l"(pol));
                int ws = 0, wp = 0, slot = 0, ep = 1;
#pragma unroll 1
                for (int n = 0; n < 24; n++) {
                    if (n >= DEPTH) {
                        mbar_wait(bars + (B_FULL + ws) * 8, wp);
                        if (++ws == NSLOT) { ws = 0; wp ^= 1; }
                    }
                    mbar_wait(bars + (B_EMPTY + slot) * 8, ep);
                    if (lead) {
                        const uint32_t fb = bars + (n == 23 ? full_bar(23) : B_FULL + slot) * 8;
                        const bool gu = n < 16;
                        mbar_expect(fb, 8192);
                        tma3d(sm + SM_RING + slot * 8192, gu ? &tm_g : &tm_d, gu ? G * 64 : rank * 512 + (n - 16) * 64, gu ? rank * 512 + n * 32 : G * 64, fb, pol);
                        sts32(sm + SM_TOK + 12, n + 1);
                    }
                    if (++slot == NSLOT) { slot = 0; ep ^= 1; }
                }
                TSL(23);
            }
        } else if (warp == 17) {
            if (lane == 0) { asm volatile("prefetch.tensormap [%0];" :: "l"(&tm_d) : "memory"); asm volatile("prefetch.tensormap [%0];" :: "l"(&tm_o) : "memory"); }
            if (lane < 2 && c + 128 * lane < 192) asm volatile("prefetch.global.L2 [%0];" :: "l"(p.tab + (c + 128 * lane) * 8));
            if (G < 56) {
                const bool lead = elect();
                int n = NSLOT;
#pragma unroll 1
                for (; n < 24; n++) {
                    const int m = n - DEPTH;
                    if (m < NSLOT) asm volatile("{ .reg .pred p; mbarrier.try_wait.parity.shared::cta.b64 p, [%0], 0;\n"
                                                "@!p mbarrier.try_wait.parity.shared::cta.b64 p, [%0], 0; @!p pmevent 1; }" :: "r"(bars + (B_FULL + m) * 8) : "memory");
                    else mbar_wait(bars + (B_PROBE + ((m - NSLOT) & 3)) * 8, ((m - NSLOT) >> 2) & 1);
                    uint32_t issued;
                    asm volatile("ld.volatile.shared.u32 %0, [%1];" : "=r"(issued) : "r"(sm + SM_TOK + 12) : "memory");
                    if ((int)issued >= n && n > NSLOT) break;
                    if (lead) {
                        const bool gu = n < 16;
                        const int c0 = gu ? G * 64 : rank * 512 + (n - 16) * 64, c1 = gu ? rank * 512 + n * 32 : G * 64;
                        asm volatile("cp.async.bulk.prefetch.tensor.3d.L2.global [%0, {%1, %2, %3}];" :: "l"(gu ? &tm_g : &tm_d), "r"(c0), "r"(c1), "r"(0) : "memory");
                        const uint32_t pb = bars + (B_PROBE + ((n - NSLOT) & 3)) * 8;
                        mbar_expect(pb, 16);
                        asm volatile("cp.async.bulk.shared::cluster.global.mbarrier::complete_tx::bytes [%0], [%1], 16, [%2];"
                                     :: "r"(sm + SM_PROBE + ((n - NSLOT) & 3) * 16),
                                        "l"(gu ? p.w2 + (size_t)(c1 + 31) * 3584 + c0 : p.wd + (size_t)(c1 + 63) * 1024 + c0), "r"(pb) : "memory");
                    }
                }
#pragma unroll 1
                for (int m = max(n - DEPTH, NSLOT); m < n; m++) mbar_wait(bars + (B_PROBE + ((m - NSLOT) & 3)) * 8, ((m - NSLOT) >> 2) & 1);
                TSL(41);
            }
        } else {
            const int sw = warp - 18;
            uint32_t tag;
            if (sw == 0) {
                uint4* const my_stats = p.sc->stats + c * 8 + (lane >> 2);
                asm volatile("ld.relaxed.gpu.global.u32 %0, [%1];" : "=r"(tag) : "l"(&p.sc->epoch) : "memory");
                float ws = 0.f;
#pragma unroll
                for (int k = 0; k < 4; k++) {
                    const uint4 w = ldg128(reinterpret_cast<const uint4*>(p.wr) + 32 * k + lane);
                    ws += (blo(w.x) + bhi(w.x)) + (blo(w.y) + bhi(w.y)) + (blo(w.z) + bhi(w.z)) + (blo(w.w) + bhi(w.w));
                }
                if (q == 0) st_relaxed128(my_stats, make_uint4(0, 0, 0, 0));
                tag = tag % 3 + 1;
                sts32(sm + SM_TOK + 8, tag);
                bar_arrive(6, 320);
#pragma unroll
                for (int o = 1; o < 32; o <<= 1) ws += __shfl_xor_sync(0xFFFFFFFFu, ws, o);
                const uint32_t tb = ((tag & 1) << 15) | ((tag >> 1) << 31);
                const uint32_t ra = sm + SM_RED + (lane >> 1) * 144 + (lane & 1) * 64;
                touch(ws);
                bar_sync(7, 288);
                const uint4 a0 = lds128(ra), a1 = lds128(ra + 16), a2 = lds128(ra + 32), a3 = lds128(ra + 48);
#define F(v) __uint_as_float(v)
                float ss = (F(a0.x) + F(a1.x)) + (F(a2.x) + F(a3.x)), dw = (F(a0.y) + F(a1.y)) + (F(a2.y) + F(a3.y));
                float sx = ((F(a0.z) + F(a1.z)) + (F(a2.z) + F(a3.z))) + ((F(a0.w) + F(a1.w)) + (F(a2.w) + F(a3.w)));
#undef F
                ss += __shfl_xor_sync(0xFFFFFFFFu, ss, 1); dw += __shfl_xor_sync(0xFFFFFFFFu, dw, 1); sx += __shfl_xor_sync(0xFFFFFFFFu, sx, 1);
                const float mean = sx * (1.0f / 1024.0f);
                const float var = fmaxf(ss * (1.0f / 1024.0f) - mean * mean, 0.f);
                const float m = rb(mean);
                float sd; asm("sqrt.approx.ftz.f32 %0, %1;" : "=f"(sd) : "f"(rb(rb(var) + 1e-5f)));
                const float rs = rcp(rb(sd));
                const float hi = rb(rs);
                const uint32_t p0 = pack_b(m, hi), p1 = pack_b(rs - hi, rs * (dw - m * ws));
                const uint32_t o0 = __shfl_xor_sync(0xFFFFFFFFu, p0, 2), o1 = __shfl_xor_sync(0xFFFFFFFFu, p1, 2);
                if (q == 0) st_relaxed128(my_stats, make_uint4(prmt(p0, o0, 0x5410), (prmt(p0, o0, 0x7632) & 0x7FFF7FFFu) | tb,
                                                               prmt(p1, o1, 0x5410), prmt(p1, o1, 0x7632)));
                TSL(9);
            } else {
                bar_sync(6, 320);
                tag = lds32(sm + SM_TOK + 8);
            }
            bar_sync(3, 320);
            const uint32_t kk = lane < 16 ? lds32(sm + SM_KEYS + lane * 4) : 0u;
            const uint32_t m1 = __reduce_max_sync(0xFFFFFFFFu, kk);
            const uint32_t m2 = __reduce_max_sync(0xFFFFFFFFu, kk == m1 ? 0u : kk);
            const uint32_t key = sw ? m2 : m1;
            const int t = (0xFFFF - (key & 0xFFFF)) & 2047;
            {
                const uint4* row = reinterpret_cast<const uint4*>(p.x + (size_t)t * 1024) + lane;
                uint4 xr[4];
#pragma unroll
                for (int i = 0; i < 4; i++) xr[i] = ldg128(row + 32 * i);
                const uint4 stk = ld_relaxed128(p.sc->stats + (((t >> 3) & 3) * 64 + (t >> 5)) * 4 + ((t >> 1) & 3));
                if (lane == 0) {
                    sts32(sm + SM_TOK + 4 * sw, t);
                    if (c == 0 && sw == 0) st_relaxed32(&p.sc->epoch, tag);
                }
                const uint32_t se = (t & 1) ? 0x3232 : 0x1010;
                const uint32_t m = prmt(stk.x, 0, se), hi = prmt(stk.y, 0, se) & 0x7FFF7FFFu, lo = prmt(stk.z, 0, se);
                const uint32_t a = sm + SM_XSEL + lane * 32 + sw * 16;
#pragma unroll
                for (int i = 0; i < 4; i++) {
                    sts128(a + i * 1024, norm2(xr[i].x, m, hi, lo), norm2(xr[i].y, m, hi, lo), norm2(xr[i].z, m, hi, lo), norm2(xr[i].w, m, hi, lo));
                    if (sw == rank && 16 * i + (lane >> 1) == G) sts128(sm + SM_XRAW + (lane & 1) * 16, xr[i].x, xr[i].y, xr[i].z, xr[i].w);
                }
                proxy_fence();
                __syncwarp();
                if (lane == 0) mbar_arrive(bars + B_TOK * 8);
                TSL(42);
            }
            if (sw == rank) {
                const int col = 4 * q + 2 * (lane >> 4) + ((lane >> 3) & 1), d = G * 16 + col;
                const float r = __uint_as_float((key & 0x80000000u) ? (key & 0x7FFF0000u) : (~key & 0xFFFF0000u));
                const float sg = rb(sigmoidf_(r));
                const float xn = blo(lds16(sm + SM_XSEL + (d >> 3) * 32 + rank * 16 + (d & 7) * 2));
                const float xv = blo(lds16(sm + SM_XRAW + col * 2));
                mbar_wait(bars + (G < 56 ? full_bar(23) : B_PEER) * 8, 0);
                TSL(24);
                const uint4* src = reinterpret_cast<const uint4*>(p.sc->part) + c * 224 + lane;
                float s0 = 0, s1 = 0, s2 = 0, s3 = 0;
                {
                    uint4 pv[7];
                    int it = 0;
                    bool ok;
                    do {
                        uint32_t bad = 0;
#pragma unroll
                        for (int i = 0; i < 7; i++) pv[i] = ld_relaxed128(src + 32 * i);
#pragma unroll
                        for (int i = 0; i < 7; i++) bad |= (pv[i].x ^ tag) | (pv[i].y ^ tag) | (pv[i].z ^ tag) | (pv[i].w ^ tag);
                        ok = __all_sync(0xFFFFFFFFu, (bad & 3) == 0);
                    } while (!ok && ++it < SPIN_LIMIT);
#pragma unroll
                    for (int i = 0; i < 7; i++) {
                        s0 += __uint_as_float(pv[i].x); s1 += __uint_as_float(pv[i].y); s2 += __uint_as_float(pv[i].z); s3 += __uint_as_float(pv[i].w);
                    }
                }
                TSL(25);
                const bool u16 = lane & 16, u8 = lane & 8;
                const float y0 = (u16 ? s2 : s0) + __shfl_xor_sync(0xFFFFFFFFu, u16 ? s0 : s2, 16);
                const float y1 = (u16 ? s3 : s1) + __shfl_xor_sync(0xFFFFFFFFu, u16 ? s1 : s3, 16);
                float y = (u8 ? y1 : y0) + __shfl_xor_sync(0xFFFFFFFFu, u8 ? y0 : y1, 8);
                y += __shfl_xor_sync(0xFFFFFFFFu, y, 4);
                const float z = rb(xn + rb(rb(y) * sg));
                const float gt = rb(siluf_(z));
                mbar_wait(bars + B_FIX * 8, 0);
                const float o = xv + rb(blo(lds16(sm + SM_FIX + col * 2)) * gt);
                if (!(lane & 4)) p.out[(size_t)t * 1024 + d] = __float2bfloat16(o);
                TSL(26); TG(29);
            }
        }
    }
}

__device__ __align__(128) const uint32_t g_tab[7680] = {
0x2fff3000,0x2e7c2fd4,0x2fc92fd4,0xad72af5a,0x2ff82ffc,0x230e2c07,0x2faf2fbc,0x217ea934,0x2fed2ff4,0xad4da8d5,0x2f912fa0,0x2e5e2bb7,
0x2fdd2fe6,0xb000af46,0x2f6e2f80,0x2fdd2fc9,0x2ff42fff,0x2e1f2fc9,0x2e1f2e7c,0xa875ad72,0x2fbc2fdd,0x9fd92a4e,0x2d4d2dba,0x2cd825db,
0x2f5a2f91,0xaeb5ac07,0x2c5d2cd8,0x30002f30,0x2ed02f1a,0xaf80aff4,0x2aaa2bb7,0x2cb02f1a,0x2fdd2ffc,0x2dba2fbc,0x2a4e2c07,0x25dba934,
0x2f462fa0,0xa7652875,0x25152875,0x2f802d27,0x2e3f2ed0,0xafa0ad72,0xa17e1cb6,0x2e3f2fe6,0x2cd82d96,0xadfeafd4,0xa934a6a1,0xa44e29f1,
0x2fbc2ff8,0x2d4d2faf,0x9fd9230e,0x2cd8217e,0x2e992f46,0xaa4e2515,0xaa4ea765,0x2fd42f80,0x2cb02dba,0xafffae99,0xad72ac5d,0x27652dba,
0x28752b05,0xab5eaee9,0xaf1aae5e,0xae3fa934,0x2f912ff4,0x2cd82fa0,0xac07a8d5,0x2f302bb7,0x2dba2ed0,0xac5d1cb6,0xae99ad72,0x2dba2fe6,
0x29932c5d,0xafc9af6e,0xafe6af6e,0xaaaa25db,0xa17e244e,0xa30ead4d,0xafafaffc,0xaff8aee9,0x2f5a2fed,0x2c5d2f91,0xaeb5ad4d,0x30002e5e,
0x2cb02e3f,0xad72a17e,0xafffafa0,0x27652e3f,0x217e2993,0xaf02afe6,0xaf02afc9,0xaf1aaaaa,0xab05a5db,0x2814aa4e,0xac07adba,0xad4dafdd,
0x2f1a2fe6,0x2bb72f80,0xaff4af46,0x2f1a2fc9,0x2b052d96,0xae5ea6a1,0xaee9afd4,0xa93429f1,0xa5db244e,0xadbaaffc,0xaa4ead4d,0xafddaee9,
0xaddcabb7,0x2cb0a17e,0x2765a17e,0x1cb6ad00,0x2ed02fdd,0x2aaa2f6e,0xaf80b000,0x2cb02fdd,0x28752cd8,0xaf1aa934,0xab5eadfe,0xae3fa44e,
0xab05a17e,0xac07afaf,0x2814a30e,0xad4daff8,0xaf6eaddc,0x2eb52765,0x2eb52cb0,0x2dba1cb6,0x29932f5a,0xa7652e99,0x25152e99,0x2aaaad96,
0xafa0ab05,0xabb7afed,0xaff4acd8,0x28d52ffc,0xa814af02,0x2f912d27,0x9fd9ae1f,0xaee9ae3f,0x2fd42c32,0xaf5a1cb6,0x30002d72,0x2fd42515,
0x28752f46,0xa8d52e7c,0xa8d52c32,0x2e3fa993,0xafedac5d,0xa934b000,0xaf30af5a,0xa8142eb5,0x1648adfe,0x2e992e5e,0x2c87a814,0xa9f1affc,
0x2fe62e1f,0xafffa875,0x2ddc2ff4,0x2ed02e1f,0x26a12f30,0xa9f12e5e,0xad96244e,0x2fd41fd9,0xafffad27,0xa515aff4,0xac32aff4,0xaddc2b5e,
0x2875acb0,0x2d272f46,0x2fa02993,0x2875aed0,0x2ee92f6e,0xaf91ac87,0x1fd92e99,0x28143000,0x244e2f1a,0xab052e3f,0xaf91a875,0x2fbc2b5e,
0xafd4addc,0x1648afc9,0x1648ae7c,0xafdd9cb6,0x2c32aa4e,0x2aaa2fd4,0x2f802e99,0x2e7caa4e,0x2d002ffc,0xae1fae5e,0xad272814,0xabb72dfe,
0x1fd92f02,0xac072e1f,0xafedad27,0x2dfe2e3f,0xaf6eae7c,0x25dbaf80,0x2c5daaaa,0xaf6eac32,0x2ddca5db,0x25153000,0x2c323000,0x2fff26a1,
0x28d52fbc,0xabb7af91,0xaff4ab05,0xafa0244e,0x96482ee9,0xac872dfe,0xae99af30,0x29f12fbc,0xaed0af02,0x2993af1a,0x2f46217e,0xacb0af02,
0x2f1a1cb6,0xa30e2fc9,0xa30e2e7c,0x2e1f2ddc,0x9fd92eb5,0xa44eb000,0xae5eaf5a,0xaf30ac5d,0xa17e2ed0,0xad002ddc,0xabb7afff,0xa17e2fe6,
0xadfeaf6e,0x2c07ae99,0x2fed2c87,0x9fd9b000,0x2fd42814,0xa9f12f30,0xad962934,0x26a12fed,0xaaaa2d00,0x2765afa0,0xa515afa0,0xa993afaf,
0xa5152eb5,0xad722dba,0x9cb6af6e,0xac322eb5,0xad00afbc,0x2d27adfe,0x2e1f2f30,0x2bb7aee9,0x2ffc2b5e,0xacd82e3f,0xafeda875,0xab052f1a,
0xadba2993,0x2c87ae7c,0x2c87ac32,0x2a4eaf46,0xaddc2d96,0xafe62c5d,0xaed02c5d,0x2fffa9f1,0x2e1fad4d,0x2e3f2814,0x2f02ac07,0xad27ab05,
0xae5e2d00,0x9fd9af1a,0xaf302b5e,0xa44e2faf,0x2e99acb0,0xad962f80,0x2f5aaaaa,0x2e99aed0,0xae3f2d72,0xaff82c32,0xaff82515,0x2f021cb6,
0x2ee9ac87,0x2d4d29f1,0x2ffc9648,0xa44eae99,0xaf6e2b05,0x26a1afbc,0xafd4a44e,0xadba2f91,0x2fc9a8d5,0xaf462e3f,0x2f802875,0x2fe6a8d5,
0xae992d4d,0xb0002c07,0xaf6ea814,0x2c872b05,0x2f80ab5e,0x2c322bb7,0x2e7c2bb7,0x2aaaaff8,0xaff42765,0x2b5eafff,0xad27ad72,0xaff42cb0,
0x2fed1648,0xaffc2c5d,0x2b052eb5,0x2cd82a4e,0xaee92d27,0xaffc2bb7,0xad4dad00,0x244e2e1f,0x2fdda993,0x29f12cb0,0x29f12ed0,0x2eb5af46,
0xafe61648,0x2d72afdd,0x9cb6afd4,0xaed01648,0x2f022934,0xafa02814,0xa8d52fed,0xa30e2f30,0xaf302d00,0xafed2b5e,0xa814af1a,0xa9342faf,
0x3000a765,0x26a12d72,0xa5db2fff,0x3000acb0,0xaf46a6a1,0x2ed0af5a,0x2cb0af5a,0xa993ac87,0x2d272cd8,0xae3f9fd9,0xaf022d4d,0xae1f2fbc,
0xaf6e2cd8,0xafd42b05,0x26a1affc,0xadba2fed,0x2fe6a30e,0x1cb62e1f,0xad722f1a,0x2ed0a30e,0xae1faaaa,0x2fafae7c,0x2fafac32,0x28d5af80,
0x29342e99,0xac07a9f1,0xafbc1648,0xaffc2c87,0xafa02cb0,0xafaf2aaa,0x2d00af80,0xafa02ed0,0x2f911648,0xa44e2eb5,0xafbc2c5d,0x2b052a4e,
0xac87acd8,0x3000ad4d,0x2f6e1fd9,0x2e99afbc,0x9cb62faf,0xa515ad27,0xac32ad27,0xad72a30e,0xafc92c87,0xaf802a4e,0x2f46adba,0xafe62c87,
0x2f02244e,0xa8d52f30,0xafa01fd9,0xa30e2e5e,0xa934ae1f,0x2fbcabb7,0x2c072d00,0x2ffcad27,0xaa4e2fff,0x26a1aed0,0x26a1afe6,0x1648addc,
0xaf4629f1,0xac3225db,0xae7c25db,0x29931648,0xab5e2f91,0xafaf2e5e,0xad002fed,0x2f1aad4d,0x2ee9a875,0xaf302ff8,0x2dfea17e,0x2fbcaff4,
0x2c5dafc9,0xa9f12d72,0x2d96afff,0x2c5dae7c,0xaf022993,0xab5e2515,0xab5ea765,0xa30e2aaa,0xacd82fd4,0xaf302dba,0xaf912f6e,0x2c07a6a1,
0x2d969fd9,0xafdd2fed,0x25db2c07,0x2f5aadfe,0x2e7caff8,0xad722f02,0x2fffae3f,0x2fc9aff8,0xaeb52934,0xaa4e244e,0x9648acd8,0xac5d2dfe,
0xaddc2ff8,0xae7c2d00,0xafc92d00,0x9cb628d5,0x2bb72515,0xaff82f80,0xab5e2f46,0x2bb7a765,0x2fbcaf5a,0xaf302fdd,0x2dfea5db,0x2ee9ad96,
0xae5e28d5,0xa934230e,0x2b05af02,0xaee92fa0,0xaeb52fff,0xad962c32,0xad962515,0xac872ddc,0x276529f1,0xaf802eb5,0xaf462fdd,0xa51529f1,
0x2ff4adfe,0xaff82fed,0x217e2c07,0x28759fd9,0xadfe2875,0xa814217e,0x2e5eaff8,0xaffc2ff4,0xaf5a2fe6,0xac872aaa,0xa6a1a993,0xaf5a2fc9,
0x9cb62c87,0xae7c2d96,0xafc92d96,0xaddc2eb5,0x2f1aac07,0xafaf2f30,0xad002f91,0xab5e2cd8,0xad962814,0xa5db1fd9,0x2fddaf91,0xaf5a2ee9,
0xafc92faf,0xaaaa28d5,0x2993ae1f,0xafe62faf,0xa8d52ddc,0xad002c32,0xad002515,0xaff82fff,0x2d4da6a1,0xae5e2dba,0xafed2f6e,0xaf912fd4,
0xad272765,0xa30e1cb6,0x2fafaddc,0xad272cb0,0xaffc2f5a,0xa81425db,0x2e5eafdd,0xadfe2d96,0xac5d2ee9,0xaa4e2934,0x9648ab05,0xaeb52e5e,
0x2993230e,0xac322b5e,0xae7c2b5e,0xaf462f02,0xacb026a1,0x9cb61648,0x2ddcaa4e,0xa76526a1,0xaff42ee9,0xa17e1fd9,0x2ff8af91,0xa8752814,
0xadfe2fa0,0xa44e230e,0x2cd8af02,0xa93428d5,0x96482aaa,0xa5db2515,0xa5dba765,0xa9f12993,0x2f462f5a,0x2c322e99,0x2e7c2e99,0xa993ad96,
0x2f1a2f30,0xa875244e,0x2e3f2e5e,0x2b5e1fd9,0x2ee92f02,0xaf30ad27,0x2dfe2e1f,0x2fbc2e3f,0x2eb52ed0,0xaf6eafff,0x2dba2ddc,0x2eb52fe6,
0x28752993,0xa8d52515,0xa8d5a765,0x2e3f2aaa,0x244e26a1,0xaf91ad96,0xab05a9f1,0x2fbc2fd4,0x96481fd9,0xae99afed,0xac87ac07,0x29f12dfe,
0xa515a17e,0x9cb6abb7,0xad72ad00,0xac32a17e,0xac5dab05,0xaf5aacd8,0xb000afed,0x2eb52ffc,0xaddcad27,0xae7caff4,0xafc9aff4,0x9cb62b5e,
0xaf02ae7c,0x217eaaaa,0xaf1aaf80,0xaf02ac32,0xafbcaf6e,0x2f302c87,0xadfeae99,0xaee9b000,0xafedafa0,0xaf30aff4,0xa934abb7,0xa81428d5,
0xafd4afff,0x1648ac32,0x1648a515,0xafddaddc,0xaed0af6e,0x2f462c5d,0x299325db,0xacb0af6e,0xad00adfe,0x2e1f2fed,0x2d272c07,0x2bb79fd9,
0xadfeaf02,0xa814ae1f,0x2e5e2d27,0xaffcae3f,0xaa4eacb0,0x2e992993,0x2fd42f46,0xaa4eaed0,0x1cb6a5db,0x2e7c3000,0x2fc93000,0x2ddc26a1,
0x2b5e2814,0xa8752934,0x2e3f2f30,0x2f1a2fed,0x1648a814,0x2c879fd9,0x2e992f91,0xa9f1aee9,0x2c322875,0x2f802fa0,0x2aaa2d27,0x2e7c2875,
0x2f1a2ddc,0xa30e2c32,0xa30e2515,0x2e1f2fff,0x2ffc2fd4,0xafedad96,0xacd8a9f1,0xab0526a1,0x2e1f2c32,0x2ff42d72,0xa8751cb6,0x2e1f2515,
0x2ffc2f6e,0x28142e99,0xae5eac87,0x2dfe3000,0x2eb52fbc,0xaf5aab05,0xb000af91,0xac5d244e,0x29932d00,0xac32afa0,0xae7cafa0,0xaf46afaf,
0x2fe62fd4,0x2ddc3000,0xafffaf5a,0x2ed02fd4,0x2d002ee9,0xad271fd9,0xae1faf91,0xabb72814,0x9fd928d5,0xae5eaff4,0xa44eabb7,0xaf30afa0,
0xadbaaaaa,0x2c87a515,0x2c872765,0x2a4ea993,0x9cb62d96,0xacb02c5d,0xa7652c5d,0x2ddca9f1,0xaff8adfe,0xa30eafbc,0xafafaee9,0xa17e2f30,
0x244ead00,0x2dfe2f1a,0x2934ab5e,0xacd8afaf,0x2fdd2e7c,0xb000a993,0x2f6e2f46,0x2fdd2c32,0xae3f9cb6,0xaff8a765,0xaff8acb0,0x2f022ddc,
0xac07afdd,0x2dfeaa4e,0x1fd9adba,0xafeda5db,0x2f6e2934,0xa6a12ee9,0x2fd42e5e,0x2dbaab05,0x27652f1a,0xaaaaaff4,0xa9932bb7,0xa5152f1a,
0xafddadfe,0xadbaaee9,0xaa4eafbc,0xa5db2f30,0x2aaaab5e,0x2fc92bb7,0x2fe62bb7,0xa993aff8,0x2e3f2fc9,0xafa01cb6,0xa17e2ddc,0x2e3f2e7c,
0xae5e9648,0x2d4dac5d,0xaf91aeb5,0xafedaa4e,0xac07aff8,0x1fd9afaf,0x2dfea30e,0xafeda17e,0x2fdd2aaa,0x29f12fe6,0x29f12fc9,0x2eb5a993,
0xa5152dba,0xaddcae99,0xafffac5d,0xac322dba,0xaf02af30,0x2fa02c07,0x28d5acd8,0x230eaf91,0x2934ad00,0x2e5eab5e,0x2ee92f1a,0xab05afaf,
0x2dba2fc9,0xac5d2ddc,0xae991cb6,0x2dba2e7c,0xaf80a6a1,0x2765af5a,0xa515af5a,0xaf46ac87,0x217eae5e,0x230e2ffc,0x2faf2dfe,0x2ff82814,
0x2f6e244e,0x2fd42934,0xa6a12dfe,0x2dbaacd8,0xa5152e3f,0xafffa17e,0xaddcafa0,0xac322e3f,0xae1faf80,0x2fafa515,0x2faf2765,0x28d5af46,
0x2f9125db,0xaee92a4e,0xa8142dba,0x9fd92fdd,0x2f1a2e7c,0x2bb72f46,0xaff4a993,0x2f1a2c32,0xaf309648,0xacd8aeb5,0x2c07ac5d,0xaf91aa4e,
0x25dbae5e,0x2dba2dfe,0x2a4e2ffc,0x2fdd2814,0x2d722faf,0xae7cad27,0xafc9ad27,0xafffa30e,0x27652fdd,0xa9932f6e,0xaaaab000,0xa5152fdd,
0xaf02ae5e,0x28d5af91,0x2fa02d4d,0x230eafed,0x2f91217e,0xa8142faf,0xaee9230e,0x9fd92ff8,0xaa4e2d72,0x26a1afc9,0x26a1ae7c,0x1648afff,
0xaf8029f1,0xafc925db,0xafe625db,0x2f461648,0x2fa0a934,0x2bb72cd8,0x2ff4a44e,0xa8d5adfe,0xafbc2875,0x2934aff8,0xaffc217e,0xac072ff4,
0x2fd4a765,0xaf5a2ddc,0x30009cb6,0x2fd4acb0,0xaf02aaaa,0xab5eacb0,0xab5eaed0,0xa30e2f80,0x2e5e2c5d,0xab053000,0x29342f5a,0x2ee9aeb5,
0xad96ad4d,0x2fddacd8,0xa5dbafbc,0xaf5a1fd9,0x2cb02e1f,0xaddca875,0x1cb62ff4,0x27652e1f,0xa6a1af91,0x29f1afed,0x2d96ae5e,0xafd42d4d,
0x9cb62ff8,0xafe62d00,0xaed02d00,0x2d7228d5,0x2875afe6,0x2d272993,0x2fa0aaaa,0x2875afc9,0xac072f5a,0x2934afdd,0xaffc25db,0xafbc2d96,
0x2cd8af1a,0x2f91ae3f,0x2f302875,0xac07ab5e,0xaeb52d72,0xad96a765,0xad96acb0,0xac872fff,0x2fc9aa4e,0xa9932fd4,0x2aaa2e99,0x2fe6aa4e,
0xaff41fd9,0x2ff8acd8,0xa17eafbc,0xa875ad4d,0x2ffca875,0x2ee9a17e,0xa44e2ff8,0x2d4daff4,0xaf6ea515,0x25dbaf46,0x2c5daf80,0xaf6e2765,
0x2d722c87,0xafe62d96,0xaed02d96,0x9cb62eb5,0xa8d5aee9,0x2bb72b05,0x2ff4a934,0x2fa0ae5e,0x2d962c07,0x25db2d4d,0xafdd2b05,0x2f5aa814,
0xa765af02,0x2f46af1a,0x2f80217e,0x2515af02,0xa8d52fff,0xad00a765,0xad00acb0,0xaff82d72,0x2dfeaeb5,0xacd83000,0x244e2f5a,0x29342c5d,
0xa17e2fc9,0xad002fff,0xabb7ad72,0xa17e2e7c,0x2d4daf5a,0x2ee9a5db,0xa44e2fdd,0x2ffcad96,0xafd42c07,0x29f1af91,0x2d96af30,0xa6a1acd8,
0x2f46230e,0xafc92b5e,0xafe62b5e,0xaf802f02,0xae7c2eb5,0xafff2dba,0x2d72af6e,0xafc92eb5,0x2ff4a814,0x217e2d4d,0xaff82b05,0x28752c07,
0xad4dab5e,0x2fedae3f,0x2e5e2875,0x2f91af1a,0x96482f80,0xa5dbacb0,0xa5dbaed0,0xa9f1aaaa,0xad729648,0xa515a6a1,0xac32a6a1,0x9cb62a4e,
0xae1f2ffc,0xae3f2c07,0xaf022fbc,0x2d27a934,0x2cd8230e,0xaffc2fa0,0x2b0528d5,0x2fedaf02,0x2e99afe6,0xad962f46,0x2f5aaf80,0x2e99afc9,
0x230eaddc,0x2d27aed0,0x2d27afe6,0xafaf2fff,0xafbc2c87,0x1fd9a9f1,0xad4d1648,0xacd82e99,0xaa4e2f30,0xac5d2814,0xaeb52fed,0x96482934,
0x2ed0a8d5,0xaf802e3f,0x2aaa2875,0x2cb0a8d5,0x2e99affc,0x3000afbc,0x2f6eac07,0xac872934,0xa993a8d5,0x2ed0afaf,0x2cb0afaf,0xaf462e1f,
0xaff42ed0,0x2b5ead72,0xad271cb6,0xaff42fe6,0xa44e2dba,0x9fd9a6a1,0xaf302fd4,0xae5e2f6e,0x2fbcad27,0x2d4dabb7,0x9fd92d00,0x2cd8ae1f,
0x2c87af80,0x2f5aae7c,0x2f5aac32,0x26a1aaaa,0xacb01648,0x2fffafdd,0x2d72afd4,0xa7651648,0xafaf2f91,0x2f1aafbc,0xab5ea44e,0xad002b05,
0x2b05230e,0xa44e28d5,0xafbc2fa0,0x2f91af02,0x3000aed0,0x26a19cb6,0xa5db2d72,0x3000afe6,0x2aaaaeb5,0x2c32a9f1,0x2e7ca9f1,0x2f80afdd,
0xad27244e,0x2e3fad4d,0x2f02affc,0x2e1faee9,0xaa4e2e5e,0xaeb52f30,0xac5d1fd9,0x9648244e,0x2cb0a30e,0xad722e1f,0xafff2f1a,0x2765a30e,
0x2ff8af46,0xabb72cb0,0xabb72ed0,0x2b5ea993,0x2b05ae99,0xa81429f1,0x2c079648,0x2d4dac87,0xafa02fe6,0xafaf2f80,0x2d00af46,0xafa02fc9,
0xa9342dba,0xafed2fd4,0xa814a6a1,0xaf302f6e,0x2c87a44e,0xb0002ffc,0xaf6e2d4d,0xae992ee9,0x2fffaf02,0xafe62ff8,0xaed02ff8,0xaddc2e3f,
0xaed02c87,0xaaaa2a4e,0x2f80adba,0xacb02c87,0xafaf2fed,0xab5e2b05,0x2f1aaffc,0xad002cd8,0xab052e1f,0xac072bb7,0x2814ad00,0xad4d2d27,
0x29f11cb6,0xac5d2c32,0xac5d2515,0xad962d72,0x2d722d96,0x25152c5d,0x2c322c5d,0x1cb6a9f1,0x2d272d4d,0xad00a814,0x2bb72c07,0x2e1f2b05,
0x2cd82d00,0xaffcaf1a,0x2b052b5e,0x2fed2faf,0x2c872cb0,0xadbaaf80,0x2a4e2aaa,0x2c872ed0,0xae3faddc,0xaff8aed0,0xaff8afe6,0x2f022fff,
0xaee9ae99,0xad4daf6e,0xaffcb000,0x244e2c87,0xaf6eaf30,0x26a1a814,0xafd4afed,0xadbaa934,0xafc9afa0,0x2f462d00,0xaf80afaf,0xafe6afa0,
0xac87ad4d,0x9648ac07,0x29f12814,0xae99ab05,0xa993ab5e,0x2ed02bb7,0x2cb02bb7,0xaf46aff8,0xa30ea765,0x2f1a2fff,0x2e1f2d72,0xa30eacb0,
0x244e1648,0x1fd92c5d,0x2f302eb5,0x2e5e2a4e,0x2ee92e1f,0x2ffc2f02,0x2d4d2e3f,0xa44ead27,0x2fdd2f80,0x29f12e7c,0x29f12c32,0x2eb52aaa,
0x2fe63000,0xad72a5db,0x1cb626a1,0x2ed03000,0x2f022f91,0xafa0afbc,0xa8d5a44e,0xa30e2b05,0x2b052d00,0xa44e2b5e,0xafbcaf1a,0x2f912faf,
0x16482765,0xafd4ad72,0xafddafff,0x16482cb0,0xaaaaa6a1,0xac32af5a,0xae7caf5a,0xaf80ac87,0xae1facd8,0x2d001fd9,0xabb7ad4d,0xad27afbc,
0xaf6eae5e,0xafd4af30,0x26a19fd9,0xadbaa44e,0xafe6aff4,0x9cb6ad27,0x2d722b5e,0xaed0aff4,0xae1faf46,0x2faf2cb0,0x2faf2ed0,0x28d5a993,
0xa934ac87,0x2c072f6e,0x2fbc3000,0x2ffc2e99,0xa8d5acb0,0x2875aaaa,0x2e3f2f80,0xa8d5aed0,0x29341648,0x2fed2eb5,0x28142c5d,0x2f302a4e,
0x2e992cd8,0x16482d4d,0xa9f19fd9,0x2c872fbc,0x2fff2faf,0xafe6ad27,0xaed0ad27,0xaddca30e,0x2fc92e99,0x2f802f5a,0xaf46ad96,0x2fe62e99,
0x2f022fed,0xa8d52b05,0xafa0affc,0xa30e2cd8,0x29342d27,0xafbcaf02,0xac07ae3f,0xaffcae1f,0xaa4e9cb6,0x26a1ac32,0x26a1a515,0x1648ad72,
0xaaaa29f1,0xaed025db,0xacb025db,0x2f801648,0xaf1aaf91,0x2875ae5e,0xae3fafed,0xab5e2d4d,0x2c07a875,0x2b052ff8,0x2d4da17e,0xa814aff4,
0x2eb52fc9,0xaf6ead72,0x2dba2fff,0x2eb52e7c,0xaf02af80,0xab5eafe6,0xab5eafc9,0xa30e2f46,0x2cd8a6a1,0x2f302d96,0x2f9129f1,0xac07afd4,
0x2d962ffc,0xafdda44e,0x25db2ee9,0x2f5a2d4d,0xae7ca17e,0x2d72abb7,0xafffad00,0xafc9a17e,0x2c5da934,0x2f5aa44e,0x30002cd8,0xaeb5adfe,
0x2d722ff8,0xacb02d00,0xa7652d00,0x2fff28d5,0xaf02a515,0x217eaf80,0xaf1aaf46,0xaf022765,0xa814af5a,0x2b052fdd,0x2d4da5db,0x2c07ad96,
0x2e5e2fa0,0x29342ff4,0xab052bb7,0x2ee9a8d5,0xaeb59cb6,0xad96aed0,0xad96afe6,0xac872d72,0xa765af6e,0x2f802c5d,0x2f4625db,0x2515af6e,
0x2ff42d4d,0xaff8a44e,0x217e2ee9,0x28752ffc,0xad4d2875,0xafbc217e,0xacd8aff8,0x1fd92ff4,0xaa4eafe6,0x2e99aaaa,0x2fd42993,0xaa4eafc9,
0x2fff2c87,0xacb02d96,0xa7652d96,0x2d722eb5,0xab5e2c07,0x2875af30,0xae3faf91,0xaf1aacd8,0xad96afbc,0xa5dbaffc,0x2fdd2934,0xaf5aac07,
0x2fc92875,0x2aaa2fa0,0xa9932d27,0x2fe62875,0xa8d52d72,0xad00aed0,0xad00afe6,0xaff89cb6,0xad4dafd4,0x2e5e2d96,0x2fed29f1,0x2f91a6a1,
0x2e1fa765,0x2ff49cb6,0xa8752ddc,0x2e1facb0,0x1fd92f5a,0xafbc25db,0xacd8afdd,0xad4d2d96,0xaeb5aee9,0x2f5aa934,0x30002b05,0x2c5dae5e,
0x2f80230e,0xaed02b5e,0xacb02b5e,0xaaaa2f02,0x2cb02fd4,0x1cb63000,0xaddcaf5a,0x27652fd4,0xaff4ac07,0xa17eaffc,0x2ff82934,0xa875afbc,
0x2dfea8d5,0x244e2ff4,0xacd82bb7,0x29342fa0,0x96482f46,0xa5dbafe6,0xa5dbafc9,0xa9f1af80,0xafff9648,0xae7ca6a1,0xafc9a6a1,0x2d722a4e,
0x2ff81fd9,0x230e2ee9,0x2faf2814,0x217eaf91,0xafeda30e,0x2d4dafa0,0xaf91a8d5,0xae5e2f02,0x2fdd2515,0xb0002aaa,0x2f6e2993,0x2fdda765,
0x230eafff,0x2d27afc9,0x2d27ae7c,0xafaf2d72,0xa8142fdd,0xaffc2a4e,0xadfe2dba,0x2e5e25db,0x2a4eaf91,0x2c5d2c07,0x2eb5acd8,0x1648af30,
0xac322f1a,0x2993aff4,0xaf462bb7,0xae7c2f1a,0x2fdd1fd9,0x2dba2814,0x2a4e2ee9,0x25dbaf91,0xaf46a8d5,0x2765afaf,0xa515afaf,0xaf802e1f,
0x2e3f2c32,0xafa02ddc,0xa17e2fff,0x2e3f2515,0xacd8adba,0x2dfe26a1,0x2934afd4,0x244eaf6e,0xa8142ff8,0xadfe2faf,0xaffc230e,0x2e5e217e,
0x2c87af46,0x2f5aa515,0x2f5a2765,0x26a1af80,0xae7c2dba,0x9cb6ae99,0xaddcac5d,0xafc92dba,0x2fafab05,0xaf1a2ee9,0x2b5e2e5e,0x2d002934,
0xaf91a30e,0xacd8a8d5,0x2c07afa0,0xaf302f02,0x2dba2c32,0xac5d2fff,0xae992ddc,0x2dba2515,0xa993aeb5,0x2fc9a9f1,0x2fe6a9f1,0x2aaaafdd,
0xa17e2fed,0xa30eadfe,0xafaf9fd9,0xaff82c07,0x2a4eafed,0x2eb5af91,0x2c5d2d4d,0x1648ae5e,0xae7c2e3f,0xaddca17e,0x9cb6afa0,0xafc92e3f,
0x2ff8a993,0xabb72fe6,0xabb72fc9,0x2b5e2aaa,0xaf30a5db,0x2fbcaa4e,0x2ee9adba,0x2dfeafdd,0x2f1a2515,0x2bb72993,0xaff42aaa,0x2f1aa765,
0xab05adba,0x2e5eafd4,0x2ee926a1,0x2934af6e,0xa5db2fed,0xadba9fd9,0xaa4eadfe,0xafdd2c07,0x2ddcaf02,0xacb02ff8,0xa7652ff8,0x9cb62e3f,
0xac322fdd,0xaf462f6e,0x2993b000,0xae7c2fdd,0x2fafacd8,0x2b5e2934,0xaf1a2dfe,0x2d00244e,0xaf30a17e,0x2ee9afaf,0x2fbca30e,0x2dfeaff8,
0x29f12ddc,0xac5da765,0xac5dacb0,0xad969cb6,0xa993aa4e,0x2765ac87,0xa515ac87,0xaaaa2dba,0xafa02f30,0xabb7244e,0xaff42e5e,0x28d51fd9,
0x28142bb7,0xaf912e1f,0x1fd92d27,0x2ee9ad00,0x2fd4aed0,0xaf5a2fff,0x3000addc,0x2fd4afe6,0x2fafaf46,0x2fa0ae7c,0x2fa0ac32,0xad002993,
0xa44eac5d,0x2f91b000,0x2b05af5a,0xafbc2eb5,0xb0002dfe,0x2c87ae5e,0xae992814,0xaf6e2ffc,0xa5152e1f,0x9cb6a875,0xad722ff4,0xac322e1f,
0x26a12b05,0xa9f12cd8,0xad962fed,0x2fd4affc,0x2fffae1f,0x2515230e,0x2c32230e,0x2ddcaf1a,0x2875ae7c,0x2d27aaaa,0x2fa0af80,0x2875ac32,
0xaee929f1,0x2f91ae99,0x9fd9ac87,0xa8149648,0xafed2f1a,0xaf302e3f,0xa934a875,0xa8142b5e,0xa6a12ddc,0xb0002fc9,0xb0002e7c,0x25db1cb6,
0x2ed0aa4e,0xaf462fd4,0xa9932e99,0x2cb0aa4e,0x2e3faffc,0xad272e5e,0x2e1fa814,0x2f02adfe,0x9fd9abb7,0x2c07ad27,0x2fedae1f,0xadfe2d00,
0xaf6e2cb0,0x25dba993,0x2c5daf46,0xaf6e2ed0,0xaddc2fdd,0xa5159648,0xac329648,0xafff2fd4,0x28d52814,0xabb72934,0xaff42f30,0xafa02fed,
0x3000aee9,0x2e99adfe,0xac872f30,0x2f6eafbc,0x2c32af02,0x2f80af1a,0x2aaa217e,0x2e7caf02,0xab5e9cb6,0x2ff4afc9,0x2ff4ae7c,0x2d27addc,
0xaffc2eb5,0x2fedb000,0x2cd8af5a,0x2b05ac5d,0xa17e2c32,0xad002d72,0xabb71cb6,0xa17e2515,0x2dfea9f1,0xac072c87,0xafed2e99,0x1fd91648,
0x2fd4afbc,0xa9f12b05,0xad962f91,0x26a1a44e,0x2aaaae3f,0xa76528d5,0x251528d5,0x2993a875,0xafe62eb5,0xaddc2dba,0x2fffaf6e,0xaed02eb5,
0xae3f2fbc,0xae1f2dfe,0x2d27af30,0xaf022ee9,0x9fd92b5e,0xae5e2e3f,0xa44ea875,0xaf302f1a,0x2d96a993,0xae992e7c,0xae992c32,0xaf5a2f46,
0x299329f1,0xa76525db,0x251525db,0x2aaa1648,0x28d52934,0xaf02acd8,0x230e244e,0x2fa02dfe,0x28142875,0xaf91aff8,0x1fd9217e,0x2ee92ff4,
0x26a12765,0xaa4eaddc,0x16481cb6,0x26a12cb0,0xaf02af46,0xab5eae7c,0xab5eac32,0xa30e2993,0xae5eaeb5,0x2b059648,0xa934aa4e,0xaee9ac5d,
0xad96adfe,0x2fdd2e5e,0xa5dba814,0xaf5aaffc,0xacb0ad27,0x2ddc2faf,0x9cb6a30e,0xa765ad27,0x2fd42f91,0x2f6e2fed,0x2dba2e5e,0xa6a1ad4d,
0x2fff2ff8,0x25152d00,0x2c322d00,0x2ddc28d5,0x2faf2fe6,0xae1fa993,0x28d52aaa,0x2faf2fc9,0x2ee92f5a,0xaf91afdd,0x1fd925db,0x28142d96,
0xacd8ab5e,0xaf91ad00,0xaf30afaf,0x2c072f1a,0xaeb5addc,0xad96afc9,0xad96ae7c,0xac879cb6,0xafc9af5a,0x2993a6a1,0xaaaaac87,0xafe6af5a,
0xaff4affc,0x2ff82e5e,0xa17ea814,0xa875adfe,0x9fd9a875,0x2c07a17e,0x2fed2ff8,0xadfeaff4,0x29f12515,0x2fdd2f46,0x2eb52f80,0x29f1a765,
0x2ddc2c87,0x25152d96,0x2c322d96,0x2fff2eb5,0x2fa02ee9,0xaf02ab05,0x230e2934,0x28d52e5e,0x2d962ee9,0x25db2dfe,0xafddaf30,0x2f5a2fbc,
0x27652bb7,0xaf46ab5e,0xaf80aff8,0xa5152bb7,0xa8d59cb6,0xad00afc9,0xad00ae7c,0xaff8addc,0xadfeac5d,0x2cd89648,0xa44eaa4e,0xa934aeb5,
0xaff8afc9,0xae3fafff,0x2f022d72,0xaff8ae7c,0xadfeaf5a,0x2c07a5db,0x2fed2fdd,0x9fd9ad96,0xa6a1ac07,0x2f6e2f91,0x2dba2f30,0x2fd42cd8,
0x2aaa230e,0xa7652b5e,0x25152b5e,0x29932f02,0x2e7c2c5d,0x2fff2d96,0xad72a9f1,0x2fc92c5d,0x2ff42fbc,0x217e2dfe,0xaff8af30,0x28752ee9,
0x2d4d2f1a,0xafedad00,0xae5eafaf,0xaf91ab5e,0x96482993,0xa5dbae7c,0xa5dbac32,0xa9f1af46,0xaddc9648,0xafe6a6a1,0xaed0a6a1,0x2fff2a4e,
0xad27affc,0x2d00ac07,0xabb7afbc,0xae1f2934,0x2e5e230e,0x1fd92fa0,0x2f3028d5,0x244eaf02,0x2c872fe6,0xadbaaf46,0x2a4e2f80,0x2c872fc9,
0x230ead72,0x2d27ac32,0x2d27a515,0xafaf9cb6,0x2fbc2e99,0x9fd92f6e,0x2d4d3000,0x2cd8ac87,0xaa4e2b05,0xac5dafbc,0xaeb5a44e,0x96482f91,
0xaed0afa0,0x2f802d00,0xaaaaafaf,0xacb0afa0,0x2c872ffc,0x16482fbc,0xa9f12c07,0x2e99a934,0xaf80a8d5,0xac32afaf,0xae7cafaf,0xaaaa2e1f,
0xa30eaed0,0x2f1a2d72,0x2e1f9cb6,0xa30eafe6,0x2fed2dba,0xaffca6a1,0x2b052fd4,0x2cd82f6e,0xafbcae1f,0xad4daf02,0x1fd9ae3f,0xacd82d27,
0x2c87a993,0x2f5a2cb0,0x2f5a2ed0,0x26a1af46,0x2cb03000,0xafffa5db,0xad7226a1,0x27653000,0xafafa934,0x2f1aa814,0xab5eafed,0xad00af30,
0x2f30230e,0x2fed28d5,0x28142fa0,0x2934af02,0x16482ed0,0xafd41cb6,0xafddad72,0x16482fe6,0xaf46aeb5,0x2ed0a9f1,0x2cb0a9f1,0xa993afdd,
0x2e1fa44e,0xad002d4d,0x2bb72ffc,0x2d272ee9,0xaa4e2cd8,0xaeb52b05,0xac5daffc,0x96482fed,0xacb0aff4,0x2d72ad27,0x2fff2b5e,0xa765aff4,
0x2ff82aaa,0xabb72e7c,0xabb72c32,0x2b5e2f80,0xab052c87,0x2814af6e,0xac07b000,0xad4dae99,0xa8d5afe6,0x2875af80,0x2e3f2f46,0xa8d5afc9,
0x2f912dba,0xa44e2fd4,0xafbca6a1,0x2b052f6e,0xae99244e,0x9648affc,0x29f1ad4d,0xac87aee9,0x1cb6af02,0x25152ff8,0x2c322ff8,0x2d722e3f,
0x2ed02e99,0x2aaa2f5a,0xaf80ad96,0x2cb02e99,0xafafa44e,0xab5eaf30,0x2f1a9fd9,0xad00ae5e,0x2b05ad27,0x2c072f02,0xa8142e3f,0x2d4d2e1f,
0x29f12fff,0xac5daed0,0xac5dafe6,0xad96addc,0xaf46aa4e,0xac32ac87,0xae7cac87,0x29932dba,0x2f1a2b05,0xa8752fed,0x2e3f2cd8,0x2b5eaffc,
0xaee9abb7,0x2f30ae1f,0xadfead27,0xafbc2d00,0x2eb52c32,0xaf6e1cb6,0x2dba2d72,0x2eb52515,0x2fafa993,0x2fa0a515,0x2fa02765,0xad00aaaa,
0xafed26a1,0xa934ad96,0xaf30a9f1,0xa8142fd4,0x30009fd9,0xac872fed,0x2e992c07,0x2f6eadfe,0xafe6a17e,0x2fffabb7,0xaddcad00,0xaed0a17e,
0xac5d2f30,0xaf5a2e5e,0xb000244e,0x2eb51fd9,0x2ddcae1f,0x2e7c230e,0x2fc9230e,0x1cb6af1a,0xaf022cb0,0x217eaf46,0xaf1aa993,0xaf022ed0,
0x2fbca9f1,0xaf302e99,0x2dfe2c87,0x2ee91648,0xa44eafa0,0x2b05aff4,0x2f91abb7,0xafbc28d5,0xa6a12fff,0xb0002c32,0xb0002515,0x25db2ddc,
0x2c32af6e,0x2aaa2c5d,0x2f8025db,0x2e7caf6e,0xae3f2dfe,0x2d27afed,0xae1fac07,0xaf021fd9,0x2dfe2bb7,0x28142d27,0xae5e2e1f,0x2ffcad00,
0xaa4eae7c,0x2e99af80,0x2fd4aaaa,0xaa4eac32,0x9cb62fdd,0xae7c9648,0xafc99648,0xaddc2fd4,0x2b5eafbc,0xa8752f91,0x2e3f2b05,0x2f1aa44e,
0xb0002814,0xae991fd9,0x2c87af91,0xaf6e2ee9,0x2ed02875,0xa9932fa0,0xaf462d27,0x2cb02875,0xab5eaddc,0x2ff4ac32,0x2ff4a515,0x2d27afff,
0x9fd92fd4,0xa44ead96,0xae5ea9f1,0xaf3026a1,0x2e1faed0,0x2ff4addc,0xa8752fff,0x2e1fafe6,0xaffc29f1,0xa814ac87,0x2e5eae99,0xadfe9648,
0x2eb52814,0xaf5a2f30,0xb0002934,0xac5d2fed,0xa993ae3f,0x2c3228d5,0x2e7c28d5,0x2f46a875,0xa5152fd4,0xad723000,0x9cb6af5a,0xac322fd4,
0x2e3faee9,0x2e1f9fd9,0xad272f91,0x2f02a814,0xaffc28d5,0x2cd8aff4,0x2fedabb7,0x2b05afa0,0x2d962aaa,0xae992515,0xae99a765,0xaf5a2993,
0x1cb6adba,0x2cb0aeb5,0x2765aeb5,0xaddc2f6e,0xaff82d4d,0xa30ea814,0xafaf2c07,0xa17e2b05,0xa44e2e3f,0xadfe2b5e,0xa9342f1a,0x2cd8a875,
0x2fddacb0,0xb0002f80,0x2f6eaaaa,0x2fddaed0,0x2d001cb6,0x217e2765,0x217e2cb0,0x2bb7addc,0x2ee9afdd,0x2d4daa4e,0x2ffcadba,0xa44ea5db,
0xa9f1a934,0x2fd4aee9,0x26a1ae5e,0xad962b05,0xafc92f1a,0x2f46aff4,0xaf802bb7,0xafe62f1a,0xafdd2d4d,0xadba2c07,0xaa4ea814,0xa5db2b05,
0xaaaa2f1a,0xafc92f02,0xafe62f02,0x2993a17e,0x2e3fa765,0xafa02fff,0xa17e2d72,0x2e3facb0,0x2e5eb000,0xad4d2eb5,0x2f91ac5d,0x2fedaf5a,
0x2ee9aff8,0x2ffcafaf,0x2d4da30e,0xa44ea17e,0xa5dbaaaa,0x2f6eafe6,0x2f6eafc9,0xac5d2993,0xafe62dba,0x2d72ae99,0x9cb6ac5d,0xaed02dba,
0xabb72f30,0x28d5ac07,0xafa02cd8,0xaff42f91,0xa9342e3f,0xae5e2f1a,0xaee92b5e,0x2b05a875,0x2dbaa765,0xac5d2d72,0xae992fff,0x2dbaacb0,
0x2f80afd4,0xa7652a4e,0x25152a4e,0x2f46ae99,0x217eacd8,0x230e1fd9,0x2fafad4d,0x2ff8afbc,0xa9f1a44e,0x26a1a934,0x2fd4adfe,0xad962cd8,
0xafe62e3f,0x9cb6a17e,0x2d72afa0,0xaed02e3f,0xad272f80,0xa8752515,0xa875a765,0xafa02f46,0x293425db,0xac072a4e,0xafbc2dba,0xaffc2fdd,
0x2f1aacb0,0x2bb7aaaa,0xaff42f80,0x2f1aaed0,0x2f30b000,0x2cd8ac5d,0xac072eb5,0x2f91af5a,0x25dbacd8,0x2dbaad4d,0x2a4e1fd9,0x2fddafbc,
0xad722875,0x2e7cae1f,0x2fc9ae1f,0x2fffaff4,0xafc92fdd,0xaf802f6e,0x2f46b000,0xafe62fdd,0xabb72e5e,0xafa02f91,0x28d5ad4d,0xaff42fed,
0x2934217e,0xafbc2faf,0xac07230e,0xaffc2ff8,0x2f5aad72,0xafd42fc9,0xafd42e7c,0xb0002fff,0x9cb69648,0xacb0a6a1,0xa765a6a1,0x2ddc2a4e,
0xa17e9fd9,0xaff4aee9,0xa875a814,0x2ff82f91,0xa44ea30e,0xadfeafa0,0xa934a8d5,0x2cd82f02,0xa5dba515,0x9648aaaa,0xa9f1a993,0xa5db2765,
0xa30e9cb6,0xad27a765,0xad27acb0,0x2faf2ddc,0xa814a5db,0xaffcaf5a,0xadfead96,0x2e5e2fdd,0xaa4ea934,0xac5daee9,0xaeb5ae5e,0x96482b05,
0xac32ab5e,0x2993a30e,0xaf46af02,0xae7cab5e,0xa5db9fd9,0xad96a814,0xaf5aaee9,0x2fdd2f91,0xaaaaa8d5,0xafc9afaf,0xafe6afaf,0x29932e1f,
0xad00ac32,0xa8d5addc,0xaff8afff,0xad00a515,0xae5eadba,0x2d4d26a1,0xaf91afd4,0xafedaf6e,0xa814a17e,0xadfea875,0xaffcaff4,0x2e5e2ff8,
0xac87aaaa,0xaf5aafe6,0xaf5aafc9,0xa6a12993,0xae7cad96,0x9cb6ac87,0xaddcaeb5,0xafc9ad96,0xafafaf30,0x2f1a2c07,0xab5eacd8,0xad00af91,
0xa934a30e,0xae5ea8d5,0xaee9afa0,0x2b052f02,0xad96ac32,0xaeb5afff,0xac87addc,0xad96a515,0xaf80aeb5,0x2765a9f1,0xa515a9f1,0xaf46afdd,
0xaff8afed,0x2ff42dfe,0x28751fd9,0x217eac07,0xaa4ea44e,0xaeb5a934,0xac5dadfe,0x96482cd8,0xae7cad00,0xaddcaff8,0x9cb6a8d5,0xafc9ad00,
0xaff8af80,0x2bb7a515,0x2bb72765,0xab5eaf46,0xaf30afdd,0x2fbc2f5a,0x2ee92d96,0x2dfe25db,0xab5ea515,0xaf02a993,0xa30eaaaa,0xab5e2765,
0xaf30adba,0xacd8afd4,0x2c0726a1,0xaf91af6e,0xafddafed,0x2d961fd9,0x2f5a2dfe,0x25dbac07,0xad72af02,0x2e7c2ff8,0x2fc92ff8,0x2fff2e3f,
0xac32a5db,0xaf46a9f1,0x29939648,0xae7ca5db,0xafafae5e,0xab5eaf91,0x2f1a2d4d,0xad00afed,0xaf30aff8,0x2ee92875,0x2fbc2ff4,0x2dfe217e,
0xa9f1ad72,0x2c5d2fc9,0x2c5d2e7c,0x2d962fff,0xaf80aa4e,0xafc9ac87,0xafe6ac87,0x2f462dba,0xa8d5af30,0x2f02a44e,0xa30eae5e,0xafa09fd9,
0x2fbc2bb7,0xa9342e1f,0x2ffc2d27,0x2c07ad00,0x26a12ed0,0xaa4eafff,0x16482ddc,0x26a12fe6,0xafafaaaa,0xafa0acb0,0xafa0aed0,0x2d002f80,
0xa44eaeb5,0x2f919648,0x2b05aa4e,0xafbcac5d,0x30002d4d,0xac872cd8,0x2e992fbc,0x2f6e9fd9,0xa5152d27,0x9cb6afaf,0xad72230e,0xac322d27,
0xafd4ab05,0xaf6eacd8,0xadbaafed,0x26a12ffc,0x1cb6ae1f,0x2fe6230e,0x2ed0230e,0xad72af1a,0x2faf2e7c,0xae1f2aaa,0x28d52f80,0x2faf2c32,
0xac0729f1,0x2934ae99,0xaffcac87,0xafbc9648,0xafedab5e,0xaf30ad00,0xa934afaf,0xa8142f1a,0x26a1ad72,0x30002765,0x30002cb0,0xa5dbafff,
0x2ed02f5a,0xaf4626a1,0xa9932c87,0x2cb02f5a,0xae3f1fd9,0x2d27acd8,0xae1fafbc,0xaf02ad4d,0xaffcabb7,0xaee9ad27,0x244eae1f,0xad4d2d00,
0x29f1acb0,0x2fdd2993,0x2eb52f46,0x29f1aed0,0x2d722fdd,0xafe69648,0xaed09648,0x9cb62fd4,0xafa0a814,0x2f02a934,0xa30eaf30,0xa8d5afed,
0xb000ac07,0xae99ad4d,0x2c87ab05,0xaf6e2814,0x2c32abb7,0x2f802b5e,0x2aaa2ff8,0x2e7cabb7,0x2b5e2fff,0xaff4a765,0xaff4acb0,0xad272d72,
0xaffcac5d,0x2fed9648,0x2cd8aa4e,0x2b05aeb5,0xaff8ac32,0xae3fad72,0x2f029cb6,0xaff8a515,0x2d4da9f1,0x2ee92c87,0xa44e2e99,0x2ffc1648,
0x26a12fbc,0xaf6eab05,0xadbaaf91,0xafd4244e,0xaf46ae3f,0x2fc928d5,0x2fe628d5,0x2f80a875,0xafe6ac5d,0xaddcad96,0x2fff29f1,0xaed0ac5d,
0x2e3fa814,0x2e1f2d4d,0xad272b05,0x2f022c07,0x9fd92f1a,0xae5ead00,0xa44eafaf,0xaf30ab5e,0xad96af80,0x2e992cb0,0x2e992ed0,0x2f5a2aaa,
0xad72adba,0xa515aeb5,0xac32aeb5,0x9cb62f6e,0x2d272dfe,0xad002fbc,0x2bb72ee9,0x2e1faf30,0xacd8ae3f,0x2ffcab5e,0xab05af1a,0xafed2875,
0x2c872e7c,0xadbaa993,0x2a4e2f46,0x2c872c32,0xad00addc,0xa17eaed0,0xa17eafe6,0xabb72fff,0x2c072e99,0xadfe2f6e,0x9fd93000,0x2fedac87,
0xa9f1af30,0x2fd4a814,0x26a1afed,0xad96a934,0x27652fa0,0xaaaaad00,0xa9932faf,0xa5152fa0,0xac87adfe,0x9648aee9,0x29f1afbc,0xae992f30,
0x29932f1a,0xaed02f02,0xacb02f02,0x2f46a17e,0xa30eafc9,0x2f1a9cb6,0x2e1faddc,0xa30eae7c,0xa44e3000,0x9fd9aeb5,0xaf302c5d,0xae5e2f5a,
0xac07ae1f,0x1fd9af02,0x2dfeae3f,0xafed2d27,0x25db2f80,0xaf6e2e7c,0xaf6e2c32,0x2c5d2aaa,0x2515b000,0x2ddc25db,0x2fffa6a1,0x2c32b000,
0xabb72f91,0x28d5afbc,0xafa0a44e,0xaff42b05,0xab05ae3f,0x244eaf1a,0x2fbcab5e,0xaf912875,0x16482fc9,0xafd42ddc,0xafdd1cb6,0x16482e7c,
0x2aaaafd4,0x2c322a4e,0x2e7c2a4e,0x2f80ae99,0xae1f2e5e,0x2d00affc,0xabb7adfe,0xad27a814,0xa9f1ae5e,0x26a1af30,0x2fd49fd9,0xad96a44e,
0xa5152ff4,0xafff2d27,0xaddcab5e,0xac322ff4,0x2d27af46,0x28752cb0,0x28752ed0,0x2fa0a993,0xaf912c87,0x2ee9af6e,0x2814b000,0x1fd9ae99,
0xa8d5ae7c,0x2875af46,0x2e3f2993,0xa8d5ac32,0xa9343000,0xafed2c5d,0xa814aeb5,0xaf302f5a,0x2e99ae5e,0x16482dfe,0xa9f12ffc,0x2c872814,
0xafff2875,0x2fe6ae1f,0x2ed0ae1f,0x2ddcaff4,0xa765ae99,0x2993af5a,0x2aaa2d96,0x2515ae99,0xabb72fed,0xafa02b05,0x28d5affc,0xaff42cd8,
0x2f91ad27,0xa8142f02,0xaee92e3f,0x9fd92e1f,0xaf5a9cb6,0x2fd4ac32,0x2fd4a515,0x3000ad72,0x2aaaaf6e,0x2ed0afdd,0x2cb0afdd,0xaf803000,
0xaf1a2934,0x2875acd8,0xae3f244e,0xab5e2dfe,0xac072faf,0xab05217e,0xad4d2ff8,0x2814230e,0x2eb5a765,0xaf6e2ddc,0x2dba9cb6,0x2eb5acb0,
0x2bb7af80,0x2f1aafe6,0x2f1aafc9,0xaff42f46,0xae5e26a1,0x2b05ad96,0xa934a9f1,0xaee92fd4,0xadba2ffc,0xa5dba44e,0xafdd2ee9,0xaa4e2d4d,
0x2cb0217e,0xaddc2bb7,0x1cb62d00,0x2765217e,0x2c5daf91,0x2f5aafed,0x3000ae5e,0xaeb52d4d,0xad72217e,0x2cb0ae3f,0x2765ae3f,0xafff2fa0,
0xaf022fe6,0x217ea993,0xaf1a2aaa,0xaf022fc9,0x28142a4e,0xab0525db,0xad4d2fdd,0xac072dba,0x2cd8afa0,0x2f91aff4,0x2f30abb7,0xac0728d5,
0xac5d9cb6,0x2dbaaed0,0x2dbaafe6,0xae992d72,0xafc92f6e,0x2993ac5d,0xaaaaa5db,0xafe62f6e,0xa30e2d4d,0xa17ea44e,0xaff82ee9,0xafaf2ffc,
0x2d4dafaf,0x2fbcaff8,0x2cd8a17e,0x9fd9a30e,0xaa4ea515,0x2e99af46,0x2fd4af80,0xaa4e2765,0xafff2e99,0x2cb0adba,0x2765adba,0xad722c5d,
0xab5e2ee9,0x2875ab05,0xae3f2934,0xaf1a2e5e,0x2dbaafbc,0x2fddaffc,0x25db2934,0x2a4eac07,0xa765a875,0x2f46afa0,0x2f80ad27,0x2515a875,
0xafa02d72,0x2e3faed0,0x2e3fafe6,0xa17e9cb6,0xadfe2fd4,0x2cd8ad96,0xa44ea9f1,0xa93426a1,0x2e1fafc9,0x2ff4afff,0xa8752d72,0x2e1fae7c,
0x9fd9aa4e,0x2fbcafdd,0x2cd8a5db,0x2d4dadba,0xaeb52c07,0x2f5aaf91,0x3000af30,0x2c5dacd8,0xaf802ff4,0x2ed0af1a,0x2cb0af1a,0x2aaaabb7,
0x2e7cafd4,0x2fffb000,0xad722f5a,0x2fc9afd4,0x230eac07,0x2ff8affc,0x217e2934,0x2fafafbc,0xad4d28d5,0x2fedaff4,0x2e5eabb7,0x2f91afa0,
0xb0002f46,0x2fddafe6,0x2fddafc9,0x2f6eaf80,0xaaaaaa4e,0xaed0ac87,0xacb0ac87,0x2f802dba,0xab5eab05,0xafafafed,0xad00acd8,0x2f1a2ffc,
0xac07abb7,0xab05ae1f,0xad4dad27,0x28142d00,0xac5dac32,0x29f19cb6,0xad96ad72,0xac5da515,0xafafaf80,0xafa0afe6,0xafa0afc9,0x2d002f46,
0xafedafd4,0xa934adba,0xaf30af6e,0xa81426a1,0xb000affc,0x2c87244e,0xae99aee9,0xaf6ead4d,0xafe6aff8,0x2fff2f02,0xaddcae3f,0xaed0aff8,
0xaeb5af30,0xaa4eae5e,0x9648a44e,0xac5d9fd9,0xad72ae1f,0x2cb0230e,0x2765230e,0xafffaf1a,0xabb7acb0,0x2ff82f46,0x2b5e2993,0xabb7aed0,
0xa814a9f1,0x2b052e99,0x2d4d2c87,0x2c071648,0xa44ea8d5,0x2b05a30e,0x2f912f02,0xafbcafa0,0x26a11cb6,0x30002ed0,0x30002fe6,0xa5dbad72,
0x2c3229f1,0x2aaa2eb5,0x2f802fdd,0x2e7c29f1,0x2e3f2d4d,0xad27a44e,0x2e1f2ee9,0x2f022ffc,0x2d4d2bb7,0x2fbc2d27,0x2cd82e1f,0x9fd9ad00,
0x2f5a2e7c,0x2c872f80,0x26a12aaa,0x2f5a2c32,0x2fff2fdd,0xacb09648,0xa7659648,0x2d722fd4,0x2f1a2fbc,0xafafaf91,0xad00ab05,0xab5e244e,
0x30002fbc,0x2e992ffc,0xac87a934,0x2f6e2c07,0x2ed02faf,0xa99328d5,0xaf46ae1f,0x2cb02faf,0x2b5e2d72,0xaff4aed0,0xaff4afe6,0xad279cb6,
0x9fd926a1,0xa44eadba,0xae5eaf6e,0xaf30afd4,0x2d272ed0,0x230e2ddc,0xafafafff,0x2d272fe6,0x1fd929f1,0xafbcac87,0xacd8ae99,0xad4d9648,
0xac5da814,0xaa4eaf30,0x9648a934,0xaeb5afed,0xaf80ae3f,0x2ed028d5,0x2cb028d5,0x2aaaa875,0xa51526a1,0xad721648,0x9cb6aa4e,0xac3226a1,
0xae3fac07,0xae1faffc,0x2d272934,0xaf02afbc,0xaffcafa0,0x2cd8a30e,0x2fed2f02,0x2b05a8d5,0xad96af46,0x2e992fe6,0x2e992fc9,0x2f5a2f80,
0xafffadba,0xae7caeb5,0xafc9aeb5,0x2d722f6e,0x217ead4d,0x2ff42814,0x2875ac07,0xaff8ab05,0x2fed2e3f,0xad4d2b5e,0x2f912f1a,0x2e5ea875,
0xa5db2cb0,0x9648af80,0xa9f12aaa,0xa5db2ed0,0xad00afff,0xa17eafc9,0xa17eae7c,0xabb72d72,0x2ee925db,0x2d4d2f5a,0x2ffc2d96,0xa44eafdd,
0x29f12f91,0xafd4ac07,0xa6a12cd8,0x2d962f30,0xafc9ab5e,0x2f46a30e,0xaf80af02,0xafe6ab5e,0x25dbad4d,0x2d96ac07,0x2f5a2814,0xafddab05,
0x2f462f1a,0xa7652f02,0x25152f02,0x2f80a17e,0xad002765,0xa8d5afff,0xaff8ad72,0xad002cb0,0xacd8b000,0x2dfe2eb5,0x2934ac5d,0x244eaf5a,
0x2ee9217e,0x2ffc2875,0x2d4d2ff4,0xa44eaff8,0x25db2f46,0xaf6e2515,0xaf6ea765,0x2c5d2f80,0xafe6ad96,0x2d72ac87,0x9cb6aeb5,0xaed0ad96,
0x2bb7ab05,0xa8d52ee9,0x2fa02e5e,0x2ff42934,0x2f912e3f,0x2cd82f1a,0xac072b5e,0x2f30a875,0xad962765,0xaeb5ad72,0xac87afff,0xad962cb0,
0xa993afd4,0x2fc92a4e,0x2fe62a4e,0x2aaaae99,0x2ff82cd8,0xaff49fd9,0xa8752d4d,0xa17e2fbc,0x29f12fed,0xa6a12f91,0xafd4ad4d,0x2d962e5e,
0xafe6ad00,0x9cb6aff8,0x2d72a8d5,0xaed0ad00,0x2d27a993,0x28752fe6,0x28752fc9,0x2fa02aaa,0x29342fdd,0xac07af5a,0xafbcad96,0xaffca5db,
0xab5e2cb0,0xaf022aaa,0xa30eaf80,0xab5e2ed0,0xab05b000,0x2e5eac5d,0x2ee92eb5,0x2934af5a,0x2fdd2cd8,0xad962d4d,0xaf5a9fd9,0xa5db2fbc,
0xaddc2875,0x2cb0ae1f,0x2765ae1f,0x1cb6aff4,0xafc9a5db,0xaf80a9f1,0x2f469648,0xafe6a5db,0x2bb7acd8,0x2fa02934,0xa8d52dfe,0x2ff4244e,
0x29342ff8,0xafbca875,0xac07aff4,0xaffca17e,0xaf5aaddc,0x2fd42765,0x2fd42cb0,0x30001cb6,0xa993af6e,0x2765afdd,0xa515afdd,0xaaaa3000,
0x28d52f91,0xaf022e5e,0x230e2fed,0x2fa0ad4d,0xa814afaf,0x2f91a17e,0x9fd9aff8,0xaee9a30e,0x26a12fc9,0xaa4ead72,0x16482fff,0x26a12e7c,
0x2bb7af46,0x2f1aae7c,0x2f1aac32,0xaff42993,0xacd82eb5,0xaf301648,0xaf912a4e,0x2c072c5d,0x2dbaadfe,0x25db2e5e,0x2fdda814,0x2a4eaffc,
0xae7c2d27,0x2d72afaf,0xafff230e,0xafc92d27,0x2fd4a934,0x2f6ea44e,0x2dba2cd8,0xa6a1adfe,0xafff217e,0xa515ae3f,0xac32ae3f,0xaddc2fa0,
0x2faf2515,0xae1f2f80,0x28d52f46,0x2fafa765,0xaee9aa4e,0x2f91a5db,0x9fd9afdd,0xa814adba,0x2e5e2b5e,0x29342d00,0xab052faf,0x2ee9af1a,
0xac5daddc,0x2dbaafc9,0x2dbaae7c,0xae999cb6,0x27652f5a,0xaf8026a1,0xaf462c87,0xa5152f5a,0x230eaffc,0x217e2e5e,0x2ff8a814,0x2fafadfe,
0x1fd92faf,0xac072ff8,0xafed217e,0x2dfe230e,0x29f1afe6,0x2fddaaaa,0x2eb52993,0x29f1afc9,0xaddc2e99,0xa515adba,0xac32adba,0xafff2c5d,
0x2fa0ac07,0xaf022f30,0x230e2f91,0x28d52cd8,0xadba2ee9,0xafdd2dfe,0xa5dbaf30,0xaa4e2fbc,0x2fc9abb7,0x2aaa2b5e,0xa9932ff8,0x2fe6abb7,
0xafa09cb6,0x2e3fafc9,0x2e3fae7c,0xa17eaddc,0x2d4d2c5d,0xae5e1648,0xafed2a4e,0xaf912eb5,0xaff82765,0xae3f1cb6,0x2f02addc,0xaff82cb0,
0x2dfe2a4e,0xac072fdd,0xafed25db,0x1fd92dba,0xa6a1aee9,0x2f6ea934,0x2dba2b05,0x2fd4ae5e,0xaaaa2ff4,0x2765af1a,0xa515af1a,0xa993abb7,
0xacb0ac5d,0x9cb6ad96,0x2ddc29f1,0xa765ac5d,0xa30e2fbc,0xaff82dfe,0xa17eaf30,0xafaf2ee9,0x2dfeaf1a,0x244e2d00,0xacd82faf,0x29342b5e,
0xb0002993,0x2fddae7c,0x2fddac32,0x2f6eaf46,0x2ddcb000,0x2fe6afd4,0x2ed0afd4,0xafff2f5a,0xad279fd9,0x2d00aee9,0xabb7a814,0xae1f2f91,
0xae5e2ff4,0x9fd9a8d5,0xaf302fa0,0xa44e2bb7,0x2c872515,0xadba2aaa,0x2a4e2993,0x2c87a765,0x2ff4ad72,0x2e1fac32,0x2e1fa515,0xa8759cb6,
0x2814ae99,0x2ffcaf6e,0x2dfeb000,0xae5e2c87,0xaf5a2b05,0x2eb5afbc,0xac5da44e,0xb0002f91,0xac322fa0,0x2993ad00,0xaf462faf,0xae7c2fa0,
0x2c871fd9,0x16482814,0xa9f12ee9,0x2e99af91,0x2f80afa0,0x2c32a875,0x2e7ca875,0x2aaaad27,0xa30eac32,0x2f1aaddc,0x2e1fafff,0xa30ea515,
0xafed2d96,0x2ffcafd4,0xab05a6a1,0xacd829f1,0xa8142e1f,0xadfe2f02,0xaffc2e3f,0x2e5ead27,0x2e99a993,0xaa4e2cb0,0xaa4e2ed0,0x2fd4af46,
0x2e7cb000,0x1cb625db,0x2ddca6a1,0x2fc9b000,0xa875a934,0x2b5ea814,0x2f1aafed,0x2e3faf30,0xaf302ff4,0xafed2fa0,0xa814a8d5,0xa9342bb7,
0x16482c32,0xafd42fff,0xafdd2ddc,0x16482515,0x2f46ac5d,0xaed02f6e,0xacb02f6e,0x2993a5db,0x2e1fafed,0xad002dfe,0x2bb71fd9,0x2d27ac07,
0xaf5a2cd8,0xac5d2b05,0x2eb5affc,0xb0002fed,0xae7c2ff4,0xaddc2d27,0x9cb6ab5e,0xafc92ff4,0x217e2aaa,0xaf022e7c,0xaf022c32,0xaf1a2f80,
0x2f30ac87,0xafbc2f6e,0xaee93000,0xadfe2e99,0xa8d5a515,0x2875a993,0x2e3faaaa,0xa8d52765,0xaf912d96,0x244ea6a1,0x2fbcafd4,0xab0529f1,
0xae992fed,0x96489fd9,0x29f1adfe,0xac872c07,0x9cb62bb7,0xa515217e,0xac32217e,0xad722d00,0x2c32ae99,0x2f46af5a,0xa9932d96,0x2e7cae99,
0xa875a44e,0x2f1aaf30,0x2b5e9fd9,0x2e3fae5e,0xaf302d27,0x2ee9af02,0x2fbcae3f,0x2dfeae1f,0xaf6e2fff,0x2eb5aed0,0x2eb5afe6,0x2dbaaddc,
0xaddcadba,0xafe6aeb5,0xaed0aeb5,0x2fff2f6e,0xae1fadfe,0xae3fafbc,0xaf02aee9,0x2d272f30,0xae5eae3f,0x9fd9ab5e,0xaf30af1a,0xa44e2875,
0xae99ae7c,0x2d962993,0xaf5aaf46,0xae99ac32,0xad00ad72,0xa17eac32,0xa17ea515,0xabb79cb6,0xac07ac87,0x2dfe29f1,0x1fd99648,0xafedae99,
0xa9f1ab05,0x2fd42fbc,0x26a1244e,0xad96af91,0xa765a8d5,0x2aaa2e3f,0x29932875,0x2515a8d5,0x2e992dfe,0x30002ee9,0x2f6e2fbc,0xac87af30,
0x2f802f1a,0x2c322f02,0x2e7c2f02,0x2aaaa17e,0x2ff42fc9,0xab5e1cb6,0x2d272ddc,0x2ff42e7c,0x2fed3000,0xaffcaeb5,0x2b052c5d,0x2cd82f5a,
0x2c072d27,0x9fd92bb7,0xadfead00,0x2fed2e1f,0x25db2993,0xaf6eacb0,0xaf6eaed0,0x2c5d2f46,0xa5151648,0xaddcafdd,0xafffafd4,0xac321648,
0xabb7a934,0x28d5a814,0xafa0afed,0xaff4af30,0xaf30ae3f,0xafedaf1a,0xa814ab5e,0xa9342875,0xb000afc9,0xa6a1addc,0x25db9cb6,0xb000ae7c,
0xaf46afd4,0x2ed02a4e,0x2cb02a4e,0xa993ae99,0xad27ae5e,0x2e3f2ffc,0x2f022dfe,0x2e1f2814,0xa9f1acd8,0x26a1ab05,0x2fd42ffc,0xad96afed,
0x2515a30e,0x2fff2e1f,0x2ddc2f1a,0x2c32a30e,0x2d272aaa,0x28752e7c,0x28752c32,0x2fa02f80,0x2f912e99,0xaee9a9f1,0xa8141648,0x9fd92c87,
0x2fa02e7c,0x2faf2f46,0xad00a993,0x2fa02c32,0x2f913000,0xa44e2c5d,0xafbcaeb5,0x2b052f5a,0x2c872e5e,0xb000adfe,0xaf6eaffc,0xae99a814,
0x9cb62875,0xa515ae1f,0xac32ae1f,0xad72aff4,0x27652c87,0xa9932a4e,0xaaaaadba,0xa5152c87,0xabb7a44e,0xafa0af30,0x28d59fd9,0xaff4ae5e,
0xaf91ae1f,0x2814abb7,0x2ee92d00,0x1fd9ad27,0xaf5aafff,0x2fd42ed0,0x2fd42fe6,0x30002ddc,0xaf46af6e,0xac32afdd,0xae7cafdd,0x29933000,
0x2b5ea934,0x2faf2cd8,0x2d00a44e,0xaf1aadfe,0x2ee92faf,0xaf30217e,0x2dfe2ff8,0x2fbc230e,0xac5d2765,0x29f1addc,0xad961cb6,0xac5d2cb0,
0x2bb7a993,0x2f1aa515,0x2f1a2765,0xaff4aaaa,0x2e5e2fd4,0xab052dba,0x29342f6e,0x2ee9a6a1,0xadba1fd9,0xa5dbafed,0xafddac07,0xaa4e2dfe,
0xacb0aff8,0x2ddc2f02,0x9cb6ae3f,0xa765aff8,0x2eb52f91,0x2a4e2fed,0x16482e5e,0x2c5dad4d,0xaddc217e,0xae7cae3f,0xafc9ae3f,0x9cb62fa0,
0xabb7afe6,0x2ff82993,0x2b5eaaaa,0xabb7afc9,0x2fbc2a4e,0xaf3025db,0x2dfe2fdd,0x2ee92dba,0xacd828d5,0xaf91230e,0xaf30af02,0x2c072fa0,
0xac5dafff,0x2dbaac32,0x2dbaa515,0xae99addc,0x2fc929f1,0xa9932eb5,0x2aaa2fdd,0x2fe629f1,0xa30e2dfe,0xa17eafed,0xaff8ac07,0xafaf1fd9,
0xadfeafaf,0xa814aff8,0x2e5ea17e,0xaffca30e,0x2f5a2515,0x2c872f46,0x26a12f80,0x2f5aa765,0x9cb62e99,0xae7cadba,0xafc9adba,0xaddc2c5d,
0xaf1aaee9,0x2faf2b05,0x2d00a934,0x2b5eae5e,0x2dbaa814,0x2fdd9fd9,0x25db2f91,0x2a4eaee9,0x27652faf,0xaf4628d5,0xaf80ae1f,0xa5152faf,
0xafa0addc,0x2e3fac32,0x2e3fa515,0xa17eafff,0x2dfea6a1,0xacd82dba,0x244e2f6e,0x29342fd4,0x2d272fc9,0x230e2fff,0xafafad72,0x2d272e7c,
0xaffcaa4e,0xa814afdd,0x2e5ea5db,0xadfeadba,0x2c5dac07,0x2a4e2f91,0x16482f30,0x2eb52cd8,0x29932ff4,0xac32af1a,0xae7caf1a,0xaf46abb7,
0xae7c26a1,0xafff1648,0x2d72aa4e,0xafc926a1,0x230eaee9,0x2ff89fd9,0x217e2f91,0x2fafa814,0x2d4d2fa0,0xafed230e,0xae5eaf02,0xaf9128d5,
0xb000aaaa,0x2fdda515,0x2fdd2765,0x2f6ea993,0x1cb6b000,0x2cb0afd4,0x2765afd4,0xaddc2f5a,0xa17e2ffc,0xaff42c07,0xa8752fbc,0x2ff8a934,
0x244eaff4,0x2dfe28d5,0x2934afa0,0xacd8abb7,0xa5db2fe6,0x9648af46,0xa9f12f80,0xa5db2fc9,0x2ff41cb6,0x2e1f2765,0x2e1f2cb0,0xa875addc,
0xafbca5db,0x1fd9af5a,0xad4dad96,0xacd82fdd,0x2f5a2934,0xaeb52ee9,0x2c5d2e5e,0x3000ab05,0xaed0ab5e,0x2f80a30e,0xaaaaaf02,0xacb0ab5e,
0xa5db2ffc,0xad962fbc,0xaf5a2c07,0x2fdda934,0x2aaaafa0,0x2fc9a875,0x2fe6a875,0xa993ad27,0xad002ed0,0xa8d5ad72,0xaff81cb6,0xad002fe6,
0x2e5ead96,0xad4d2fd4,0x2f9126a1,0x2feda9f1,0xafbca17e,0xad4da875,0x1fd9aff4,0xacd82ff8,0x2e992aaa,0xaa4e2fe6,0xaa4e2fc9,0x2fd4a993,
0xacb0ad96,0x2fffac87,0x2d72aeb5,0xa765ad96,0x28752f30,0xab5eac07,0xaf1a2cd8,0xae3f2f91,0x2934aff4,0x2e5eafa0,0x2ee928d5,0xab05abb7,
0xad962ed0,0xaeb51cb6,0xac87ad72,0xad962fe6,0x2f80ac5d,0xa7652f6e,0x25152f6e,0x2f46a5db,0xaff8244e,0x2ff4ad4d,0x2875affc,0x217eaee9,
0x2f5a244e,0x2c5d2934,0xaeb52dfe,0x3000acd8,0xacb0ad00,0x2d72aff8,0x2fffa8d5,0xa765ad00,0x217e2f80,0xaf022515,0xaf02a765,0xaf1a2f46,
0x2b05afdd,0xa8142f5a,0x2c072d96,0x2d4d25db,0xab5e2fe6,0xaf022f80,0xa30eaf46,0xab5e2fc9,0x2f30ad96,0x2cd826a1,0xac072fd4,0x2f91a9f1,
0xafdd244e,0x2d96affc,0x2f5aad4d,0x25dbaee9,0x2d722bb7,0xae7c217e,0xafc9217e,0xafff2d00,0xaed0a5db,0xaaaaa9f1,0x2f809648,0xacb0a5db,
0x28752e5e,0xaf1a2f91,0xab5ead4d,0xae3f2fed,0x2b05aff8,0x2c072875,0xa8142ff4,0x2d4d217e,0xaf6e2d72,0x2eb5afc9,0x2eb5ae7c,0x2dbaafff,
0x2f80af5a,0x2fc9ae99,0x2fe6ae99,0xaf462d96,0xa8d5ab05,0x2f02afed,0xa30eacd8,0xafa02ffc,0xafbc2f02,0x2934ad27,0xaffc2e1f,0xac072e3f,
0x26a12c32,0xaa4e1cb6,0x16482d72,0x26a12515,0x28752aaa,0xa8d52cb0,0xa8d52ed0,0x2e3faf80,0x2fedaeb5,0x29349648,0x2f30aa4e,0x2814ac5d,
0x1648ad4d,0x2e99acd8,0x2c87afbc,0xa9f11fd9,0xafe62d27,0x2fffafaf,0xaddc230e,0xaed02d27,0xafd42f30,0xaf6e2e5e,0xadba244e,0x26a11fd9,
0x9cb62d27,0xafe62ff4,0xaed02ff4,0x2d72ab5e,0x2fafacb0,0xae1f2f46,0x28d52993,0x2fafaed0,0x2c07af6e,0xa9342c87,0x2ffcae99,0x2fbcb000,
0xa44eab5e,0x2b05ad00,0x2f91afaf,0xafbc2f1a,0xafd42d72,0x1648a765,0x1648acb0,0xafdd2fff,0xac322f5a,0xaaaa26a1,0xaf802c87,0xae7c2f5a,
0x2d009fd9,0xae1f2cd8,0xad272fbc,0xabb72d4d,0x2ffcaf02,0x2ee9ae1f,0xa44e2d27,0x2d4dae3f,0x29f1ae7c,0x2fddaf80,0x2eb5aaaa,0x29f1ac32,
0xad7225db,0x2fe6b000,0x2ed0b000,0x1cb6a6a1,0xafa02fbc,0x2f02af91,0xa30eab05,0xa8d5244e,0x96482c07,0xac872d4d,0xae992b05,0x29f1a814,
0x2ed0abb7,0xa9932b5e,0xaf462ff8,0x2cb0abb7,0x2f1aafff,0xa30e2765,0xa30e2cb0,0x2e1fad72,0x1fd9ac5d,0x244e9648,0x2e5eaa4e,0x2f30aeb5,
0xaff82ed0,0xae3f2ddc,0x2f02afff,0xaff82fe6,0xad4d2f6e,0xaee92e99,0x244eac87,0xaffc3000,0x26a12814,0xaf6e2f30,0xadba2934,0xafd42fed,
0x2f46ad00,0xafc92fa0,0xafe62fa0,0xaf802faf,0x2515ac5d,0x2d72ad96,0x1cb629f1,0x2c32ac5d,0xad002814,0x2d27ad4d,0x2e1fab05,0x2bb7ac07,
0xaffc2f1a,0x2cd8ad00,0x2fedafaf,0x2b05ab5e,0xadba2f80,0x2c87acb0,0x2c87aed0,0x2a4eaaaa,0xaf80af6e,0xafc9afdd,0xafe6afdd,0x2f463000,
0xafa0af91,0xabb7ae5e,0xaff4afed,0x28d52d4d,0xafbcafaf,0x2934a17e,0xaffcaff8,0xac07a30e,0xafd4afc9,0x2f5a2d72,0xb000afff,0xafd4ae7c,
0x2bb72aaa,0x2f1a2cb0,0x2f1a2ed0,0xaff4af80,0x2cd82c5d,0x2f303000,0x2f912f5a,0xac07aeb5,0x2dba2d4d,0x25db2cd8,0x2fdd2fbc,0x2a4e9fd9,
0x2e7c2e1f,0xad72a875,0x2fff2ff4,0x2fc92e1f,0x26a12934,0xa9f1244e,0xad96acd8,0x2fd42dfe,0x9cb6217e,0xafe6ae3f,0xaed0ae3f,0x2d722fa0,
0xa875a515,0xad27af80,0xafa0af46,0xa8752765,0xac07aa4e,0x2934a5db,0xaffcafdd,0xafbcadba,0xae5eaf1a,0xa934ae3f,0x2b052875,0xaee9ab5e,
0xac5dad72,0x2dba2765,0x2dba2cb0,0xae99afff,0xa765aa4e,0x2f802fd4,0x2f462e99,0x2515aa4e,0x230e9fd9,0x217e2cd8,0x2ff82fbc,0x2faf2d4d,
0x2ffc2faf,0x2ee92ff8,0xa44e217e,0x2d4d230e,0x2f6e2fe6,0xa5db2aaa,0xac5da993,0x2f6e2fc9,0x2d722e99,0xafe6adba,0xaed0adba,0x9cb62c5d,
0x28d52c07,0xabb7af30,0xaff4af91,0xafa0acd8,0xadbaac07,0xafddad4d,0xa5dbab05,0xaa4e2814,0xafc9af02,0xaaaaaf1a,0x2993217e,0xafe6af02,
0xafa0afff,0x2e3f2765,0x2e3f2cb0,0xa17ead72,0xad4daeb5,0x2e5e3000,0x2fed2f5a,0x2f912c5d,0x217ea765,0x2d009cb6,0x2bb72ddc,0x217eacb0,
0x2d4d2a4e,0x2ee92fdd,0xa44e25db,0x2ffc2dba,0x2fd42ee9,0xa9f12934,0xad96ab05,0x26a12e5e,0x2f462ff4,0xafc9af1a,0xafe6af1a,0xaf80abb7,
0x2cb02eb5,0x1cb62dba,0xaddcaf6e,0x27652eb5,0xa30e2814,0xaff8ad4d,0xa17eab05,0xafafac07,0xadfeab5e,0xa44eae3f,0x2cd82875,0xa934af1a,
0xb000af80,0x2fdd2cb0,0x2fdd2ed0,0x2f6e2aaa,0xad72b000,0xa515afd4,0xac32afd4,0x9cb62f5a,0x2e1f1fd9,0x2e3f2ee9,0x2f022814,0xad27af91,
0x2cd82ff4,0xaffca8d5,0x2b052fa0,0x2fed2bb7,0xae99a515,0x2d96aaaa,0xaf5aa993,0xae992765,0x2ff42ddc,0x2e1f2ed0,0x2e1f2fe6,0xa875afff,
0xa8142c87,0xaffca9f1,0xadfe1648,0x2e5e2e99,0xaf5aaf30,0x2eb5a814,0xac5dafed,0xb000a934,0x2c32a8d5,0xa9932e3f,0x2f462875,0x2e7ca8d5,
0xae999fd9,0xb000a814,0xaf6eaee9,0x2c872f91,0xa993afa0,0x2ed0a875,0x2cb0a875,0xaf46ad27,0x2ff42c32,0xab5e2ddc,0x2d272fff,0x2ff42515,
0xa44e2d96,0x9fd9afd4,0xaf30a6a1,0xae5e29f1,0x2814ad27,0x2dfeabb7,0x2ffc2d00,0xae5eae1f,0x2e992f80,0xaa4e2e7c,0xaa4e2c32,0x2fd42aaa,
0xae7c1648,0x9cb6afdd,0xaddcafd4,0xafc91648,0xa875af91,0x2b5e2fbc,0x2f1a244e,0x2e3fab05,0x2b052ff4,0xa44e2fa0,0xafbca8d5,0x2f912bb7,
0xb000ac32,0xa6a1afff,0x25dbaddc,0xb000a515,0x2aaaac5d,0x2c322f6e,0x2e7c2f6e,0x2f80a5db,0x2d272fed,0xae3fadfe,0xaf029fd9,0xae1f2c07,
0xaf5aae5e,0xac5daf30,0x2eb59fd9,0xb000a44e,0x2e7ca30e,0x2ddc2e1f,0x1cb62f1a,0x2fc9a30e,0x217e2f46,0xaf02acb0,0xaf02aed0,0xaf1a2993,
0xaf30ae99,0x2fbc29f1,0x2ee99648,0x2dfeac87,0x2fa02515,0x2faf2993,0xad002aaa,0x2fa0a765,0xa9342d96,0xafeda6a1,0xa814afd4,0xaf3029f1,
0xac87afed,0x30001fd9,0x2f6e2dfe,0x2e99ac07,0x2fff2bb7,0xafe6217e,0xaed0217e,0xaddc2d00,0xac322c87,0xaf462a4e,0x2993adba,0xae7c2c87,
0xa875afed,0x2f1aab05,0x2b5e2ffc,0x2e3facd8,0x2f302e1f,0xaee92bb7,0xafbcad00,0xadfe2d27,0xaf6e9cb6,0x2eb5ac32,0x2eb5a515,0x2dbaad72,
0x2aaaaf5a,0x2ed0ae99,0x2cb0ae99,0xaf802d96,0xab5e2f30,0xafaf244e,0xad002e5e,0x2f1a1fd9,0x2c07af02,0x2b052d27,0x2d4dae1f,0xa814ae3f,
0xac5d2ed0,0x29f1afff,0xad962ddc,0xac5d2fe6,0x28752f80,0xa8d52fe6,0xa8d52fc9,0x2e3faf46,0xa44eafd4,0x2f91adba,0x2b05af6e,0xafbc26a1,
0x96482ffc,0xae99a44e,0xac872ee9,0x29f12d4d,0x2515aff8,0x1cb62f02,0x2d72ae3f,0x2c32aff8,0xaeb5ab05,0xaa4eacd8,0x9648afed,0xac5d2ffc,
0x2d722d27,0xacb02ff4,0xa7652ff4,0x2fffab5e,0xabb7ae7c,0x2ff8aaaa,0x2b5eaf80,0xabb7ac32,0x28142f6e,0xab05ac87,0xad4d2e99,0xac073000,
0x2feda8d5,0x2f30a30e,0x29342f02,0x2814afa0,0xafd49cb6,0x1648aed0,0x1648afe6,0xafdd2d72,0x2ed029f1,0xaf462eb5,0xa9932fdd,0x2cb029f1,
0xad00ad4d,0x2e1f244e,0x2d27aee9,0x2bb7affc,0xad4d2f02,0xafbc2e1f,0xacd8ad27,0x1fd92e3f,0x2f5aacb0,0x2c872993,0x26a12f46,0x2f5aaed0,
0xafff25db,0x2cb0b000,0x2765b000,0xad72a6a1,0x2f1a2814,0xafaf2934,0xad002f30,0xab5e2fed,0x1648afbc,0x2c87affc,0x2e992934,0xa9f1ac07,
0xac322faf,0xaf8028d5,0xaaaaae1f,0xae7c2faf,0x2f1aad72,0xa30e2ed0,0xa30e2fe6,0x2e1f1cb6,0xaffc26a1,0x2fedadba,0x2cd8af6e,0x2b05afd4,
0x2d272c32,0x230e2d72,0xafaf1cb6,0x2d272515,0x9fd9af6e,0x2fbcae99,0x2cd82c87,0x2d4db000,0xac5d2fbc,0xaa4eab05,0x9648af91,0xaeb5244e,
0x2f80ad00,0xaed02fa0,0xacb02fa0,0xaaaa2faf,0xafe626a1,0xaddc1648,0x2fffaa4e,0xaed026a1,0x2d002c07,0xad272ffc,0xae1fa934,0xabb72fbc,
0x1fd9afa0,0x2e5ea30e,0x244e2f02,0x2f30a8d5,0xadba2f46,0x2c87afe6,0x2c87afc9,0x2a4eaf80,0x2fffad96,0x2e7cac5d,0x2fc9ac5d,0xad7229f1,
0x217eadfe,0x2ff4afbc,0x2875aee9,0xaff82f30,0xafed2d00,0x2d4daf1a,0xaf912b5e,0xae5e2faf,0xa5db2e7c,0x9648a993,0xa9f12f46,0xa5db2c32,
0xae3f2fff,0xaff82fc9,0xaff82e7c,0x2f02ad72,0x2c0725db,0xadfe2f5a,0x9fd92d96,0x2fedafdd,0x2f6eaf91,0xa6a12c07,0x2fd4acd8,0x2dbaaf30,
0xa765ab5e,0x2aaaa30e,0x2993af02,0x2515ab5e,0x25dbadfe,0x2d96aee9,0x2f5aafbc,0xafdd2f30,0xaf462b5e,0x2765abb7,0xa515abb7,0xaf802ff8,
0xad002fc9,0xa8d51cb6,0xaff82ddc,0xad002e7c,0x2cd81648,0xadfe2c5d,0xa9342eb5,0xa44e2a4e,0x2c07217e,0x9fd92875,0xadfe2ff4,0x2fedaff8,
0x2fddaf46,0x29f1a515,0x29f12765,0x2eb5af80,0x2515ad96,0x2ddcac87,0x2fffaeb5,0x2c32ad96,0xaf022b05,0x2fa0aee9,0x28d5ae5e,0x230ea934,
0xaf912d00,0xacd82b5e,0x2c07af1a,0xaf302faf,0xad962fc9,0xaeb52ddc,0xac871cb6,0xad962e7c,0x299326a1,0xafc92f5a,0xafe62f5a,0xaaaa2c87,
0x2ff8ae5e,0xaff42ffc,0xa8752dfe,0xa17e2814,0x2f6eafed,0x2fd4af91,0xa6a12d4d,0x2dbaae5e,0x2515ad00,0x2fffaff8,0x2ddca8d5,0x2c32ad00,
0xae1f2993,0x2fafafe6,0x2fafafc9,0x28d5aaaa,0xaf912fdd,0x2ee9af5a,0x2814ad96,0x1fd9a5db,0xab5e2e7c,0xaf022f46,0xa30ea993,0xab5e2c32,
0x2b051648,0xae5e2eb5,0xaee92c5d,0xa9342a4e,0x2fddae5e,0xad962dfe,0xaf5a2ffc,0xa5db2814,0x2ddcafaf,0xacb02d27,0xa7652d27,0x9cb6230e,
0xa765a5db,0x2993a9f1,0x2aaa9648,0x2515a5db,0xaf022cd8,0x28d5a934,0x2fa0adfe,0x230ea44e,0xaf912ff8,0x2814a875,0x2ee9aff4,0x1fd9a17e,
0xaa4e2ddc,0x26a1a765,0x26a1acb0,0x16489cb6,0x9de49e49,0xae47aeb3,0x997f9a49,0xa9d8aaaf,0x9d1b9d7f,0xad70addc,0x97db98b6,0xa82da902,
0x9c529cb6,0xac99ad04,0x94b69648,0xa502a6ad,0x9b129bdb,0xab85ac2e,0x8e489248,0x9eada2ad,0xa46ba4b7,0xaf06af7f,0xa020a0b6,0xaa89ab78,
0xa3a9a420,0xae15ae8d,0x9de49f12,0xa8aaa999,0xa27ba312,0xad24ad9c,0x9b129cb6,0xa599a777,0xa14da1e4,0xac34acac,0x94b698b6,0x9f76a376,
0xa75da7db,0xafc5b025,0xa2dfa3db,0xab39ac21,0xa662a6e0,0xaebaaf3f,0xa0e9a1e4,0xa928aa31,0xa567a5e4,0xadafae34,0x9de49fdb,0xa630a820,
0xa46ba4e9,0xaca6ad2a,0x97db9bdb,0xa020a420,0xa928a980,0xb042b08c,0xa4d0a580,0xabeaac86,0xa878a8d0,0xaf5faff2,0xa2dfa420,0xa9a6aac8,
0xa790a820,0xae3baecd,0xa020a17f,0xa6c7a885,0xa630a6e0,0xad17ada9,0x997f9d7f,0xa084a484,0xaaa2ab13,0xb0a2b0f3,0xa630a712,0xac4daceb,
0xa9bfaa31,0xb002b052,0xa46ba54d,0xaa24ab5f,0xa8dda94e,0xaec6af65,0xa14da312,0xa75da8e9,0xa7f4a86b,0xad89ae28,0x9b129f12,0xa0e9a4e9,
0xac0eac54,0xb103b15a,0xa790a852,0xaca6ad50,0xab07ab91,0xb055b0ac,0xa567a67b,0xaaa2abf6,0xa9f2aa7c,0xaf52affe,0xa27ba452,0xa7f4a94e,
0xa8dda967,0xadfbaea7,0x9c52a052,0xa14da54d,0xacccad1e,0xb163b1c1,0xa878a91c,0xacfeadb6,0xac27ac79,0xb0a9b106,0xa662a7a9,0xab20ac47,
0xab07abab,0xafdeb04c,0xa3a9a51b,0xa846a9b3,0xa9bfaa63,0xae6daf26,0x9d1ba11b,0xa1b2a5b2,0xad89ade8,0xb1c5b229,0xa928a9e5,0xad57ae1b,
0xacccad2a,0xb0fcb160,0xa75da86b,0xab9eac93,0xac0eac6d,0xb035b099,0xa46ba5e4,0xa891aa17,0xaaa2ab5f,0xaee0afa5,0x9de4a1e4,0xa216a617,
0xb226b292,0xb4a2b4f6,0xadafae80,0xb03cb0d9,0xb150b1bb,0xb3fab44f,0xac0eacde,0xae08af3f,0xb07cb0e6,0xb2b6b357,0xa8ddaa7c,0xab39acd2,
0xaf52b012,0xb177b216,0xa27ba67b,0xa4d0a8d0,0xb288b2fb,0xb4d5b52d,0xae08aee6,0xb069b10c,0xb1a4b216,0xb428b47e,0xac4dad2a,0xae47af8c,
0xb0c2b133,0xb2feb3a7,0xa928aae1,0xab85ad04,0xafc5b052,0xb1b1b257,0xa2dfa6e0,0xa502a902,0xb2eab364,0xb509b565,0xae61af4c,0xb095b140,
0xb1f8b271,0xb454b4ae,0xac8cad76,0xae87afd8,0xb109b181,0xb347b3f7,0xa974ab46,0xabd1ad37,0xb01cb092,0xb1ebb298,0xa344a744,0xa534a935,
0xb34db3cf,0xb53db59d,0xaebaafb2,0xb0c2b174,0xb24db2cd,0xb480b4de,0xacccadc2,0xaec6b012,0xb150b1ce,0xb390b423,0xa9bfabab,0xac0ead6a,
0xb055b0d2,0xb226b2da,0xa3a9a7a9,0xa567a967,0xb3b1b41d,0xb571b5d6,0xaf13b00c,0xb0efb1a7,0xb2a2b329,0xb4acb50e,0xad0bae0e,0xaf06b039,
0xb197b21c,0xb3d9b44c,0xaa0bac08,0xac34ad9c,0xb08fb113,0xb261b31c,0xa407a807,0xa599a999,0xb40ab453,0xb5a6b60f,0xaf6cb03f,0xb11cb1db,
0xb2f8b386,0xb4d9b53f,0xad4aae5a,0xaf45b05f,0xb1deb26b,0xb411b474,0xaa56ac3a,0xac5aadcf,0xb0c9b153,0xb29cb35e,0xa439a839,0xa5cba9cc,
0xb43db489,0xb5dbb649,0xafc5b072,0xb14ab20f,0xb34db3e3,0xb506b570,0xad89aea7,0xaf85b085,0xb226b2b9,0xb436b49d,0xaaa2ac6d,0xac80ae02,
0xb103b194,0xb2d7b3a0,0xa46ba86b,0xa5fda9fe,0xb46fb4bf,0xb611b683,0xb00fb0a5,0xb177b243,0xb3a3b420,0xb533b5a1,0xadc9aef3,0xafc5b0ac,
0xb26eb308,0xb45bb4c6,0xaaeeac9f,0xaca6ae34,0xb13db1d5,0xb312b3e3,0xa49da89e,0xa630aa31,0xb647b6be,0xb806b857,0xb1a4b278,0xb312b40f,
0xb560b5d2,0xb6d6b76f,0xb002b0d2,0xb103b209,0xb480b4ef,0xb5b1b642,0xacccae67,0xadfbaffe,0xb34db413,0xb498b523,0xa662aa63,0xa7f4abf6,
0xb67eb6fa,0xb824b878,0xb1d2b2ac,0xb340b42a,0xb58db604,0xb707b7a5,0xb022b0f9,0xb123b230,0xb4a6b519,0xb5d8b66d,0xacf1ae9a,0xae21b019,
0xb389b434,0xb4b7b546,0xa694aa95,0xa813ac14,0xb6b5b736,0xb842b899,0xb1ffb2e1,0xb36eb445,0xb5bbb637,0xb738b7db,0xb042b120,0xb143b257,
0xb4cbb542,0xb5ffb699,0xad17aecd,0xae47b032,0xb3c5b456,0xb4d5b569,0xa6c7aac8,0xa82dac2e,0xb6edb773,0xb860b8bb,0xb22db315,0xb39db460,
0xb5eab66a,0xb769b809,0xb062b146,0xb163b27e,0xb4f1b56c,0xb627b6c6,0xad3daf00,0xae6db04c,0xb400b478,0xb4f4b58c,0xa6f9aafa,0xa846ac47,
0xb725b7b0,0xb87fb8dd,0xb25ab34a,0xb3cbb47b,0xb618b69d,0xb79bb825,0xb082b16d,0xb184b2a5,0xb517b596,0xb64eb6f2,0xad63af32,0xae93b065,
0xb41eb49a,0xb513b5af,0xa72bab2d,0xa85fac60,0xb75eb7ee,0xb89eb8ff,0xb288b37f,0xb3fab496,0xb647b6d1,0xb7cdb841,0xb0a2b194,0xb1a4b2cd,
0xb53db5c1,0xb676b71f,0xad89af65,0xaebab07f,0xb43db4bc,0xb533b5d2,0xa75dab5f,0xa878ac79,0xb797b817,0xb8beb923,0xb2b6b3b4,0xb414b4b1,
0xb676b705,0xb800b85d,0xb0c2b1bb,0xb1c5b2f4,0xb563b5eb,0xb69fb74d,0xadafaf98,0xaee0b099,0xb45bb4de,0xb552b5f6,0xa790ab91,0xa891ac93,
0xb7d1b837,0xb8deb946,0xb2e4b3e9,0xb42cb4cd,0xb6a6b73a,0xb81ab87a,0xb0e3b1e2,0xb1e5b31c,0xb58ab616,0xb6c7b77a,0xadd5afcb,0xaf06b0b2,
0xb479b500,0xb571b61a,0xa7c2abc4,0xa8aaacac,0xb8feb96b,0xba15baa6,0xb443b4e8,0xb502b5c8,0xb834b897,0xb90eb98d,0xb205b343,0xb30bb442,
0xb6f0b7a8,0xb822b895,0xaf2cb0cc,0xb02fb19a,0xb591b63e,0xb694b767,0xa8c4acc5,0xa98dad90,0xb91fb990,0xba3abad1,0xb45bb504,0xb51ab5e4,
0xb84eb8b4,0xb92ab9ae,0xb226b36b,0xb32cb456,0xb71ab7d7,0xb838b8ae,0xaf52b0e6,0xb042b1b4,0xb5b1b662,0xb6b5b78d,0xa8ddacde,0xa9a6ada9,
0xb941b9b5,0xba61bafd,0xb473b51f,0xb533b601,0xb868b8d2,0xb947b9cf,0xb247b393,0xb34db46a,0xb743b803,0xb84eb8c7,0xaf78b0ff,0xb055b1ce,
0xb5d1b687,0xb6d6b7b4,0xa8f6acf8,0xa9bfadc2,0xb963b9dc,0xba88bb29,0xb48ab53b,0xb54bb61e,0xb883b8f0,0xb965b9f1,0xb267b3bb,0xb36eb47e,
0xb76db81b,0xb864b8e1,0xaf9fb119,0xb069b1e8,0xb5f1b6ac,0xb6f8b7db,0xa90fad11,0xa9d8addc,0xb985ba02,0xbaafbb57,0xb4a2b557,0xb563b63a,
0xb89eb90f,0xb983ba14,0xb288b3e3,0xb390b493,0xb797b833,0xb87bb8fb,0xafc5b133,0xb07cb202,0xb611b6d1,0xb71ab801,0xa928ad2a,0xa9f2adf5,
0xb9a8ba2a,0xbad8bb86,0xb4bab573,0xb57cb657,0xb8b9b92e,0xb9a1ba37,0xb2a9b405,0xb3b1b4a7,0xb7c2b84b,0xb892b915,0xafebb14d,0xb08fb21c,
0xb631b6f6,0xb73bb815,0xa941ad44,0xaa0bae0e,0xb9ccba53,0xbb01bbb6,0xb4d2b58f,0xb594b675,0xb8d5b94d,0xb9c0ba5a,0xb2cab419,0xb3d2b4bc,
0xb7ecb863,0xb8a9b930,0xb009b167,0xb0a2b236,0xb652b71b,0xb75eb829,0xa95bad5d,0xaa24ae28,0xb9f0ba7c,0xbb2bbbe7,0xb4eab5ab,0xb5adb692,
0xb8f1b96d,0xb9dfba7e,0xb2eab42e,0xb3f3b4d0,0xb80cb87c,0xb8c0b94b,0xb01cb181,0xb0b6b250,0xb673b741,0xb780b83d,0xa974ad76,0xaa3dae41,
0xe480000,0x1ead0000,0x1b121a49,0x2b852aaf,0x14b61248,0x250222ad,0x1c521bdb,0x2c992c2e,0x17db1648,0x282d26ad,0x1d1b1cb6,0x2d702d04,
0x197f18b6,0x29d82902,0x1de41d7f,0x2e472ddc,0x14b60000,0x1f760000,0x214d20b6,0x2c342b78,0x1b1218b6,0x25992376,0x227b21e4,0x2d242cac,
0x1de41cb6,0x28aa2777,0x23a92312,0x2e152d9c,0x20201f12,0x2a892999,0x246b2420,0x2f062e8d,0x17db0000,0x20200000,0x246b23db,0x2ca62c21,
0x1de41bdb,0x26302420,0x256724e9,0x2daf2d2a,0x20e91fdb,0x29282820,0x266225e4,0x2eba2e34,0x22df21e4,0x2b392a31,0x275d26e0,0x2fc52f3f,
0x197f0000,0x20840000,0x26302580,0x2d172c86,0x20201d7f,0x26c72484,0x279026e0,0x2e3b2da9,0x22df217f,0x29a62885,0x28782820,0x2f5f2ecd,
0x24d02420,0x2bea2ac8,0x292828d0,0x30422ff2,0x1b120000,0x20e90000,0x27f42712,0x2d892ceb,0x214d1f12,0x275d24e9,0x28dd286b,0x2ec62e28,
0x246b2312,0x2a2428e9,0x29bf294e,0x30022f65,0x2630254d,0x2c4d2b5f,0x2aa22a31,0x30a23052,0x1c520000,0x214d0000,0x28dd2852,0x2dfb2d50,
0x227b2052,0x27f4254d,0x29f22967,0x2f522ea7,0x25672452,0x2aa2294e,0x2b072a7c,0x30552ffe,0x2790267b,0x2ca62bf6,0x2c0e2b91,0x310330ac,
0x1d1b0000,0x21b20000,0x29bf291c,0x2e6d2db6,0x23a9211b,0x284625b2,0x2b072a63,0x2fde2f26,0x2662251b,0x2b2029b3,0x2c272bab,0x30a9304c,
0x287827a9,0x2cfe2c47,0x2ccc2c79,0x31633106,0x1de40000,0x22160000,0x2aa229e5,0x2ee02e1b,0x246b21e4,0x28912617,0x2c0e2b5f,0x30352fa5,
0x275d25e4,0x2b9e2a17,0x2ccc2c6d,0x30fc3099,0x2928286b,0x2d572c93,0x2d892d2a,0x31c53160,0x227b0000,0x24d00000,0x2f522e80,0x317730d9,
0x28dd267b,0x2b3928d0,0x307c3012,0x32b63216,0x2c0e2a7c,0x2e082cd2,0x315030e6,0x33fa3357,0x2daf2cde,0x303c2f3f,0x322631bb,0x34a2344f,
0x22df0000,0x25020000,0x2fc52ee6,0x31b1310c,0x292826e0,0x2b852902,0x30c23052,0x32fe3257,0x2c4d2ae1,0x2e472d04,0x31a43133,0x342833a7,
0x2e082d2a,0x30692f8c,0x32883216,0x34d5347e,0x23440000,0x25340000,0x301c2f4c,0x31eb3140,0x29742744,0x2bd12935,0x31093092,0x33473298,
0x2c8c2b46,0x2e872d37,0x31f83181,0x345433f7,0x2e612d76,0x30952fd8,0x32ea3271,0x350934ae,0x23a90000,0x25670000,0x30552fb2,0x32263174,
0x29bf27a9,0x2c0e2967,0x315030d2,0x339032da,0x2ccc2bab,0x2ec62d6a,0x324d31ce,0x34803423,0x2eba2dc2,0x30c23012,0x334d32cd,0x353d34de,
0x24070000,0x25990000,0x308f300c,0x326131a7,0x2a0b2807,0x2c342999,0x31973113,0x33d9331c,0x2d0b2c08,0x2f062d9c,0x32a2321c,0x34ac344c,
0x2f132e0e,0x30ef3039,0x33b13329,0x3571350e,0x24390000,0x25cb0000,0x30c9303f,0x329c31db,0x2a562839,0x2c5a29cc,0x31de3153,0x3411335e,
0x2d4a2c3a,0x2f452dcf,0x32f8326b,0x34d93474,0x2f6c2e5a,0x311c305f,0x340a3386,0x35a6353f,0x246b0000,0x25fd0000,0x31033072,0x32d7320f,
0x2aa2286b,0x2c8029fe,0x32263194,0x343633a0,0x2d892c6d,0x2f852e02,0x334d32b9,0x3506349d,0x2fc52ea7,0x314a3085,0x343d33e3,0x35db3570,
0x249d0000,0x26300000,0x313d30a5,0x33123243,0x2aee289e,0x2ca62a31,0x326e31d5,0x345b33e3,0x2dc92c9f,0x2fc52e34,0x33a33308,0x353334c6,
0x300f2ef3,0x317730ac,0x346f3420,0x361135a1,0x26620000,0x27f40000,0x334d3278,0x3498340f,0x2ccc2a63,0x2dfb2bf6,0x34803413,0x35b13523,
0x30022e67,0x31032ffe,0x356034ef,0x36d63642,0x31a430d2,0x33123209,0x364735d2,0x3806376f,0x26940000,0x28130000,0x338932ac,0x34b7342a,
0x2cf12a95,0x2e212c14,0x34a63434,0x35d83546,0x30222e9a,0x31233019,0x358d3519,0x3707366d,0x31d230f9,0x33403230,0x367e3604,0x382437a5,
0x26c70000,0x282d0000,0x33c532e1,0x34d53445,0x2d172ac8,0x2e472c2e,0x34cb3456,0x35ff3569,0x30422ecd,0x31433032,0x35bb3542,0x37383699,
0x31ff3120,0x336e3257,0x36b53637,0x384237db,0x26f90000,0x28460000,0x34003315,0x34f43460,0x2d3d2afa,0x2e6d2c47,0x34f13478,0x3627358c,
0x30622f00,0x3163304c,0x35ea356c,0x376936c6,0x322d3146,0x339d327e,0x36ed366a,0x38603809,0x272b0000,0x285f0000,0x341e334a,0x3513347b,
0x2d632b2d,0x2e932c60,0x3517349a,0x364e35af,0x30822f32,0x31843065,0x36183596,0x379b36f2,0x325a316d,0x33cb32a5,0x3725369d,0x387f3825,
0x275d0000,0x28780000,0x343d337f,0x35333496,0x2d892b5f,0x2eba2c79,0x353d34bc,0x367635d2,0x30a22f65,0x31a4307f,0x364735c1,0x37cd371f,
0x32883194,0x33fa32cd,0x375e36d1,0x389e3841,0x27900000,0x28910000,0x345b33b4,0x355234b1,0x2daf2b91,0x2ee02c93,0x356334de,0x369f35f6,
0x30c22f98,0x31c53099,0x367635eb,0x3800374d,0x32b631bb,0x341432f4,0x37973705,0x38be385d,0x27c20000,0x28aa0000,0x347933e9,0x357134cd,
0x2dd52bc4,0x2f062cac,0x358a3500,0x36c7361a,0x30e32fcb,0x31e530b2,0x36a63616,0x381a377a,0x32e431e2,0x342c331c,0x37d1373a,0x38de387a,
0x28c40000,0x298d0000,0x359134e8,0x369435c8,0x2f2c2cc5,0x302f2d90,0x36f0363e,0x38223767,0x320530cc,0x330b319a,0x383437a8,0x390e3895,
0x34433343,0x35023442,0x38fe3897,0x3a15398d,0x28dd0000,0x29a60000,0x35b13504,0x36b535e4,0x2f522cde,0x30422da9,0x371a3662,0x3838378d,
0x322630e6,0x332c31b4,0x384e37d7,0x392a38ae,0x345b336b,0x351a3456,0x391f38b4,0x3a3a39ae,0x28f60000,0x29bf0000,0x35d1351f,0x36d63601,
0x2f782cf8,0x30552dc2,0x37433687,0x384e37b4,0x324730ff,0x334d31ce,0x38683803,0x394738c7,0x34733393,0x3533346a,0x394138d2,0x3a6139cf,
0x290f0000,0x29d80000,0x35f1353b,0x36f8361e,0x2f9f2d11,0x30692ddc,0x376d36ac,0x386437db,0x32673119,0x336e31e8,0x3883381b,0x396538e1,
0x348a33bb,0x354b347e,0x396338f0,0x3a8839f1,0x29280000,0x29f20000,0x36113557,0x371a363a,0x2fc52d2a,0x307c2df5,0x379736d1,0x387b3801,
0x32883133,0x33903202,0x389e3833,0x398338fb,0x34a233e3,0x35633493,0x3985390f,0x3aaf3a14,0x29410000,0x2a0b0000,0x36313573,0x373b3657,
0x2feb2d44,0x308f2e0e,0x37c236f6,0x38923815,0x32a9314d,0x33b1321c,0x38b9384b,0x39a13915,0x34ba3405,0x357c34a7,0x39a8392e,0x3ad83a37,
0x295b0000,0x2a240000,0x3652358f,0x375e3675,0x30092d5d,0x30a22e28,0x37ec371b,0x38a93829,0x32ca3167,0x33d23236,0x38d53863,0x39c03930,
0x34d23419,0x359434bc,0x39cc394d,0x3b013a5a,0x29740000,0x2a3d0000,0x367335ab,0x37803692,0x301c2d76,0x30b62e41,0x380c3741,0x38c0383d,
0x32ea3181,0x33f33250,0x38f1387c,0x39df394b,0x34ea342e,0x35ad34d0,0x39f0396d,0x3b2b3a7e,0xa1e4a248,0xb238b2a1,0x9d7f9e48,0xadd5aeaa,
0xa11ba17f,0xb166b1cf,0x9bdb9cb6,0xac2bad00,0xa052a0b6,0xb093b0fd,0x98b69a48,0xa901aaac,0x9f129fdb,0xaf7eb029,0x92489648,0xa2ada6ad,
0xa86ba8b6,0xb2f0b365,0xa420a4b6,0xae84af72,0xa7a8a81f,0xb207b27c,0xa1e4a311,0xaca9ad97,0xa67ba711,0xb11cb191,0x9f12a0b6,0xa998ab75,
0xa54da5e4,0xb02fb0a6,0x98b69cb6,0xa376a776,0xab5cabd9,0xb3a8b414,0xa6dfa7da,0xaf33b01d,0xaa61aade,0xb2a7b328,0xa4e9a5e4,0xad26ae2d,
0xa966a9e3,0xb1a4b226,0xa1e4a3db,0xaa2fac1f,0xa86ba8e8,0xb09fb122,0x9bdb9fdb,0xa420a81f,0xad26ad7e,0xb42fb475,0xa8cfa97f,0xafe2b080,
0xac77acce,0xb346b3d3,0xa6dfa81f,0xada3aec3,0xab8eac1f,0xb22cb2b9,0xa420a57f,0xaac5ac83,0xaa2faade,0xb10fb19e,0x9d7fa17f,0xa484a884,
0xae9daf0e,0xb48ab4d5,0xaa2fab11,0xb048b0e4,0xadbcae2d,0xb3e5b43e,0xa86ba94d,0xae20af59,0xacdbad4c,0xb2b3b34c,0xa54da711,0xab5cace7,
0xabf2ac6a,0xb17fb219,0x9f12a311,0xa4e9a8e8,0xb00ab04e,0xb4e4b534,0xab8eac51,0xb09fb147,0xaf01af8b,0xb441b493,0xa966aa7a,0xae9dafef,
0xadeeae78,0xb33ab3df,0xa67ba852,0xabf2ad4c,0xacdbad65,0xb1eeb294,0xa052a452,0xa54da94d,0xb0c5b115,0xb53db593,0xac77ad1a,0xb0f6b1aa,
0xb023b074,0xb490b4e7,0xaa61aba7,0xaf1ab042,0xaf01afa4,0xb3c0b438,0xa7a8a91b,0xac44adb0,0xadbcae5f,0xb25db30f,0xa11ba51b,0xa5b2a9b1,
0xb17fb1db,0xb596b5f1,0xad26ade2,0xb14db20d,0xb0c5b122,0xb4deb53a,0xab5cac6a,0xaf97b08d,0xb00ab067,0xb423b481,0xa86ba9e3,0xac90ae14,
0xae9daf59,0xb2ccb389,0xa1e4a5e4,0xa616aa16,0xb5eeb64e,0xb846b887,0xb1a4b26f,0xb429b4bd,0xb52cb58d,0xb783b805,0xb00ab0d7,0xb1fab328,
0xb466b4c9,0xb66db6f9,0xacdbae78,0xaf33b0cb,0xb33ab402,0xb54fb5df,0xa67baa7a,0xa8cfacce,0xb645b6aa,0xb86eb8b0,0xb1fab2d2,0xb454b4ed,
0xb579b5df,0xb7cab82a,0xb048b122,0xb238b371,0xb4a8b511,0xb6adb73d,0xad26aedc,0xaf7eb0fd,0xb3a8b43e,0xb584b61a,0xa6dfaade,0xa901ad00,
0xb69bb705,0xb895b8d8,0xb251b334,0xb47eb51d,0xb5c5b631,0xb809b850,0xb086b16c,0xb276b3ba,0xb4eab558,0xb6ebb780,0xad71af40,0xafc9b12e,
0xb40bb47b,0xb5b9b654,0xa744ab43,0xa934ad33,0xb6f1b75e,0xb8bbb900,0xb2a7b396,0xb4a8b54c,0xb611b682,0xb82cb874,0xb0c5b1b6,0xb2b3b402,
0xb52cb59f,0xb729b7c2,0xadbcafa4,0xb00ab160,0xb441b4b7,0xb5eeb68d,0xa7a8aba7,0xa966ad65,0xb745b7b7,0xb8e1b927,0xb2fdb3f7,0xb4d2b57c,
0xb65cb6d2,0xb84eb899,0xb103b201,0xb2f0b426,0xb56db5e5,0xb767b802,0xae07b004,0xb02fb191,0xb478b4f3,0xb622b6c6,0xa806ac06,0xa998ad97,
0xb799b807,0xb906b94d,0xb352b42c,0xb4fcb5ab,0xb6a7b721,0xb871b8bc,0xb141b24b,0xb32eb44b,0xb5aeb62b,0xb7a4b822,0xae52b036,0xb055b1c3,
0xb4aeb52f,0xb656b6ff,0xa839ac38,0xa9caadc9,0xb7ebb832,0xb92ab972,0xb3a8b45d,0xb526b5da,0xb6f1b76f,0xb892b8e0,0xb17fb294,0xb36bb46f,
0xb5eeb670,0xb7e0b842,0xae9db067,0xb07ab1f4,0xb4e4b56a,0xb68ab737,0xa86bac6a,0xa9fdadfb,0xb81eb85d,0xb94eb996,0xb3fdb48d,0xb54fb608,
0xb73ab7bd,0xb8b4b902,0xb1bdb2de,0xb3a8b493,0xb62eb6b5,0xb80eb862,0xaee8b099,0xb09fb226,0xb51ab5a5,0xb6beb76f,0xa89dac9c,0xaa2fae2d,
0xb971b9ba,0xba6cbab5,0xb579b637,0xb6beb7a1,0xb8d4b924,0xb9c8ba1d,0xb3e5b4b7,0xb4e4b5d4,0xb82cb881,0xb90db96d,0xb0c5b257,0xb1eeb3df,
0xb6f1b7a6,0xb83eb8a8,0xaa61ae5f,0xabf2afef,0xb993b9dc,0xba88bad0,0xb5a2b665,0xb6e5b7cd,0xb8f5b946,0xb9e4ba39,0xb411b4db,0xb502b5f7,
0xb849b8a0,0xb928b989,0xb0eab288,0xb213b408,0xb724b7dd,0xb856b8c1,0xaa93ae91,0xac12b010,0xb9b4b9fe,0xbaa2bae9,0xb5cbb693,0xb70db7f9,
0xb914b966,0xb9ffba54,0xb42fb4ff,0xb520b61a,0xb866b8bf,0xb942b9a4,0xb10fb2b9,0xb238b420,0xb756b80a,0xb86eb8db,0xaac5aec3,0xac2bb029,
0xb9d5ba1f,0xbabcbb02,0xb5f4b6c1,0xb734b812,0xb934b986,0xba1aba6f,0xb44eb523,0xb53db63c,0xb883b8dd,0xb95cb9be,0xb134b2ea,0xb25db438,
0xb788b825,0xb885b8f3,0xaaf8aef5,0xac44b042,0xb9f5ba3f,0xbad5bb1a,0xb61db6ee,0xb75cb828,0xb953b9a6,0xba34ba89,0xb46cb546,0xb55bb65f,
0xb89fb8fb,0xb975b9d8,0xb15ab31b,0xb282b451,0xb7bab840,0xb89db90c,0xab2aaf27,0xac5eb05b,0xba14ba5e,0xbaedbb30,0xb645b71b,0xb783b83d,
0xb971b9c5,0xba4ebaa2,0xb48ab56a,0xb579b682,0xb8bbb918,0xb98eb9f2,0xb17fb34c,0xb2a7b469,0xb7ebb85a,0xb8b4b924,0xab5caf59,0xac77b074,
0xba32ba7c,0xbb04bb46,0xb66db748,0xb7a9b852,0xb98eb9e3,0xba66baba,0xb4a8b58d,0xb596b6a4,0xb8d7b935,0xb9a7ba0b,0xb1a4b37d,0xb2ccb481,
0xb80eb874,0xb8cab93c,0xab8eaf8b,0xac90b08d,0xba4fba99,0xbb1bbb5a,0xb696b775,0xb7d0b867,0xb9abba00,0xba7fbad1,0xb4c6b5b1,0xb5b3b6c6,
0xb8f2b951,0xb9bfba23,0xb1c9b3ae,0xb2f0b499,0xb826b88e,0xb8e1b954,0xabc0afbd,0xaca9b0a6,0xbb30bb6e,0xbbb5bbdd,0xb7f6b87c,0xb890b91d,
0xba96bae8,0xbb39bb7f,0xb5d1b6e8,0xb6b8b7f3,0xb9d7ba3b,0xba86bae6,0xb315b4b1,0xb41db570,0xb8f7b96b,0xb9a0ba19,0xacc2b0be,0xad8ab185,
0xbb44bb80,0xbbc1bbe6,0xb80eb891,0xb8a2b930,0xbaadbafe,0xbb4bbb8e,0xb5eeb70a,0xb6d4b80a,0xb9efba52,0xba9abaf9,0xb33ab4c9,0xb42fb587,
0xb90db982,0xb9b4ba2d,0xacdbb0d7,0xada3b19e,0xbb57bb91,0xbbcdbbed,0xb821b8a6,0xb8b4b943,0xbac3bb13,0xbb5bbb9c,0xb60bb72c,0xb6f1b81a,
0xba05ba69,0xbaadbb0b,0xb35fb4e1,0xb441b59f,0xb923b999,0xb9c8ba41,0xacf4b0f0,0xadbcb1b6,0xbb69bba0,0xbbd6bbf4,0xb834b8ba,0xb8c5b956,
0xbad9bb27,0xbb6bbba9,0xb628b74e,0xb70db82a,0xba1cba7f,0xbac0bb1d,0xb383b4f9,0xb454b5b6,0xb939b9af,0xb9dbba54,0xad0db109,0xadd5b1cf,
0xbb7bbbaf,0xbbdfbbf8,0xb846b8ce,0xb8d7b969,0xbaedbb3a,0xbb7abbb5,0xb645b76f,0xb729b83a,0xba32ba95,0xbad2bb2e,0xb3a8b511,0xb466b5ce,
0xb94eb9c5,0xb9efba67,0xad26b122,0xadeeb1e8,0xbb8bbbbc,0xbbe7bbfc,0xb859b8e2,0xb8e8b97b,0xbb01bb4c,0xbb88bbc0,0xb662b790,0xb745b84a,
0xba48baaa,0xbae4bb3e,0xb3cdb529,0xb478b5e5,0xb963b9da,0xba01ba7a,0xad3fb13b,0xae07b201,0xbb9abbc9,0xbbeebbff,0xb86bb8f6,0xb8fab98d,
0xbb15bb5e,0xbb95bbcb,0xb67fb7b2,0xb761b85a,0xba5dbabf,0xbaf5bb4e,0xb3f1b540,0xb48ab5fd,0xb978b9f0,0xba14ba8c,0xad58b153,0xae20b219,
0xbba8bbd4,0xbbf4bc00,0xb87eb909,0xb90bb99f,0xbb27bb6f,0xbba2bbd4,0xb69bb7d2,0xb77db86a,0xba72bad3,0xbb06bb5d,0xb40bb558,0xb49cb614,
0xb98cba04,0xba26ba9e,0xad71b16c,0xae39b232,0x12480000,0x22ad0000,0x1f121e48,0x2f7e2eaa,0x18b61648,0x290126ad,0x20521fdb,0x30933029,
0x1bdb1a48,0x2c2b2aac,0x211b20b6,0x316630fd,0x1d7f1cb6,0x2dd52d00,0x21e4217f,0x323831cf,0x18b60000,0x23760000,0x254d24b6,0x302f2f72,
0x1f121cb6,0x29982776,0x267b25e4,0x311c30a6,0x21e420b6,0x2ca92b75,0x27a82711,0x32073191,0x24202311,0x2e842d97,0x286b281f,0x32f0327c,
0x1bdb0000,0x24200000,0x286b27da,0x309f301d,0x21e41fdb,0x2a2f281f,0x296628e8,0x31a43122,0x24e923db,0x2d262c1f,0x2a6129e3,0x32a73226,
0x26df25e4,0x2f332e2d,0x2b5c2ade,0x33a83328,0x1d7f0000,0x24840000,0x2a2f297f,0x310f3080,0x2420217f,0x2ac52884,0x2b8e2ade,0x322c319e,
0x26df257f,0x2da32c83,0x2c772c1f,0x334632b9,0x28cf281f,0x2fe22ec3,0x2d262cce,0x342f33d3,0x1f120000,0x24e90000,0x2bf22b11,0x317f30e4,
0x254d2311,0x2b5c28e8,0x2cdb2c6a,0x32b33219,0x286b2711,0x2e202ce7,0x2dbc2d4c,0x33e5334c,0x2a2f294d,0x30482f59,0x2e9d2e2d,0x348a343e,
0x20520000,0x254d0000,0x2cdb2c51,0x31ee3147,0x267b2452,0x2bf2294d,0x2dee2d65,0x333a3294,0x29662852,0x2e9d2d4c,0x2f012e78,0x344133df,
0x2b8e2a7a,0x309f2fef,0x300a2f8b,0x34e43493,0x211b0000,0x25b20000,0x2dbc2d1a,0x325d31aa,0x27a8251b,0x2c4429b1,0x2f012e5f,0x33c0330f,
0x2a61291b,0x2f1a2db0,0x30232fa4,0x34903438,0x2c772ba7,0x30f63042,0x30c53074,0x353d34e7,0x21e40000,0x26160000,0x2e9d2de2,0x32cc320d,
0x286b25e4,0x2c902a16,0x300a2f59,0x34233389,0x2b5c29e3,0x2f972e14,0x30c53067,0x34de3481,0x2d262c6a,0x314d308d,0x317f3122,0x3596353a,
0x267b0000,0x28cf0000,0x333a326f,0x354f34bd,0x2cdb2a7a,0x2f332cce,0x34663402,0x366d35df,0x300a2e78,0x31fa30cb,0x352c34c9,0x378336f9,
0x31a430d7,0x34293328,0x35ee358d,0x38463805,0x26df0000,0x29010000,0x33a832d2,0x358434ed,0x2d262ade,0x2f7e2d00,0x34a8343e,0x36ad361a,
0x30482edc,0x323830fd,0x35793511,0x37ca373d,0x31fa3122,0x34543371,0x364535df,0x386e382a,0x27440000,0x29340000,0x340b3334,0x35b9351d,
0x2d712b43,0x2fc92d33,0x34ea347b,0x36eb3654,0x30862f40,0x3276312e,0x35c53558,0x38093780,0x3251316c,0x347e33ba,0x369b3631,0x38953850,
0x27a80000,0x29660000,0x34413396,0x35ee354c,0x2dbc2ba7,0x300a2d65,0x352c34b7,0x3729368d,0x30c52fa4,0x32b33160,0x3611359f,0x382c37c2,
0x32a731b6,0x34a83402,0x36f13682,0x38bb3874,0x28060000,0x29980000,0x347833f7,0x3622357c,0x2e072c06,0x302f2d97,0x356d34f3,0x376736c6,
0x31033004,0x32f03191,0x365c35e5,0x384e3802,0x32fd3201,0x34d23426,0x374536d2,0x38e13899,0x28390000,0x29ca0000,0x34ae342c,0x365635ab,
0x2e522c38,0x30552dc9,0x35ae352f,0x37a436ff,0x31413036,0x332e31c3,0x36a7362b,0x38713822,0x3352324b,0x34fc344b,0x37993721,0x390638bc,
0x286b0000,0x29fd0000,0x34e4345d,0x368a35da,0x2e9d2c6a,0x307a2dfb,0x35ee356a,0x37e03737,0x317f3067,0x336b31f4,0x36f13670,0x38923842,
0x33a83294,0x3526346f,0x37eb376f,0x392a38e0,0x289d0000,0x2a2f0000,0x351a348d,0x36be3608,0x2ee82c9c,0x309f2e2d,0x362e35a5,0x380e376f,
0x31bd3099,0x33a83226,0x373a36b5,0x38b43862,0x33fd32de,0x354f3493,0x381e37bd,0x394e3902,0x2a610000,0x2bf20000,0x36f13637,0x383e37a1,
0x30c52e5f,0x31ee2fef,0x382c37a6,0x390d38a8,0x33e53257,0x34e433df,0x38d43881,0x39c8396d,0x357934b7,0x36be35d4,0x39713924,0x3a6c3a1d,
0x2a930000,0x2c120000,0x37243665,0x385637cd,0x30ea2e91,0x32133010,0x384937dd,0x392838c1,0x34113288,0x35023408,0x38f538a0,0x39e43989,
0x35a234db,0x36e535f7,0x39933946,0x3a883a39,0x2ac50000,0x2c2b0000,0x37563693,0x386e37f9,0x310f2ec3,0x32383029,0x3866380a,0x394238db,
0x342f32b9,0x35203420,0x391438bf,0x39ff39a4,0x35cb34ff,0x370d361a,0x39b43966,0x3aa23a54,0x2af80000,0x2c440000,0x378836c1,0x38853812,
0x31342ef5,0x325d3042,0x38833825,0x395c38f3,0x344e32ea,0x353d3438,0x393438dd,0x3a1a39be,0x35f43523,0x3734363c,0x39d53986,0x3abc3a6f,
0x2b2a0000,0x2c5e0000,0x37ba36ee,0x389d3828,0x315a2f27,0x3282305b,0x389f3840,0x3975390c,0x346c331b,0x355b3451,0x395338fb,0x3a3439d8,
0x361d3546,0x375c365f,0x39f539a6,0x3ad53a89,0x2b5c0000,0x2c770000,0x37eb371b,0x38b4383d,0x317f2f59,0x32a73074,0x38bb385a,0x398e3924,
0x348a334c,0x35793469,0x39713918,0x3a4e39f2,0x3645356a,0x37833682,0x3a1439c5,0x3aed3aa2,0x2b8e0000,0x2c900000,0x380e3748,0x38ca3852,
0x31a42f8b,0x32cc308d,0x38d73874,0x39a7393c,0x34a8337d,0x35963481,0x398e3935,0x3a663a0b,0x366d358d,0x37a936a4,0x3a3239e3,0x3b043aba,
0x2bc00000,0x2ca90000,0x38263775,0x38e13867,0x31c92fbd,0x32f030a6,0x38f2388e,0x39bf3954,0x34c633ae,0x35b33499,0x39ab3951,0x3a7f3a23,
0x369635b1,0x37d036c6,0x3a4f3a00,0x3b1b3ad1,0x2cc20000,0x2d8a0000,0x38f7387c,0x39a0391d,0x331530be,0x341d3185,0x39d7396b,0x3a863a19,
0x35d134b1,0x36b83570,0x3a963a3b,0x3b393ae6,0x37f636e8,0x389037f3,0x3b303ae8,0x3bb53b7f,0x2cdb0000,0x2da30000,0x390d3891,0x39b43930,
0x333a30d7,0x342f319e,0x39ef3982,0x3a9a3a2d,0x35ee34c9,0x36d43587,0x3aad3a52,0x3b4b3af9,0x380e370a,0x38a2380a,0x3b443afe,0x3bc13b8e,
0x2cf40000,0x2dbc0000,0x392338a6,0x39c83943,0x335f30f0,0x344131b6,0x3a053999,0x3aad3a41,0x360b34e1,0x36f1359f,0x3ac33a69,0x3b5b3b0b,
0x3821372c,0x38b4381a,0x3b573b13,0x3bcd3b9c,0x2d0d0000,0x2dd50000,0x393938ba,0x39db3956,0x33833109,0x345431cf,0x3a1c39af,0x3ac03a54,
0x362834f9,0x370d35b6,0x3ad93a7f,0x3b6b3b1d,0x3834374e,0x38c5382a,0x3b693b27,0x3bd63ba9,0x2d260000,0x2dee0000,0x394e38ce,0x39ef3969,
0x33a83122,0x346631e8,0x3a3239c5,0x3ad23a67,0x36453511,0x372935ce,0x3aed3a95,0x3b7a3b2e,0x3846376f,0x38d7383a,0x3b7b3b3a,0x3bdf3bb5,
0x2d3f0000,0x2e070000,0x396338e2,0x3a01397b,0x33cd313b,0x34783201,0x3a4839da,0x3ae43a7a,0x36623529,0x374535e5,0x3b013aaa,0x3b883b3e,
0x38593790,0x38e8384a,0x3b8b3b4c,0x3be73bc0,0x2d580000,0x2e200000,0x397838f6,0x3a14398d,0x33f13153,0x348a3219,0x3a5d39f0,0x3af53a8c,
0x367f3540,0x376135fd,0x3b153abf,0x3b953b4e,0x386b37b2,0x38fa385a,0x3b9a3b5e,0x3bee3bcb,0x2d710000,0x2e390000,0x398c3909,0x3a26399f,
0x340b316c,0x349c3232,0x3a723a04,0x3b063a9e,0x369b3558,0x377d3614,0x3b273ad3,0x3ba23b5d,0x387e37d2,0x390b386a,0x3ba83b6f,0x3bf43bd4,
0x0,0x0,0x0,0x0,0x2a3e0000,0x30722e1f,0x32a731a8,0x33d93364,0x2e1f0000,0x336431a8,0x33643400,0x2e1f31a8,
0x30720000,0x33d93364,0x2a3e31a8,0xb2a7ae1f,0x31a80000,0x31a83400,0xb1a80000,0xb1a8b400,0x32a70000,0x2a3e3364,0xb3d9b1a8,0x3072ae1f,
0x33640000,0xae1f31a8,0xae1fb400,0x336431a8,0x33d90000,0xb2a72e1f,0x3072b1a8,0xaa3e3364,0x34000000,0xb4000000,0x34000000,0xb4000000,
0x33d90000,0xb2a7ae1f,0x307231a8,0xaa3eb364,0x33640000,0xae1fb1a8,0xae1f3400,0x3364b1a8,0x32a70000,0x2a3eb364,0xb3d931a8,0x30722e1f,
0x31a80000,0x31a8b400,0xb1a80000,0xb1a83400,0x30720000,0x33d9b364,0x2a3eb1a8,0xb2a72e1f,0x2e1f0000,0x3364b1a8,0x3364b400,0x2e1fb1a8,
0x2a3e0000,0x3072ae1f,0x32a7b1a8,0x33d9b364,0x0,0x0,0x0,0x0,0xaa3e0000,0xb0722e1f,0xb2a731a8,0xb3d93364,
0xae1f0000,0xb36431a8,0xb3643400,0xae1f31a8,0xb0720000,0xb3d93364,0xaa3e31a8,0x32a7ae1f,0xb1a80000,0xb1a83400,0x31a80000,0x31a8b400,
0xb2a70000,0xaa3e3364,0x33d9b1a8,0xb072ae1f,0xb3640000,0x2e1f31a8,0x2e1fb400,0xb36431a8,0xb3d90000,0x32a72e1f,0xb072b1a8,0x2a3e3364,
0xb4000000,0x34000000,0xb4000000,0x34000000,0xb3d90000,0x32a7ae1f,0xb07231a8,0x2a3eb364,0xb3640000,0x2e1fb1a8,0x2e1f3400,0xb364b1a8,
0xb2a70000,0xaa3eb364,0x33d931a8,0xb0722e1f,0xb1a80000,0xb1a8b400,0x31a80000,0x31a83400,0xb0720000,0xb3d9b364,0xaa3eb1a8,0x32a72e1f,
0xae1f0000,0xb364b1a8,0xb364b400,0xae1fb1a8,0xaa3e0000,0xb072ae1f,0xb2a7b1a8,0xb3d9b364,0x0,0x0,0x0,0x0,
0x33d93400,0x32a73364,0x307231a8,0x2a3e2e1f,0xae1f0000,0xb364b1a8,0xb364b400,0xae1fb1a8,0xb2a7b400,0x2a3eae1f,0x33d931a8,0x30723364,
0x31a80000,0x31a83400,0xb1a80000,0xb1a8b400,0x30723400,0xb3d9ae1f,0x2a3eb1a8,0x32a73364,0xb3640000,0x2e1fb1a8,0x2e1f3400,0xb364b1a8,
0xaa3eb400,0x30723364,0xb2a7b1a8,0x33d92e1f,0x34000000,0xb4000000,0x34000000,0xb4000000,0xaa3e3400,0x3072b364,0xb2a731a8,0x33d9ae1f,
0xb3640000,0x2e1f31a8,0x2e1fb400,0xb36431a8,0x3072b400,0xb3d92e1f,0x2a3e31a8,0x32a7b364,0x31a80000,0x31a8b400,0xb1a80000,0xb1a83400,
0xb2a73400,0x2a3e2e1f,0x33d9b1a8,0x3072b364,0xae1f0000,0xb36431a8,0xb3643400,0xae1f31a8,0x33d9b400,0x32a7b364,0x3072b1a8,0x2a3eae1f,
0x0,0x0,0x0,0x0,0xb3d93400,0xb2a73364,0xb07231a8,0xaa3e2e1f,0x2e1f0000,0x3364b1a8,0x3364b400,0x2e1fb1a8,
0x32a7b400,0xaa3eae1f,0xb3d931a8,0xb0723364,0xb1a80000,0xb1a83400,0x31a80000,0x31a8b400,0xb0723400,0x33d9ae1f,0xaa3eb1a8,0xb2a73364,
0x33640000,0xae1fb1a8,0xae1f3400,0x3364b1a8,0x2a3eb400,0xb0723364,0x32a7b1a8,0xb3d92e1f,0xb4000000,0x34000000,0xb4000000,0x34000000,
0x2a3e3400,0xb072b364,0x32a731a8,0xb3d9ae1f,0x33640000,0xae1f31a8,0xae1fb400,0x336431a8,0xb072b400,0x33d92e1f,0xaa3e31a8,0xb2a7b364,
0xb1a80000,0xb1a8b400,0x31a80000,0x31a83400,0x32a73400,0xaa3e2e1f,0xb3d9b1a8,0xb072b364,0x2e1f0000,0x336431a8,0x33643400,0x2e1f31a8,
0xb3d9b400,0xb2a7b364,0xb072b1a8,0xaa3eae1f,0x0,0x0,0x0,0x0,0xaa3e0000,0xb072ae1f,0xb2a7b1a8,0xb3d9b364,
0x2e1f0000,0x336431a8,0x33643400,0x2e1f31a8,0xb0720000,0xb3d9b364,0xaa3eb1a8,0x32a72e1f,0x31a80000,0x31a83400,0xb1a80000,0xb1a8b400,
0xb2a70000,0xaa3eb364,0x33d931a8,0xb0722e1f,0x33640000,0xae1f31a8,0xae1fb400,0x336431a8,0xb3d90000,0x32a7ae1f,0xb07231a8,0x2a3eb364,
0x34000000,0xb4000000,0x34000000,0xb4000000,0xb3d90000,0x32a72e1f,0xb072b1a8,0x2a3e3364,0x33640000,0xae1fb1a8,0xae1f3400,0x3364b1a8,
0xb2a70000,0xaa3e3364,0x33d9b1a8,0xb072ae1f,0x31a80000,0x31a8b400,0xb1a80000,0xb1a83400,0xb0720000,0xb3d93364,0xaa3e31a8,0x32a7ae1f,
0x2e1f0000,0x3364b1a8,0x3364b400,0x2e1fb1a8,0xaa3e0000,0xb0722e1f,0xb2a731a8,0xb3d93364,0x0,0x0,0x0,0x0,
0x2a3e0000,0x3072ae1f,0x32a7b1a8,0x33d9b364,0xae1f0000,0xb36431a8,0xb3643400,0xae1f31a8,0x30720000,0x33d9b364,0x2a3eb1a8,0xb2a72e1f,
0xb1a80000,0xb1a83400,0x31a80000,0x31a8b400,0x32a70000,0x2a3eb364,0xb3d931a8,0x30722e1f,0xb3640000,0x2e1f31a8,0x2e1fb400,0xb36431a8,
0x33d90000,0xb2a7ae1f,0x307231a8,0xaa3eb364,0xb4000000,0x34000000,0xb4000000,0x34000000,0x33d90000,0xb2a72e1f,0x3072b1a8,0xaa3e3364,
0xb3640000,0x2e1fb1a8,0x2e1f3400,0xb364b1a8,0x32a70000,0x2a3e3364,0xb3d9b1a8,0x3072ae1f,0xb1a80000,0xb1a8b400,0x31a80000,0x31a83400,
0x30720000,0x33d93364,0x2a3e31a8,0xb2a7ae1f,0xae1f0000,0xb364b1a8,0xb364b400,0xae1fb1a8,0x2a3e0000,0x30722e1f,0x32a731a8,0x33d93364,
0x0,0x0,0x0,0x0,0xb3d9b400,0xb2a7b364,0xb072b1a8,0xaa3eae1f,0xae1f0000,0xb364b1a8,0xb364b400,0xae1fb1a8,
0x32a73400,0xaa3e2e1f,0xb3d9b1a8,0xb072b364,0x31a80000,0x31a83400,0xb1a80000,0xb1a8b400,0xb072b400,0x33d92e1f,0xaa3e31a8,0xb2a7b364,
0xb3640000,0x2e1fb1a8,0x2e1f3400,0xb364b1a8,0x2a3e3400,0xb072b364,0x32a731a8,0xb3d9ae1f,0x34000000,0xb4000000,0x34000000,0xb4000000,
0x2a3eb400,0xb0723364,0x32a7b1a8,0xb3d92e1f,0xb3640000,0x2e1f31a8,0x2e1fb400,0xb36431a8,0xb0723400,0x33d9ae1f,0xaa3eb1a8,0xb2a73364,
0x31a80000,0x31a8b400,0xb1a80000,0xb1a83400,0x32a7b400,0xaa3eae1f,0xb3d931a8,0xb0723364,0xae1f0000,0xb36431a8,0xb3643400,0xae1f31a8,
0xb3d93400,0xb2a73364,0xb07231a8,0xaa3e2e1f,0x0,0x0,0x0,0x0,0x33d9b400,0x32a7b364,0x3072b1a8,0x2a3eae1f,
0x2e1f0000,0x3364b1a8,0x3364b400,0x2e1fb1a8,0xb2a73400,0x2a3e2e1f,0x33d9b1a8,0x3072b364,0xb1a80000,0xb1a83400,0x31a80000,0x31a8b400,
0x3072b400,0xb3d92e1f,0x2a3e31a8,0x32a7b364,0x33640000,0xae1fb1a8,0xae1f3400,0x3364b1a8,0xaa3e3400,0x3072b364,0xb2a731a8,0x33d9ae1f,
0xb4000000,0x34000000,0xb4000000,0x34000000,0xaa3eb400,0x30723364,0xb2a7b1a8,0x33d92e1f,0x33640000,0xae1f31a8,0xae1fb400,0x336431a8,
0x30723400,0xb3d9ae1f,0x2a3eb1a8,0x32a73364,0xb1a80000,0xb1a8b400,0x31a80000,0x31a83400,0xb2a7b400,0x2a3eae1f,0x33d931a8,0x30723364,
0x2e1f0000,0x336431a8,0x33643400,0x2e1f31a8,0x33d93400,0x32a73364,0x307231a8,0x2a3e2e1f,0x34003400,0x34003400,0x34003400,0x34003400,
0x33d93400,0x32a73364,0x307231a8,0x2a3e2e1f,0x33643400,0x2e1f31a8,0xae1f0000,0xb364b1a8,0x32a73400,0xaa3e2e1f,0xb3d9b1a8,0xb072b364,
0x31a83400,0xb1a80000,0xb1a8b400,0x31a80000,0x30723400,0xb3d9ae1f,0x2a3eb1a8,0x32a73364,0x2e1f3400,0xb364b1a8,0x33640000,0xae1f31a8,
0x2a3e3400,0xb072b364,0x32a731a8,0xb3d9ae1f,0x3400,0xb400,0x3400,0xb400,0xaa3e3400,0x3072b364,0xb2a731a8,0x33d9ae1f,
0xae1f3400,0x3364b1a8,0xb3640000,0x2e1f31a8,0xb0723400,0x33d9ae1f,0xaa3eb1a8,0xb2a73364,0xb1a83400,0x31a80000,0x31a8b400,0xb1a80000,
0xb2a73400,0x2a3e2e1f,0x33d9b1a8,0x3072b364,0xb3643400,0xae1f31a8,0x2e1f0000,0x3364b1a8,0xb3d93400,0xb2a73364,0xb07231a8,0xaa3e2e1f,
0xb4003400,0xb4003400,0xb4003400,0xb4003400,0xb3d93400,0xb2a73364,0xb07231a8,0xaa3e2e1f,0xb3643400,0xae1f31a8,0x2e1f0000,0x3364b1a8,
0xb2a73400,0x2a3e2e1f,0x33d9b1a8,0x3072b364,0xb1a83400,0x31a80000,0x31a8b400,0xb1a80000,0xb0723400,0x33d9ae1f,0xaa3eb1a8,0xb2a73364,
0xae1f3400,0x3364b1a8,0xb3640000,0x2e1f31a8,0xaa3e3400,0x3072b364,0xb2a731a8,0x33d9ae1f,0x3400,0xb400,0x3400,0xb400,
0x2a3e3400,0xb072b364,0x32a731a8,0xb3d9ae1f,0x2e1f3400,0xb364b1a8,0x33640000,0xae1f31a8,0x30723400,0xb3d9ae1f,0x2a3eb1a8,0x32a73364,
0x31a83400,0xb1a80000,0xb1a8b400,0x31a80000,0x32a73400,0xaa3e2e1f,0xb3d9b1a8,0xb072b364,0x33643400,0x2e1f31a8,0xae1f0000,0xb364b1a8,
0x33d93400,0x32a73364,0x307231a8,0x2a3e2e1f,0x34003400,0x34003400,0x34003400,0x34003400,0xaa3e0000,0xb072ae1f,0xb2a7b1a8,0xb3d9b364,
0xb364b400,0xae1fb1a8,0x2e1f0000,0x336431a8,0x30720000,0x33d93364,0x2a3e31a8,0xb2a7ae1f,0x31a83400,0xb1a80000,0xb1a8b400,0x31a80000,
0xb2a70000,0xaa3eb364,0x33d931a8,0xb0722e1f,0xae1fb400,0x336431a8,0xb3640000,0x2e1fb1a8,0x33d90000,0xb2a72e1f,0x3072b1a8,0xaa3e3364,
0x3400,0xb400,0x3400,0xb400,0xb3d90000,0x32a72e1f,0xb072b1a8,0x2a3e3364,0x2e1fb400,0xb36431a8,0x33640000,0xae1fb1a8,
0x32a70000,0x2a3eb364,0xb3d931a8,0x30722e1f,0xb1a83400,0x31a80000,0x31a8b400,0xb1a80000,0xb0720000,0xb3d93364,0xaa3e31a8,0x32a7ae1f,
0x3364b400,0x2e1fb1a8,0xae1f0000,0xb36431a8,0x2a3e0000,0x3072ae1f,0x32a7b1a8,0x33d9b364,0xb4003400,0xb4003400,0xb4003400,0xb4003400,
0x2a3e0000,0x3072ae1f,0x32a7b1a8,0x33d9b364,0x3364b400,0x2e1fb1a8,0xae1f0000,0xb36431a8,0xb0720000,0xb3d93364,0xaa3e31a8,0x32a7ae1f,
0xb1a83400,0x31a80000,0x31a8b400,0xb1a80000,0x32a70000,0x2a3eb364,0xb3d931a8,0x30722e1f,0x2e1fb400,0xb36431a8,0x33640000,0xae1fb1a8,
0xb3d90000,0x32a72e1f,0xb072b1a8,0x2a3e3364,0x3400,0xb400,0x3400,0xb400,0x33d90000,0xb2a72e1f,0x3072b1a8,0xaa3e3364,
0xae1fb400,0x336431a8,0xb3640000,0x2e1fb1a8,0xb2a70000,0xaa3eb364,0x33d931a8,0xb0722e1f,0x31a83400,0xb1a80000,0xb1a8b400,0x31a80000,
0x30720000,0x33d93364,0x2a3e31a8,0xb2a7ae1f,0xb364b400,0xae1fb1a8,0x2e1f0000,0x336431a8,0xaa3e0000,0xb072ae1f,0xb2a7b1a8,0xb3d9b364,
0x34003400,0x34003400,0x34003400,0x34003400,0xb3d9b400,0xb2a7b364,0xb072b1a8,0xaa3eae1f,0x33643400,0x2e1f31a8,0xae1f0000,0xb364b1a8,
0xb2a7b400,0x2a3eae1f,0x33d931a8,0x30723364,0x31a83400,0xb1a80000,0xb1a8b400,0x31a80000,0xb072b400,0x33d92e1f,0xaa3e31a8,0xb2a7b364,
0x2e1f3400,0xb364b1a8,0x33640000,0xae1f31a8,0xaa3eb400,0x30723364,0xb2a7b1a8,0x33d92e1f,0x3400,0xb400,0x3400,0xb400,
0x2a3eb400,0xb0723364,0x32a7b1a8,0xb3d92e1f,0xae1f3400,0x3364b1a8,0xb3640000,0x2e1f31a8,0x3072b400,0xb3d92e1f,0x2a3e31a8,0x32a7b364,
0xb1a83400,0x31a80000,0x31a8b400,0xb1a80000,0x32a7b400,0xaa3eae1f,0xb3d931a8,0xb0723364,0xb3643400,0xae1f31a8,0x2e1f0000,0x3364b1a8,
0x33d9b400,0x32a7b364,0x3072b1a8,0x2a3eae1f,0xb4003400,0xb4003400,0xb4003400,0xb4003400,0x33d9b400,0x32a7b364,0x3072b1a8,0x2a3eae1f,
0xb3643400,0xae1f31a8,0x2e1f0000,0x3364b1a8,0x32a7b400,0xaa3eae1f,0xb3d931a8,0xb0723364,0xb1a83400,0x31a80000,0x31a8b400,0xb1a80000,
0x3072b400,0xb3d92e1f,0x2a3e31a8,0x32a7b364,0xae1f3400,0x3364b1a8,0xb3640000,0x2e1f31a8,0x2a3eb400,0xb0723364,0x32a7b1a8,0xb3d92e1f,
0x3400,0xb400,0x3400,0xb400,0xaa3eb400,0x30723364,0xb2a7b1a8,0x33d92e1f,0x2e1f3400,0xb364b1a8,0x33640000,0xae1f31a8,
0xb072b400,0x33d92e1f,0xaa3e31a8,0xb2a7b364,0x31a83400,0xb1a80000,0xb1a8b400,0x31a80000,0xb2a7b400,0x2a3eae1f,0x33d931a8,0x30723364,
0x33643400,0x2e1f31a8,0xae1f0000,0xb364b1a8,0xb3d9b400,0xb2a7b364,0xb072b1a8,0xaa3eae1f,0x34003400,0x34003400,0x34003400,0x34003400,
0x2a3e0000,0x30722e1f,0x32a731a8,0x33d93364,0xb364b400,0xae1fb1a8,0x2e1f0000,0x336431a8,0xb0720000,0xb3d9b364,0xaa3eb1a8,0x32a72e1f,
0x31a83400,0xb1a80000,0xb1a8b400,0x31a80000,0x32a70000,0x2a3e3364,0xb3d9b1a8,0x3072ae1f,0xae1fb400,0x336431a8,0xb3640000,0x2e1fb1a8,
0xb3d90000,0x32a7ae1f,0xb07231a8,0x2a3eb364,0x3400,0xb400,0x3400,0xb400,0x33d90000,0xb2a7ae1f,0x307231a8,0xaa3eb364,
0x2e1fb400,0xb36431a8,0x33640000,0xae1fb1a8,0xb2a70000,0xaa3e3364,0x33d9b1a8,0xb072ae1f,0xb1a83400,0x31a80000,0x31a8b400,0xb1a80000,
0x30720000,0x33d9b364,0x2a3eb1a8,0xb2a72e1f,0x3364b400,0x2e1fb1a8,0xae1f0000,0xb36431a8,0xaa3e0000,0xb0722e1f,0xb2a731a8,0xb3d93364,
0xb4003400,0xb4003400,0xb4003400,0xb4003400,0xaa3e0000,0xb0722e1f,0xb2a731a8,0xb3d93364,0x3364b400,0x2e1fb1a8,0xae1f0000,0xb36431a8,
0x30720000,0x33d9b364,0x2a3eb1a8,0xb2a72e1f,0xb1a83400,0x31a80000,0x31a8b400,0xb1a80000,0xb2a70000,0xaa3e3364,0x33d9b1a8,0xb072ae1f,
0x2e1fb400,0xb36431a8,0x33640000,0xae1fb1a8,0x33d90000,0xb2a7ae1f,0x307231a8,0xaa3eb364,0x3400,0xb400,0x3400,0xb400,
0xb3d90000,0x32a7ae1f,0xb07231a8,0x2a3eb364,0xae1fb400,0x336431a8,0xb3640000,0x2e1fb1a8,0x32a70000,0x2a3e3364,0xb3d9b1a8,0x3072ae1f,
0x31a83400,0xb1a80000,0xb1a8b400,0x31a80000,0xb0720000,0xb3d9b364,0xaa3eb1a8,0x32a72e1f,0xb364b400,0xae1fb1a8,0x2e1f0000,0x336431a8,
0x2a3e0000,0x30722e1f,0x32a731a8,0x33d93364,0x0,0x0,0x0,0x0,0xaa3e0000,0xb072ae1f,0xb2a7b1a8,0xb3d9b364,
0xae1f0000,0xb364b1a8,0xb364b400,0xae1fb1a8,0xb0720000,0xb3d9b364,0xaa3eb1a8,0x32a72e1f,0xb1a80000,0xb1a8b400,0x31a80000,0x31a83400,
0xb2a70000,0xaa3eb364,0x33d931a8,0xb0722e1f,0xb3640000,0x2e1fb1a8,0x2e1f3400,0xb364b1a8,0xb3d90000,0x32a7ae1f,0xb07231a8,0x2a3eb364,
0xb4000000,0x34000000,0xb4000000,0x34000000,0xb3d90000,0x32a72e1f,0xb072b1a8,0x2a3e3364,0xb3640000,0x2e1f31a8,0x2e1fb400,0xb36431a8,
0xb2a70000,0xaa3e3364,0x33d9b1a8,0xb072ae1f,0xb1a80000,0xb1a83400,0x31a80000,0x31a8b400,0xb0720000,0xb3d93364,0xaa3e31a8,0x32a7ae1f,
0xae1f0000,0xb36431a8,0xb3643400,0xae1f31a8,0xaa3e0000,0xb0722e1f,0xb2a731a8,0xb3d93364,0x0,0x0,0x0,0x0,
0x2a3e0000,0x3072ae1f,0x32a7b1a8,0x33d9b364,0x2e1f0000,0x3364b1a8,0x3364b400,0x2e1fb1a8,0x30720000,0x33d9b364,0x2a3eb1a8,0xb2a72e1f,
0x31a80000,0x31a8b400,0xb1a80000,0xb1a83400,0x32a70000,0x2a3eb364,0xb3d931a8,0x30722e1f,0x33640000,0xae1fb1a8,0xae1f3400,0x3364b1a8,
0x33d90000,0xb2a7ae1f,0x307231a8,0xaa3eb364,0x34000000,0xb4000000,0x34000000,0xb4000000,0x33d90000,0xb2a72e1f,0x3072b1a8,0xaa3e3364,
0x33640000,0xae1f31a8,0xae1fb400,0x336431a8,0x32a70000,0x2a3e3364,0xb3d9b1a8,0x3072ae1f,0x31a80000,0x31a83400,0xb1a80000,0xb1a8b400,
0x30720000,0x33d93364,0x2a3e31a8,0xb2a7ae1f,0x2e1f0000,0x336431a8,0x33643400,0x2e1f31a8,0x2a3e0000,0x30722e1f,0x32a731a8,0x33d93364,
0x0,0x0,0x0,0x0,0xb3d9b400,0xb2a7b364,0xb072b1a8,0xaa3eae1f,0x2e1f0000,0x336431a8,0x33643400,0x2e1f31a8,
0x32a73400,0xaa3e2e1f,0xb3d9b1a8,0xb072b364,0xb1a80000,0xb1a8b400,0x31a80000,0x31a83400,0xb072b400,0x33d92e1f,0xaa3e31a8,0xb2a7b364,
0x33640000,0xae1f31a8,0xae1fb400,0x336431a8,0x2a3e3400,0xb072b364,0x32a731a8,0xb3d9ae1f,0xb4000000,0x34000000,0xb4000000,0x34000000,
0x2a3eb400,0xb0723364,0x32a7b1a8,0xb3d92e1f,0x33640000,0xae1fb1a8,0xae1f3400,0x3364b1a8,0xb0723400,0x33d9ae1f,0xaa3eb1a8,0xb2a73364,
0xb1a80000,0xb1a83400,0x31a80000,0x31a8b400,0x32a7b400,0xaa3eae1f,0xb3d931a8,0xb0723364,0x2e1f0000,0x3364b1a8,0x3364b400,0x2e1fb1a8,
0xb3d93400,0xb2a73364,0xb07231a8,0xaa3e2e1f,0x0,0x0,0x0,0x0,0x33d9b400,0x32a7b364,0x3072b1a8,0x2a3eae1f,
0xae1f0000,0xb36431a8,0xb3643400,0xae1f31a8,0xb2a73400,0x2a3e2e1f,0x33d9b1a8,0x3072b364,0x31a80000,0x31a8b400,0xb1a80000,0xb1a83400,
0x3072b400,0xb3d92e1f,0x2a3e31a8,0x32a7b364,0xb3640000,0x2e1f31a8,0x2e1fb400,0xb36431a8,0xaa3e3400,0x3072b364,0xb2a731a8,0x33d9ae1f,
0x34000000,0xb4000000,0x34000000,0xb4000000,0xaa3eb400,0x30723364,0xb2a7b1a8,0x33d92e1f,0xb3640000,0x2e1fb1a8,0x2e1f3400,0xb364b1a8,
0x30723400,0xb3d9ae1f,0x2a3eb1a8,0x32a73364,0x31a80000,0x31a83400,0xb1a80000,0xb1a8b400,0xb2a7b400,0x2a3eae1f,0x33d931a8,0x30723364,
0xae1f0000,0xb364b1a8,0xb364b400,0xae1fb1a8,0x33d93400,0x32a73364,0x307231a8,0x2a3e2e1f,0x0,0x0,0x0,0x0,
0x2a3e0000,0x30722e1f,0x32a731a8,0x33d93364,0xae1f0000,0xb364b1a8,0xb364b400,0xae1fb1a8,0x30720000,0x33d93364,0x2a3e31a8,0xb2a7ae1f,
0xb1a80000,0xb1a8b400,0x31a80000,0x31a83400,0x32a70000,0x2a3e3364,0xb3d9b1a8,0x3072ae1f,0xb3640000,0x2e1fb1a8,0x2e1f3400,0xb364b1a8,
0x33d90000,0xb2a72e1f,0x3072b1a8,0xaa3e3364,0xb4000000,0x34000000,0xb4000000,0x34000000,0x33d90000,0xb2a7ae1f,0x307231a8,0xaa3eb364,
0xb3640000,0x2e1f31a8,0x2e1fb400,0xb36431a8,0x32a70000,0x2a3eb364,0xb3d931a8,0x30722e1f,0xb1a80000,0xb1a83400,0x31a80000,0x31a8b400,
0x30720000,0x33d9b364,0x2a3eb1a8,0xb2a72e1f,0xae1f0000,0xb36431a8,0xb3643400,0xae1f31a8,0x2a3e0000,0x3072ae1f,0x32a7b1a8,0x33d9b364,
0x0,0x0,0x0,0x0,0xaa3e0000,0xb0722e1f,0xb2a731a8,0xb3d93364,0x2e1f0000,0x3364b1a8,0x3364b400,0x2e1fb1a8,
0xb0720000,0xb3d93364,0xaa3e31a8,0x32a7ae1f,0x31a80000,0x31a8b400,0xb1a80000,0xb1a83400,0xb2a70000,0xaa3e3364,0x33d9b1a8,0xb072ae1f,
0x33640000,0xae1fb1a8,0xae1f3400,0x3364b1a8,0xb3d90000,0x32a72e1f,0xb072b1a8,0x2a3e3364,0x34000000,0xb4000000,0x34000000,0xb4000000,
0xb3d90000,0x32a7ae1f,0xb07231a8,0x2a3eb364,0x33640000,0xae1f31a8,0xae1fb400,0x336431a8,0xb2a70000,0xaa3eb364,0x33d931a8,0xb0722e1f,
0x31a80000,0x31a83400,0xb1a80000,0xb1a8b400,0xb0720000,0xb3d9b364,0xaa3eb1a8,0x32a72e1f,0x2e1f0000,0x336431a8,0x33643400,0x2e1f31a8,
0xaa3e0000,0xb072ae1f,0xb2a7b1a8,0xb3d9b364,0x0,0x0,0x0,0x0,0x33d93400,0x32a73364,0x307231a8,0x2a3e2e1f,
0x2e1f0000,0x336431a8,0x33643400,0x2e1f31a8,0xb2a7b400,0x2a3eae1f,0x33d931a8,0x30723364,0xb1a80000,0xb1a8b400,0x31a80000,0x31a83400,
0x30723400,0xb3d9ae1f,0x2a3eb1a8,0x32a73364,0x33640000,0xae1f31a8,0xae1fb400,0x336431a8,0xaa3eb400,0x30723364,0xb2a7b1a8,0x33d92e1f,
0xb4000000,0x34000000,0xb4000000,0x34000000,0xaa3e3400,0x3072b364,0xb2a731a8,0x33d9ae1f,0x33640000,0xae1fb1a8,0xae1f3400,0x3364b1a8,
0x3072b400,0xb3d92e1f,0x2a3e31a8,0x32a7b364,0xb1a80000,0xb1a83400,0x31a80000,0x31a8b400,0xb2a73400,0x2a3e2e1f,0x33d9b1a8,0x3072b364,
0x2e1f0000,0x3364b1a8,0x3364b400,0x2e1fb1a8,0x33d9b400,0x32a7b364,0x3072b1a8,0x2a3eae1f,0x0,0x0,0x0,0x0,
0xb3d93400,0xb2a73364,0xb07231a8,0xaa3e2e1f,0xae1f0000,0xb36431a8,0xb3643400,0xae1f31a8,0x32a7b400,0xaa3eae1f,0xb3d931a8,0xb0723364,
0x31a80000,0x31a8b400,0xb1a80000,0xb1a83400,0xb0723400,0x33d9ae1f,0xaa3eb1a8,0xb2a73364,0xb3640000,0x2e1f31a8,0x2e1fb400,0xb36431a8,
0x2a3eb400,0xb0723364,0x32a7b1a8,0xb3d92e1f,0x34000000,0xb4000000,0x34000000,0xb4000000,0x2a3e3400,0xb072b364,0x32a731a8,0xb3d9ae1f,
0xb3640000,0x2e1fb1a8,0x2e1f3400,0xb364b1a8,0xb072b400,0x33d92e1f,0xaa3e31a8,0xb2a7b364,0x31a80000,0x31a83400,0xb1a80000,0xb1a8b400,
0x32a73400,0xaa3e2e1f,0xb3d9b1a8,0xb072b364,0xae1f0000,0xb364b1a8,0xb364b400,0xae1fb1a8,0xb3d9b400,0xb2a7b364,0xb072b1a8,0xaa3eae1f,
};

typedef CUresult (*EncodeFn)(CUtensorMap*, CUtensorMapDataType, cuuint32_t, void*, const cuuint64_t*, const cuuint64_t*,
                             const cuuint32_t*, const cuuint32_t*, CUtensorMapInterleave, CUtensorMapSwizzle,
                             CUtensorMapL2promotion, CUtensorMapFloatOOBfill);

}

extern "C" void kernel_launch(void* const* d_in, const int* in_sizes, int n_in, void* d_out, int out_size) {
    Params p;
    p.x = (const __nv_bfloat16*)d_in[0];
    p.lar = (const __nv_bfloat16*)d_in[1];
    p.aim = (const __nv_bfloat16*)d_in[2];
    p.cr = (const __nv_bfloat16*)d_in[3];
    p.ci = (const __nv_bfloat16*)d_in[4];
    p.logdt = (const __nv_bfloat16*)d_in[5];
    p.dskip = (const __nv_bfloat16*)d_in[6];
    p.wr = (const __nv_bfloat16*)d_in[8];
    p.out = (__nv_bfloat16*)d_out;
    cudaGetSymbolAddress((void**)&p.sc, g_scratch);
    cudaGetSymbolAddress((void**)&p.tab, g_tab);

    void* fn = nullptr;
    cudaDriverEntryPointQueryResult qr;
    cudaGetDriverEntryPoint("cuTensorMapEncodeTiled", &fn, cudaEnableDefault, &qr);
    EncodeFn enc = (EncodeFn)fn;
    CUtensorMap tm_x, tm_g, tm_d, tm_o;
    const cuuint32_t es[5] = {1, 1, 1, 1, 1};
    {
        const cuuint64_t gd[5] = {1024, 4, 64, 2, 4}, gs[4] = {4096, 65536, 2048, 16384};
        const cuuint32_t bx[5] = {16, 4, 64, 2, 2};
        enc(&tm_x, CU_TENSOR_MAP_DATA_TYPE_BFLOAT16, 5, d_in[0], gd, gs, bx, es, CU_TENSOR_MAP_INTERLEAVE_NONE,
            CU_TENSOR_MAP_SWIZZLE_32B, (CUtensorMapL2promotion)XPROMO, CU_TENSOR_MAP_FLOAT_OOB_FILL_NONE);
        const cuuint32_t bo[5] = {16, 4, 16, 1, 1};
        enc(&tm_o, CU_TENSOR_MAP_DATA_TYPE_BFLOAT16, 5, d_out, gd, gs, bo, es, CU_TENSOR_MAP_INTERLEAVE_NONE,
            CU_TENSOR_MAP_SWIZZLE_32B, CU_TENSOR_MAP_L2_PROMOTION_NONE, CU_TENSOR_MAP_FLOAT_OOB_FILL_NONE);
    }
    {
        char *wg = (char*)d_in[9], *wu = (char*)d_in[10];
        p.up_first = wu < wg;
        p.w2 = (const __nv_bfloat16*)(p.up_first ? wg : wu);
        p.wd = (const __nv_bfloat16*)d_in[11];
        const cuuint64_t gd[3] = {3584, 1024, 2}, gs[2] = {7168, (cuuint64_t)(p.up_first ? wg - wu : wu - wg)};
        const cuuint32_t bx[3] = {64, 32, 2};
        enc(&tm_g, CU_TENSOR_MAP_DATA_TYPE_BFLOAT16, 3, p.up_first ? wu : wg, gd, gs, bx, es, CU_TENSOR_MAP_INTERLEAVE_NONE,
            CU_TENSOR_MAP_SWIZZLE_128B, CU_TENSOR_MAP_L2_PROMOTION_NONE, CU_TENSOR_MAP_FLOAT_OOB_FILL_NONE);
    }
    {
        const cuuint64_t gd[3] = {1024, 3584, 1}, gs[2] = {2048, 2048 * 3584};
        const cuuint32_t bx[3] = {64, 64, 1};
        enc(&tm_d, CU_TENSOR_MAP_DATA_TYPE_BFLOAT16, 3, d_in[11], gd, gs, bx, es, CU_TENSOR_MAP_INTERLEAVE_NONE,
            CU_TENSOR_MAP_SWIZZLE_128B, CU_TENSOR_MAP_L2_PROMOTION_NONE, CU_TENSOR_MAP_FLOAT_OOB_FILL_NONE);
    }
    cudaFuncSetAttribute(fused_kernel, cudaFuncAttributeMaxDynamicSharedMemorySize, SM_TOTAL + 256);
    fused_kernel<<<128, NTHREADS, SM_TOTAL + 256>>>(p, tm_x, tm_g, tm_d, tm_o);
}
```

```cpp
#include <cuda_runtime.h>
#include <cuda.h>
#include <cuda_bf16.h>
#include <cuda_fp16.h>
#include <stdint.h>

#define TG(i)
#define TS(i)
#define TSL(i)

#define TSW 0
#define XFIRST 8
#define XPROMO 0
#define NSLOT 6
#define DEPTH 4

namespace {

constexpr int NTHREADS = 512;
constexpr int SPIN_LIMIT = 1 << 16;

constexpr int SM_SLAB = 0;
constexpr int SM_RING = 65536;
constexpr int SM_F2   = SM_RING + NSLOT * 8192;
constexpr int SUB     = 1088;
constexpr int SM_U    = SM_F2 + 1536;
constexpr int SM_K    = SM_U + 32 * SUB;
constexpr int SM_S    = SM_K + 32 * SUB;
constexpr int SM_XSEL = SM_S + 32 * SUB;
constexpr int SM_PAIR = SM_XSEL + 4096;
constexpr int SM_H    = SM_PAIR + 2048;
constexpr int SM_KEYS = SM_H + 1024;
constexpr int SM_TOK  = SM_KEYS + 64;
constexpr int SM_FIX  = SM_TOK + 16;
constexpr int SM_XRAW = SM_FIX + 32;
constexpr int SM_SCL  = SM_XRAW + 32;
constexpr int SM_PROBE = SM_SCL + 16;
constexpr int SM_BAR  = SM_PROBE + 64;
constexpr int SM_RED  = SM_XSEL;
constexpr int B_FULL = 0, B_EMPTY = 8, B_STG = 16, B_PROBE = 20, B_MISC = 24, B_ROW = 32, NBAR = 48;
constexpr int B_PEER = B_MISC, B_TOK = B_MISC + 1, B_FIX = B_MISC + 2, B_PAIR = B_MISC + 3, B_SLAB = B_MISC + 4, B_F2 = B_MISC + 5;
constexpr int SM_TOTAL = SM_BAR + NBAR * 8;
static_assert(SM_TOTAL <= 232448 && NSLOT < 8 && DEPTH <= NSLOT && DEPTH <= 4, "smem");
__host__ __device__ constexpr int full_bar(int n) { return B_FULL + (n == 23 ? 7 : n % NSLOT); }
__host__ __device__ constexpr int full_par(int n) { return n == 23 ? 0 : (n / NSLOT) & 1; }
constexpr int KP = 272;

struct Scratch {
    uint4 stats[1024];
    uint32_t part[128 * 56 * 16];
    uint32_t epoch;
};
__device__ Scratch g_scratch;

struct Params {
    const __nv_bfloat16 *lar, *aim, *cr, *ci, *logdt, *dskip;
    const __nv_bfloat16 *x, *wr;
    __nv_bfloat16* out;
    Scratch* sc;
    const uint4* tab;
    int up_first;
    const __nv_bfloat16 *w2, *wd;
};

__device__ __forceinline__ uint4 ldg128(const void* p) {
    uint4 v; asm volatile("ld.global.nc.v4.u32 {%0,%1,%2,%3}, [%4];" : "=r"(v.x), "=r"(v.y), "=r"(v.z), "=r"(v.w) : "l"(p)); return v;
}
__device__ __forceinline__ uint4 ld_relaxed128(const void* p) {
    uint4 v;
    asm volatile("{ .reg .b128 t; ld.relaxed.gpu.global.b128 t, [%4]; mov.b128 {%0,%1,%2,%3}, t; }"
                 : "=r"(v.x), "=r"(v.y), "=r"(v.z), "=r"(v.w) : "l"(p) : "memory");
    return v;
}
__device__ __forceinline__ void st_relaxed128(void* p, uint4 v) {
    asm volatile("{ .reg .b128 t; mov.b128 t, {%1,%2,%3,%4}; st.relaxed.gpu.global.b128 [%0], t; }"
                 :: "l"(p), "r"(v.x), "r"(v.y), "r"(v.z), "r"(v.w) : "memory");
}
__device__ __forceinline__ void st_relaxed32(void* p, uint32_t v) {
    asm volatile("st.relaxed.gpu.global.u32 [%0], %1;" :: "l"(p), "r"(v) : "memory");
}
__device__ __forceinline__ uint32_t lds32(uint32_t a) { uint32_t v; asm volatile("ld.shared.u32 %0, [%1];" : "=r"(v) : "r"(a)); return v; }
__device__ __forceinline__ uint32_t lds16(uint32_t a) { uint32_t v; asm volatile("ld.shared.u16 %0, [%1];" : "=r"(v) : "r"(a)); return v; }
__device__ __forceinline__ uint2 lds64(uint32_t a) { uint2 v; asm volatile("ld.shared.v2.u32 {%0,%1}, [%2];" : "=r"(v.x), "=r"(v.y) : "r"(a)); return v; }
__device__ __forceinline__ uint4 lds128(uint32_t a) {
    uint4 v; asm volatile("ld.shared.v4.u32 {%0,%1,%2,%3}, [%4];" : "=r"(v.x), "=r"(v.y), "=r"(v.z), "=r"(v.w) : "r"(a)); return v;
}
__device__ __forceinline__ void sts16(uint32_t a, uint32_t v) { asm volatile("st.shared.u16 [%0], %1;" :: "r"(a), "h"((uint16_t)v) : "memory"); }
__device__ __forceinline__ void sts32(uint32_t a, uint32_t v) { asm volatile("st.shared.u32 [%0], %1;" :: "r"(a), "r"(v) : "memory"); }
__device__ __forceinline__ void sts64(uint32_t a, uint32_t x, uint32_t y) { asm volatile("st.shared.v2.u32 [%0], {%1,%2};" :: "r"(a), "r"(x), "r"(y) : "memory"); }
__device__ __forceinline__ void sts128(uint32_t a, uint32_t x, uint32_t y, uint32_t z, uint32_t w) {
    asm volatile("st.shared.v4.u32 [%0], {%1,%2,%3,%4};" :: "r"(a), "r"(x), "r"(y), "r"(z), "r"(w) : "memory");
}
__device__ __forceinline__ void ldsm4(uint32_t a, uint32_t& r0, uint32_t& r1, uint32_t& r2, uint32_t& r3) {
    asm volatile("ldmatrix.sync.aligned.m8n8.x4.shared.b16 {%0,%1,%2,%3}, [%4];" : "=r"(r0), "=r"(r1), "=r"(r2), "=r"(r3) : "r"(a));
}
__device__ __forceinline__ void mma_f16(float (&d)[4], uint32_t a0, uint32_t a1, uint32_t a2, uint32_t a3, uint32_t b0, uint32_t b1) {
    asm("mma.sync.aligned.m16n8k16.row.col.f32.f16.f16.f32 {%0,%1,%2,%3}, {%4,%5,%6,%7}, {%8,%9}, {%0,%1,%2,%3};"
        : "+f"(d[0]), "+f"(d[1]), "+f"(d[2]), "+f"(d[3]) : "r"(a0), "r"(a1), "r"(a2), "r"(a3), "r"(b0), "r"(b1));
}
__device__ __forceinline__ void mma_bf16(float (&d)[4], uint32_t a0, uint32_t a1, uint32_t a2, uint32_t a3, uint32_t b0, uint32_t b1) {
    asm("mma.sync.aligned.m16n8k16.row.col.f32.bf16.bf16.f32 {%0,%1,%2,%3}, {%4,%5,%6,%7}, {%8,%9}, {%0,%1,%2,%3};"
        : "+f"(d[0]), "+f"(d[1]), "+f"(d[2]), "+f"(d[3]) : "r"(a0), "r"(a1), "r"(a2), "r"(a3), "r"(b0), "r"(b1));
}
__device__ __forceinline__ uint32_t prmt(uint32_t a, uint32_t b, uint32_t s) { uint32_t d; asm("prmt.b32 %0, %1, %2, %3;" : "=r"(d) : "r"(a), "r"(b), "r"(s)); return d; }
__device__ __forceinline__ uint32_t pack_h(float lo, float hi) { uint32_t d; asm("cvt.rn.f16x2.f32 %0, %1, %2;" : "=r"(d) : "f"(hi), "f"(lo)); return d; }
__device__ __forceinline__ uint32_t pack_b(float lo, float hi) { uint32_t d; asm("cvt.rn.bf16x2.f32 %0, %1, %2;" : "=r"(d) : "f"(hi), "f"(lo)); return d; }
__device__ __forceinline__ float blo(uint32_t v) { return __uint_as_float(v << 16); }
__device__ __forceinline__ float bhi(uint32_t v) { return __uint_as_float(v & 0xFFFF0000u); }
__device__ __forceinline__ float rb(float v) { return blo(pack_b(v, v)); }
__device__ __forceinline__ uint32_t bsub2(uint32_t a, uint32_t b) { uint32_t d; asm("sub.rn.bf16x2 %0, %1, %2;" : "=r"(d) : "r"(a), "r"(b)); return d; }
__device__ __forceinline__ uint32_t bmul2(uint32_t a, uint32_t b) { uint32_t d; asm("mul.rn.bf16x2 %0, %1, %2;" : "=r"(d) : "r"(a), "r"(b)); return d; }
__device__ __forceinline__ uint32_t bfma2(uint32_t a, uint32_t b, uint32_t c) { uint32_t d; asm("fma.rn.bf16x2 %0, %1, %2, %3;" : "=r"(d) : "r"(a), "r"(b), "r"(c)); return d; }
__device__ __forceinline__ uint32_t dup_lo(uint32_t v) { uint32_t d; asm("{ .reg .b16 l, h; mov.b32 {l, h}, %1; mov.b32 %0, {l, l}; }" : "=r"(d) : "r"(v)); return d; }
__device__ __forceinline__ uint32_t dup_hi(uint32_t v) { uint32_t d; asm("{ .reg .b16 l, h; mov.b32 {l, h}, %1; mov.b32 %0, {h, h}; }" : "=r"(d) : "r"(v)); return d; }
__device__ __forceinline__ uint32_t norm2(uint32_t x, uint32_t m, uint32_t hi, uint32_t lo) {
    uint32_t a = bsub2(x, m);
    return bfma2(a, hi, bmul2(a, lo));
}
__device__ __forceinline__ float ex2(float v) { float d; asm("ex2.approx.ftz.f32 %0, %1;" : "=f"(d) : "f"(v)); return d; }
__device__ __forceinline__ float rcp(float v) { float d; asm("rcp.approx.ftz.f32 %0, %1;" : "=f"(d) : "f"(v)); return d; }
__device__ __forceinline__ float sigmoidf_(float v) { return rcp(1.0f + ex2(-1.4426950408889634f * v)); }
__device__ __forceinline__ float siluf_(float v) { return v * sigmoidf_(v); }

__device__ __forceinline__ void mbar_init(uint32_t a, int n) { asm volatile("mbarrier.init.shared::cta.b64 [%0], %1;" :: "r"(a), "r"(n) : "memory"); }
__device__ __forceinline__ void mbar_expect(uint32_t a, int tx) { asm volatile("mbarrier.arrive.expect_tx.shared::cta.b64 _, [%0], %1;" :: "r"(a), "r"(tx) : "memory"); }
__device__ __forceinline__ void mbar_arrive(uint32_t a) { asm volatile("mbarrier.arrive.shared::cta.b64 _, [%0];" :: "r"(a) : "memory"); }
__device__ __forceinline__ void mbar_wait(uint32_t a, int parity) {
    asm volatile("{ .reg .pred p;\n"
                 "W: mbarrier.try_wait.parity.shared::cta.b64 p, [%0], %1;\n"
                 "@!p bra.uni W; }" :: "r"(a), "r"(parity) : "memory");
}
__device__ __forceinline__ uint32_t mapa(uint32_t a, uint32_t rank) { uint32_t d; asm("mapa.shared::cluster.u32 %0, %1, %2;" : "=r"(d) : "r"(a), "r"(rank)); return d; }
__device__ __forceinline__ void st_async4(uint32_t a, uint32_t x, uint32_t y, uint32_t z, uint32_t w, uint32_t bar) {
    asm volatile("st.async.weak.shared::cluster.mbarrier::complete_tx::bytes.v4.b32 [%0], {%1,%2,%3,%4}, [%5];"
                 :: "r"(a), "r"(x), "r"(y), "r"(z), "r"(w), "r"(bar) : "memory");
}
__device__ __forceinline__ void stsm4(uint32_t a, uint32_t r0, uint32_t r1, uint32_t r2, uint32_t r3) {
    asm volatile("stmatrix.sync.aligned.m8n8.x4.shared.b16 [%0], {%1,%2,%3,%4};" :: "r"(a), "r"(r0), "r"(r1), "r"(r2), "r"(r3) : "memory");
}
__device__ __forceinline__ void proxy_fence() { asm volatile("fence.proxy.async.shared::cta;" ::: "memory"); }
__device__ __forceinline__ void bar_sync(int id, int n) { asm volatile("bar.sync %0, %1;" :: "r"(id), "r"(n) : "memory"); }
__device__ __forceinline__ void bar_arrive(int id, int n) { asm volatile("bar.arrive %0, %1;" :: "r"(id), "r"(n) : "memory"); }
__device__ __forceinline__ void cluster_arrive() { asm volatile("barrier.cluster.arrive.relaxed.aligned;" ::: "memory"); }
__device__ __forceinline__ void cluster_wait() { asm volatile("barrier.cluster.wait.aligned;" ::: "memory"); }
__device__ __forceinline__ void tma3d(uint32_t dst, const CUtensorMap* tm, int c0, int c1, uint32_t bar, uint64_t pol) {
    asm volatile("cp.async.bulk.tensor.3d.shared::cluster.global.mbarrier::complete_tx::bytes.L2::cache_hint [%0], [%1, {%3, %4, %6}], [%2], %5;"
                 :: "r"(dst), "l"(tm), "r"(bar), "r"(c0), "r"(c1), "l"(pol), "r"(0) : "memory");
}
__device__ __forceinline__ bool elect() {
    uint32_t p; asm volatile("{ .reg .pred p; elect.sync _|p, 0xFFFFFFFF; selp.u32 %0, 1, 0, p; }" : "=r"(p)); return p;
}

struct cf { float r, i; };
__device__ __forceinline__ cf cmul(cf a, cf b) { return {a.r * b.r - a.i * b.i, a.r * b.i + a.i * b.r}; }
__device__ __forceinline__ cf csq(cf a) { return {a.r * a.r - a.i * a.i, (a.r + a.r) * a.i}; }
__device__ __forceinline__ cf cexp_(float a2, float b) { float m = ex2(a2); return {m * __cosf(b), m * __sinf(b)}; }
struct hc { uint32_t r, i; };
__device__ __forceinline__ hc pk(cf a, cf b) { return {pack_h(a.r, b.r), pack_h(a.i, b.i)}; }
__device__ __forceinline__ hc hmulc(hc a, hc b) {
    const __half2 ar = *reinterpret_cast<__half2*>(&a.r), ai = *reinterpret_cast<__half2*>(&a.i);
    const __half2 br = *reinterpret_cast<__half2*>(&b.r), bi = *reinterpret_cast<__half2*>(&b.i);
    const __half2 r = __hfma2(ar, br, __hneg2(__hmul2_rn(ai, bi))), i = __hfma2(ar, bi, __hmul2_rn(ai, br));
    return {*reinterpret_cast<const uint32_t*>(&r), *reinterpret_cast<const uint32_t*>(&i)};
}
__device__ __forceinline__ void sth(uint32_t a, hc v) { sts32(a, v.r); sts32(a + 128, v.i); }
__device__ __forceinline__ uint32_t cpy(uint32_t v, uint32_t z) { uint32_t d; asm("xor.b32 %0, %1, %2;" : "=r"(d) : "r"(v), "r"(z)); return d; }
__device__ __forceinline__ void sched_fence() { asm volatile("pmevent 0;" ::: "memory"); }
__device__ __forceinline__ float tanh_(float v) { float d; asm("tanh.approx.f32 %0, %1;" : "=f"(d) : "f"(v)); return d; }
__device__ __forceinline__ float silu2(float h) {
    return h * rcp(fmaf(ex2(-2.8853900817779268f * h), 0.5f, 0.5f));
}
__device__ __forceinline__ uint32_t hfma2_(uint32_t a, uint32_t b, uint32_t c) { uint32_t d; asm("fma.rn.f16x2 %0, %1, %2, %3;" : "=r"(d) : "r"(a), "r"(b), "r"(c)); return d; }
__device__ __forceinline__ uint32_t hfms2_(uint32_t a, uint32_t b, uint32_t c) {
    uint32_t d; asm("{ .reg .b32 t; neg.f16x2 t, %1; fma.rn.f16x2 %0, t, %2, %3; }" : "=r"(d) : "r"(a), "r"(b), "r"(c)); return d;
}

__device__ __forceinline__ uint64_t bdesc(uint32_t addr, uint32_t sbo) {
    return (uint64_t)((addr & 0x3FFFFu) >> 4) | ((uint64_t)(128 >> 4) << 16) | ((uint64_t)(sbo >> 4) << 32);
}
__device__ __forceinline__ void wg_h(uint32_t (&d)[16], const uint32_t* a, const uint32_t* b, uint64_t d0, uint64_t d1, uint64_t d2, uint64_t d3) {
    asm volatile(
        "wgmma.mma_async.sync.aligned.m64n64k16.f16.f16.f16 {%0,%1,%2,%3,%4,%5,%6,%7,%8,%9,%10,%11,%12,%13,%14,%15}, {%16,%17,%18,%19}, %32, 0, 1, 1, 1;\n"
        "wgmma.mma_async.sync.aligned.m64n64k16.f16.f16.f16 {%0,%1,%2,%3,%4,%5,%6,%7,%8,%9,%10,%11,%12,%13,%14,%15}, {%20,%21,%22,%23}, %33, 1, 1, 1, 1;\n"
        "wgmma.mma_async.sync.aligned.m64n64k16.f16.f16.f16 {%0,%1,%2,%3,%4,%5,%6,%7,%8,%9,%10,%11,%12,%13,%14,%15}, {%24,%25,%26,%27}, %34, 1, 1, 1, 1;\n"
        "wgmma.mma_async.sync.aligned.m64n64k16.f16.f16.f16 {%0,%1,%2,%3,%4,%5,%6,%7,%8,%9,%10,%11,%12,%13,%14,%15}, {%28,%29,%30,%31}, %35, 1, 1, 1, 1;\n"
        : "=r"(d[0]), "=r"(d[1]), "=r"(d[2]), "=r"(d[3]), "=r"(d[4]), "=r"(d[5]), "=r"(d[6]), "=r"(d[7]), "=r"(d[8]), "=r"(d[9]), "=r"(d[10]), "=r"(d[11]), "=r"(d[12]), "=r"(d[13]), "=r"(d[14]), "=r"(d[15])
        : "r"(a[0]), "r"(a[1]), "r"(a[2]), "r"(a[3]), "r"(a[4]), "r"(a[5]), "r"(a[6]), "r"(a[7]), "r"(b[0]), "r"(b[1]), "r"(b[2]), "r"(b[3]), "r"(b[4]), "r"(b[5]), "r"(b[6]), "r"(b[7]), "l"(d0), "l"(d1), "l"(d2), "l"(d3));
}
__device__ __forceinline__ void wg_f0(float (&d)[32], const uint32_t* a, const uint32_t* b, uint64_t d0, uint64_t d1, uint64_t d2, uint64_t d3) {
    asm volatile(
        "wgmma.mma_async.sync.aligned.m64n64k16.f32.f16.f16 {%0,%1,%2,%3,%4,%5,%6,%7,%8,%9,%10,%11,%12,%13,%14,%15,%16,%17,%18,%19,%20,%21,%22,%23,%24,%25,%26,%27,%28,%29,%30,%31}, {%32,%33,%34,%35}, %48, 0, 1, 1, 1;\n"
        "wgmma.mma_async.sync.aligned.m64n64k16.f32.f16.f16 {%0,%1,%2,%3,%4,%5,%6,%7,%8,%9,%10,%11,%12,%13,%14,%15,%16,%17,%18,%19,%20,%21,%22,%23,%24,%25,%26,%27,%28,%29,%30,%31}, {%36,%37,%38,%39}, %49, 1, 1, 1, 1;\n"
        "wgmma.mma_async.sync.aligned.m64n64k16.f32.f16.f16 {%0,%1,%2,%3,%4,%5,%6,%7,%8,%9,%10,%11,%12,%13,%14,%15,%16,%17,%18,%19,%20,%21,%22,%23,%24,%25,%26,%27,%28,%29,%30,%31}, {%40,%41,%42,%43}, %50, 1, 1, 1, 1;\n"
        "wgmma.mma_async.sync.aligned.m64n64k16.f32.f16.f16 {%0,%1,%2,%3,%4,%5,%6,%7,%8,%9,%10,%11,%12,%13,%14,%15,%16,%17,%18,%19,%20,%21,%22,%23,%24,%25,%26,%27,%28,%29,%30,%31}, {%44,%45,%46,%47}, %51, 1, 1, 1, 1;\n"
        : "=f"(d[0]), "=f"(d[1]), "=f"(d[2]), "=f"(d[3]), "=f"(d[4]), "=f"(d[5]), "=f"(d[6]), "=f"(d[7]), "=f"(d[8]), "=f"(d[9]), "=f"(d[10]), "=f"(d[11]), "=f"(d[12]), "=f"(d[13]), "=f"(d[14]), "=f"(d[15]), "=f"(d[16]), "=f"(d[17]), "=f"(d[18]), "=f"(d[19]), "=f"(d[20]), "=f"(d[21]), "=f"(d[22]), "=f"(d[23]), "=f"(d[24]), "=f"(d[25]), "=f"(d[26]), "=f"(d[27]), "=f"(d[28]), "=f"(d[29]), "=f"(d[30]), "=f"(d[31])
        : "r"(a[0]), "r"(a[1]), "r"(a[2]), "r"(a[3]), "r"(a[4]), "r"(a[5]), "r"(a[6]), "r"(a[7]), "r"(b[0]), "r"(b[1]), "r"(b[2]), "r"(b[3]), "r"(b[4]), "r"(b[5]), "r"(b[6]), "r"(b[7]), "l"(d0), "l"(d1), "l"(d2), "l"(d3));
}
__device__ __forceinline__ void wg_f1(float (&d)[32], const uint32_t* a, const uint32_t* b, uint64_t d0, uint64_t d1, uint64_t d2, uint64_t d3) {
    asm volatile(
        "wgmma.mma_async.sync.aligned.m64n64k16.f32.f16.f16 {%0,%1,%2,%3,%4,%5,%6,%7,%8,%9,%10,%11,%12,%13,%14,%15,%16,%17,%18,%19,%20,%21,%22,%23,%24,%25,%26,%27,%28,%29,%30,%31}, {%32,%33,%34,%35}, %48, 1, 1, 1, 1;\n"
        "wgmma.mma_async.sync.aligned.m64n64k16.f32.f16.f16 {%0,%1,%2,%3,%4,%5,%6,%7,%8,%9,%10,%11,%12,%13,%14,%15,%16,%17,%18,%19,%20,%21,%22,%23,%24,%25,%26,%27,%28,%29,%30,%31}, {%36,%37,%38,%39}, %49, 1, 1, 1, 1;\n"
        "wgmma.mma_async.sync.aligned.m64n64k16.f32.f16.f16 {%0,%1,%2,%3,%4,%5,%6,%7,%8,%9,%10,%11,%12,%13,%14,%15,%16,%17,%18,%19,%20,%21,%22,%23,%24,%25,%26,%27,%28,%29,%30,%31}, {%40,%41,%42,%43}, %50, 1, 1, 1, 1;\n"
        "wgmma.mma_async.sync.aligned.m64n64k16.f32.f16.f16 {%0,%1,%2,%3,%4,%5,%6,%7,%8,%9,%10,%11,%12,%13,%14,%15,%16,%17,%18,%19,%20,%21,%22,%23,%24,%25,%26,%27,%28,%29,%30,%31}, {%44,%45,%46,%47}, %51, 1, 1, 1, 1;\n"
        : "+f"(d[0]), "+f"(d[1]), "+f"(d[2]), "+f"(d[3]), "+f"(d[4]), "+f"(d[5]), "+f"(d[6]), "+f"(d[7]), "+f"(d[8]), "+f"(d[9]), "+f"(d[10]), "+f"(d[11]), "+f"(d[12]), "+f"(d[13]), "+f"(d[14]), "+f"(d[15]), "+f"(d[16]), "+f"(d[17]), "+f"(d[18]), "+f"(d[19]), "+f"(d[20]), "+f"(d[21]), "+f"(d[22]), "+f"(d[23]), "+f"(d[24]), "+f"(d[25]), "+f"(d[26]), "+f"(d[27]), "+f"(d[28]), "+f"(d[29]), "+f"(d[30]), "+f"(d[31])
        : "r"(a[0]), "r"(a[1]), "r"(a[2]), "r"(a[3]), "r"(a[4]), "r"(a[5]), "r"(a[6]), "r"(a[7]), "r"(b[0]), "r"(b[1]), "r"(b[2]), "r"(b[3]), "r"(b[4]), "r"(b[5]), "r"(b[6]), "r"(b[7]), "l"(d0), "l"(d1), "l"(d2), "l"(d3));
}
__device__ __forceinline__ void wg_s(uint32_t* d, const uint32_t* a, const uint32_t* b, uint64_t d0, uint64_t d1) {
    asm volatile(
        "wgmma.mma_async.sync.aligned.m64n32k16.f16.f16.f16 {%0,%1,%2,%3,%4,%5,%6,%7}, {%8,%9,%10,%11}, %16, 0, 1, 1, 1;\n"
        "wgmma.mma_async.sync.aligned.m64n32k16.f16.f16.f16 {%0,%1,%2,%3,%4,%5,%6,%7}, {%12,%13,%14,%15}, %17, 1, 1, 1, 1;\n"
        : "=r"(d[0]), "=r"(d[1]), "=r"(d[2]), "=r"(d[3]), "=r"(d[4]), "=r"(d[5]), "=r"(d[6]), "=r"(d[7])
        : "r"(a[0]), "r"(a[1]), "r"(a[2]), "r"(a[3]), "r"(b[0]), "r"(b[1]), "r"(b[2]), "r"(b[3]), "l"(d0), "l"(d1));
}
template <int ACC> __device__ __forceinline__ void wg_w(float (&d)[4], uint64_t da, uint64_t db) {
    asm volatile("wgmma.mma_async.sync.aligned.m64n8k16.f32.bf16.bf16 {%0,%1,%2,%3}, %4, %5, %6, 1, 1, 1, 0;"
                 : "+f"(d[0]), "+f"(d[1]), "+f"(d[2]), "+f"(d[3]) : "l"(da), "l"(db), "n"(ACC));
}
__device__ __forceinline__ void wg_w0(float (&d)[4], uint64_t da, uint64_t db) {
    asm volatile("wgmma.mma_async.sync.aligned.m64n8k16.f32.bf16.bf16 {%0,%1,%2,%3}, %4, %5, 0, 1, 1, 1, 0;"
                 : "=f"(d[0]), "=f"(d[1]), "=f"(d[2]), "=f"(d[3]) : "l"(da), "l"(db));
}
__device__ __forceinline__ void wg_fence() { asm volatile("wgmma.fence.sync.aligned;" ::: "memory"); }
__device__ __forceinline__ void wg_commit() { asm volatile("wgmma.commit_group.sync.aligned;" ::: "memory"); }
template <int N> __device__ __forceinline__ void wg_wait() { asm volatile("wgmma.wait_group.sync.aligned %0;" :: "n"(N) : "memory"); }
__device__ __forceinline__ void touch(uint32_t& r) { asm volatile("" : "+r"(r) :: "memory"); }
__device__ __forceinline__ void touch(float& r) { asm volatile("" : "+f"(r) :: "memory"); }
template <class T, int N> __device__ __forceinline__ void touch(T (&r)[N]) {
#pragma unroll
    for (int i = 0; i < N; i++) touch(r[i]);
}

__global__ void __cluster_dims__(2, 1, 1) __launch_bounds__(NTHREADS, 1)
fused_kernel(const Params p, const __grid_constant__ CUtensorMap tm_x, const __grid_constant__ CUtensorMap tm_g,
             const __grid_constant__ CUtensorMap tm_d, const __grid_constant__ CUtensorMap tm_o)
{
    extern __shared__ __align__(1024) uint8_t smem_raw[];
    const uint32_t sm = (uint32_t)__cvta_generic_to_shared(smem_raw);
    const uint32_t bars = sm + SM_BAR;
    const int tid = threadIdx.x, lane = tid & 31;
    const int warp = __shfl_sync(0xFFFFFFFFu, tid >> 5, 0);
    const int g = lane >> 2, q = lane & 3;
    const int c = blockIdx.x, rank = c & 1, G = c >> 1;

    if (lane == 0 && warp >= 8) {
        const int v = warp - 8;
        mbar_init(bars + (B_STG + v) * 8, 1);
        mbar_init(bars + (B_EMPTY + v) * 8, 4);
        mbar_init(bars + (B_FULL + v) * 8, 1);
        mbar_init(bars + (B_MISC + v) * 8, (v == 1 || v == 2) ? 2 : 1);
        if (v < 4) mbar_expect(bars + (B_STG + v) * 8, 4096);
        if (v >= 2) mbar_expect(bars + (B_MISC + v) * 8, v == 2 ? 32 : v == 3 ? 2048 : v == 4 ? 65536 : 1536);
        asm volatile("fence.mbarrier_init.release.cluster;" ::: "memory");
    }
    __syncwarp();
    cluster_arrive();

    if (warp < 8) {
        const int ch = c * 8 + warp;
        const uint2 lar4 = __ldg(reinterpret_cast<const uint2*>(p.lar + ch * 128) + lane);
        const uint2 aim4 = __ldg(reinterpret_cast<const uint2*>(p.aim + ch * 128) + lane);
        const uint2 cr4 = __ldg(reinterpret_cast<const uint2*>(p.cr + ch * 128) + lane);
        const uint2 ci4 = __ldg(reinterpret_cast<const uint2*>(p.ci + ch * 128) + lane);
        uint32_t ldt_raw, dsk_raw;
        asm volatile("ld.global.nc.u16 %0, [%1];" : "=r"(ldt_raw) : "l"(p.logdt + ch));
        asm volatile("ld.global.nc.u16 %0, [%1];" : "=r"(dsk_raw) : "l"(p.dskip + ch));
        const float logdt = blo(ldt_raw), dsk = blo(dsk_raw);
        asm volatile("setmaxnreg.inc.sync.aligned.u32 168;");
        const int wgi = warp >> 2, w = warp & 3;
        const uint32_t wb = sm + SM_K + (w < 2 ? 16 * w + 8 * wgi : 16 + 16 * wgi + 8 * w) * SUB;
        sth(wb + lane * 4, hc{0x3C003C00u, 0u});

        const float dt = rb(expf(logdt));
        float outscale, cs, dn;
        {
            uint32_t m0 = __vmaxu2(__vmaxu2(cr4.x & 0x7FFF7FFFu, cr4.y & 0x7FFF7FFFu), __vmaxu2(ci4.x & 0x7FFF7FFFu, ci4.y & 0x7FFF7FFFu));
            uint32_t m1 = max(m0 & 0xFFFFu, m0 >> 16);
            float cmax = blo(__reduce_max_sync(0xFFFFFFFFu, m1));
            const float sc = fminf(fmaxf(fmaxf(2.0f * dt * cmax, fabsf(dsk) * (1.0f / 1024.0f)), 1e-30f), 1e30f);
            outscale = __uint_as_float(__float_as_uint(sc) & 0x7F800000u);
            const float inv = __uint_as_float(0x7F000000u - __float_as_uint(outscale));
            cs = 2.0f * dt * inv;
            dn = dsk * inv;
        }
        TSL(0);
        if (warp == TSW) TSL(39);
        uint32_t fc[16], fs[16], ta[4], tb[4];
        {
            touch(cs);
            sched_fence();
            const uint4* tp = p.tab + (tid & 127);
#pragma unroll
            for (int i = 0; i < 10; i++) {
                const uint4 u = ldg128(tp + i * 128);
                uint32_t* t = i < 4 ? fc + 4 * i : i < 8 ? fs + 4 * (i - 4) : i == 8 ? ta : tb;
                t[0] = u.x; t[1] = u.y; t[2] = u.z; t[3] = u.w;
            }
        }
        float kacc[2][3][4];
#pragma unroll
        for (int i = 0; i < 2; i++)
#pragma unroll
            for (int j = 0; j < 3; j++) kacc[i][j][0] = kacc[i][j][1] = kacc[i][j][2] = kacc[i][j][3] = 0.f;
        if (lane == 0) kacc[0][0][0] = dn;
        {
            const uint32_t st = wb + lane * 4;
            const uint32_t zk = lds32(wb + 128);
            const uint32_t la = wb + ((lane & 8) ? 29 : (lane & 7)) * KP + (lane >> 4) * 128;
            const uint32_t lo = wb + ((lane >> 3) & 1) * 128 + (lane >> 4) * 16;
            const uint32_t lb = lo + (8 + (lane & 7)) * KP, lb2 = lo + (24 + min(lane & 7, 4)) * KP, lm = lo + 30 * KP;
#pragma unroll 1
            for (int s = 0; s < 2; s++) {
                const uint32_t wl = s ? lar4.y : lar4.x, wa = s ? aim4.y : aim4.x, wr_ = s ? cr4.y : cr4.x, wi = s ? ci4.y : ci4.x;
                const uint32_t ea = pack_b(ex2(blo(wl) * 1.4426950408889634f), ex2(bhi(wl) * 1.4426950408889634f));
                const float a2[2] = {-(blo(ea) * dt) * 1.4426950408889634f, -(bhi(ea) * dt) * 1.4426950408889634f};
                const float b[2] = {blo(wa) * dt, bhi(wa) * dt};
                {
                    cf z8[2], z16[2], z32[2], z64[2], z128[2];
#pragma unroll
                    for (int e = 0; e < 2; e++) {
                        z8[e] = cexp_(a2[e] * 8.f, b[e] * 8.f);
                        z16[e] = csq(z8[e]); z32[e] = csq(z16[e]); z64[e] = csq(z32[e]); z128[e] = csq(z64[e]);
                    }
                    const hc r1 = pk(z8[0], z8[1]), r2 = pk(z16[0], z16[1]), r3 = hmulc(r1, r2), r4 = pk(z32[0], z32[1]);
                    sth(st + 1 * KP, r1); sth(st + 2 * KP, r2); sth(st + 3 * KP, r3); sth(st + 4 * KP, r4);
                    sth(st + 5 * KP, hmulc(r1, r4)); sth(st + 6 * KP, hmulc(r2, r4)); sth(st + 7 * KP, hmulc(r3, r4));
                    sth(st + 29 * KP, pk(z64[0], z64[1])); sth(st + 30 * KP, pk(z128[0], z128[1]));
                }
                {
                    cf C[2], z2[2], z4[2], v2[2], v4[2], c1[2], d1[2];
#pragma unroll
                    for (int e = 0; e < 2; e++) {
                        C[e] = {(e ? bhi(wr_) : blo(wr_)) * cs, (e ? bhi(wi) : blo(wi)) * -cs};
                        const cf z = cexp_(a2[e], -b[e]);
                        const cf v = cexp_(a2[e] * 256.f, b[e] * -256.f);
                        z2[e] = csq(z); z4[e] = csq(z2[e]); v2[e] = csq(v); v4[e] = csq(v2[e]);
                        c1[e] = cmul(C[e], z); d1[e] = cmul(C[e], v);
                    }
                    const hc l0 = pk(C[0], C[1]), l1 = pk(c1[0], c1[1]), e1 = pk(d1[0], d1[1]);
                    const hc h = pk(z2[0], z2[1]), f = pk(z4[0], z4[1]), w = pk(v2[0], v2[1]), y = pk(v4[0], v4[1]);
                    const hc l2 = hmulc(l0, h), l3 = hmulc(l1, h), e2 = hmulc(l0, w), e3 = hmulc(e1, w), e4 = hmulc(l0, y), g2 = hmulc(e1, h);
                    sth(st + 8 * KP, l0); sth(st + 9 * KP, l1); sth(st + 10 * KP, l2); sth(st + 11 * KP, l3);
                    sth(st + 12 * KP, hmulc(l0, f)); sth(st + 13 * KP, hmulc(l1, f)); sth(st + 14 * KP, hmulc(l2, f)); sth(st + 15 * KP, hmulc(l3, f));
                    sth(st + 16 * KP, e1);
                    sth(st + 17 * KP, g2);
                    sth(st + 18 * KP, hmulc(e1, f));
                    sth(st + 19 * KP, hmulc(g2, f));
                    sth(st + 20 * KP, e2);
                    sth(st + 21 * KP, hmulc(e2, f));
                    sth(st + 22 * KP, e3);
                    sth(st + 23 * KP, hmulc(e3, f));
                    sth(st + 24 * KP, e4);
                    sth(st + 25 * KP, hmulc(e1, y));
                    sth(st + 26 * KP, hmulc(e2, y));
                    sth(st + 27 * KP, hmulc(e3, y));
                    sth(st + 28 * KP, hmulc(e4, y));
                }
                __syncwarp();
                if (warp == TSW) TSL(s ? 34 : 27);
#pragma unroll
                for (int kp = 0; kp < 4; kp++) {
                    uint32_t bb[3][4], m2[4];
                    ldsm4(lm + kp * 32, m2[0], m2[1], m2[2], m2[3]);
                    ldsm4(lb + kp * 32, bb[0][0], bb[0][1], bb[0][2], bb[0][3]);
                    ldsm4(lb + 8 * KP + kp * 32, bb[1][0], bb[1][1], bb[1][2], bb[1][3]);
                    ldsm4(lb2 + kp * 32, bb[2][0], bb[2][1], bb[2][2], bb[2][3]);
#pragma unroll
                    for (int k2 = 0; k2 < 2; k2++) {
                        hc v0, m1;
                        ldsm4(la + kp * 32 + k2 * 16, v0.r, m1.r, v0.i, m1.i);
                        const hc mm = {m2[2 * k2], m2[2 * k2 + 1]};
                        const hc v1 = hmulc(v0, m1), v2 = hmulc(v0, mm), v3 = hmulc(v1, mm);
                        v0.r = cpy(v0.r, zk); v0.i = cpy(v0.i, zk);
#pragma unroll
                        for (int nt = 0; nt < 3; nt++) {
                            mma_f16(kacc[0][nt], v0.r, v1.r, v0.i, v1.i, bb[nt][2 * k2], bb[nt][2 * k2 + 1]);
                            mma_f16(kacc[1][nt], v2.r, v3.r, v2.i, v3.i, bb[nt][2 * k2], bb[nt][2 * k2 + 1]);
                        }
                    }
                }
                __syncwarp();
                if (warp == TSW) TSL(s ? 40 : 33);
            }
        }
        TSL(1);
        bar_sync(10 + wgi, 128);
        {
            const uint32_t tb_ = sm + SM_S + (16 * wgi + w) * SUB;
            const uint32_t seg = sm + SM_K + (2 * warp + (lane & 1)) * SUB + (lane >> 1) * 16;
            uint32_t v0[4];
#pragma unroll
            for (int m = 0; m < 4; m++) {
                constexpr float S = 1.0f / 512.0f;
                const float (&k0)[4] = kacc[m >> 1][0], (&k1)[4] = kacc[m >> 1][1], (&k2)[4] = kacc[m >> 1][2];
                const int R = 8 * m + g, o = 2 * (m & 1);
                v0[m] = pack_h(k0[o] * S, k0[o + 1] * S);
                sts32(tb_ + (q < 2 ? 4 * R + 2 * q : 64 * q + 2 * R) * 2, pack_h(k1[o] * S, k1[o + 1] * S));
                const uint32_t v2 = pack_h(k2[o] * S, k2[o + 1] * S);
                if (q < 2 || (m == 0 && lane == 2)) sts16(tb_ + (256 + 64 * q + R) * 2, v2);
                if (q < 2) sts16(tb_ + (288 + 64 * q + R) * 2, v2 >> 16);
            }
            stsm4(seg, v0[0], v0[1], v0[2], v0[3]);
            if (lane == 0) sts16(sm + SM_SCL + warp * 2, __float_as_uint(32768.0f * outscale) >> 16);
            __syncwarp();
            const uint2 l1 = lds64(tb_ + lane * 8);
            const uint32_t l1n = lds16(tb_ + lane * 8 + 8);
            uint32_t l2[2], l2n[2], l3[4], l3n[4];
#pragma unroll
            for (int i = 0; i < 2; i++) { l2[i] = lds32(tb_ + 256 + i * 128 + lane * 4); l2n[i] = lds16(tb_ + 260 + i * 128 + lane * 4); }
#pragma unroll
            for (int i = 0; i < 4; i++) { l3[i] = lds16(tb_ + 512 + i * 64 + lane * 2); l3n[i] = lds16(tb_ + 514 + i * 64 + lane * 2); }
            sts128(seg + 256, prmt(l1.x, 0, 0x1010), prmt(l1.x, l1.y, 0x5432), prmt(l1.y, 0, 0x1010), prmt(l1.y, l1n, 0x5432));
#pragma unroll
            for (int i = 0; i < 2; i++) sts128(seg + 512 + i * 256, prmt(l2[i], 0, 0x1010), l2[i], prmt(l2[i], 0, 0x3232), prmt(l2n[i], 0, 0x1010));
            const uint32_t s3 = (lane & 1) ? 0x5454 : 0x5410;
#pragma unroll
            for (int i = 0; i < 4; i++) {
                const uint32_t vv = prmt(l3[i], 0, 0x1010);
                sts128(seg + 16 * SUB + i * 256, vv, vv, prmt(l3[i], l3n[i], s3), prmt(l3n[i], 0, 0x1010));
            }
        }
        proxy_fence();
        TSL(2);
        cluster_wait();
        mbar_wait(bars + B_F2 * 8, 0);
        bar_sync(10 + wgi, 128);
        const uint64_t dre = bdesc(sm + SM_F2 + 512, 256), dim = bdesc(sm + SM_F2, 256);
        uint32_t k0[32], k1[32];
#pragma unroll
        for (int b = 0; b < 2; b++) {
            const uint64_t d1 = bdesc(sm + SM_K + (16 * b + 8 * wgi) * SUB, SUB);
            uint32_t re[16], im[16];
            wg_fence();
            wg_h(re, fc, fc + 8, d1, d1 + 16, d1 + 32, d1 + 48);
            wg_h(im, fs, fs + 8, d1, d1 + 16, d1 + 32, d1 + 48);
            wg_commit();
            wg_wait<0>();
            touch(re); touch(im);
            uint32_t (&kk)[32] = b ? k1 : k0;
#pragma unroll
            for (int hh = 0; hh < 2; hh++) {
#pragma unroll
                for (int i = 8 * hh; i < 8 * hh + 8; i++) {
                    re[i] = hfma2_(ta[i & 3], im[i], re[i]); im[i] = hfms2_(tb[i & 3], re[i], im[i]); re[i] = hfma2_(ta[i & 3], im[i], re[i]);
                }
                wg_fence();
                wg_s(kk + 16 * hh, re + 8 * hh, im + 8 * hh, dre, dim);
                wg_s(kk + 16 * hh + 8, re + 8 * hh + 4, im + 8 * hh + 4, dre, dim);
                wg_commit();
            }
            wg_wait<0>();
            touch(kk);
        }
        {
            const uint32_t sg = (g & 1) ? 0xBC00BC00u : 0x3C003C00u;
#pragma unroll
            for (int i = 0; i < 16; i++) {
                const int r = 8 * (i >> 2) + (i & 3);
                k1[r] = hfms2_(sg, k0[r + 4], k1[r]); k1[r + 4] = hfma2_(sg, k0[r], k1[r + 4]);
            }
            touch(k1);
        }
        if (warp == TSW) TSL(35);
        bar_sync(2, 384);
        asm volatile("setmaxnreg.inc.sync.aligned.u32 208;");
        TSL(3);
        const uint32_t rowo = (16 * w + (lane & 15)) * 16;
        const uint32_t xo = sm + SM_SLAB + wgi * 32768 + (16 * w + g) * 128 + q * 32 + ((rank ^ (g & 1)) * 16);
        const uint32_t peer = mapa(sm, rank ^ 1), so = SM_U + 8 * wgi * SUB + w * 1024 + lane * 16;
#pragma unroll
        for (int b = 0; b < 2; b++) {
            uint32_t gt[4][4];
            uint32_t h[2][4];
            auto load_h = [&](int c0) {
#pragma unroll
                for (int cc = 0; cc < 2; cc++)
                    ldsm4(sm + SM_U + (16 * b + 4 * (c0 + cc) + 2 * (lane >> 4) + wgi) * SUB + rowo, h[cc][0], h[cc][1], h[cc][2], h[cc][3]);
            };
            auto gates = [&](int c0) {
                sched_fence();
#pragma unroll
                for (int cc = 0; cc < 2; cc++)
#pragma unroll
                    for (int i = 0; i < 2; i++) {
                        const float2 f0 = __half22float2(*reinterpret_cast<const __half2*>(&h[cc][i]));
                        const float2 f1 = __half22float2(*reinterpret_cast<const __half2*>(&h[cc][2 + i]));
                        gt[2 * i][c0 + cc] = pack_b(silu2(f0.x), silu2(f1.x)); gt[2 * i + 1][c0 + cc] = pack_b(silu2(f0.y), silu2(f1.y));
                        touch(gt[2 * i][c0 + cc]); touch(gt[2 * i + 1][c0 + cc]);
                    }
                sched_fence();
            };
            const uint32_t zb = sm + (b ? SM_K : SM_S);
            uint32_t re[16], im[16], su[2][16], z[2][16], y[2][16];
            auto twiddle = [&](int hh) {
#pragma unroll
                for (int i = 8 * hh; i < 8 * hh + 8; i++) {
                    re[i] = hfma2_(ta[i & 3], im[i], re[i]); im[i] = hfms2_(tb[i & 3], re[i], im[i]); re[i] = hfma2_(ta[i & 3], im[i], re[i]);
                    touch(re[i]); touch(im[i]);
                }
            };
            auto dft16 = [&](int hh) {
                wg_fence();
                wg_s(su[hh], re + 8 * hh, im + 8 * hh, dre, dim); wg_s(su[hh] + 8, re + 8 * hh + 4, im + 8 * hh + 4, dre, dim);
                wg_commit();
                sched_fence();
            };
            auto product = [&](int hh) {
#pragma unroll
                for (int i = 0; i < 8; i++) {
                    const int r = 8 * (i >> 2) + (i & 3), kr = 16 * hh + r;
                    const hc u = {su[hh][r], su[hh][r + 4]};
                    if (b == 0) {
                        const hc t = hmulc(u, hc{k0[kr], k0[kr + 4]}), pp = hmulc(u, hc{k1[kr], k1[kr + 4]});
                        z[hh][r] = t.r; z[hh][r + 4] = t.i; k1[kr] = pp.r; k1[kr + 4] = pp.i;
                        touch(k1[kr]); touch(k1[kr + 4]);
                    } else {
                        z[hh][r] = hfms2_(u.i, k0[kr + 4], hfma2_(u.r, k0[kr], k1[kr]));
                        z[hh][r + 4] = hfma2_(u.i, k0[kr], hfma2_(u.r, k0[kr + 4], k1[kr + 4]));
                    }
                }
                touch(z[hh]);
            };
            auto idft16 = [&](int hh) {
                wg_fence();
                wg_s(y[hh], z[hh] + 4, z[hh], dre, dim); wg_s(y[hh] + 8, z[hh] + 12, z[hh] + 8, dre, dim);
                wg_commit();
                sched_fence();
            };
            auto untwiddle = [&](int hh) {
#pragma unroll
                for (int i = 0; i < 2; i++) {
                    uint32_t* const yi = y[hh] + 8 * i, * const yr = yi + 4;
#pragma unroll
                    for (int n = 0; n < 4; n++) {
                        yr[n] = hfms2_(ta[n], yi[n], yr[n]); yi[n] = hfma2_(tb[n], yr[n], yi[n]); yr[n] = hfms2_(ta[n], yi[n], yr[n]);
                    }
                    const uint32_t a = zb + (16 * wgi + 8 * hh + 4 * i + (lane >> 4)) * SUB + rowo;
                    stsm4(a, yr[0], yr[1], yr[2], yr[3]);
                    stsm4(a + 2 * SUB, yi[0], yi[1], yi[2], yi[3]);
                }
            };
            auto done = [&]() { sched_fence(); wg_wait<0>(); };
            auto flush = [&](int bb) {
                mbar_wait(bars + (B_STG + 2 * bb + wgi) * 8, 0);
                const uint4 r0 = lds128(sm + so + 16 * bb * SUB), r1 = lds128(sm + so + 16 * bb * SUB + 512);
                const uint32_t a = (xo ^ 16) + bb * 8192 + rank * 16384;
                sts128(a, r0.x, r0.y, r0.z, r0.w); sts128(a + 1024, r1.x, r1.y, r1.z, r1.w);
                proxy_fence();
                __syncwarp();
                if (lane == 0) {
                    asm volatile("cp.async.bulk.tensor.5d.global.shared::cta.bulk_group [%0, {%2, %3, %4, %5, %6}], [%1];"
                                 :: "l"(&tm_o), "r"(sm + SM_SLAB + wgi * 32768 + rank * 16384 + bb * 8192 + w * 2048),
                                    "r"(G * 16), "r"(0), "r"(64 * bb + 16 * w), "r"(rank), "r"(wgi) : "memory");
                    asm volatile("cp.async.bulk.commit_group;" ::: "memory");
                }
                __syncwarp();
            };
            {
                const uint64_t d1 = bdesc(sm + SM_U + (16 * b + 8 * wgi) * SUB, SUB);
                if (wgi) { load_h(0); gates(0); }
                wg_fence();
                wg_h(re, fc, fc + 8, d1, d1 + 16, d1 + 32, d1 + 48);
                wg_h(im, fs, fs + 8, d1, d1 + 16, d1 + 32, d1 + 48);
                wg_commit();
                if (b) flush(0);
                wg_wait<0>();
                touch(re); touch(im);
            }
            twiddle(0); dft16(0);
            twiddle(1); done(); touch(su[0]); dft16(1);
            product(0); done(); touch(su[1]); idft16(0);
            product(1); done(); touch(y[0]); idft16(1);
            untwiddle(0); done(); touch(y[1]);
            untwiddle(1);
            proxy_fence();
            if (!wgi) { load_h(0); gates(0); }
            load_h(2);
            uint4 xv[4];
#pragma unroll
            for (int i = 0; i < 4; i++) xv[i] = lds128(xo + b * 8192 + (i & 1) * 16384 + (i >> 1) * 1024);
            if (warp == TSW) TSL(36 + b);
            bar_sync(1, 256);
            if (warp == 0 && lane == 0) asm volatile("mbarrier.arrive.relaxed.cluster.shared::cluster.b64 _, [%0];" :: "r"(peer + SM_BAR + B_PEER * 8) : "memory");
            if (b == 0) TSL(4);
            float acc[32];
            const uint64_t d4 = bdesc(zb + wgi * SUB, 4 * SUB);
            if (wgi == 1) bar_sync(5, 256);
            wg_fence();
            wg_f0(acc, fc, fc + 8, d4, d4 + 16, d4 + 32, d4 + 48);
            wg_f1(acc, fs, fs + 8, d4 + SUB / 8, d4 + SUB / 8 + 16, d4 + SUB / 8 + 32, d4 + SUB / 8 + 48);
            wg_commit();
            if (wgi == 0) bar_arrive(5, 256);
            gates(2);
            if (b == 0) mbar_wait(bars + B_TOK * 8, 0);
            mbar_wait(bars + B_PEER * 8, b);
            const uint2 tk = lds64(sm + SM_TOK);
            const uint4 sc = lds128(sm + SM_SCL);
            wg_wait<0>();
            touch(acc);
            uint32_t s[4][4], o[4][4];
#pragma unroll
            for (int i = 0; i < 4; i++) {
#pragma unroll
                for (int j = 0; j < 4; j++) s[i][j] = pack_b(acc[8 * j + i], acc[8 * j + 4 + i]);
                o[i][0] = bfma2(bmul2(s[i][0], gt[i][0]), sc.x, xv[i].x); o[i][1] = bfma2(bmul2(s[i][1], gt[i][1]), sc.y, xv[i].y);
                o[i][2] = bfma2(bmul2(s[i][2], gt[i][2]), sc.z, xv[i].z); o[i][3] = bfma2(bmul2(s[i][3], gt[i][3]), sc.w, xv[i].w);
            }
            const uint32_t sb = SM_BAR + (B_STG + 2 * b + wgi) * 8;
#pragma unroll
            for (int e = 0; e < 2; e++)
                if (e == rank) {
#pragma unroll
                    for (int hi = 0; hi < 2; hi++) {
                        const uint32_t (&r)[4] = o[2 * hi + 1 - e], (&l)[4] = o[2 * hi + e];
                        st_async4(peer + so + 16 * b * SUB + hi * 512, r[0], r[1], r[2], r[3], peer + sb);
                        sts128(xo + b * 8192 + e * 16384 + hi * 1024, l[0], l[1], l[2], l[3]);
                    }
                }
            if (warp == TSW) TSL(5 + b);
#pragma unroll
            for (int k = 0; k < 2; k++) {
                const int t = k ? tk.y : tk.x;
                if ((t & ~0x81) == 1024 * b + 256 * w + 16 * g + 8 * wgi + 2 * q) {
                    uint32_t f[4];
#pragma unroll
                    for (int j = 0; j < 4; j++) {
                        const uint32_t lo = (t & 1) ? s[1][j] : s[0][j], hi = (t & 1) ? s[3][j] : s[2][j];
                        f[j] = (t & 128) ? hi : lo;
                    }
                    const uint32_t dst = mapa(sm, k);
                    st_async4(dst + SM_FIX + rank * 16, bmul2(f[0], sc.x), bmul2(f[1], sc.y), bmul2(f[2], sc.z), bmul2(f[3], sc.w),
                              dst + SM_BAR + B_FIX * 8);
                }
            }
            __syncwarp();
            if (b) {
                flush(1);
                TSL(7);
                if (lane == 0) {
#pragma unroll
                    for (int bb = 0; bb < 2; bb++) {
                        if (bb == 0) asm volatile("cp.async.bulk.wait_group 1;" ::: "memory"); else asm volatile("cp.async.bulk.wait_group 0;" ::: "memory");
#pragma unroll
                        for (int k = 0; k < 2; k++)
                            if (((k ? tk.y : tk.x) & 0x709) == 1024 * bb + 256 * w + 8 * wgi + rank)
                                asm volatile("mbarrier.arrive.release.cluster.shared::cluster.b64 _, [%0];" :: "r"(mapa(bars + B_FIX * 8, k)) : "memory");
                    }
                }
            }
        }
        TSL(17); TG(30);
    } else if (warp < 12) {
        const int v = warp - 8;
        const uint32_t xs = sm + SM_U + v * 8192;
        if (elect()) {
#pragma unroll
            for (int r = 0; r < 4; r++) mbar_init(bars + (B_ROW + 4 * v + r) * 8, 1);
            asm volatile("fence.mbarrier_init.release.cluster;" ::: "memory");
#pragma unroll
            for (int r = 0; r < 4; r++) {
                mbar_expect(bars + (B_ROW + 4 * v + r) * 8, 2048);
                asm volatile("cp.async.bulk.shared::cluster.global.mbarrier::complete_tx::bytes [%0], [%1], 2048, [%2];"
                             :: "r"(xs + r * 2048), "l"(p.x + (size_t)(32 * (c & 63) + 16 * (v >> 1) + 8 * (c >> 6) + 4 * (v & 1) + r) * 1024),
                                "r"(bars + (B_ROW + 4 * v + r) * 8) : "memory");
            }
        }
        __syncwarp();
        uint4 w4[4];
#pragma unroll
        for (int k = 0; k < 4; k++) w4[k] = ldg128(reinterpret_cast<const uint4*>(p.wr) + 32 * k + lane);
        uint32_t* const my_part = p.sc->part + ((2 * (32 * rank + v) + (q & 1)) * 56 + G) * 16 + g + 8 * (q >> 1);
        if (G < 56) {
#pragma unroll
            for (int n = 0; n < 8; n++) st_relaxed32(my_part + n * 8 * 56 * 16, 0);
        }
        {
            constexpr uint32_t ONE = 0x3F803F80u;
            const uint32_t zr = p.up_first >> 1;
#pragma unroll
            for (int k = 0; k < 4; k++) { w4[k].x = cpy(w4[k].x, zr); w4[k].y = cpy(w4[k].y, zr); w4[k].z = cpy(w4[k].z, zr); w4[k].w = cpy(w4[k].w, zr); }
            const bool od = g & 1;
#pragma unroll 1
            for (int r = 0; r < 4; r++) {
                mbar_wait(bars + (B_ROW + 4 * v + r) * 8, 0);
                TSL(43);
                uint4 x[4];
#pragma unroll
                for (int k = 0; k < 4; k++) x[k] = lds128(xs + r * 2048 + k * 512 + lane * 16);
                float s1[4] = {0, 0, 0, 0}, q0[4] = {0, 0, 0, 0}, q1[4] = {0, 0, 0, 0};
#pragma unroll
                for (int k = 0; k < 4; k++) {
                    mma_bf16(q0, cpy(x[k].x, zr), w4[k].x, cpy(x[k].y, zr), w4[k].y, x[k].x, x[k].y);
                    mma_bf16(q1, cpy(x[k].z, zr), w4[k].z, cpy(x[k].w, zr), w4[k].w, x[k].z, x[k].w);
                    mma_bf16(s1, x[k].x, x[k].y, x[k].z, x[k].w, ONE, ONE);
                }
                const float qq = (od ? q0[1] : q0[0]) + (od ? q1[1] : q1[0]), ww = (od ? q0[3] : q0[2]) + (od ? q1[3] : q1[2]);
                if (q == (g >> 1))
                    sts128(sm + SM_RED + (4 * v + r) * 144 + g * 16, __float_as_uint(qq), __float_as_uint(ww), __float_as_uint(s1[0]), __float_as_uint(s1[2]));
            }
            bar_arrive(7, 160);
        }
        TSL(8);
        bar_sync(6, 192);
        const uint32_t tag = lds32(sm + SM_TOK + 8);
        cluster_wait();
        {
            uint4 st[8] = {};
            const uint4* src = p.sc->stats + 64 * v + lane;
            const uint32_t tb = ((tag & 1) << 15) | ((tag >> 1) << 31);
#pragma unroll
            for (int i = 0; i < 8; i++) st[i].y = ~tb;
            int it = 0;
            bool ok;
            if (warp == 8) TSL(44);
            do {
                uint32_t bad = 0;
#pragma unroll
                for (int i = 0; i < 8; i++)
                    asm volatile("{ .reg .pred p; .reg .b128 t; setp.ne.u32 p, %5, 0; mov.b128 t, {%0,%1,%2,%3};\n"
                                 "@p ld.relaxed.gpu.global.b128 t, [%4]; mov.b128 {%0,%1,%2,%3}, t; }"
                                 : "+r"(st[i].x), "+r"(st[i].y), "+r"(st[i].z), "+r"(st[i].w)
                                 : "l"(src + (i >> 2) * 256 + ((i >> 1) & 1) * 512 + (i & 1) * 32), "r"((st[i].y ^ tb) & 0x80008000u) : "memory");
#pragma unroll
                for (int i = 0; i < 8; i++) bad |= st[i].y ^ tb;
                ok = __all_sync(0xFFFFFFFFu, (bad & 0x80008000u) == 0);
                if (warp == 8 && it == 0) TSL(45);
            } while (!ok && ++it < SPIN_LIMIT);
            TSL(11); TG(31);
            uint32_t h1[8], h2[8];
#pragma unroll
            for (int i = 0; i < 8; i++) {
                const uint32_t o2 = st[i].w ^ (prmt(st[i].w, 0, 0xBB99) | 0x80008000u);
                const uint32_t id = 0xFFFF - (256 * v + 16 * g + 2 * q) - ((i >> 2) * 1024 + ((i >> 1) & 1) * 8 + (i & 1) * 128);
                const uint32_t k0 = prmt(o2, id, 0x1054), k1 = prmt(o2, id - 1, 0x3254);
                h1[i] = max(k0, k1); h2[i] = min(k0, k1);
            }
#pragma unroll
            for (int n = 4; n > 0; n >>= 1)
#pragma unroll
                for (int i = 0; i < n; i++) { h2[i] = __vimax3_u32(min(h1[i], h1[i + n]), h2[i], h2[i + n]); h1[i] = max(h1[i], h1[i + n]); }
            const uint32_t w1 = __reduce_max_sync(0xFFFFFFFFu, h1[0]);
            const uint32_t w2 = __reduce_max_sync(0xFFFFFFFFu, h1[0] == w1 ? h2[0] : h1[0]);
            if (lane == 0) sts64(sm + SM_KEYS + v * 8, w1, w2);
            bar_arrive(3, 192);
#pragma unroll
            for (int i = 0; i < 8; i++) { st[i].y = bmul2(st[i].y & 0x7FFF7FFFu, 0x3F003F00u); st[i].z = bmul2(st[i].z, 0x3F003F00u); }
            mbar_wait(bars + B_SLAB * 8, 0);
            TSL(10);
            const uint32_t a = sm + SM_SLAB + (16 * v + g) * 128 + q * 32 + ((rank ^ (g & 1)) * 16);
            const uint32_t ua = sm + SM_U + (lane >> 4) * SUB + (16 * v + (lane & 15)) * 16;
#pragma unroll
            for (int b = 0; b < 2; b++) {
                uint32_t o[8][4];
#pragma unroll
                for (int i = 0; i < 4; i++) {
                    const uint4 e = lds128(a + b * 8192 + (i >> 1) * 32768 + (i & 1) * 1024), d = lds128(a + b * 8192 + (i >> 1) * 32768 + (i & 1) * 1024 + 16384);
                    const uint4& t = st[4 * b + i];
                    const uint32_t xe[4] = {e.x, e.y, e.z, e.w}, xd[4] = {d.x, d.y, d.z, d.w};
#pragma unroll
                    for (int n = 0; n < 4; n++) {
                        const uint32_t ne = norm2(xe[n], dup_lo(t.x), dup_lo(t.y), dup_lo(t.z)), nd = norm2(xd[n], dup_hi(t.x), dup_hi(t.y), dup_hi(t.z));
                        o[2 * n][i] = pack_h(blo(ne), blo(nd)); o[2 * n + 1][i] = pack_h(bhi(ne), bhi(nd));
                    }
                }
#pragma unroll
                for (int cc = 0; cc < 8; cc++) stsm4(ua + (16 * b + 2 * cc) * SUB, o[cc][0], o[cc][1], o[cc][2], o[cc][3]);
            }
            proxy_fence();
            bar_arrive(2, 384);
        }
        TSL(12);
        {
            asm volatile("setmaxnreg.dec.sync.aligned.u32 40;");
            if (G < 56) {
                const uint64_t dw = (uint64_t)(((sm + SM_RING) & 0x3FFFFu) >> 4) | (1ull << 16) | (64ull << 32) | (1ull << 62);
                const uint64_t dx = (uint64_t)(((sm + SM_XSEL + rank * 2048) & 0x3FFFFu) >> 4) | (2ull << 16) | (8ull << 32);
                const uint64_t dh = (uint64_t)(((sm + SM_H) & 0x3FFFFu) >> 4) | (8ull << 16) | (8ull << 32);
                float ag[4] = {0, 0, 0, 0}, au[4] = {0, 0, 0, 0};
                touch(ag); touch(au);
                mbar_wait(bars + B_TOK * 8, 0);
                TSL(13);
                int slot = 0, ph = 0;
#pragma unroll 1
                for (int n = 0; n < 16; n++) {
                    mbar_wait(bars + (B_FULL + slot) * 8, ph);
                    const uint64_t a = dw + slot * 512, b = dx + n * 8;
                    wg_fence();
                    wg_w<1>(ag, a, b); wg_w<1>(au, a + 256, b); wg_w<1>(ag, a + 128, b + 4); wg_w<1>(au, a + 384, b + 4);
                    wg_commit();
                    wg_wait<0>();
                    touch(ag); touch(au);
                    if (lane == 0) mbar_arrive(bars + (B_EMPTY + slot) * 8);
                    if (++slot == NSLOT) { slot = 0; ph ^= 1; }
                }
                TSL(14);
                if (q == 0) {
#pragma unroll
                    for (int r = 0; r < 2; r++) {
                        const uint32_t dst = mapa(sm, r), o = dst + SM_PAIR + rank * 1024 + v * 256 + g * 32;
                        st_async4(o, __float_as_uint(ag[0]), __float_as_uint(ag[1]), __float_as_uint(ag[2]), __float_as_uint(ag[3]), dst + SM_BAR + B_PAIR * 8);
                        st_async4(o + 16, __float_as_uint(au[0]), __float_as_uint(au[1]), __float_as_uint(au[2]), __float_as_uint(au[3]), dst + SM_BAR + B_PAIR * 8);
                    }
                }
                mbar_wait(bars + B_PAIR * 8, 0);
                {
                    const uint32_t o = sm + SM_PAIR + v * 256 + g * 32 + q * 4, og = o + (p.up_first ? 16 : 0), ou = o + (p.up_first ? 0 : 16);
                    const float gs = rb(__uint_as_float(lds32(og)) + __uint_as_float(lds32(og + 1024)));
                    const float us = rb(__uint_as_float(lds32(ou)) + __uint_as_float(lds32(ou + 1024)));
                    const float hv = rb(siluf_(gs)) * us;
                    const uint32_t hd = sm + SM_H + (2 * v + (q >> 1)) * 128 + (q & 1) * 32 + g * 2, hb = pack_b(hv, hv);
                    sts16(hd, hb); sts16(hd + 64, hb);
                }
                proxy_fence();
                bar_sync(4, 128);
                TSL(15);
#pragma unroll 1
                for (int n = 0; n < 8; n++) {
                    mbar_wait(bars + (n == 7 ? full_bar(23) : B_FULL + slot) * 8, n == 7 ? 0 : ph);
                    const uint64_t a = dw + slot * 512;
                    float d[4];
                    wg_fence();
                    wg_w0(d, a, dh); wg_w<1>(d, a + 128, dh + 16); wg_w<1>(d, a + 256, dh + 32); wg_w<1>(d, a + 384, dh + 48);
                    wg_commit();
                    wg_wait<0>();
                    touch(d);
                    st_relaxed32(my_part + n * 8 * 56 * 16, (__float_as_uint((q & 2) ? d[2] : d[0]) & ~3u) | tag);
                    if (lane == 0) mbar_arrive(bars + (B_EMPTY + slot) * 8);
                    if (++slot == NSLOT) { slot = 0; ph ^= 1; }
                }
                TSL(16);
            }
        }
    } else {
        asm volatile("setmaxnreg.dec.sync.aligned.u32 48;");
        cluster_wait();
        if (warp == 12) {
            TSL(19);
            const bool lead = elect();
            if (lead) {
                sts32(sm + SM_TOK + 12, 0);
                asm volatile("cp.async.bulk.tensor.5d.shared::cluster.global.mbarrier::complete_tx::bytes.multicast::cluster"
                             " [%0], [%1, {%3, %4, %4, %4, %5}], [%2], %6;"
                             :: "r"(sm + SM_SLAB + rank * 32768), "l"(&tm_x), "r"(bars + B_SLAB * 8), "r"(G * 16), "r"(0), "r"(rank), "h"((uint16_t)3) : "memory");
            }
            TSL(20);
            if (G < 56) {
                uint64_t pol; asm volatile("createpolicy.fractional.L2::evict_first.b64 %0, 1.0;" : "=l"(pol));
                int ws = 0, wp = 0, slot = 0, ep = 1;
#pragma unroll 1
                for (int n = 0; n < 24; n++) {
                    if (n >= DEPTH) {
                        mbar_wait(bars + (B_FULL + ws) * 8, wp);
                        if (++ws == NSLOT) { ws = 0; wp ^= 1; }
                    }
                    mbar_wait(bars + (B_EMPTY + slot) * 8, ep);
                    if (lead) {
                        const uint32_t fb = bars + (n == 23 ? full_bar(23) : B_FULL + slot) * 8;
                        const bool gu = n < 16;
                        mbar_expect(fb, 8192);
                        tma3d(sm + SM_RING + slot * 8192, gu ? &tm_g : &tm_d, gu ? G * 64 : rank * 512 + (n - 16) * 64, gu ? rank * 512 + n * 32 : G * 64, fb, pol);
                        sts32(sm + SM_TOK + 12, n + 1);
                    }
                    if (++slot == NSLOT) { slot = 0; ep ^= 1; }
                }
                TSL(23);
            }
        } else if (warp == 13) {
            if (lane == 0) { asm volatile("prefetch.tensormap [%0];" :: "l"(&tm_d) : "memory"); asm volatile("prefetch.tensormap [%0];" :: "l"(&tm_o) : "memory"); }
            if (lane == 0) asm volatile("cp.async.bulk.shared::cluster.global.mbarrier::complete_tx::bytes [%0], [%1], 1536, [%2];"
                                        :: "r"(sm + SM_F2), "l"(p.tab + 1280), "r"(bars + B_F2 * 8) : "memory");
            if (G < 56) {
                const bool lead = elect();
                int n = NSLOT;
#pragma unroll 1
                for (; n < 24; n++) {
                    const int m = n - DEPTH;
                    if (m < NSLOT) asm volatile("{ .reg .pred p; mbarrier.try_wait.parity.shared::cta.b64 p, [%0], 0;\n"
                                                "@!p mbarrier.try_wait.parity.shared::cta.b64 p, [%0], 0; @!p pmevent 1; }" :: "r"(bars + (B_FULL + m) * 8) : "memory");
                    else mbar_wait(bars + (B_PROBE + ((m - NSLOT) & 3)) * 8, ((m - NSLOT) >> 2) & 1);
                    uint32_t issued;
                    asm volatile("ld.volatile.shared.u32 %0, [%1];" : "=r"(issued) : "r"(sm + SM_TOK + 12) : "memory");
                    if ((int)issued >= n && n > NSLOT) break;
                    if (lead) {
                        const bool gu = n < 16;
                        const int c0 = gu ? G * 64 : rank * 512 + (n - 16) * 64, c1 = gu ? rank * 512 + n * 32 : G * 64;
                        asm volatile("cp.async.bulk.prefetch.tensor.3d.L2.global [%0, {%1, %2, %3}];" :: "l"(gu ? &tm_g : &tm_d), "r"(c0), "r"(c1), "r"(0) : "memory");
                        const uint32_t pb = bars + (B_PROBE + ((n - NSLOT) & 3)) * 8;
                        mbar_expect(pb, 16);
                        asm volatile("cp.async.bulk.shared::cluster.global.mbarrier::complete_tx::bytes [%0], [%1], 16, [%2];"
                                     :: "r"(sm + SM_PROBE + ((n - NSLOT) & 3) * 16),
                                        "l"(gu ? p.w2 + (size_t)(c1 + 31) * 3584 + c0 : p.wd + (size_t)(c1 + 63) * 1024 + c0), "r"(pb) : "memory");
                    }
                }
#pragma unroll 1
                for (int m = max(n - DEPTH, NSLOT); m < n; m++) mbar_wait(bars + (B_PROBE + ((m - NSLOT) & 3)) * 8, ((m - NSLOT) >> 2) & 1);
                TSL(41);
            }
        } else {
            const int sw = warp - 14;
            uint32_t tag;
            if (sw == 0) {
                uint4* const my_stats = p.sc->stats + c * 8 + (lane >> 2);
                asm volatile("ld.relaxed.gpu.global.u32 %0, [%1];" : "=r"(tag) : "l"(&p.sc->epoch) : "memory");
                float ws = 0.f;
#pragma unroll
                for (int k = 0; k < 4; k++) {
                    const uint4 w = ldg128(reinterpret_cast<const uint4*>(p.wr) + 32 * k + lane);
                    ws += (blo(w.x) + bhi(w.x)) + (blo(w.y) + bhi(w.y)) + (blo(w.z) + bhi(w.z)) + (blo(w.w) + bhi(w.w));
                }
                if (q == 0) st_relaxed128(my_stats, make_uint4(0, 0, 0, 0));
                tag = tag % 3 + 1;
                sts32(sm + SM_TOK + 8, tag);
                bar_arrive(6, 192);
#pragma unroll
                for (int o = 1; o < 32; o <<= 1) ws += __shfl_xor_sync(0xFFFFFFFFu, ws, o);
                const uint32_t tb = ((tag & 1) << 15) | ((tag >> 1) << 31);
                const uint32_t ra = sm + SM_RED + (lane >> 1) * 144 + (lane & 1) * 64;
                touch(ws);
                bar_sync(7, 160);
                const uint4 a0 = lds128(ra), a1 = lds128(ra + 16), a2 = lds128(ra + 32), a3 = lds128(ra + 48);
#define F(v) __uint_as_float(v)
                float ss = (F(a0.x) + F(a1.x)) + (F(a2.x) + F(a3.x)), dw = (F(a0.y) + F(a1.y)) + (F(a2.y) + F(a3.y));
                float sx = ((F(a0.z) + F(a1.z)) + (F(a2.z) + F(a3.z))) + ((F(a0.w) + F(a1.w)) + (F(a2.w) + F(a3.w)));
#undef F
                ss += __shfl_xor_sync(0xFFFFFFFFu, ss, 1); dw += __shfl_xor_sync(0xFFFFFFFFu, dw, 1); sx += __shfl_xor_sync(0xFFFFFFFFu, sx, 1);
                const float mean = sx * (1.0f / 1024.0f);
                const float var = fmaxf(ss * (1.0f / 1024.0f) - mean * mean, 0.f);
                const float m = rb(mean);
                float sd; asm("sqrt.approx.ftz.f32 %0, %1;" : "=f"(sd) : "f"(rb(rb(var) + 1e-5f)));
                const float rs = rcp(rb(sd));
                const float hi = rb(rs);
                const uint32_t p0 = pack_b(m, hi), p1 = pack_b(rs - hi, rs * (dw - m * ws));
                const uint32_t o0 = __shfl_xor_sync(0xFFFFFFFFu, p0, 2), o1 = __shfl_xor_sync(0xFFFFFFFFu, p1, 2);
                if (q == 0) st_relaxed128(my_stats, make_uint4(prmt(p0, o0, 0x5410), (prmt(p0, o0, 0x7632) & 0x7FFF7FFFu) | tb,
                                                               prmt(p1, o1, 0x5410), prmt(p1, o1, 0x7632)));
                TSL(9);
            } else {
                bar_sync(6, 192);
                tag = lds32(sm + SM_TOK + 8);
            }
            bar_sync(3, 192);
            const uint32_t kk = lane < 8 ? lds32(sm + SM_KEYS + lane * 4) : 0u;
            const uint32_t m1 = __reduce_max_sync(0xFFFFFFFFu, kk);
            const uint32_t m2 = __reduce_max_sync(0xFFFFFFFFu, kk == m1 ? 0u : kk);
            const uint32_t key = sw ? m2 : m1;
            const int t = (0xFFFF - (key & 0xFFFF)) & 2047;
            {
                const uint4* row = reinterpret_cast<const uint4*>(p.x + (size_t)t * 1024) + lane;
                uint4 xr[4];
#pragma unroll
                for (int i = 0; i < 4; i++) xr[i] = ldg128(row + 32 * i);
                const uint4 stk = ld_relaxed128(p.sc->stats + (((t >> 3) & 1) * 128 + (t >> 4)) * 4 + ((t >> 1) & 3));
                if (lane == 0) {
                    sts32(sm + SM_TOK + 4 * sw, t);
                    if (c == 0 && sw == 0) st_relaxed32(&p.sc->epoch, tag);
                }
                const uint32_t se = (t & 1) ? 0x3232 : 0x1010;
                const uint32_t m = prmt(stk.x, 0, se), hi = prmt(stk.y, 0, se) & 0x7FFF7FFFu, lo = prmt(stk.z, 0, se);
                const uint32_t a = sm + SM_XSEL + lane * 32 + sw * 16;
#pragma unroll
                for (int i = 0; i < 4; i++) {
                    sts128(a + i * 1024, norm2(xr[i].x, m, hi, lo), norm2(xr[i].y, m, hi, lo), norm2(xr[i].z, m, hi, lo), norm2(xr[i].w, m, hi, lo));
                    if (sw == rank && 16 * i + (lane >> 1) == G) sts128(sm + SM_XRAW + (lane & 1) * 16, xr[i].x, xr[i].y, xr[i].z, xr[i].w);
                }
                proxy_fence();
                __syncwarp();
                if (lane == 0) mbar_arrive(bars + B_TOK * 8);
                TSL(42);
            }
            if (sw == rank) {
                const int col = 4 * q + 2 * (lane >> 4) + ((lane >> 3) & 1), d = G * 16 + col;
                const float r = __uint_as_float((key & 0x80000000u) ? (key & 0x7FFF0000u) : (~key & 0xFFFF0000u));
                const float sg = rb(sigmoidf_(r));
                const float xn = blo(lds16(sm + SM_XSEL + (d >> 3) * 32 + rank * 16 + (d & 7) * 2));
                const float xv = blo(lds16(sm + SM_XRAW + col * 2));
                mbar_wait(bars + (G < 56 ? full_bar(23) : B_STG + 2) * 8, 0);
                TSL(24);
                const uint4* src = reinterpret_cast<const uint4*>(p.sc->part) + c * 224 + lane;
                float s0 = 0, s1 = 0, s2 = 0, s3 = 0;
                {
                    uint4 pv[7];
                    int it = 0;
                    bool ok;
                    do {
                        uint32_t bad = 0;
#pragma unroll
                        for (int i = 0; i < 7; i++) pv[i] = ld_relaxed128(src + 32 * i);
#pragma unroll
                        for (int i = 0; i < 7; i++) bad |= (pv[i].x ^ tag) | (pv[i].y ^ tag) | (pv[i].z ^ tag) | (pv[i].w ^ tag);
                        ok = __all_sync(0xFFFFFFFFu, (bad & 3) == 0);
                    } while (!ok && ++it < SPIN_LIMIT);
#pragma unroll
                    for (int i = 0; i < 7; i++) {
                        s0 += __uint_as_float(pv[i].x); s1 += __uint_as_float(pv[i].y); s2 += __uint_as_float(pv[i].z); s3 += __uint_as_float(pv[i].w);
                    }
                }
                TSL(25);
                const bool u16 = lane & 16, u8 = lane & 8;
                const float y0 = (u16 ? s2 : s0) + __shfl_xor_sync(0xFFFFFFFFu, u16 ? s0 : s2, 16);
                const float y1 = (u16 ? s3 : s1) + __shfl_xor_sync(0xFFFFFFFFu, u16 ? s1 : s3, 16);
                float y = (u8 ? y1 : y0) + __shfl_xor_sync(0xFFFFFFFFu, u8 ? y0 : y1, 8);
                y += __shfl_xor_sync(0xFFFFFFFFu, y, 4);
                const float z = rb(xn + rb(rb(y) * sg));
                const float gt = rb(siluf_(z));
                mbar_wait(bars + B_FIX * 8, 0);
                const float o = xv + rb(blo(lds16(sm + SM_FIX + col * 2)) * gt);
                if (!(lane & 4)) p.out[(size_t)t * 1024 + d] = __float2bfloat16(o);
                TSL(26); TG(29);
            }
        }
    }
}

__device__ __align__(128) const uint32_t g_tab[5504] = {
0x2fff3000,0x2e7c2fd4,0x2fc92fd4,0xad72af5a,0x2ff82ffc,0x230e2c07,0x2faf2fbc,0x217ea934,0x2fed2ff4,0xad4da8d5,0x2f912fa0,0x2e5e2bb7,
0x2fdd2fe6,0xb000af46,0x2f6e2f80,0x2fdd2fc9,0x2ff42fff,0x2e1f2fc9,0x2e1f2e7c,0xa875ad72,0x2fbc2fdd,0x9fd92a4e,0x2d4d2dba,0x2cd825db,
0x2f5a2f91,0xaeb5ac07,0x2c5d2cd8,0x30002f30,0x2ed02f1a,0xaf80aff4,0x2aaa2bb7,0x2cb02f1a,0x2fdd2ffc,0x2dba2fbc,0x2a4e2c07,0x25dba934,
0x2f462fa0,0xa7652875,0x25152875,0x2f802d27,0x2e3f2ed0,0xafa0ad72,0xa17e1cb6,0x2e3f2fe6,0x2cd82d96,0xadfeafd4,0xa934a6a1,0xa44e29f1,
0x2fbc2ff8,0x2d4d2faf,0x9fd9230e,0x2cd8217e,0x2e992f46,0xaa4e2515,0xaa4ea765,0x2fd42f80,0x2cb02dba,0xafffae99,0xad72ac5d,0x27652dba,
0x28752b05,0xab5eaee9,0xaf1aae5e,0xae3fa934,0x2f912ff4,0x2cd82fa0,0xac07a8d5,0x2f302bb7,0x2dba2ed0,0xac5d1cb6,0xae99ad72,0x2dba2fe6,
0x29932c5d,0xafc9af6e,0xafe6af6e,0xaaaa25db,0xa17e244e,0xa30ead4d,0xafafaffc,0xaff8aee9,0x2f5a2fed,0x2c5d2f91,0xaeb5ad4d,0x30002e5e,
0x2cb02e3f,0xad72a17e,0xafffafa0,0x27652e3f,0x217e2993,0xaf02afe6,0xaf02afc9,0xaf1aaaaa,0xab05a5db,0x2814aa4e,0xac07adba,0xad4dafdd,
0x2f1a2fe6,0x2bb72f80,0xaff4af46,0x2f1a2fc9,0x2b052d96,0xae5ea6a1,0xaee9afd4,0xa93429f1,0xa5db244e,0xadbaaffc,0xaa4ead4d,0xafddaee9,
0xaddcabb7,0x2cb0a17e,0x2765a17e,0x1cb6ad00,0x2ed02fdd,0x2aaa2f6e,0xaf80b000,0x2cb02fdd,0x28752cd8,0xaf1aa934,0xab5eadfe,0xae3fa44e,
0xab05a17e,0xac07afaf,0x2814a30e,0xad4daff8,0xaf6eaddc,0x2eb52765,0x2eb52cb0,0x2dba1cb6,0x29932f5a,0xa7652e99,0x25152e99,0x2aaaad96,
0xafa0ab05,0xabb7afed,0xaff4acd8,0x28d52ffc,0xa814af02,0x2f912d27,0x9fd9ae1f,0xaee9ae3f,0x2fd42c32,0xaf5a1cb6,0x30002d72,0x2fd42515,
0x28752f46,0xa8d52e7c,0xa8d52c32,0x2e3fa993,0xafedac5d,0xa934b000,0xaf30af5a,0xa8142eb5,0x1648adfe,0x2e992e5e,0x2c87a814,0xa9f1affc,
0x2fe62e1f,0xafffa875,0x2ddc2ff4,0x2ed02e1f,0x26a12f30,0xa9f12e5e,0xad96244e,0x2fd41fd9,0xafffad27,0xa515aff4,0xac32aff4,0xaddc2b5e,
0x2875acb0,0x2d272f46,0x2fa02993,0x2875aed0,0x2ee92f6e,0xaf91ac87,0x1fd92e99,0x28143000,0x244e2f1a,0xab052e3f,0xaf91a875,0x2fbc2b5e,
0xafd4addc,0x1648afc9,0x1648ae7c,0xafdd9cb6,0x2c32aa4e,0x2aaa2fd4,0x2f802e99,0x2e7caa4e,0x2d002ffc,0xae1fae5e,0xad272814,0xabb72dfe,
0x1fd92f02,0xac072e1f,0xafedad27,0x2dfe2e3f,0xaf6eae7c,0x25dbaf80,0x2c5daaaa,0xaf6eac32,0x2ddca5db,0x25153000,0x2c323000,0x2fff26a1,
0x28d52fbc,0xabb7af91,0xaff4ab05,0xafa0244e,0x96482ee9,0xac872dfe,0xae99af30,0x29f12fbc,0xaed0af02,0x2993af1a,0x2f46217e,0xacb0af02,
0x2f1a1cb6,0xa30e2fc9,0xa30e2e7c,0x2e1f2ddc,0x9fd92eb5,0xa44eb000,0xae5eaf5a,0xaf30ac5d,0xa17e2ed0,0xad002ddc,0xabb7afff,0xa17e2fe6,
0xadfeaf6e,0x2c07ae99,0x2fed2c87,0x9fd9b000,0x2fd42814,0xa9f12f30,0xad962934,0x26a12fed,0xaaaa2d00,0x2765afa0,0xa515afa0,0xa993afaf,
0xa5152eb5,0xad722dba,0x9cb6af6e,0xac322eb5,0xad00afbc,0x2d27adfe,0x2e1f2f30,0x2bb7aee9,0x2ffc2b5e,0xacd82e3f,0xafeda875,0xab052f1a,
0xadba2993,0x2c87ae7c,0x2c87ac32,0x2a4eaf46,0xaddc2d96,0xafe62c5d,0xaed02c5d,0x2fffa9f1,0x2e1fad4d,0x2e3f2814,0x2f02ac07,0xad27ab05,
0xae5e2d00,0x9fd9af1a,0xaf302b5e,0xa44e2faf,0x2e99acb0,0xad962f80,0x2f5aaaaa,0x2e99aed0,0xae3f2d72,0xaff82c32,0xaff82515,0x2f021cb6,
0x2ee9ac87,0x2d4d29f1,0x2ffc9648,0xa44eae99,0xaf6e2b05,0x26a1afbc,0xafd4a44e,0xadba2f91,0x2fc9a8d5,0xaf462e3f,0x2f802875,0x2fe6a8d5,
0xae992d4d,0xb0002c07,0xaf6ea814,0x2c872b05,0x2f80ab5e,0x2c322bb7,0x2e7c2bb7,0x2aaaaff8,0xaff42765,0x2b5eafff,0xad27ad72,0xaff42cb0,
0x2fed1648,0xaffc2c5d,0x2b052eb5,0x2cd82a4e,0xaee92d27,0xaffc2bb7,0xad4dad00,0x244e2e1f,0x2fdda993,0x29f12cb0,0x29f12ed0,0x2eb5af46,
0xafe61648,0x2d72afdd,0x9cb6afd4,0xaed01648,0x2f022934,0xafa02814,0xa8d52fed,0xa30e2f30,0xaf302d00,0xafed2b5e,0xa814af1a,0xa9342faf,
0x3000a765,0x26a12d72,0xa5db2fff,0x3000acb0,0xaf46a6a1,0x2ed0af5a,0x2cb0af5a,0xa993ac87,0x2d272cd8,0xae3f9fd9,0xaf022d4d,0xae1f2fbc,
0xaf6e2cd8,0xafd42b05,0x26a1affc,0xadba2fed,0x2fe6a30e,0x1cb62e1f,0xad722f1a,0x2ed0a30e,0xae1faaaa,0x2fafae7c,0x2fafac32,0x28d5af80,
0x29342e99,0xac07a9f1,0xafbc1648,0xaffc2c87,0xafa02cb0,0xafaf2aaa,0x2d00af80,0xafa02ed0,0x2f911648,0xa44e2eb5,0xafbc2c5d,0x2b052a4e,
0xac87acd8,0x3000ad4d,0x2f6e1fd9,0x2e99afbc,0x9cb62faf,0xa515ad27,0xac32ad27,0xad72a30e,0xafc92c87,0xaf802a4e,0x2f46adba,0xafe62c87,
0x2f02244e,0xa8d52f30,0xafa01fd9,0xa30e2e5e,0xa934ae1f,0x2fbcabb7,0x2c072d00,0x2ffcad27,0xaa4e2fff,0x26a1aed0,0x26a1afe6,0x1648addc,
0xaf4629f1,0xac3225db,0xae7c25db,0x29931648,0xab5e2f91,0xafaf2e5e,0xad002fed,0x2f1aad4d,0x2ee9a875,0xaf302ff8,0x2dfea17e,0x2fbcaff4,
0x2c5dafc9,0xa9f12d72,0x2d96afff,0x2c5dae7c,0xaf022993,0xab5e2515,0xab5ea765,0xa30e2aaa,0xacd82fd4,0xaf302dba,0xaf912f6e,0x2c07a6a1,
0x2d969fd9,0xafdd2fed,0x25db2c07,0x2f5aadfe,0x2e7caff8,0xad722f02,0x2fffae3f,0x2fc9aff8,0xaeb52934,0xaa4e244e,0x9648acd8,0xac5d2dfe,
0xaddc2ff8,0xae7c2d00,0xafc92d00,0x9cb628d5,0x2bb72515,0xaff82f80,0xab5e2f46,0x2bb7a765,0x2fbcaf5a,0xaf302fdd,0x2dfea5db,0x2ee9ad96,
0xae5e28d5,0xa934230e,0x2b05af02,0xaee92fa0,0xaeb52fff,0xad962c32,0xad962515,0xac872ddc,0x276529f1,0xaf802eb5,0xaf462fdd,0xa51529f1,
0x2ff4adfe,0xaff82fed,0x217e2c07,0x28759fd9,0xadfe2875,0xa814217e,0x2e5eaff8,0xaffc2ff4,0xaf5a2fe6,0xac872aaa,0xa6a1a993,0xaf5a2fc9,
0x9cb62c87,0xae7c2d96,0xafc92d96,0xaddc2eb5,0x2f1aac07,0xafaf2f30,0xad002f91,0xab5e2cd8,0xad962814,0xa5db1fd9,0x2fddaf91,0xaf5a2ee9,
0xafc92faf,0xaaaa28d5,0x2993ae1f,0xafe62faf,0xa8d52ddc,0xad002c32,0xad002515,0xaff82fff,0x2d4da6a1,0xae5e2dba,0xafed2f6e,0xaf912fd4,
0xad272765,0xa30e1cb6,0x2fafaddc,0xad272cb0,0xaffc2f5a,0xa81425db,0x2e5eafdd,0xadfe2d96,0xac5d2ee9,0xaa4e2934,0x9648ab05,0xaeb52e5e,
0x2993230e,0xac322b5e,0xae7c2b5e,0xaf462f02,0xacb026a1,0x9cb61648,0x2ddcaa4e,0xa76526a1,0xaff42ee9,0xa17e1fd9,0x2ff8af91,0xa8752814,
0xadfe2fa0,0xa44e230e,0x2cd8af02,0xa93428d5,0x96482aaa,0xa5db2515,0xa5dba765,0xa9f12993,0x2f462f5a,0x2c322e99,0x2e7c2e99,0xa993ad96,
0x2f1a2f30,0xa875244e,0x2e3f2e5e,0x2b5e1fd9,0x2ee92f02,0xaf30ad27,0x2dfe2e1f,0x2fbc2e3f,0x2eb52ed0,0xaf6eafff,0x2dba2ddc,0x2eb52fe6,
0x28752993,0xa8d52515,0xa8d5a765,0x2e3f2aaa,0x244e26a1,0xaf91ad96,0xab05a9f1,0x2fbc2fd4,0x96481fd9,0xae99afed,0xac87ac07,0x29f12dfe,
0xa515a17e,0x9cb6abb7,0xad72ad00,0xac32a17e,0xac5dab05,0xaf5aacd8,0xb000afed,0x2eb52ffc,0xaddcad27,0xae7caff4,0xafc9aff4,0x9cb62b5e,
0xaf02ae7c,0x217eaaaa,0xaf1aaf80,0xaf02ac32,0xafbcaf6e,0x2f302c87,0xadfeae99,0xaee9b000,0xafedafa0,0xaf30aff4,0xa934abb7,0xa81428d5,
0xafd4afff,0x1648ac32,0x1648a515,0xafddaddc,0xaed0af6e,0x2f462c5d,0x299325db,0xacb0af6e,0xad00adfe,0x2e1f2fed,0x2d272c07,0x2bb79fd9,
0xadfeaf02,0xa814ae1f,0x2e5e2d27,0xaffcae3f,0xaa4eacb0,0x2e992993,0x2fd42f46,0xaa4eaed0,0x1cb6a5db,0x2e7c3000,0x2fc93000,0x2ddc26a1,
0x2b5e2814,0xa8752934,0x2e3f2f30,0x2f1a2fed,0x1648a814,0x2c879fd9,0x2e992f91,0xa9f1aee9,0x2c322875,0x2f802fa0,0x2aaa2d27,0x2e7c2875,
0x2f1a2ddc,0xa30e2c32,0xa30e2515,0x2e1f2fff,0x2ffc2fd4,0xafedad96,0xacd8a9f1,0xab0526a1,0x2e1f2c32,0x2ff42d72,0xa8751cb6,0x2e1f2515,
0x2ffc2f6e,0x28142e99,0xae5eac87,0x2dfe3000,0x2eb52fbc,0xaf5aab05,0xb000af91,0xac5d244e,0x29932d00,0xac32afa0,0xae7cafa0,0xaf46afaf,
0x2fe62fd4,0x2ddc3000,0xafffaf5a,0x2ed02fd4,0x2d002ee9,0xad271fd9,0xae1faf91,0xabb72814,0x9fd928d5,0xae5eaff4,0xa44eabb7,0xaf30afa0,
0xadbaaaaa,0x2c87a515,0x2c872765,0x2a4ea993,0x9cb62d96,0xacb02c5d,0xa7652c5d,0x2ddca9f1,0xaff8adfe,0xa30eafbc,0xafafaee9,0xa17e2f30,
0x244ead00,0x2dfe2f1a,0x2934ab5e,0xacd8afaf,0x2fdd2e7c,0xb000a993,0x2f6e2f46,0x2fdd2c32,0xae3f9cb6,0xaff8a765,0xaff8acb0,0x2f022ddc,
0xac07afdd,0x2dfeaa4e,0x1fd9adba,0xafeda5db,0x2f6e2934,0xa6a12ee9,0x2fd42e5e,0x2dbaab05,0x27652f1a,0xaaaaaff4,0xa9932bb7,0xa5152f1a,
0xafddadfe,0xadbaaee9,0xaa4eafbc,0xa5db2f30,0x2aaaab5e,0x2fc92bb7,0x2fe62bb7,0xa993aff8,0x2e3f2fc9,0xafa01cb6,0xa17e2ddc,0x2e3f2e7c,
0xae5e9648,0x2d4dac5d,0xaf91aeb5,0xafedaa4e,0xac07aff8,0x1fd9afaf,0x2dfea30e,0xafeda17e,0x2fdd2aaa,0x29f12fe6,0x29f12fc9,0x2eb5a993,
0xa5152dba,0xaddcae99,0xafffac5d,0xac322dba,0xaf02af30,0x2fa02c07,0x28d5acd8,0x230eaf91,0x2934ad00,0x2e5eab5e,0x2ee92f1a,0xab05afaf,
0x2dba2fc9,0xac5d2ddc,0xae991cb6,0x2dba2e7c,0xaf80a6a1,0x2765af5a,0xa515af5a,0xaf46ac87,0x217eae5e,0x230e2ffc,0x2faf2dfe,0x2ff82814,
0x2f6e244e,0x2fd42934,0xa6a12dfe,0x2dbaacd8,0xa5152e3f,0xafffa17e,0xaddcafa0,0xac322e3f,0xae1faf80,0x2fafa515,0x2faf2765,0x28d5af46,
0x2f9125db,0xaee92a4e,0xa8142dba,0x9fd92fdd,0x2f1a2e7c,0x2bb72f46,0xaff4a993,0x2f1a2c32,0xaf309648,0xacd8aeb5,0x2c07ac5d,0xaf91aa4e,
0x25dbae5e,0x2dba2dfe,0x2a4e2ffc,0x2fdd2814,0x2d722faf,0xae7cad27,0xafc9ad27,0xafffa30e,0x27652fdd,0xa9932f6e,0xaaaab000,0xa5152fdd,
0xaf02ae5e,0x28d5af91,0x2fa02d4d,0x230eafed,0x2f91217e,0xa8142faf,0xaee9230e,0x9fd92ff8,0xaa4e2d72,0x26a1afc9,0x26a1ae7c,0x1648afff,
0xaf8029f1,0xafc925db,0xafe625db,0x2f461648,0x2fa0a934,0x2bb72cd8,0x2ff4a44e,0xa8d5adfe,0xafbc2875,0x2934aff8,0xaffc217e,0xac072ff4,
0x2fd4a765,0xaf5a2ddc,0x30009cb6,0x2fd4acb0,0xaf02aaaa,0xab5eacb0,0xab5eaed0,0xa30e2f80,0x2e5e2c5d,0xab053000,0x29342f5a,0x2ee9aeb5,
0xad96ad4d,0x2fddacd8,0xa5dbafbc,0xaf5a1fd9,0x2cb02e1f,0xaddca875,0x1cb62ff4,0x27652e1f,0xa6a1af91,0x29f1afed,0x2d96ae5e,0xafd42d4d,
0x9cb62ff8,0xafe62d00,0xaed02d00,0x2d7228d5,0x2875afe6,0x2d272993,0x2fa0aaaa,0x2875afc9,0xac072f5a,0x2934afdd,0xaffc25db,0xafbc2d96,
0x2cd8af1a,0x2f91ae3f,0x2f302875,0xac07ab5e,0xaeb52d72,0xad96a765,0xad96acb0,0xac872fff,0x2fc9aa4e,0xa9932fd4,0x2aaa2e99,0x2fe6aa4e,
0xaff41fd9,0x2ff8acd8,0xa17eafbc,0xa875ad4d,0x2ffca875,0x2ee9a17e,0xa44e2ff8,0x2d4daff4,0xaf6ea515,0x25dbaf46,0x2c5daf80,0xaf6e2765,
0x2d722c87,0xafe62d96,0xaed02d96,0x9cb62eb5,0xa8d5aee9,0x2bb72b05,0x2ff4a934,0x2fa0ae5e,0x2d962c07,0x25db2d4d,0xafdd2b05,0x2f5aa814,
0xa765af02,0x2f46af1a,0x2f80217e,0x2515af02,0xa8d52fff,0xad00a765,0xad00acb0,0xaff82d72,0x2dfeaeb5,0xacd83000,0x244e2f5a,0x29342c5d,
0xa17e2fc9,0xad002fff,0xabb7ad72,0xa17e2e7c,0x2d4daf5a,0x2ee9a5db,0xa44e2fdd,0x2ffcad96,0xafd42c07,0x29f1af91,0x2d96af30,0xa6a1acd8,
0x2f46230e,0xafc92b5e,0xafe62b5e,0xaf802f02,0xae7c2eb5,0xafff2dba,0x2d72af6e,0xafc92eb5,0x2ff4a814,0x217e2d4d,0xaff82b05,0x28752c07,
0xad4dab5e,0x2fedae3f,0x2e5e2875,0x2f91af1a,0x96482f80,0xa5dbacb0,0xa5dbaed0,0xa9f1aaaa,0xad729648,0xa515a6a1,0xac32a6a1,0x9cb62a4e,
0xae1f2ffc,0xae3f2c07,0xaf022fbc,0x2d27a934,0x2cd8230e,0xaffc2fa0,0x2b0528d5,0x2fedaf02,0x2e99afe6,0xad962f46,0x2f5aaf80,0x2e99afc9,
0x230eaddc,0x2d27aed0,0x2d27afe6,0xafaf2fff,0xafbc2c87,0x1fd9a9f1,0xad4d1648,0xacd82e99,0xaa4e2f30,0xac5d2814,0xaeb52fed,0x96482934,
0x2ed0a8d5,0xaf802e3f,0x2aaa2875,0x2cb0a8d5,0x2e99affc,0x3000afbc,0x2f6eac07,0xac872934,0xa993a8d5,0x2ed0afaf,0x2cb0afaf,0xaf462e1f,
0xaff42ed0,0x2b5ead72,0xad271cb6,0xaff42fe6,0xa44e2dba,0x9fd9a6a1,0xaf302fd4,0xae5e2f6e,0x2fbcad27,0x2d4dabb7,0x9fd92d00,0x2cd8ae1f,
0x2c87af80,0x2f5aae7c,0x2f5aac32,0x26a1aaaa,0xacb01648,0x2fffafdd,0x2d72afd4,0xa7651648,0xafaf2f91,0x2f1aafbc,0xab5ea44e,0xad002b05,
0x2b05230e,0xa44e28d5,0xafbc2fa0,0x2f91af02,0x3000aed0,0x26a19cb6,0xa5db2d72,0x3000afe6,0x2aaaaeb5,0x2c32a9f1,0x2e7ca9f1,0x2f80afdd,
0xad27244e,0x2e3fad4d,0x2f02affc,0x2e1faee9,0xaa4e2e5e,0xaeb52f30,0xac5d1fd9,0x9648244e,0x2cb0a30e,0xad722e1f,0xafff2f1a,0x2765a30e,
0x2ff8af46,0xabb72cb0,0xabb72ed0,0x2b5ea993,0x2b05ae99,0xa81429f1,0x2c079648,0x2d4dac87,0xafa02fe6,0xafaf2f80,0x2d00af46,0xafa02fc9,
0xa9342dba,0xafed2fd4,0xa814a6a1,0xaf302f6e,0x2c87a44e,0xb0002ffc,0xaf6e2d4d,0xae992ee9,0x2fffaf02,0xafe62ff8,0xaed02ff8,0xaddc2e3f,
0xaed02c87,0xaaaa2a4e,0x2f80adba,0xacb02c87,0xafaf2fed,0xab5e2b05,0x2f1aaffc,0xad002cd8,0xab052e1f,0xac072bb7,0x2814ad00,0xad4d2d27,
0x29f11cb6,0xac5d2c32,0xac5d2515,0xad962d72,0x2d722d96,0x25152c5d,0x2c322c5d,0x1cb6a9f1,0x2d272d4d,0xad00a814,0x2bb72c07,0x2e1f2b05,
0x2cd82d00,0xaffcaf1a,0x2b052b5e,0x2fed2faf,0x2c872cb0,0xadbaaf80,0x2a4e2aaa,0x2c872ed0,0xae3faddc,0xaff8aed0,0xaff8afe6,0x2f022fff,
0xaee9ae99,0xad4daf6e,0xaffcb000,0x244e2c87,0xaf6eaf30,0x26a1a814,0xafd4afed,0xadbaa934,0xafc9afa0,0x2f462d00,0xaf80afaf,0xafe6afa0,
0xac87ad4d,0x9648ac07,0x29f12814,0xae99ab05,0xa993ab5e,0x2ed02bb7,0x2cb02bb7,0xaf46aff8,0xa30ea765,0x2f1a2fff,0x2e1f2d72,0xa30eacb0,
0x244e1648,0x1fd92c5d,0x2f302eb5,0x2e5e2a4e,0x2ee92e1f,0x2ffc2f02,0x2d4d2e3f,0xa44ead27,0x2fdd2f80,0x29f12e7c,0x29f12c32,0x2eb52aaa,
0x2fe63000,0xad72a5db,0x1cb626a1,0x2ed03000,0x2f022f91,0xafa0afbc,0xa8d5a44e,0xa30e2b05,0x2b052d00,0xa44e2b5e,0xafbcaf1a,0x2f912faf,
0x16482765,0xafd4ad72,0xafddafff,0x16482cb0,0xaaaaa6a1,0xac32af5a,0xae7caf5a,0xaf80ac87,0xae1facd8,0x2d001fd9,0xabb7ad4d,0xad27afbc,
0xaf6eae5e,0xafd4af30,0x26a19fd9,0xadbaa44e,0xafe6aff4,0x9cb6ad27,0x2d722b5e,0xaed0aff4,0xae1faf46,0x2faf2cb0,0x2faf2ed0,0x28d5a993,
0xa934ac87,0x2c072f6e,0x2fbc3000,0x2ffc2e99,0xa8d5acb0,0x2875aaaa,0x2e3f2f80,0xa8d5aed0,0x29341648,0x2fed2eb5,0x28142c5d,0x2f302a4e,
0x2e992cd8,0x16482d4d,0xa9f19fd9,0x2c872fbc,0x2fff2faf,0xafe6ad27,0xaed0ad27,0xaddca30e,0x2fc92e99,0x2f802f5a,0xaf46ad96,0x2fe62e99,
0x2f022fed,0xa8d52b05,0xafa0affc,0xa30e2cd8,0x29342d27,0xafbcaf02,0xac07ae3f,0xaffcae1f,0xaa4e9cb6,0x26a1ac32,0x26a1a515,0x1648ad72,
0xaaaa29f1,0xaed025db,0xacb025db,0x2f801648,0xaf1aaf91,0x2875ae5e,0xae3fafed,0xab5e2d4d,0x2c07a875,0x2b052ff8,0x2d4da17e,0xa814aff4,
0x2eb52fc9,0xaf6ead72,0x2dba2fff,0x2eb52e7c,0xaf02af80,0xab5eafe6,0xab5eafc9,0xa30e2f46,0x2cd8a6a1,0x2f302d96,0x2f9129f1,0xac07afd4,
0x2d962ffc,0xafdda44e,0x25db2ee9,0x2f5a2d4d,0xae7ca17e,0x2d72abb7,0xafffad00,0xafc9a17e,0x2c5da934,0x2f5aa44e,0x30002cd8,0xaeb5adfe,
0x2d722ff8,0xacb02d00,0xa7652d00,0x2fff28d5,0xaf02a515,0x217eaf80,0xaf1aaf46,0xaf022765,0xa814af5a,0x2b052fdd,0x2d4da5db,0x2c07ad96,
0x2e5e2fa0,0x29342ff4,0xab052bb7,0x2ee9a8d5,0xaeb59cb6,0xad96aed0,0xad96afe6,0xac872d72,0xa765af6e,0x2f802c5d,0x2f4625db,0x2515af6e,
0x2ff42d4d,0xaff8a44e,0x217e2ee9,0x28752ffc,0xad4d2875,0xafbc217e,0xacd8aff8,0x1fd92ff4,0xaa4eafe6,0x2e99aaaa,0x2fd42993,0xaa4eafc9,
0x2fff2c87,0xacb02d96,0xa7652d96,0x2d722eb5,0xab5e2c07,0x2875af30,0xae3faf91,0xaf1aacd8,0xad96afbc,0xa5dbaffc,0x2fdd2934,0xaf5aac07,
0x2fc92875,0x2aaa2fa0,0xa9932d27,0x2fe62875,0xa8d52d72,0xad00aed0,0xad00afe6,0xaff89cb6,0xad4dafd4,0x2e5e2d96,0x2fed29f1,0x2f91a6a1,
0x2e1fa765,0x2ff49cb6,0xa8752ddc,0x2e1facb0,0x1fd92f5a,0xafbc25db,0xacd8afdd,0xad4d2d96,0xaeb5aee9,0x2f5aa934,0x30002b05,0x2c5dae5e,
0x2f80230e,0xaed02b5e,0xacb02b5e,0xaaaa2f02,0x2cb02fd4,0x1cb63000,0xaddcaf5a,0x27652fd4,0xaff4ac07,0xa17eaffc,0x2ff82934,0xa875afbc,
0x2dfea8d5,0x244e2ff4,0xacd82bb7,0x29342fa0,0x96482f46,0xa5dbafe6,0xa5dbafc9,0xa9f1af80,0xafff9648,0xae7ca6a1,0xafc9a6a1,0x2d722a4e,
0x2ff81fd9,0x230e2ee9,0x2faf2814,0x217eaf91,0xafeda30e,0x2d4dafa0,0xaf91a8d5,0xae5e2f02,0x2fdd2515,0xb0002aaa,0x2f6e2993,0x2fdda765,
0x230eafff,0x2d27afc9,0x2d27ae7c,0xafaf2d72,0xa8142fdd,0xaffc2a4e,0xadfe2dba,0x2e5e25db,0x2a4eaf91,0x2c5d2c07,0x2eb5acd8,0x1648af30,
0xac322f1a,0x2993aff4,0xaf462bb7,0xae7c2f1a,0x2fdd1fd9,0x2dba2814,0x2a4e2ee9,0x25dbaf91,0xaf46a8d5,0x2765afaf,0xa515afaf,0xaf802e1f,
0x2e3f2c32,0xafa02ddc,0xa17e2fff,0x2e3f2515,0xacd8adba,0x2dfe26a1,0x2934afd4,0x244eaf6e,0xa8142ff8,0xadfe2faf,0xaffc230e,0x2e5e217e,
0x2c87af46,0x2f5aa515,0x2f5a2765,0x26a1af80,0xae7c2dba,0x9cb6ae99,0xaddcac5d,0xafc92dba,0x2fafab05,0xaf1a2ee9,0x2b5e2e5e,0x2d002934,
0xaf91a30e,0xacd8a8d5,0x2c07afa0,0xaf302f02,0x2dba2c32,0xac5d2fff,0xae992ddc,0x2dba2515,0xa993aeb5,0x2fc9a9f1,0x2fe6a9f1,0x2aaaafdd,
0xa17e2fed,0xa30eadfe,0xafaf9fd9,0xaff82c07,0x2a4eafed,0x2eb5af91,0x2c5d2d4d,0x1648ae5e,0xae7c2e3f,0xaddca17e,0x9cb6afa0,0xafc92e3f,
0x2ff8a993,0xabb72fe6,0xabb72fc9,0x2b5e2aaa,0xaf30a5db,0x2fbcaa4e,0x2ee9adba,0x2dfeafdd,0x2f1a2515,0x2bb72993,0xaff42aaa,0x2f1aa765,
0xab05adba,0x2e5eafd4,0x2ee926a1,0x2934af6e,0xa5db2fed,0xadba9fd9,0xaa4eadfe,0xafdd2c07,0x2ddcaf02,0xacb02ff8,0xa7652ff8,0x9cb62e3f,
0xac322fdd,0xaf462f6e,0x2993b000,0xae7c2fdd,0x2fafacd8,0x2b5e2934,0xaf1a2dfe,0x2d00244e,0xaf30a17e,0x2ee9afaf,0x2fbca30e,0x2dfeaff8,
0x29f12ddc,0xac5da765,0xac5dacb0,0xad969cb6,0xa993aa4e,0x2765ac87,0xa515ac87,0xaaaa2dba,0xafa02f30,0xabb7244e,0xaff42e5e,0x28d51fd9,
0x28142bb7,0xaf912e1f,0x1fd92d27,0x2ee9ad00,0x2fd4aed0,0xaf5a2fff,0x3000addc,0x2fd4afe6,0x2fafaf46,0x2fa0ae7c,0x2fa0ac32,0xad002993,
0xa44eac5d,0x2f91b000,0x2b05af5a,0xafbc2eb5,0xb0002dfe,0x2c87ae5e,0xae992814,0xaf6e2ffc,0xa5152e1f,0x9cb6a875,0xad722ff4,0xac322e1f,
0x26a12b05,0xa9f12cd8,0xad962fed,0x2fd4affc,0x2fffae1f,0x2515230e,0x2c32230e,0x2ddcaf1a,0x2875ae7c,0x2d27aaaa,0x2fa0af80,0x2875ac32,
0xaee929f1,0x2f91ae99,0x9fd9ac87,0xa8149648,0xafed2f1a,0xaf302e3f,0xa934a875,0xa8142b5e,0xa6a12ddc,0xb0002fc9,0xb0002e7c,0x25db1cb6,
0x2ed0aa4e,0xaf462fd4,0xa9932e99,0x2cb0aa4e,0x2e3faffc,0xad272e5e,0x2e1fa814,0x2f02adfe,0x9fd9abb7,0x2c07ad27,0x2fedae1f,0xadfe2d00,
0xaf6e2cb0,0x25dba993,0x2c5daf46,0xaf6e2ed0,0xaddc2fdd,0xa5159648,0xac329648,0xafff2fd4,0x28d52814,0xabb72934,0xaff42f30,0xafa02fed,
0x3000aee9,0x2e99adfe,0xac872f30,0x2f6eafbc,0x2c32af02,0x2f80af1a,0x2aaa217e,0x2e7caf02,0xab5e9cb6,0x2ff4afc9,0x2ff4ae7c,0x2d27addc,
0xaffc2eb5,0x2fedb000,0x2cd8af5a,0x2b05ac5d,0xa17e2c32,0xad002d72,0xabb71cb6,0xa17e2515,0x2dfea9f1,0xac072c87,0xafed2e99,0x1fd91648,
0x2fd4afbc,0xa9f12b05,0xad962f91,0x26a1a44e,0x2aaaae3f,0xa76528d5,0x251528d5,0x2993a875,0xafe62eb5,0xaddc2dba,0x2fffaf6e,0xaed02eb5,
0xae3f2fbc,0xae1f2dfe,0x2d27af30,0xaf022ee9,0x9fd92b5e,0xae5e2e3f,0xa44ea875,0xaf302f1a,0x2d96a993,0xae992e7c,0xae992c32,0xaf5a2f46,
0x299329f1,0xa76525db,0x251525db,0x2aaa1648,0x28d52934,0xaf02acd8,0x230e244e,0x2fa02dfe,0x28142875,0xaf91aff8,0x1fd9217e,0x2ee92ff4,
0x26a12765,0xaa4eaddc,0x16481cb6,0x26a12cb0,0xaf02af46,0xab5eae7c,0xab5eac32,0xa30e2993,0xae5eaeb5,0x2b059648,0xa934aa4e,0xaee9ac5d,
0xad96adfe,0x2fdd2e5e,0xa5dba814,0xaf5aaffc,0xacb0ad27,0x2ddc2faf,0x9cb6a30e,0xa765ad27,0x2fd42f91,0x2f6e2fed,0x2dba2e5e,0xa6a1ad4d,
0x2fff2ff8,0x25152d00,0x2c322d00,0x2ddc28d5,0x2faf2fe6,0xae1fa993,0x28d52aaa,0x2faf2fc9,0x2ee92f5a,0xaf91afdd,0x1fd925db,0x28142d96,
0xacd8ab5e,0xaf91ad00,0xaf30afaf,0x2c072f1a,0xaeb5addc,0xad96afc9,0xad96ae7c,0xac879cb6,0xafc9af5a,0x2993a6a1,0xaaaaac87,0xafe6af5a,
0xaff4affc,0x2ff82e5e,0xa17ea814,0xa875adfe,0x9fd9a875,0x2c07a17e,0x2fed2ff8,0xadfeaff4,0x29f12515,0x2fdd2f46,0x2eb52f80,0x29f1a765,
0x2ddc2c87,0x25152d96,0x2c322d96,0x2fff2eb5,0x2fa02ee9,0xaf02ab05,0x230e2934,0x28d52e5e,0x2d962ee9,0x25db2dfe,0xafddaf30,0x2f5a2fbc,
0x27652bb7,0xaf46ab5e,0xaf80aff8,0xa5152bb7,0xa8d59cb6,0xad00afc9,0xad00ae7c,0xaff8addc,0xadfeac5d,0x2cd89648,0xa44eaa4e,0xa934aeb5,
0xaff8afc9,0xae3fafff,0x2f022d72,0xaff8ae7c,0xadfeaf5a,0x2c07a5db,0x2fed2fdd,0x9fd9ad96,0xa6a1ac07,0x2f6e2f91,0x2dba2f30,0x2fd42cd8,
0x2aaa230e,0xa7652b5e,0x25152b5e,0x29932f02,0x2e7c2c5d,0x2fff2d96,0xad72a9f1,0x2fc92c5d,0x2ff42fbc,0x217e2dfe,0xaff8af30,0x28752ee9,
0x2d4d2f1a,0xafedad00,0xae5eafaf,0xaf91ab5e,0x96482993,0xa5dbae7c,0xa5dbac32,0xa9f1af46,0xaddc9648,0xafe6a6a1,0xaed0a6a1,0x2fff2a4e,
0xad27affc,0x2d00ac07,0xabb7afbc,0xae1f2934,0x2e5e230e,0x1fd92fa0,0x2f3028d5,0x244eaf02,0x2c872fe6,0xadbaaf46,0x2a4e2f80,0x2c872fc9,
0x230ead72,0x2d27ac32,0x2d27a515,0xafaf9cb6,0x2fbc2e99,0x9fd92f6e,0x2d4d3000,0x2cd8ac87,0xaa4e2b05,0xac5dafbc,0xaeb5a44e,0x96482f91,
0xaed0afa0,0x2f802d00,0xaaaaafaf,0xacb0afa0,0x2c872ffc,0x16482fbc,0xa9f12c07,0x2e99a934,0xaf80a8d5,0xac32afaf,0xae7cafaf,0xaaaa2e1f,
0xa30eaed0,0x2f1a2d72,0x2e1f9cb6,0xa30eafe6,0x2fed2dba,0xaffca6a1,0x2b052fd4,0x2cd82f6e,0xafbcae1f,0xad4daf02,0x1fd9ae3f,0xacd82d27,
0x2c87a993,0x2f5a2cb0,0x2f5a2ed0,0x26a1af46,0x2cb03000,0xafffa5db,0xad7226a1,0x27653000,0xafafa934,0x2f1aa814,0xab5eafed,0xad00af30,
0x2f30230e,0x2fed28d5,0x28142fa0,0x2934af02,0x16482ed0,0xafd41cb6,0xafddad72,0x16482fe6,0xaf46aeb5,0x2ed0a9f1,0x2cb0a9f1,0xa993afdd,
0x2e1fa44e,0xad002d4d,0x2bb72ffc,0x2d272ee9,0xaa4e2cd8,0xaeb52b05,0xac5daffc,0x96482fed,0xacb0aff4,0x2d72ad27,0x2fff2b5e,0xa765aff4,
0x2ff82aaa,0xabb72e7c,0xabb72c32,0x2b5e2f80,0xab052c87,0x2814af6e,0xac07b000,0xad4dae99,0xa8d5afe6,0x2875af80,0x2e3f2f46,0xa8d5afc9,
0x2f912dba,0xa44e2fd4,0xafbca6a1,0x2b052f6e,0xae99244e,0x9648affc,0x29f1ad4d,0xac87aee9,0x1cb6af02,0x25152ff8,0x2c322ff8,0x2d722e3f,
0x2ed02e99,0x2aaa2f5a,0xaf80ad96,0x2cb02e99,0xafafa44e,0xab5eaf30,0x2f1a9fd9,0xad00ae5e,0x2b05ad27,0x2c072f02,0xa8142e3f,0x2d4d2e1f,
0x29f12fff,0xac5daed0,0xac5dafe6,0xad96addc,0xaf46aa4e,0xac32ac87,0xae7cac87,0x29932dba,0x2f1a2b05,0xa8752fed,0x2e3f2cd8,0x2b5eaffc,
0xaee9abb7,0x2f30ae1f,0xadfead27,0xafbc2d00,0x2eb52c32,0xaf6e1cb6,0x2dba2d72,0x2eb52515,0x2fafa993,0x2fa0a515,0x2fa02765,0xad00aaaa,
0xafed26a1,0xa934ad96,0xaf30a9f1,0xa8142fd4,0x30009fd9,0xac872fed,0x2e992c07,0x2f6eadfe,0xafe6a17e,0x2fffabb7,0xaddcad00,0xaed0a17e,
0xac5d2f30,0xaf5a2e5e,0xb000244e,0x2eb51fd9,0x2ddcae1f,0x2e7c230e,0x2fc9230e,0x1cb6af1a,0xaf022cb0,0x217eaf46,0xaf1aa993,0xaf022ed0,
0x2fbca9f1,0xaf302e99,0x2dfe2c87,0x2ee91648,0xa44eafa0,0x2b05aff4,0x2f91abb7,0xafbc28d5,0xa6a12fff,0xb0002c32,0xb0002515,0x25db2ddc,
0x2c32af6e,0x2aaa2c5d,0x2f8025db,0x2e7caf6e,0xae3f2dfe,0x2d27afed,0xae1fac07,0xaf021fd9,0x2dfe2bb7,0x28142d27,0xae5e2e1f,0x2ffcad00,
0xaa4eae7c,0x2e99af80,0x2fd4aaaa,0xaa4eac32,0x9cb62fdd,0xae7c9648,0xafc99648,0xaddc2fd4,0x2b5eafbc,0xa8752f91,0x2e3f2b05,0x2f1aa44e,
0xb0002814,0xae991fd9,0x2c87af91,0xaf6e2ee9,0x2ed02875,0xa9932fa0,0xaf462d27,0x2cb02875,0xab5eaddc,0x2ff4ac32,0x2ff4a515,0x2d27afff,
0x9fd92fd4,0xa44ead96,0xae5ea9f1,0xaf3026a1,0x2e1faed0,0x2ff4addc,0xa8752fff,0x2e1fafe6,0xaffc29f1,0xa814ac87,0x2e5eae99,0xadfe9648,
0x2eb52814,0xaf5a2f30,0xb0002934,0xac5d2fed,0xa993ae3f,0x2c3228d5,0x2e7c28d5,0x2f46a875,0xa5152fd4,0xad723000,0x9cb6af5a,0xac322fd4,
0x2e3faee9,0x2e1f9fd9,0xad272f91,0x2f02a814,0xaffc28d5,0x2cd8aff4,0x2fedabb7,0x2b05afa0,0x2d962aaa,0xae992515,0xae99a765,0xaf5a2993,
0x1cb6adba,0x2cb0aeb5,0x2765aeb5,0xaddc2f6e,0xaff82d4d,0xa30ea814,0xafaf2c07,0xa17e2b05,0xa44e2e3f,0xadfe2b5e,0xa9342f1a,0x2cd8a875,
0x2fddacb0,0xb0002f80,0x2f6eaaaa,0x2fddaed0,0x2d001cb6,0x217e2765,0x217e2cb0,0x2bb7addc,0x2ee9afdd,0x2d4daa4e,0x2ffcadba,0xa44ea5db,
0xa9f1a934,0x2fd4aee9,0x26a1ae5e,0xad962b05,0xafc92f1a,0x2f46aff4,0xaf802bb7,0xafe62f1a,0xafdd2d4d,0xadba2c07,0xaa4ea814,0xa5db2b05,
0xaaaa2f1a,0xafc92f02,0xafe62f02,0x2993a17e,0x2e3fa765,0xafa02fff,0xa17e2d72,0x2e3facb0,0x2e5eb000,0xad4d2eb5,0x2f91ac5d,0x2fedaf5a,
0x2ee9aff8,0x2ffcafaf,0x2d4da30e,0xa44ea17e,0xa5dbaaaa,0x2f6eafe6,0x2f6eafc9,0xac5d2993,0xafe62dba,0x2d72ae99,0x9cb6ac5d,0xaed02dba,
0xabb72f30,0x28d5ac07,0xafa02cd8,0xaff42f91,0xa9342e3f,0xae5e2f1a,0xaee92b5e,0x2b05a875,0x2dbaa765,0xac5d2d72,0xae992fff,0x2dbaacb0,
0x2f80afd4,0xa7652a4e,0x25152a4e,0x2f46ae99,0x217eacd8,0x230e1fd9,0x2fafad4d,0x2ff8afbc,0xa9f1a44e,0x26a1a934,0x2fd4adfe,0xad962cd8,
0xafe62e3f,0x9cb6a17e,0x2d72afa0,0xaed02e3f,0xad272f80,0xa8752515,0xa875a765,0xafa02f46,0x293425db,0xac072a4e,0xafbc2dba,0xaffc2fdd,
0x2f1aacb0,0x2bb7aaaa,0xaff42f80,0x2f1aaed0,0x2f30b000,0x2cd8ac5d,0xac072eb5,0x2f91af5a,0x25dbacd8,0x2dbaad4d,0x2a4e1fd9,0x2fddafbc,
0xad722875,0x2e7cae1f,0x2fc9ae1f,0x2fffaff4,0xafc92fdd,0xaf802f6e,0x2f46b000,0xafe62fdd,0xabb72e5e,0xafa02f91,0x28d5ad4d,0xaff42fed,
0x2934217e,0xafbc2faf,0xac07230e,0xaffc2ff8,0x2f5aad72,0xafd42fc9,0xafd42e7c,0xb0002fff,0x9cb69648,0xacb0a6a1,0xa765a6a1,0x2ddc2a4e,
0xa17e9fd9,0xaff4aee9,0xa875a814,0x2ff82f91,0xa44ea30e,0xadfeafa0,0xa934a8d5,0x2cd82f02,0xa5dba515,0x9648aaaa,0xa9f1a993,0xa5db2765,
0xa30e9cb6,0xad27a765,0xad27acb0,0x2faf2ddc,0xa814a5db,0xaffcaf5a,0xadfead96,0x2e5e2fdd,0xaa4ea934,0xac5daee9,0xaeb5ae5e,0x96482b05,
0xac32ab5e,0x2993a30e,0xaf46af02,0xae7cab5e,0xa5db9fd9,0xad96a814,0xaf5aaee9,0x2fdd2f91,0xaaaaa8d5,0xafc9afaf,0xafe6afaf,0x29932e1f,
0xad00ac32,0xa8d5addc,0xaff8afff,0xad00a515,0xae5eadba,0x2d4d26a1,0xaf91afd4,0xafedaf6e,0xa814a17e,0xadfea875,0xaffcaff4,0x2e5e2ff8,
0xac87aaaa,0xaf5aafe6,0xaf5aafc9,0xa6a12993,0xae7cad96,0x9cb6ac87,0xaddcaeb5,0xafc9ad96,0xafafaf30,0x2f1a2c07,0xab5eacd8,0xad00af91,
0xa934a30e,0xae5ea8d5,0xaee9afa0,0x2b052f02,0xad96ac32,0xaeb5afff,0xac87addc,0xad96a515,0xaf80aeb5,0x2765a9f1,0xa515a9f1,0xaf46afdd,
0xaff8afed,0x2ff42dfe,0x28751fd9,0x217eac07,0xaa4ea44e,0xaeb5a934,0xac5dadfe,0x96482cd8,0xae7cad00,0xaddcaff8,0x9cb6a8d5,0xafc9ad00,
0xaff8af80,0x2bb7a515,0x2bb72765,0xab5eaf46,0xaf30afdd,0x2fbc2f5a,0x2ee92d96,0x2dfe25db,0xab5ea515,0xaf02a993,0xa30eaaaa,0xab5e2765,
0xaf30adba,0xacd8afd4,0x2c0726a1,0xaf91af6e,0xafddafed,0x2d961fd9,0x2f5a2dfe,0x25dbac07,0xad72af02,0x2e7c2ff8,0x2fc92ff8,0x2fff2e3f,
0xac32a5db,0xaf46a9f1,0x29939648,0xae7ca5db,0xafafae5e,0xab5eaf91,0x2f1a2d4d,0xad00afed,0xaf30aff8,0x2ee92875,0x2fbc2ff4,0x2dfe217e,
0xa9f1ad72,0x2c5d2fc9,0x2c5d2e7c,0x2d962fff,0xaf80aa4e,0xafc9ac87,0xafe6ac87,0x2f462dba,0xa8d5af30,0x2f02a44e,0xa30eae5e,0xafa09fd9,
0x2fbc2bb7,0xa9342e1f,0x2ffc2d27,0x2c07ad00,0x26a12ed0,0xaa4eafff,0x16482ddc,0x26a12fe6,0xafafaaaa,0xafa0acb0,0xafa0aed0,0x2d002f80,
0xa44eaeb5,0x2f919648,0x2b05aa4e,0xafbcac5d,0x30002d4d,0xac872cd8,0x2e992fbc,0x2f6e9fd9,0xa5152d27,0x9cb6afaf,0xad72230e,0xac322d27,
0xafd4ab05,0xaf6eacd8,0xadbaafed,0x26a12ffc,0x1cb6ae1f,0x2fe6230e,0x2ed0230e,0xad72af1a,0x2faf2e7c,0xae1f2aaa,0x28d52f80,0x2faf2c32,
0xac0729f1,0x2934ae99,0xaffcac87,0xafbc9648,0xafedab5e,0xaf30ad00,0xa934afaf,0xa8142f1a,0x26a1ad72,0x30002765,0x30002cb0,0xa5dbafff,
0x2ed02f5a,0xaf4626a1,0xa9932c87,0x2cb02f5a,0xae3f1fd9,0x2d27acd8,0xae1fafbc,0xaf02ad4d,0xaffcabb7,0xaee9ad27,0x244eae1f,0xad4d2d00,
0x29f1acb0,0x2fdd2993,0x2eb52f46,0x29f1aed0,0x2d722fdd,0xafe69648,0xaed09648,0x9cb62fd4,0xafa0a814,0x2f02a934,0xa30eaf30,0xa8d5afed,
0xb000ac07,0xae99ad4d,0x2c87ab05,0xaf6e2814,0x2c32abb7,0x2f802b5e,0x2aaa2ff8,0x2e7cabb7,0x2b5e2fff,0xaff4a765,0xaff4acb0,0xad272d72,
0xaffcac5d,0x2fed9648,0x2cd8aa4e,0x2b05aeb5,0xaff8ac32,0xae3fad72,0x2f029cb6,0xaff8a515,0x2d4da9f1,0x2ee92c87,0xa44e2e99,0x2ffc1648,
0x26a12fbc,0xaf6eab05,0xadbaaf91,0xafd4244e,0xaf46ae3f,0x2fc928d5,0x2fe628d5,0x2f80a875,0xafe6ac5d,0xaddcad96,0x2fff29f1,0xaed0ac5d,
0x2e3fa814,0x2e1f2d4d,0xad272b05,0x2f022c07,0x9fd92f1a,0xae5ead00,0xa44eafaf,0xaf30ab5e,0xad96af80,0x2e992cb0,0x2e992ed0,0x2f5a2aaa,
0xad72adba,0xa515aeb5,0xac32aeb5,0x9cb62f6e,0x2d272dfe,0xad002fbc,0x2bb72ee9,0x2e1faf30,0xacd8ae3f,0x2ffcab5e,0xab05af1a,0xafed2875,
0x2c872e7c,0xadbaa993,0x2a4e2f46,0x2c872c32,0xad00addc,0xa17eaed0,0xa17eafe6,0xabb72fff,0x2c072e99,0xadfe2f6e,0x9fd93000,0x2fedac87,
0xa9f1af30,0x2fd4a814,0x26a1afed,0xad96a934,0x27652fa0,0xaaaaad00,0xa9932faf,0xa5152fa0,0xac87adfe,0x9648aee9,0x29f1afbc,0xae992f30,
0x29932f1a,0xaed02f02,0xacb02f02,0x2f46a17e,0xa30eafc9,0x2f1a9cb6,0x2e1faddc,0xa30eae7c,0xa44e3000,0x9fd9aeb5,0xaf302c5d,0xae5e2f5a,
0xac07ae1f,0x1fd9af02,0x2dfeae3f,0xafed2d27,0x25db2f80,0xaf6e2e7c,0xaf6e2c32,0x2c5d2aaa,0x2515b000,0x2ddc25db,0x2fffa6a1,0x2c32b000,
0xabb72f91,0x28d5afbc,0xafa0a44e,0xaff42b05,0xab05ae3f,0x244eaf1a,0x2fbcab5e,0xaf912875,0x16482fc9,0xafd42ddc,0xafdd1cb6,0x16482e7c,
0x2aaaafd4,0x2c322a4e,0x2e7c2a4e,0x2f80ae99,0xae1f2e5e,0x2d00affc,0xabb7adfe,0xad27a814,0xa9f1ae5e,0x26a1af30,0x2fd49fd9,0xad96a44e,
0xa5152ff4,0xafff2d27,0xaddcab5e,0xac322ff4,0x2d27af46,0x28752cb0,0x28752ed0,0x2fa0a993,0xaf912c87,0x2ee9af6e,0x2814b000,0x1fd9ae99,
0xa8d5ae7c,0x2875af46,0x2e3f2993,0xa8d5ac32,0xa9343000,0xafed2c5d,0xa814aeb5,0xaf302f5a,0x2e99ae5e,0x16482dfe,0xa9f12ffc,0x2c872814,
0xafff2875,0x2fe6ae1f,0x2ed0ae1f,0x2ddcaff4,0xa765ae99,0x2993af5a,0x2aaa2d96,0x2515ae99,0xabb72fed,0xafa02b05,0x28d5affc,0xaff42cd8,
0x2f91ad27,0xa8142f02,0xaee92e3f,0x9fd92e1f,0xaf5a9cb6,0x2fd4ac32,0x2fd4a515,0x3000ad72,0x2aaaaf6e,0x2ed0afdd,0x2cb0afdd,0xaf803000,
0xaf1a2934,0x2875acd8,0xae3f244e,0xab5e2dfe,0xac072faf,0xab05217e,0xad4d2ff8,0x2814230e,0x2eb5a765,0xaf6e2ddc,0x2dba9cb6,0x2eb5acb0,
0x2bb7af80,0x2f1aafe6,0x2f1aafc9,0xaff42f46,0xae5e26a1,0x2b05ad96,0xa934a9f1,0xaee92fd4,0xadba2ffc,0xa5dba44e,0xafdd2ee9,0xaa4e2d4d,
0x2cb0217e,0xaddc2bb7,0x1cb62d00,0x2765217e,0x2c5daf91,0x2f5aafed,0x3000ae5e,0xaeb52d4d,0xad72217e,0x2cb0ae3f,0x2765ae3f,0xafff2fa0,
0xaf022fe6,0x217ea993,0xaf1a2aaa,0xaf022fc9,0x28142a4e,0xab0525db,0xad4d2fdd,0xac072dba,0x2cd8afa0,0x2f91aff4,0x2f30abb7,0xac0728d5,
0xac5d9cb6,0x2dbaaed0,0x2dbaafe6,0xae992d72,0xafc92f6e,0x2993ac5d,0xaaaaa5db,0xafe62f6e,0xa30e2d4d,0xa17ea44e,0xaff82ee9,0xafaf2ffc,
0x2d4dafaf,0x2fbcaff8,0x2cd8a17e,0x9fd9a30e,0xaa4ea515,0x2e99af46,0x2fd4af80,0xaa4e2765,0xafff2e99,0x2cb0adba,0x2765adba,0xad722c5d,
0xab5e2ee9,0x2875ab05,0xae3f2934,0xaf1a2e5e,0x2dbaafbc,0x2fddaffc,0x25db2934,0x2a4eac07,0xa765a875,0x2f46afa0,0x2f80ad27,0x2515a875,
0xafa02d72,0x2e3faed0,0x2e3fafe6,0xa17e9cb6,0xadfe2fd4,0x2cd8ad96,0xa44ea9f1,0xa93426a1,0x2e1fafc9,0x2ff4afff,0xa8752d72,0x2e1fae7c,
0x9fd9aa4e,0x2fbcafdd,0x2cd8a5db,0x2d4dadba,0xaeb52c07,0x2f5aaf91,0x3000af30,0x2c5dacd8,0xaf802ff4,0x2ed0af1a,0x2cb0af1a,0x2aaaabb7,
0x2e7cafd4,0x2fffb000,0xad722f5a,0x2fc9afd4,0x230eac07,0x2ff8affc,0x217e2934,0x2fafafbc,0xad4d28d5,0x2fedaff4,0x2e5eabb7,0x2f91afa0,
0xb0002f46,0x2fddafe6,0x2fddafc9,0x2f6eaf80,0xaaaaaa4e,0xaed0ac87,0xacb0ac87,0x2f802dba,0xab5eab05,0xafafafed,0xad00acd8,0x2f1a2ffc,
0xac07abb7,0xab05ae1f,0xad4dad27,0x28142d00,0xac5dac32,0x29f19cb6,0xad96ad72,0xac5da515,0xafafaf80,0xafa0afe6,0xafa0afc9,0x2d002f46,
0xafedafd4,0xa934adba,0xaf30af6e,0xa81426a1,0xb000affc,0x2c87244e,0xae99aee9,0xaf6ead4d,0xafe6aff8,0x2fff2f02,0xaddcae3f,0xaed0aff8,
0xaeb5af30,0xaa4eae5e,0x9648a44e,0xac5d9fd9,0xad72ae1f,0x2cb0230e,0x2765230e,0xafffaf1a,0xabb7acb0,0x2ff82f46,0x2b5e2993,0xabb7aed0,
0xa814a9f1,0x2b052e99,0x2d4d2c87,0x2c071648,0xa44ea8d5,0x2b05a30e,0x2f912f02,0xafbcafa0,0x26a11cb6,0x30002ed0,0x30002fe6,0xa5dbad72,
0x2c3229f1,0x2aaa2eb5,0x2f802fdd,0x2e7c29f1,0x2e3f2d4d,0xad27a44e,0x2e1f2ee9,0x2f022ffc,0x2d4d2bb7,0x2fbc2d27,0x2cd82e1f,0x9fd9ad00,
0x2f5a2e7c,0x2c872f80,0x26a12aaa,0x2f5a2c32,0x2fff2fdd,0xacb09648,0xa7659648,0x2d722fd4,0x2f1a2fbc,0xafafaf91,0xad00ab05,0xab5e244e,
0x30002fbc,0x2e992ffc,0xac87a934,0x2f6e2c07,0x2ed02faf,0xa99328d5,0xaf46ae1f,0x2cb02faf,0x2b5e2d72,0xaff4aed0,0xaff4afe6,0xad279cb6,
0x9fd926a1,0xa44eadba,0xae5eaf6e,0xaf30afd4,0x2d272ed0,0x230e2ddc,0xafafafff,0x2d272fe6,0x1fd929f1,0xafbcac87,0xacd8ae99,0xad4d9648,
0xac5da814,0xaa4eaf30,0x9648a934,0xaeb5afed,0xaf80ae3f,0x2ed028d5,0x2cb028d5,0x2aaaa875,0xa51526a1,0xad721648,0x9cb6aa4e,0xac3226a1,
0xae3fac07,0xae1faffc,0x2d272934,0xaf02afbc,0xaffcafa0,0x2cd8a30e,0x2fed2f02,0x2b05a8d5,0xad96af46,0x2e992fe6,0x2e992fc9,0x2f5a2f80,
0xafffadba,0xae7caeb5,0xafc9aeb5,0x2d722f6e,0x217ead4d,0x2ff42814,0x2875ac07,0xaff8ab05,0x2fed2e3f,0xad4d2b5e,0x2f912f1a,0x2e5ea875,
0xa5db2cb0,0x9648af80,0xa9f12aaa,0xa5db2ed0,0xad00afff,0xa17eafc9,0xa17eae7c,0xabb72d72,0x2ee925db,0x2d4d2f5a,0x2ffc2d96,0xa44eafdd,
0x29f12f91,0xafd4ac07,0xa6a12cd8,0x2d962f30,0xafc9ab5e,0x2f46a30e,0xaf80af02,0xafe6ab5e,0x25dbad4d,0x2d96ac07,0x2f5a2814,0xafddab05,
0x2f462f1a,0xa7652f02,0x25152f02,0x2f80a17e,0xad002765,0xa8d5afff,0xaff8ad72,0xad002cb0,0xacd8b000,0x2dfe2eb5,0x2934ac5d,0x244eaf5a,
0x2ee9217e,0x2ffc2875,0x2d4d2ff4,0xa44eaff8,0x25db2f46,0xaf6e2515,0xaf6ea765,0x2c5d2f80,0xafe6ad96,0x2d72ac87,0x9cb6aeb5,0xaed0ad96,
0x2bb7ab05,0xa8d52ee9,0x2fa02e5e,0x2ff42934,0x2f912e3f,0x2cd82f1a,0xac072b5e,0x2f30a875,0xad962765,0xaeb5ad72,0xac87afff,0xad962cb0,
0xa993afd4,0x2fc92a4e,0x2fe62a4e,0x2aaaae99,0x2ff82cd8,0xaff49fd9,0xa8752d4d,0xa17e2fbc,0x29f12fed,0xa6a12f91,0xafd4ad4d,0x2d962e5e,
0xafe6ad00,0x9cb6aff8,0x2d72a8d5,0xaed0ad00,0x2d27a993,0x28752fe6,0x28752fc9,0x2fa02aaa,0x29342fdd,0xac07af5a,0xafbcad96,0xaffca5db,
0xab5e2cb0,0xaf022aaa,0xa30eaf80,0xab5e2ed0,0xab05b000,0x2e5eac5d,0x2ee92eb5,0x2934af5a,0x2fdd2cd8,0xad962d4d,0xaf5a9fd9,0xa5db2fbc,
0xaddc2875,0x2cb0ae1f,0x2765ae1f,0x1cb6aff4,0xafc9a5db,0xaf80a9f1,0x2f469648,0xafe6a5db,0x2bb7acd8,0x2fa02934,0xa8d52dfe,0x2ff4244e,
0x29342ff8,0xafbca875,0xac07aff4,0xaffca17e,0xaf5aaddc,0x2fd42765,0x2fd42cb0,0x30001cb6,0xa993af6e,0x2765afdd,0xa515afdd,0xaaaa3000,
0x28d52f91,0xaf022e5e,0x230e2fed,0x2fa0ad4d,0xa814afaf,0x2f91a17e,0x9fd9aff8,0xaee9a30e,0x26a12fc9,0xaa4ead72,0x16482fff,0x26a12e7c,
0x2bb7af46,0x2f1aae7c,0x2f1aac32,0xaff42993,0xacd82eb5,0xaf301648,0xaf912a4e,0x2c072c5d,0x2dbaadfe,0x25db2e5e,0x2fdda814,0x2a4eaffc,
0xae7c2d27,0x2d72afaf,0xafff230e,0xafc92d27,0x2fd4a934,0x2f6ea44e,0x2dba2cd8,0xa6a1adfe,0xafff217e,0xa515ae3f,0xac32ae3f,0xaddc2fa0,
0x2faf2515,0xae1f2f80,0x28d52f46,0x2fafa765,0xaee9aa4e,0x2f91a5db,0x9fd9afdd,0xa814adba,0x2e5e2b5e,0x29342d00,0xab052faf,0x2ee9af1a,
0xac5daddc,0x2dbaafc9,0x2dbaae7c,0xae999cb6,0x27652f5a,0xaf8026a1,0xaf462c87,0xa5152f5a,0x230eaffc,0x217e2e5e,0x2ff8a814,0x2fafadfe,
0x1fd92faf,0xac072ff8,0xafed217e,0x2dfe230e,0x29f1afe6,0x2fddaaaa,0x2eb52993,0x29f1afc9,0xaddc2e99,0xa515adba,0xac32adba,0xafff2c5d,
0x2fa0ac07,0xaf022f30,0x230e2f91,0x28d52cd8,0xadba2ee9,0xafdd2dfe,0xa5dbaf30,0xaa4e2fbc,0x2fc9abb7,0x2aaa2b5e,0xa9932ff8,0x2fe6abb7,
0xafa09cb6,0x2e3fafc9,0x2e3fae7c,0xa17eaddc,0x2d4d2c5d,0xae5e1648,0xafed2a4e,0xaf912eb5,0xaff82765,0xae3f1cb6,0x2f02addc,0xaff82cb0,
0x2dfe2a4e,0xac072fdd,0xafed25db,0x1fd92dba,0xa6a1aee9,0x2f6ea934,0x2dba2b05,0x2fd4ae5e,0xaaaa2ff4,0x2765af1a,0xa515af1a,0xa993abb7,
0xacb0ac5d,0x9cb6ad96,0x2ddc29f1,0xa765ac5d,0xa30e2fbc,0xaff82dfe,0xa17eaf30,0xafaf2ee9,0x2dfeaf1a,0x244e2d00,0xacd82faf,0x29342b5e,
0xb0002993,0x2fddae7c,0x2fddac32,0x2f6eaf46,0x2ddcb000,0x2fe6afd4,0x2ed0afd4,0xafff2f5a,0xad279fd9,0x2d00aee9,0xabb7a814,0xae1f2f91,
0xae5e2ff4,0x9fd9a8d5,0xaf302fa0,0xa44e2bb7,0x2c872515,0xadba2aaa,0x2a4e2993,0x2c87a765,0x2ff4ad72,0x2e1fac32,0x2e1fa515,0xa8759cb6,
0x2814ae99,0x2ffcaf6e,0x2dfeb000,0xae5e2c87,0xaf5a2b05,0x2eb5afbc,0xac5da44e,0xb0002f91,0xac322fa0,0x2993ad00,0xaf462faf,0xae7c2fa0,
0x2c871fd9,0x16482814,0xa9f12ee9,0x2e99af91,0x2f80afa0,0x2c32a875,0x2e7ca875,0x2aaaad27,0xa30eac32,0x2f1aaddc,0x2e1fafff,0xa30ea515,
0xafed2d96,0x2ffcafd4,0xab05a6a1,0xacd829f1,0xa8142e1f,0xadfe2f02,0xaffc2e3f,0x2e5ead27,0x2e99a993,0xaa4e2cb0,0xaa4e2ed0,0x2fd4af46,
0x2e7cb000,0x1cb625db,0x2ddca6a1,0x2fc9b000,0xa875a934,0x2b5ea814,0x2f1aafed,0x2e3faf30,0xaf302ff4,0xafed2fa0,0xa814a8d5,0xa9342bb7,
0x16482c32,0xafd42fff,0xafdd2ddc,0x16482515,0x2f46ac5d,0xaed02f6e,0xacb02f6e,0x2993a5db,0x2e1fafed,0xad002dfe,0x2bb71fd9,0x2d27ac07,
0xaf5a2cd8,0xac5d2b05,0x2eb5affc,0xb0002fed,0xae7c2ff4,0xaddc2d27,0x9cb6ab5e,0xafc92ff4,0x217e2aaa,0xaf022e7c,0xaf022c32,0xaf1a2f80,
0x2f30ac87,0xafbc2f6e,0xaee93000,0xadfe2e99,0xa8d5a515,0x2875a993,0x2e3faaaa,0xa8d52765,0xaf912d96,0x244ea6a1,0x2fbcafd4,0xab0529f1,
0xae992fed,0x96489fd9,0x29f1adfe,0xac872c07,0x9cb62bb7,0xa515217e,0xac32217e,0xad722d00,0x2c32ae99,0x2f46af5a,0xa9932d96,0x2e7cae99,
0xa875a44e,0x2f1aaf30,0x2b5e9fd9,0x2e3fae5e,0xaf302d27,0x2ee9af02,0x2fbcae3f,0x2dfeae1f,0xaf6e2fff,0x2eb5aed0,0x2eb5afe6,0x2dbaaddc,
0xaddcadba,0xafe6aeb5,0xaed0aeb5,0x2fff2f6e,0xae1fadfe,0xae3fafbc,0xaf02aee9,0x2d272f30,0xae5eae3f,0x9fd9ab5e,0xaf30af1a,0xa44e2875,
0xae99ae7c,0x2d962993,0xaf5aaf46,0xae99ac32,0xad00ad72,0xa17eac32,0xa17ea515,0xabb79cb6,0xac07ac87,0x2dfe29f1,0x1fd99648,0xafedae99,
0xa9f1ab05,0x2fd42fbc,0x26a1244e,0xad96af91,0xa765a8d5,0x2aaa2e3f,0x29932875,0x2515a8d5,0x2e992dfe,0x30002ee9,0x2f6e2fbc,0xac87af30,
0x2f802f1a,0x2c322f02,0x2e7c2f02,0x2aaaa17e,0x2ff42fc9,0xab5e1cb6,0x2d272ddc,0x2ff42e7c,0x2fed3000,0xaffcaeb5,0x2b052c5d,0x2cd82f5a,
0x2c072d27,0x9fd92bb7,0xadfead00,0x2fed2e1f,0x25db2993,0xaf6eacb0,0xaf6eaed0,0x2c5d2f46,0xa5151648,0xaddcafdd,0xafffafd4,0xac321648,
0xabb7a934,0x28d5a814,0xafa0afed,0xaff4af30,0xaf30ae3f,0xafedaf1a,0xa814ab5e,0xa9342875,0xb000afc9,0xa6a1addc,0x25db9cb6,0xb000ae7c,
0xaf46afd4,0x2ed02a4e,0x2cb02a4e,0xa993ae99,0xad27ae5e,0x2e3f2ffc,0x2f022dfe,0x2e1f2814,0xa9f1acd8,0x26a1ab05,0x2fd42ffc,0xad96afed,
0x2515a30e,0x2fff2e1f,0x2ddc2f1a,0x2c32a30e,0x2d272aaa,0x28752e7c,0x28752c32,0x2fa02f80,0x2f912e99,0xaee9a9f1,0xa8141648,0x9fd92c87,
0x2fa02e7c,0x2faf2f46,0xad00a993,0x2fa02c32,0x2f913000,0xa44e2c5d,0xafbcaeb5,0x2b052f5a,0x2c872e5e,0xb000adfe,0xaf6eaffc,0xae99a814,
0x9cb62875,0xa515ae1f,0xac32ae1f,0xad72aff4,0x27652c87,0xa9932a4e,0xaaaaadba,0xa5152c87,0xabb7a44e,0xafa0af30,0x28d59fd9,0xaff4ae5e,
0xaf91ae1f,0x2814abb7,0x2ee92d00,0x1fd9ad27,0xaf5aafff,0x2fd42ed0,0x2fd42fe6,0x30002ddc,0xaf46af6e,0xac32afdd,0xae7cafdd,0x29933000,
0x2b5ea934,0x2faf2cd8,0x2d00a44e,0xaf1aadfe,0x2ee92faf,0xaf30217e,0x2dfe2ff8,0x2fbc230e,0xac5d2765,0x29f1addc,0xad961cb6,0xac5d2cb0,
0x2bb7a993,0x2f1aa515,0x2f1a2765,0xaff4aaaa,0x2e5e2fd4,0xab052dba,0x29342f6e,0x2ee9a6a1,0xadba1fd9,0xa5dbafed,0xafddac07,0xaa4e2dfe,
0xacb0aff8,0x2ddc2f02,0x9cb6ae3f,0xa765aff8,0x2eb52f91,0x2a4e2fed,0x16482e5e,0x2c5dad4d,0xaddc217e,0xae7cae3f,0xafc9ae3f,0x9cb62fa0,
0xabb7afe6,0x2ff82993,0x2b5eaaaa,0xabb7afc9,0x2fbc2a4e,0xaf3025db,0x2dfe2fdd,0x2ee92dba,0xacd828d5,0xaf91230e,0xaf30af02,0x2c072fa0,
0xac5dafff,0x2dbaac32,0x2dbaa515,0xae99addc,0x2fc929f1,0xa9932eb5,0x2aaa2fdd,0x2fe629f1,0xa30e2dfe,0xa17eafed,0xaff8ac07,0xafaf1fd9,
0xadfeafaf,0xa814aff8,0x2e5ea17e,0xaffca30e,0x2f5a2515,0x2c872f46,0x26a12f80,0x2f5aa765,0x9cb62e99,0xae7cadba,0xafc9adba,0xaddc2c5d,
0xaf1aaee9,0x2faf2b05,0x2d00a934,0x2b5eae5e,0x2dbaa814,0x2fdd9fd9,0x25db2f91,0x2a4eaee9,0x27652faf,0xaf4628d5,0xaf80ae1f,0xa5152faf,
0xafa0addc,0x2e3fac32,0x2e3fa515,0xa17eafff,0x2dfea6a1,0xacd82dba,0x244e2f6e,0x29342fd4,0x2d272fc9,0x230e2fff,0xafafad72,0x2d272e7c,
0xaffcaa4e,0xa814afdd,0x2e5ea5db,0xadfeadba,0x2c5dac07,0x2a4e2f91,0x16482f30,0x2eb52cd8,0x29932ff4,0xac32af1a,0xae7caf1a,0xaf46abb7,
0xae7c26a1,0xafff1648,0x2d72aa4e,0xafc926a1,0x230eaee9,0x2ff89fd9,0x217e2f91,0x2fafa814,0x2d4d2fa0,0xafed230e,0xae5eaf02,0xaf9128d5,
0xb000aaaa,0x2fdda515,0x2fdd2765,0x2f6ea993,0x1cb6b000,0x2cb0afd4,0x2765afd4,0xaddc2f5a,0xa17e2ffc,0xaff42c07,0xa8752fbc,0x2ff8a934,
0x244eaff4,0x2dfe28d5,0x2934afa0,0xacd8abb7,0xa5db2fe6,0x9648af46,0xa9f12f80,0xa5db2fc9,0x2ff41cb6,0x2e1f2765,0x2e1f2cb0,0xa875addc,
0xafbca5db,0x1fd9af5a,0xad4dad96,0xacd82fdd,0x2f5a2934,0xaeb52ee9,0x2c5d2e5e,0x3000ab05,0xaed0ab5e,0x2f80a30e,0xaaaaaf02,0xacb0ab5e,
0xa5db2ffc,0xad962fbc,0xaf5a2c07,0x2fdda934,0x2aaaafa0,0x2fc9a875,0x2fe6a875,0xa993ad27,0xad002ed0,0xa8d5ad72,0xaff81cb6,0xad002fe6,
0x2e5ead96,0xad4d2fd4,0x2f9126a1,0x2feda9f1,0xafbca17e,0xad4da875,0x1fd9aff4,0xacd82ff8,0x2e992aaa,0xaa4e2fe6,0xaa4e2fc9,0x2fd4a993,
0xacb0ad96,0x2fffac87,0x2d72aeb5,0xa765ad96,0x28752f30,0xab5eac07,0xaf1a2cd8,0xae3f2f91,0x2934aff4,0x2e5eafa0,0x2ee928d5,0xab05abb7,
0xad962ed0,0xaeb51cb6,0xac87ad72,0xad962fe6,0x2f80ac5d,0xa7652f6e,0x25152f6e,0x2f46a5db,0xaff8244e,0x2ff4ad4d,0x2875affc,0x217eaee9,
0x2f5a244e,0x2c5d2934,0xaeb52dfe,0x3000acd8,0xacb0ad00,0x2d72aff8,0x2fffa8d5,0xa765ad00,0x217e2f80,0xaf022515,0xaf02a765,0xaf1a2f46,
0x2b05afdd,0xa8142f5a,0x2c072d96,0x2d4d25db,0xab5e2fe6,0xaf022f80,0xa30eaf46,0xab5e2fc9,0x2f30ad96,0x2cd826a1,0xac072fd4,0x2f91a9f1,
0xafdd244e,0x2d96affc,0x2f5aad4d,0x25dbaee9,0x2d722bb7,0xae7c217e,0xafc9217e,0xafff2d00,0xaed0a5db,0xaaaaa9f1,0x2f809648,0xacb0a5db,
0x28752e5e,0xaf1a2f91,0xab5ead4d,0xae3f2fed,0x2b05aff8,0x2c072875,0xa8142ff4,0x2d4d217e,0xaf6e2d72,0x2eb5afc9,0x2eb5ae7c,0x2dbaafff,
0x2f80af5a,0x2fc9ae99,0x2fe6ae99,0xaf462d96,0xa8d5ab05,0x2f02afed,0xa30eacd8,0xafa02ffc,0xafbc2f02,0x2934ad27,0xaffc2e1f,0xac072e3f,
0x26a12c32,0xaa4e1cb6,0x16482d72,0x26a12515,0x28752aaa,0xa8d52cb0,0xa8d52ed0,0x2e3faf80,0x2fedaeb5,0x29349648,0x2f30aa4e,0x2814ac5d,
0x1648ad4d,0x2e99acd8,0x2c87afbc,0xa9f11fd9,0xafe62d27,0x2fffafaf,0xaddc230e,0xaed02d27,0xafd42f30,0xaf6e2e5e,0xadba244e,0x26a11fd9,
0x9cb62d27,0xafe62ff4,0xaed02ff4,0x2d72ab5e,0x2fafacb0,0xae1f2f46,0x28d52993,0x2fafaed0,0x2c07af6e,0xa9342c87,0x2ffcae99,0x2fbcb000,
0xa44eab5e,0x2b05ad00,0x2f91afaf,0xafbc2f1a,0xafd42d72,0x1648a765,0x1648acb0,0xafdd2fff,0xac322f5a,0xaaaa26a1,0xaf802c87,0xae7c2f5a,
0x2d009fd9,0xae1f2cd8,0xad272fbc,0xabb72d4d,0x2ffcaf02,0x2ee9ae1f,0xa44e2d27,0x2d4dae3f,0x29f1ae7c,0x2fddaf80,0x2eb5aaaa,0x29f1ac32,
0xad7225db,0x2fe6b000,0x2ed0b000,0x1cb6a6a1,0xafa02fbc,0x2f02af91,0xa30eab05,0xa8d5244e,0x96482c07,0xac872d4d,0xae992b05,0x29f1a814,
0x2ed0abb7,0xa9932b5e,0xaf462ff8,0x2cb0abb7,0x2f1aafff,0xa30e2765,0xa30e2cb0,0x2e1fad72,0x1fd9ac5d,0x244e9648,0x2e5eaa4e,0x2f30aeb5,
0xaff82ed0,0xae3f2ddc,0x2f02afff,0xaff82fe6,0xad4d2f6e,0xaee92e99,0x244eac87,0xaffc3000,0x26a12814,0xaf6e2f30,0xadba2934,0xafd42fed,
0x2f46ad00,0xafc92fa0,0xafe62fa0,0xaf802faf,0x2515ac5d,0x2d72ad96,0x1cb629f1,0x2c32ac5d,0xad002814,0x2d27ad4d,0x2e1fab05,0x2bb7ac07,
0xaffc2f1a,0x2cd8ad00,0x2fedafaf,0x2b05ab5e,0xadba2f80,0x2c87acb0,0x2c87aed0,0x2a4eaaaa,0xaf80af6e,0xafc9afdd,0xafe6afdd,0x2f463000,
0xafa0af91,0xabb7ae5e,0xaff4afed,0x28d52d4d,0xafbcafaf,0x2934a17e,0xaffcaff8,0xac07a30e,0xafd4afc9,0x2f5a2d72,0xb000afff,0xafd4ae7c,
0x2bb72aaa,0x2f1a2cb0,0x2f1a2ed0,0xaff4af80,0x2cd82c5d,0x2f303000,0x2f912f5a,0xac07aeb5,0x2dba2d4d,0x25db2cd8,0x2fdd2fbc,0x2a4e9fd9,
0x2e7c2e1f,0xad72a875,0x2fff2ff4,0x2fc92e1f,0x26a12934,0xa9f1244e,0xad96acd8,0x2fd42dfe,0x9cb6217e,0xafe6ae3f,0xaed0ae3f,0x2d722fa0,
0xa875a515,0xad27af80,0xafa0af46,0xa8752765,0xac07aa4e,0x2934a5db,0xaffcafdd,0xafbcadba,0xae5eaf1a,0xa934ae3f,0x2b052875,0xaee9ab5e,
0xac5dad72,0x2dba2765,0x2dba2cb0,0xae99afff,0xa765aa4e,0x2f802fd4,0x2f462e99,0x2515aa4e,0x230e9fd9,0x217e2cd8,0x2ff82fbc,0x2faf2d4d,
0x2ffc2faf,0x2ee92ff8,0xa44e217e,0x2d4d230e,0x2f6e2fe6,0xa5db2aaa,0xac5da993,0x2f6e2fc9,0x2d722e99,0xafe6adba,0xaed0adba,0x9cb62c5d,
0x28d52c07,0xabb7af30,0xaff4af91,0xafa0acd8,0xadbaac07,0xafddad4d,0xa5dbab05,0xaa4e2814,0xafc9af02,0xaaaaaf1a,0x2993217e,0xafe6af02,
0xafa0afff,0x2e3f2765,0x2e3f2cb0,0xa17ead72,0xad4daeb5,0x2e5e3000,0x2fed2f5a,0x2f912c5d,0x217ea765,0x2d009cb6,0x2bb72ddc,0x217eacb0,
0x2d4d2a4e,0x2ee92fdd,0xa44e25db,0x2ffc2dba,0x2fd42ee9,0xa9f12934,0xad96ab05,0x26a12e5e,0x2f462ff4,0xafc9af1a,0xafe6af1a,0xaf80abb7,
0x2cb02eb5,0x1cb62dba,0xaddcaf6e,0x27652eb5,0xa30e2814,0xaff8ad4d,0xa17eab05,0xafafac07,0xadfeab5e,0xa44eae3f,0x2cd82875,0xa934af1a,
0xb000af80,0x2fdd2cb0,0x2fdd2ed0,0x2f6e2aaa,0xad72b000,0xa515afd4,0xac32afd4,0x9cb62f5a,0x2e1f1fd9,0x2e3f2ee9,0x2f022814,0xad27af91,
0x2cd82ff4,0xaffca8d5,0x2b052fa0,0x2fed2bb7,0xae99a515,0x2d96aaaa,0xaf5aa993,0xae992765,0x2ff42ddc,0x2e1f2ed0,0x2e1f2fe6,0xa875afff,
0xa8142c87,0xaffca9f1,0xadfe1648,0x2e5e2e99,0xaf5aaf30,0x2eb5a814,0xac5dafed,0xb000a934,0x2c32a8d5,0xa9932e3f,0x2f462875,0x2e7ca8d5,
0xae999fd9,0xb000a814,0xaf6eaee9,0x2c872f91,0xa993afa0,0x2ed0a875,0x2cb0a875,0xaf46ad27,0x2ff42c32,0xab5e2ddc,0x2d272fff,0x2ff42515,
0xa44e2d96,0x9fd9afd4,0xaf30a6a1,0xae5e29f1,0x2814ad27,0x2dfeabb7,0x2ffc2d00,0xae5eae1f,0x2e992f80,0xaa4e2e7c,0xaa4e2c32,0x2fd42aaa,
0xae7c1648,0x9cb6afdd,0xaddcafd4,0xafc91648,0xa875af91,0x2b5e2fbc,0x2f1a244e,0x2e3fab05,0x2b052ff4,0xa44e2fa0,0xafbca8d5,0x2f912bb7,
0xb000ac32,0xa6a1afff,0x25dbaddc,0xb000a515,0x2aaaac5d,0x2c322f6e,0x2e7c2f6e,0x2f80a5db,0x2d272fed,0xae3fadfe,0xaf029fd9,0xae1f2c07,
0xaf5aae5e,0xac5daf30,0x2eb59fd9,0xb000a44e,0x2e7ca30e,0x2ddc2e1f,0x1cb62f1a,0x2fc9a30e,0x217e2f46,0xaf02acb0,0xaf02aed0,0xaf1a2993,
0xaf30ae99,0x2fbc29f1,0x2ee99648,0x2dfeac87,0x2fa02515,0x2faf2993,0xad002aaa,0x2fa0a765,0xa9342d96,0xafeda6a1,0xa814afd4,0xaf3029f1,
0xac87afed,0x30001fd9,0x2f6e2dfe,0x2e99ac07,0x2fff2bb7,0xafe6217e,0xaed0217e,0xaddc2d00,0xac322c87,0xaf462a4e,0x2993adba,0xae7c2c87,
0xa875afed,0x2f1aab05,0x2b5e2ffc,0x2e3facd8,0x2f302e1f,0xaee92bb7,0xafbcad00,0xadfe2d27,0xaf6e9cb6,0x2eb5ac32,0x2eb5a515,0x2dbaad72,
0x2aaaaf5a,0x2ed0ae99,0x2cb0ae99,0xaf802d96,0xab5e2f30,0xafaf244e,0xad002e5e,0x2f1a1fd9,0x2c07af02,0x2b052d27,0x2d4dae1f,0xa814ae3f,
0xac5d2ed0,0x29f1afff,0xad962ddc,0xac5d2fe6,0x28752f80,0xa8d52fe6,0xa8d52fc9,0x2e3faf46,0xa44eafd4,0x2f91adba,0x2b05af6e,0xafbc26a1,
0x96482ffc,0xae99a44e,0xac872ee9,0x29f12d4d,0x2515aff8,0x1cb62f02,0x2d72ae3f,0x2c32aff8,0xaeb5ab05,0xaa4eacd8,0x9648afed,0xac5d2ffc,
0x2d722d27,0xacb02ff4,0xa7652ff4,0x2fffab5e,0xabb7ae7c,0x2ff8aaaa,0x2b5eaf80,0xabb7ac32,0x28142f6e,0xab05ac87,0xad4d2e99,0xac073000,
0x2feda8d5,0x2f30a30e,0x29342f02,0x2814afa0,0xafd49cb6,0x1648aed0,0x1648afe6,0xafdd2d72,0x2ed029f1,0xaf462eb5,0xa9932fdd,0x2cb029f1,
0xad00ad4d,0x2e1f244e,0x2d27aee9,0x2bb7affc,0xad4d2f02,0xafbc2e1f,0xacd8ad27,0x1fd92e3f,0x2f5aacb0,0x2c872993,0x26a12f46,0x2f5aaed0,
0xafff25db,0x2cb0b000,0x2765b000,0xad72a6a1,0x2f1a2814,0xafaf2934,0xad002f30,0xab5e2fed,0x1648afbc,0x2c87affc,0x2e992934,0xa9f1ac07,
0xac322faf,0xaf8028d5,0xaaaaae1f,0xae7c2faf,0x2f1aad72,0xa30e2ed0,0xa30e2fe6,0x2e1f1cb6,0xaffc26a1,0x2fedadba,0x2cd8af6e,0x2b05afd4,
0x2d272c32,0x230e2d72,0xafaf1cb6,0x2d272515,0x9fd9af6e,0x2fbcae99,0x2cd82c87,0x2d4db000,0xac5d2fbc,0xaa4eab05,0x9648af91,0xaeb5244e,
0x2f80ad00,0xaed02fa0,0xacb02fa0,0xaaaa2faf,0xafe626a1,0xaddc1648,0x2fffaa4e,0xaed026a1,0x2d002c07,0xad272ffc,0xae1fa934,0xabb72fbc,
0x1fd9afa0,0x2e5ea30e,0x244e2f02,0x2f30a8d5,0xadba2f46,0x2c87afe6,0x2c87afc9,0x2a4eaf80,0x2fffad96,0x2e7cac5d,0x2fc9ac5d,0xad7229f1,
0x217eadfe,0x2ff4afbc,0x2875aee9,0xaff82f30,0xafed2d00,0x2d4daf1a,0xaf912b5e,0xae5e2faf,0xa5db2e7c,0x9648a993,0xa9f12f46,0xa5db2c32,
0xae3f2fff,0xaff82fc9,0xaff82e7c,0x2f02ad72,0x2c0725db,0xadfe2f5a,0x9fd92d96,0x2fedafdd,0x2f6eaf91,0xa6a12c07,0x2fd4acd8,0x2dbaaf30,
0xa765ab5e,0x2aaaa30e,0x2993af02,0x2515ab5e,0x25dbadfe,0x2d96aee9,0x2f5aafbc,0xafdd2f30,0xaf462b5e,0x2765abb7,0xa515abb7,0xaf802ff8,
0xad002fc9,0xa8d51cb6,0xaff82ddc,0xad002e7c,0x2cd81648,0xadfe2c5d,0xa9342eb5,0xa44e2a4e,0x2c07217e,0x9fd92875,0xadfe2ff4,0x2fedaff8,
0x2fddaf46,0x29f1a515,0x29f12765,0x2eb5af80,0x2515ad96,0x2ddcac87,0x2fffaeb5,0x2c32ad96,0xaf022b05,0x2fa0aee9,0x28d5ae5e,0x230ea934,
0xaf912d00,0xacd82b5e,0x2c07af1a,0xaf302faf,0xad962fc9,0xaeb52ddc,0xac871cb6,0xad962e7c,0x299326a1,0xafc92f5a,0xafe62f5a,0xaaaa2c87,
0x2ff8ae5e,0xaff42ffc,0xa8752dfe,0xa17e2814,0x2f6eafed,0x2fd4af91,0xa6a12d4d,0x2dbaae5e,0x2515ad00,0x2fffaff8,0x2ddca8d5,0x2c32ad00,
0xae1f2993,0x2fafafe6,0x2fafafc9,0x28d5aaaa,0xaf912fdd,0x2ee9af5a,0x2814ad96,0x1fd9a5db,0xab5e2e7c,0xaf022f46,0xa30ea993,0xab5e2c32,
0x2b051648,0xae5e2eb5,0xaee92c5d,0xa9342a4e,0x2fddae5e,0xad962dfe,0xaf5a2ffc,0xa5db2814,0x2ddcafaf,0xacb02d27,0xa7652d27,0x9cb6230e,
0xa765a5db,0x2993a9f1,0x2aaa9648,0x2515a5db,0xaf022cd8,0x28d5a934,0x2fa0adfe,0x230ea44e,0xaf912ff8,0x2814a875,0x2ee9aff4,0x1fd9a17e,
0xaa4e2ddc,0x26a1a765,0x26a1acb0,0x16489cb6,0x9d7f9e49,0xaddcaeb3,0x12480000,0x22ad0000,0x9bdb9cb6,0xac2ead04,0x18b61648,0x290226ad,
0x98b69a49,0xa902aaaf,0x1bdb1a49,0x2c2e2aaf,0x92489648,0xa2ada6ad,0x1d7f1cb6,0x2ddc2d04,0xa420a4b7,0xae8daf7f,0x18b60000,0x23760000,
0xa1e4a312,0xacacad9c,0x1f121cb6,0x29992777,0x9f12a0b6,0xa999ab78,0x21e420b6,0x2cac2b78,0x98b69cb6,0xa376a777,0x24202312,0x2e8d2d9c,
0xa6e0a7db,0xaf3fb025,0x1bdb0000,0x24200000,0xa4e9a5e4,0xad2aae34,0x21e41fdb,0x2a312820,0xa1e4a3db,0xaa31ac21,0x24e923db,0x2d2a2c21,
0x9bdb9fdb,0xa420a820,0x26e025e4,0x2f3f2e34,0xa8d0a980,0xaff2b08c,0x1d7f0000,0x24840000,0xa6e0a820,0xada9aecd,0x2420217f,0x2ac82885,
0xa420a580,0xaac8ac86,0x26e02580,0x2da92c86,0x9d7fa17f,0xa484a885,0x28d02820,0x2ff22ecd,0xaa31ab13,0xb052b0f3,0x1f120000,0x24e90000,
0xa86ba94e,0xae28af65,0x254d2312,0x2b5f28e9,0xa54da712,0xab5faceb,0x286b2712,0x2e282ceb,0x9f12a312,0xa4e9a8e9,0x2a31294e,0x30522f65,
0xab91ac54,0xb0acb15a,0x20520000,0x254d0000,0xa967aa7c,0xaea7affe,0x267b2452,0x2bf6294e,0xa67ba852,0xabf6ad50,0x29672852,0x2ea72d50,
0xa052a452,0xa54da94e,0x2b912a7c,0x30ac2ffe,0xac79ad1e,0xb106b1c1,0x211b0000,0x25b20000,0xaa63abab,0xaf26b04c,0x27a9251b,0x2c4729b3,
0xa7a9a91c,0xac47adb6,0x2a63291c,0x2f262db6,0xa11ba51b,0xa5b2a9b3,0x2c792bab,0x3106304c,0xad2aade8,0xb160b229,0x21e40000,0x26170000,
0xab5fac6d,0xafa5b099,0x286b25e4,0x2c932a17,0xa86ba9e5,0xac93ae1b,0x2b5f29e5,0x2fa52e1b,0xa1e4a5e4,0xa617aa17,0x2d2a2c6d,0x31603099,
0xb1bbb292,0xb44fb4f6,0x267b0000,0x28d00000,0xb012b0e6,0xb216b357,0x2cde2a7c,0x2f3f2cd2,0xacdeae80,0xaf3fb0d9,0x30122e80,0x321630d9,
0xa67baa7c,0xa8d0acd2,0x31bb30e6,0x344f3357,0xb216b2fb,0xb47eb52d,0x26e00000,0x29020000,0xb052b133,0xb257b3a7,0x2d2a2ae1,0x2f8c2d04,
0xad2aaee6,0xaf8cb10c,0x30522ee6,0x3257310c,0xa6e0aae1,0xa902ad04,0x32163133,0x347e33a7,0xb271b364,0xb4aeb565,0x27440000,0x29350000,
0xb092b181,0xb298b3f7,0x2d762b46,0x2fd82d37,0xad76af4c,0xafd8b140,0x30922f4c,0x32983140,0xa744ab46,0xa935ad37,0x32713181,0x34ae33f7,
0xb2cdb3cf,0xb4deb59d,0x27a90000,0x29670000,0xb0d2b1ce,0xb2dab423,0x2dc22bab,0x30122d6a,0xadc2afb2,0xb012b174,0x30d22fb2,0x32da3174,
0xa7a9abab,0xa967ad6a,0x32cd31ce,0x34de3423,0xb329b41d,0xb50eb5d6,0x28070000,0x29990000,0xb113b21c,0xb31cb44c,0x2e0e2c08,0x30392d9c,
0xae0eb00c,0xb039b1a7,0x3113300c,0x331c31a7,0xa807ac08,0xa999ad9c,0x3329321c,0x350e344c,0xb386b453,0xb53fb60f,0x28390000,0x29cc0000,
0xb153b26b,0xb35eb474,0x2e5a2c3a,0x305f2dcf,0xae5ab03f,0xb05fb1db,0x3153303f,0x335e31db,0xa839ac3a,0xa9ccadcf,0x3386326b,0x353f3474,
0xb3e3b489,0xb570b649,0x286b0000,0x29fe0000,0xb194b2b9,0xb3a0b49d,0x2ea72c6d,0x30852e02,0xaea7b072,0xb085b20f,0x31943072,0x33a0320f,
0xa86bac6d,0xa9feae02,0x33e332b9,0x3570349d,0xb420b4bf,0xb5a1b683,0x289e0000,0x2a310000,0xb1d5b308,0xb3e3b4c6,0x2ef32c9f,0x30ac2e34,
0xaef3b0a5,0xb0acb243,0x31d530a5,0x33e33243,0xa89eac9f,0xaa31ae34,0x34203308,0x35a134c6,0xb5d2b6be,0xb76fb857,0x2a630000,0x2bf60000,
0xb413b4ef,0xb523b642,0x30d22e67,0x32092ffe,0xb0d2b278,0xb209b40f,0x34133278,0x3523340f,0xaa63ae67,0xabf6affe,0x35d234ef,0x376f3642,
0xb604b6fa,0xb7a5b878,0x2a950000,0x2c140000,0xb434b519,0xb546b66d,0x30f92e9a,0x32303019,0xb0f9b2ac,0xb230b42a,0x343432ac,0x3546342a,
0xaa95ae9a,0xac14b019,0x36043519,0x37a5366d,0xb637b736,0xb7dbb899,0x2ac80000,0x2c2e0000,0xb456b542,0xb569b699,0x31202ecd,0x32573032,
0xb120b2e1,0xb257b445,0x345632e1,0x35693445,0xaac8aecd,0xac2eb032,0x36373542,0x37db3699,0xb66ab773,0xb809b8bb,0x2afa0000,0x2c470000,
0xb478b56c,0xb58cb6c6,0x31462f00,0x327e304c,0xb146b315,0xb27eb460,0x34783315,0x358c3460,0xaafaaf00,0xac47b04c,0x366a356c,0x380936c6,
0xb69db7b0,0xb825b8dd,0x2b2d0000,0x2c600000,0xb49ab596,0xb5afb6f2,0x316d2f32,0x32a53065,0xb16db34a,0xb2a5b47b,0x349a334a,0x35af347b,
0xab2daf32,0xac60b065,0x369d3596,0x382536f2,0xb6d1b7ee,0xb841b8ff,0x2b5f0000,0x2c790000,0xb4bcb5c1,0xb5d2b71f,0x31942f65,0x32cd307f,
0xb194b37f,0xb2cdb496,0x34bc337f,0x35d23496,0xab5faf65,0xac79b07f,0x36d135c1,0x3841371f,0xb705b817,0xb85db923,0x2b910000,0x2c930000,
0xb4deb5eb,0xb5f6b74d,0x31bb2f98,0x32f43099,0xb1bbb3b4,0xb2f4b4b1,0x34de33b4,0x35f634b1,0xab91af98,0xac93b099,0x370535eb,0x385d374d,
0xb73ab837,0xb87ab946,0x2bc40000,0x2cac0000,0xb500b616,0xb61ab77a,0x31e22fcb,0x331c30b2,0xb1e2b3e9,0xb31cb4cd,0x350033e9,0x361a34cd,
0xabc4afcb,0xacacb0b2,0x373a3616,0x387a377a,0xb897b96b,0xb98dbaa6,0x2cc50000,0x2d900000,0xb63eb7a8,0xb767b895,0x334330cc,0x3442319a,
0xb343b4e8,0xb442b5c8,0x363e34e8,0x376735c8,0xacc5b0cc,0xad90b19a,0x389737a8,0x398d3895,0xb8b4b990,0xb9aebad1,0x2cde0000,0x2da90000,
0xb662b7d7,0xb78db8ae,0x336b30e6,0x345631b4,0xb36bb504,0xb456b5e4,0x36623504,0x378d35e4,0xacdeb0e6,0xada9b1b4,0x38b437d7,0x39ae38ae,
0xb8d2b9b5,0xb9cfbafd,0x2cf80000,0x2dc20000,0xb687b803,0xb7b4b8c7,0x339330ff,0x346a31ce,0xb393b51f,0xb46ab601,0x3687351f,0x37b43601,
0xacf8b0ff,0xadc2b1ce,0x38d23803,0x39cf38c7,0xb8f0b9dc,0xb9f1bb29,0x2d110000,0x2ddc0000,0xb6acb81b,0xb7dbb8e1,0x33bb3119,0x347e31e8,
0xb3bbb53b,0xb47eb61e,0x36ac353b,0x37db361e,0xad11b119,0xaddcb1e8,0x38f0381b,0x39f138e1,0xb90fba02,0xba14bb57,0x2d2a0000,0x2df50000,
0xb6d1b833,0xb801b8fb,0x33e33133,0x34933202,0xb3e3b557,0xb493b63a,0x36d13557,0x3801363a,0xad2ab133,0xadf5b202,0x390f3833,0x3a1438fb,
0xb92eba2a,0xba37bb86,0x2d440000,0x2e0e0000,0xb6f6b84b,0xb815b915,0x3405314d,0x34a7321c,0xb405b573,0xb4a7b657,0x36f63573,0x38153657,
0xad44b14d,0xae0eb21c,0x392e384b,0x3a373915,0xb94dba53,0xba5abbb6,0x2d5d0000,0x2e280000,0xb71bb863,0xb829b930,0x34193167,0x34bc3236,
0xb419b58f,0xb4bcb675,0x371b358f,0x38293675,0xad5db167,0xae28b236,0x394d3863,0x3a5a3930,0xb96dba7c,0xba7ebbe7,0x2d760000,0x2e410000,
0xb741b87c,0xb83db94b,0x342e3181,0x34d03250,0xb42eb5ab,0xb4d0b692,0x374135ab,0x383d3692,0xad76b181,0xae41b250,0x396d387c,0x3a7e394b,
0xa17fa248,0xb1cfb2a1,0x16480000,0x26ad0000,0x9fdba0b6,0xb029b0fd,0x1cb61a48,0x2d002aac,0x9cb69e48,0xad00aeaa,0x1fdb1e48,0x30292eaa,
0x96489a48,0xa6adaaac,0x217f20b6,0x31cf30fd,0xa81fa8b6,0xb27cb365,0x1cb60000,0x27760000,0xa5e4a711,0xb0a6b191,0x231120b6,0x2d972b75,
0xa311a4b6,0xad97af72,0x25e424b6,0x30a62f72,0x9cb6a0b6,0xa776ab75,0x281f2711,0x327c3191,0xaadeabd9,0xb328b414,0x1fdb0000,0x281f0000,
0xa8e8a9e3,0xb122b226,0x25e423db,0x2e2d2c1f,0xa5e4a7da,0xae2db01d,0x28e827da,0x3122301d,0x9fdba3db,0xa81fac1f,0x2ade29e3,0x33283226,
0xaccead7e,0xb3d3b475,0x217f0000,0x28840000,0xaadeac1f,0xb19eb2b9,0x281f257f,0x2ec32c83,0xa81fa97f,0xaec3b080,0x2ade297f,0x319e3080,
0xa17fa57f,0xa884ac83,0x2cce2c1f,0x33d332b9,0xae2daf0e,0xb43eb4d5,0x23110000,0x28e80000,0xac6aad4c,0xb219b34c,0x294d2711,0x2f592ce7,
0xa94dab11,0xaf59b0e4,0x2c6a2b11,0x321930e4,0xa311a711,0xa8e8ace7,0x2e2d2d4c,0x343e334c,0xaf8bb04e,0xb493b534,0x24520000,0x294d0000,
0xad65ae78,0xb294b3df,0x2a7a2852,0x2fef2d4c,0xaa7aac51,0xafefb147,0x2d652c51,0x32943147,0xa452a852,0xa94dad4c,0x2f8b2e78,0x349333df,
0xb074b115,0xb4e7b593,0x251b0000,0x29b10000,0xae5fafa4,0xb30fb438,0x2ba7291b,0x30422db0,0xaba7ad1a,0xb042b1aa,0x2e5f2d1a,0x330f31aa,
0xa51ba91b,0xa9b1adb0,0x30742fa4,0x34e73438,0xb122b1db,0xb53ab5f1,0x25e40000,0x2a160000,0xaf59b067,0xb389b481,0x2c6a29e3,0x308d2e14,
0xac6aade2,0xb08db20d,0x2f592de2,0x3389320d,0xa5e4a9e3,0xaa16ae14,0x31223067,0x353a3481,0xb58db64e,0xb805b887,0x2a7a0000,0x2cce0000,
0xb402b4c9,0xb5dfb6f9,0x30d72e78,0x332830cb,0xb0d7b26f,0xb328b4bd,0x3402326f,0x35df34bd,0xaa7aae78,0xacceb0cb,0x358d34c9,0x380536f9,
0xb5dfb6aa,0xb82ab8b0,0x2ade0000,0x2d000000,0xb43eb511,0xb61ab73d,0x31222edc,0x337130fd,0xb122b2d2,0xb371b4ed,0x343e32d2,0x361a34ed,
0xaadeaedc,0xad00b0fd,0x35df3511,0x382a373d,0xb631b705,0xb850b8d8,0x2b430000,0x2d330000,0xb47bb558,0xb654b780,0x316c2f40,0x33ba312e,
0xb16cb334,0xb3bab51d,0x347b3334,0x3654351d,0xab43af40,0xad33b12e,0x36313558,0x38503780,0xb682b75e,0xb874b900,0x2ba70000,0x2d650000,
0xb4b7b59f,0xb68db7c2,0x31b62fa4,0x34023160,0xb1b6b396,0xb402b54c,0x34b73396,0x368d354c,0xaba7afa4,0xad65b160,0x3682359f,0x387437c2,
0xb6d2b7b7,0xb899b927,0x2c060000,0x2d970000,0xb4f3b5e5,0xb6c6b802,0x32013004,0x34263191,0xb201b3f7,0xb426b57c,0x34f333f7,0x36c6357c,
0xac06b004,0xad97b191,0x36d235e5,0x38993802,0xb721b807,0xb8bcb94d,0x2c380000,0x2dc90000,0xb52fb62b,0xb6ffb822,0x324b3036,0x344b31c3,
0xb24bb42c,0xb44bb5ab,0x352f342c,0x36ff35ab,0xac38b036,0xadc9b1c3,0x3721362b,0x38bc3822,0xb76fb832,0xb8e0b972,0x2c6a0000,0x2dfb0000,
0xb56ab670,0xb737b842,0x32943067,0x346f31f4,0xb294b45d,0xb46fb5da,0x356a345d,0x373735da,0xac6ab067,0xadfbb1f4,0x376f3670,0x38e03842,
0xb7bdb85d,0xb902b996,0x2c9c0000,0x2e2d0000,0xb5a5b6b5,0xb76fb862,0x32de3099,0x34933226,0xb2deb48d,0xb493b608,0x35a5348d,0x376f3608,
0xac9cb099,0xae2db226,0x37bd36b5,0x39023862,0xb924b9ba,0xba1dbab5,0x2e5f0000,0x2fef0000,0xb7a6b881,0xb8a8b96d,0x34b73257,0x35d433df,
0xb4b7b637,0xb5d4b7a1,0x37a63637,0x38a837a1,0xae5fb257,0xafefb3df,0x39243881,0x3a1d396d,0xb946b9dc,0xba39bad0,0x2e910000,0x30100000,
0xb7ddb8a0,0xb8c1b989,0x34db3288,0x35f73408,0xb4dbb665,0xb5f7b7cd,0x37dd3665,0x38c137cd,0xae91b288,0xb010b408,0x394638a0,0x3a393989,
0xb966b9fe,0xba54bae9,0x2ec30000,0x30290000,0xb80ab8bf,0xb8dbb9a4,0x34ff32b9,0x361a3420,0xb4ffb693,0xb61ab7f9,0x380a3693,0x38db37f9,
0xaec3b2b9,0xb029b420,0x396638bf,0x3a5439a4,0xb986ba1f,0xba6fbb02,0x2ef50000,0x30420000,0xb825b8dd,0xb8f3b9be,0x352332ea,0x363c3438,
0xb523b6c1,0xb63cb812,0x382536c1,0x38f33812,0xaef5b2ea,0xb042b438,0x398638dd,0x3a6f39be,0xb9a6ba3f,0xba89bb1a,0x2f270000,0x305b0000,
0xb840b8fb,0xb90cb9d8,0x3546331b,0x365f3451,0xb546b6ee,0xb65fb828,0x384036ee,0x390c3828,0xaf27b31b,0xb05bb451,0x39a638fb,0x3a8939d8,
0xb9c5ba5e,0xbaa2bb30,0x2f590000,0x30740000,0xb85ab918,0xb924b9f2,0x356a334c,0x36823469,0xb56ab71b,0xb682b83d,0x385a371b,0x3924383d,
0xaf59b34c,0xb074b469,0x39c53918,0x3aa239f2,0xb9e3ba7c,0xbababb46,0x2f8b0000,0x308d0000,0xb874b935,0xb93cba0b,0x358d337d,0x36a43481,
0xb58db748,0xb6a4b852,0x38743748,0x393c3852,0xaf8bb37d,0xb08db481,0x39e33935,0x3aba3a0b,0xba00ba99,0xbad1bb5a,0x2fbd0000,0x30a60000,
0xb88eb951,0xb954ba23,0x35b133ae,0x36c63499,0xb5b1b775,0xb6c6b867,0x388e3775,0x39543867,0xafbdb3ae,0xb0a6b499,0x3a003951,0x3ad13a23,
0xbae8bb6e,0xbb7fbbdd,0x30be0000,0x31850000,0xb96bba3b,0xba19bae6,0x36e834b1,0x37f33570,0xb6e8b87c,0xb7f3b91d,0x396b387c,0x3a19391d,
0xb0beb4b1,0xb185b570,0x3ae83a3b,0x3b7f3ae6,0xbafebb80,0xbb8ebbe6,0x30d70000,0x319e0000,0xb982ba52,0xba2dbaf9,0x370a34c9,0x380a3587,
0xb70ab891,0xb80ab930,0x39823891,0x3a2d3930,0xb0d7b4c9,0xb19eb587,0x3afe3a52,0x3b8e3af9,0xbb13bb91,0xbb9cbbed,0x30f00000,0x31b60000,
0xb999ba69,0xba41bb0b,0x372c34e1,0x381a359f,0xb72cb8a6,0xb81ab943,0x399938a6,0x3a413943,0xb0f0b4e1,0xb1b6b59f,0x3b133a69,0x3b9c3b0b,
0xbb27bba0,0xbba9bbf4,0x31090000,0x31cf0000,0xb9afba7f,0xba54bb1d,0x374e34f9,0x382a35b6,0xb74eb8ba,0xb82ab956,0x39af38ba,0x3a543956,
0xb109b4f9,0xb1cfb5b6,0x3b273a7f,0x3ba93b1d,0xbb3abbaf,0xbbb5bbf8,0x31220000,0x31e80000,0xb9c5ba95,0xba67bb2e,0x376f3511,0x383a35ce,
0xb76fb8ce,0xb83ab969,0x39c538ce,0x3a673969,0xb122b511,0xb1e8b5ce,0x3b3a3a95,0x3bb53b2e,0xbb4cbbbc,0xbbc0bbfc,0x313b0000,0x32010000,
0xb9dabaaa,0xba7abb3e,0x37903529,0x384a35e5,0xb790b8e2,0xb84ab97b,0x39da38e2,0x3a7a397b,0xb13bb529,0xb201b5e5,0x3b4c3aaa,0x3bc03b3e,
0xbb5ebbc9,0xbbcbbbff,0x31530000,0x32190000,0xb9f0babf,0xba8cbb4e,0x37b23540,0x385a35fd,0xb7b2b8f6,0xb85ab98d,0x39f038f6,0x3a8c398d,
0xb153b540,0xb219b5fd,0x3b5e3abf,0x3bcb3b4e,0xbb6fbbd4,0xbbd4bc00,0x316c0000,0x32320000,0xba04bad3,0xba9ebb5d,0x37d23558,0x386a3614,
0xb7d2b909,0xb86ab99f,0x3a043909,0x3a9e399f,0xb16cb558,0xb232b614,0x3b6f3ad3,0x3bd43b5d,0x0,0x0,0x0,0x0,
0x2e1f0000,0x336431a8,0x33643400,0x2e1f31a8,0x31a80000,0x31a83400,0xb1a80000,0xb1a8b400,0x33640000,0xae1f31a8,0xae1fb400,0x336431a8,
0x34000000,0xb4000000,0x34000000,0xb4000000,0x33640000,0xae1fb1a8,0xae1f3400,0x3364b1a8,0x31a80000,0x31a8b400,0xb1a80000,0xb1a83400,
0x2e1f0000,0x3364b1a8,0x3364b400,0x2e1fb1a8,0x0,0x0,0x0,0x0,0xae1f0000,0xb36431a8,0xb3643400,0xae1f31a8,
0xb1a80000,0xb1a83400,0x31a80000,0x31a8b400,0xb3640000,0x2e1f31a8,0x2e1fb400,0xb36431a8,0xb4000000,0x34000000,0xb4000000,0x34000000,
0xb3640000,0x2e1fb1a8,0x2e1f3400,0xb364b1a8,0xb1a80000,0xb1a8b400,0x31a80000,0x31a83400,0xae1f0000,0xb364b1a8,0xb364b400,0xae1fb1a8,
0x0,0x0,0x0,0x0,0xae1f0000,0xb364b1a8,0xb364b400,0xae1fb1a8,0x31a80000,0x31a83400,0xb1a80000,0xb1a8b400,
0xb3640000,0x2e1fb1a8,0x2e1f3400,0xb364b1a8,0x34000000,0xb4000000,0x34000000,0xb4000000,0xb3640000,0x2e1f31a8,0x2e1fb400,0xb36431a8,
0x31a80000,0x31a8b400,0xb1a80000,0xb1a83400,0xae1f0000,0xb36431a8,0xb3643400,0xae1f31a8,0x0,0x0,0x0,0x0,
0x2e1f0000,0x3364b1a8,0x3364b400,0x2e1fb1a8,0xb1a80000,0xb1a83400,0x31a80000,0x31a8b400,0x33640000,0xae1fb1a8,0xae1f3400,0x3364b1a8,
0xb4000000,0x34000000,0xb4000000,0x34000000,0x33640000,0xae1f31a8,0xae1fb400,0x336431a8,0xb1a80000,0xb1a8b400,0x31a80000,0x31a83400,
0x2e1f0000,0x336431a8,0x33643400,0x2e1f31a8,0x34003400,0x34003400,0x34003400,0x34003400,0x33643400,0x2e1f31a8,0xae1f0000,0xb364b1a8,
0x31a83400,0xb1a80000,0xb1a8b400,0x31a80000,0x2e1f3400,0xb364b1a8,0x33640000,0xae1f31a8,0x3400,0xb400,0x3400,0xb400,
0xae1f3400,0x3364b1a8,0xb3640000,0x2e1f31a8,0xb1a83400,0x31a80000,0x31a8b400,0xb1a80000,0xb3643400,0xae1f31a8,0x2e1f0000,0x3364b1a8,
0xb4003400,0xb4003400,0xb4003400,0xb4003400,0xb3643400,0xae1f31a8,0x2e1f0000,0x3364b1a8,0xb1a83400,0x31a80000,0x31a8b400,0xb1a80000,
0xae1f3400,0x3364b1a8,0xb3640000,0x2e1f31a8,0x3400,0xb400,0x3400,0xb400,0x2e1f3400,0xb364b1a8,0x33640000,0xae1f31a8,
0x31a83400,0xb1a80000,0xb1a8b400,0x31a80000,0x33643400,0x2e1f31a8,0xae1f0000,0xb364b1a8,0x34003400,0x34003400,0x34003400,0x34003400,
0xb364b400,0xae1fb1a8,0x2e1f0000,0x336431a8,0x31a83400,0xb1a80000,0xb1a8b400,0x31a80000,0xae1fb400,0x336431a8,0xb3640000,0x2e1fb1a8,
0x3400,0xb400,0x3400,0xb400,0x2e1fb400,0xb36431a8,0x33640000,0xae1fb1a8,0xb1a83400,0x31a80000,0x31a8b400,0xb1a80000,
0x3364b400,0x2e1fb1a8,0xae1f0000,0xb36431a8,0xb4003400,0xb4003400,0xb4003400,0xb4003400,0x3364b400,0x2e1fb1a8,0xae1f0000,0xb36431a8,
0xb1a83400,0x31a80000,0x31a8b400,0xb1a80000,0x2e1fb400,0xb36431a8,0x33640000,0xae1fb1a8,0x3400,0xb400,0x3400,0xb400,
0xae1fb400,0x336431a8,0xb3640000,0x2e1fb1a8,0x31a83400,0xb1a80000,0xb1a8b400,0x31a80000,0xb364b400,0xae1fb1a8,0x2e1f0000,0x336431a8,
0x0,0x0,0x0,0x0,0xae1f0000,0xb364b1a8,0xb364b400,0xae1fb1a8,0xb1a80000,0xb1a8b400,0x31a80000,0x31a83400,
0xb3640000,0x2e1fb1a8,0x2e1f3400,0xb364b1a8,0xb4000000,0x34000000,0xb4000000,0x34000000,0xb3640000,0x2e1f31a8,0x2e1fb400,0xb36431a8,
0xb1a80000,0xb1a83400,0x31a80000,0x31a8b400,0xae1f0000,0xb36431a8,0xb3643400,0xae1f31a8,0x0,0x0,0x0,0x0,
0x2e1f0000,0x3364b1a8,0x3364b400,0x2e1fb1a8,0x31a80000,0x31a8b400,0xb1a80000,0xb1a83400,0x33640000,0xae1fb1a8,0xae1f3400,0x3364b1a8,
0x34000000,0xb4000000,0x34000000,0xb4000000,0x33640000,0xae1f31a8,0xae1fb400,0x336431a8,0x31a80000,0x31a83400,0xb1a80000,0xb1a8b400,
0x2e1f0000,0x336431a8,0x33643400,0x2e1f31a8,0x0,0x0,0x0,0x0,0x2e1f0000,0x336431a8,0x33643400,0x2e1f31a8,
0xb1a80000,0xb1a8b400,0x31a80000,0x31a83400,0x33640000,0xae1f31a8,0xae1fb400,0x336431a8,0xb4000000,0x34000000,0xb4000000,0x34000000,
0x33640000,0xae1fb1a8,0xae1f3400,0x3364b1a8,0xb1a80000,0xb1a83400,0x31a80000,0x31a8b400,0x2e1f0000,0x3364b1a8,0x3364b400,0x2e1fb1a8,
0x0,0x0,0x0,0x0,0xae1f0000,0xb36431a8,0xb3643400,0xae1f31a8,0x31a80000,0x31a8b400,0xb1a80000,0xb1a83400,
0xb3640000,0x2e1f31a8,0x2e1fb400,0xb36431a8,0x34000000,0xb4000000,0x34000000,0xb4000000,0xb3640000,0x2e1fb1a8,0x2e1f3400,0xb364b1a8,
0x31a80000,0x31a83400,0xb1a80000,0xb1a8b400,0xae1f0000,0xb364b1a8,0xb364b400,0xae1fb1a8,
};

typedef CUresult (*EncodeFn)(CUtensorMap*, CUtensorMapDataType, cuuint32_t, void*, const cuuint64_t*, const cuuint64_t*,
                             const cuuint32_t*, const cuuint32_t*, CUtensorMapInterleave, CUtensorMapSwizzle,
                             CUtensorMapL2promotion, CUtensorMapFloatOOBfill);

}

extern "C" void kernel_launch(void* const* d_in, const int* in_sizes, int n_in, void* d_out, int out_size) {
    Params p;
    p.x = (const __nv_bfloat16*)d_in[0];
    p.lar = (const __nv_bfloat16*)d_in[1];
    p.aim = (const __nv_bfloat16*)d_in[2];
    p.cr = (const __nv_bfloat16*)d_in[3];
    p.ci = (const __nv_bfloat16*)d_in[4];
    p.logdt = (const __nv_bfloat16*)d_in[5];
    p.dskip = (const __nv_bfloat16*)d_in[6];
    p.wr = (const __nv_bfloat16*)d_in[8];
    p.out = (__nv_bfloat16*)d_out;
    cudaGetSymbolAddress((void**)&p.sc, g_scratch);
    cudaGetSymbolAddress((void**)&p.tab, g_tab);

    void* fn = nullptr;
    cudaDriverEntryPointQueryResult qr;
    cudaGetDriverEntryPoint("cuTensorMapEncodeTiled", &fn, cudaEnableDefault, &qr);
    EncodeFn enc = (EncodeFn)fn;
    CUtensorMap tm_x, tm_g, tm_d, tm_o;
    const cuuint32_t es[5] = {1, 1, 1, 1, 1};
    {
        const cuuint64_t gd[5] = {1024, 4, 128, 2, 2}, gs[4] = {4096, 32768, 2048, 16384};
        const cuuint32_t bx[5] = {16, 4, 128, 2, 1};
        enc(&tm_x, CU_TENSOR_MAP_DATA_TYPE_BFLOAT16, 5, d_in[0], gd, gs, bx, es, CU_TENSOR_MAP_INTERLEAVE_NONE,
            CU_TENSOR_MAP_SWIZZLE_32B, (CUtensorMapL2promotion)XPROMO, CU_TENSOR_MAP_FLOAT_OOB_FILL_NONE);
        const cuuint32_t bo[5] = {16, 4, 16, 1, 1};
        enc(&tm_o, CU_TENSOR_MAP_DATA_TYPE_BFLOAT16, 5, d_out, gd, gs, bo, es, CU_TENSOR_MAP_INTERLEAVE_NONE,
            CU_TENSOR_MAP_SWIZZLE_32B, CU_TENSOR_MAP_L2_PROMOTION_NONE, CU_TENSOR_MAP_FLOAT_OOB_FILL_NONE);
    }
    {
        char *wg = (char*)d_in[9], *wu = (char*)d_in[10];
        p.up_first = wu < wg;
        p.w2 = (const __nv_bfloat16*)(p.up_first ? wg : wu);
        p.wd = (const __nv_bfloat16*)d_in[11];
        const cuuint64_t gd[3] = {3584, 1024, 2}, gs[2] = {7168, (cuuint64_t)(p.up_first ? wg - wu : wu - wg)};
        const cuuint32_t bx[3] = {64, 32, 2};
        enc(&tm_g, CU_TENSOR_MAP_DATA_TYPE_BFLOAT16, 3, p.up_first ? wu : wg, gd, gs, bx, es, CU_TENSOR_MAP_INTERLEAVE_NONE,
            CU_TENSOR_MAP_SWIZZLE_128B, CU_TENSOR_MAP_L2_PROMOTION_NONE, CU_TENSOR_MAP_FLOAT_OOB_FILL_NONE);
    }
    {
        const cuuint64_t gd[3] = {1024, 3584, 1}, gs[2] = {2048, 2048 * 3584};
        const cuuint32_t bx[3] = {64, 64, 1};
        enc(&tm_d, CU_TENSOR_MAP_DATA_TYPE_BFLOAT16, 3, d_in[11], gd, gs, bx, es, CU_TENSOR_MAP_INTERLEAVE_NONE,
            CU_TENSOR_MAP_SWIZZLE_128B, CU_TENSOR_MAP_L2_PROMOTION_NONE, CU_TENSOR_MAP_FLOAT_OOB_FILL_NONE);
    }
    cudaFuncSetAttribute(fused_kernel, cudaFuncAttributeMaxDynamicSharedMemorySize, SM_TOTAL + 256);
    fused_kernel<<<128, NTHREADS, SM_TOTAL + 256>>>(p, tm_x, tm_g, tm_d, tm_o);
}
```

```cpp
#include <cuda_runtime.h>
#include <cuda.h>
#include <cuda_bf16.h>
#include <cuda_fp16.h>
#include <stdint.h>

#define TG(i)
#define TS(i)
#define TSL(i)

#define TSW 0
#define XFIRST 8
#define XPROMO 0
#define SDELAY 2000
#define EDELAY 800
#define POLLAFTER 1
#define STAG2
#define FILL 0x6420
#define NSLOT 10
#define LDEPTH 8
#define DEPTH 4

namespace {

constexpr int NTHREADS = 512;
constexpr int SPIN_LIMIT = 1 << 16;

constexpr int SM_SLAB = 0;
constexpr int SM_RING = 65536;
constexpr int NS0     = 6;
constexpr int SUB     = 1088;
constexpr int SM_K    = SM_RING + NS0 * 8192;
constexpr int SM_S    = SM_K + 32 * SUB;
constexpr int SM_U    = SM_S + 32 * SUB;
constexpr int SM_F2   = SM_U + 32 * SUB;
constexpr int SM_XSEL = SM_F2 + 1536;
constexpr int SM_PAIR = SM_XSEL + 4096;
constexpr int SM_H    = SM_PAIR + 2048;
constexpr int SM_KEYS = SM_H + 1024;
constexpr int SM_TOK  = SM_KEYS + 64;
constexpr int SM_FIX  = SM_TOK + 16;
constexpr int SM_XRAW = SM_FIX + 32;
constexpr int SM_SCL  = SM_XRAW + 32;
constexpr int SM_PROBE = SM_SCL + 16;
constexpr int SM_BAR  = SM_PROBE + 64;
constexpr int SM_RED  = SM_XSEL;
constexpr int B_FULL = 0, B_EMPTY = 12, B_STG = 24, B_PROBE = 28, B_MISC = 32, B_ROW = 40, NBAR = 48;
constexpr int B_PEER = B_MISC  , B_TOK = B_MISC + 1, B_FIX = B_MISC + 2, B_PAIR = B_MISC + 3, B_SLAB = B_MISC + 4, B_F2 = B_MISC + 6;
constexpr int SM_TOTAL = SM_BAR + NBAR * 8;
static_assert(SM_TOTAL <= 232448 && NSLOT == 10 && LDEPTH <= NSLOT && DEPTH <= 4, "smem");
__host__ __device__ constexpr int full_bar(int n) { return B_FULL + (n == 23 ? NSLOT : n % NSLOT); }
constexpr int KP = 272;

struct Scratch {
    uint4 stats[1024];
    uint32_t part[128 * 56 * 16];
    uint32_t epoch;
};
__device__ Scratch g_scratch;

struct Params {
    const __nv_bfloat16 *lar, *aim, *cr, *ci, *logdt, *dskip;
    const __nv_bfloat16 *x, *wr;
    __nv_bfloat16* out;
    Scratch* sc;
    const uint4* tab;
    int up_first;
    const __nv_bfloat16 *w2, *wd;
};

__device__ __forceinline__ uint4 ldg128(const void* p) {
    uint4 v; asm volatile("ld.global.nc.v4.u32 {%0,%1,%2,%3}, [%4];" : "=r"(v.x), "=r"(v.y), "=r"(v.z), "=r"(v.w) : "l"(p)); return v;
}
__device__ __forceinline__ uint4 ld_relaxed128(const void* p) {
    uint4 v;
    asm volatile("{ .reg .b128 t; ld.relaxed.gpu.global.b128 t, [%4]; mov.b128 {%0,%1,%2,%3}, t; }"
                 : "=r"(v.x), "=r"(v.y), "=r"(v.z), "=r"(v.w) : "l"(p) : "memory");
    return v;
}
__device__ __forceinline__ void st_relaxed128(void* p, uint4 v) {
    asm volatile("{ .reg .b128 t; mov.b128 t, {%1,%2,%3,%4}; st.relaxed.gpu.global.b128 [%0], t; }"
                 :: "l"(p), "r"(v.x), "r"(v.y), "r"(v.z), "r"(v.w) : "memory");
}
__device__ __forceinline__ void st_relaxed32(void* p, uint32_t v) {
    asm volatile("st.relaxed.gpu.global.u32 [%0], %1;" :: "l"(p), "r"(v) : "memory");
}
__device__ __forceinline__ uint32_t lds32(uint32_t a) { uint32_t v; asm volatile("ld.shared.u32 %0, [%1];" : "=r"(v) : "r"(a)); return v; }
__device__ __forceinline__ uint32_t lds16(uint32_t a) { uint32_t v; asm volatile("ld.shared.u16 %0, [%1];" : "=r"(v) : "r"(a)); return v; }
__device__ __forceinline__ uint2 lds64(uint32_t a) { uint2 v; asm volatile("ld.shared.v2.u32 {%0,%1}, [%2];" : "=r"(v.x), "=r"(v.y) : "r"(a)); return v; }
__device__ __forceinline__ uint4 lds128(uint32_t a) {
    uint4 v; asm volatile("ld.shared.v4.u32 {%0,%1,%2,%3}, [%4];" : "=r"(v.x), "=r"(v.y), "=r"(v.z), "=r"(v.w) : "r"(a)); return v;
}
__device__ __forceinline__ void sts16(uint32_t a, uint32_t v) { asm volatile("st.shared.u16 [%0], %1;" :: "r"(a), "h"((uint16_t)v) : "memory"); }
__device__ __forceinline__ void sts32(uint32_t a, uint32_t v) { asm volatile("st.shared.u32 [%0], %1;" :: "r"(a), "r"(v) : "memory"); }
__device__ __forceinline__ void sts64(uint32_t a, uint32_t x, uint32_t y) { asm volatile("st.shared.v2.u32 [%0], {%1,%2};" :: "r"(a), "r"(x), "r"(y) : "memory"); }
__device__ __forceinline__ void sts128(uint32_t a, uint32_t x, uint32_t y, uint32_t z, uint32_t w) {
    asm volatile("st.shared.v4.u32 [%0], {%1,%2,%3,%4};" :: "r"(a), "r"(x), "r"(y), "r"(z), "r"(w) : "memory");
}
__device__ __forceinline__ void ldsm4(uint32_t a, uint32_t& r0, uint32_t& r1, uint32_t& r2, uint32_t& r3) {
    asm volatile("ldmatrix.sync.aligned.m8n8.x4.shared.b16 {%0,%1,%2,%3}, [%4];" : "=r"(r0), "=r"(r1), "=r"(r2), "=r"(r3) : "r"(a));
}
__device__ __forceinline__ void mma_f16(float (&d)[4], uint32_t a0, uint32_t a1, uint32_t a2, uint32_t a3, uint32_t b0, uint32_t b1) {
    asm("mma.sync.aligned.m16n8k16.row.col.f32.f16.f16.f32 {%0,%1,%2,%3}, {%4,%5,%6,%7}, {%8,%9}, {%0,%1,%2,%3};"
        : "+f"(d[0]), "+f"(d[1]), "+f"(d[2]), "+f"(d[3]) : "r"(a0), "r"(a1), "r"(a2), "r"(a3), "r"(b0), "r"(b1));
}
__device__ __forceinline__ void mma_bf16(float (&d)[4], uint32_t a0, uint32_t a1, uint32_t a2, uint32_t a3, uint32_t b0, uint32_t b1) {
    asm("mma.sync.aligned.m16n8k16.row.col.f32.bf16.bf16.f32 {%0,%1,%2,%3}, {%4,%5,%6,%7}, {%8,%9}, {%0,%1,%2,%3};"
        : "+f"(d[0]), "+f"(d[1]), "+f"(d[2]), "+f"(d[3]) : "r"(a0), "r"(a1), "r"(a2), "r"(a3), "r"(b0), "r"(b1));
}
__device__ __forceinline__ uint32_t prmt(uint32_t a, uint32_t b, uint32_t s) { uint32_t d; asm("prmt.b32 %0, %1, %2, %3;" : "=r"(d) : "r"(a), "r"(b), "r"(s)); return d; }
__device__ __forceinline__ uint32_t pack_h(float lo, float hi) { uint32_t d; asm("cvt.rn.f16x2.f32 %0, %1, %2;" : "=r"(d) : "f"(hi), "f"(lo)); return d; }
__device__ __forceinline__ uint32_t pack_b(float lo, float hi) { uint32_t d; asm("cvt.rn.bf16x2.f32 %0, %1, %2;" : "=r"(d) : "f"(hi), "f"(lo)); return d; }
__device__ __forceinline__ float blo(uint32_t v) { return __uint_as_float(v << 16); }
__device__ __forceinline__ float bhi(uint32_t v) { return __uint_as_float(v & 0xFFFF0000u); }
__device__ __forceinline__ float rb(float v) { return blo(pack_b(v, v)); }
__device__ __forceinline__ uint32_t bsub2(uint32_t a, uint32_t b) { uint32_t d; asm("sub.rn.bf16x2 %0, %1, %2;" : "=r"(d) : "r"(a), "r"(b)); return d; }
__device__ __forceinline__ uint32_t bmul2(uint32_t a, uint32_t b) { uint32_t d; asm("mul.rn.bf16x2 %0, %1, %2;" : "=r"(d) : "r"(a), "r"(b)); return d; }
__device__ __forceinline__ uint32_t bfma2(uint32_t a, uint32_t b, uint32_t c) { uint32_t d; asm("fma.rn.bf16x2 %0, %1, %2, %3;" : "=r"(d) : "r"(a), "r"(b), "r"(c)); return d; }
__device__ __forceinline__ uint32_t dup_lo(uint32_t v) { uint32_t d; asm("{ .reg .b16 l, h; mov.b32 {l, h}, %1; mov.b32 %0, {l, l}; }" : "=r"(d) : "r"(v)); return d; }
__device__ __forceinline__ uint32_t dup_hi(uint32_t v) { uint32_t d; asm("{ .reg .b16 l, h; mov.b32 {l, h}, %1; mov.b32 %0, {h, h}; }" : "=r"(d) : "r"(v)); return d; }
__device__ __forceinline__ uint32_t norm2(uint32_t x, uint32_t m, uint32_t hi, uint32_t lo) {
    uint32_t a = bsub2(x, m);
    return bfma2(a, hi, bmul2(a, lo));
}
__device__ __forceinline__ float ex2(float v) { float d; asm("ex2.approx.ftz.f32 %0, %1;" : "=f"(d) : "f"(v)); return d; }
__device__ __forceinline__ float rcp(float v) { float d; asm("rcp.approx.ftz.f32 %0, %1;" : "=f"(d) : "f"(v)); return d; }
__device__ __forceinline__ float sigmoidf_(float v) { return rcp(1.0f + ex2(-1.4426950408889634f * v)); }
__device__ __forceinline__ float siluf_(float v) { return v * sigmoidf_(v); }

__device__ __forceinline__ void mbar_init(uint32_t a, int n) { asm volatile("mbarrier.init.shared::cta.b64 [%0], %1;" :: "r"(a), "r"(n) : "memory"); }
__device__ __forceinline__ void mbar_expect(uint32_t a, int tx) { asm volatile("mbarrier.arrive.expect_tx.shared::cta.b64 _, [%0], %1;" :: "r"(a), "r"(tx) : "memory"); }
__device__ __forceinline__ void mbar_arrive(uint32_t a) { asm volatile("mbarrier.arrive.shared::cta.b64 _, [%0];" :: "r"(a) : "memory"); }
__device__ __forceinline__ void mbar_wait(uint32_t a, int parity) {
    asm volatile("{ .reg .pred p;\n"
                 "W: mbarrier.try_wait.parity.shared::cta.b64 p, [%0], %1;\n"
                 "@!p bra.uni W; }" :: "r"(a), "r"(parity) : "memory");
}
__device__ __forceinline__ uint32_t mapa(uint32_t a, uint32_t rank) { uint32_t d; asm("mapa.shared::cluster.u32 %0, %1, %2;" : "=r"(d) : "r"(a), "r"(rank)); return d; }
__device__ __forceinline__ void st_async2(uint32_t a, uint32_t x, uint32_t y, uint32_t bar) {
    asm volatile("st.async.weak.shared::cluster.mbarrier::complete_tx::bytes.v2.b32 [%0], {%1,%2}, [%3];" :: "r"(a), "r"(x), "r"(y), "r"(bar) : "memory");
}
__device__ __forceinline__ void st_async4(uint32_t a, uint32_t x, uint32_t y, uint32_t z, uint32_t w, uint32_t bar) {
    asm volatile("st.async.weak.shared::cluster.mbarrier::complete_tx::bytes.v4.b32 [%0], {%1,%2,%3,%4}, [%5];"
                 :: "r"(a), "r"(x), "r"(y), "r"(z), "r"(w), "r"(bar) : "memory");
}
__device__ __forceinline__ void stsm4(uint32_t a, uint32_t r0, uint32_t r1, uint32_t r2, uint32_t r3) {
    asm volatile("stmatrix.sync.aligned.m8n8.x4.shared.b16 [%0], {%1,%2,%3,%4};" :: "r"(a), "r"(r0), "r"(r1), "r"(r2), "r"(r3) : "memory");
}
__device__ __forceinline__ void proxy_fence() { asm volatile("fence.proxy.async.shared::cta;" ::: "memory"); }
__device__ __forceinline__ void bar_sync(int id, int n) { asm volatile("bar.sync %0, %1;" :: "r"(id), "r"(n) : "memory"); }
__device__ __forceinline__ void bar_arrive(int id, int n) { asm volatile("bar.arrive %0, %1;" :: "r"(id), "r"(n) : "memory"); }
__device__ __forceinline__ void cluster_arrive() { asm volatile("barrier.cluster.arrive.relaxed.aligned;" ::: "memory"); }
__device__ __forceinline__ void cluster_wait() { asm volatile("barrier.cluster.wait.aligned;" ::: "memory"); }
__device__ __forceinline__ void tma3d(uint32_t dst, const CUtensorMap* tm, int c0, int c1, uint32_t bar, uint64_t pol) {
    asm volatile("cp.async.bulk.tensor.3d.shared::cluster.global.mbarrier::complete_tx::bytes.L2::cache_hint [%0], [%1, {%3, %4, %6}], [%2], %5;"
                 :: "r"(dst), "l"(tm), "r"(bar), "r"(c0), "r"(c1), "l"(pol), "r"(0) : "memory");
}
__device__ __forceinline__ bool elect() {
    uint32_t p; asm volatile("{ .reg .pred p; elect.sync _|p, 0xFFFFFFFF; selp.u32 %0, 1, 0, p; }" : "=r"(p)); return p;
}

struct cf { float r, i; };
__device__ __forceinline__ cf cmul(cf a, cf b) { return {a.r * b.r - a.i * b.i, a.r * b.i + a.i * b.r}; }
__device__ __forceinline__ cf csq(cf a) { return {a.r * a.r - a.i * a.i, (a.r + a.r) * a.i}; }
__device__ __forceinline__ cf cexp_(float a2, float b) { float m = ex2(a2); return {m * __cosf(b), m * __sinf(b)}; }
struct hc { uint32_t r, i; };
__device__ __forceinline__ hc pk(cf a, cf b) { return {pack_h(a.r, b.r), pack_h(a.i, b.i)}; }
__device__ __forceinline__ hc hmulc(hc a, hc b) {
    const __half2 ar = *reinterpret_cast<__half2*>(&a.r), ai = *reinterpret_cast<__half2*>(&a.i);
    const __half2 br = *reinterpret_cast<__half2*>(&b.r), bi = *reinterpret_cast<__half2*>(&b.i);
    const __half2 r = __hfma2(ar, br, __hneg2(__hmul2_rn(ai, bi))), i = __hfma2(ar, bi, __hmul2_rn(ai, br));
    return {*reinterpret_cast<const uint32_t*>(&r), *reinterpret_cast<const uint32_t*>(&i)};
}
__device__ __forceinline__ void sth(uint32_t a, hc v) { sts32(a, v.r); sts32(a + 128, v.i); }
__device__ __forceinline__ uint32_t cpy(uint32_t v, uint32_t z) { uint32_t d; asm("xor.b32 %0, %1, %2;" : "=r"(d) : "r"(v), "r"(z)); return d; }
__device__ __forceinline__ void sched_fence() { asm volatile("pmevent 0;" ::: "memory"); }
__device__ __forceinline__ float tanh_(float v) { float d; asm("tanh.approx.f32 %0, %1;" : "=f"(d) : "f"(v)); return d; }
__device__ __forceinline__ float silu2(float h) {
    return h * rcp(fmaf(ex2(-2.8853900817779268f * h), 0.5f, 0.5f));
}
__device__ __forceinline__ uint32_t hfma2_(uint32_t a, uint32_t b, uint32_t c) { uint32_t d; asm("fma.rn.f16x2 %0, %1, %2, %3;" : "=r"(d) : "r"(a), "r"(b), "r"(c)); return d; }
__device__ __forceinline__ uint32_t hfms2_(uint32_t a, uint32_t b, uint32_t c) {
    uint32_t d; asm("{ .reg .b32 t; neg.f16x2 t, %1; fma.rn.f16x2 %0, t, %2, %3; }" : "=r"(d) : "r"(a), "r"(b), "r"(c)); return d;
}

__device__ __forceinline__ uint64_t bdesc(uint32_t addr, uint32_t sbo) {
    return (uint64_t)((addr & 0x3FFFFu) >> 4) | ((uint64_t)(128 >> 4) << 16) | ((uint64_t)(sbo >> 4) << 32);
}
__device__ __forceinline__ void wg_h(uint32_t (&d)[16], const uint32_t* a, const uint32_t* b, uint64_t d0, uint64_t d1, uint64_t d2, uint64_t d3) {
    asm volatile(
        "wgmma.mma_async.sync.aligned.m64n64k16.f16.f16.f16 {%0,%1,%2,%3,%4,%5,%6,%7,%8,%9,%10,%11,%12,%13,%14,%15}, {%16,%17,%18,%19}, %32, 0, 1, 1, 1;\n"
        "wgmma.mma_async.sync.aligned.m64n64k16.f16.f16.f16 {%0,%1,%2,%3,%4,%5,%6,%7,%8,%9,%10,%11,%12,%13,%14,%15}, {%20,%21,%22,%23}, %33, 1, 1, 1, 1;\n"
        "wgmma.mma_async.sync.aligned.m64n64k16.f16.f16.f16 {%0,%1,%2,%3,%4,%5,%6,%7,%8,%9,%10,%11,%12,%13,%14,%15}, {%24,%25,%26,%27}, %34, 1, 1, 1, 1;\n"
        "wgmma.mma_async.sync.aligned.m64n64k16.f16.f16.f16 {%0,%1,%2,%3,%4,%5,%6,%7,%8,%9,%10,%11,%12,%13,%14,%15}, {%28,%29,%30,%31}, %35, 1, 1, 1, 1;\n"
        : "=r"(d[0]), "=r"(d[1]), "=r"(d[2]), "=r"(d[3]), "=r"(d[4]), "=r"(d[5]), "=r"(d[6]), "=r"(d[7]), "=r"(d[8]), "=r"(d[9]), "=r"(d[10]), "=r"(d[11]), "=r"(d[12]), "=r"(d[13]), "=r"(d[14]), "=r"(d[15])
        : "r"(a[0]), "r"(a[1]), "r"(a[2]), "r"(a[3]), "r"(a[4]), "r"(a[5]), "r"(a[6]), "r"(a[7]), "r"(b[0]), "r"(b[1]), "r"(b[2]), "r"(b[3]), "r"(b[4]), "r"(b[5]), "r"(b[6]), "r"(b[7]), "l"(d0), "l"(d1), "l"(d2), "l"(d3));
}
__device__ __forceinline__ void wg_f0(float (&d)[32], const uint32_t* a, const uint32_t* b, uint64_t d0, uint64_t d1, uint64_t d2, uint64_t d3) {
    asm volatile(
        "wgmma.mma_async.sync.aligned.m64n64k16.f32.f16.f16 {%0,%1,%2,%3,%4,%5,%6,%7,%8,%9,%10,%11,%12,%13,%14,%15,%16,%17,%18,%19,%20,%21,%22,%23,%24,%25,%26,%27,%28,%29,%30,%31}, {%32,%33,%34,%35}, %48, 0, 1, 1, 1;\n"
        "wgmma.mma_async.sync.aligned.m64n64k16.f32.f16.f16 {%0,%1,%2,%3,%4,%5,%6,%7,%8,%9,%10,%11,%12,%13,%14,%15,%16,%17,%18,%19,%20,%21,%22,%23,%24,%25,%26,%27,%28,%29,%30,%31}, {%36,%37,%38,%39}, %49, 1, 1, 1, 1;\n"
        "wgmma.mma_async.sync.aligned.m64n64k16.f32.f16.f16 {%0,%1,%2,%3,%4,%5,%6,%7,%8,%9,%10,%11,%12,%13,%14,%15,%16,%17,%18,%19,%20,%21,%22,%23,%24,%25,%26,%27,%28,%29,%30,%31}, {%40,%41,%42,%43}, %50, 1, 1, 1, 1;\n"
        "wgmma.mma_async.sync.aligned.m64n64k16.f32.f16.f16 {%0,%1,%2,%3,%4,%5,%6,%7,%8,%9,%10,%11,%12,%13,%14,%15,%16,%17,%18,%19,%20,%21,%22,%23,%24,%25,%26,%27,%28,%29,%30,%31}, {%44,%45,%46,%47}, %51, 1, 1, 1, 1;\n"
        : "=f"(d[0]), "=f"(d[1]), "=f"(d[2]), "=f"(d[3]), "=f"(d[4]), "=f"(d[5]), "=f"(d[6]), "=f"(d[7]), "=f"(d[8]), "=f"(d[9]), "=f"(d[10]), "=f"(d[11]), "=f"(d[12]), "=f"(d[13]), "=f"(d[14]), "=f"(d[15]), "=f"(d[16]), "=f"(d[17]), "=f"(d[18]), "=f"(d[19]), "=f"(d[20]), "=f"(d[21]), "=f"(d[22]), "=f"(d[23]), "=f"(d[24]), "=f"(d[25]), "=f"(d[26]), "=f"(d[27]), "=f"(d[28]), "=f"(d[29]), "=f"(d[30]), "=f"(d[31])
        : "r"(a[0]), "r"(a[1]), "r"(a[2]), "r"(a[3]), "r"(a[4]), "r"(a[5]), "r"(a[6]), "r"(a[7]), "r"(b[0]), "r"(b[1]), "r"(b[2]), "r"(b[3]), "r"(b[4]), "r"(b[5]), "r"(b[6]), "r"(b[7]), "l"(d0), "l"(d1), "l"(d2), "l"(d3));
}
__device__ __forceinline__ void wg_f1(float (&d)[32], const uint32_t* a, const uint32_t* b, uint64_t d0, uint64_t d1, uint64_t d2, uint64_t d3) {
    asm volatile(
        "wgmma.mma_async.sync.aligned.m64n64k16.f32.f16.f16 {%0,%1,%2,%3,%4,%5,%6,%7,%8,%9,%10,%11,%12,%13,%14,%15,%16,%17,%18,%19,%20,%21,%22,%23,%24,%25,%26,%27,%28,%29,%30,%31}, {%32,%33,%34,%35}, %48, 1, 1, 1, 1;\n"
        "wgmma.mma_async.sync.aligned.m64n64k16.f32.f16.f16 {%0,%1,%2,%3,%4,%5,%6,%7,%8,%9,%10,%11,%12,%13,%14,%15,%16,%17,%18,%19,%20,%21,%22,%23,%24,%25,%26,%27,%28,%29,%30,%31}, {%36,%37,%38,%39}, %49, 1, 1, 1, 1;\n"
        "wgmma.mma_async.sync.aligned.m64n64k16.f32.f16.f16 {%0,%1,%2,%3,%4,%5,%6,%7,%8,%9,%10,%11,%12,%13,%14,%15,%16,%17,%18,%19,%20,%21,%22,%23,%24,%25,%26,%27,%28,%29,%30,%31}, {%40,%41,%42,%43}, %50, 1, 1, 1, 1;\n"
        "wgmma.mma_async.sync.aligned.m64n64k16.f32.f16.f16 {%0,%1,%2,%3,%4,%5,%6,%7,%8,%9,%10,%11,%12,%13,%14,%15,%16,%17,%18,%19,%20,%21,%22,%23,%24,%25,%26,%27,%28,%29,%30,%31}, {%44,%45,%46,%47}, %51, 1, 1, 1, 1;\n"
        : "+f"(d[0]), "+f"(d[1]), "+f"(d[2]), "+f"(d[3]), "+f"(d[4]), "+f"(d[5]), "+f"(d[6]), "+f"(d[7]), "+f"(d[8]), "+f"(d[9]), "+f"(d[10]), "+f"(d[11]), "+f"(d[12]), "+f"(d[13]), "+f"(d[14]), "+f"(d[15]), "+f"(d[16]), "+f"(d[17]), "+f"(d[18]), "+f"(d[19]), "+f"(d[20]), "+f"(d[21]), "+f"(d[22]), "+f"(d[23]), "+f"(d[24]), "+f"(d[25]), "+f"(d[26]), "+f"(d[27]), "+f"(d[28]), "+f"(d[29]), "+f"(d[30]), "+f"(d[31])
        : "r"(a[0]), "r"(a[1]), "r"(a[2]), "r"(a[3]), "r"(a[4]), "r"(a[5]), "r"(a[6]), "r"(a[7]), "r"(b[0]), "r"(b[1]), "r"(b[2]), "r"(b[3]), "r"(b[4]), "r"(b[5]), "r"(b[6]), "r"(b[7]), "l"(d0), "l"(d1), "l"(d2), "l"(d3));
}
__device__ __forceinline__ void wg_s(uint32_t* d, const uint32_t* a, const uint32_t* b, uint64_t d0, uint64_t d1) {
    asm volatile(
        "wgmma.mma_async.sync.aligned.m64n32k16.f16.f16.f16 {%0,%1,%2,%3,%4,%5,%6,%7}, {%8,%9,%10,%11}, %16, 0, 1, 1, 1;\n"
        "wgmma.mma_async.sync.aligned.m64n32k16.f16.f16.f16 {%0,%1,%2,%3,%4,%5,%6,%7}, {%12,%13,%14,%15}, %17, 1, 1, 1, 1;\n"
        : "=r"(d[0]), "=r"(d[1]), "=r"(d[2]), "=r"(d[3]), "=r"(d[4]), "=r"(d[5]), "=r"(d[6]), "=r"(d[7])
        : "r"(a[0]), "r"(a[1]), "r"(a[2]), "r"(a[3]), "r"(b[0]), "r"(b[1]), "r"(b[2]), "r"(b[3]), "l"(d0), "l"(d1));
}
template <int ACC> __device__ __forceinline__ void wg_w(float (&d)[4], uint64_t da, uint64_t db) {
    asm volatile("wgmma.mma_async.sync.aligned.m64n8k16.f32.bf16.bf16 {%0,%1,%2,%3}, %4, %5, %6, 1, 1, 1, 0;"
                 : "+f"(d[0]), "+f"(d[1]), "+f"(d[2]), "+f"(d[3]) : "l"(da), "l"(db), "n"(ACC));
}
__device__ __forceinline__ void wg_w0(float (&d)[4], uint64_t da, uint64_t db) {
    asm volatile("wgmma.mma_async.sync.aligned.m64n8k16.f32.bf16.bf16 {%0,%1,%2,%3}, %4, %5, 0, 1, 1, 1, 0;"
                 : "=f"(d[0]), "=f"(d[1]), "=f"(d[2]), "=f"(d[3]) : "l"(da), "l"(db));
}
__device__ __forceinline__ void wg_fence() { asm volatile("wgmma.fence.sync.aligned;" ::: "memory"); }
__device__ __forceinline__ void wg_commit() { asm volatile("wgmma.commit_group.sync.aligned;" ::: "memory"); }
template <int N> __device__ __forceinline__ void wg_wait() { asm volatile("wgmma.wait_group.sync.aligned %0;" :: "n"(N) : "memory"); }
__device__ __forceinline__ void touch(uint32_t& r) { asm volatile("" : "+r"(r) :: "memory"); }
__device__ __forceinline__ void touch(float& r) { asm volatile("" : "+f"(r) :: "memory"); }
template <class T, int N> __device__ __forceinline__ void touch(T (&r)[N]) {
#pragma unroll
    for (int i = 0; i < N; i++) touch(r[i]);
}

__global__ void __cluster_dims__(2, 1, 1) __launch_bounds__(NTHREADS, 1)
fused_kernel(const Params p, const __grid_constant__ CUtensorMap tm_x, const __grid_constant__ CUtensorMap tm_g,
             const __grid_constant__ CUtensorMap tm_d, const __grid_constant__ CUtensorMap tm_o)
{
    extern __shared__ __align__(1024) uint8_t smem_raw[];
    const uint32_t sm = (uint32_t)__cvta_generic_to_shared(smem_raw);
    const uint32_t bars = sm + SM_BAR;
    const int tid = threadIdx.x, lane = tid & 31;
    const int warp = __shfl_sync(0xFFFFFFFFu, tid >> 5, 0);
    const int g = lane >> 2, q = lane & 3;
    const int c = blockIdx.x, rank = c & 1, G = c >> 1;

    if (lane == 0 && warp >= 8) {
        const int v = warp - 8;
        mbar_init(bars + (B_STG + v) * 8, 1);
        mbar_init(bars + (B_EMPTY + v) * 8, 4);
        mbar_init(bars + (B_FULL + v) * 8, 1);
        if (v >= 4) { mbar_init(bars + (B_FULL + 4 + v) * 8, 1); mbar_init(bars + (B_EMPTY + 4 + v) * 8, 4); }
        mbar_init(bars + (B_MISC + v) * 8, (v == 1 || v == 2) ? 2 : 1);
        if (v < 4) mbar_expect(bars + (B_STG + v) * 8, 4096);
        if (v >= 2 && v < 7) mbar_expect(bars + (B_MISC + v) * 8, v == 2 ? 32 : v == 3 ? 2048 : v < 6 ? 32768 : 1536);
        asm volatile("fence.mbarrier_init.release.cluster;" ::: "memory");
    }
    __syncwarp();
    cluster_arrive();

    if (warp < 8) {
        const int ch = c * 8 + warp;
        const uint2 lar4 = __ldg(reinterpret_cast<const uint2*>(p.lar + ch * 128) + lane);
        const uint2 aim4 = __ldg(reinterpret_cast<const uint2*>(p.aim + ch * 128) + lane);
        const uint2 cr4 = __ldg(reinterpret_cast<const uint2*>(p.cr + ch * 128) + lane);
        const uint2 ci4 = __ldg(reinterpret_cast<const uint2*>(p.ci + ch * 128) + lane);
        uint32_t ldt_raw, dsk_raw;
        asm volatile("ld.global.nc.u16 %0, [%1];" : "=r"(ldt_raw) : "l"(p.logdt + ch));
        asm volatile("ld.global.nc.u16 %0, [%1];" : "=r"(dsk_raw) : "l"(p.dskip + ch));
        const float logdt = blo(ldt_raw), dsk = blo(dsk_raw);
        asm volatile("setmaxnreg.inc.sync.aligned.u32 168;");
        const int wgi = warp >> 2, w = warp & 3;
        const uint32_t wb = sm + SM_K + (w < 2 ? 16 * w + 8 * wgi : 16 + 16 * wgi + 8 * w) * SUB;
        sth(wb + lane * 4, hc{0x3C003C00u, 0u});

        const float dt = rb(expf(logdt));
        float outscale, cs, dn;
        {
            uint32_t m0 = __vmaxu2(__vmaxu2(cr4.x & 0x7FFF7FFFu, cr4.y & 0x7FFF7FFFu), __vmaxu2(ci4.x & 0x7FFF7FFFu, ci4.y & 0x7FFF7FFFu));
            uint32_t m1 = max(m0 & 0xFFFFu, m0 >> 16);
            float cmax = blo(__reduce_max_sync(0xFFFFFFFFu, m1));
            const float sc = fminf(fmaxf(fmaxf(2.0f * dt * cmax, fabsf(dsk) * (1.0f / 1024.0f)), 1e-30f), 1e30f);
            outscale = __uint_as_float(__float_as_uint(sc) & 0x7F800000u);
            const float inv = __uint_as_float(0x7F000000u - __float_as_uint(outscale));
            cs = 2.0f * dt * inv;
            dn = dsk * inv;
        }
        if (warp == TSW) TSL(39);
        uint32_t fc[16], fs[16], ta[4], tb[4];
        {
            touch(cs);
            sched_fence();
            const uint4* tp = p.tab + (tid & 127);
#pragma unroll
            for (int i = 0; i < 10; i++) {
                const uint4 u = ldg128(tp + i * 128);
                uint32_t* t = i < 4 ? fc + 4 * i : i < 8 ? fs + 4 * (i - 4) : i == 8 ? ta : tb;
                t[0] = u.x; t[1] = u.y; t[2] = u.z; t[3] = u.w;
            }
        }
        float kacc[2][3][4];
#pragma unroll
        for (int i = 0; i < 2; i++)
#pragma unroll
            for (int j = 0; j < 3; j++) kacc[i][j][0] = kacc[i][j][1] = kacc[i][j][2] = kacc[i][j][3] = 0.f;
        if (lane == 0) kacc[0][0][0] = dn;
        {
            const uint32_t st = wb + lane * 4;
            const uint32_t zk = lds32(wb + 128);
            const uint32_t la = wb + ((lane & 8) ? 29 : (lane & 7)) * KP + (lane >> 4) * 128;
            const uint32_t lo = wb + ((lane >> 3) & 1) * 128 + (lane >> 4) * 16;
            const uint32_t lb = lo + (8 + (lane & 7)) * KP, lb2 = lo + (24 + min(lane & 7, 4)) * KP, lm = lo + 30 * KP;
#pragma unroll 1
            for (int s = 0; s < 2; s++) {
                const uint32_t wl = s ? lar4.y : lar4.x, wa = s ? aim4.y : aim4.x, wr_ = s ? cr4.y : cr4.x, wi = s ? ci4.y : ci4.x;
                const uint32_t ea = pack_b(ex2(blo(wl) * 1.4426950408889634f), ex2(bhi(wl) * 1.4426950408889634f));
                const float a2[2] = {-(blo(ea) * dt) * 1.4426950408889634f, -(bhi(ea) * dt) * 1.4426950408889634f};
                const float b[2] = {blo(wa) * dt, bhi(wa) * dt};
                {
                    cf z8[2], z16[2], z32[2], z64[2], z128[2];
#pragma unroll
                    for (int e = 0; e < 2; e++) {
                        z8[e] = cexp_(a2[e] * 8.f, b[e] * 8.f);
                        z16[e] = csq(z8[e]); z32[e] = csq(z16[e]); z64[e] = csq(z32[e]); z128[e] = csq(z64[e]);
                    }
                    const hc r1 = pk(z8[0], z8[1]), r2 = pk(z16[0], z16[1]), r3 = hmulc(r1, r2), r4 = pk(z32[0], z32[1]);
                    sth(st + 1 * KP, r1); sth(st + 2 * KP, r2); sth(st + 3 * KP, r3); sth(st + 4 * KP, r4);
                    sth(st + 5 * KP, hmulc(r1, r4)); sth(st + 6 * KP, hmulc(r2, r4)); sth(st + 7 * KP, hmulc(r3, r4));
                    sth(st + 29 * KP, pk(z64[0], z64[1])); sth(st + 30 * KP, pk(z128[0], z128[1]));
                }
                {
                    cf C[2], z2[2], z4[2], v2[2], v4[2], c1[2], d1[2];
#pragma unroll
                    for (int e = 0; e < 2; e++) {
                        C[e] = {(e ? bhi(wr_) : blo(wr_)) * cs, (e ? bhi(wi) : blo(wi)) * -cs};
                        const cf z = cexp_(a2[e], -b[e]);
                        const cf v = cexp_(a2[e] * 256.f, b[e] * -256.f);
                        z2[e] = csq(z); z4[e] = csq(z2[e]); v2[e] = csq(v); v4[e] = csq(v2[e]);
                        c1[e] = cmul(C[e], z); d1[e] = cmul(C[e], v);
                    }
                    const hc l0 = pk(C[0], C[1]), l1 = pk(c1[0], c1[1]), e1 = pk(d1[0], d1[1]);
                    const hc h = pk(z2[0], z2[1]), f = pk(z4[0], z4[1]), w = pk(v2[0], v2[1]), y = pk(v4[0], v4[1]);
                    const hc l2 = hmulc(l0, h), l3 = hmulc(l1, h), e2 = hmulc(l0, w), e3 = hmulc(e1, w), e4 = hmulc(l0, y), g2 = hmulc(e1, h);
                    sth(st + 8 * KP, l0); sth(st + 9 * KP, l1); sth(st + 10 * KP, l2); sth(st + 11 * KP, l3);
                    sth(st + 12 * KP, hmulc(l0, f)); sth(st + 13 * KP, hmulc(l1, f)); sth(st + 14 * KP, hmulc(l2, f)); sth(st + 15 * KP, hmulc(l3, f));
                    sth(st + 16 * KP, e1);
                    sth(st + 17 * KP, g2);
                    sth(st + 18 * KP, hmulc(e1, f));
                    sth(st + 19 * KP, hmulc(g2, f));
                    sth(st + 20 * KP, e2);
                    sth(st + 21 * KP, hmulc(e2, f));
                    sth(st + 22 * KP, e3);
                    sth(st + 23 * KP, hmulc(e3, f));
                    sth(st + 24 * KP, e4);
                    sth(st + 25 * KP, hmulc(e1, y));
                    sth(st + 26 * KP, hmulc(e2, y));
                    sth(st + 27 * KP, hmulc(e3, y));
                    sth(st + 28 * KP, hmulc(e4, y));
                }
                __syncwarp();
                if (warp == TSW) TSL(s ? 34 : 27);
#pragma unroll
                for (int kp = 0; kp < 4; kp++) {
                    uint32_t bb[3][4], m2[4];
                    ldsm4(lm + kp * 32, m2[0], m2[1], m2[2], m2[3]);
                    ldsm4(lb + kp * 32, bb[0][0], bb[0][1], bb[0][2], bb[0][3]);
                    ldsm4(lb + 8 * KP + kp * 32, bb[1][0], bb[1][1], bb[1][2], bb[1][3]);
                    ldsm4(lb2 + kp * 32, bb[2][0], bb[2][1], bb[2][2], bb[2][3]);
#pragma unroll
                    for (int k2 = 0; k2 < 2; k2++) {
                        hc v0, m1;
                        ldsm4(la + kp * 32 + k2 * 16, v0.r, m1.r, v0.i, m1.i);
                        const hc mm = {m2[2 * k2], m2[2 * k2 + 1]};
                        const hc v1 = hmulc(v0, m1), v2 = hmulc(v0, mm), v3 = hmulc(v1, mm);
                        v0.r = cpy(v0.r, zk); v0.i = cpy(v0.i, zk);
#pragma unroll
                        for (int nt = 0; nt < 3; nt++) {
                            mma_f16(kacc[0][nt], v0.r, v1.r, v0.i, v1.i, bb[nt][2 * k2], bb[nt][2 * k2 + 1]);
                            mma_f16(kacc[1][nt], v2.r, v3.r, v2.i, v3.i, bb[nt][2 * k2], bb[nt][2 * k2 + 1]);
                        }
                    }
                }
                __syncwarp();
                if (warp == TSW) TSL(s ? 40 : 33);
            }
        }
        TSL(1);
        bar_sync(10 + wgi, 128);
        {
            const uint32_t tb_ = sm + SM_S + (16 * wgi + w) * SUB;
            const uint32_t seg = sm + SM_K + (2 * warp + (lane & 1)) * SUB + (lane >> 1) * 16;
            uint32_t v0[4];
#pragma unroll
            for (int m = 0; m < 4; m++) {
                constexpr float S = 1.0f / 512.0f;
                const float (&k0)[4] = kacc[m >> 1][0], (&k1)[4] = kacc[m >> 1][1], (&k2)[4] = kacc[m >> 1][2];
                const int R = 8 * m + g, o = 2 * (m & 1);
                v0[m] = pack_h(k0[o] * S, k0[o + 1] * S);
                sts32(tb_ + (q < 2 ? 4 * R + 2 * q : 64 * q + 2 * R) * 2, pack_h(k1[o] * S, k1[o + 1] * S));
                const uint32_t v2 = pack_h(k2[o] * S, k2[o + 1] * S);
                if (q < 2 || (m == 0 && lane == 2)) sts16(tb_ + (256 + 64 * q + R) * 2, v2);
                if (q < 2) sts16(tb_ + (288 + 64 * q + R) * 2, v2 >> 16);
            }
            stsm4(seg, v0[0], v0[1], v0[2], v0[3]);
            if (lane == 0) sts16(sm + SM_SCL + warp * 2, __float_as_uint(32768.0f * outscale) >> 16);
            __syncwarp();
            const uint2 l1 = lds64(tb_ + lane * 8);
            const uint32_t l1n = lds16(tb_ + lane * 8 + 8);
            uint32_t l2[2], l2n[2], l3[4], l3n[4];
#pragma unroll
            for (int i = 0; i < 2; i++) { l2[i] = lds32(tb_ + 256 + i * 128 + lane * 4); l2n[i] = lds16(tb_ + 260 + i * 128 + lane * 4); }
#pragma unroll
            for (int i = 0; i < 4; i++) { l3[i] = lds16(tb_ + 512 + i * 64 + lane * 2); l3n[i] = lds16(tb_ + 514 + i * 64 + lane * 2); }
            sts128(seg + 256, prmt(l1.x, 0, 0x1010), prmt(l1.x, l1.y, 0x5432), prmt(l1.y, 0, 0x1010), prmt(l1.y, l1n, 0x5432));
#pragma unroll
            for (int i = 0; i < 2; i++) sts128(seg + 512 + i * 256, prmt(l2[i], 0, 0x1010), l2[i], prmt(l2[i], 0, 0x3232), prmt(l2n[i], 0, 0x1010));
            const uint32_t s3 = (lane & 1) ? 0x5454 : 0x5410;
#pragma unroll
            for (int i = 0; i < 4; i++) {
                const uint32_t vv = prmt(l3[i], 0, 0x1010);
                sts128(seg + 16 * SUB + i * 256, vv, vv, prmt(l3[i], l3n[i], s3), prmt(l3n[i], 0, 0x1010));
            }
        }
        proxy_fence();
        TSL(2);
        cluster_wait();
        mbar_wait(bars + B_F2 * 8, 0);
        bar_sync(10 + wgi, 128);
        const uint64_t dre = bdesc(sm + SM_F2 + 512, 256), dim = bdesc(sm + SM_F2, 256);
        uint32_t k0[32], k1[32];
#pragma unroll
        for (int b = 0; b < 2; b++) {
            const uint64_t d1 = bdesc(sm + SM_K + (16 * b + 8 * wgi) * SUB, SUB);
            uint32_t re[16], im[16];
            if (b == 0 && wgi == 1) bar_sync(5, 256);
            wg_fence();
            wg_h(re, fc, fc + 8, d1, d1 + 16, d1 + 32, d1 + 48);
            wg_h(im, fs, fs + 8, d1, d1 + 16, d1 + 32, d1 + 48);
            wg_commit();
            if (b == 0 && wgi == 0) bar_arrive(5, 256);
            wg_wait<0>();
            touch(re); touch(im);
            uint32_t (&kk)[32] = b ? k1 : k0;
#pragma unroll
            for (int hh = 0; hh < 2; hh++) {
#pragma unroll
                for (int i = 8 * hh; i < 8 * hh + 8; i++) {
                    re[i] = hfma2_(ta[i & 3], im[i], re[i]); im[i] = hfms2_(tb[i & 3], re[i], im[i]); re[i] = hfma2_(ta[i & 3], im[i], re[i]);
                }
                wg_fence();
                wg_s(kk + 16 * hh, re + 8 * hh, im + 8 * hh, dre, dim);
                wg_s(kk + 16 * hh + 8, re + 8 * hh + 4, im + 8 * hh + 4, dre, dim);
                wg_commit();
            }
            wg_wait<0>();
            touch(kk);
        }
        if (warp == TSW) TSL(35);
        bar_sync(10 + wgi, 128);
        if (lane == 0) {
            asm volatile("mbarrier.arrive.shared::cta.b64 _, [%0], 2;" :: "r"(bars + (B_EMPTY + NS0 + w) * 8) : "memory");
        }
        bar_sync(1 + wgi, 256);
        asm volatile("setmaxnreg.inc.sync.aligned.u32 208;");
        TSL(3);
        touch(k1);
        {
            const uint32_t sg = (g & 1) ? 0xBC00BC00u : 0x3C003C00u;
#pragma unroll
            for (int i = 0; i < 16; i++) {
                const int r = 8 * (i >> 2) + (i & 3);
                k1[r] = hfms2_(sg, k0[r + 4], k1[r]); k1[r + 4] = hfma2_(sg, k0[r], k1[r + 4]);
            }
            touch(k1);
        }
        const uint32_t rowo = (16 * w + (lane & 15)) * 16;
        const uint32_t xo = sm + SM_SLAB + (16 * w + g) * 128 + q * 32 + ((rank ^ (g & 1)) * 16) + wgi * 8;
        const uint32_t peer = mapa(sm, rank ^ 1), so = SM_U + 8 * wgi * SUB + w * 1024 + lane * 16;
#pragma unroll
        for (int b = 0; b < 2; b++) {
            uint32_t gt[4][4];
            uint32_t h[4][4];
            auto load_h = [&](int cc) {
                ldsm4(sm + SM_U + (16 * b + 8 * wgi + 4 * (cc >> 1) + 2 * (lane >> 4) + (cc & 1)) * SUB + rowo, h[cc][0], h[cc][1], h[cc][2], h[cc][3]);
            };
            auto gates = [&](int cc) {
#pragma unroll
                for (int i = 0; i < 2; i++) {
                    const float2 f0 = __half22float2(*reinterpret_cast<const __half2*>(&h[cc][i]));
                    const float2 f1 = __half22float2(*reinterpret_cast<const __half2*>(&h[cc][2 + i]));
                    gt[2 * i][cc] = pack_b(silu2(f0.x), silu2(f1.x)); gt[2 * i + 1][cc] = pack_b(silu2(f0.y), silu2(f1.y));
                    touch(gt[2 * i][cc]); touch(gt[2 * i + 1][cc]);
                }
            };
            const uint32_t zb = sm + SM_S + 16 * wgi * SUB;
            constexpr int zi = 8 * SUB;
            uint32_t re[16], im[16], su[2][16], z[2][16], y[2][16];
            auto twiddle = [&](int hh) {
#pragma unroll
                for (int i = 8 * hh; i < 8 * hh + 8; i++) {
                    re[i] = hfma2_(ta[i & 3], im[i], re[i]); im[i] = hfms2_(tb[i & 3], re[i], im[i]); re[i] = hfma2_(ta[i & 3], im[i], re[i]);
                    touch(re[i]); touch(im[i]);
                }
            };
            auto dft16 = [&](int hh) {
                wg_fence();
                wg_s(su[hh], re + 8 * hh, im + 8 * hh, dre, dim); wg_s(su[hh] + 8, re + 8 * hh + 4, im + 8 * hh + 4, dre, dim);
                wg_commit();
                sched_fence();
            };
            auto product = [&](int hh) {
#pragma unroll
                for (int i = 0; i < 8; i++) {
                    const int r = 8 * (i >> 2) + (i & 3), kr = 16 * hh + r;
                    const hc u = {su[hh][r], su[hh][r + 4]};
                    if (b == 0) {
                        const hc t = hmulc(u, hc{k0[kr], k0[kr + 4]}), pp = hmulc(u, hc{k1[kr], k1[kr + 4]});
                        z[hh][r] = t.r; z[hh][r + 4] = t.i; k1[kr] = pp.r; k1[kr + 4] = pp.i;
                        touch(k1[kr]); touch(k1[kr + 4]);
                    } else {
                        z[hh][r] = hfms2_(u.i, k0[kr + 4], hfma2_(u.r, k0[kr], k1[kr]));
                        z[hh][r + 4] = hfma2_(u.i, k0[kr], hfma2_(u.r, k0[kr + 4], k1[kr + 4]));
                    }
                }
                touch(z[hh]);
            };
            auto idft16 = [&](int hh) {
                wg_fence();
                wg_s(y[hh], z[hh] + 4, z[hh], dre, dim); wg_s(y[hh] + 8, z[hh] + 12, z[hh] + 8, dre, dim);
                wg_commit();
                sched_fence();
            };
            auto untwiddle = [&](int hh) {
#pragma unroll
                for (int i = 0; i < 2; i++) {
                    uint32_t* const yi = y[hh] + 8 * i, * const yr = yi + 4;
#pragma unroll
                    for (int n = 0; n < 4; n++) {
                        yr[n] = hfms2_(ta[n], yi[n], yr[n]); yi[n] = hfma2_(tb[n], yr[n], yi[n]); yr[n] = hfms2_(ta[n], yi[n], yr[n]);
                    }
                    const uint32_t a = zb + (4 * hh + 2 * i + (lane >> 4)) * SUB + rowo;
                    stsm4(a, yr[0], yr[1], yr[2], yr[3]);
                    stsm4(a + zi, yi[0], yi[1], yi[2], yi[3]);
                }
            };
            auto done = [&]() { sched_fence(); wg_wait<0>(); };
            auto flush = [&](int bb) {
                mbar_wait(bars + (B_STG + 2 * bb + wgi) * 8, 0);
                const uint4 r0 = lds128(sm + so + 16 * bb * SUB), r1 = lds128(sm + so + 16 * bb * SUB + 512);
                const uint32_t a = (xo ^ 16) + bb * 8192 + rank * 16384;
                sts64(a, r0.x, r0.y); sts64(a + 1024, r0.z, r0.w); sts64(a + 32768, r1.x, r1.y); sts64(a + 32768 + 1024, r1.z, r1.w);
                proxy_fence();
                const int id = bb ? (w ? 4 + w : 3) : 12 + w;
                if (wgi == 0) {
                    bar_arrive(id, 64);
                } else {
                    bar_sync(id, 64);
                    if (lane == 0) {
#pragma unroll
                        for (int j = 0; j < 2; j++)
                            asm volatile("cp.async.bulk.tensor.5d.global.shared::cta.bulk_group [%0, {%2, %3, %4, %5, %6}], [%1];"
                                         :: "l"(&tm_o), "r"(sm + SM_SLAB + j * 32768 + rank * 16384 + bb * 8192 + w * 2048),
                                            "r"(G * 16), "r"(0), "r"(64 * bb + 16 * w), "r"(rank), "r"(j) : "memory");
                        asm volatile("cp.async.bulk.commit_group;" ::: "memory");
                    }
                    __syncwarp();
                }
            };
            {
                const uint64_t d1 = bdesc(sm + SM_U + (16 * b + 8 * wgi) * SUB, SUB);
                load_h(0);
                if (b == 0 && wgi == 1) bar_sync(9, 256);
                wg_fence();
                wg_h(re, fc, fc + 8, d1, d1 + 16, d1 + 32, d1 + 48);
                wg_h(im, fs, fs + 8, d1, d1 + 16, d1 + 32, d1 + 48);
                wg_commit();
                if (b == 0 && wgi == 0) bar_arrive(9, 256);
                sched_fence();
                if (b) flush(0);
                gates(0);
                done();
                touch(re); touch(im);
            }
            twiddle(0); twiddle(1); load_h(1); dft16(0); dft16(1);
            load_h(2); wg_wait<1>(); touch(su[0]);
            product(0); gates(1); done(); touch(su[1]); idft16(0);
            load_h(3); product(1); gates(2); done(); touch(y[0]); idft16(1);
            if (b) bar_sync(10 + wgi, 128);
            untwiddle(0); gates(3); done(); touch(y[1]);
            untwiddle(1);
            proxy_fence();
            uint2 xv[2][4];
#pragma unroll
            for (int i = 0; i < 8; i++) xv[i >> 2][i & 3] = lds64(xo + b * 8192 + (i >> 2) * 32768 + (i & 1) * 16384 + ((i >> 1) & 1) * 1024);
            if (warp == TSW) TSL(36 + b);
            bar_sync(10 + wgi, 128);
            if (w == 0 && lane == 0) asm volatile("mbarrier.arrive.relaxed.cluster.shared::cluster.b64 _, [%0];" :: "r"(peer + SM_BAR + (B_PEER + 7 * wgi) * 8) : "memory");
            if (b == 0) TSL(4);
            float acc[32];
            const uint64_t d4 = bdesc(zb, SUB);
            wg_fence();
            wg_f0(acc, fc, fc + 8, d4, d4 + 16, d4 + 32, d4 + 48);
            wg_f1(acc, fs, fs + 8, d4 + zi / 16, d4 + zi / 16 + 16, d4 + zi / 16 + 32, d4 + zi / 16 + 48);
            wg_commit();
            if (b == 0) mbar_wait(bars + B_TOK * 8, 0);
            mbar_wait(bars + (B_PEER + 7 * wgi) * 8, b);
            const uint2 tk = lds64(sm + SM_TOK), sc = lds64(sm + SM_SCL + wgi * 8);
            wg_wait<0>();
            touch(acc);
            uint32_t s[2][4][2], o[2][4][2];
#pragma unroll
            for (int j = 0; j < 2; j++)
#pragma unroll
                for (int i = 0; i < 4; i++) {
                    s[j][i][0] = pack_b(acc[4 * j + i], acc[8 + 4 * j + i]); s[j][i][1] = pack_b(acc[16 + 4 * j + i], acc[24 + 4 * j + i]);
                    o[j][i][0] = bfma2(bmul2(s[j][i][0], gt[i][j]), sc.x, xv[j][i].x); o[j][i][1] = bfma2(bmul2(s[j][i][1], gt[i][2 + j]), sc.y, xv[j][i].y);
                }
            const uint32_t sb = SM_BAR + (B_STG + 2 * b + wgi) * 8;
#pragma unroll
            for (int e = 0; e < 2; e++)
                if (e == rank) {
#pragma unroll
                    for (int j = 0; j < 2; j++) {
                        st_async4(peer + so + 16 * b * SUB + j * 512, o[j][1 - e][0], o[j][1 - e][1], o[j][3 - e][0], o[j][3 - e][1], peer + sb);
                        sts64(xo + b * 8192 + e * 16384 + j * 32768, o[j][e][0], o[j][e][1]);
                        sts64(xo + b * 8192 + e * 16384 + j * 32768 + 1024, o[j][2 + e][0], o[j][2 + e][1]);
                    }
                }
            if (warp == TSW) TSL(5 + b);
#pragma unroll
            for (int k = 0; k < 2; k++) {
                const int t = k ? tk.y : tk.x;
                if ((t & ~0x89) == 1024 * b + 256 * w + 16 * g + 2 * q) {
                    uint32_t f[2];
#pragma unroll
                    for (int n = 0; n < 2; n++) {
                        const uint32_t a0 = (t & 1) ? s[0][1][n] : s[0][0][n], a1 = (t & 1) ? s[0][3][n] : s[0][2][n];
                        const uint32_t b0 = (t & 1) ? s[1][1][n] : s[1][0][n], b1 = (t & 1) ? s[1][3][n] : s[1][2][n];
                        f[n] = (t & 8) ? ((t & 128) ? b1 : b0) : ((t & 128) ? a1 : a0);
                    }
                    const uint32_t dst = mapa(sm, k);
                    st_async2(dst + SM_FIX + rank * 16 + wgi * 8, bmul2(f[0], sc.x), bmul2(f[1], sc.y), dst + SM_BAR + B_FIX * 8);
                }
            }
            __syncwarp();
            if (b) {
                flush(1);
                TSL(7);
                if (lane == 0 && wgi == 1) {
#pragma unroll
                    for (int bb = 0; bb < 2; bb++) {
                        if (bb == 0) asm volatile("cp.async.bulk.wait_group 1;" ::: "memory"); else asm volatile("cp.async.bulk.wait_group 0;" ::: "memory");
#pragma unroll
                        for (int k = 0; k < 2; k++)
                            if (((k ? tk.y : tk.x) & 0x701) == 1024 * bb + 256 * w + rank)
                                asm volatile("mbarrier.arrive.release.cluster.shared::cluster.b64 _, [%0];" :: "r"(mapa(bars + B_FIX * 8, k)) : "memory");
                    }
                }
            }
        }
        TSL(17); TG(30);
    } else if (warp < 12) {
        const int v = warp - 8;
        const uint32_t xs = sm + SM_U + v * 8192;
        if (elect()) {
#pragma unroll
            for (int r = 0; r < 2; r++) mbar_init(bars + (B_ROW + 2 * v + r) * 8, 1);
            asm volatile("fence.mbarrier_init.release.cluster;" ::: "memory");
#pragma unroll
            for (int e = 0; e < 2; e++) {
                if (e) { const int t0_ = clock(); while ((int)clock() - t0_ < EDELAY) __nanosleep(40); }
                mbar_expect(bars + (B_ROW + 2 * v + e) * 8, 4096);
#pragma unroll
                for (int r = 0; r < 2; r++)
                    asm volatile("cp.async.bulk.shared::cluster.global.mbarrier::complete_tx::bytes [%0], [%1], 2048, [%2];"
                                 :: "r"(xs + e * 4096 + r * 2048), "l"(p.x + (size_t)(32 * (c & 63) + 16 * (v >> 1) + 8 * (c >> 6) + 4 * (v & 1) + 2 * r + e) * 1024),
                                    "r"(bars + (B_ROW + 2 * v + e) * 8) : "memory");
            }
        }
        __syncwarp();
        uint4 w4[4];
#pragma unroll
        for (int k = 0; k < 4; k++) w4[k] = ldg128(reinterpret_cast<const uint4*>(p.wr) + 32 * k + lane);
        uint32_t* const my_part = p.sc->part + ((2 * (32 * rank + v) + (q & 1)) * 56 + G) * 16 + g + 8 * (q >> 1);
        if (G < 56) {
#pragma unroll
            for (int n = 0; n < 8; n++) st_relaxed32(my_part + n * 8 * 56 * 16, 0);
        }
        {
            constexpr uint32_t ONE = 0x3F803F80u;
            const uint32_t zr = p.up_first >> 1;
            uint4 w5[4];
#pragma unroll
            for (int k = 0; k < 4; k++) {
                w5[k].x = w4[k].x + zr; w5[k].y = w4[k].y + zr; w5[k].z = w4[k].z + zr; w5[k].w = w4[k].w + zr;
                w4[k].x = cpy(w4[k].x, zr); w4[k].y = cpy(w4[k].y, zr); w4[k].z = cpy(w4[k].z, zr); w4[k].w = cpy(w4[k].w, zr);
            }
            const bool od = g & 1;
#pragma unroll 1
            for (int r2 = 0; r2 < 2; r2++) {
                mbar_wait(bars + (B_ROW + 2 * v + r2) * 8, 0);
                TSL(r2 ? 43 : 0);
                float s1[2][4] = {}, q0[2][4] = {};
#pragma unroll
                for (int k = 0; k < 4; k++)
#pragma unroll
                    for (int r = 0; r < 2; r++) {
                        const uint4 x = lds128(xs + r2 * 4096 + r * 2048 + k * 512 + lane * 16);
                        const uint4& ww = r ? w5[k] : w4[k];
                        mma_bf16(q0[r], cpy(x.x, zr), ww.x, cpy(x.y, zr), ww.y, x.x, x.y);
                        mma_bf16(s1[r], x.x, x.y, x.z, x.w, ONE, ONE);
                        mma_bf16(q0[r], cpy(x.z, zr), ww.z, cpy(x.w, zr), ww.w, x.z, x.w);
                    }
#pragma unroll
                for (int r = 0; r < 2; r++)
                    if (q == (g >> 1))
                        sts128(sm + SM_RED + (4 * v + r2 + 2 * r) * 144 + g * 16, __float_as_uint(od ? q0[r][1] : q0[r][0]),
                               __float_as_uint(od ? q0[r][3] : q0[r][2]), __float_as_uint(s1[r][0]), __float_as_uint(s1[r][2]));
            }
            bar_arrive(7, 160);
        }
        TSL(8);
        bar_sync(6, 192);
        const uint32_t tag = lds32(sm + SM_TOK + 8);
        cluster_wait();
        {
            uint4 st[8] = {};
            const uint4* src = p.sc->stats + 64 * v + lane;
            const uint32_t tb = ((tag & 1) << 15) | ((tag >> 1) << 31);
#pragma unroll
            for (int i = 0; i < 8; i++) st[i].y = ~tb;
            int it = 0;
            bool ok;
            mbar_wait(bars + (B_SLAB + POLLAFTER) * 8, 0);
            if (warp == 8) TSL(44);
            do {
                uint32_t bad = 0;
#pragma unroll
                for (int i = 0; i < 8; i++)
                    asm volatile("{ .reg .pred p; .reg .b128 t; setp.ne.u32 p, %5, 0; mov.b128 t, {%0,%1,%2,%3};\n"
                                 "@p ld.relaxed.gpu.global.b128 t, [%4]; mov.b128 {%0,%1,%2,%3}, t; }"
                                 : "+r"(st[i].x), "+r"(st[i].y), "+r"(st[i].z), "+r"(st[i].w)
                                 : "l"(src + (i >> 2) * 256 + ((i >> 1) & 1) * 512 + (i & 1) * 32), "r"((st[i].y ^ tb) & 0x80008000u) : "memory");
#pragma unroll
                for (int i = 0; i < 8; i++) bad |= st[i].y ^ tb;
                ok = __all_sync(0xFFFFFFFFu, (bad & 0x80008000u) == 0);
                if (warp == 8 && it == 0) TSL(45);
            } while (!ok && ++it < SPIN_LIMIT);
            TSL(11); TG(31);
            uint32_t h1[8], h2[8];
#pragma unroll
            for (int i = 0; i < 8; i++) {
                const uint32_t o2 = st[i].w ^ (prmt(st[i].w, 0, 0xBB99) | 0x80008000u);
                const uint32_t id = 0xFFFF - (256 * v + 16 * g + 2 * q) - ((i >> 2) * 1024 + ((i >> 1) & 1) * 8 + (i & 1) * 128);
                const uint32_t k0 = prmt(o2, id, 0x1054), k1 = prmt(o2, id - 1, 0x3254);
                h1[i] = max(k0, k1); h2[i] = min(k0, k1);
            }
#pragma unroll
            for (int n = 4; n > 0; n >>= 1)
#pragma unroll
                for (int i = 0; i < n; i++) { h2[i] = __vimax3_u32(min(h1[i], h1[i + n]), h2[i], h2[i + n]); h1[i] = max(h1[i], h1[i + n]); }
            const uint32_t w1 = __reduce_max_sync(0xFFFFFFFFu, h1[0]);
            const uint32_t w2 = __reduce_max_sync(0xFFFFFFFFu, h1[0] == w1 ? h2[0] : h1[0]);
            if (lane == 0) sts64(sm + SM_KEYS + v * 8, w1, w2);
            bar_arrive(3, 192);
#pragma unroll
            for (int i = 0; i < 8; i++) { st[i].y = bmul2(st[i].y & 0x7FFF7FFFu, 0x3F003F00u); st[i].z = bmul2(st[i].z, 0x3F003F00u); }
            const uint32_t a = sm + SM_SLAB + (16 * v + g) * 128 + q * 32 + ((rank ^ (g & 1)) * 16);
            const uint32_t ua = sm + SM_U + (lane >> 4) * SUB + (16 * v + (lane & 15)) * 16;
#pragma unroll
            for (int b = 0; b < 2; b++) {
                uint32_t o[8][4];
                mbar_wait(bars + (B_SLAB + b) * 8, 0);
                TSL(b ? 38 : 10);
#pragma unroll
                for (int i = 0; i < 4; i++) {
                    const uint4 e = lds128(a + b * 8192 + (i >> 1) * 32768 + (i & 1) * 1024), d = lds128(a + b * 8192 + (i >> 1) * 32768 + (i & 1) * 1024 + 16384);
                    const uint4& t = st[4 * b + i];
                    const uint32_t xe[4] = {e.x, e.y, e.z, e.w}, xd[4] = {d.x, d.y, d.z, d.w};
#pragma unroll
                    for (int n = 0; n < 4; n++) {
                        const uint32_t ne = norm2(xe[n], dup_lo(t.x), dup_lo(t.y), dup_lo(t.z)), nd = norm2(xd[n], dup_hi(t.x), dup_hi(t.y), dup_hi(t.z));
                        o[2 * n][i] = pack_h(blo(ne), blo(nd)); o[2 * n + 1][i] = pack_h(bhi(ne), bhi(nd));
                    }
                }
#pragma unroll
                for (int cc = 0; cc < 8; cc++) stsm4(ua + (16 * b + 2 * cc) * SUB, o[cc][0], o[cc][1], o[cc][2], o[cc][3]);
            }
            proxy_fence();
            bar_arrive(1, 256); bar_arrive(2, 256);
        }
        TSL(12);
        {
            asm volatile("setmaxnreg.dec.sync.aligned.u32 48;");
            if (G < 56) {
                const uint64_t dw = (uint64_t)(((sm + SM_RING) & 0x3FFFFu) >> 4) | (1ull << 16) | (64ull << 32) | (1ull << 62);
                const uint64_t dx = (uint64_t)(((sm + SM_XSEL + rank * 2048) & 0x3FFFFu) >> 4) | (2ull << 16) | (8ull << 32);
                const uint64_t dh = (uint64_t)(((sm + SM_H) & 0x3FFFFu) >> 4) | (8ull << 16) | (8ull << 32);
                float ag[4] = {0, 0, 0, 0}, au[4] = {0, 0, 0, 0};
                touch(ag); touch(au);
                mbar_wait(bars + B_TOK * 8, 0);
                TSL(13);
                static_assert(NSLOT % 2 == 0, "chunks are consumed in pairs");
                int slot = 0, ph = 0;
#pragma unroll 1
                for (int n = 0; n < 16; n += 2) {
                    const uint64_t a = dw + slot * 512, b = dx + n * 8;
                    mbar_wait(bars + (B_FULL + slot) * 8, ph);
                    mbar_wait(bars + (B_FULL + slot + 1) * 8, ph);
                    wg_fence();
                    wg_w<1>(ag, a, b); wg_w<1>(au, a + 256, b); wg_w<1>(ag, a + 128, b + 4); wg_w<1>(au, a + 384, b + 4);
                    wg_w<1>(ag, a + 512, b + 8); wg_w<1>(au, a + 768, b + 8); wg_w<1>(ag, a + 640, b + 12); wg_w<1>(au, a + 896, b + 12);
                    wg_commit();
                    wg_wait<0>();
                    touch(ag); touch(au);
                    if (lane == 0) { mbar_arrive(bars + (B_EMPTY + slot) * 8); mbar_arrive(bars + (B_EMPTY + slot + 1) * 8); }
                    slot += 2;
                    if (slot == NSLOT) { slot = 0; ph ^= 1; }
                }
                TSL(14);
                if (q == 0) {
#pragma unroll
                    for (int r = 0; r < 2; r++) {
                        const uint32_t dst = mapa(sm, r), o = dst + SM_PAIR + rank * 1024 + v * 256 + g * 32;
                        st_async4(o, __float_as_uint(ag[0]), __float_as_uint(ag[1]), __float_as_uint(ag[2]), __float_as_uint(ag[3]), dst + SM_BAR + B_PAIR * 8);
                        st_async4(o + 16, __float_as_uint(au[0]), __float_as_uint(au[1]), __float_as_uint(au[2]), __float_as_uint(au[3]), dst + SM_BAR + B_PAIR * 8);
                    }
                }
                mbar_wait(bars + B_PAIR * 8, 0);
                {
                    const uint32_t o = sm + SM_PAIR + v * 256 + g * 32 + q * 4, og = o + (p.up_first ? 16 : 0), ou = o + (p.up_first ? 0 : 16);
                    const float gs = rb(__uint_as_float(lds32(og)) + __uint_as_float(lds32(og + 1024)));
                    const float us = rb(__uint_as_float(lds32(ou)) + __uint_as_float(lds32(ou + 1024)));
                    const float hv = rb(siluf_(gs)) * us;
                    const uint32_t hd = sm + SM_H + (2 * v + (q >> 1)) * 128 + (q & 1) * 32 + g * 2, hb = pack_b(hv, hv);
                    sts16(hd, hb); sts16(hd + 64, hb);
                }
                proxy_fence();
                bar_sync(4, 128);
                TSL(15);
#pragma unroll 1
                for (int n = 0; n < 8; n += 2) {
                    const uint64_t a = dw + slot * 512;
                    mbar_wait(bars + (B_FULL + slot) * 8, ph);
                    mbar_wait(bars + (n == 6 ? full_bar(23) : B_FULL + slot + 1) * 8, n == 6 ? 0 : ph);
                    float d[4], e[4];
                    wg_fence();
                    wg_w0(d, a, dh); wg_w0(e, a + 512, dh); wg_w<1>(d, a + 128, dh + 16); wg_w<1>(e, a + 640, dh + 16);
                    wg_w<1>(d, a + 256, dh + 32); wg_w<1>(e, a + 768, dh + 32); wg_w<1>(d, a + 384, dh + 48); wg_w<1>(e, a + 896, dh + 48);
                    wg_commit();
                    wg_wait<0>();
                    touch(d); touch(e);
                    st_relaxed32(my_part + n * 8 * 56 * 16, (__float_as_uint((q & 2) ? d[2] : d[0]) & ~3u) | tag);
                    st_relaxed32(my_part + (n + 1) * 8 * 56 * 16, (__float_as_uint((q & 2) ? e[2] : e[0]) & ~3u) | tag);
                    if (lane == 0) { mbar_arrive(bars + (B_EMPTY + slot) * 8); mbar_arrive(bars + (B_EMPTY + slot + 1) * 8); }
                    slot += 2;
                    if (slot == NSLOT) { slot = 0; ph ^= 1; }
                }
                TSL(16);
            }
        }
    } else {
        asm volatile("setmaxnreg.dec.sync.aligned.u32 48;");
        cluster_wait();
        if (warp == 12) {
            TSL(19);
            const bool lead = elect();
            asm volatile("prefetch.tensormap [%0];" :: "l"(&tm_x) : "memory");
            { const int t0_ = clock(); while ((int)clock() - t0_ < SDELAY) __nanosleep(40); }
            uint64_t pol; asm volatile("createpolicy.fractional.L2::evict_first.b64 %0, 1.0;" : "=l"(pol));
            if (lead) {
                sts32(sm + SM_TOK + 12, NS0);
                int n = 0;
#pragma unroll 1
                for (int i = 0; i < 4; i++) {
                    if (G < 56) {
#pragma unroll 1
                        for (; n < ((FILL >> (4 * i)) & 15); n++) {
                            mbar_expect(bars + (B_FULL + n) * 8, 8192);
                            tma3d(sm + SM_RING + n * 8192, &tm_g, G * 64, rank * 512 + n * 32, bars + (B_FULL + n) * 8, pol);
                        }
                    }
                    asm volatile("cp.async.bulk.tensor.5d.shared::cluster.global.mbarrier::complete_tx::bytes.multicast::cluster"
                                 " [%0], [%1, {%3, %4, %5, %6, %7}], [%2], %8;"
                                 :: "r"(sm + SM_SLAB + rank * 32768 + (i >> 1) * 16384 + (i & 1) * 8192), "l"(&tm_x), "r"(bars + (B_SLAB + (i & 1)) * 8),
                                    "r"(G * 16), "r"(0), "r"(64 * (i & 1)), "r"(i >> 1), "r"(rank), "h"((uint16_t)3) : "memory");
                }
            }
            __syncwarp();
            TSL(20);
            if (G < 56) {
                int ws = LDEPTH < NS0 ? NS0 - LDEPTH : 0, wp = 0, slot = NS0, ep = 0;
#pragma unroll 1
                for (int n = NS0; n < 24; n++) {
                    if (n >= LDEPTH) {
                        mbar_wait(bars + (B_FULL + ws) * 8, wp);
                        if (++ws == NSLOT) { ws = 0; wp ^= 1; }
                    }
                    mbar_wait(bars + (B_EMPTY + slot) * 8, ep);
                    if (lead) {
                        const uint32_t fb = bars + (n == 23 ? full_bar(23) : B_FULL + slot) * 8;
                        const bool gu = n < 16;
                        mbar_expect(fb, 8192);
                        tma3d(sm + SM_RING + slot * 8192, gu ? &tm_g : &tm_d, gu ? G * 64 : rank * 512 + (n - 16) * 64, gu ? rank * 512 + n * 32 : G * 64, fb, pol);
                        sts32(sm + SM_TOK + 12, n + 1);
                    }
                    if (++slot == NSLOT) slot = 0;
                    if (slot == NS0) ep ^= 1;
                }
                TSL(23);
            }
        } else if (warp == 13) {
            if (lane == 0) { asm volatile("prefetch.tensormap [%0];" :: "l"(&tm_d) : "memory"); asm volatile("prefetch.tensormap [%0];" :: "l"(&tm_o) : "memory"); }
            if (lane == 0) asm volatile("cp.async.bulk.shared::cluster.global.mbarrier::complete_tx::bytes [%0], [%1], 1536, [%2];"
                                        :: "r"(sm + SM_F2), "l"(p.tab + 1280), "r"(bars + B_F2 * 8) : "memory");
            if (G < 56) {
                const bool lead = elect();
                int n = NS0;
#pragma unroll 1
                for (; n < 24; n++) {
                    const int m = n - DEPTH;
                    if (m < NS0) asm volatile("{ .reg .pred p; mbarrier.try_wait.parity.shared::cta.b64 p, [%0], 0;\n"
                                                "@!p mbarrier.try_wait.parity.shared::cta.b64 p, [%0], 0; @!p pmevent 1; }" :: "r"(bars + (B_FULL + m) * 8) : "memory");
                    else mbar_wait(bars + (B_PROBE + ((m - NS0) & 3)) * 8, ((m - NS0) >> 2) & 1);
                    uint32_t issued;
                    asm volatile("ld.volatile.shared.u32 %0, [%1];" : "=r"(issued) : "r"(sm + SM_TOK + 12) : "memory");
                    if ((int)issued >= n && n > NS0) break;
                    if (lead) {
                        const bool gu = n < 16;
                        const int c0 = gu ? G * 64 : rank * 512 + (n - 16) * 64, c1 = gu ? rank * 512 + n * 32 : G * 64;
                        asm volatile("cp.async.bulk.prefetch.tensor.3d.L2.global [%0, {%1, %2, %3}];" :: "l"(gu ? &tm_g : &tm_d), "r"(c0), "r"(c1), "r"(0) : "memory");
                        const uint32_t pb = bars + (B_PROBE + ((n - NS0) & 3)) * 8;
                        mbar_expect(pb, 16);
                        asm volatile("cp.async.bulk.shared::cluster.global.mbarrier::complete_tx::bytes [%0], [%1], 16, [%2];"
                                     :: "r"(sm + SM_PROBE + ((n - NS0) & 3) * 16),
                                        "l"(gu ? p.w2 + (size_t)(c1 + 31) * 3584 + c0 : p.wd + (size_t)(c1 + 63) * 1024 + c0), "r"(pb) : "memory");
                    }
                }
#pragma unroll 1
                for (int m = max(n - DEPTH, NS0); m < n; m++) mbar_wait(bars + (B_PROBE + ((m - NS0) & 3)) * 8, ((m - NS0) >> 2) & 1);
                TSL(41);
            }
        } else {
            const int sw = warp - 14;
            uint32_t tag;
            if (sw == 0) {
                uint4* const my_stats = p.sc->stats + c * 8 + (lane >> 2);
                asm volatile("ld.relaxed.gpu.global.u32 %0, [%1];" : "=r"(tag) : "l"(&p.sc->epoch) : "memory");
                float ws = 0.f;
#pragma unroll
                for (int k = 0; k < 4; k++) {
                    const uint4 w = ldg128(reinterpret_cast<const uint4*>(p.wr) + 32 * k + lane);
                    ws += (blo(w.x) + bhi(w.x)) + (blo(w.y) + bhi(w.y)) + (blo(w.z) + bhi(w.z)) + (blo(w.w) + bhi(w.w));
                }
                if (q == 0) st_relaxed128(my_stats, make_uint4(0, 0, 0, 0));
                tag = tag % 3 + 1;
                sts32(sm + SM_TOK + 8, tag);
                bar_arrive(6, 192);
#pragma unroll
                for (int o = 1; o < 32; o <<= 1) ws += __shfl_xor_sync(0xFFFFFFFFu, ws, o);
                const uint32_t tb = ((tag & 1) << 15) | ((tag >> 1) << 31);
                const uint32_t ra = sm + SM_RED + (lane >> 1) * 144 + (lane & 1) * 64;
                touch(ws);
                bar_sync(7, 160);
                const uint4 a0 = lds128(ra), a1 = lds128(ra + 16), a2 = lds128(ra + 32), a3 = lds128(ra + 48);
#define F(v) __uint_as_float(v)
                float ss = (F(a0.x) + F(a1.x)) + (F(a2.x) + F(a3.x)), dw = (F(a0.y) + F(a1.y)) + (F(a2.y) + F(a3.y));
                float sx = ((F(a0.z) + F(a1.z)) + (F(a2.z) + F(a3.z))) + ((F(a0.w) + F(a1.w)) + (F(a2.w) + F(a3.w)));
#undef F
                ss += __shfl_xor_sync(0xFFFFFFFFu, ss, 1); dw += __shfl_xor_sync(0xFFFFFFFFu, dw, 1); sx += __shfl_xor_sync(0xFFFFFFFFu, sx, 1);
                const float mean = sx * (1.0f / 1024.0f);
                const float var = fmaxf(ss * (1.0f / 1024.0f) - mean * mean, 0.f);
                const float m = rb(mean);
                float sd; asm("sqrt.approx.ftz.f32 %0, %1;" : "=f"(sd) : "f"(rb(rb(var) + 1e-5f)));
                const float rs = rcp(rb(sd));
                const float hi = rb(rs);
                const uint32_t p0 = pack_b(m, hi), p1 = pack_b(rs - hi, rs * (dw - m * ws));
                const uint32_t o0 = __shfl_xor_sync(0xFFFFFFFFu, p0, 2), o1 = __shfl_xor_sync(0xFFFFFFFFu, p1, 2);
                if (q == 0) st_relaxed128(my_stats, make_uint4(prmt(p0, o0, 0x5410), (prmt(p0, o0, 0x7632) & 0x7FFF7FFFu) | tb,
                                                               prmt(p1, o1, 0x5410), prmt(p1, o1, 0x7632)));
                TSL(9);
            } else {
                bar_sync(6, 192);
                tag = lds32(sm + SM_TOK + 8);
            }
            bar_sync(3, 192);
            const uint32_t kk = lane < 8 ? lds32(sm + SM_KEYS + lane * 4) : 0u;
            const uint32_t m1 = __reduce_max_sync(0xFFFFFFFFu, kk);
            const uint32_t m2 = __reduce_max_sync(0xFFFFFFFFu, kk == m1 ? 0u : kk);
            const uint32_t key = sw ? m2 : m1;
            const int t = (0xFFFF - (key & 0xFFFF)) & 2047;
            {
                const uint4* row = reinterpret_cast<const uint4*>(p.x + (size_t)t * 1024) + lane;
                uint4 xr[4];
#pragma unroll
                for (int i = 0; i < 4; i++) xr[i] = ldg128(row + 32 * i);
                const uint4 stk = ld_relaxed128(p.sc->stats + (((t >> 3) & 1) * 128 + (t >> 4)) * 4 + ((t >> 1) & 3));
                if (lane == 0) {
                    sts32(sm + SM_TOK + 4 * sw, t);
                    if (c == 0 && sw == 0) st_relaxed32(&p.sc->epoch, tag);
                }
                const uint32_t se = (t & 1) ? 0x3232 : 0x1010;
                const uint32_t m = prmt(stk.x, 0, se), hi = prmt(stk.y, 0, se) & 0x7FFF7FFFu, lo = prmt(stk.z, 0, se);
                const uint32_t a = sm + SM_XSEL + lane * 32 + sw * 16;
#pragma unroll
                for (int i = 0; i < 4; i++) {
                    sts128(a + i * 1024, norm2(xr[i].x, m, hi, lo), norm2(xr[i].y, m, hi, lo), norm2(xr[i].z, m, hi, lo), norm2(xr[i].w, m, hi, lo));
                    if (sw == rank && 16 * i + (lane >> 1) == G) sts128(sm + SM_XRAW + (lane & 1) * 16, xr[i].x, xr[i].y, xr[i].z, xr[i].w);
                }
                proxy_fence();
                __syncwarp();
                if (lane == 0) mbar_arrive(bars + B_TOK * 8);
                TSL(42);
            }
            if (sw == rank) {
                const int col = 4 * q + 2 * (lane >> 4) + ((lane >> 3) & 1), d = G * 16 + col;
                const float r = __uint_as_float((key & 0x80000000u) ? (key & 0x7FFF0000u) : (~key & 0xFFFF0000u));
                const float sg = rb(sigmoidf_(r));
                const float xn = blo(lds16(sm + SM_XSEL + (d >> 3) * 32 + rank * 16 + (d & 7) * 2));
                const float xv = blo(lds16(sm + SM_XRAW + col * 2));
                mbar_wait(bars + (G < 56 ? full_bar(23) : B_STG + 2) * 8, 0);
                TSL(24);
                const uint4* src = reinterpret_cast<const uint4*>(p.sc->part) + c * 224 + lane;
                float s0 = 0, s1 = 0, s2 = 0, s3 = 0;
                {
                    uint4 pv[7];
                    int it = 0;
                    bool ok;
                    do {
                        uint32_t bad = 0;
#pragma unroll
                        for (int i = 0; i < 7; i++) pv[i] = ld_relaxed128(src + 32 * i);
#pragma unroll
                        for (int i = 0; i < 7; i++) bad |= (pv[i].x ^ tag) | (pv[i].y ^ tag) | (pv[i].z ^ tag) | (pv[i].w ^ tag);
                        ok = __all_sync(0xFFFFFFFFu, (bad & 3) == 0);
                    } while (!ok && ++it < SPIN_LIMIT);
#pragma unroll
                    for (int i = 0; i < 7; i++) {
                        s0 += __uint_as_float(pv[i].x); s1 += __uint_as_float(pv[i].y); s2 += __uint_as_float(pv[i].z); s3 += __uint_as_float(pv[i].w);
                    }
                }
                TSL(25);
                const bool u16 = lane & 16, u8 = lane & 8;
                const float y0 = (u16 ? s2 : s0) + __shfl_xor_sync(0xFFFFFFFFu, u16 ? s0 : s2, 16);
                const float y1 = (u16 ? s3 : s1) + __shfl_xor_sync(0xFFFFFFFFu, u16 ? s1 : s3, 16);
                float y = (u8 ? y1 : y0) + __shfl_xor_sync(0xFFFFFFFFu, u8 ? y0 : y1, 8);
                y += __shfl_xor_sync(0xFFFFFFFFu, y, 4);
                const float z = rb(xn + rb(rb(y) * sg));
                const float gt = rb(siluf_(z));
                mbar_wait(bars + B_FIX * 8, 0);
                const float o = xv + rb(blo(lds16(sm + SM_FIX + col * 2)) * gt);
                if (!(lane & 4)) p.out[(size_t)t * 1024 + d] = __float2bfloat16(o);
                TSL(26); TG(29);
            }
        }
    }
}

__device__ __align__(128) const uint32_t g_tab[5504] = {
0x2fff3000,0x2e7c2fd4,0x2fc92fd4,0xad72af5a,0x2ff82ffc,0x230e2c07,0x2faf2fbc,0x217ea934,0x2fed2ff4,0xad4da8d5,0x2f912fa0,0x2e5e2bb7,
0x2fdd2fe6,0xb000af46,0x2f6e2f80,0x2fdd2fc9,0x2ff42fff,0x2e1f2fc9,0x2e1f2e7c,0xa875ad72,0x2fbc2fdd,0x9fd92a4e,0x2d4d2dba,0x2cd825db,
0x2f5a2f91,0xaeb5ac07,0x2c5d2cd8,0x30002f30,0x2ed02f1a,0xaf80aff4,0x2aaa2bb7,0x2cb02f1a,0x2fdd2ffc,0x2dba2fbc,0x2a4e2c07,0x25dba934,
0x2f462fa0,0xa7652875,0x25152875,0x2f802d27,0x2e3f2ed0,0xafa0ad72,0xa17e1cb6,0x2e3f2fe6,0x2cd82d96,0xadfeafd4,0xa934a6a1,0xa44e29f1,
0x2fbc2ff8,0x2d4d2faf,0x9fd9230e,0x2cd8217e,0x2e992f46,0xaa4e2515,0xaa4ea765,0x2fd42f80,0x2cb02dba,0xafffae99,0xad72ac5d,0x27652dba,
0x28752b05,0xab5eaee9,0xaf1aae5e,0xae3fa934,0x2f912ff4,0x2cd82fa0,0xac07a8d5,0x2f302bb7,0x2dba2ed0,0xac5d1cb6,0xae99ad72,0x2dba2fe6,
0x29932c5d,0xafc9af6e,0xafe6af6e,0xaaaa25db,0xa17e244e,0xa30ead4d,0xafafaffc,0xaff8aee9,0x2f5a2fed,0x2c5d2f91,0xaeb5ad4d,0x30002e5e,
0x2cb02e3f,0xad72a17e,0xafffafa0,0x27652e3f,0x217e2993,0xaf02afe6,0xaf02afc9,0xaf1aaaaa,0xab05a5db,0x2814aa4e,0xac07adba,0xad4dafdd,
0x2f1a2fe6,0x2bb72f80,0xaff4af46,0x2f1a2fc9,0x2b052d96,0xae5ea6a1,0xaee9afd4,0xa93429f1,0xa5db244e,0xadbaaffc,0xaa4ead4d,0xafddaee9,
0xaddcabb7,0x2cb0a17e,0x2765a17e,0x1cb6ad00,0x2ed02fdd,0x2aaa2f6e,0xaf80b000,0x2cb02fdd,0x28752cd8,0xaf1aa934,0xab5eadfe,0xae3fa44e,
0xab05a17e,0xac07afaf,0x2814a30e,0xad4daff8,0xaf6eaddc,0x2eb52765,0x2eb52cb0,0x2dba1cb6,0x29932f5a,0xa7652e99,0x25152e99,0x2aaaad96,
0xafa0ab05,0xabb7afed,0xaff4acd8,0x28d52ffc,0xa814af02,0x2f912d27,0x9fd9ae1f,0xaee9ae3f,0x2fd42c32,0xaf5a1cb6,0x30002d72,0x2fd42515,
0x28752f46,0xa8d52e7c,0xa8d52c32,0x2e3fa993,0xafedac5d,0xa934b000,0xaf30af5a,0xa8142eb5,0x1648adfe,0x2e992e5e,0x2c87a814,0xa9f1affc,
0x2fe62e1f,0xafffa875,0x2ddc2ff4,0x2ed02e1f,0x26a12f30,0xa9f12e5e,0xad96244e,0x2fd41fd9,0xafffad27,0xa515aff4,0xac32aff4,0xaddc2b5e,
0x2875acb0,0x2d272f46,0x2fa02993,0x2875aed0,0x2ee92f6e,0xaf91ac87,0x1fd92e99,0x28143000,0x244e2f1a,0xab052e3f,0xaf91a875,0x2fbc2b5e,
0xafd4addc,0x1648afc9,0x1648ae7c,0xafdd9cb6,0x2c32aa4e,0x2aaa2fd4,0x2f802e99,0x2e7caa4e,0x2d002ffc,0xae1fae5e,0xad272814,0xabb72dfe,
0x1fd92f02,0xac072e1f,0xafedad27,0x2dfe2e3f,0xaf6eae7c,0x25dbaf80,0x2c5daaaa,0xaf6eac32,0x2ddca5db,0x25153000,0x2c323000,0x2fff26a1,
0x28d52fbc,0xabb7af91,0xaff4ab05,0xafa0244e,0x96482ee9,0xac872dfe,0xae99af30,0x29f12fbc,0xaed0af02,0x2993af1a,0x2f46217e,0xacb0af02,
0x2f1a1cb6,0xa30e2fc9,0xa30e2e7c,0x2e1f2ddc,0x9fd92eb5,0xa44eb000,0xae5eaf5a,0xaf30ac5d,0xa17e2ed0,0xad002ddc,0xabb7afff,0xa17e2fe6,
0xadfeaf6e,0x2c07ae99,0x2fed2c87,0x9fd9b000,0x2fd42814,0xa9f12f30,0xad962934,0x26a12fed,0xaaaa2d00,0x2765afa0,0xa515afa0,0xa993afaf,
0xa5152eb5,0xad722dba,0x9cb6af6e,0xac322eb5,0xad00afbc,0x2d27adfe,0x2e1f2f30,0x2bb7aee9,0x2ffc2b5e,0xacd82e3f,0xafeda875,0xab052f1a,
0xadba2993,0x2c87ae7c,0x2c87ac32,0x2a4eaf46,0xaddc2d96,0xafe62c5d,0xaed02c5d,0x2fffa9f1,0x2e1fad4d,0x2e3f2814,0x2f02ac07,0xad27ab05,
0xae5e2d00,0x9fd9af1a,0xaf302b5e,0xa44e2faf,0x2e99acb0,0xad962f80,0x2f5aaaaa,0x2e99aed0,0xae3f2d72,0xaff82c32,0xaff82515,0x2f021cb6,
0x2ee9ac87,0x2d4d29f1,0x2ffc9648,0xa44eae99,0xaf6e2b05,0x26a1afbc,0xafd4a44e,0xadba2f91,0x2fc9a8d5,0xaf462e3f,0x2f802875,0x2fe6a8d5,
0xae992d4d,0xb0002c07,0xaf6ea814,0x2c872b05,0x2f80ab5e,0x2c322bb7,0x2e7c2bb7,0x2aaaaff8,0xaff42765,0x2b5eafff,0xad27ad72,0xaff42cb0,
0x2fed1648,0xaffc2c5d,0x2b052eb5,0x2cd82a4e,0xaee92d27,0xaffc2bb7,0xad4dad00,0x244e2e1f,0x2fdda993,0x29f12cb0,0x29f12ed0,0x2eb5af46,
0xafe61648,0x2d72afdd,0x9cb6afd4,0xaed01648,0x2f022934,0xafa02814,0xa8d52fed,0xa30e2f30,0xaf302d00,0xafed2b5e,0xa814af1a,0xa9342faf,
0x3000a765,0x26a12d72,0xa5db2fff,0x3000acb0,0xaf46a6a1,0x2ed0af5a,0x2cb0af5a,0xa993ac87,0x2d272cd8,0xae3f9fd9,0xaf022d4d,0xae1f2fbc,
0xaf6e2cd8,0xafd42b05,0x26a1affc,0xadba2fed,0x2fe6a30e,0x1cb62e1f,0xad722f1a,0x2ed0a30e,0xae1faaaa,0x2fafae7c,0x2fafac32,0x28d5af80,
0x29342e99,0xac07a9f1,0xafbc1648,0xaffc2c87,0xafa02cb0,0xafaf2aaa,0x2d00af80,0xafa02ed0,0x2f911648,0xa44e2eb5,0xafbc2c5d,0x2b052a4e,
0xac87acd8,0x3000ad4d,0x2f6e1fd9,0x2e99afbc,0x9cb62faf,0xa515ad27,0xac32ad27,0xad72a30e,0xafc92c87,0xaf802a4e,0x2f46adba,0xafe62c87,
0x2f02244e,0xa8d52f30,0xafa01fd9,0xa30e2e5e,0xa934ae1f,0x2fbcabb7,0x2c072d00,0x2ffcad27,0xaa4e2fff,0x26a1aed0,0x26a1afe6,0x1648addc,
0xaf4629f1,0xac3225db,0xae7c25db,0x29931648,0xab5e2f91,0xafaf2e5e,0xad002fed,0x2f1aad4d,0x2ee9a875,0xaf302ff8,0x2dfea17e,0x2fbcaff4,
0x2c5dafc9,0xa9f12d72,0x2d96afff,0x2c5dae7c,0xaf022993,0xab5e2515,0xab5ea765,0xa30e2aaa,0xacd82fd4,0xaf302dba,0xaf912f6e,0x2c07a6a1,
0x2d969fd9,0xafdd2fed,0x25db2c07,0x2f5aadfe,0x2e7caff8,0xad722f02,0x2fffae3f,0x2fc9aff8,0xaeb52934,0xaa4e244e,0x9648acd8,0xac5d2dfe,
0xaddc2ff8,0xae7c2d00,0xafc92d00,0x9cb628d5,0x2bb72515,0xaff82f80,0xab5e2f46,0x2bb7a765,0x2fbcaf5a,0xaf302fdd,0x2dfea5db,0x2ee9ad96,
0xae5e28d5,0xa934230e,0x2b05af02,0xaee92fa0,0xaeb52fff,0xad962c32,0xad962515,0xac872ddc,0x276529f1,0xaf802eb5,0xaf462fdd,0xa51529f1,
0x2ff4adfe,0xaff82fed,0x217e2c07,0x28759fd9,0xadfe2875,0xa814217e,0x2e5eaff8,0xaffc2ff4,0xaf5a2fe6,0xac872aaa,0xa6a1a993,0xaf5a2fc9,
0x9cb62c87,0xae7c2d96,0xafc92d96,0xaddc2eb5,0x2f1aac07,0xafaf2f30,0xad002f91,0xab5e2cd8,0xad962814,0xa5db1fd9,0x2fddaf91,0xaf5a2ee9,
0xafc92faf,0xaaaa28d5,0x2993ae1f,0xafe62faf,0xa8d52ddc,0xad002c32,0xad002515,0xaff82fff,0x2d4da6a1,0xae5e2dba,0xafed2f6e,0xaf912fd4,
0xad272765,0xa30e1cb6,0x2fafaddc,0xad272cb0,0xaffc2f5a,0xa81425db,0x2e5eafdd,0xadfe2d96,0xac5d2ee9,0xaa4e2934,0x9648ab05,0xaeb52e5e,
0x2993230e,0xac322b5e,0xae7c2b5e,0xaf462f02,0xacb026a1,0x9cb61648,0x2ddcaa4e,0xa76526a1,0xaff42ee9,0xa17e1fd9,0x2ff8af91,0xa8752814,
0xadfe2fa0,0xa44e230e,0x2cd8af02,0xa93428d5,0x96482aaa,0xa5db2515,0xa5dba765,0xa9f12993,0x2f462f5a,0x2c322e99,0x2e7c2e99,0xa993ad96,
0x2f1a2f30,0xa875244e,0x2e3f2e5e,0x2b5e1fd9,0x2ee92f02,0xaf30ad27,0x2dfe2e1f,0x2fbc2e3f,0x2eb52ed0,0xaf6eafff,0x2dba2ddc,0x2eb52fe6,
0x28752993,0xa8d52515,0xa8d5a765,0x2e3f2aaa,0x244e26a1,0xaf91ad96,0xab05a9f1,0x2fbc2fd4,0x96481fd9,0xae99afed,0xac87ac07,0x29f12dfe,
0xa515a17e,0x9cb6abb7,0xad72ad00,0xac32a17e,0xac5dab05,0xaf5aacd8,0xb000afed,0x2eb52ffc,0xaddcad27,0xae7caff4,0xafc9aff4,0x9cb62b5e,
0xaf02ae7c,0x217eaaaa,0xaf1aaf80,0xaf02ac32,0xafbcaf6e,0x2f302c87,0xadfeae99,0xaee9b000,0xafedafa0,0xaf30aff4,0xa934abb7,0xa81428d5,
0xafd4afff,0x1648ac32,0x1648a515,0xafddaddc,0xaed0af6e,0x2f462c5d,0x299325db,0xacb0af6e,0xad00adfe,0x2e1f2fed,0x2d272c07,0x2bb79fd9,
0xadfeaf02,0xa814ae1f,0x2e5e2d27,0xaffcae3f,0xaa4eacb0,0x2e992993,0x2fd42f46,0xaa4eaed0,0x1cb6a5db,0x2e7c3000,0x2fc93000,0x2ddc26a1,
0x2b5e2814,0xa8752934,0x2e3f2f30,0x2f1a2fed,0x1648a814,0x2c879fd9,0x2e992f91,0xa9f1aee9,0x2c322875,0x2f802fa0,0x2aaa2d27,0x2e7c2875,
0x2f1a2ddc,0xa30e2c32,0xa30e2515,0x2e1f2fff,0x2ffc2fd4,0xafedad96,0xacd8a9f1,0xab0526a1,0x2e1f2c32,0x2ff42d72,0xa8751cb6,0x2e1f2515,
0x2ffc2f6e,0x28142e99,0xae5eac87,0x2dfe3000,0x2eb52fbc,0xaf5aab05,0xb000af91,0xac5d244e,0x29932d00,0xac32afa0,0xae7cafa0,0xaf46afaf,
0x2fe62fd4,0x2ddc3000,0xafffaf5a,0x2ed02fd4,0x2d002ee9,0xad271fd9,0xae1faf91,0xabb72814,0x9fd928d5,0xae5eaff4,0xa44eabb7,0xaf30afa0,
0xadbaaaaa,0x2c87a515,0x2c872765,0x2a4ea993,0x9cb62d96,0xacb02c5d,0xa7652c5d,0x2ddca9f1,0xaff8adfe,0xa30eafbc,0xafafaee9,0xa17e2f30,
0x244ead00,0x2dfe2f1a,0x2934ab5e,0xacd8afaf,0x2fdd2e7c,0xb000a993,0x2f6e2f46,0x2fdd2c32,0xae3f9cb6,0xaff8a765,0xaff8acb0,0x2f022ddc,
0xac07afdd,0x2dfeaa4e,0x1fd9adba,0xafeda5db,0x2f6e2934,0xa6a12ee9,0x2fd42e5e,0x2dbaab05,0x27652f1a,0xaaaaaff4,0xa9932bb7,0xa5152f1a,
0xafddadfe,0xadbaaee9,0xaa4eafbc,0xa5db2f30,0x2aaaab5e,0x2fc92bb7,0x2fe62bb7,0xa993aff8,0x2e3f2fc9,0xafa01cb6,0xa17e2ddc,0x2e3f2e7c,
0xae5e9648,0x2d4dac5d,0xaf91aeb5,0xafedaa4e,0xac07aff8,0x1fd9afaf,0x2dfea30e,0xafeda17e,0x2fdd2aaa,0x29f12fe6,0x29f12fc9,0x2eb5a993,
0xa5152dba,0xaddcae99,0xafffac5d,0xac322dba,0xaf02af30,0x2fa02c07,0x28d5acd8,0x230eaf91,0x2934ad00,0x2e5eab5e,0x2ee92f1a,0xab05afaf,
0x2dba2fc9,0xac5d2ddc,0xae991cb6,0x2dba2e7c,0xaf80a6a1,0x2765af5a,0xa515af5a,0xaf46ac87,0x217eae5e,0x230e2ffc,0x2faf2dfe,0x2ff82814,
0x2f6e244e,0x2fd42934,0xa6a12dfe,0x2dbaacd8,0xa5152e3f,0xafffa17e,0xaddcafa0,0xac322e3f,0xae1faf80,0x2fafa515,0x2faf2765,0x28d5af46,
0x2f9125db,0xaee92a4e,0xa8142dba,0x9fd92fdd,0x2f1a2e7c,0x2bb72f46,0xaff4a993,0x2f1a2c32,0xaf309648,0xacd8aeb5,0x2c07ac5d,0xaf91aa4e,
0x25dbae5e,0x2dba2dfe,0x2a4e2ffc,0x2fdd2814,0x2d722faf,0xae7cad27,0xafc9ad27,0xafffa30e,0x27652fdd,0xa9932f6e,0xaaaab000,0xa5152fdd,
0xaf02ae5e,0x28d5af91,0x2fa02d4d,0x230eafed,0x2f91217e,0xa8142faf,0xaee9230e,0x9fd92ff8,0xaa4e2d72,0x26a1afc9,0x26a1ae7c,0x1648afff,
0xaf8029f1,0xafc925db,0xafe625db,0x2f461648,0x2fa0a934,0x2bb72cd8,0x2ff4a44e,0xa8d5adfe,0xafbc2875,0x2934aff8,0xaffc217e,0xac072ff4,
0x2fd4a765,0xaf5a2ddc,0x30009cb6,0x2fd4acb0,0xaf02aaaa,0xab5eacb0,0xab5eaed0,0xa30e2f80,0x2e5e2c5d,0xab053000,0x29342f5a,0x2ee9aeb5,
0xad96ad4d,0x2fddacd8,0xa5dbafbc,0xaf5a1fd9,0x2cb02e1f,0xaddca875,0x1cb62ff4,0x27652e1f,0xa6a1af91,0x29f1afed,0x2d96ae5e,0xafd42d4d,
0x9cb62ff8,0xafe62d00,0xaed02d00,0x2d7228d5,0x2875afe6,0x2d272993,0x2fa0aaaa,0x2875afc9,0xac072f5a,0x2934afdd,0xaffc25db,0xafbc2d96,
0x2cd8af1a,0x2f91ae3f,0x2f302875,0xac07ab5e,0xaeb52d72,0xad96a765,0xad96acb0,0xac872fff,0x2fc9aa4e,0xa9932fd4,0x2aaa2e99,0x2fe6aa4e,
0xaff41fd9,0x2ff8acd8,0xa17eafbc,0xa875ad4d,0x2ffca875,0x2ee9a17e,0xa44e2ff8,0x2d4daff4,0xaf6ea515,0x25dbaf46,0x2c5daf80,0xaf6e2765,
0x2d722c87,0xafe62d96,0xaed02d96,0x9cb62eb5,0xa8d5aee9,0x2bb72b05,0x2ff4a934,0x2fa0ae5e,0x2d962c07,0x25db2d4d,0xafdd2b05,0x2f5aa814,
0xa765af02,0x2f46af1a,0x2f80217e,0x2515af02,0xa8d52fff,0xad00a765,0xad00acb0,0xaff82d72,0x2dfeaeb5,0xacd83000,0x244e2f5a,0x29342c5d,
0xa17e2fc9,0xad002fff,0xabb7ad72,0xa17e2e7c,0x2d4daf5a,0x2ee9a5db,0xa44e2fdd,0x2ffcad96,0xafd42c07,0x29f1af91,0x2d96af30,0xa6a1acd8,
0x2f46230e,0xafc92b5e,0xafe62b5e,0xaf802f02,0xae7c2eb5,0xafff2dba,0x2d72af6e,0xafc92eb5,0x2ff4a814,0x217e2d4d,0xaff82b05,0x28752c07,
0xad4dab5e,0x2fedae3f,0x2e5e2875,0x2f91af1a,0x96482f80,0xa5dbacb0,0xa5dbaed0,0xa9f1aaaa,0xad729648,0xa515a6a1,0xac32a6a1,0x9cb62a4e,
0xae1f2ffc,0xae3f2c07,0xaf022fbc,0x2d27a934,0x2cd8230e,0xaffc2fa0,0x2b0528d5,0x2fedaf02,0x2e99afe6,0xad962f46,0x2f5aaf80,0x2e99afc9,
0x230eaddc,0x2d27aed0,0x2d27afe6,0xafaf2fff,0xafbc2c87,0x1fd9a9f1,0xad4d1648,0xacd82e99,0xaa4e2f30,0xac5d2814,0xaeb52fed,0x96482934,
0x2ed0a8d5,0xaf802e3f,0x2aaa2875,0x2cb0a8d5,0x2e99affc,0x3000afbc,0x2f6eac07,0xac872934,0xa993a8d5,0x2ed0afaf,0x2cb0afaf,0xaf462e1f,
0xaff42ed0,0x2b5ead72,0xad271cb6,0xaff42fe6,0xa44e2dba,0x9fd9a6a1,0xaf302fd4,0xae5e2f6e,0x2fbcad27,0x2d4dabb7,0x9fd92d00,0x2cd8ae1f,
0x2c87af80,0x2f5aae7c,0x2f5aac32,0x26a1aaaa,0xacb01648,0x2fffafdd,0x2d72afd4,0xa7651648,0xafaf2f91,0x2f1aafbc,0xab5ea44e,0xad002b05,
0x2b05230e,0xa44e28d5,0xafbc2fa0,0x2f91af02,0x3000aed0,0x26a19cb6,0xa5db2d72,0x3000afe6,0x2aaaaeb5,0x2c32a9f1,0x2e7ca9f1,0x2f80afdd,
0xad27244e,0x2e3fad4d,0x2f02affc,0x2e1faee9,0xaa4e2e5e,0xaeb52f30,0xac5d1fd9,0x9648244e,0x2cb0a30e,0xad722e1f,0xafff2f1a,0x2765a30e,
0x2ff8af46,0xabb72cb0,0xabb72ed0,0x2b5ea993,0x2b05ae99,0xa81429f1,0x2c079648,0x2d4dac87,0xafa02fe6,0xafaf2f80,0x2d00af46,0xafa02fc9,
0xa9342dba,0xafed2fd4,0xa814a6a1,0xaf302f6e,0x2c87a44e,0xb0002ffc,0xaf6e2d4d,0xae992ee9,0x2fffaf02,0xafe62ff8,0xaed02ff8,0xaddc2e3f,
0xaed02c87,0xaaaa2a4e,0x2f80adba,0xacb02c87,0xafaf2fed,0xab5e2b05,0x2f1aaffc,0xad002cd8,0xab052e1f,0xac072bb7,0x2814ad00,0xad4d2d27,
0x29f11cb6,0xac5d2c32,0xac5d2515,0xad962d72,0x2d722d96,0x25152c5d,0x2c322c5d,0x1cb6a9f1,0x2d272d4d,0xad00a814,0x2bb72c07,0x2e1f2b05,
0x2cd82d00,0xaffcaf1a,0x2b052b5e,0x2fed2faf,0x2c872cb0,0xadbaaf80,0x2a4e2aaa,0x2c872ed0,0xae3faddc,0xaff8aed0,0xaff8afe6,0x2f022fff,
0xaee9ae99,0xad4daf6e,0xaffcb000,0x244e2c87,0xaf6eaf30,0x26a1a814,0xafd4afed,0xadbaa934,0xafc9afa0,0x2f462d00,0xaf80afaf,0xafe6afa0,
0xac87ad4d,0x9648ac07,0x29f12814,0xae99ab05,0xa993ab5e,0x2ed02bb7,0x2cb02bb7,0xaf46aff8,0xa30ea765,0x2f1a2fff,0x2e1f2d72,0xa30eacb0,
0x244e1648,0x1fd92c5d,0x2f302eb5,0x2e5e2a4e,0x2ee92e1f,0x2ffc2f02,0x2d4d2e3f,0xa44ead27,0x2fdd2f80,0x29f12e7c,0x29f12c32,0x2eb52aaa,
0x2fe63000,0xad72a5db,0x1cb626a1,0x2ed03000,0x2f022f91,0xafa0afbc,0xa8d5a44e,0xa30e2b05,0x2b052d00,0xa44e2b5e,0xafbcaf1a,0x2f912faf,
0x16482765,0xafd4ad72,0xafddafff,0x16482cb0,0xaaaaa6a1,0xac32af5a,0xae7caf5a,0xaf80ac87,0xae1facd8,0x2d001fd9,0xabb7ad4d,0xad27afbc,
0xaf6eae5e,0xafd4af30,0x26a19fd9,0xadbaa44e,0xafe6aff4,0x9cb6ad27,0x2d722b5e,0xaed0aff4,0xae1faf46,0x2faf2cb0,0x2faf2ed0,0x28d5a993,
0xa934ac87,0x2c072f6e,0x2fbc3000,0x2ffc2e99,0xa8d5acb0,0x2875aaaa,0x2e3f2f80,0xa8d5aed0,0x29341648,0x2fed2eb5,0x28142c5d,0x2f302a4e,
0x2e992cd8,0x16482d4d,0xa9f19fd9,0x2c872fbc,0x2fff2faf,0xafe6ad27,0xaed0ad27,0xaddca30e,0x2fc92e99,0x2f802f5a,0xaf46ad96,0x2fe62e99,
0x2f022fed,0xa8d52b05,0xafa0affc,0xa30e2cd8,0x29342d27,0xafbcaf02,0xac07ae3f,0xaffcae1f,0xaa4e9cb6,0x26a1ac32,0x26a1a515,0x1648ad72,
0xaaaa29f1,0xaed025db,0xacb025db,0x2f801648,0xaf1aaf91,0x2875ae5e,0xae3fafed,0xab5e2d4d,0x2c07a875,0x2b052ff8,0x2d4da17e,0xa814aff4,
0x2eb52fc9,0xaf6ead72,0x2dba2fff,0x2eb52e7c,0xaf02af80,0xab5eafe6,0xab5eafc9,0xa30e2f46,0x2cd8a6a1,0x2f302d96,0x2f9129f1,0xac07afd4,
0x2d962ffc,0xafdda44e,0x25db2ee9,0x2f5a2d4d,0xae7ca17e,0x2d72abb7,0xafffad00,0xafc9a17e,0x2c5da934,0x2f5aa44e,0x30002cd8,0xaeb5adfe,
0x2d722ff8,0xacb02d00,0xa7652d00,0x2fff28d5,0xaf02a515,0x217eaf80,0xaf1aaf46,0xaf022765,0xa814af5a,0x2b052fdd,0x2d4da5db,0x2c07ad96,
0x2e5e2fa0,0x29342ff4,0xab052bb7,0x2ee9a8d5,0xaeb59cb6,0xad96aed0,0xad96afe6,0xac872d72,0xa765af6e,0x2f802c5d,0x2f4625db,0x2515af6e,
0x2ff42d4d,0xaff8a44e,0x217e2ee9,0x28752ffc,0xad4d2875,0xafbc217e,0xacd8aff8,0x1fd92ff4,0xaa4eafe6,0x2e99aaaa,0x2fd42993,0xaa4eafc9,
0x2fff2c87,0xacb02d96,0xa7652d96,0x2d722eb5,0xab5e2c07,0x2875af30,0xae3faf91,0xaf1aacd8,0xad96afbc,0xa5dbaffc,0x2fdd2934,0xaf5aac07,
0x2fc92875,0x2aaa2fa0,0xa9932d27,0x2fe62875,0xa8d52d72,0xad00aed0,0xad00afe6,0xaff89cb6,0xad4dafd4,0x2e5e2d96,0x2fed29f1,0x2f91a6a1,
0x2e1fa765,0x2ff49cb6,0xa8752ddc,0x2e1facb0,0x1fd92f5a,0xafbc25db,0xacd8afdd,0xad4d2d96,0xaeb5aee9,0x2f5aa934,0x30002b05,0x2c5dae5e,
0x2f80230e,0xaed02b5e,0xacb02b5e,0xaaaa2f02,0x2cb02fd4,0x1cb63000,0xaddcaf5a,0x27652fd4,0xaff4ac07,0xa17eaffc,0x2ff82934,0xa875afbc,
0x2dfea8d5,0x244e2ff4,0xacd82bb7,0x29342fa0,0x96482f46,0xa5dbafe6,0xa5dbafc9,0xa9f1af80,0xafff9648,0xae7ca6a1,0xafc9a6a1,0x2d722a4e,
0x2ff81fd9,0x230e2ee9,0x2faf2814,0x217eaf91,0xafeda30e,0x2d4dafa0,0xaf91a8d5,0xae5e2f02,0x2fdd2515,0xb0002aaa,0x2f6e2993,0x2fdda765,
0x230eafff,0x2d27afc9,0x2d27ae7c,0xafaf2d72,0xa8142fdd,0xaffc2a4e,0xadfe2dba,0x2e5e25db,0x2a4eaf91,0x2c5d2c07,0x2eb5acd8,0x1648af30,
0xac322f1a,0x2993aff4,0xaf462bb7,0xae7c2f1a,0x2fdd1fd9,0x2dba2814,0x2a4e2ee9,0x25dbaf91,0xaf46a8d5,0x2765afaf,0xa515afaf,0xaf802e1f,
0x2e3f2c32,0xafa02ddc,0xa17e2fff,0x2e3f2515,0xacd8adba,0x2dfe26a1,0x2934afd4,0x244eaf6e,0xa8142ff8,0xadfe2faf,0xaffc230e,0x2e5e217e,
0x2c87af46,0x2f5aa515,0x2f5a2765,0x26a1af80,0xae7c2dba,0x9cb6ae99,0xaddcac5d,0xafc92dba,0x2fafab05,0xaf1a2ee9,0x2b5e2e5e,0x2d002934,
0xaf91a30e,0xacd8a8d5,0x2c07afa0,0xaf302f02,0x2dba2c32,0xac5d2fff,0xae992ddc,0x2dba2515,0xa993aeb5,0x2fc9a9f1,0x2fe6a9f1,0x2aaaafdd,
0xa17e2fed,0xa30eadfe,0xafaf9fd9,0xaff82c07,0x2a4eafed,0x2eb5af91,0x2c5d2d4d,0x1648ae5e,0xae7c2e3f,0xaddca17e,0x9cb6afa0,0xafc92e3f,
0x2ff8a993,0xabb72fe6,0xabb72fc9,0x2b5e2aaa,0xaf30a5db,0x2fbcaa4e,0x2ee9adba,0x2dfeafdd,0x2f1a2515,0x2bb72993,0xaff42aaa,0x2f1aa765,
0xab05adba,0x2e5eafd4,0x2ee926a1,0x2934af6e,0xa5db2fed,0xadba9fd9,0xaa4eadfe,0xafdd2c07,0x2ddcaf02,0xacb02ff8,0xa7652ff8,0x9cb62e3f,
0xac322fdd,0xaf462f6e,0x2993b000,0xae7c2fdd,0x2fafacd8,0x2b5e2934,0xaf1a2dfe,0x2d00244e,0xaf30a17e,0x2ee9afaf,0x2fbca30e,0x2dfeaff8,
0x29f12ddc,0xac5da765,0xac5dacb0,0xad969cb6,0xa993aa4e,0x2765ac87,0xa515ac87,0xaaaa2dba,0xafa02f30,0xabb7244e,0xaff42e5e,0x28d51fd9,
0x28142bb7,0xaf912e1f,0x1fd92d27,0x2ee9ad00,0x2fd4aed0,0xaf5a2fff,0x3000addc,0x2fd4afe6,0x2fafaf46,0x2fa0ae7c,0x2fa0ac32,0xad002993,
0xa44eac5d,0x2f91b000,0x2b05af5a,0xafbc2eb5,0xb0002dfe,0x2c87ae5e,0xae992814,0xaf6e2ffc,0xa5152e1f,0x9cb6a875,0xad722ff4,0xac322e1f,
0x26a12b05,0xa9f12cd8,0xad962fed,0x2fd4affc,0x2fffae1f,0x2515230e,0x2c32230e,0x2ddcaf1a,0x2875ae7c,0x2d27aaaa,0x2fa0af80,0x2875ac32,
0xaee929f1,0x2f91ae99,0x9fd9ac87,0xa8149648,0xafed2f1a,0xaf302e3f,0xa934a875,0xa8142b5e,0xa6a12ddc,0xb0002fc9,0xb0002e7c,0x25db1cb6,
0x2ed0aa4e,0xaf462fd4,0xa9932e99,0x2cb0aa4e,0x2e3faffc,0xad272e5e,0x2e1fa814,0x2f02adfe,0x9fd9abb7,0x2c07ad27,0x2fedae1f,0xadfe2d00,
0xaf6e2cb0,0x25dba993,0x2c5daf46,0xaf6e2ed0,0xaddc2fdd,0xa5159648,0xac329648,0xafff2fd4,0x28d52814,0xabb72934,0xaff42f30,0xafa02fed,
0x3000aee9,0x2e99adfe,0xac872f30,0x2f6eafbc,0x2c32af02,0x2f80af1a,0x2aaa217e,0x2e7caf02,0xab5e9cb6,0x2ff4afc9,0x2ff4ae7c,0x2d27addc,
0xaffc2eb5,0x2fedb000,0x2cd8af5a,0x2b05ac5d,0xa17e2c32,0xad002d72,0xabb71cb6,0xa17e2515,0x2dfea9f1,0xac072c87,0xafed2e99,0x1fd91648,
0x2fd4afbc,0xa9f12b05,0xad962f91,0x26a1a44e,0x2aaaae3f,0xa76528d5,0x251528d5,0x2993a875,0xafe62eb5,0xaddc2dba,0x2fffaf6e,0xaed02eb5,
0xae3f2fbc,0xae1f2dfe,0x2d27af30,0xaf022ee9,0x9fd92b5e,0xae5e2e3f,0xa44ea875,0xaf302f1a,0x2d96a993,0xae992e7c,0xae992c32,0xaf5a2f46,
0x299329f1,0xa76525db,0x251525db,0x2aaa1648,0x28d52934,0xaf02acd8,0x230e244e,0x2fa02dfe,0x28142875,0xaf91aff8,0x1fd9217e,0x2ee92ff4,
0x26a12765,0xaa4eaddc,0x16481cb6,0x26a12cb0,0xaf02af46,0xab5eae7c,0xab5eac32,0xa30e2993,0xae5eaeb5,0x2b059648,0xa934aa4e,0xaee9ac5d,
0xad96adfe,0x2fdd2e5e,0xa5dba814,0xaf5aaffc,0xacb0ad27,0x2ddc2faf,0x9cb6a30e,0xa765ad27,0x2fd42f91,0x2f6e2fed,0x2dba2e5e,0xa6a1ad4d,
0x2fff2ff8,0x25152d00,0x2c322d00,0x2ddc28d5,0x2faf2fe6,0xae1fa993,0x28d52aaa,0x2faf2fc9,0x2ee92f5a,0xaf91afdd,0x1fd925db,0x28142d96,
0xacd8ab5e,0xaf91ad00,0xaf30afaf,0x2c072f1a,0xaeb5addc,0xad96afc9,0xad96ae7c,0xac879cb6,0xafc9af5a,0x2993a6a1,0xaaaaac87,0xafe6af5a,
0xaff4affc,0x2ff82e5e,0xa17ea814,0xa875adfe,0x9fd9a875,0x2c07a17e,0x2fed2ff8,0xadfeaff4,0x29f12515,0x2fdd2f46,0x2eb52f80,0x29f1a765,
0x2ddc2c87,0x25152d96,0x2c322d96,0x2fff2eb5,0x2fa02ee9,0xaf02ab05,0x230e2934,0x28d52e5e,0x2d962ee9,0x25db2dfe,0xafddaf30,0x2f5a2fbc,
0x27652bb7,0xaf46ab5e,0xaf80aff8,0xa5152bb7,0xa8d59cb6,0xad00afc9,0xad00ae7c,0xaff8addc,0xadfeac5d,0x2cd89648,0xa44eaa4e,0xa934aeb5,
0xaff8afc9,0xae3fafff,0x2f022d72,0xaff8ae7c,0xadfeaf5a,0x2c07a5db,0x2fed2fdd,0x9fd9ad96,0xa6a1ac07,0x2f6e2f91,0x2dba2f30,0x2fd42cd8,
0x2aaa230e,0xa7652b5e,0x25152b5e,0x29932f02,0x2e7c2c5d,0x2fff2d96,0xad72a9f1,0x2fc92c5d,0x2ff42fbc,0x217e2dfe,0xaff8af30,0x28752ee9,
0x2d4d2f1a,0xafedad00,0xae5eafaf,0xaf91ab5e,0x96482993,0xa5dbae7c,0xa5dbac32,0xa9f1af46,0xaddc9648,0xafe6a6a1,0xaed0a6a1,0x2fff2a4e,
0xad27affc,0x2d00ac07,0xabb7afbc,0xae1f2934,0x2e5e230e,0x1fd92fa0,0x2f3028d5,0x244eaf02,0x2c872fe6,0xadbaaf46,0x2a4e2f80,0x2c872fc9,
0x230ead72,0x2d27ac32,0x2d27a515,0xafaf9cb6,0x2fbc2e99,0x9fd92f6e,0x2d4d3000,0x2cd8ac87,0xaa4e2b05,0xac5dafbc,0xaeb5a44e,0x96482f91,
0xaed0afa0,0x2f802d00,0xaaaaafaf,0xacb0afa0,0x2c872ffc,0x16482fbc,0xa9f12c07,0x2e99a934,0xaf80a8d5,0xac32afaf,0xae7cafaf,0xaaaa2e1f,
0xa30eaed0,0x2f1a2d72,0x2e1f9cb6,0xa30eafe6,0x2fed2dba,0xaffca6a1,0x2b052fd4,0x2cd82f6e,0xafbcae1f,0xad4daf02,0x1fd9ae3f,0xacd82d27,
0x2c87a993,0x2f5a2cb0,0x2f5a2ed0,0x26a1af46,0x2cb03000,0xafffa5db,0xad7226a1,0x27653000,0xafafa934,0x2f1aa814,0xab5eafed,0xad00af30,
0x2f30230e,0x2fed28d5,0x28142fa0,0x2934af02,0x16482ed0,0xafd41cb6,0xafddad72,0x16482fe6,0xaf46aeb5,0x2ed0a9f1,0x2cb0a9f1,0xa993afdd,
0x2e1fa44e,0xad002d4d,0x2bb72ffc,0x2d272ee9,0xaa4e2cd8,0xaeb52b05,0xac5daffc,0x96482fed,0xacb0aff4,0x2d72ad27,0x2fff2b5e,0xa765aff4,
0x2ff82aaa,0xabb72e7c,0xabb72c32,0x2b5e2f80,0xab052c87,0x2814af6e,0xac07b000,0xad4dae99,0xa8d5afe6,0x2875af80,0x2e3f2f46,0xa8d5afc9,
0x2f912dba,0xa44e2fd4,0xafbca6a1,0x2b052f6e,0xae99244e,0x9648affc,0x29f1ad4d,0xac87aee9,0x1cb6af02,0x25152ff8,0x2c322ff8,0x2d722e3f,
0x2ed02e99,0x2aaa2f5a,0xaf80ad96,0x2cb02e99,0xafafa44e,0xab5eaf30,0x2f1a9fd9,0xad00ae5e,0x2b05ad27,0x2c072f02,0xa8142e3f,0x2d4d2e1f,
0x29f12fff,0xac5daed0,0xac5dafe6,0xad96addc,0xaf46aa4e,0xac32ac87,0xae7cac87,0x29932dba,0x2f1a2b05,0xa8752fed,0x2e3f2cd8,0x2b5eaffc,
0xaee9abb7,0x2f30ae1f,0xadfead27,0xafbc2d00,0x2eb52c32,0xaf6e1cb6,0x2dba2d72,0x2eb52515,0x2fafa993,0x2fa0a515,0x2fa02765,0xad00aaaa,
0xafed26a1,0xa934ad96,0xaf30a9f1,0xa8142fd4,0x30009fd9,0xac872fed,0x2e992c07,0x2f6eadfe,0xafe6a17e,0x2fffabb7,0xaddcad00,0xaed0a17e,
0xac5d2f30,0xaf5a2e5e,0xb000244e,0x2eb51fd9,0x2ddcae1f,0x2e7c230e,0x2fc9230e,0x1cb6af1a,0xaf022cb0,0x217eaf46,0xaf1aa993,0xaf022ed0,
0x2fbca9f1,0xaf302e99,0x2dfe2c87,0x2ee91648,0xa44eafa0,0x2b05aff4,0x2f91abb7,0xafbc28d5,0xa6a12fff,0xb0002c32,0xb0002515,0x25db2ddc,
0x2c32af6e,0x2aaa2c5d,0x2f8025db,0x2e7caf6e,0xae3f2dfe,0x2d27afed,0xae1fac07,0xaf021fd9,0x2dfe2bb7,0x28142d27,0xae5e2e1f,0x2ffcad00,
0xaa4eae7c,0x2e99af80,0x2fd4aaaa,0xaa4eac32,0x9cb62fdd,0xae7c9648,0xafc99648,0xaddc2fd4,0x2b5eafbc,0xa8752f91,0x2e3f2b05,0x2f1aa44e,
0xb0002814,0xae991fd9,0x2c87af91,0xaf6e2ee9,0x2ed02875,0xa9932fa0,0xaf462d27,0x2cb02875,0xab5eaddc,0x2ff4ac32,0x2ff4a515,0x2d27afff,
0x9fd92fd4,0xa44ead96,0xae5ea9f1,0xaf3026a1,0x2e1faed0,0x2ff4addc,0xa8752fff,0x2e1fafe6,0xaffc29f1,0xa814ac87,0x2e5eae99,0xadfe9648,
0x2eb52814,0xaf5a2f30,0xb0002934,0xac5d2fed,0xa993ae3f,0x2c3228d5,0x2e7c28d5,0x2f46a875,0xa5152fd4,0xad723000,0x9cb6af5a,0xac322fd4,
0x2e3faee9,0x2e1f9fd9,0xad272f91,0x2f02a814,0xaffc28d5,0x2cd8aff4,0x2fedabb7,0x2b05afa0,0x2d962aaa,0xae992515,0xae99a765,0xaf5a2993,
0x1cb6adba,0x2cb0aeb5,0x2765aeb5,0xaddc2f6e,0xaff82d4d,0xa30ea814,0xafaf2c07,0xa17e2b05,0xa44e2e3f,0xadfe2b5e,0xa9342f1a,0x2cd8a875,
0x2fddacb0,0xb0002f80,0x2f6eaaaa,0x2fddaed0,0x2d001cb6,0x217e2765,0x217e2cb0,0x2bb7addc,0x2ee9afdd,0x2d4daa4e,0x2ffcadba,0xa44ea5db,
0xa9f1a934,0x2fd4aee9,0x26a1ae5e,0xad962b05,0xafc92f1a,0x2f46aff4,0xaf802bb7,0xafe62f1a,0xafdd2d4d,0xadba2c07,0xaa4ea814,0xa5db2b05,
0xaaaa2f1a,0xafc92f02,0xafe62f02,0x2993a17e,0x2e3fa765,0xafa02fff,0xa17e2d72,0x2e3facb0,0x2e5eb000,0xad4d2eb5,0x2f91ac5d,0x2fedaf5a,
0x2ee9aff8,0x2ffcafaf,0x2d4da30e,0xa44ea17e,0xa5dbaaaa,0x2f6eafe6,0x2f6eafc9,0xac5d2993,0xafe62dba,0x2d72ae99,0x9cb6ac5d,0xaed02dba,
0xabb72f30,0x28d5ac07,0xafa02cd8,0xaff42f91,0xa9342e3f,0xae5e2f1a,0xaee92b5e,0x2b05a875,0x2dbaa765,0xac5d2d72,0xae992fff,0x2dbaacb0,
0x2f80afd4,0xa7652a4e,0x25152a4e,0x2f46ae99,0x217eacd8,0x230e1fd9,0x2fafad4d,0x2ff8afbc,0xa9f1a44e,0x26a1a934,0x2fd4adfe,0xad962cd8,
0xafe62e3f,0x9cb6a17e,0x2d72afa0,0xaed02e3f,0xad272f80,0xa8752515,0xa875a765,0xafa02f46,0x293425db,0xac072a4e,0xafbc2dba,0xaffc2fdd,
0x2f1aacb0,0x2bb7aaaa,0xaff42f80,0x2f1aaed0,0x2f30b000,0x2cd8ac5d,0xac072eb5,0x2f91af5a,0x25dbacd8,0x2dbaad4d,0x2a4e1fd9,0x2fddafbc,
0xad722875,0x2e7cae1f,0x2fc9ae1f,0x2fffaff4,0xafc92fdd,0xaf802f6e,0x2f46b000,0xafe62fdd,0xabb72e5e,0xafa02f91,0x28d5ad4d,0xaff42fed,
0x2934217e,0xafbc2faf,0xac07230e,0xaffc2ff8,0x2f5aad72,0xafd42fc9,0xafd42e7c,0xb0002fff,0x9cb69648,0xacb0a6a1,0xa765a6a1,0x2ddc2a4e,
0xa17e9fd9,0xaff4aee9,0xa875a814,0x2ff82f91,0xa44ea30e,0xadfeafa0,0xa934a8d5,0x2cd82f02,0xa5dba515,0x9648aaaa,0xa9f1a993,0xa5db2765,
0xa30e9cb6,0xad27a765,0xad27acb0,0x2faf2ddc,0xa814a5db,0xaffcaf5a,0xadfead96,0x2e5e2fdd,0xaa4ea934,0xac5daee9,0xaeb5ae5e,0x96482b05,
0xac32ab5e,0x2993a30e,0xaf46af02,0xae7cab5e,0xa5db9fd9,0xad96a814,0xaf5aaee9,0x2fdd2f91,0xaaaaa8d5,0xafc9afaf,0xafe6afaf,0x29932e1f,
0xad00ac32,0xa8d5addc,0xaff8afff,0xad00a515,0xae5eadba,0x2d4d26a1,0xaf91afd4,0xafedaf6e,0xa814a17e,0xadfea875,0xaffcaff4,0x2e5e2ff8,
0xac87aaaa,0xaf5aafe6,0xaf5aafc9,0xa6a12993,0xae7cad96,0x9cb6ac87,0xaddcaeb5,0xafc9ad96,0xafafaf30,0x2f1a2c07,0xab5eacd8,0xad00af91,
0xa934a30e,0xae5ea8d5,0xaee9afa0,0x2b052f02,0xad96ac32,0xaeb5afff,0xac87addc,0xad96a515,0xaf80aeb5,0x2765a9f1,0xa515a9f1,0xaf46afdd,
0xaff8afed,0x2ff42dfe,0x28751fd9,0x217eac07,0xaa4ea44e,0xaeb5a934,0xac5dadfe,0x96482cd8,0xae7cad00,0xaddcaff8,0x9cb6a8d5,0xafc9ad00,
0xaff8af80,0x2bb7a515,0x2bb72765,0xab5eaf46,0xaf30afdd,0x2fbc2f5a,0x2ee92d96,0x2dfe25db,0xab5ea515,0xaf02a993,0xa30eaaaa,0xab5e2765,
0xaf30adba,0xacd8afd4,0x2c0726a1,0xaf91af6e,0xafddafed,0x2d961fd9,0x2f5a2dfe,0x25dbac07,0xad72af02,0x2e7c2ff8,0x2fc92ff8,0x2fff2e3f,
0xac32a5db,0xaf46a9f1,0x29939648,0xae7ca5db,0xafafae5e,0xab5eaf91,0x2f1a2d4d,0xad00afed,0xaf30aff8,0x2ee92875,0x2fbc2ff4,0x2dfe217e,
0xa9f1ad72,0x2c5d2fc9,0x2c5d2e7c,0x2d962fff,0xaf80aa4e,0xafc9ac87,0xafe6ac87,0x2f462dba,0xa8d5af30,0x2f02a44e,0xa30eae5e,0xafa09fd9,
0x2fbc2bb7,0xa9342e1f,0x2ffc2d27,0x2c07ad00,0x26a12ed0,0xaa4eafff,0x16482ddc,0x26a12fe6,0xafafaaaa,0xafa0acb0,0xafa0aed0,0x2d002f80,
0xa44eaeb5,0x2f919648,0x2b05aa4e,0xafbcac5d,0x30002d4d,0xac872cd8,0x2e992fbc,0x2f6e9fd9,0xa5152d27,0x9cb6afaf,0xad72230e,0xac322d27,
0xafd4ab05,0xaf6eacd8,0xadbaafed,0x26a12ffc,0x1cb6ae1f,0x2fe6230e,0x2ed0230e,0xad72af1a,0x2faf2e7c,0xae1f2aaa,0x28d52f80,0x2faf2c32,
0xac0729f1,0x2934ae99,0xaffcac87,0xafbc9648,0xafedab5e,0xaf30ad00,0xa934afaf,0xa8142f1a,0x26a1ad72,0x30002765,0x30002cb0,0xa5dbafff,
0x2ed02f5a,0xaf4626a1,0xa9932c87,0x2cb02f5a,0xae3f1fd9,0x2d27acd8,0xae1fafbc,0xaf02ad4d,0xaffcabb7,0xaee9ad27,0x244eae1f,0xad4d2d00,
0x29f1acb0,0x2fdd2993,0x2eb52f46,0x29f1aed0,0x2d722fdd,0xafe69648,0xaed09648,0x9cb62fd4,0xafa0a814,0x2f02a934,0xa30eaf30,0xa8d5afed,
0xb000ac07,0xae99ad4d,0x2c87ab05,0xaf6e2814,0x2c32abb7,0x2f802b5e,0x2aaa2ff8,0x2e7cabb7,0x2b5e2fff,0xaff4a765,0xaff4acb0,0xad272d72,
0xaffcac5d,0x2fed9648,0x2cd8aa4e,0x2b05aeb5,0xaff8ac32,0xae3fad72,0x2f029cb6,0xaff8a515,0x2d4da9f1,0x2ee92c87,0xa44e2e99,0x2ffc1648,
0x26a12fbc,0xaf6eab05,0xadbaaf91,0xafd4244e,0xaf46ae3f,0x2fc928d5,0x2fe628d5,0x2f80a875,0xafe6ac5d,0xaddcad96,0x2fff29f1,0xaed0ac5d,
0x2e3fa814,0x2e1f2d4d,0xad272b05,0x2f022c07,0x9fd92f1a,0xae5ead00,0xa44eafaf,0xaf30ab5e,0xad96af80,0x2e992cb0,0x2e992ed0,0x2f5a2aaa,
0xad72adba,0xa515aeb5,0xac32aeb5,0x9cb62f6e,0x2d272dfe,0xad002fbc,0x2bb72ee9,0x2e1faf30,0xacd8ae3f,0x2ffcab5e,0xab05af1a,0xafed2875,
0x2c872e7c,0xadbaa993,0x2a4e2f46,0x2c872c32,0xad00addc,0xa17eaed0,0xa17eafe6,0xabb72fff,0x2c072e99,0xadfe2f6e,0x9fd93000,0x2fedac87,
0xa9f1af30,0x2fd4a814,0x26a1afed,0xad96a934,0x27652fa0,0xaaaaad00,0xa9932faf,0xa5152fa0,0xac87adfe,0x9648aee9,0x29f1afbc,0xae992f30,
0x29932f1a,0xaed02f02,0xacb02f02,0x2f46a17e,0xa30eafc9,0x2f1a9cb6,0x2e1faddc,0xa30eae7c,0xa44e3000,0x9fd9aeb5,0xaf302c5d,0xae5e2f5a,
0xac07ae1f,0x1fd9af02,0x2dfeae3f,0xafed2d27,0x25db2f80,0xaf6e2e7c,0xaf6e2c32,0x2c5d2aaa,0x2515b000,0x2ddc25db,0x2fffa6a1,0x2c32b000,
0xabb72f91,0x28d5afbc,0xafa0a44e,0xaff42b05,0xab05ae3f,0x244eaf1a,0x2fbcab5e,0xaf912875,0x16482fc9,0xafd42ddc,0xafdd1cb6,0x16482e7c,
0x2aaaafd4,0x2c322a4e,0x2e7c2a4e,0x2f80ae99,0xae1f2e5e,0x2d00affc,0xabb7adfe,0xad27a814,0xa9f1ae5e,0x26a1af30,0x2fd49fd9,0xad96a44e,
0xa5152ff4,0xafff2d27,0xaddcab5e,0xac322ff4,0x2d27af46,0x28752cb0,0x28752ed0,0x2fa0a993,0xaf912c87,0x2ee9af6e,0x2814b000,0x1fd9ae99,
0xa8d5ae7c,0x2875af46,0x2e3f2993,0xa8d5ac32,0xa9343000,0xafed2c5d,0xa814aeb5,0xaf302f5a,0x2e99ae5e,0x16482dfe,0xa9f12ffc,0x2c872814,
0xafff2875,0x2fe6ae1f,0x2ed0ae1f,0x2ddcaff4,0xa765ae99,0x2993af5a,0x2aaa2d96,0x2515ae99,0xabb72fed,0xafa02b05,0x28d5affc,0xaff42cd8,
0x2f91ad27,0xa8142f02,0xaee92e3f,0x9fd92e1f,0xaf5a9cb6,0x2fd4ac32,0x2fd4a515,0x3000ad72,0x2aaaaf6e,0x2ed0afdd,0x2cb0afdd,0xaf803000,
0xaf1a2934,0x2875acd8,0xae3f244e,0xab5e2dfe,0xac072faf,0xab05217e,0xad4d2ff8,0x2814230e,0x2eb5a765,0xaf6e2ddc,0x2dba9cb6,0x2eb5acb0,
0x2bb7af80,0x2f1aafe6,0x2f1aafc9,0xaff42f46,0xae5e26a1,0x2b05ad96,0xa934a9f1,0xaee92fd4,0xadba2ffc,0xa5dba44e,0xafdd2ee9,0xaa4e2d4d,
0x2cb0217e,0xaddc2bb7,0x1cb62d00,0x2765217e,0x2c5daf91,0x2f5aafed,0x3000ae5e,0xaeb52d4d,0xad72217e,0x2cb0ae3f,0x2765ae3f,0xafff2fa0,
0xaf022fe6,0x217ea993,0xaf1a2aaa,0xaf022fc9,0x28142a4e,0xab0525db,0xad4d2fdd,0xac072dba,0x2cd8afa0,0x2f91aff4,0x2f30abb7,0xac0728d5,
0xac5d9cb6,0x2dbaaed0,0x2dbaafe6,0xae992d72,0xafc92f6e,0x2993ac5d,0xaaaaa5db,0xafe62f6e,0xa30e2d4d,0xa17ea44e,0xaff82ee9,0xafaf2ffc,
0x2d4dafaf,0x2fbcaff8,0x2cd8a17e,0x9fd9a30e,0xaa4ea515,0x2e99af46,0x2fd4af80,0xaa4e2765,0xafff2e99,0x2cb0adba,0x2765adba,0xad722c5d,
0xab5e2ee9,0x2875ab05,0xae3f2934,0xaf1a2e5e,0x2dbaafbc,0x2fddaffc,0x25db2934,0x2a4eac07,0xa765a875,0x2f46afa0,0x2f80ad27,0x2515a875,
0xafa02d72,0x2e3faed0,0x2e3fafe6,0xa17e9cb6,0xadfe2fd4,0x2cd8ad96,0xa44ea9f1,0xa93426a1,0x2e1fafc9,0x2ff4afff,0xa8752d72,0x2e1fae7c,
0x9fd9aa4e,0x2fbcafdd,0x2cd8a5db,0x2d4dadba,0xaeb52c07,0x2f5aaf91,0x3000af30,0x2c5dacd8,0xaf802ff4,0x2ed0af1a,0x2cb0af1a,0x2aaaabb7,
0x2e7cafd4,0x2fffb000,0xad722f5a,0x2fc9afd4,0x230eac07,0x2ff8affc,0x217e2934,0x2fafafbc,0xad4d28d5,0x2fedaff4,0x2e5eabb7,0x2f91afa0,
0xb0002f46,0x2fddafe6,0x2fddafc9,0x2f6eaf80,0xaaaaaa4e,0xaed0ac87,0xacb0ac87,0x2f802dba,0xab5eab05,0xafafafed,0xad00acd8,0x2f1a2ffc,
0xac07abb7,0xab05ae1f,0xad4dad27,0x28142d00,0xac5dac32,0x29f19cb6,0xad96ad72,0xac5da515,0xafafaf80,0xafa0afe6,0xafa0afc9,0x2d002f46,
0xafedafd4,0xa934adba,0xaf30af6e,0xa81426a1,0xb000affc,0x2c87244e,0xae99aee9,0xaf6ead4d,0xafe6aff8,0x2fff2f02,0xaddcae3f,0xaed0aff8,
0xaeb5af30,0xaa4eae5e,0x9648a44e,0xac5d9fd9,0xad72ae1f,0x2cb0230e,0x2765230e,0xafffaf1a,0xabb7acb0,0x2ff82f46,0x2b5e2993,0xabb7aed0,
0xa814a9f1,0x2b052e99,0x2d4d2c87,0x2c071648,0xa44ea8d5,0x2b05a30e,0x2f912f02,0xafbcafa0,0x26a11cb6,0x30002ed0,0x30002fe6,0xa5dbad72,
0x2c3229f1,0x2aaa2eb5,0x2f802fdd,0x2e7c29f1,0x2e3f2d4d,0xad27a44e,0x2e1f2ee9,0x2f022ffc,0x2d4d2bb7,0x2fbc2d27,0x2cd82e1f,0x9fd9ad00,
0x2f5a2e7c,0x2c872f80,0x26a12aaa,0x2f5a2c32,0x2fff2fdd,0xacb09648,0xa7659648,0x2d722fd4,0x2f1a2fbc,0xafafaf91,0xad00ab05,0xab5e244e,
0x30002fbc,0x2e992ffc,0xac87a934,0x2f6e2c07,0x2ed02faf,0xa99328d5,0xaf46ae1f,0x2cb02faf,0x2b5e2d72,0xaff4aed0,0xaff4afe6,0xad279cb6,
0x9fd926a1,0xa44eadba,0xae5eaf6e,0xaf30afd4,0x2d272ed0,0x230e2ddc,0xafafafff,0x2d272fe6,0x1fd929f1,0xafbcac87,0xacd8ae99,0xad4d9648,
0xac5da814,0xaa4eaf30,0x9648a934,0xaeb5afed,0xaf80ae3f,0x2ed028d5,0x2cb028d5,0x2aaaa875,0xa51526a1,0xad721648,0x9cb6aa4e,0xac3226a1,
0xae3fac07,0xae1faffc,0x2d272934,0xaf02afbc,0xaffcafa0,0x2cd8a30e,0x2fed2f02,0x2b05a8d5,0xad96af46,0x2e992fe6,0x2e992fc9,0x2f5a2f80,
0xafffadba,0xae7caeb5,0xafc9aeb5,0x2d722f6e,0x217ead4d,0x2ff42814,0x2875ac07,0xaff8ab05,0x2fed2e3f,0xad4d2b5e,0x2f912f1a,0x2e5ea875,
0xa5db2cb0,0x9648af80,0xa9f12aaa,0xa5db2ed0,0xad00afff,0xa17eafc9,0xa17eae7c,0xabb72d72,0x2ee925db,0x2d4d2f5a,0x2ffc2d96,0xa44eafdd,
0x29f12f91,0xafd4ac07,0xa6a12cd8,0x2d962f30,0xafc9ab5e,0x2f46a30e,0xaf80af02,0xafe6ab5e,0x25dbad4d,0x2d96ac07,0x2f5a2814,0xafddab05,
0x2f462f1a,0xa7652f02,0x25152f02,0x2f80a17e,0xad002765,0xa8d5afff,0xaff8ad72,0xad002cb0,0xacd8b000,0x2dfe2eb5,0x2934ac5d,0x244eaf5a,
0x2ee9217e,0x2ffc2875,0x2d4d2ff4,0xa44eaff8,0x25db2f46,0xaf6e2515,0xaf6ea765,0x2c5d2f80,0xafe6ad96,0x2d72ac87,0x9cb6aeb5,0xaed0ad96,
0x2bb7ab05,0xa8d52ee9,0x2fa02e5e,0x2ff42934,0x2f912e3f,0x2cd82f1a,0xac072b5e,0x2f30a875,0xad962765,0xaeb5ad72,0xac87afff,0xad962cb0,
0xa993afd4,0x2fc92a4e,0x2fe62a4e,0x2aaaae99,0x2ff82cd8,0xaff49fd9,0xa8752d4d,0xa17e2fbc,0x29f12fed,0xa6a12f91,0xafd4ad4d,0x2d962e5e,
0xafe6ad00,0x9cb6aff8,0x2d72a8d5,0xaed0ad00,0x2d27a993,0x28752fe6,0x28752fc9,0x2fa02aaa,0x29342fdd,0xac07af5a,0xafbcad96,0xaffca5db,
0xab5e2cb0,0xaf022aaa,0xa30eaf80,0xab5e2ed0,0xab05b000,0x2e5eac5d,0x2ee92eb5,0x2934af5a,0x2fdd2cd8,0xad962d4d,0xaf5a9fd9,0xa5db2fbc,
0xaddc2875,0x2cb0ae1f,0x2765ae1f,0x1cb6aff4,0xafc9a5db,0xaf80a9f1,0x2f469648,0xafe6a5db,0x2bb7acd8,0x2fa02934,0xa8d52dfe,0x2ff4244e,
0x29342ff8,0xafbca875,0xac07aff4,0xaffca17e,0xaf5aaddc,0x2fd42765,0x2fd42cb0,0x30001cb6,0xa993af6e,0x2765afdd,0xa515afdd,0xaaaa3000,
0x28d52f91,0xaf022e5e,0x230e2fed,0x2fa0ad4d,0xa814afaf,0x2f91a17e,0x9fd9aff8,0xaee9a30e,0x26a12fc9,0xaa4ead72,0x16482fff,0x26a12e7c,
0x2bb7af46,0x2f1aae7c,0x2f1aac32,0xaff42993,0xacd82eb5,0xaf301648,0xaf912a4e,0x2c072c5d,0x2dbaadfe,0x25db2e5e,0x2fdda814,0x2a4eaffc,
0xae7c2d27,0x2d72afaf,0xafff230e,0xafc92d27,0x2fd4a934,0x2f6ea44e,0x2dba2cd8,0xa6a1adfe,0xafff217e,0xa515ae3f,0xac32ae3f,0xaddc2fa0,
0x2faf2515,0xae1f2f80,0x28d52f46,0x2fafa765,0xaee9aa4e,0x2f91a5db,0x9fd9afdd,0xa814adba,0x2e5e2b5e,0x29342d00,0xab052faf,0x2ee9af1a,
0xac5daddc,0x2dbaafc9,0x2dbaae7c,0xae999cb6,0x27652f5a,0xaf8026a1,0xaf462c87,0xa5152f5a,0x230eaffc,0x217e2e5e,0x2ff8a814,0x2fafadfe,
0x1fd92faf,0xac072ff8,0xafed217e,0x2dfe230e,0x29f1afe6,0x2fddaaaa,0x2eb52993,0x29f1afc9,0xaddc2e99,0xa515adba,0xac32adba,0xafff2c5d,
0x2fa0ac07,0xaf022f30,0x230e2f91,0x28d52cd8,0xadba2ee9,0xafdd2dfe,0xa5dbaf30,0xaa4e2fbc,0x2fc9abb7,0x2aaa2b5e,0xa9932ff8,0x2fe6abb7,
0xafa09cb6,0x2e3fafc9,0x2e3fae7c,0xa17eaddc,0x2d4d2c5d,0xae5e1648,0xafed2a4e,0xaf912eb5,0xaff82765,0xae3f1cb6,0x2f02addc,0xaff82cb0,
0x2dfe2a4e,0xac072fdd,0xafed25db,0x1fd92dba,0xa6a1aee9,0x2f6ea934,0x2dba2b05,0x2fd4ae5e,0xaaaa2ff4,0x2765af1a,0xa515af1a,0xa993abb7,
0xacb0ac5d,0x9cb6ad96,0x2ddc29f1,0xa765ac5d,0xa30e2fbc,0xaff82dfe,0xa17eaf30,0xafaf2ee9,0x2dfeaf1a,0x244e2d00,0xacd82faf,0x29342b5e,
0xb0002993,0x2fddae7c,0x2fddac32,0x2f6eaf46,0x2ddcb000,0x2fe6afd4,0x2ed0afd4,0xafff2f5a,0xad279fd9,0x2d00aee9,0xabb7a814,0xae1f2f91,
0xae5e2ff4,0x9fd9a8d5,0xaf302fa0,0xa44e2bb7,0x2c872515,0xadba2aaa,0x2a4e2993,0x2c87a765,0x2ff4ad72,0x2e1fac32,0x2e1fa515,0xa8759cb6,
0x2814ae99,0x2ffcaf6e,0x2dfeb000,0xae5e2c87,0xaf5a2b05,0x2eb5afbc,0xac5da44e,0xb0002f91,0xac322fa0,0x2993ad00,0xaf462faf,0xae7c2fa0,
0x2c871fd9,0x16482814,0xa9f12ee9,0x2e99af91,0x2f80afa0,0x2c32a875,0x2e7ca875,0x2aaaad27,0xa30eac32,0x2f1aaddc,0x2e1fafff,0xa30ea515,
0xafed2d96,0x2ffcafd4,0xab05a6a1,0xacd829f1,0xa8142e1f,0xadfe2f02,0xaffc2e3f,0x2e5ead27,0x2e99a993,0xaa4e2cb0,0xaa4e2ed0,0x2fd4af46,
0x2e7cb000,0x1cb625db,0x2ddca6a1,0x2fc9b000,0xa875a934,0x2b5ea814,0x2f1aafed,0x2e3faf30,0xaf302ff4,0xafed2fa0,0xa814a8d5,0xa9342bb7,
0x16482c32,0xafd42fff,0xafdd2ddc,0x16482515,0x2f46ac5d,0xaed02f6e,0xacb02f6e,0x2993a5db,0x2e1fafed,0xad002dfe,0x2bb71fd9,0x2d27ac07,
0xaf5a2cd8,0xac5d2b05,0x2eb5affc,0xb0002fed,0xae7c2ff4,0xaddc2d27,0x9cb6ab5e,0xafc92ff4,0x217e2aaa,0xaf022e7c,0xaf022c32,0xaf1a2f80,
0x2f30ac87,0xafbc2f6e,0xaee93000,0xadfe2e99,0xa8d5a515,0x2875a993,0x2e3faaaa,0xa8d52765,0xaf912d96,0x244ea6a1,0x2fbcafd4,0xab0529f1,
0xae992fed,0x96489fd9,0x29f1adfe,0xac872c07,0x9cb62bb7,0xa515217e,0xac32217e,0xad722d00,0x2c32ae99,0x2f46af5a,0xa9932d96,0x2e7cae99,
0xa875a44e,0x2f1aaf30,0x2b5e9fd9,0x2e3fae5e,0xaf302d27,0x2ee9af02,0x2fbcae3f,0x2dfeae1f,0xaf6e2fff,0x2eb5aed0,0x2eb5afe6,0x2dbaaddc,
0xaddcadba,0xafe6aeb5,0xaed0aeb5,0x2fff2f6e,0xae1fadfe,0xae3fafbc,0xaf02aee9,0x2d272f30,0xae5eae3f,0x9fd9ab5e,0xaf30af1a,0xa44e2875,
0xae99ae7c,0x2d962993,0xaf5aaf46,0xae99ac32,0xad00ad72,0xa17eac32,0xa17ea515,0xabb79cb6,0xac07ac87,0x2dfe29f1,0x1fd99648,0xafedae99,
0xa9f1ab05,0x2fd42fbc,0x26a1244e,0xad96af91,0xa765a8d5,0x2aaa2e3f,0x29932875,0x2515a8d5,0x2e992dfe,0x30002ee9,0x2f6e2fbc,0xac87af30,
0x2f802f1a,0x2c322f02,0x2e7c2f02,0x2aaaa17e,0x2ff42fc9,0xab5e1cb6,0x2d272ddc,0x2ff42e7c,0x2fed3000,0xaffcaeb5,0x2b052c5d,0x2cd82f5a,
0x2c072d27,0x9fd92bb7,0xadfead00,0x2fed2e1f,0x25db2993,0xaf6eacb0,0xaf6eaed0,0x2c5d2f46,0xa5151648,0xaddcafdd,0xafffafd4,0xac321648,
0xabb7a934,0x28d5a814,0xafa0afed,0xaff4af30,0xaf30ae3f,0xafedaf1a,0xa814ab5e,0xa9342875,0xb000afc9,0xa6a1addc,0x25db9cb6,0xb000ae7c,
0xaf46afd4,0x2ed02a4e,0x2cb02a4e,0xa993ae99,0xad27ae5e,0x2e3f2ffc,0x2f022dfe,0x2e1f2814,0xa9f1acd8,0x26a1ab05,0x2fd42ffc,0xad96afed,
0x2515a30e,0x2fff2e1f,0x2ddc2f1a,0x2c32a30e,0x2d272aaa,0x28752e7c,0x28752c32,0x2fa02f80,0x2f912e99,0xaee9a9f1,0xa8141648,0x9fd92c87,
0x2fa02e7c,0x2faf2f46,0xad00a993,0x2fa02c32,0x2f913000,0xa44e2c5d,0xafbcaeb5,0x2b052f5a,0x2c872e5e,0xb000adfe,0xaf6eaffc,0xae99a814,
0x9cb62875,0xa515ae1f,0xac32ae1f,0xad72aff4,0x27652c87,0xa9932a4e,0xaaaaadba,0xa5152c87,0xabb7a44e,0xafa0af30,0x28d59fd9,0xaff4ae5e,
0xaf91ae1f,0x2814abb7,0x2ee92d00,0x1fd9ad27,0xaf5aafff,0x2fd42ed0,0x2fd42fe6,0x30002ddc,0xaf46af6e,0xac32afdd,0xae7cafdd,0x29933000,
0x2b5ea934,0x2faf2cd8,0x2d00a44e,0xaf1aadfe,0x2ee92faf,0xaf30217e,0x2dfe2ff8,0x2fbc230e,0xac5d2765,0x29f1addc,0xad961cb6,0xac5d2cb0,
0x2bb7a993,0x2f1aa515,0x2f1a2765,0xaff4aaaa,0x2e5e2fd4,0xab052dba,0x29342f6e,0x2ee9a6a1,0xadba1fd9,0xa5dbafed,0xafddac07,0xaa4e2dfe,
0xacb0aff8,0x2ddc2f02,0x9cb6ae3f,0xa765aff8,0x2eb52f91,0x2a4e2fed,0x16482e5e,0x2c5dad4d,0xaddc217e,0xae7cae3f,0xafc9ae3f,0x9cb62fa0,
0xabb7afe6,0x2ff82993,0x2b5eaaaa,0xabb7afc9,0x2fbc2a4e,0xaf3025db,0x2dfe2fdd,0x2ee92dba,0xacd828d5,0xaf91230e,0xaf30af02,0x2c072fa0,
0xac5dafff,0x2dbaac32,0x2dbaa515,0xae99addc,0x2fc929f1,0xa9932eb5,0x2aaa2fdd,0x2fe629f1,0xa30e2dfe,0xa17eafed,0xaff8ac07,0xafaf1fd9,
0xadfeafaf,0xa814aff8,0x2e5ea17e,0xaffca30e,0x2f5a2515,0x2c872f46,0x26a12f80,0x2f5aa765,0x9cb62e99,0xae7cadba,0xafc9adba,0xaddc2c5d,
0xaf1aaee9,0x2faf2b05,0x2d00a934,0x2b5eae5e,0x2dbaa814,0x2fdd9fd9,0x25db2f91,0x2a4eaee9,0x27652faf,0xaf4628d5,0xaf80ae1f,0xa5152faf,
0xafa0addc,0x2e3fac32,0x2e3fa515,0xa17eafff,0x2dfea6a1,0xacd82dba,0x244e2f6e,0x29342fd4,0x2d272fc9,0x230e2fff,0xafafad72,0x2d272e7c,
0xaffcaa4e,0xa814afdd,0x2e5ea5db,0xadfeadba,0x2c5dac07,0x2a4e2f91,0x16482f30,0x2eb52cd8,0x29932ff4,0xac32af1a,0xae7caf1a,0xaf46abb7,
0xae7c26a1,0xafff1648,0x2d72aa4e,0xafc926a1,0x230eaee9,0x2ff89fd9,0x217e2f91,0x2fafa814,0x2d4d2fa0,0xafed230e,0xae5eaf02,0xaf9128d5,
0xb000aaaa,0x2fdda515,0x2fdd2765,0x2f6ea993,0x1cb6b000,0x2cb0afd4,0x2765afd4,0xaddc2f5a,0xa17e2ffc,0xaff42c07,0xa8752fbc,0x2ff8a934,
0x244eaff4,0x2dfe28d5,0x2934afa0,0xacd8abb7,0xa5db2fe6,0x9648af46,0xa9f12f80,0xa5db2fc9,0x2ff41cb6,0x2e1f2765,0x2e1f2cb0,0xa875addc,
0xafbca5db,0x1fd9af5a,0xad4dad96,0xacd82fdd,0x2f5a2934,0xaeb52ee9,0x2c5d2e5e,0x3000ab05,0xaed0ab5e,0x2f80a30e,0xaaaaaf02,0xacb0ab5e,
0xa5db2ffc,0xad962fbc,0xaf5a2c07,0x2fdda934,0x2aaaafa0,0x2fc9a875,0x2fe6a875,0xa993ad27,0xad002ed0,0xa8d5ad72,0xaff81cb6,0xad002fe6,
0x2e5ead96,0xad4d2fd4,0x2f9126a1,0x2feda9f1,0xafbca17e,0xad4da875,0x1fd9aff4,0xacd82ff8,0x2e992aaa,0xaa4e2fe6,0xaa4e2fc9,0x2fd4a993,
0xacb0ad96,0x2fffac87,0x2d72aeb5,0xa765ad96,0x28752f30,0xab5eac07,0xaf1a2cd8,0xae3f2f91,0x2934aff4,0x2e5eafa0,0x2ee928d5,0xab05abb7,
0xad962ed0,0xaeb51cb6,0xac87ad72,0xad962fe6,0x2f80ac5d,0xa7652f6e,0x25152f6e,0x2f46a5db,0xaff8244e,0x2ff4ad4d,0x2875affc,0x217eaee9,
0x2f5a244e,0x2c5d2934,0xaeb52dfe,0x3000acd8,0xacb0ad00,0x2d72aff8,0x2fffa8d5,0xa765ad00,0x217e2f80,0xaf022515,0xaf02a765,0xaf1a2f46,
0x2b05afdd,0xa8142f5a,0x2c072d96,0x2d4d25db,0xab5e2fe6,0xaf022f80,0xa30eaf46,0xab5e2fc9,0x2f30ad96,0x2cd826a1,0xac072fd4,0x2f91a9f1,
0xafdd244e,0x2d96affc,0x2f5aad4d,0x25dbaee9,0x2d722bb7,0xae7c217e,0xafc9217e,0xafff2d00,0xaed0a5db,0xaaaaa9f1,0x2f809648,0xacb0a5db,
0x28752e5e,0xaf1a2f91,0xab5ead4d,0xae3f2fed,0x2b05aff8,0x2c072875,0xa8142ff4,0x2d4d217e,0xaf6e2d72,0x2eb5afc9,0x2eb5ae7c,0x2dbaafff,
0x2f80af5a,0x2fc9ae99,0x2fe6ae99,0xaf462d96,0xa8d5ab05,0x2f02afed,0xa30eacd8,0xafa02ffc,0xafbc2f02,0x2934ad27,0xaffc2e1f,0xac072e3f,
0x26a12c32,0xaa4e1cb6,0x16482d72,0x26a12515,0x28752aaa,0xa8d52cb0,0xa8d52ed0,0x2e3faf80,0x2fedaeb5,0x29349648,0x2f30aa4e,0x2814ac5d,
0x1648ad4d,0x2e99acd8,0x2c87afbc,0xa9f11fd9,0xafe62d27,0x2fffafaf,0xaddc230e,0xaed02d27,0xafd42f30,0xaf6e2e5e,0xadba244e,0x26a11fd9,
0x9cb62d27,0xafe62ff4,0xaed02ff4,0x2d72ab5e,0x2fafacb0,0xae1f2f46,0x28d52993,0x2fafaed0,0x2c07af6e,0xa9342c87,0x2ffcae99,0x2fbcb000,
0xa44eab5e,0x2b05ad00,0x2f91afaf,0xafbc2f1a,0xafd42d72,0x1648a765,0x1648acb0,0xafdd2fff,0xac322f5a,0xaaaa26a1,0xaf802c87,0xae7c2f5a,
0x2d009fd9,0xae1f2cd8,0xad272fbc,0xabb72d4d,0x2ffcaf02,0x2ee9ae1f,0xa44e2d27,0x2d4dae3f,0x29f1ae7c,0x2fddaf80,0x2eb5aaaa,0x29f1ac32,
0xad7225db,0x2fe6b000,0x2ed0b000,0x1cb6a6a1,0xafa02fbc,0x2f02af91,0xa30eab05,0xa8d5244e,0x96482c07,0xac872d4d,0xae992b05,0x29f1a814,
0x2ed0abb7,0xa9932b5e,0xaf462ff8,0x2cb0abb7,0x2f1aafff,0xa30e2765,0xa30e2cb0,0x2e1fad72,0x1fd9ac5d,0x244e9648,0x2e5eaa4e,0x2f30aeb5,
0xaff82ed0,0xae3f2ddc,0x2f02afff,0xaff82fe6,0xad4d2f6e,0xaee92e99,0x244eac87,0xaffc3000,0x26a12814,0xaf6e2f30,0xadba2934,0xafd42fed,
0x2f46ad00,0xafc92fa0,0xafe62fa0,0xaf802faf,0x2515ac5d,0x2d72ad96,0x1cb629f1,0x2c32ac5d,0xad002814,0x2d27ad4d,0x2e1fab05,0x2bb7ac07,
0xaffc2f1a,0x2cd8ad00,0x2fedafaf,0x2b05ab5e,0xadba2f80,0x2c87acb0,0x2c87aed0,0x2a4eaaaa,0xaf80af6e,0xafc9afdd,0xafe6afdd,0x2f463000,
0xafa0af91,0xabb7ae5e,0xaff4afed,0x28d52d4d,0xafbcafaf,0x2934a17e,0xaffcaff8,0xac07a30e,0xafd4afc9,0x2f5a2d72,0xb000afff,0xafd4ae7c,
0x2bb72aaa,0x2f1a2cb0,0x2f1a2ed0,0xaff4af80,0x2cd82c5d,0x2f303000,0x2f912f5a,0xac07aeb5,0x2dba2d4d,0x25db2cd8,0x2fdd2fbc,0x2a4e9fd9,
0x2e7c2e1f,0xad72a875,0x2fff2ff4,0x2fc92e1f,0x26a12934,0xa9f1244e,0xad96acd8,0x2fd42dfe,0x9cb6217e,0xafe6ae3f,0xaed0ae3f,0x2d722fa0,
0xa875a515,0xad27af80,0xafa0af46,0xa8752765,0xac07aa4e,0x2934a5db,0xaffcafdd,0xafbcadba,0xae5eaf1a,0xa934ae3f,0x2b052875,0xaee9ab5e,
0xac5dad72,0x2dba2765,0x2dba2cb0,0xae99afff,0xa765aa4e,0x2f802fd4,0x2f462e99,0x2515aa4e,0x230e9fd9,0x217e2cd8,0x2ff82fbc,0x2faf2d4d,
0x2ffc2faf,0x2ee92ff8,0xa44e217e,0x2d4d230e,0x2f6e2fe6,0xa5db2aaa,0xac5da993,0x2f6e2fc9,0x2d722e99,0xafe6adba,0xaed0adba,0x9cb62c5d,
0x28d52c07,0xabb7af30,0xaff4af91,0xafa0acd8,0xadbaac07,0xafddad4d,0xa5dbab05,0xaa4e2814,0xafc9af02,0xaaaaaf1a,0x2993217e,0xafe6af02,
0xafa0afff,0x2e3f2765,0x2e3f2cb0,0xa17ead72,0xad4daeb5,0x2e5e3000,0x2fed2f5a,0x2f912c5d,0x217ea765,0x2d009cb6,0x2bb72ddc,0x217eacb0,
0x2d4d2a4e,0x2ee92fdd,0xa44e25db,0x2ffc2dba,0x2fd42ee9,0xa9f12934,0xad96ab05,0x26a12e5e,0x2f462ff4,0xafc9af1a,0xafe6af1a,0xaf80abb7,
0x2cb02eb5,0x1cb62dba,0xaddcaf6e,0x27652eb5,0xa30e2814,0xaff8ad4d,0xa17eab05,0xafafac07,0xadfeab5e,0xa44eae3f,0x2cd82875,0xa934af1a,
0xb000af80,0x2fdd2cb0,0x2fdd2ed0,0x2f6e2aaa,0xad72b000,0xa515afd4,0xac32afd4,0x9cb62f5a,0x2e1f1fd9,0x2e3f2ee9,0x2f022814,0xad27af91,
0x2cd82ff4,0xaffca8d5,0x2b052fa0,0x2fed2bb7,0xae99a515,0x2d96aaaa,0xaf5aa993,0xae992765,0x2ff42ddc,0x2e1f2ed0,0x2e1f2fe6,0xa875afff,
0xa8142c87,0xaffca9f1,0xadfe1648,0x2e5e2e99,0xaf5aaf30,0x2eb5a814,0xac5dafed,0xb000a934,0x2c32a8d5,0xa9932e3f,0x2f462875,0x2e7ca8d5,
0xae999fd9,0xb000a814,0xaf6eaee9,0x2c872f91,0xa993afa0,0x2ed0a875,0x2cb0a875,0xaf46ad27,0x2ff42c32,0xab5e2ddc,0x2d272fff,0x2ff42515,
0xa44e2d96,0x9fd9afd4,0xaf30a6a1,0xae5e29f1,0x2814ad27,0x2dfeabb7,0x2ffc2d00,0xae5eae1f,0x2e992f80,0xaa4e2e7c,0xaa4e2c32,0x2fd42aaa,
0xae7c1648,0x9cb6afdd,0xaddcafd4,0xafc91648,0xa875af91,0x2b5e2fbc,0x2f1a244e,0x2e3fab05,0x2b052ff4,0xa44e2fa0,0xafbca8d5,0x2f912bb7,
0xb000ac32,0xa6a1afff,0x25dbaddc,0xb000a515,0x2aaaac5d,0x2c322f6e,0x2e7c2f6e,0x2f80a5db,0x2d272fed,0xae3fadfe,0xaf029fd9,0xae1f2c07,
0xaf5aae5e,0xac5daf30,0x2eb59fd9,0xb000a44e,0x2e7ca30e,0x2ddc2e1f,0x1cb62f1a,0x2fc9a30e,0x217e2f46,0xaf02acb0,0xaf02aed0,0xaf1a2993,
0xaf30ae99,0x2fbc29f1,0x2ee99648,0x2dfeac87,0x2fa02515,0x2faf2993,0xad002aaa,0x2fa0a765,0xa9342d96,0xafeda6a1,0xa814afd4,0xaf3029f1,
0xac87afed,0x30001fd9,0x2f6e2dfe,0x2e99ac07,0x2fff2bb7,0xafe6217e,0xaed0217e,0xaddc2d00,0xac322c87,0xaf462a4e,0x2993adba,0xae7c2c87,
0xa875afed,0x2f1aab05,0x2b5e2ffc,0x2e3facd8,0x2f302e1f,0xaee92bb7,0xafbcad00,0xadfe2d27,0xaf6e9cb6,0x2eb5ac32,0x2eb5a515,0x2dbaad72,
0x2aaaaf5a,0x2ed0ae99,0x2cb0ae99,0xaf802d96,0xab5e2f30,0xafaf244e,0xad002e5e,0x2f1a1fd9,0x2c07af02,0x2b052d27,0x2d4dae1f,0xa814ae3f,
0xac5d2ed0,0x29f1afff,0xad962ddc,0xac5d2fe6,0x28752f80,0xa8d52fe6,0xa8d52fc9,0x2e3faf46,0xa44eafd4,0x2f91adba,0x2b05af6e,0xafbc26a1,
0x96482ffc,0xae99a44e,0xac872ee9,0x29f12d4d,0x2515aff8,0x1cb62f02,0x2d72ae3f,0x2c32aff8,0xaeb5ab05,0xaa4eacd8,0x9648afed,0xac5d2ffc,
0x2d722d27,0xacb02ff4,0xa7652ff4,0x2fffab5e,0xabb7ae7c,0x2ff8aaaa,0x2b5eaf80,0xabb7ac32,0x28142f6e,0xab05ac87,0xad4d2e99,0xac073000,
0x2feda8d5,0x2f30a30e,0x29342f02,0x2814afa0,0xafd49cb6,0x1648aed0,0x1648afe6,0xafdd2d72,0x2ed029f1,0xaf462eb5,0xa9932fdd,0x2cb029f1,
0xad00ad4d,0x2e1f244e,0x2d27aee9,0x2bb7affc,0xad4d2f02,0xafbc2e1f,0xacd8ad27,0x1fd92e3f,0x2f5aacb0,0x2c872993,0x26a12f46,0x2f5aaed0,
0xafff25db,0x2cb0b000,0x2765b000,0xad72a6a1,0x2f1a2814,0xafaf2934,0xad002f30,0xab5e2fed,0x1648afbc,0x2c87affc,0x2e992934,0xa9f1ac07,
0xac322faf,0xaf8028d5,0xaaaaae1f,0xae7c2faf,0x2f1aad72,0xa30e2ed0,0xa30e2fe6,0x2e1f1cb6,0xaffc26a1,0x2fedadba,0x2cd8af6e,0x2b05afd4,
0x2d272c32,0x230e2d72,0xafaf1cb6,0x2d272515,0x9fd9af6e,0x2fbcae99,0x2cd82c87,0x2d4db000,0xac5d2fbc,0xaa4eab05,0x9648af91,0xaeb5244e,
0x2f80ad00,0xaed02fa0,0xacb02fa0,0xaaaa2faf,0xafe626a1,0xaddc1648,0x2fffaa4e,0xaed026a1,0x2d002c07,0xad272ffc,0xae1fa934,0xabb72fbc,
0x1fd9afa0,0x2e5ea30e,0x244e2f02,0x2f30a8d5,0xadba2f46,0x2c87afe6,0x2c87afc9,0x2a4eaf80,0x2fffad96,0x2e7cac5d,0x2fc9ac5d,0xad7229f1,
0x217eadfe,0x2ff4afbc,0x2875aee9,0xaff82f30,0xafed2d00,0x2d4daf1a,0xaf912b5e,0xae5e2faf,0xa5db2e7c,0x9648a993,0xa9f12f46,0xa5db2c32,
0xae3f2fff,0xaff82fc9,0xaff82e7c,0x2f02ad72,0x2c0725db,0xadfe2f5a,0x9fd92d96,0x2fedafdd,0x2f6eaf91,0xa6a12c07,0x2fd4acd8,0x2dbaaf30,
0xa765ab5e,0x2aaaa30e,0x2993af02,0x2515ab5e,0x25dbadfe,0x2d96aee9,0x2f5aafbc,0xafdd2f30,0xaf462b5e,0x2765abb7,0xa515abb7,0xaf802ff8,
0xad002fc9,0xa8d51cb6,0xaff82ddc,0xad002e7c,0x2cd81648,0xadfe2c5d,0xa9342eb5,0xa44e2a4e,0x2c07217e,0x9fd92875,0xadfe2ff4,0x2fedaff8,
0x2fddaf46,0x29f1a515,0x29f12765,0x2eb5af80,0x2515ad96,0x2ddcac87,0x2fffaeb5,0x2c32ad96,0xaf022b05,0x2fa0aee9,0x28d5ae5e,0x230ea934,
0xaf912d00,0xacd82b5e,0x2c07af1a,0xaf302faf,0xad962fc9,0xaeb52ddc,0xac871cb6,0xad962e7c,0x299326a1,0xafc92f5a,0xafe62f5a,0xaaaa2c87,
0x2ff8ae5e,0xaff42ffc,0xa8752dfe,0xa17e2814,0x2f6eafed,0x2fd4af91,0xa6a12d4d,0x2dbaae5e,0x2515ad00,0x2fffaff8,0x2ddca8d5,0x2c32ad00,
0xae1f2993,0x2fafafe6,0x2fafafc9,0x28d5aaaa,0xaf912fdd,0x2ee9af5a,0x2814ad96,0x1fd9a5db,0xab5e2e7c,0xaf022f46,0xa30ea993,0xab5e2c32,
0x2b051648,0xae5e2eb5,0xaee92c5d,0xa9342a4e,0x2fddae5e,0xad962dfe,0xaf5a2ffc,0xa5db2814,0x2ddcafaf,0xacb02d27,0xa7652d27,0x9cb6230e,
0xa765a5db,0x2993a9f1,0x2aaa9648,0x2515a5db,0xaf022cd8,0x28d5a934,0x2fa0adfe,0x230ea44e,0xaf912ff8,0x2814a875,0x2ee9aff4,0x1fd9a17e,
0xaa4e2ddc,0x26a1a765,0x26a1acb0,0x16489cb6,0x9d7f9e49,0xaddcaeb3,0x12480000,0x22ad0000,0x9bdb9cb6,0xac2ead04,0x18b61648,0x290226ad,
0x98b69a49,0xa902aaaf,0x1bdb1a49,0x2c2e2aaf,0x92489648,0xa2ada6ad,0x1d7f1cb6,0x2ddc2d04,0xa420a4b7,0xae8daf7f,0x18b60000,0x23760000,
0xa1e4a312,0xacacad9c,0x1f121cb6,0x29992777,0x9f12a0b6,0xa999ab78,0x21e420b6,0x2cac2b78,0x98b69cb6,0xa376a777,0x24202312,0x2e8d2d9c,
0xa6e0a7db,0xaf3fb025,0x1bdb0000,0x24200000,0xa4e9a5e4,0xad2aae34,0x21e41fdb,0x2a312820,0xa1e4a3db,0xaa31ac21,0x24e923db,0x2d2a2c21,
0x9bdb9fdb,0xa420a820,0x26e025e4,0x2f3f2e34,0xa8d0a980,0xaff2b08c,0x1d7f0000,0x24840000,0xa6e0a820,0xada9aecd,0x2420217f,0x2ac82885,
0xa420a580,0xaac8ac86,0x26e02580,0x2da92c86,0x9d7fa17f,0xa484a885,0x28d02820,0x2ff22ecd,0xaa31ab13,0xb052b0f3,0x1f120000,0x24e90000,
0xa86ba94e,0xae28af65,0x254d2312,0x2b5f28e9,0xa54da712,0xab5faceb,0x286b2712,0x2e282ceb,0x9f12a312,0xa4e9a8e9,0x2a31294e,0x30522f65,
0xab91ac54,0xb0acb15a,0x20520000,0x254d0000,0xa967aa7c,0xaea7affe,0x267b2452,0x2bf6294e,0xa67ba852,0xabf6ad50,0x29672852,0x2ea72d50,
0xa052a452,0xa54da94e,0x2b912a7c,0x30ac2ffe,0xac79ad1e,0xb106b1c1,0x211b0000,0x25b20000,0xaa63abab,0xaf26b04c,0x27a9251b,0x2c4729b3,
0xa7a9a91c,0xac47adb6,0x2a63291c,0x2f262db6,0xa11ba51b,0xa5b2a9b3,0x2c792bab,0x3106304c,0xad2aade8,0xb160b229,0x21e40000,0x26170000,
0xab5fac6d,0xafa5b099,0x286b25e4,0x2c932a17,0xa86ba9e5,0xac93ae1b,0x2b5f29e5,0x2fa52e1b,0xa1e4a5e4,0xa617aa17,0x2d2a2c6d,0x31603099,
0xb1bbb292,0xb44fb4f6,0x267b0000,0x28d00000,0xb012b0e6,0xb216b357,0x2cde2a7c,0x2f3f2cd2,0xacdeae80,0xaf3fb0d9,0x30122e80,0x321630d9,
0xa67baa7c,0xa8d0acd2,0x31bb30e6,0x344f3357,0xb216b2fb,0xb47eb52d,0x26e00000,0x29020000,0xb052b133,0xb257b3a7,0x2d2a2ae1,0x2f8c2d04,
0xad2aaee6,0xaf8cb10c,0x30522ee6,0x3257310c,0xa6e0aae1,0xa902ad04,0x32163133,0x347e33a7,0xb271b364,0xb4aeb565,0x27440000,0x29350000,
0xb092b181,0xb298b3f7,0x2d762b46,0x2fd82d37,0xad76af4c,0xafd8b140,0x30922f4c,0x32983140,0xa744ab46,0xa935ad37,0x32713181,0x34ae33f7,
0xb2cdb3cf,0xb4deb59d,0x27a90000,0x29670000,0xb0d2b1ce,0xb2dab423,0x2dc22bab,0x30122d6a,0xadc2afb2,0xb012b174,0x30d22fb2,0x32da3174,
0xa7a9abab,0xa967ad6a,0x32cd31ce,0x34de3423,0xb329b41d,0xb50eb5d6,0x28070000,0x29990000,0xb113b21c,0xb31cb44c,0x2e0e2c08,0x30392d9c,
0xae0eb00c,0xb039b1a7,0x3113300c,0x331c31a7,0xa807ac08,0xa999ad9c,0x3329321c,0x350e344c,0xb386b453,0xb53fb60f,0x28390000,0x29cc0000,
0xb153b26b,0xb35eb474,0x2e5a2c3a,0x305f2dcf,0xae5ab03f,0xb05fb1db,0x3153303f,0x335e31db,0xa839ac3a,0xa9ccadcf,0x3386326b,0x353f3474,
0xb3e3b489,0xb570b649,0x286b0000,0x29fe0000,0xb194b2b9,0xb3a0b49d,0x2ea72c6d,0x30852e02,0xaea7b072,0xb085b20f,0x31943072,0x33a0320f,
0xa86bac6d,0xa9feae02,0x33e332b9,0x3570349d,0xb420b4bf,0xb5a1b683,0x289e0000,0x2a310000,0xb1d5b308,0xb3e3b4c6,0x2ef32c9f,0x30ac2e34,
0xaef3b0a5,0xb0acb243,0x31d530a5,0x33e33243,0xa89eac9f,0xaa31ae34,0x34203308,0x35a134c6,0xb5d2b6be,0xb76fb857,0x2a630000,0x2bf60000,
0xb413b4ef,0xb523b642,0x30d22e67,0x32092ffe,0xb0d2b278,0xb209b40f,0x34133278,0x3523340f,0xaa63ae67,0xabf6affe,0x35d234ef,0x376f3642,
0xb604b6fa,0xb7a5b878,0x2a950000,0x2c140000,0xb434b519,0xb546b66d,0x30f92e9a,0x32303019,0xb0f9b2ac,0xb230b42a,0x343432ac,0x3546342a,
0xaa95ae9a,0xac14b019,0x36043519,0x37a5366d,0xb637b736,0xb7dbb899,0x2ac80000,0x2c2e0000,0xb456b542,0xb569b699,0x31202ecd,0x32573032,
0xb120b2e1,0xb257b445,0x345632e1,0x35693445,0xaac8aecd,0xac2eb032,0x36373542,0x37db3699,0xb66ab773,0xb809b8bb,0x2afa0000,0x2c470000,
0xb478b56c,0xb58cb6c6,0x31462f00,0x327e304c,0xb146b315,0xb27eb460,0x34783315,0x358c3460,0xaafaaf00,0xac47b04c,0x366a356c,0x380936c6,
0xb69db7b0,0xb825b8dd,0x2b2d0000,0x2c600000,0xb49ab596,0xb5afb6f2,0x316d2f32,0x32a53065,0xb16db34a,0xb2a5b47b,0x349a334a,0x35af347b,
0xab2daf32,0xac60b065,0x369d3596,0x382536f2,0xb6d1b7ee,0xb841b8ff,0x2b5f0000,0x2c790000,0xb4bcb5c1,0xb5d2b71f,0x31942f65,0x32cd307f,
0xb194b37f,0xb2cdb496,0x34bc337f,0x35d23496,0xab5faf65,0xac79b07f,0x36d135c1,0x3841371f,0xb705b817,0xb85db923,0x2b910000,0x2c930000,
0xb4deb5eb,0xb5f6b74d,0x31bb2f98,0x32f43099,0xb1bbb3b4,0xb2f4b4b1,0x34de33b4,0x35f634b1,0xab91af98,0xac93b099,0x370535eb,0x385d374d,
0xb73ab837,0xb87ab946,0x2bc40000,0x2cac0000,0xb500b616,0xb61ab77a,0x31e22fcb,0x331c30b2,0xb1e2b3e9,0xb31cb4cd,0x350033e9,0x361a34cd,
0xabc4afcb,0xacacb0b2,0x373a3616,0x387a377a,0xb897b96b,0xb98dbaa6,0x2cc50000,0x2d900000,0xb63eb7a8,0xb767b895,0x334330cc,0x3442319a,
0xb343b4e8,0xb442b5c8,0x363e34e8,0x376735c8,0xacc5b0cc,0xad90b19a,0x389737a8,0x398d3895,0xb8b4b990,0xb9aebad1,0x2cde0000,0x2da90000,
0xb662b7d7,0xb78db8ae,0x336b30e6,0x345631b4,0xb36bb504,0xb456b5e4,0x36623504,0x378d35e4,0xacdeb0e6,0xada9b1b4,0x38b437d7,0x39ae38ae,
0xb8d2b9b5,0xb9cfbafd,0x2cf80000,0x2dc20000,0xb687b803,0xb7b4b8c7,0x339330ff,0x346a31ce,0xb393b51f,0xb46ab601,0x3687351f,0x37b43601,
0xacf8b0ff,0xadc2b1ce,0x38d23803,0x39cf38c7,0xb8f0b9dc,0xb9f1bb29,0x2d110000,0x2ddc0000,0xb6acb81b,0xb7dbb8e1,0x33bb3119,0x347e31e8,
0xb3bbb53b,0xb47eb61e,0x36ac353b,0x37db361e,0xad11b119,0xaddcb1e8,0x38f0381b,0x39f138e1,0xb90fba02,0xba14bb57,0x2d2a0000,0x2df50000,
0xb6d1b833,0xb801b8fb,0x33e33133,0x34933202,0xb3e3b557,0xb493b63a,0x36d13557,0x3801363a,0xad2ab133,0xadf5b202,0x390f3833,0x3a1438fb,
0xb92eba2a,0xba37bb86,0x2d440000,0x2e0e0000,0xb6f6b84b,0xb815b915,0x3405314d,0x34a7321c,0xb405b573,0xb4a7b657,0x36f63573,0x38153657,
0xad44b14d,0xae0eb21c,0x392e384b,0x3a373915,0xb94dba53,0xba5abbb6,0x2d5d0000,0x2e280000,0xb71bb863,0xb829b930,0x34193167,0x34bc3236,
0xb419b58f,0xb4bcb675,0x371b358f,0x38293675,0xad5db167,0xae28b236,0x394d3863,0x3a5a3930,0xb96dba7c,0xba7ebbe7,0x2d760000,0x2e410000,
0xb741b87c,0xb83db94b,0x342e3181,0x34d03250,0xb42eb5ab,0xb4d0b692,0x374135ab,0x383d3692,0xad76b181,0xae41b250,0x396d387c,0x3a7e394b,
0xa17fa248,0xb1cfb2a1,0x16480000,0x26ad0000,0x9fdba0b6,0xb029b0fd,0x1cb61a48,0x2d002aac,0x9cb69e48,0xad00aeaa,0x1fdb1e48,0x30292eaa,
0x96489a48,0xa6adaaac,0x217f20b6,0x31cf30fd,0xa81fa8b6,0xb27cb365,0x1cb60000,0x27760000,0xa5e4a711,0xb0a6b191,0x231120b6,0x2d972b75,
0xa311a4b6,0xad97af72,0x25e424b6,0x30a62f72,0x9cb6a0b6,0xa776ab75,0x281f2711,0x327c3191,0xaadeabd9,0xb328b414,0x1fdb0000,0x281f0000,
0xa8e8a9e3,0xb122b226,0x25e423db,0x2e2d2c1f,0xa5e4a7da,0xae2db01d,0x28e827da,0x3122301d,0x9fdba3db,0xa81fac1f,0x2ade29e3,0x33283226,
0xaccead7e,0xb3d3b475,0x217f0000,0x28840000,0xaadeac1f,0xb19eb2b9,0x281f257f,0x2ec32c83,0xa81fa97f,0xaec3b080,0x2ade297f,0x319e3080,
0xa17fa57f,0xa884ac83,0x2cce2c1f,0x33d332b9,0xae2daf0e,0xb43eb4d5,0x23110000,0x28e80000,0xac6aad4c,0xb219b34c,0x294d2711,0x2f592ce7,
0xa94dab11,0xaf59b0e4,0x2c6a2b11,0x321930e4,0xa311a711,0xa8e8ace7,0x2e2d2d4c,0x343e334c,0xaf8bb04e,0xb493b534,0x24520000,0x294d0000,
0xad65ae78,0xb294b3df,0x2a7a2852,0x2fef2d4c,0xaa7aac51,0xafefb147,0x2d652c51,0x32943147,0xa452a852,0xa94dad4c,0x2f8b2e78,0x349333df,
0xb074b115,0xb4e7b593,0x251b0000,0x29b10000,0xae5fafa4,0xb30fb438,0x2ba7291b,0x30422db0,0xaba7ad1a,0xb042b1aa,0x2e5f2d1a,0x330f31aa,
0xa51ba91b,0xa9b1adb0,0x30742fa4,0x34e73438,0xb122b1db,0xb53ab5f1,0x25e40000,0x2a160000,0xaf59b067,0xb389b481,0x2c6a29e3,0x308d2e14,
0xac6aade2,0xb08db20d,0x2f592de2,0x3389320d,0xa5e4a9e3,0xaa16ae14,0x31223067,0x353a3481,0xb58db64e,0xb805b887,0x2a7a0000,0x2cce0000,
0xb402b4c9,0xb5dfb6f9,0x30d72e78,0x332830cb,0xb0d7b26f,0xb328b4bd,0x3402326f,0x35df34bd,0xaa7aae78,0xacceb0cb,0x358d34c9,0x380536f9,
0xb5dfb6aa,0xb82ab8b0,0x2ade0000,0x2d000000,0xb43eb511,0xb61ab73d,0x31222edc,0x337130fd,0xb122b2d2,0xb371b4ed,0x343e32d2,0x361a34ed,
0xaadeaedc,0xad00b0fd,0x35df3511,0x382a373d,0xb631b705,0xb850b8d8,0x2b430000,0x2d330000,0xb47bb558,0xb654b780,0x316c2f40,0x33ba312e,
0xb16cb334,0xb3bab51d,0x347b3334,0x3654351d,0xab43af40,0xad33b12e,0x36313558,0x38503780,0xb682b75e,0xb874b900,0x2ba70000,0x2d650000,
0xb4b7b59f,0xb68db7c2,0x31b62fa4,0x34023160,0xb1b6b396,0xb402b54c,0x34b73396,0x368d354c,0xaba7afa4,0xad65b160,0x3682359f,0x387437c2,
0xb6d2b7b7,0xb899b927,0x2c060000,0x2d970000,0xb4f3b5e5,0xb6c6b802,0x32013004,0x34263191,0xb201b3f7,0xb426b57c,0x34f333f7,0x36c6357c,
0xac06b004,0xad97b191,0x36d235e5,0x38993802,0xb721b807,0xb8bcb94d,0x2c380000,0x2dc90000,0xb52fb62b,0xb6ffb822,0x324b3036,0x344b31c3,
0xb24bb42c,0xb44bb5ab,0x352f342c,0x36ff35ab,0xac38b036,0xadc9b1c3,0x3721362b,0x38bc3822,0xb76fb832,0xb8e0b972,0x2c6a0000,0x2dfb0000,
0xb56ab670,0xb737b842,0x32943067,0x346f31f4,0xb294b45d,0xb46fb5da,0x356a345d,0x373735da,0xac6ab067,0xadfbb1f4,0x376f3670,0x38e03842,
0xb7bdb85d,0xb902b996,0x2c9c0000,0x2e2d0000,0xb5a5b6b5,0xb76fb862,0x32de3099,0x34933226,0xb2deb48d,0xb493b608,0x35a5348d,0x376f3608,
0xac9cb099,0xae2db226,0x37bd36b5,0x39023862,0xb924b9ba,0xba1dbab5,0x2e5f0000,0x2fef0000,0xb7a6b881,0xb8a8b96d,0x34b73257,0x35d433df,
0xb4b7b637,0xb5d4b7a1,0x37a63637,0x38a837a1,0xae5fb257,0xafefb3df,0x39243881,0x3a1d396d,0xb946b9dc,0xba39bad0,0x2e910000,0x30100000,
0xb7ddb8a0,0xb8c1b989,0x34db3288,0x35f73408,0xb4dbb665,0xb5f7b7cd,0x37dd3665,0x38c137cd,0xae91b288,0xb010b408,0x394638a0,0x3a393989,
0xb966b9fe,0xba54bae9,0x2ec30000,0x30290000,0xb80ab8bf,0xb8dbb9a4,0x34ff32b9,0x361a3420,0xb4ffb693,0xb61ab7f9,0x380a3693,0x38db37f9,
0xaec3b2b9,0xb029b420,0x396638bf,0x3a5439a4,0xb986ba1f,0xba6fbb02,0x2ef50000,0x30420000,0xb825b8dd,0xb8f3b9be,0x352332ea,0x363c3438,
0xb523b6c1,0xb63cb812,0x382536c1,0x38f33812,0xaef5b2ea,0xb042b438,0x398638dd,0x3a6f39be,0xb9a6ba3f,0xba89bb1a,0x2f270000,0x305b0000,
0xb840b8fb,0xb90cb9d8,0x3546331b,0x365f3451,0xb546b6ee,0xb65fb828,0x384036ee,0x390c3828,0xaf27b31b,0xb05bb451,0x39a638fb,0x3a8939d8,
0xb9c5ba5e,0xbaa2bb30,0x2f590000,0x30740000,0xb85ab918,0xb924b9f2,0x356a334c,0x36823469,0xb56ab71b,0xb682b83d,0x385a371b,0x3924383d,
0xaf59b34c,0xb074b469,0x39c53918,0x3aa239f2,0xb9e3ba7c,0xbababb46,0x2f8b0000,0x308d0000,0xb874b935,0xb93cba0b,0x358d337d,0x36a43481,
0xb58db748,0xb6a4b852,0x38743748,0x393c3852,0xaf8bb37d,0xb08db481,0x39e33935,0x3aba3a0b,0xba00ba99,0xbad1bb5a,0x2fbd0000,0x30a60000,
0xb88eb951,0xb954ba23,0x35b133ae,0x36c63499,0xb5b1b775,0xb6c6b867,0x388e3775,0x39543867,0xafbdb3ae,0xb0a6b499,0x3a003951,0x3ad13a23,
0xbae8bb6e,0xbb7fbbdd,0x30be0000,0x31850000,0xb96bba3b,0xba19bae6,0x36e834b1,0x37f33570,0xb6e8b87c,0xb7f3b91d,0x396b387c,0x3a19391d,
0xb0beb4b1,0xb185b570,0x3ae83a3b,0x3b7f3ae6,0xbafebb80,0xbb8ebbe6,0x30d70000,0x319e0000,0xb982ba52,0xba2dbaf9,0x370a34c9,0x380a3587,
0xb70ab891,0xb80ab930,0x39823891,0x3a2d3930,0xb0d7b4c9,0xb19eb587,0x3afe3a52,0x3b8e3af9,0xbb13bb91,0xbb9cbbed,0x30f00000,0x31b60000,
0xb999ba69,0xba41bb0b,0x372c34e1,0x381a359f,0xb72cb8a6,0xb81ab943,0x399938a6,0x3a413943,0xb0f0b4e1,0xb1b6b59f,0x3b133a69,0x3b9c3b0b,
0xbb27bba0,0xbba9bbf4,0x31090000,0x31cf0000,0xb9afba7f,0xba54bb1d,0x374e34f9,0x382a35b6,0xb74eb8ba,0xb82ab956,0x39af38ba,0x3a543956,
0xb109b4f9,0xb1cfb5b6,0x3b273a7f,0x3ba93b1d,0xbb3abbaf,0xbbb5bbf8,0x31220000,0x31e80000,0xb9c5ba95,0xba67bb2e,0x376f3511,0x383a35ce,
0xb76fb8ce,0xb83ab969,0x39c538ce,0x3a673969,0xb122b511,0xb1e8b5ce,0x3b3a3a95,0x3bb53b2e,0xbb4cbbbc,0xbbc0bbfc,0x313b0000,0x32010000,
0xb9dabaaa,0xba7abb3e,0x37903529,0x384a35e5,0xb790b8e2,0xb84ab97b,0x39da38e2,0x3a7a397b,0xb13bb529,0xb201b5e5,0x3b4c3aaa,0x3bc03b3e,
0xbb5ebbc9,0xbbcbbbff,0x31530000,0x32190000,0xb9f0babf,0xba8cbb4e,0x37b23540,0x385a35fd,0xb7b2b8f6,0xb85ab98d,0x39f038f6,0x3a8c398d,
0xb153b540,0xb219b5fd,0x3b5e3abf,0x3bcb3b4e,0xbb6fbbd4,0xbbd4bc00,0x316c0000,0x32320000,0xba04bad3,0xba9ebb5d,0x37d23558,0x386a3614,
0xb7d2b909,0xb86ab99f,0x3a043909,0x3a9e399f,0xb16cb558,0xb232b614,0x3b6f3ad3,0x3bd43b5d,0x0,0x0,0x0,0x0,
0x2e1f0000,0x336431a8,0x33643400,0x2e1f31a8,0x31a80000,0x31a83400,0xb1a80000,0xb1a8b400,0x33640000,0xae1f31a8,0xae1fb400,0x336431a8,
0x34000000,0xb4000000,0x34000000,0xb4000000,0x33640000,0xae1fb1a8,0xae1f3400,0x3364b1a8,0x31a80000,0x31a8b400,0xb1a80000,0xb1a83400,
0x2e1f0000,0x3364b1a8,0x3364b400,0x2e1fb1a8,0x0,0x0,0x0,0x0,0xae1f0000,0xb36431a8,0xb3643400,0xae1f31a8,
0xb1a80000,0xb1a83400,0x31a80000,0x31a8b400,0xb3640000,0x2e1f31a8,0x2e1fb400,0xb36431a8,0xb4000000,0x34000000,0xb4000000,0x34000000,
0xb3640000,0x2e1fb1a8,0x2e1f3400,0xb364b1a8,0xb1a80000,0xb1a8b400,0x31a80000,0x31a83400,0xae1f0000,0xb364b1a8,0xb364b400,0xae1fb1a8,
0x0,0x0,0x0,0x0,0xae1f0000,0xb364b1a8,0xb364b400,0xae1fb1a8,0x31a80000,0x31a83400,0xb1a80000,0xb1a8b400,
0xb3640000,0x2e1fb1a8,0x2e1f3400,0xb364b1a8,0x34000000,0xb4000000,0x34000000,0xb4000000,0xb3640000,0x2e1f31a8,0x2e1fb400,0xb36431a8,
0x31a80000,0x31a8b400,0xb1a80000,0xb1a83400,0xae1f0000,0xb36431a8,0xb3643400,0xae1f31a8,0x0,0x0,0x0,0x0,
0x2e1f0000,0x3364b1a8,0x3364b400,0x2e1fb1a8,0xb1a80000,0xb1a83400,0x31a80000,0x31a8b400,0x33640000,0xae1fb1a8,0xae1f3400,0x3364b1a8,
0xb4000000,0x34000000,0xb4000000,0x34000000,0x33640000,0xae1f31a8,0xae1fb400,0x336431a8,0xb1a80000,0xb1a8b400,0x31a80000,0x31a83400,
0x2e1f0000,0x336431a8,0x33643400,0x2e1f31a8,0x34003400,0x34003400,0x34003400,0x34003400,0x33643400,0x2e1f31a8,0xae1f0000,0xb364b1a8,
0x31a83400,0xb1a80000,0xb1a8b400,0x31a80000,0x2e1f3400,0xb364b1a8,0x33640000,0xae1f31a8,0x3400,0xb400,0x3400,0xb400,
0xae1f3400,0x3364b1a8,0xb3640000,0x2e1f31a8,0xb1a83400,0x31a80000,0x31a8b400,0xb1a80000,0xb3643400,0xae1f31a8,0x2e1f0000,0x3364b1a8,
0xb4003400,0xb4003400,0xb4003400,0xb4003400,0xb3643400,0xae1f31a8,0x2e1f0000,0x3364b1a8,0xb1a83400,0x31a80000,0x31a8b400,0xb1a80000,
0xae1f3400,0x3364b1a8,0xb3640000,0x2e1f31a8,0x3400,0xb400,0x3400,0xb400,0x2e1f3400,0xb364b1a8,0x33640000,0xae1f31a8,
0x31a83400,0xb1a80000,0xb1a8b400,0x31a80000,0x33643400,0x2e1f31a8,0xae1f0000,0xb364b1a8,0x34003400,0x34003400,0x34003400,0x34003400,
0xb364b400,0xae1fb1a8,0x2e1f0000,0x336431a8,0x31a83400,0xb1a80000,0xb1a8b400,0x31a80000,0xae1fb400,0x336431a8,0xb3640000,0x2e1fb1a8,
0x3400,0xb400,0x3400,0xb400,0x2e1fb400,0xb36431a8,0x33640000,0xae1fb1a8,0xb1a83400,0x31a80000,0x31a8b400,0xb1a80000,
0x3364b400,0x2e1fb1a8,0xae1f0000,0xb36431a8,0xb4003400,0xb4003400,0xb4003400,0xb4003400,0x3364b400,0x2e1fb1a8,0xae1f0000,0xb36431a8,
0xb1a83400,0x31a80000,0x31a8b400,0xb1a80000,0x2e1fb400,0xb36431a8,0x33640000,0xae1fb1a8,0x3400,0xb400,0x3400,0xb400,
0xae1fb400,0x336431a8,0xb3640000,0x2e1fb1a8,0x31a83400,0xb1a80000,0xb1a8b400,0x31a80000,0xb364b400,0xae1fb1a8,0x2e1f0000,0x336431a8,
0x0,0x0,0x0,0x0,0xae1f0000,0xb364b1a8,0xb364b400,0xae1fb1a8,0xb1a80000,0xb1a8b400,0x31a80000,0x31a83400,
0xb3640000,0x2e1fb1a8,0x2e1f3400,0xb364b1a8,0xb4000000,0x34000000,0xb4000000,0x34000000,0xb3640000,0x2e1f31a8,0x2e1fb400,0xb36431a8,
0xb1a80000,0xb1a83400,0x31a80000,0x31a8b400,0xae1f0000,0xb36431a8,0xb3643400,0xae1f31a8,0x0,0x0,0x0,0x0,
0x2e1f0000,0x3364b1a8,0x3364b400,0x2e1fb1a8,0x31a80000,0x31a8b400,0xb1a80000,0xb1a83400,0x33640000,0xae1fb1a8,0xae1f3400,0x3364b1a8,
0x34000000,0xb4000000,0x34000000,0xb4000000,0x33640000,0xae1f31a8,0xae1fb400,0x336431a8,0x31a80000,0x31a83400,0xb1a80000,0xb1a8b400,
0x2e1f0000,0x336431a8,0x33643400,0x2e1f31a8,0x0,0x0,0x0,0x0,0x2e1f0000,0x336431a8,0x33643400,0x2e1f31a8,
0xb1a80000,0xb1a8b400,0x31a80000,0x31a83400,0x33640000,0xae1f31a8,0xae1fb400,0x336431a8,0xb4000000,0x34000000,0xb4000000,0x34000000,
0x33640000,0xae1fb1a8,0xae1f3400,0x3364b1a8,0xb1a80000,0xb1a83400,0x31a80000,0x31a8b400,0x2e1f0000,0x3364b1a8,0x3364b400,0x2e1fb1a8,
0x0,0x0,0x0,0x0,0xae1f0000,0xb36431a8,0xb3643400,0xae1f31a8,0x31a80000,0x31a8b400,0xb1a80000,0xb1a83400,
0xb3640000,0x2e1f31a8,0x2e1fb400,0xb36431a8,0x34000000,0xb4000000,0x34000000,0xb4000000,0xb3640000,0x2e1fb1a8,0x2e1f3400,0xb364b1a8,
0x31a80000,0x31a83400,0xb1a80000,0xb1a8b400,0xae1f0000,0xb364b1a8,0xb364b400,0xae1fb1a8,
};

typedef CUresult (*EncodeFn)(CUtensorMap*, CUtensorMapDataType, cuuint32_t, void*, const cuuint64_t*, const cuuint64_t*,
                             const cuuint32_t*, const cuuint32_t*, CUtensorMapInterleave, CUtensorMapSwizzle,
                             CUtensorMapL2promotion, CUtensorMapFloatOOBfill);

}

extern "C" void kernel_launch(void* const* d_in, const int* in_sizes, int n_in, void* d_out, int out_size) {
    Params p;
    p.x = (const __nv_bfloat16*)d_in[0];
    p.lar = (const __nv_bfloat16*)d_in[1];
    p.aim = (const __nv_bfloat16*)d_in[2];
    p.cr = (const __nv_bfloat16*)d_in[3];
    p.ci = (const __nv_bfloat16*)d_in[4];
    p.logdt = (const __nv_bfloat16*)d_in[5];
    p.dskip = (const __nv_bfloat16*)d_in[6];
    p.wr = (const __nv_bfloat16*)d_in[8];
    p.out = (__nv_bfloat16*)d_out;
    cudaGetSymbolAddress((void**)&p.sc, g_scratch);
    cudaGetSymbolAddress((void**)&p.tab, g_tab);

    void* fn = nullptr;
    cudaDriverEntryPointQueryResult qr;
    cudaGetDriverEntryPoint("cuTensorMapEncodeTiled", &fn, cudaEnableDefault, &qr);
    EncodeFn enc = (EncodeFn)fn;
    CUtensorMap tm_x, tm_g, tm_d, tm_o;
    const cuuint32_t es[5] = {1, 1, 1, 1, 1};
    {
        const cuuint64_t gd[5] = {1024, 4, 128, 2, 2}, gs[4] = {4096, 32768, 2048, 16384};
        const cuuint32_t bx[5] = {16, 4, 64, 1, 1};
        enc(&tm_x, CU_TENSOR_MAP_DATA_TYPE_BFLOAT16, 5, d_in[0], gd, gs, bx, es, CU_TENSOR_MAP_INTERLEAVE_NONE,
            CU_TENSOR_MAP_SWIZZLE_32B, (CUtensorMapL2promotion)XPROMO, CU_TENSOR_MAP_FLOAT_OOB_FILL_NONE);
        const cuuint32_t bo[5] = {16, 4, 16, 1, 1};
        enc(&tm_o, CU_TENSOR_MAP_DATA_TYPE_BFLOAT16, 5, d_out, gd, gs, bo, es, CU_TENSOR_MAP_INTERLEAVE_NONE,
            CU_TENSOR_MAP_SWIZZLE_32B, CU_TENSOR_MAP_L2_PROMOTION_NONE, CU_TENSOR_MAP_FLOAT_OOB_FILL_NONE);
    }
    {
        char *wg = (char*)d_in[9], *wu = (char*)d_in[10];
        p.up_first = wu < wg;
        p.w2 = (const __nv_bfloat16*)(p.up_first ? wg : wu);
        p.wd = (const __nv_bfloat16*)d_in[11];
        const cuuint64_t gd[3] = {3584, 1024, 2}, gs[2] = {7168, (cuuint64_t)(p.up_first ? wg - wu : wu - wg)};
        const cuuint32_t bx[3] = {64, 32, 2};
        enc(&tm_g, CU_TENSOR_MAP_DATA_TYPE_BFLOAT16, 3, p.up_first ? wu : wg, gd, gs, bx, es, CU_TENSOR_MAP_INTERLEAVE_NONE,
            CU_TENSOR_MAP_SWIZZLE_128B, CU_TENSOR_MAP_L2_PROMOTION_NONE, CU_TENSOR_MAP_FLOAT_OOB_FILL_NONE);
    }
    {
        const cuuint64_t gd[3] = {1024, 3584, 1}, gs[2] = {2048, 2048 * 3584};
        const cuuint32_t bx[3] = {64, 64, 1};
        enc(&tm_d, CU_TENSOR_MAP_DATA_TYPE_BFLOAT16, 3, d_in[11], gd, gs, bx, es, CU_TENSOR_MAP_INTERLEAVE_NONE,
            CU_TENSOR_MAP_SWIZZLE_128B, CU_TENSOR_MAP_L2_PROMOTION_NONE, CU_TENSOR_MAP_FLOAT_OOB_FILL_NONE);
    }
    cudaFuncSetAttribute(fused_kernel, cudaFuncAttributeMaxDynamicSharedMemorySize, SM_TOTAL + 256);
    fused_kernel<<<128, NTHREADS, SM_TOTAL + 256>>>(p, tm_x, tm_g, tm_d, tm_o);
}
```

```cpp
#include <cuda_runtime.h>
#include <cuda.h>
#include <cuda_bf16.h>
#include <cuda_fp16.h>
#include <stdint.h>

#define TG(i)
#define TS(i)
#define TSL(i)

#define TSW 0
#define SDELAY 2000
#define EDELAY 800
#define FILL 0xA20
#define IDEPTH 4

namespace {

constexpr int NTHREADS = 512;
constexpr int SPIN_LIMIT = 1 << 16;

constexpr int SM_SLAB = 0;
constexpr int SM_RING = 65536;
constexpr int SUB     = 1088;
constexpr int SM_K    = SM_RING + 6 * 8192;
constexpr int SM_S    = SM_K + 32 * SUB;
constexpr int SM_U    = SM_S + 32 * SUB;
constexpr int SM_F2   = SM_U + 32 * SUB;
constexpr int SM_XSEL = SM_F2 + 1536;
constexpr int SM_PAIR = SM_XSEL + 4096;
constexpr int SM_H    = SM_PAIR + 2048;
constexpr int SM_KEYS = SM_H + 1024;
constexpr int SM_TOK  = SM_KEYS + 64;
constexpr int SM_FIX  = SM_TOK + 16;
constexpr int SM_XRAW = SM_FIX + 32;
constexpr int SM_SCL  = SM_XRAW + 32;
constexpr int SM_BAR  = SM_SCL + 16;
constexpr int SM_RED  = SM_XSEL;
constexpr int SM_TAB  = SM_RING + 3 * 8192;
constexpr int B_FULL = 0, B_ROW = 24, B_STG = 32, B_PEER = 34, B_SLAB = 36, B_TOK = 38, B_EFREE = 39, B_FIX = 40, B_PAIR = 41,
              B_TAB = 42, B_TFREE = 43, B_KFREE = 44, NBAR = 45;
constexpr int SM_TOTAL = SM_BAR + NBAR * 8;
static_assert(SM_TOTAL + 256 <= 232448, "smem");
__device__ __forceinline__ uint32_t chunk_off(int n) {
    return n < 4 ? SM_SLAB + 8192 + n * 16384 : SM_RING + (n - (n < 10 ? 4 : n < 20 ? 10 : 20)) * 8192;
}
constexpr int KP = 272;

struct Scratch {
    uint4 stats[1024];
    uint32_t part[128 * 56 * 16];
    uint32_t epoch;
};
__device__ Scratch g_scratch;

struct Params {
    const __nv_bfloat16 *lar, *aim, *cr, *ci, *logdt, *dskip;
    const __nv_bfloat16 *x, *wr;
    __nv_bfloat16* out;
    Scratch* sc;
    const uint4* tab;
    int up_first;
};

__device__ __forceinline__ uint4 ldg128(const void* p) {
    uint4 v; asm volatile("ld.global.nc.v4.u32 {%0,%1,%2,%3}, [%4];" : "=r"(v.x), "=r"(v.y), "=r"(v.z), "=r"(v.w) : "l"(p)); return v;
}
__device__ __forceinline__ uint4 ld_relaxed128(const void* p) {
    uint4 v;
    asm volatile("{ .reg .b128 t; ld.relaxed.gpu.global.b128 t, [%4]; mov.b128 {%0,%1,%2,%3}, t; }"
                 : "=r"(v.x), "=r"(v.y), "=r"(v.z), "=r"(v.w) : "l"(p) : "memory");
    return v;
}
__device__ __forceinline__ void st_relaxed128(void* p, uint4 v) {
    asm volatile("{ .reg .b128 t; mov.b128 t, {%1,%2,%3,%4}; st.relaxed.gpu.global.b128 [%0], t; }"
                 :: "l"(p), "r"(v.x), "r"(v.y), "r"(v.z), "r"(v.w) : "memory");
}
__device__ __forceinline__ void st_relaxed32(void* p, uint32_t v) {
    asm volatile("st.relaxed.gpu.global.u32 [%0], %1;" :: "l"(p), "r"(v) : "memory");
}
__device__ __forceinline__ uint32_t lds32(uint32_t a) { uint32_t v; asm volatile("ld.shared.u32 %0, [%1];" : "=r"(v) : "r"(a)); return v; }
__device__ __forceinline__ uint32_t lds16(uint32_t a) { uint32_t v; asm volatile("ld.shared.u16 %0, [%1];" : "=r"(v) : "r"(a)); return v; }
__device__ __forceinline__ uint2 lds64(uint32_t a) { uint2 v; asm volatile("ld.shared.v2.u32 {%0,%1}, [%2];" : "=r"(v.x), "=r"(v.y) : "r"(a)); return v; }
__device__ __forceinline__ uint4 lds128(uint32_t a) {
    uint4 v; asm volatile("ld.shared.v4.u32 {%0,%1,%2,%3}, [%4];" : "=r"(v.x), "=r"(v.y), "=r"(v.z), "=r"(v.w) : "r"(a)); return v;
}
__device__ __forceinline__ void sts16(uint32_t a, uint32_t v) { asm volatile("st.shared.u16 [%0], %1;" :: "r"(a), "h"((uint16_t)v) : "memory"); }
__device__ __forceinline__ void sts32(uint32_t a, uint32_t v) { asm volatile("st.shared.u32 [%0], %1;" :: "r"(a), "r"(v) : "memory"); }
__device__ __forceinline__ void sts64(uint32_t a, uint32_t x, uint32_t y) { asm volatile("st.shared.v2.u32 [%0], {%1,%2};" :: "r"(a), "r"(x), "r"(y) : "memory"); }
__device__ __forceinline__ void sts128(uint32_t a, uint32_t x, uint32_t y, uint32_t z, uint32_t w) {
    asm volatile("st.shared.v4.u32 [%0], {%1,%2,%3,%4};" :: "r"(a), "r"(x), "r"(y), "r"(z), "r"(w) : "memory");
}
__device__ __forceinline__ void ldsm4(uint32_t a, uint32_t& r0, uint32_t& r1, uint32_t& r2, uint32_t& r3) {
    asm volatile("ldmatrix.sync.aligned.m8n8.x4.shared.b16 {%0,%1,%2,%3}, [%4];" : "=r"(r0), "=r"(r1), "=r"(r2), "=r"(r3) : "r"(a));
}
__device__ __forceinline__ void mma_f16(float (&d)[4], uint32_t a0, uint32_t a1, uint32_t a2, uint32_t a3, uint32_t b0, uint32_t b1) {
    asm("mma.sync.aligned.m16n8k16.row.col.f32.f16.f16.f32 {%0,%1,%2,%3}, {%4,%5,%6,%7}, {%8,%9}, {%0,%1,%2,%3};"
        : "+f"(d[0]), "+f"(d[1]), "+f"(d[2]), "+f"(d[3]) : "r"(a0), "r"(a1), "r"(a2), "r"(a3), "r"(b0), "r"(b1));
}
__device__ __forceinline__ void mma_bf16(float (&d)[4], uint32_t a0, uint32_t a1, uint32_t a2, uint32_t a3, uint32_t b0, uint32_t b1) {
    asm("mma.sync.aligned.m16n8k16.row.col.f32.bf16.bf16.f32 {%0,%1,%2,%3}, {%4,%5,%6,%7}, {%8,%9}, {%0,%1,%2,%3};"
        : "+f"(d[0]), "+f"(d[1]), "+f"(d[2]), "+f"(d[3]) : "r"(a0), "r"(a1), "r"(a2), "r"(a3), "r"(b0), "r"(b1));
}
__device__ __forceinline__ uint32_t prmt(uint32_t a, uint32_t b, uint32_t s) { uint32_t d; asm("prmt.b32 %0, %1, %2, %3;" : "=r"(d) : "r"(a), "r"(b), "r"(s)); return d; }
__device__ __forceinline__ uint32_t pack_h(float lo, float hi) { uint32_t d; asm("cvt.rn.f16x2.f32 %0, %1, %2;" : "=r"(d) : "f"(hi), "f"(lo)); return d; }
__device__ __forceinline__ uint32_t pack_b(float lo, float hi) { uint32_t d; asm("cvt.rn.bf16x2.f32 %0, %1, %2;" : "=r"(d) : "f"(hi), "f"(lo)); return d; }
__device__ __forceinline__ float blo(uint32_t v) { return __uint_as_float(v << 16); }
__device__ __forceinline__ float bhi(uint32_t v) { return __uint_as_float(v & 0xFFFF0000u); }
__device__ __forceinline__ float rb(float v) { return blo(pack_b(v, v)); }
__device__ __forceinline__ uint32_t bsub2(uint32_t a, uint32_t b) { uint32_t d; asm("sub.rn.bf16x2 %0, %1, %2;" : "=r"(d) : "r"(a), "r"(b)); return d; }
__device__ __forceinline__ uint32_t bmul2(uint32_t a, uint32_t b) { uint32_t d; asm("mul.rn.bf16x2 %0, %1, %2;" : "=r"(d) : "r"(a), "r"(b)); return d; }
__device__ __forceinline__ uint32_t bfma2(uint32_t a, uint32_t b, uint32_t c) { uint32_t d; asm("fma.rn.bf16x2 %0, %1, %2, %3;" : "=r"(d) : "r"(a), "r"(b), "r"(c)); return d; }
__device__ __forceinline__ uint32_t dup_lo(uint32_t v) { uint32_t d; asm("{ .reg .b16 l, h; mov.b32 {l, h}, %1; mov.b32 %0, {l, l}; }" : "=r"(d) : "r"(v)); return d; }
__device__ __forceinline__ uint32_t dup_hi(uint32_t v) { uint32_t d; asm("{ .reg .b16 l, h; mov.b32 {l, h}, %1; mov.b32 %0, {h, h}; }" : "=r"(d) : "r"(v)); return d; }
__device__ __forceinline__ uint32_t norm2(uint32_t x, uint32_t m, uint32_t hi, uint32_t lo) {
    uint32_t a = bsub2(x, m);
    return bfma2(a, hi, bmul2(a, lo));
}
__device__ __forceinline__ float ex2(float v) { float d; asm("ex2.approx.ftz.f32 %0, %1;" : "=f"(d) : "f"(v)); return d; }
__device__ __forceinline__ float rcp(float v) { float d; asm("rcp.approx.ftz.f32 %0, %1;" : "=f"(d) : "f"(v)); return d; }
__device__ __forceinline__ float sigmoidf_(float v) { return rcp(1.0f + ex2(-1.4426950408889634f * v)); }
__device__ __forceinline__ float siluf_(float v) { return v * sigmoidf_(v); }

__device__ __forceinline__ void mbar_init(uint32_t a, int n) { asm volatile("mbarrier.init.shared::cta.b64 [%0], %1;" :: "r"(a), "r"(n) : "memory"); }
__device__ __forceinline__ void mbar_expect(uint32_t a, int tx) { asm volatile("mbarrier.arrive.expect_tx.shared::cta.b64 _, [%0], %1;" :: "r"(a), "r"(tx) : "memory"); }
__device__ __forceinline__ void mbar_arrive(uint32_t a) { asm volatile("mbarrier.arrive.shared::cta.b64 _, [%0];" :: "r"(a) : "memory"); }
__device__ __forceinline__ void mbar_wait(uint32_t a, int parity) {
    asm volatile("{ .reg .pred p;\n"
                 "W: mbarrier.try_wait.parity.shared::cta.b64 p, [%0], %1;\n"
                 "@!p bra.uni W; }" :: "r"(a), "r"(parity) : "memory");
}
__device__ __forceinline__ bool mbar_test(uint32_t a) {
    uint32_t d; asm volatile("{ .reg .pred p; mbarrier.test_wait.parity.shared::cta.b64 p, [%1], 0; selp.u32 %0, 1, 0, p; }" : "=r"(d) : "r"(a) : "memory"); return d;
}
__device__ __forceinline__ void mbar_arrive_peer(uint32_t a) { asm volatile("mbarrier.arrive.relaxed.cluster.shared::cluster.b64 _, [%0];" :: "r"(a) : "memory"); }
__device__ __forceinline__ uint32_t mapa(uint32_t a, uint32_t rank) { uint32_t d; asm("mapa.shared::cluster.u32 %0, %1, %2;" : "=r"(d) : "r"(a), "r"(rank)); return d; }
__device__ __forceinline__ void st_async2(uint32_t a, uint32_t x, uint32_t y, uint32_t bar) {
    asm volatile("st.async.weak.shared::cluster.mbarrier::complete_tx::bytes.v2.b32 [%0], {%1,%2}, [%3];" :: "r"(a), "r"(x), "r"(y), "r"(bar) : "memory");
}
__device__ __forceinline__ void st_async4(uint32_t a, uint32_t x, uint32_t y, uint32_t z, uint32_t w, uint32_t bar) {
    asm volatile("st.async.weak.shared::cluster.mbarrier::complete_tx::bytes.v4.b32 [%0], {%1,%2,%3,%4}, [%5];"
                 :: "r"(a), "r"(x), "r"(y), "r"(z), "r"(w), "r"(bar) : "memory");
}
__device__ __forceinline__ void stsm4(uint32_t a, uint32_t r0, uint32_t r1, uint32_t r2, uint32_t r3) {
    asm volatile("stmatrix.sync.aligned.m8n8.x4.shared.b16 [%0], {%1,%2,%3,%4};" :: "r"(a), "r"(r0), "r"(r1), "r"(r2), "r"(r3) : "memory");
}
__device__ __forceinline__ void proxy_fence() { asm volatile("fence.proxy.async.shared::cta;" ::: "memory"); }
__device__ __forceinline__ void bar_sync(int id, int n) { asm volatile("bar.sync %0, %1;" :: "r"(id), "r"(n) : "memory"); }
__device__ __forceinline__ void bar_arrive(int id, int n) { asm volatile("bar.arrive %0, %1;" :: "r"(id), "r"(n) : "memory"); }
__device__ __forceinline__ void cluster_arrive() { asm volatile("barrier.cluster.arrive.relaxed.aligned;" ::: "memory"); }
__device__ __forceinline__ void cluster_wait() { asm volatile("barrier.cluster.wait.aligned;" ::: "memory"); }
__device__ __forceinline__ void tma3d(uint32_t dst, const CUtensorMap* tm, int c0, int c1, uint32_t bar, uint64_t pol) {
    asm volatile("cp.async.bulk.tensor.3d.shared::cluster.global.mbarrier::complete_tx::bytes.L2::cache_hint [%0], [%1, {%3, %4, %6}], [%2], %5;"
                 :: "r"(dst), "l"(tm), "r"(bar), "r"(c0), "r"(c1), "l"(pol), "r"(0) : "memory");
}
__device__ __forceinline__ bool elect() {
    uint32_t p; asm volatile("{ .reg .pred p; elect.sync _|p, 0xFFFFFFFF; selp.u32 %0, 1, 0, p; }" : "=r"(p)); return p;
}

struct cf { float r, i; };
__device__ __forceinline__ cf cmul(cf a, cf b) { return {a.r * b.r - a.i * b.i, a.r * b.i + a.i * b.r}; }
__device__ __forceinline__ cf csq(cf a) { return {a.r * a.r - a.i * a.i, (a.r + a.r) * a.i}; }
__device__ __forceinline__ cf cexp_(float a2, float b) { float m = ex2(a2); return {m * __cosf(b), m * __sinf(b)}; }
struct hc { uint32_t r, i; };
__device__ __forceinline__ hc pk(cf a, cf b) { return {pack_h(a.r, b.r), pack_h(a.i, b.i)}; }
__device__ __forceinline__ hc hmulc(hc a, hc b) {
    const __half2 ar = *reinterpret_cast<__half2*>(&a.r), ai = *reinterpret_cast<__half2*>(&a.i);
    const __half2 br = *reinterpret_cast<__half2*>(&b.r), bi = *reinterpret_cast<__half2*>(&b.i);
    const __half2 r = __hfma2(ar, br, __hneg2(__hmul2_rn(ai, bi))), i = __hfma2(ar, bi, __hmul2_rn(ai, br));
    return {*reinterpret_cast<const uint32_t*>(&r), *reinterpret_cast<const uint32_t*>(&i)};
}
__device__ __forceinline__ void sth(uint32_t a, hc v) { sts32(a, v.r); sts32(a + 128, v.i); }
__device__ __forceinline__ uint32_t cpy(uint32_t v, uint32_t z) { uint32_t d; asm("xor.b32 %0, %1, %2;" : "=r"(d) : "r"(v), "r"(z)); return d; }
__device__ __forceinline__ void sched_fence() { asm volatile("pmevent 0;" ::: "memory"); }
__device__ __forceinline__ float tanh_(float v) { float d; asm("tanh.approx.f32 %0, %1;" : "=f"(d) : "f"(v)); return d; }
__device__ __forceinline__ float silu2(float h) {
    return h * rcp(fmaf(ex2(-2.8853900817779268f * h), 0.5f, 0.5f));
}
__device__ __forceinline__ uint32_t hfma2_(uint32_t a, uint32_t b, uint32_t c) { uint32_t d; asm("fma.rn.f16x2 %0, %1, %2, %3;" : "=r"(d) : "r"(a), "r"(b), "r"(c)); return d; }
__device__ __forceinline__ uint32_t hfms2_(uint32_t a, uint32_t b, uint32_t c) {
    uint32_t d; asm("{ .reg .b32 t; neg.f16x2 t, %1; fma.rn.f16x2 %0, t, %2, %3; }" : "=r"(d) : "r"(a), "r"(b), "r"(c)); return d;
}

__device__ __forceinline__ uint64_t bdesc(uint32_t addr, uint32_t sbo) {
    return (uint64_t)((addr & 0x3FFFFu) >> 4) | ((uint64_t)(128 >> 4) << 16) | ((uint64_t)(sbo >> 4) << 32);
}
__device__ __forceinline__ void wg_h(uint32_t (&d)[16], const uint32_t* a, const uint32_t* b, uint64_t d0, uint64_t d1, uint64_t d2, uint64_t d3) {
    asm volatile(
        "wgmma.mma_async.sync.aligned.m64n64k16.f16.f16.f16 {%0,%1,%2,%3,%4,%5,%6,%7,%8,%9,%10,%11,%12,%13,%14,%15}, {%16,%17,%18,%19}, %32, 0, 1, 1, 1;\n"
        "wgmma.mma_async.sync.aligned.m64n64k16.f16.f16.f16 {%0,%1,%2,%3,%4,%5,%6,%7,%8,%9,%10,%11,%12,%13,%14,%15}, {%20,%21,%22,%23}, %33, 1, 1, 1, 1;\n"
        "wgmma.mma_async.sync.aligned.m64n64k16.f16.f16.f16 {%0,%1,%2,%3,%4,%5,%6,%7,%8,%9,%10,%11,%12,%13,%14,%15}, {%24,%25,%26,%27}, %34, 1, 1, 1, 1;\n"
        "wgmma.mma_async.sync.aligned.m64n64k16.f16.f16.f16 {%0,%1,%2,%3,%4,%5,%6,%7,%8,%9,%10,%11,%12,%13,%14,%15}, {%28,%29,%30,%31}, %35, 1, 1, 1, 1;\n"
        : "=r"(d[0]), "=r"(d[1]), "=r"(d[2]), "=r"(d[3]), "=r"(d[4]), "=r"(d[5]), "=r"(d[6]), "=r"(d[7]), "=r"(d[8]), "=r"(d[9]), "=r"(d[10]), "=r"(d[11]), "=r"(d[12]), "=r"(d[13]), "=r"(d[14]), "=r"(d[15])
        : "r"(a[0]), "r"(a[1]), "r"(a[2]), "r"(a[3]), "r"(a[4]), "r"(a[5]), "r"(a[6]), "r"(a[7]), "r"(b[0]), "r"(b[1]), "r"(b[2]), "r"(b[3]), "r"(b[4]), "r"(b[5]), "r"(b[6]), "r"(b[7]), "l"(d0), "l"(d1), "l"(d2), "l"(d3));
}
__device__ __forceinline__ void wg_f0(float (&d)[32], const uint32_t* a, const uint32_t* b, uint64_t d0, uint64_t d1, uint64_t d2, uint64_t d3) {
    asm volatile(
        "wgmma.mma_async.sync.aligned.m64n64k16.f32.f16.f16 {%0,%1,%2,%3,%4,%5,%6,%7,%8,%9,%10,%11,%12,%13,%14,%15,%16,%17,%18,%19,%20,%21,%22,%23,%24,%25,%26,%27,%28,%29,%30,%31}, {%32,%33,%34,%35}, %48, 0, 1, 1, 1;\n"
        "wgmma.mma_async.sync.aligned.m64n64k16.f32.f16.f16 {%0,%1,%2,%3,%4,%5,%6,%7,%8,%9,%10,%11,%12,%13,%14,%15,%16,%17,%18,%19,%20,%21,%22,%23,%24,%25,%26,%27,%28,%29,%30,%31}, {%36,%37,%38,%39}, %49, 1, 1, 1, 1;\n"
        "wgmma.mma_async.sync.aligned.m64n64k16.f32.f16.f16 {%0,%1,%2,%3,%4,%5,%6,%7,%8,%9,%10,%11,%12,%13,%14,%15,%16,%17,%18,%19,%20,%21,%22,%23,%24,%25,%26,%27,%28,%29,%30,%31}, {%40,%41,%42,%43}, %50, 1, 1, 1, 1;\n"
        "wgmma.mma_async.sync.aligned.m64n64k16.f32.f16.f16 {%0,%1,%2,%3,%4,%5,%6,%7,%8,%9,%10,%11,%12,%13,%14,%15,%16,%17,%18,%19,%20,%21,%22,%23,%24,%25,%26,%27,%28,%29,%30,%31}, {%44,%45,%46,%47}, %51, 1, 1, 1, 1;\n"
        : "=f"(d[0]), "=f"(d[1]), "=f"(d[2]), "=f"(d[3]), "=f"(d[4]), "=f"(d[5]), "=f"(d[6]), "=f"(d[7]), "=f"(d[8]), "=f"(d[9]), "=f"(d[10]), "=f"(d[11]), "=f"(d[12]), "=f"(d[13]), "=f"(d[14]), "=f"(d[15]), "=f"(d[16]), "=f"(d[17]), "=f"(d[18]), "=f"(d[19]), "=f"(d[20]), "=f"(d[21]), "=f"(d[22]), "=f"(d[23]), "=f"(d[24]), "=f"(d[25]), "=f"(d[26]), "=f"(d[27]), "=f"(d[28]), "=f"(d[29]), "=f"(d[30]), "=f"(d[31])
        : "r"(a[0]), "r"(a[1]), "r"(a[2]), "r"(a[3]), "r"(a[4]), "r"(a[5]), "r"(a[6]), "r"(a[7]), "r"(b[0]), "r"(b[1]), "r"(b[2]), "r"(b[3]), "r"(b[4]), "r"(b[5]), "r"(b[6]), "r"(b[7]), "l"(d0), "l"(d1), "l"(d2), "l"(d3));
}
__device__ __forceinline__ void wg_f1(float (&d)[32], const uint32_t* a, const uint32_t* b, uint64_t d0, uint64_t d1, uint64_t d2, uint64_t d3) {
    asm volatile(
        "wgmma.mma_async.sync.aligned.m64n64k16.f32.f16.f16 {%0,%1,%2,%3,%4,%5,%6,%7,%8,%9,%10,%11,%12,%13,%14,%15,%16,%17,%18,%19,%20,%21,%22,%23,%24,%25,%26,%27,%28,%29,%30,%31}, {%32,%33,%34,%35}, %48, 1, 1, 1, 1;\n"
        "wgmma.mma_async.sync.aligned.m64n64k16.f32.f16.f16 {%0,%1,%2,%3,%4,%5,%6,%7,%8,%9,%10,%11,%12,%13,%14,%15,%16,%17,%18,%19,%20,%21,%22,%23,%24,%25,%26,%27,%28,%29,%30,%31}, {%36,%37,%38,%39}, %49, 1, 1, 1, 1;\n"
        "wgmma.mma_async.sync.aligned.m64n64k16.f32.f16.f16 {%0,%1,%2,%3,%4,%5,%6,%7,%8,%9,%10,%11,%12,%13,%14,%15,%16,%17,%18,%19,%20,%21,%22,%23,%24,%25,%26,%27,%28,%29,%30,%31}, {%40,%41,%42,%43}, %50, 1, 1, 1, 1;\n"
        "wgmma.mma_async.sync.aligned.m64n64k16.f32.f16.f16 {%0,%1,%2,%3,%4,%5,%6,%7,%8,%9,%10,%11,%12,%13,%14,%15,%16,%17,%18,%19,%20,%21,%22,%23,%24,%25,%26,%27,%28,%29,%30,%31}, {%44,%45,%46,%47}, %51, 1, 1, 1, 1;\n"
        : "+f"(d[0]), "+f"(d[1]), "+f"(d[2]), "+f"(d[3]), "+f"(d[4]), "+f"(d[5]), "+f"(d[6]), "+f"(d[7]), "+f"(d[8]), "+f"(d[9]), "+f"(d[10]), "+f"(d[11]), "+f"(d[12]), "+f"(d[13]), "+f"(d[14]), "+f"(d[15]), "+f"(d[16]), "+f"(d[17]), "+f"(d[18]), "+f"(d[19]), "+f"(d[20]), "+f"(d[21]), "+f"(d[22]), "+f"(d[23]), "+f"(d[24]), "+f"(d[25]), "+f"(d[26]), "+f"(d[27]), "+f"(d[28]), "+f"(d[29]), "+f"(d[30]), "+f"(d[31])
        : "r"(a[0]), "r"(a[1]), "r"(a[2]), "r"(a[3]), "r"(a[4]), "r"(a[5]), "r"(a[6]), "r"(a[7]), "r"(b[0]), "r"(b[1]), "r"(b[2]), "r"(b[3]), "r"(b[4]), "r"(b[5]), "r"(b[6]), "r"(b[7]), "l"(d0), "l"(d1), "l"(d2), "l"(d3));
}
__device__ __forceinline__ void wg_s(uint32_t* d, const uint32_t* a, const uint32_t* b, uint64_t d0, uint64_t d1) {
    asm volatile(
        "wgmma.mma_async.sync.aligned.m64n32k16.f16.f16.f16 {%0,%1,%2,%3,%4,%5,%6,%7}, {%8,%9,%10,%11}, %16, 0, 1, 1, 1;\n"
        "wgmma.mma_async.sync.aligned.m64n32k16.f16.f16.f16 {%0,%1,%2,%3,%4,%5,%6,%7}, {%12,%13,%14,%15}, %17, 1, 1, 1, 1;\n"
        : "=r"(d[0]), "=r"(d[1]), "=r"(d[2]), "=r"(d[3]), "=r"(d[4]), "=r"(d[5]), "=r"(d[6]), "=r"(d[7])
        : "r"(a[0]), "r"(a[1]), "r"(a[2]), "r"(a[3]), "r"(b[0]), "r"(b[1]), "r"(b[2]), "r"(b[3]), "l"(d0), "l"(d1));
}
template <int ACC> __device__ __forceinline__ void wg_w(float (&d)[4], uint64_t da, uint64_t db) {
    asm volatile("wgmma.mma_async.sync.aligned.m64n8k16.f32.bf16.bf16 {%0,%1,%2,%3}, %4, %5, %6, 1, 1, 1, 0;"
                 : "+f"(d[0]), "+f"(d[1]), "+f"(d[2]), "+f"(d[3]) : "l"(da), "l"(db), "n"(ACC));
}
__device__ __forceinline__ void wg_w0(float (&d)[4], uint64_t da, uint64_t db) {
    asm volatile("wgmma.mma_async.sync.aligned.m64n8k16.f32.bf16.bf16 {%0,%1,%2,%3}, %4, %5, 0, 1, 1, 1, 0;"
                 : "=f"(d[0]), "=f"(d[1]), "=f"(d[2]), "=f"(d[3]) : "l"(da), "l"(db));
}
__device__ __forceinline__ void wg_fence() { asm volatile("wgmma.fence.sync.aligned;" ::: "memory"); }
__device__ __forceinline__ void wg_commit() { asm volatile("wgmma.commit_group.sync.aligned;" ::: "memory"); }
template <int N> __device__ __forceinline__ void wg_wait() { asm volatile("wgmma.wait_group.sync.aligned %0;" :: "n"(N) : "memory"); }
__device__ __forceinline__ void touch(uint32_t& r) { asm volatile("" : "+r"(r) :: "memory"); }
__device__ __forceinline__ void touch(float& r) { asm volatile("" : "+f"(r) :: "memory"); }
template <class T, int N> __device__ __forceinline__ void touch(T (&r)[N]) {
#pragma unroll
    for (int i = 0; i < N; i++) touch(r[i]);
}

__global__ void __cluster_dims__(2, 1, 1) __launch_bounds__(NTHREADS, 1)
fused_kernel(const Params p, const __grid_constant__ CUtensorMap tm_x, const __grid_constant__ CUtensorMap tm_g,
             const __grid_constant__ CUtensorMap tm_d, const __grid_constant__ CUtensorMap tm_o)
{
    extern __shared__ __align__(1024) uint8_t smem_raw[];
    const uint32_t sm = (uint32_t)__cvta_generic_to_shared(smem_raw);
    const uint32_t bars = sm + SM_BAR;
    const int tid = threadIdx.x, lane = tid & 31;
    const int g = lane >> 2, q = lane & 3;
    const int c = blockIdx.x, rank = c & 1, G = c >> 1;

    if (tid < 256) {
        uint2 lar4, aim4, cr4, ci4;
        uint32_t ldt_raw, dsk_raw;
        {
            const uint32_t i = c * 256 + tid;
            asm volatile("ld.global.nc.v2.u32 {%0,%1}, [%10]; ld.global.nc.v2.u32 {%2,%3}, [%11]; ld.global.nc.u16 %8, [%14];\n"
                         "ld.global.nc.v2.u32 {%4,%5}, [%12]; ld.global.nc.v2.u32 {%6,%7}, [%13]; ld.global.nc.u16 %9, [%15];"
                         : "=r"(lar4.x), "=r"(lar4.y), "=r"(aim4.x), "=r"(aim4.y), "=r"(cr4.x), "=r"(cr4.y), "=r"(ci4.x), "=r"(ci4.y), "=r"(ldt_raw), "=r"(dsk_raw)
                         : "l"(p.lar + i * 4), "l"(p.aim + i * 4), "l"(p.cr + i * 4), "l"(p.ci + i * 4), "l"(p.logdt + (i >> 5)), "l"(p.dskip + (i >> 5)));
        }
        cluster_arrive();
        sched_fence();
        const int warp = __shfl_sync(0xFFFFFFFFu, tid >> 5, 0);
        const float logdt = blo(ldt_raw), dsk = blo(dsk_raw);
        asm volatile("setmaxnreg.inc.sync.aligned.u32 168;");
        const int wgi = warp >> 2, w = warp & 3;
        const uint32_t wb = sm + SM_K + (w < 2 ? 16 * w + 8 * wgi : 16 + 16 * wgi + 8 * w) * SUB;
        sth(wb + lane * 4, hc{0x3C003C00u, 0u});

        const float dt = rb(expf(logdt));
        float outscale, cs, dn;
        {
            uint32_t m0 = __vmaxu2(__vmaxu2(cr4.x & 0x7FFF7FFFu, cr4.y & 0x7FFF7FFFu), __vmaxu2(ci4.x & 0x7FFF7FFFu, ci4.y & 0x7FFF7FFFu));
            uint32_t m1 = max(m0 & 0xFFFFu, m0 >> 16);
            float cmax = blo(__reduce_max_sync(0xFFFFFFFFu, m1));
            const float sc = fminf(fmaxf(fmaxf(2.0f * dt * cmax, fabsf(dsk) * (1.0f / 1024.0f)), 1e-30f), 1e30f);
            outscale = __uint_as_float(__float_as_uint(sc) & 0x7F800000u);
            const float inv = __uint_as_float(0x7F000000u - __float_as_uint(outscale));
            cs = 2.0f * dt * inv;
            dn = dsk * inv;
        }
        if (warp == TSW) TSL(39);
        uint32_t fc[16], fs[16], ta[4], tb[4];
        float kacc[2][3][4];
#pragma unroll
        for (int i = 0; i < 2; i++)
#pragma unroll
            for (int j = 0; j < 3; j++) kacc[i][j][0] = kacc[i][j][1] = kacc[i][j][2] = kacc[i][j][3] = 0.f;
        if (lane == 0) kacc[0][0][0] = dn;
        {
            const uint32_t st = wb + lane * 4;
            const uint32_t zk = lds32(wb + 128);
            const uint32_t la = wb + ((lane & 8) ? 29 : (lane & 7)) * KP + (lane >> 4) * 128;
            const uint32_t lo = wb + ((lane >> 3) & 1) * 128 + (lane >> 4) * 16;
            const uint32_t lb = lo + (8 + (lane & 7)) * KP, lb2 = lo + (24 + min(lane & 7, 4)) * KP, lm = lo + 30 * KP;
#pragma unroll 1
            for (int s = 0; s < 2; s++) {
                const uint32_t wl = s ? lar4.y : lar4.x, wa = s ? aim4.y : aim4.x, wr_ = s ? cr4.y : cr4.x, wi = s ? ci4.y : ci4.x;
                const uint32_t ea = pack_b(ex2(blo(wl) * 1.4426950408889634f), ex2(bhi(wl) * 1.4426950408889634f));
                const float a2[2] = {-(blo(ea) * dt) * 1.4426950408889634f, -(bhi(ea) * dt) * 1.4426950408889634f};
                const float b[2] = {blo(wa) * dt, bhi(wa) * dt};
                {
                    cf z8[2], z16[2], z32[2], z64[2], z128[2];
#pragma unroll
                    for (int e = 0; e < 2; e++) {
                        z8[e] = cexp_(a2[e] * 8.f, b[e] * 8.f);
                        z16[e] = csq(z8[e]); z32[e] = csq(z16[e]); z64[e] = csq(z32[e]); z128[e] = csq(z64[e]);
                    }
                    const hc r1 = pk(z8[0], z8[1]), r2 = pk(z16[0], z16[1]), r3 = hmulc(r1, r2), r4 = pk(z32[0], z32[1]);
                    sth(st + 1 * KP, r1); sth(st + 2 * KP, r2); sth(st + 3 * KP, r3); sth(st + 4 * KP, r4);
                    sth(st + 5 * KP, hmulc(r1, r4)); sth(st + 6 * KP, hmulc(r2, r4)); sth(st + 7 * KP, hmulc(r3, r4));
                    sth(st + 29 * KP, pk(z64[0], z64[1])); sth(st + 30 * KP, pk(z128[0], z128[1]));
                }
                {
                    cf C[2], z2[2], z4[2], v2[2], v4[2], c1[2], d1[2];
#pragma unroll
                    for (int e = 0; e < 2; e++) {
                        C[e] = {(e ? bhi(wr_) : blo(wr_)) * cs, (e ? bhi(wi) : blo(wi)) * -cs};
                        const cf z = cexp_(a2[e], -b[e]);
                        const cf v = cexp_(a2[e] * 256.f, b[e] * -256.f);
                        z2[e] = csq(z); z4[e] = csq(z2[e]); v2[e] = csq(v); v4[e] = csq(v2[e]);
                        c1[e] = cmul(C[e], z); d1[e] = cmul(C[e], v);
                    }
                    const hc l0 = pk(C[0], C[1]), l1 = pk(c1[0], c1[1]), e1 = pk(d1[0], d1[1]);
                    const hc h = pk(z2[0], z2[1]), f = pk(z4[0], z4[1]), w = pk(v2[0], v2[1]), y = pk(v4[0], v4[1]);
                    const hc l2 = hmulc(l0, h), l3 = hmulc(l1, h), e2 = hmulc(l0, w), e3 = hmulc(e1, w), e4 = hmulc(l0, y), g2 = hmulc(e1, h);
                    sth(st + 8 * KP, l0); sth(st + 9 * KP, l1); sth(st + 10 * KP, l2); sth(st + 11 * KP, l3);
                    sth(st + 12 * KP, hmulc(l0, f)); sth(st + 13 * KP, hmulc(l1, f)); sth(st + 14 * KP, hmulc(l2, f)); sth(st + 15 * KP, hmulc(l3, f));
                    sth(st + 16 * KP, e1);
                    sth(st + 17 * KP, g2);
                    sth(st + 18 * KP, hmulc(e1, f));
                    sth(st + 19 * KP, hmulc(g2, f));
                    sth(st + 20 * KP, e2);
                    sth(st + 21 * KP, hmulc(e2, f));
                    sth(st + 22 * KP, e3);
                    sth(st + 23 * KP, hmulc(e3, f));
                    sth(st + 24 * KP, e4);
                    sth(st + 25 * KP, hmulc(e1, y));
                    sth(st + 26 * KP, hmulc(e2, y));
                    sth(st + 27 * KP, hmulc(e3, y));
                    sth(st + 28 * KP, hmulc(e4, y));
                }
                __syncwarp();
                if (warp == TSW) TSL(s ? 34 : 27);
                if (s == 1 && lane == 0) mbar_arrive(bars + B_TFREE * 8 + (tb[3] & zk));
#pragma unroll
                for (int kp = 0; kp < 4; kp++) {
                    uint32_t bb[3][4], m2[4];
                    ldsm4(lm + kp * 32, m2[0], m2[1], m2[2], m2[3]);
                    ldsm4(lb + kp * 32, bb[0][0], bb[0][1], bb[0][2], bb[0][3]);
                    ldsm4(lb + 8 * KP + kp * 32, bb[1][0], bb[1][1], bb[1][2], bb[1][3]);
                    ldsm4(lb2 + kp * 32, bb[2][0], bb[2][1], bb[2][2], bb[2][3]);
#pragma unroll
                    for (int k2 = 0; k2 < 2; k2++) {
                        hc v0, m1;
                        ldsm4(la + kp * 32 + k2 * 16, v0.r, m1.r, v0.i, m1.i);
                        const hc mm = {m2[2 * k2], m2[2 * k2 + 1]};
                        const hc v1 = hmulc(v0, m1), v2 = hmulc(v0, mm), v3 = hmulc(v1, mm);
                        v0.r = cpy(v0.r, zk); v0.i = cpy(v0.i, zk);
#pragma unroll
                        for (int nt = 0; nt < 3; nt++) {
                            mma_f16(kacc[0][nt], v0.r, v1.r, v0.i, v1.i, bb[nt][2 * k2], bb[nt][2 * k2 + 1]);
                            mma_f16(kacc[1][nt], v2.r, v3.r, v2.i, v3.i, bb[nt][2 * k2], bb[nt][2 * k2 + 1]);
                        }
                    }
                }
                __syncwarp();
                if (warp == TSW) TSL(s ? 40 : 33);
                if (s == 0) {
                    cluster_wait();
                    mbar_wait(bars + B_TAB * 8, 0);
#pragma unroll
                    for (int i = 0; i < 10; i++) {
                        const uint4 u = lds128(sm + SM_TAB + i * 2048 + (tid & 127) * 16);
                        uint32_t* t = i < 4 ? fc + 4 * i : i < 8 ? fs + 4 * (i - 4) : i == 8 ? ta : tb;
                        t[0] = u.x; t[1] = u.y; t[2] = u.z; t[3] = u.w;
                    }
                }
            }
        }
        TSL(1);
        bar_sync(10 + wgi, 128);
        {
            const uint32_t tb_ = sm + SM_S + (16 * wgi + w) * SUB;
            const uint32_t seg = sm + SM_K + (2 * warp + (lane & 1)) * SUB + (lane >> 1) * 16;
            uint32_t v0[4];
#pragma unroll
            for (int m = 0; m < 4; m++) {
                constexpr float S = 1.0f / 512.0f;
                const float (&k0)[4] = kacc[m >> 1][0], (&k1)[4] = kacc[m >> 1][1], (&k2)[4] = kacc[m >> 1][2];
                const int R = 8 * m + g, o = 2 * (m & 1);
                v0[m] = pack_h(k0[o] * S, k0[o + 1] * S);
                sts32(tb_ + (q < 2 ? 4 * R + 2 * q : 64 * q + 2 * R) * 2, pack_h(k1[o] * S, k1[o + 1] * S));
                const uint32_t v2 = pack_h(k2[o] * S, k2[o + 1] * S);
                if (q < 2 || (m == 0 && lane == 2)) sts16(tb_ + (256 + 64 * q + R) * 2, v2);
                if (q < 2) sts16(tb_ + (288 + 64 * q + R) * 2, v2 >> 16);
            }
            stsm4(seg, v0[0], v0[1], v0[2], v0[3]);
            if (lane == 0) sts16(sm + SM_SCL + warp * 2, __float_as_uint(32768.0f * outscale) >> 16);
            __syncwarp();
            const uint2 l1 = lds64(tb_ + lane * 8);
            const uint32_t l1n = lds16(tb_ + lane * 8 + 8);
            uint32_t l2[2], l2n[2], l3[4], l3n[4];
#pragma unroll
            for (int i = 0; i < 2; i++) { l2[i] = lds32(tb_ + 256 + i * 128 + lane * 4); l2n[i] = lds16(tb_ + 260 + i * 128 + lane * 4); }
#pragma unroll
            for (int i = 0; i < 4; i++) { l3[i] = lds16(tb_ + 512 + i * 64 + lane * 2); l3n[i] = lds16(tb_ + 514 + i * 64 + lane * 2); }
            sts128(seg + 256, prmt(l1.x, 0, 0x1010), prmt(l1.x, l1.y, 0x5432), prmt(l1.y, 0, 0x1010), prmt(l1.y, l1n, 0x5432));
#pragma unroll
            for (int i = 0; i < 2; i++) sts128(seg + 512 + i * 256, prmt(l2[i], 0, 0x1010), l2[i], prmt(l2[i], 0, 0x3232), prmt(l2n[i], 0, 0x1010));
            const uint32_t s3 = (lane & 1) ? 0x5454 : 0x5410;
#pragma unroll
            for (int i = 0; i < 4; i++) {
                const uint32_t vv = prmt(l3[i], 0, 0x1010);
                sts128(seg + 16 * SUB + i * 256, vv, vv, prmt(l3[i], l3n[i], s3), prmt(l3n[i], 0, 0x1010));
            }
        }
        proxy_fence();
        TSL(2);
        bar_sync(10 + wgi, 128);
        const uint64_t dre = bdesc(sm + SM_F2 + 512, 256), dim = bdesc(sm + SM_F2, 256);
        uint32_t k0[32], k1[32];
#pragma unroll
        for (int b = 0; b < 2; b++) {
            const uint64_t d1 = bdesc(sm + SM_K + (16 * b + 8 * wgi) * SUB, SUB);
            uint32_t re[16], im[16];
            if (b == 0 && wgi == 1) bar_sync(5, 256);
            wg_fence();
            wg_h(re, fc, fc + 8, d1, d1 + 16, d1 + 32, d1 + 48);
            wg_h(im, fs, fs + 8, d1, d1 + 16, d1 + 32, d1 + 48);
            wg_commit();
            if (b == 0 && wgi == 0) bar_arrive(5, 256);
            wg_wait<0>();
            touch(re); touch(im);
            if (b == 1 && lane == 0) mbar_arrive(bars + B_KFREE * 8);
            uint32_t (&kk)[32] = b ? k1 : k0;
#pragma unroll
            for (int hh = 0; hh < 2; hh++) {
#pragma unroll
                for (int i = 8 * hh; i < 8 * hh + 8; i++) {
                    re[i] = hfma2_(ta[i & 3], im[i], re[i]); im[i] = hfms2_(tb[i & 3], re[i], im[i]); re[i] = hfma2_(ta[i & 3], im[i], re[i]);
                }
                wg_fence();
                wg_s(kk + 16 * hh, re + 8 * hh, im + 8 * hh, dre, dim);
                wg_s(kk + 16 * hh + 8, re + 8 * hh + 4, im + 8 * hh + 4, dre, dim);
                wg_commit();
            }
            wg_wait<0>();
            touch(kk);
        }
        if (warp == TSW) TSL(35);
        bar_sync(1 + wgi, 256);
        asm volatile("setmaxnreg.inc.sync.aligned.u32 200;");
        TSL(3);
        touch(k1);
        {
            const uint32_t sg = (g & 1) ? 0xBC00BC00u : 0x3C003C00u;
#pragma unroll
            for (int i = 0; i < 16; i++) {
                const int r = 8 * (i >> 2) + (i & 3);
                k1[r] = hfms2_(sg, k0[r + 4], k1[r]); k1[r + 4] = hfma2_(sg, k0[r], k1[r + 4]);
            }
            touch(k1);
        }
        const uint32_t rowo = (16 * w + (lane & 15)) * 16;
        const uint32_t xo = sm + SM_SLAB + (16 * w + g) * 128 + q * 32 + ((rank ^ (g & 1)) * 16) + wgi * 8;
        const uint32_t peer = mapa(sm, rank ^ 1), so = SM_U + 8 * wgi * SUB + w * 1024 + lane * 16;
#pragma unroll
        for (int b = 0; b < 2; b++) {
            uint32_t gt[4][4];
            uint32_t h[4][4];
            auto load_h = [&](int cc) {
                ldsm4(sm + SM_U + (16 * b + 8 * wgi + 4 * (cc >> 1) + 2 * (lane >> 4) + (cc & 1)) * SUB + rowo, h[cc][0], h[cc][1], h[cc][2], h[cc][3]);
            };
            auto gates = [&](int cc) {
#pragma unroll
                for (int i = 0; i < 2; i++) {
                    const float2 f0 = __half22float2(*reinterpret_cast<const __half2*>(&h[cc][i]));
                    const float2 f1 = __half22float2(*reinterpret_cast<const __half2*>(&h[cc][2 + i]));
                    gt[2 * i][cc] = pack_b(silu2(f0.x), silu2(f1.x)); gt[2 * i + 1][cc] = pack_b(silu2(f0.y), silu2(f1.y));
                    touch(gt[2 * i][cc]); touch(gt[2 * i + 1][cc]);
                }
            };
            const uint32_t zb = sm + SM_S + 16 * wgi * SUB;
            constexpr int zi = 8 * SUB;
            uint32_t re[16], im[16], su[2][16], z[2][16], y[2][16];
            auto twiddle = [&](int hh) {
#pragma unroll
                for (int i = 8 * hh; i < 8 * hh + 8; i++) {
                    re[i] = hfma2_(ta[i & 3], im[i], re[i]); im[i] = hfms2_(tb[i & 3], re[i], im[i]); re[i] = hfma2_(ta[i & 3], im[i], re[i]);
                    touch(re[i]); touch(im[i]);
                }
            };
            auto dft16 = [&](int hh) {
                wg_fence();
                wg_s(su[hh], re + 8 * hh, im + 8 * hh, dre, dim); wg_s(su[hh] + 8, re + 8 * hh + 4, im + 8 * hh + 4, dre, dim);
                wg_commit();
                sched_fence();
            };
            auto product = [&](int hh) {
#pragma unroll
                for (int i = 0; i < 8; i++) {
                    const int r = 8 * (i >> 2) + (i & 3), kr = 16 * hh + r;
                    const hc u = {su[hh][r], su[hh][r + 4]};
                    if (b == 0) {
                        const hc t = hmulc(u, hc{k0[kr], k0[kr + 4]}), pp = hmulc(u, hc{k1[kr], k1[kr + 4]});
                        z[hh][r] = t.r; z[hh][r + 4] = t.i; k1[kr] = pp.r; k1[kr + 4] = pp.i;
                        touch(k1[kr]); touch(k1[kr + 4]);
                    } else {
                        z[hh][r] = hfms2_(u.i, k0[kr + 4], hfma2_(u.r, k0[kr], k1[kr]));
                        z[hh][r + 4] = hfma2_(u.i, k0[kr], hfma2_(u.r, k0[kr + 4], k1[kr + 4]));
                    }
                }
                touch(z[hh]);
            };
            auto idft16 = [&](int hh) {
                wg_fence();
                wg_s(y[hh], z[hh] + 4, z[hh], dre, dim); wg_s(y[hh] + 8, z[hh] + 12, z[hh] + 8, dre, dim);
                wg_commit();
                sched_fence();
            };
            auto untwiddle = [&](int hh) {
#pragma unroll
                for (int i = 0; i < 2; i++) {
                    uint32_t* const yi = y[hh] + 8 * i, * const yr = yi + 4;
#pragma unroll
                    for (int n = 0; n < 4; n++) {
                        yr[n] = hfms2_(ta[n], yi[n], yr[n]); yi[n] = hfma2_(tb[n], yr[n], yi[n]); yr[n] = hfms2_(ta[n], yi[n], yr[n]);
                    }
                    const uint32_t a = zb + (4 * hh + 2 * i + (lane >> 4)) * SUB + rowo;
                    stsm4(a, yr[0], yr[1], yr[2], yr[3]);
                    stsm4(a + zi, yi[0], yi[1], yi[2], yi[3]);
                }
            };
            auto done = [&]() { sched_fence(); wg_wait<0>(); };
            {
                const uint64_t d1 = bdesc(sm + SM_U + (16 * b + 8 * wgi) * SUB, SUB);
                if (b) bar_sync(12 + wgi, 256);
                load_h(0);
                if (b == 0 && wgi == 1) bar_sync(9, 256);
                wg_fence();
                wg_h(re, fc, fc + 8, d1, d1 + 16, d1 + 32, d1 + 48);
                wg_h(im, fs, fs + 8, d1, d1 + 16, d1 + 32, d1 + 48);
                wg_commit();
                if (b == 0 && wgi == 0) bar_arrive(9, 256);
                sched_fence();
                gates(0);
                done();
                touch(re); touch(im);
            }
            twiddle(0); twiddle(1); load_h(1); dft16(0); dft16(1);
            load_h(2); wg_wait<1>(); touch(su[0]);
            product(0); gates(1); done(); touch(su[1]); idft16(0);
            load_h(3); product(1); gates(2); done(); touch(y[0]); idft16(1);
            untwiddle(0); gates(3); done(); touch(y[1]);
            untwiddle(1);
            proxy_fence();
            uint2 xv[2][4];
#pragma unroll
            for (int i = 0; i < 8; i++) xv[i >> 2][i & 3] = lds64(xo + b * 8192 + (i >> 2) * 32768 + (i & 1) * 16384 + ((i >> 1) & 1) * 1024);
            if (warp == TSW) TSL(36 + b);
            bar_sync(10 + wgi, 128);
            if (w == 0 && lane == 0) mbar_arrive_peer(peer + SM_BAR + (B_PEER + wgi) * 8);
            if (b == 0) TSL(4);
            float acc[32];
            const uint64_t d4 = bdesc(zb, SUB);
            wg_fence();
            wg_f0(acc, fc, fc + 8, d4, d4 + 16, d4 + 32, d4 + 48);
            wg_f1(acc, fs, fs + 8, d4 + zi / 16, d4 + zi / 16 + 16, d4 + zi / 16 + 32, d4 + zi / 16 + 48);
            wg_commit();
            if (b == 0) mbar_wait(bars + B_TOK * 8, 0);
            mbar_wait(bars + (B_PEER + wgi) * 8, b);
            const uint2 tk = lds64(sm + SM_TOK), sc = lds64(sm + SM_SCL + wgi * 8);
            wg_wait<0>();
            touch(acc);
            uint32_t s[2][4][2], o[2][4][2];
#pragma unroll
            for (int j = 0; j < 2; j++)
#pragma unroll
                for (int i = 0; i < 4; i++) {
                    s[j][i][0] = pack_b(acc[4 * j + i], acc[8 + 4 * j + i]); s[j][i][1] = pack_b(acc[16 + 4 * j + i], acc[24 + 4 * j + i]);
                    o[j][i][0] = bfma2(bmul2(s[j][i][0], gt[i][j]), sc.x, xv[j][i].x); o[j][i][1] = bfma2(bmul2(s[j][i][1], gt[i][2 + j]), sc.y, xv[j][i].y);
                }
            const uint32_t sb = SM_BAR + (B_STG + b) * 8;
#pragma unroll
            for (int e = 0; e < 2; e++)
                if (e == rank) {
#pragma unroll
                    for (int j = 0; j < 2; j++) {
                        st_async4(peer + so + 16 * b * SUB + j * 512, o[j][1 - e][0], o[j][1 - e][1], o[j][3 - e][0], o[j][3 - e][1], peer + sb);
                        sts128(sm + so + (16 * b + 4) * SUB + j * 512, o[j][e][0], o[j][e][1], o[j][2 + e][0], o[j][2 + e][1]);
                    }
                }
            __syncwarp();
            if (lane == 0) mbar_arrive(sm + sb);
            if (warp == TSW) TSL(5 + b);
#pragma unroll
            for (int k = 0; k < 2; k++) {
                const int t = k ? tk.y : tk.x;
                if ((t & ~0x89) == 1024 * b + 256 * w + 16 * g + 2 * q) {
                    uint32_t f[2];
#pragma unroll
                    for (int n = 0; n < 2; n++) {
                        const uint32_t a0 = (t & 1) ? s[0][1][n] : s[0][0][n], a1 = (t & 1) ? s[0][3][n] : s[0][2][n];
                        const uint32_t b0 = (t & 1) ? s[1][1][n] : s[1][0][n], b1 = (t & 1) ? s[1][3][n] : s[1][2][n];
                        f[n] = (t & 8) ? ((t & 128) ? b1 : b0) : ((t & 128) ? a1 : a0);
                    }
                    const uint32_t dst = mapa(sm, k);
                    st_async2(dst + SM_FIX + rank * 16 + wgi * 8, bmul2(f[0], sc.x), bmul2(f[1], sc.y), dst + SM_BAR + B_FIX * 8);
                }
            }
            __syncwarp();
        }
        TSL(7);
    } else {
    const int warp = __shfl_sync(0xFFFFFFFFu, tid >> 5, 0);
    auto load_slab = [&](int i) {
        asm volatile("cp.async.bulk.tensor.5d.shared::cluster.global.mbarrier::complete_tx::bytes.multicast::cluster"
                     " [%0], [%1, {%3, %4, %5, %6, %7}], [%2], %8;"
                     :: "r"(sm + SM_SLAB + rank * 32768 + (i & 1) * 16384 + (i >> 1) * 8192), "l"(&tm_x), "r"(bars + (B_SLAB + (i >> 1)) * 8),
                        "r"(G * 16), "r"(0), "r"(64 * (i >> 1)), "r"(i & 1), "r"(rank), "h"((uint16_t)3) : "memory");
    };
    if (warp < 12) {
        const int v = warp - 8;
        cluster_arrive();
        const uint32_t xs = sm + SM_U + v * 8192;
        if (elect()) {
#pragma unroll
            for (int r = 0; r < 2; r++) mbar_init(bars + (B_ROW + 2 * v + r) * 8, 1);
            asm volatile("fence.mbarrier_init.release.cluster;" ::: "memory");
#pragma unroll
            for (int e = 0; e < 2; e++) {
                if (e) { const int t0_ = clock(); while ((int)clock() - t0_ < EDELAY) __nanosleep(40); }
                mbar_expect(bars + (B_ROW + 2 * v + e) * 8, 4096);
#pragma unroll
                for (int r = 0; r < 2; r++)
                    asm volatile("cp.async.bulk.shared::cluster.global.mbarrier::complete_tx::bytes [%0], [%1], 2048, [%2];"
                                 :: "r"(xs + e * 4096 + r * 2048), "l"(p.x + (size_t)(32 * (c & 63) + 16 * (v >> 1) + 8 * (c >> 6) + 4 * (v & 1) + 2 * r + e) * 1024),
                                    "r"(bars + (B_ROW + 2 * v + e) * 8) : "memory");
            }
        }
        __syncwarp();
        uint4 w4[4];
#pragma unroll
        for (int k = 0; k < 4; k++) w4[k] = ldg128(reinterpret_cast<const uint4*>(p.wr) + 32 * k + lane);
        {
            constexpr uint32_t ONE = 0x3F803F80u;
            const uint32_t zr = p.up_first >> 1;
            uint4 w5[4];
#pragma unroll
            for (int k = 0; k < 4; k++) {
                w5[k].x = w4[k].x + zr; w5[k].y = w4[k].y + zr; w5[k].z = w4[k].z + zr; w5[k].w = w4[k].w + zr;
                w4[k].x = cpy(w4[k].x, zr); w4[k].y = cpy(w4[k].y, zr); w4[k].z = cpy(w4[k].z, zr); w4[k].w = cpy(w4[k].w, zr);
            }
            const bool od = g & 1;
#pragma unroll 1
            for (int r2 = 0; r2 < 2; r2++) {
                mbar_wait(bars + (B_ROW + 2 * v + r2) * 8, 0);
                TSL(r2 ? 43 : 0);
                float s1[2][4] = {}, q0[2][4] = {};
#pragma unroll
                for (int k = 0; k < 4; k++)
#pragma unroll
                    for (int r = 0; r < 2; r++) {
                        const uint4 x = lds128(xs + r2 * 4096 + r * 2048 + k * 512 + lane * 16);
                        const uint4& ww = r ? w5[k] : w4[k];
                        mma_bf16(q0[r], cpy(x.x, zr), ww.x, cpy(x.y, zr), ww.y, x.x, x.y);
                        mma_bf16(s1[r], x.x, x.y, x.z, x.w, ONE, ONE);
                        mma_bf16(q0[r], cpy(x.z, zr), ww.z, cpy(x.w, zr), ww.w, x.z, x.w);
                    }
#pragma unroll
                for (int r = 0; r < 2; r++)
                    if (q == (g >> 1))
                        sts128(sm + SM_RED + (4 * v + r2 + 2 * r) * 144 + g * 16, __float_as_uint(od ? q0[r][1] : q0[r][0]),
                               __float_as_uint(od ? q0[r][3] : q0[r][2]), __float_as_uint(s1[r][0]), __float_as_uint(s1[r][2]));
            }
            bar_arrive(7, 160);
        }
        TSL(8);
        bar_sync(6, 160);
        const uint32_t tag = lds32(sm + SM_TOK + 8);
        cluster_wait();
        {
            uint4 st[8] = {};
            const uint4* src = p.sc->stats + 64 * v + lane;
            const uint32_t tb = ((tag & 1) << 15) | ((tag >> 1) << 31);
#pragma unroll
            for (int i = 0; i < 8; i++) st[i].y = ~tb;
            int it = 0;
            bool ok;
            if (warp == 8) TSL(44);
            do {
                uint32_t bad = 0;
#pragma unroll
                for (int i = 0; i < 8; i++)
                    asm volatile("{ .reg .pred p; .reg .b128 t; setp.ne.u32 p, %5, 0; mov.b128 t, {%0,%1,%2,%3};\n"
                                 "@p ld.relaxed.gpu.global.b128 t, [%4]; mov.b128 {%0,%1,%2,%3}, t; }"
                                 : "+r"(st[i].x), "+r"(st[i].y), "+r"(st[i].z), "+r"(st[i].w)
                                 : "l"(src + (i >> 2) * 256 + ((i >> 1) & 1) * 512 + (i & 1) * 32), "r"((st[i].y ^ tb) & 0x80008000u) : "memory");
#pragma unroll
                for (int i = 0; i < 8; i++) bad |= st[i].y ^ tb;
                ok = __all_sync(0xFFFFFFFFu, (bad & 0x80008000u) == 0);
                if (warp == 8 && it == 0) TSL(45);
            } while (!ok && ++it < SPIN_LIMIT);
            TSL(11); TG(31);
            uint32_t h1[4], h2[4];
#pragma unroll
            for (int i = 0; i < 4; i++) { h1[i] = max(st[i].w, st[i + 4].w); h2[i] = min(st[i].w, st[i + 4].w); }
#pragma unroll
            for (int n = 2; n > 0; n >>= 1)
#pragma unroll
                for (int i = 0; i < n; i++) { h2[i] = __vimax3_u32(min(h1[i], h1[i + n]), h2[i], h2[i + n]); h1[i] = max(h1[i], h1[i + n]); }
            const uint32_t w1 = __reduce_max_sync(0xFFFFFFFFu, h1[0]);
            const uint32_t w2 = __reduce_max_sync(0xFFFFFFFFu, h1[0] == w1 ? h2[0] : h1[0]);
            if (lane == 0) sts64(sm + SM_KEYS + v * 8, w1, w2);
            bar_arrive(3, 192);
            asm volatile("setmaxnreg.dec.sync.aligned.u32 64;");
            const uint32_t xo = sm + SM_SLAB + (16 * v + g) * 128 + q * 32 + ((rank ^ (g & 1)) * 16);
            const uint32_t ua = sm + SM_U + 2 * (lane >> 3) * SUB + (16 * v + (lane & 7)) * 16;
#pragma unroll
            for (int b = 0; b < 2; b++) {
                if (b && v == 0) {
                    mbar_wait(bars + B_EFREE * 8, 0);
                    if (elect()) { load_slab(2); load_slab(3); }
                    __syncwarp();
                }
                mbar_wait(bars + (B_SLAB + b) * 8, 0);
                TSL(b ? 38 : 10);
#pragma unroll
                for (int i = 0; i < 4; i++) {
                    const uint4 e = lds128(xo + b * 8192 + (i >> 1) * 32768 + (i & 1) * 1024), d = lds128(xo + b * 8192 + (i >> 1) * 32768 + (i & 1) * 1024 + 16384);
                    const uint32_t m = st[4 * b + i].x, hi = bmul2(st[4 * b + i].y & 0x7FFF7FFFu, 0x3F003F00u), lo = bmul2(st[4 * b + i].z, 0x3F003F00u);
                    const uint32_t xe[4] = {e.x, e.y, e.z, e.w}, xd[4] = {d.x, d.y, d.z, d.w};
                    uint32_t o[8];
#pragma unroll
                    for (int n = 0; n < 4; n++) {
                        const uint32_t ne = norm2(xe[n], dup_lo(m), dup_lo(hi), dup_lo(lo)), nd = norm2(xd[n], dup_hi(m), dup_hi(hi), dup_hi(lo));
                        o[2 * n] = pack_h(blo(ne), blo(nd)); o[2 * n + 1] = pack_h(bhi(ne), bhi(nd));
                    }
                    stsm4(ua + (16 * b + (i >> 1)) * SUB + (i & 1) * 128, o[0], o[1], o[2], o[3]);
                    stsm4(ua + (16 * b + 8 + (i >> 1)) * SUB + (i & 1) * 128, o[4], o[5], o[6], o[7]);
                }
                proxy_fence();
                bar_arrive(b ? 12 : 1, 256); bar_arrive(b ? 13 : 2, 256);
                TSL(b ? 41 : 12);
            }
#pragma unroll 1
            for (int b = 0; b < 2; b++) {
                mbar_wait(bars + (B_STG + b) * 8, 0);
                const uint32_t src = sm + SM_U + 16 * b * SUB + v * 1024 + lane * 16, dst = xo + b * 8192 + rank * 16384;
                const uint2 tr = lds64(sm + SM_TOK);
#pragma unroll
                for (int i = 0; i < 4; i++) {
                    const uint4 r0 = lds128(src + (i & 1) * 4 * SUB + (i >> 1) * 512), r1 = lds128(src + (8 + (i & 1) * 4) * SUB + (i >> 1) * 512);
                    const uint32_t a = (dst ^ ((i & 1) ? 0 : 16)) + (i >> 1) * 32768;
                    sts128(a, r0.x, r0.y, r1.x, r1.y); sts128(a + 1024, r0.z, r0.w, r1.z, r1.w);
                }
                proxy_fence();
                __syncwarp();
#pragma unroll 1
                for (int j = 0; j < 2; j++) {
                    const uint32_t box = sm + SM_SLAB + j * 32768 + rank * 16384 + b * 8192 + v * 2048;
                    const int t0 = 1024 * b + 256 * v + 8 * j + rank;
                    if ((tr.x & 0x709) != t0 && (tr.y & 0x709) != t0) {
                        if (lane == 0) {
                            asm volatile("cp.async.bulk.tensor.5d.global.shared::cta.bulk_group [%0, {%2, %3, %4, %5, %6}], [%1];"
                                         :: "l"(&tm_o), "r"(box), "r"(G * 16), "r"(0), "r"(64 * b + 16 * v), "r"(rank), "r"(j) : "memory");
                            asm volatile("cp.async.bulk.commit_group;" ::: "memory");
                        }
                    } else {
#pragma unroll
                        for (int i = 0; i < 4; i++) {
                            const uint4 o = lds128(box + i * 512 + lane * 16);
                            const int t = t0 + 64 * i + 16 * (lane >> 3) + (lane & 6);
                            if (t != tr.x && t != tr.y)
                                *reinterpret_cast<uint4*>(p.out + (size_t)t * 1024 + G * 16 + ((lane ^ (lane >> 3)) & 1) * 8) = o;
                        }
                    }
                    __syncwarp();
                }
                TSL(b ? 23 : 22);
            }
            if (lane == 0) asm volatile("cp.async.bulk.wait_group.read 0;" ::: "memory");
            TSL(17); TG(30);
        }
    } else {
        const int v = warp - 12;
        if (lane == 0) {
            if (v == 1) {
                mbar_init(bars + B_TAB * 8, 1); mbar_init(bars + B_TFREE * 8, 8); mbar_init(bars + B_KFREE * 8, 8);
                mbar_expect(bars + B_TAB * 8, 20480 + 1536);
            } else if (v == 0) {
                mbar_init(bars + B_SLAB * 8, 1); mbar_init(bars + (B_SLAB + 1) * 8, 1); mbar_init(bars + B_TOK * 8, 2); mbar_init(bars + B_EFREE * 8, 2);
                mbar_expect(bars + B_SLAB * 8, 32768); mbar_expect(bars + (B_SLAB + 1) * 8, 32768);
            } else {
                mbar_init(bars + (B_STG + v - 2) * 8, 9); mbar_init(bars + (B_PEER + v - 2) * 8, 1); mbar_init(bars + (B_FIX + v - 2) * 8, 1);
                mbar_expect(bars + (B_STG + v - 2) * 8, 8192); mbar_expect(bars + (B_FIX + v - 2) * 8, v == 2 ? 32 : 2048);
            }
#pragma unroll
            for (int i = 0; i < 6; i++) mbar_init(bars + (B_FULL + 6 * v + i) * 8, 1);
            asm volatile("fence.mbarrier_init.release.cluster;" ::: "memory");
        }
        __syncwarp();
        cluster_arrive();
        asm volatile("setmaxnreg.dec.sync.aligned.u32 48;");
        uint64_t pol; asm volatile("createpolicy.fractional.L2::evict_first.b64 %0, 1.0;" : "=l"(pol));
        auto load_chunk = [&](int n) {
            const bool gu = n < 16;
            mbar_expect(bars + (B_FULL + n) * 8, 8192);
            tma3d(sm + chunk_off(n), gu ? &tm_g : &tm_d, gu ? G * 64 : rank * 512 + (n - 16) * 64, gu ? rank * 512 + n * 32 : G * 64, bars + (B_FULL + n) * 8, pol);
        };
        uint32_t* const my_part = p.sc->part + ((2 * (32 * rank + v) + (q & 1)) * 56 + G) * 16 + g + 8 * (q >> 1);
        if (G < 56) {
#pragma unroll
            for (int n = 0; n < 8; n++) st_relaxed32(my_part + n * 8 * 56 * 16, 0);
        }
        cluster_wait();
        const bool lead = elect();
        bool kpend = G < 56 && v == 1;
        auto load_k = [&]() { if (lead) { load_chunk(16); load_chunk(17); load_chunk(18); load_chunk(19); } kpend = false; TSL(21); };
        uint32_t key = 0;
        if (v == 0) {
            TSL(19);
            asm volatile("prefetch.tensormap [%0];" :: "l"(&tm_x) : "memory");
            asm volatile("prefetch.tensormap [%0];" :: "l"(&tm_g) : "memory");
            { const int t0_ = clock(); while ((int)clock() - t0_ < SDELAY) __nanosleep(40); }
            if (lead) {
                int n = 0;
#pragma unroll 1
                for (int i = 0; i < 3; i++) {
                    if (G < 56) {
#pragma unroll 1
                        for (; n < ((FILL >> (4 * i)) & 15); n++) {
                            if (n >= IDEPTH) mbar_wait(bars + (B_FULL + n - IDEPTH) * 8, 0);
                            if (n == 7) mbar_wait(bars + B_TFREE * 8, 0);
                            load_chunk(n);
                        }
                    }
                    if (i < 2) load_slab(i);
                }
            }
            __syncwarp();
            TSL(20);
        } else if (v == 1) {
            if (lead) {
                asm volatile("cp.async.bulk.shared::cluster.global.mbarrier::complete_tx::bytes [%0], [%1], 20480, [%2];"
                             :: "r"(sm + SM_TAB), "l"(p.tab), "r"(bars + B_TAB * 8) : "memory");
                asm volatile("cp.async.bulk.shared::cluster.global.mbarrier::complete_tx::bytes [%0], [%1], 1536, [%2];"
                             :: "r"(sm + SM_F2), "l"(p.tab + 1280), "r"(bars + B_TAB * 8) : "memory");
                asm volatile("prefetch.tensormap [%0];" :: "l"(&tm_d) : "memory");
                asm volatile("prefetch.tensormap [%0];" :: "l"(&tm_o) : "memory");
            }
            mbar_wait(bars + B_TFREE * 8, 0);
            while (kpend && !mbar_test(bars + B_TOK * 8)) {
                if (mbar_test(bars + B_KFREE * 8)) load_k(); else __nanosleep(60);
            }
        } else {
            const int sw = v - 2;
            if (sw == 0) {
                uint32_t tag;
                uint4* const my_stats = p.sc->stats + c * 8 + (lane >> 2);
                asm volatile("ld.relaxed.gpu.global.u32 %0, [%1];" : "=r"(tag) : "l"(&p.sc->epoch) : "memory");
                float ws = 0.f;
#pragma unroll
                for (int k = 0; k < 4; k++) {
                    const uint4 w = ldg128(reinterpret_cast<const uint4*>(p.wr) + 32 * k + lane);
                    ws += (blo(w.x) + bhi(w.x)) + (blo(w.y) + bhi(w.y)) + (blo(w.z) + bhi(w.z)) + (blo(w.w) + bhi(w.w));
                }
                if (q == 0) st_relaxed128(my_stats, make_uint4(0, 0, 0, 0));
                tag = tag % 3 + 1;
                sts32(sm + SM_TOK + 8, tag);
                bar_arrive(6, 160);
#pragma unroll
                for (int o = 1; o < 32; o <<= 1) ws += __shfl_xor_sync(0xFFFFFFFFu, ws, o);
                const uint32_t tb = ((tag & 1) << 15) | ((tag >> 1) << 31);
                const uint32_t ra = sm + SM_RED + (lane >> 1) * 144 + (lane & 1) * 64;
                const uint32_t kidx = 0xFFFF - (32 * (c & 63) + 16 * (lane >> 4) + 8 * (c >> 6) + ((lane >> 1) & 7));
                touch(ws);
                bar_sync(7, 160);
                const uint4 a0 = lds128(ra), a1 = lds128(ra + 16), a2 = lds128(ra + 32), a3 = lds128(ra + 48);
#define F(v) __uint_as_float(v)
                float ss = (F(a0.x) + F(a1.x)) + (F(a2.x) + F(a3.x)), dw = (F(a0.y) + F(a1.y)) + (F(a2.y) + F(a3.y));
                float sx = ((F(a0.z) + F(a1.z)) + (F(a2.z) + F(a3.z))) + ((F(a0.w) + F(a1.w)) + (F(a2.w) + F(a3.w)));
#undef F
                ss += __shfl_xor_sync(0xFFFFFFFFu, ss, 1); dw += __shfl_xor_sync(0xFFFFFFFFu, dw, 1); sx += __shfl_xor_sync(0xFFFFFFFFu, sx, 1);
                const float mean = sx * (1.0f / 1024.0f);
                const float var = fmaxf(ss * (1.0f / 1024.0f) - mean * mean, 0.f);
                const float m = rb(mean);
                float sd; asm("sqrt.approx.ftz.f32 %0, %1;" : "=f"(sd) : "f"(rb(rb(var) + 1e-5f)));
                const float rs = rcp(rb(sd));
                const float hi = rb(rs);
                const uint32_t p0 = pack_b(m, hi), p1 = pack_b(rs - hi, rs * (dw - m * ws));
                const uint32_t o0 = __shfl_xor_sync(0xFFFFFFFFu, p0, 2), o1 = __shfl_xor_sync(0xFFFFFFFFu, p1, 2);
                const uint32_t kr = ((p1 ^ (p1 >> 31 ? 0xFFFF0000u : 0x80000000u)) & 0xFFFF0000u) | kidx;
                const uint32_t k1 = __reduce_max_sync(0xFFFFFFFFu, kr), k2 = __reduce_max_sync(0xFFFFFFFFu, kr == k1 ? 0u : kr);
                if (q == 0) st_relaxed128(my_stats, make_uint4(prmt(p0, o0, 0x5410), (prmt(p0, o0, 0x7632) & 0x7FFF7FFFu) | tb,
                                                               prmt(p1, o1, 0x5410), lane == 0 ? k1 : lane == 4 ? k2 : 0u));
                TSL(9);
            }
            bar_sync(3, 192);
            const uint32_t kk = lane < 8 ? lds32(sm + SM_KEYS + lane * 4) : 0u;
            const uint32_t m1 = __reduce_max_sync(0xFFFFFFFFu, kk);
            const uint32_t m2 = __reduce_max_sync(0xFFFFFFFFu, kk == m1 ? 0u : kk);
            key = sw ? m2 : m1;
            const int t = (0xFFFF - (key & 0xFFFF)) & 2047;
            {
                const uint4* row = reinterpret_cast<const uint4*>(p.x + (size_t)t * 1024) + lane;
                uint4 xr[4];
#pragma unroll
                for (int i = 0; i < 4; i++) xr[i] = ldg128(row + 32 * i);
                const uint4 stk = ld_relaxed128(p.sc->stats + (((t >> 3) & 1) * 128 + (t >> 4)) * 4 + ((t >> 1) & 3));
                if (lane == 0) {
                    sts32(sm + SM_TOK + 4 * sw, t);
                    if (c == 0 && sw == 0) st_relaxed32(&p.sc->epoch, lds32(sm + SM_TOK + 8));
                }
                const uint32_t se = (t & 1) ? 0x3232 : 0x1010;
                const uint32_t m = prmt(stk.x, 0, se), hi = prmt(stk.y, 0, se) & 0x7FFF7FFFu, lo = prmt(stk.z, 0, se);
                const uint32_t a = sm + SM_XSEL + lane * 32 + sw * 16;
#pragma unroll
                for (int i = 0; i < 4; i++) {
                    sts128(a + i * 1024, norm2(xr[i].x, m, hi, lo), norm2(xr[i].y, m, hi, lo), norm2(xr[i].z, m, hi, lo), norm2(xr[i].w, m, hi, lo));
                    if (sw == rank && 16 * i + (lane >> 1) == G) sts128(sm + SM_XRAW + (lane & 1) * 16, xr[i].x, xr[i].y, xr[i].z, xr[i].w);
                }
                proxy_fence();
                __syncwarp();
                if (lane == 0) mbar_arrive(bars + B_TOK * 8);
                TSL(42);
            }
        }
        mbar_wait(bars + B_TOK * 8, 0);
        const uint32_t tag = lds32(sm + SM_TOK + 8);
        {
            if (G < 56) {
                const uint64_t dw = (uint64_t)((sm & 0x3FFFFu) >> 4) | (1ull << 16) | (64ull << 32) | (1ull << 62);
                const uint64_t dx = (uint64_t)(((sm + SM_XSEL + rank * 2048) & 0x3FFFFu) >> 4) | (2ull << 16) | (8ull << 32);
                const uint64_t dh = (uint64_t)(((sm + SM_H) & 0x3FFFFu) >> 4) | (8ull << 16) | (8ull << 32);
                float ag[4] = {0, 0, 0, 0}, au[4] = {0, 0, 0, 0};
                touch(ag); touch(au);
                TSL(13);
#pragma unroll 1
                for (int n = 0; n < 16; n += 2) {
                    const uint64_t a = dw + (chunk_off(n) >> 4), a2 = a + (n < 4 ? 1024 : 512), b = dx + n * 8;
                    mbar_wait(bars + (B_FULL + n) * 8, 0);
                    mbar_wait(bars + (B_FULL + n + 1) * 8, 0);
                    wg_fence();
                    wg_w<1>(ag, a, b); wg_w<1>(au, a + 256, b); wg_w<1>(ag, a + 128, b + 4); wg_w<1>(au, a + 384, b + 4);
                    wg_w<1>(ag, a2, b + 8); wg_w<1>(au, a2 + 256, b + 8); wg_w<1>(ag, a2 + 128, b + 12); wg_w<1>(au, a2 + 384, b + 12);
                    wg_commit();
                    wg_wait<0>();
                    touch(ag); touch(au);
                    bar_sync(4, 128);
                    if (v == 0) {
                        if (lead) {
                            if (n == 2) { mbar_arrive(bars + B_EFREE * 8); mbar_arrive_peer(mapa(bars + B_EFREE * 8, rank ^ 1)); }
                            if (n >= 4 && n < 14) { const int m = n + (n < 10 ? 6 : 10); load_chunk(m); load_chunk(m + 1); }
                        }
                        __syncwarp();
                    }
                    if (kpend && mbar_test(bars + B_KFREE * 8)) load_k();
                }
                if (kpend) { mbar_wait(bars + B_KFREE * 8, 0); load_k(); }
                TSL(14);
                if (q == 0) {
#pragma unroll
                    for (int r = 0; r < 2; r++) {
                        const uint32_t dst = mapa(sm, r), o = dst + SM_PAIR + rank * 1024 + v * 256 + g * 32;
                        st_async4(o, __float_as_uint(ag[0]), __float_as_uint(ag[1]), __float_as_uint(ag[2]), __float_as_uint(ag[3]), dst + SM_BAR + B_PAIR * 8);
                        st_async4(o + 16, __float_as_uint(au[0]), __float_as_uint(au[1]), __float_as_uint(au[2]), __float_as_uint(au[3]), dst + SM_BAR + B_PAIR * 8);
                    }
                }
                mbar_wait(bars + B_PAIR * 8, 0);
                {
                    const uint32_t o = sm + SM_PAIR + v * 256 + g * 32 + q * 4, og = o + (p.up_first ? 16 : 0), ou = o + (p.up_first ? 0 : 16);
                    const float gs = rb(__uint_as_float(lds32(og)) + __uint_as_float(lds32(og + 1024)));
                    const float us = rb(__uint_as_float(lds32(ou)) + __uint_as_float(lds32(ou + 1024)));
                    const float hv = rb(siluf_(gs)) * us;
                    const uint32_t hd = sm + SM_H + (2 * v + (q >> 1)) * 128 + (q & 1) * 32 + g * 2, hb = pack_b(hv, hv);
                    sts16(hd, hb); sts16(hd + 64, hb);
                }
                proxy_fence();
                bar_sync(4, 128);
                TSL(15);
#pragma unroll 1
                for (int n = 0; n < 8; n += 2) {
                    const uint64_t a = dw + (chunk_off(16 + n) >> 4);
                    mbar_wait(bars + (B_FULL + 16 + n) * 8, 0);
                    mbar_wait(bars + (B_FULL + 17 + n) * 8, 0);
                    if (n == 6) TSL(24);
                    float d[4], e[4];
                    wg_fence();
                    wg_w0(d, a, dh); wg_w0(e, a + 512, dh); wg_w<1>(d, a + 128, dh + 16); wg_w<1>(e, a + 640, dh + 16);
                    wg_w<1>(d, a + 256, dh + 32); wg_w<1>(e, a + 768, dh + 32); wg_w<1>(d, a + 384, dh + 48); wg_w<1>(e, a + 896, dh + 48);
                    wg_commit();
                    wg_wait<0>();
                    touch(d); touch(e);
                    st_relaxed32(my_part + n * 8 * 56 * 16, (__float_as_uint((q & 2) ? d[2] : d[0]) & ~3u) | tag);
                    st_relaxed32(my_part + (n + 1) * 8 * 56 * 16, (__float_as_uint((q & 2) ? e[2] : e[0]) & ~3u) | tag);
                }
                TSL(16);
            } else {
                if (v == 0 && lead) { mbar_arrive(bars + B_EFREE * 8); mbar_arrive(bars + B_EFREE * 8); }
                mbar_wait(bars + B_STG * 8, 0);
            }
            if (v == 2 + rank) {
                const int t = (0xFFFF - (key & 0xFFFF)) & 2047;
                const int col = 4 * q + 2 * (lane >> 4) + ((lane >> 3) & 1), d = G * 16 + col;
                const float r = __uint_as_float((key & 0x80000000u) ? (key & 0x7FFF0000u) : (~key & 0xFFFF0000u));
                const float sg = rb(sigmoidf_(r));
                const float xn = blo(lds16(sm + SM_XSEL + (d >> 3) * 32 + rank * 16 + (d & 7) * 2));
                const float xv = blo(lds16(sm + SM_XRAW + col * 2));
                const uint4* src = reinterpret_cast<const uint4*>(p.sc->part) + c * 224 + lane;
                float s0 = 0, s1 = 0, s2 = 0, s3 = 0;
                {
                    uint4 pv[7];
                    int it = 0;
                    bool ok;
                    do {
                        uint32_t bad = 0;
#pragma unroll
                        for (int i = 0; i < 7; i++) pv[i] = ld_relaxed128(src + 32 * i);
#pragma unroll
                        for (int i = 0; i < 7; i++) bad |= (pv[i].x ^ tag) | (pv[i].y ^ tag) | (pv[i].z ^ tag) | (pv[i].w ^ tag);
                        ok = __all_sync(0xFFFFFFFFu, (bad & 3) == 0);
                    } while (!ok && ++it < SPIN_LIMIT);
#pragma unroll
                    for (int i = 0; i < 7; i++) {
                        s0 += __uint_as_float(pv[i].x); s1 += __uint_as_float(pv[i].y); s2 += __uint_as_float(pv[i].z); s3 += __uint_as_float(pv[i].w);
                    }
                }
                TSL(25);
                const bool u16 = lane & 16, u8 = lane & 8;
                const float y0 = (u16 ? s2 : s0) + __shfl_xor_sync(0xFFFFFFFFu, u16 ? s0 : s2, 16);
                const float y1 = (u16 ? s3 : s1) + __shfl_xor_sync(0xFFFFFFFFu, u16 ? s1 : s3, 16);
                float y = (u8 ? y1 : y0) + __shfl_xor_sync(0xFFFFFFFFu, u8 ? y0 : y1, 8);
                y += __shfl_xor_sync(0xFFFFFFFFu, y, 4);
                const float z = rb(xn + rb(rb(y) * sg));
                const float gt = rb(siluf_(z));
                mbar_wait(bars + B_FIX * 8, 0);
                const float o = xv + rb(blo(lds16(sm + SM_FIX + col * 2)) * gt);
                if (!(lane & 4)) p.out[(size_t)t * 1024 + d] = __float2bfloat16(o);
                TSL(26); TG(29);
            }
        }
    }
    }
}

__device__ __align__(128) const uint32_t g_tab[5504] = {
0x2fff3000,0x2e7c2fd4,0x2fc92fd4,0xad72af5a,0x2ff82ffc,0x230e2c07,0x2faf2fbc,0x217ea934,0x2fed2ff4,0xad4da8d5,0x2f912fa0,0x2e5e2bb7,
0x2fdd2fe6,0xb000af46,0x2f6e2f80,0x2fdd2fc9,0x2ff42fff,0x2e1f2fc9,0x2e1f2e7c,0xa875ad72,0x2fbc2fdd,0x9fd92a4e,0x2d4d2dba,0x2cd825db,
0x2f5a2f91,0xaeb5ac07,0x2c5d2cd8,0x30002f30,0x2ed02f1a,0xaf80aff4,0x2aaa2bb7,0x2cb02f1a,0x2fdd2ffc,0x2dba2fbc,0x2a4e2c07,0x25dba934,
0x2f462fa0,0xa7652875,0x25152875,0x2f802d27,0x2e3f2ed0,0xafa0ad72,0xa17e1cb6,0x2e3f2fe6,0x2cd82d96,0xadfeafd4,0xa934a6a1,0xa44e29f1,
0x2fbc2ff8,0x2d4d2faf,0x9fd9230e,0x2cd8217e,0x2e992f46,0xaa4e2515,0xaa4ea765,0x2fd42f80,0x2cb02dba,0xafffae99,0xad72ac5d,0x27652dba,
0x28752b05,0xab5eaee9,0xaf1aae5e,0xae3fa934,0x2f912ff4,0x2cd82fa0,0xac07a8d5,0x2f302bb7,0x2dba2ed0,0xac5d1cb6,0xae99ad72,0x2dba2fe6,
0x29932c5d,0xafc9af6e,0xafe6af6e,0xaaaa25db,0xa17e244e,0xa30ead4d,0xafafaffc,0xaff8aee9,0x2f5a2fed,0x2c5d2f91,0xaeb5ad4d,0x30002e5e,
0x2cb02e3f,0xad72a17e,0xafffafa0,0x27652e3f,0x217e2993,0xaf02afe6,0xaf02afc9,0xaf1aaaaa,0xab05a5db,0x2814aa4e,0xac07adba,0xad4dafdd,
0x2f1a2fe6,0x2bb72f80,0xaff4af46,0x2f1a2fc9,0x2b052d96,0xae5ea6a1,0xaee9afd4,0xa93429f1,0xa5db244e,0xadbaaffc,0xaa4ead4d,0xafddaee9,
0xaddcabb7,0x2cb0a17e,0x2765a17e,0x1cb6ad00,0x2ed02fdd,0x2aaa2f6e,0xaf80b000,0x2cb02fdd,0x28752cd8,0xaf1aa934,0xab5eadfe,0xae3fa44e,
0xab05a17e,0xac07afaf,0x2814a30e,0xad4daff8,0xaf6eaddc,0x2eb52765,0x2eb52cb0,0x2dba1cb6,0x29932f5a,0xa7652e99,0x25152e99,0x2aaaad96,
0xafa0ab05,0xabb7afed,0xaff4acd8,0x28d52ffc,0xa814af02,0x2f912d27,0x9fd9ae1f,0xaee9ae3f,0x2fd42c32,0xaf5a1cb6,0x30002d72,0x2fd42515,
0x28752f46,0xa8d52e7c,0xa8d52c32,0x2e3fa993,0xafedac5d,0xa934b000,0xaf30af5a,0xa8142eb5,0x1648adfe,0x2e992e5e,0x2c87a814,0xa9f1affc,
0x2fe62e1f,0xafffa875,0x2ddc2ff4,0x2ed02e1f,0x26a12f30,0xa9f12e5e,0xad96244e,0x2fd41fd9,0xafffad27,0xa515aff4,0xac32aff4,0xaddc2b5e,
0x2875acb0,0x2d272f46,0x2fa02993,0x2875aed0,0x2ee92f6e,0xaf91ac87,0x1fd92e99,0x28143000,0x244e2f1a,0xab052e3f,0xaf91a875,0x2fbc2b5e,
0xafd4addc,0x1648afc9,0x1648ae7c,0xafdd9cb6,0x2c32aa4e,0x2aaa2fd4,0x2f802e99,0x2e7caa4e,0x2d002ffc,0xae1fae5e,0xad272814,0xabb72dfe,
0x1fd92f02,0xac072e1f,0xafedad27,0x2dfe2e3f,0xaf6eae7c,0x25dbaf80,0x2c5daaaa,0xaf6eac32,0x2ddca5db,0x25153000,0x2c323000,0x2fff26a1,
0x28d52fbc,0xabb7af91,0xaff4ab05,0xafa0244e,0x96482ee9,0xac872dfe,0xae99af30,0x29f12fbc,0xaed0af02,0x2993af1a,0x2f46217e,0xacb0af02,
0x2f1a1cb6,0xa30e2fc9,0xa30e2e7c,0x2e1f2ddc,0x9fd92eb5,0xa44eb000,0xae5eaf5a,0xaf30ac5d,0xa17e2ed0,0xad002ddc,0xabb7afff,0xa17e2fe6,
0xadfeaf6e,0x2c07ae99,0x2fed2c87,0x9fd9b000,0x2fd42814,0xa9f12f30,0xad962934,0x26a12fed,0xaaaa2d00,0x2765afa0,0xa515afa0,0xa993afaf,
0xa5152eb5,0xad722dba,0x9cb6af6e,0xac322eb5,0xad00afbc,0x2d27adfe,0x2e1f2f30,0x2bb7aee9,0x2ffc2b5e,0xacd82e3f,0xafeda875,0xab052f1a,
0xadba2993,0x2c87ae7c,0x2c87ac32,0x2a4eaf46,0xaddc2d96,0xafe62c5d,0xaed02c5d,0x2fffa9f1,0x2e1fad4d,0x2e3f2814,0x2f02ac07,0xad27ab05,
0xae5e2d00,0x9fd9af1a,0xaf302b5e,0xa44e2faf,0x2e99acb0,0xad962f80,0x2f5aaaaa,0x2e99aed0,0xae3f2d72,0xaff82c32,0xaff82515,0x2f021cb6,
0x2ee9ac87,0x2d4d29f1,0x2ffc9648,0xa44eae99,0xaf6e2b05,0x26a1afbc,0xafd4a44e,0xadba2f91,0x2fc9a8d5,0xaf462e3f,0x2f802875,0x2fe6a8d5,
0xae992d4d,0xb0002c07,0xaf6ea814,0x2c872b05,0x2f80ab5e,0x2c322bb7,0x2e7c2bb7,0x2aaaaff8,0xaff42765,0x2b5eafff,0xad27ad72,0xaff42cb0,
0x2fed1648,0xaffc2c5d,0x2b052eb5,0x2cd82a4e,0xaee92d27,0xaffc2bb7,0xad4dad00,0x244e2e1f,0x2fdda993,0x29f12cb0,0x29f12ed0,0x2eb5af46,
0xafe61648,0x2d72afdd,0x9cb6afd4,0xaed01648,0x2f022934,0xafa02814,0xa8d52fed,0xa30e2f30,0xaf302d00,0xafed2b5e,0xa814af1a,0xa9342faf,
0x3000a765,0x26a12d72,0xa5db2fff,0x3000acb0,0xaf46a6a1,0x2ed0af5a,0x2cb0af5a,0xa993ac87,0x2d272cd8,0xae3f9fd9,0xaf022d4d,0xae1f2fbc,
0xaf6e2cd8,0xafd42b05,0x26a1affc,0xadba2fed,0x2fe6a30e,0x1cb62e1f,0xad722f1a,0x2ed0a30e,0xae1faaaa,0x2fafae7c,0x2fafac32,0x28d5af80,
0x29342e99,0xac07a9f1,0xafbc1648,0xaffc2c87,0xafa02cb0,0xafaf2aaa,0x2d00af80,0xafa02ed0,0x2f911648,0xa44e2eb5,0xafbc2c5d,0x2b052a4e,
0xac87acd8,0x3000ad4d,0x2f6e1fd9,0x2e99afbc,0x9cb62faf,0xa515ad27,0xac32ad27,0xad72a30e,0xafc92c87,0xaf802a4e,0x2f46adba,0xafe62c87,
0x2f02244e,0xa8d52f30,0xafa01fd9,0xa30e2e5e,0xa934ae1f,0x2fbcabb7,0x2c072d00,0x2ffcad27,0xaa4e2fff,0x26a1aed0,0x26a1afe6,0x1648addc,
0xaf4629f1,0xac3225db,0xae7c25db,0x29931648,0xab5e2f91,0xafaf2e5e,0xad002fed,0x2f1aad4d,0x2ee9a875,0xaf302ff8,0x2dfea17e,0x2fbcaff4,
0x2c5dafc9,0xa9f12d72,0x2d96afff,0x2c5dae7c,0xaf022993,0xab5e2515,0xab5ea765,0xa30e2aaa,0xacd82fd4,0xaf302dba,0xaf912f6e,0x2c07a6a1,
0x2d969fd9,0xafdd2fed,0x25db2c07,0x2f5aadfe,0x2e7caff8,0xad722f02,0x2fffae3f,0x2fc9aff8,0xaeb52934,0xaa4e244e,0x9648acd8,0xac5d2dfe,
0xaddc2ff8,0xae7c2d00,0xafc92d00,0x9cb628d5,0x2bb72515,0xaff82f80,0xab5e2f46,0x2bb7a765,0x2fbcaf5a,0xaf302fdd,0x2dfea5db,0x2ee9ad96,
0xae5e28d5,0xa934230e,0x2b05af02,0xaee92fa0,0xaeb52fff,0xad962c32,0xad962515,0xac872ddc,0x276529f1,0xaf802eb5,0xaf462fdd,0xa51529f1,
0x2ff4adfe,0xaff82fed,0x217e2c07,0x28759fd9,0xadfe2875,0xa814217e,0x2e5eaff8,0xaffc2ff4,0xaf5a2fe6,0xac872aaa,0xa6a1a993,0xaf5a2fc9,
0x9cb62c87,0xae7c2d96,0xafc92d96,0xaddc2eb5,0x2f1aac07,0xafaf2f30,0xad002f91,0xab5e2cd8,0xad962814,0xa5db1fd9,0x2fddaf91,0xaf5a2ee9,
0xafc92faf,0xaaaa28d5,0x2993ae1f,0xafe62faf,0xa8d52ddc,0xad002c32,0xad002515,0xaff82fff,0x2d4da6a1,0xae5e2dba,0xafed2f6e,0xaf912fd4,
0xad272765,0xa30e1cb6,0x2fafaddc,0xad272cb0,0xaffc2f5a,0xa81425db,0x2e5eafdd,0xadfe2d96,0xac5d2ee9,0xaa4e2934,0x9648ab05,0xaeb52e5e,
0x2993230e,0xac322b5e,0xae7c2b5e,0xaf462f02,0xacb026a1,0x9cb61648,0x2ddcaa4e,0xa76526a1,0xaff42ee9,0xa17e1fd9,0x2ff8af91,0xa8752814,
0xadfe2fa0,0xa44e230e,0x2cd8af02,0xa93428d5,0x96482aaa,0xa5db2515,0xa5dba765,0xa9f12993,0x2f462f5a,0x2c322e99,0x2e7c2e99,0xa993ad96,
0x2f1a2f30,0xa875244e,0x2e3f2e5e,0x2b5e1fd9,0x2ee92f02,0xaf30ad27,0x2dfe2e1f,0x2fbc2e3f,0x2eb52ed0,0xaf6eafff,0x2dba2ddc,0x2eb52fe6,
0x28752993,0xa8d52515,0xa8d5a765,0x2e3f2aaa,0x244e26a1,0xaf91ad96,0xab05a9f1,0x2fbc2fd4,0x96481fd9,0xae99afed,0xac87ac07,0x29f12dfe,
0xa515a17e,0x9cb6abb7,0xad72ad00,0xac32a17e,0xac5dab05,0xaf5aacd8,0xb000afed,0x2eb52ffc,0xaddcad27,0xae7caff4,0xafc9aff4,0x9cb62b5e,
0xaf02ae7c,0x217eaaaa,0xaf1aaf80,0xaf02ac32,0xafbcaf6e,0x2f302c87,0xadfeae99,0xaee9b000,0xafedafa0,0xaf30aff4,0xa934abb7,0xa81428d5,
0xafd4afff,0x1648ac32,0x1648a515,0xafddaddc,0xaed0af6e,0x2f462c5d,0x299325db,0xacb0af6e,0xad00adfe,0x2e1f2fed,0x2d272c07,0x2bb79fd9,
0xadfeaf02,0xa814ae1f,0x2e5e2d27,0xaffcae3f,0xaa4eacb0,0x2e992993,0x2fd42f46,0xaa4eaed0,0x1cb6a5db,0x2e7c3000,0x2fc93000,0x2ddc26a1,
0x2b5e2814,0xa8752934,0x2e3f2f30,0x2f1a2fed,0x1648a814,0x2c879fd9,0x2e992f91,0xa9f1aee9,0x2c322875,0x2f802fa0,0x2aaa2d27,0x2e7c2875,
0x2f1a2ddc,0xa30e2c32,0xa30e2515,0x2e1f2fff,0x2ffc2fd4,0xafedad96,0xacd8a9f1,0xab0526a1,0x2e1f2c32,0x2ff42d72,0xa8751cb6,0x2e1f2515,
0x2ffc2f6e,0x28142e99,0xae5eac87,0x2dfe3000,0x2eb52fbc,0xaf5aab05,0xb000af91,0xac5d244e,0x29932d00,0xac32afa0,0xae7cafa0,0xaf46afaf,
0x2fe62fd4,0x2ddc3000,0xafffaf5a,0x2ed02fd4,0x2d002ee9,0xad271fd9,0xae1faf91,0xabb72814,0x9fd928d5,0xae5eaff4,0xa44eabb7,0xaf30afa0,
0xadbaaaaa,0x2c87a515,0x2c872765,0x2a4ea993,0x9cb62d96,0xacb02c5d,0xa7652c5d,0x2ddca9f1,0xaff8adfe,0xa30eafbc,0xafafaee9,0xa17e2f30,
0x244ead00,0x2dfe2f1a,0x2934ab5e,0xacd8afaf,0x2fdd2e7c,0xb000a993,0x2f6e2f46,0x2fdd2c32,0xae3f9cb6,0xaff8a765,0xaff8acb0,0x2f022ddc,
0xac07afdd,0x2dfeaa4e,0x1fd9adba,0xafeda5db,0x2f6e2934,0xa6a12ee9,0x2fd42e5e,0x2dbaab05,0x27652f1a,0xaaaaaff4,0xa9932bb7,0xa5152f1a,
0xafddadfe,0xadbaaee9,0xaa4eafbc,0xa5db2f30,0x2aaaab5e,0x2fc92bb7,0x2fe62bb7,0xa993aff8,0x2e3f2fc9,0xafa01cb6,0xa17e2ddc,0x2e3f2e7c,
0xae5e9648,0x2d4dac5d,0xaf91aeb5,0xafedaa4e,0xac07aff8,0x1fd9afaf,0x2dfea30e,0xafeda17e,0x2fdd2aaa,0x29f12fe6,0x29f12fc9,0x2eb5a993,
0xa5152dba,0xaddcae99,0xafffac5d,0xac322dba,0xaf02af30,0x2fa02c07,0x28d5acd8,0x230eaf91,0x2934ad00,0x2e5eab5e,0x2ee92f1a,0xab05afaf,
0x2dba2fc9,0xac5d2ddc,0xae991cb6,0x2dba2e7c,0xaf80a6a1,0x2765af5a,0xa515af5a,0xaf46ac87,0x217eae5e,0x230e2ffc,0x2faf2dfe,0x2ff82814,
0x2f6e244e,0x2fd42934,0xa6a12dfe,0x2dbaacd8,0xa5152e3f,0xafffa17e,0xaddcafa0,0xac322e3f,0xae1faf80,0x2fafa515,0x2faf2765,0x28d5af46,
0x2f9125db,0xaee92a4e,0xa8142dba,0x9fd92fdd,0x2f1a2e7c,0x2bb72f46,0xaff4a993,0x2f1a2c32,0xaf309648,0xacd8aeb5,0x2c07ac5d,0xaf91aa4e,
0x25dbae5e,0x2dba2dfe,0x2a4e2ffc,0x2fdd2814,0x2d722faf,0xae7cad27,0xafc9ad27,0xafffa30e,0x27652fdd,0xa9932f6e,0xaaaab000,0xa5152fdd,
0xaf02ae5e,0x28d5af91,0x2fa02d4d,0x230eafed,0x2f91217e,0xa8142faf,0xaee9230e,0x9fd92ff8,0xaa4e2d72,0x26a1afc9,0x26a1ae7c,0x1648afff,
0xaf8029f1,0xafc925db,0xafe625db,0x2f461648,0x2fa0a934,0x2bb72cd8,0x2ff4a44e,0xa8d5adfe,0xafbc2875,0x2934aff8,0xaffc217e,0xac072ff4,
0x2fd4a765,0xaf5a2ddc,0x30009cb6,0x2fd4acb0,0xaf02aaaa,0xab5eacb0,0xab5eaed0,0xa30e2f80,0x2e5e2c5d,0xab053000,0x29342f5a,0x2ee9aeb5,
0xad96ad4d,0x2fddacd8,0xa5dbafbc,0xaf5a1fd9,0x2cb02e1f,0xaddca875,0x1cb62ff4,0x27652e1f,0xa6a1af91,0x29f1afed,0x2d96ae5e,0xafd42d4d,
0x9cb62ff8,0xafe62d00,0xaed02d00,0x2d7228d5,0x2875afe6,0x2d272993,0x2fa0aaaa,0x2875afc9,0xac072f5a,0x2934afdd,0xaffc25db,0xafbc2d96,
0x2cd8af1a,0x2f91ae3f,0x2f302875,0xac07ab5e,0xaeb52d72,0xad96a765,0xad96acb0,0xac872fff,0x2fc9aa4e,0xa9932fd4,0x2aaa2e99,0x2fe6aa4e,
0xaff41fd9,0x2ff8acd8,0xa17eafbc,0xa875ad4d,0x2ffca875,0x2ee9a17e,0xa44e2ff8,0x2d4daff4,0xaf6ea515,0x25dbaf46,0x2c5daf80,0xaf6e2765,
0x2d722c87,0xafe62d96,0xaed02d96,0x9cb62eb5,0xa8d5aee9,0x2bb72b05,0x2ff4a934,0x2fa0ae5e,0x2d962c07,0x25db2d4d,0xafdd2b05,0x2f5aa814,
0xa765af02,0x2f46af1a,0x2f80217e,0x2515af02,0xa8d52fff,0xad00a765,0xad00acb0,0xaff82d72,0x2dfeaeb5,0xacd83000,0x244e2f5a,0x29342c5d,
0xa17e2fc9,0xad002fff,0xabb7ad72,0xa17e2e7c,0x2d4daf5a,0x2ee9a5db,0xa44e2fdd,0x2ffcad96,0xafd42c07,0x29f1af91,0x2d96af30,0xa6a1acd8,
0x2f46230e,0xafc92b5e,0xafe62b5e,0xaf802f02,0xae7c2eb5,0xafff2dba,0x2d72af6e,0xafc92eb5,0x2ff4a814,0x217e2d4d,0xaff82b05,0x28752c07,
0xad4dab5e,0x2fedae3f,0x2e5e2875,0x2f91af1a,0x96482f80,0xa5dbacb0,0xa5dbaed0,0xa9f1aaaa,0xad729648,0xa515a6a1,0xac32a6a1,0x9cb62a4e,
0xae1f2ffc,0xae3f2c07,0xaf022fbc,0x2d27a934,0x2cd8230e,0xaffc2fa0,0x2b0528d5,0x2fedaf02,0x2e99afe6,0xad962f46,0x2f5aaf80,0x2e99afc9,
0x230eaddc,0x2d27aed0,0x2d27afe6,0xafaf2fff,0xafbc2c87,0x1fd9a9f1,0xad4d1648,0xacd82e99,0xaa4e2f30,0xac5d2814,0xaeb52fed,0x96482934,
0x2ed0a8d5,0xaf802e3f,0x2aaa2875,0x2cb0a8d5,0x2e99affc,0x3000afbc,0x2f6eac07,0xac872934,0xa993a8d5,0x2ed0afaf,0x2cb0afaf,0xaf462e1f,
0xaff42ed0,0x2b5ead72,0xad271cb6,0xaff42fe6,0xa44e2dba,0x9fd9a6a1,0xaf302fd4,0xae5e2f6e,0x2fbcad27,0x2d4dabb7,0x9fd92d00,0x2cd8ae1f,
0x2c87af80,0x2f5aae7c,0x2f5aac32,0x26a1aaaa,0xacb01648,0x2fffafdd,0x2d72afd4,0xa7651648,0xafaf2f91,0x2f1aafbc,0xab5ea44e,0xad002b05,
0x2b05230e,0xa44e28d5,0xafbc2fa0,0x2f91af02,0x3000aed0,0x26a19cb6,0xa5db2d72,0x3000afe6,0x2aaaaeb5,0x2c32a9f1,0x2e7ca9f1,0x2f80afdd,
0xad27244e,0x2e3fad4d,0x2f02affc,0x2e1faee9,0xaa4e2e5e,0xaeb52f30,0xac5d1fd9,0x9648244e,0x2cb0a30e,0xad722e1f,0xafff2f1a,0x2765a30e,
0x2ff8af46,0xabb72cb0,0xabb72ed0,0x2b5ea993,0x2b05ae99,0xa81429f1,0x2c079648,0x2d4dac87,0xafa02fe6,0xafaf2f80,0x2d00af46,0xafa02fc9,
0xa9342dba,0xafed2fd4,0xa814a6a1,0xaf302f6e,0x2c87a44e,0xb0002ffc,0xaf6e2d4d,0xae992ee9,0x2fffaf02,0xafe62ff8,0xaed02ff8,0xaddc2e3f,
0xaed02c87,0xaaaa2a4e,0x2f80adba,0xacb02c87,0xafaf2fed,0xab5e2b05,0x2f1aaffc,0xad002cd8,0xab052e1f,0xac072bb7,0x2814ad00,0xad4d2d27,
0x29f11cb6,0xac5d2c32,0xac5d2515,0xad962d72,0x2d722d96,0x25152c5d,0x2c322c5d,0x1cb6a9f1,0x2d272d4d,0xad00a814,0x2bb72c07,0x2e1f2b05,
0x2cd82d00,0xaffcaf1a,0x2b052b5e,0x2fed2faf,0x2c872cb0,0xadbaaf80,0x2a4e2aaa,0x2c872ed0,0xae3faddc,0xaff8aed0,0xaff8afe6,0x2f022fff,
0xaee9ae99,0xad4daf6e,0xaffcb000,0x244e2c87,0xaf6eaf30,0x26a1a814,0xafd4afed,0xadbaa934,0xafc9afa0,0x2f462d00,0xaf80afaf,0xafe6afa0,
0xac87ad4d,0x9648ac07,0x29f12814,0xae99ab05,0xa993ab5e,0x2ed02bb7,0x2cb02bb7,0xaf46aff8,0xa30ea765,0x2f1a2fff,0x2e1f2d72,0xa30eacb0,
0x244e1648,0x1fd92c5d,0x2f302eb5,0x2e5e2a4e,0x2ee92e1f,0x2ffc2f02,0x2d4d2e3f,0xa44ead27,0x2fdd2f80,0x29f12e7c,0x29f12c32,0x2eb52aaa,
0x2fe63000,0xad72a5db,0x1cb626a1,0x2ed03000,0x2f022f91,0xafa0afbc,0xa8d5a44e,0xa30e2b05,0x2b052d00,0xa44e2b5e,0xafbcaf1a,0x2f912faf,
0x16482765,0xafd4ad72,0xafddafff,0x16482cb0,0xaaaaa6a1,0xac32af5a,0xae7caf5a,0xaf80ac87,0xae1facd8,0x2d001fd9,0xabb7ad4d,0xad27afbc,
0xaf6eae5e,0xafd4af30,0x26a19fd9,0xadbaa44e,0xafe6aff4,0x9cb6ad27,0x2d722b5e,0xaed0aff4,0xae1faf46,0x2faf2cb0,0x2faf2ed0,0x28d5a993,
0xa934ac87,0x2c072f6e,0x2fbc3000,0x2ffc2e99,0xa8d5acb0,0x2875aaaa,0x2e3f2f80,0xa8d5aed0,0x29341648,0x2fed2eb5,0x28142c5d,0x2f302a4e,
0x2e992cd8,0x16482d4d,0xa9f19fd9,0x2c872fbc,0x2fff2faf,0xafe6ad27,0xaed0ad27,0xaddca30e,0x2fc92e99,0x2f802f5a,0xaf46ad96,0x2fe62e99,
0x2f022fed,0xa8d52b05,0xafa0affc,0xa30e2cd8,0x29342d27,0xafbcaf02,0xac07ae3f,0xaffcae1f,0xaa4e9cb6,0x26a1ac32,0x26a1a515,0x1648ad72,
0xaaaa29f1,0xaed025db,0xacb025db,0x2f801648,0xaf1aaf91,0x2875ae5e,0xae3fafed,0xab5e2d4d,0x2c07a875,0x2b052ff8,0x2d4da17e,0xa814aff4,
0x2eb52fc9,0xaf6ead72,0x2dba2fff,0x2eb52e7c,0xaf02af80,0xab5eafe6,0xab5eafc9,0xa30e2f46,0x2cd8a6a1,0x2f302d96,0x2f9129f1,0xac07afd4,
0x2d962ffc,0xafdda44e,0x25db2ee9,0x2f5a2d4d,0xae7ca17e,0x2d72abb7,0xafffad00,0xafc9a17e,0x2c5da934,0x2f5aa44e,0x30002cd8,0xaeb5adfe,
0x2d722ff8,0xacb02d00,0xa7652d00,0x2fff28d5,0xaf02a515,0x217eaf80,0xaf1aaf46,0xaf022765,0xa814af5a,0x2b052fdd,0x2d4da5db,0x2c07ad96,
0x2e5e2fa0,0x29342ff4,0xab052bb7,0x2ee9a8d5,0xaeb59cb6,0xad96aed0,0xad96afe6,0xac872d72,0xa765af6e,0x2f802c5d,0x2f4625db,0x2515af6e,
0x2ff42d4d,0xaff8a44e,0x217e2ee9,0x28752ffc,0xad4d2875,0xafbc217e,0xacd8aff8,0x1fd92ff4,0xaa4eafe6,0x2e99aaaa,0x2fd42993,0xaa4eafc9,
0x2fff2c87,0xacb02d96,0xa7652d96,0x2d722eb5,0xab5e2c07,0x2875af30,0xae3faf91,0xaf1aacd8,0xad96afbc,0xa5dbaffc,0x2fdd2934,0xaf5aac07,
0x2fc92875,0x2aaa2fa0,0xa9932d27,0x2fe62875,0xa8d52d72,0xad00aed0,0xad00afe6,0xaff89cb6,0xad4dafd4,0x2e5e2d96,0x2fed29f1,0x2f91a6a1,
0x2e1fa765,0x2ff49cb6,0xa8752ddc,0x2e1facb0,0x1fd92f5a,0xafbc25db,0xacd8afdd,0xad4d2d96,0xaeb5aee9,0x2f5aa934,0x30002b05,0x2c5dae5e,
0x2f80230e,0xaed02b5e,0xacb02b5e,0xaaaa2f02,0x2cb02fd4,0x1cb63000,0xaddcaf5a,0x27652fd4,0xaff4ac07,0xa17eaffc,0x2ff82934,0xa875afbc,
0x2dfea8d5,0x244e2ff4,0xacd82bb7,0x29342fa0,0x96482f46,0xa5dbafe6,0xa5dbafc9,0xa9f1af80,0xafff9648,0xae7ca6a1,0xafc9a6a1,0x2d722a4e,
0x2ff81fd9,0x230e2ee9,0x2faf2814,0x217eaf91,0xafeda30e,0x2d4dafa0,0xaf91a8d5,0xae5e2f02,0x2fdd2515,0xb0002aaa,0x2f6e2993,0x2fdda765,
0x230eafff,0x2d27afc9,0x2d27ae7c,0xafaf2d72,0xa8142fdd,0xaffc2a4e,0xadfe2dba,0x2e5e25db,0x2a4eaf91,0x2c5d2c07,0x2eb5acd8,0x1648af30,
0xac322f1a,0x2993aff4,0xaf462bb7,0xae7c2f1a,0x2fdd1fd9,0x2dba2814,0x2a4e2ee9,0x25dbaf91,0xaf46a8d5,0x2765afaf,0xa515afaf,0xaf802e1f,
0x2e3f2c32,0xafa02ddc,0xa17e2fff,0x2e3f2515,0xacd8adba,0x2dfe26a1,0x2934afd4,0x244eaf6e,0xa8142ff8,0xadfe2faf,0xaffc230e,0x2e5e217e,
0x2c87af46,0x2f5aa515,0x2f5a2765,0x26a1af80,0xae7c2dba,0x9cb6ae99,0xaddcac5d,0xafc92dba,0x2fafab05,0xaf1a2ee9,0x2b5e2e5e,0x2d002934,
0xaf91a30e,0xacd8a8d5,0x2c07afa0,0xaf302f02,0x2dba2c32,0xac5d2fff,0xae992ddc,0x2dba2515,0xa993aeb5,0x2fc9a9f1,0x2fe6a9f1,0x2aaaafdd,
0xa17e2fed,0xa30eadfe,0xafaf9fd9,0xaff82c07,0x2a4eafed,0x2eb5af91,0x2c5d2d4d,0x1648ae5e,0xae7c2e3f,0xaddca17e,0x9cb6afa0,0xafc92e3f,
0x2ff8a993,0xabb72fe6,0xabb72fc9,0x2b5e2aaa,0xaf30a5db,0x2fbcaa4e,0x2ee9adba,0x2dfeafdd,0x2f1a2515,0x2bb72993,0xaff42aaa,0x2f1aa765,
0xab05adba,0x2e5eafd4,0x2ee926a1,0x2934af6e,0xa5db2fed,0xadba9fd9,0xaa4eadfe,0xafdd2c07,0x2ddcaf02,0xacb02ff8,0xa7652ff8,0x9cb62e3f,
0xac322fdd,0xaf462f6e,0x2993b000,0xae7c2fdd,0x2fafacd8,0x2b5e2934,0xaf1a2dfe,0x2d00244e,0xaf30a17e,0x2ee9afaf,0x2fbca30e,0x2dfeaff8,
0x29f12ddc,0xac5da765,0xac5dacb0,0xad969cb6,0xa993aa4e,0x2765ac87,0xa515ac87,0xaaaa2dba,0xafa02f30,0xabb7244e,0xaff42e5e,0x28d51fd9,
0x28142bb7,0xaf912e1f,0x1fd92d27,0x2ee9ad00,0x2fd4aed0,0xaf5a2fff,0x3000addc,0x2fd4afe6,0x2fafaf46,0x2fa0ae7c,0x2fa0ac32,0xad002993,
0xa44eac5d,0x2f91b000,0x2b05af5a,0xafbc2eb5,0xb0002dfe,0x2c87ae5e,0xae992814,0xaf6e2ffc,0xa5152e1f,0x9cb6a875,0xad722ff4,0xac322e1f,
0x26a12b05,0xa9f12cd8,0xad962fed,0x2fd4affc,0x2fffae1f,0x2515230e,0x2c32230e,0x2ddcaf1a,0x2875ae7c,0x2d27aaaa,0x2fa0af80,0x2875ac32,
0xaee929f1,0x2f91ae99,0x9fd9ac87,0xa8149648,0xafed2f1a,0xaf302e3f,0xa934a875,0xa8142b5e,0xa6a12ddc,0xb0002fc9,0xb0002e7c,0x25db1cb6,
0x2ed0aa4e,0xaf462fd4,0xa9932e99,0x2cb0aa4e,0x2e3faffc,0xad272e5e,0x2e1fa814,0x2f02adfe,0x9fd9abb7,0x2c07ad27,0x2fedae1f,0xadfe2d00,
0xaf6e2cb0,0x25dba993,0x2c5daf46,0xaf6e2ed0,0xaddc2fdd,0xa5159648,0xac329648,0xafff2fd4,0x28d52814,0xabb72934,0xaff42f30,0xafa02fed,
0x3000aee9,0x2e99adfe,0xac872f30,0x2f6eafbc,0x2c32af02,0x2f80af1a,0x2aaa217e,0x2e7caf02,0xab5e9cb6,0x2ff4afc9,0x2ff4ae7c,0x2d27addc,
0xaffc2eb5,0x2fedb000,0x2cd8af5a,0x2b05ac5d,0xa17e2c32,0xad002d72,0xabb71cb6,0xa17e2515,0x2dfea9f1,0xac072c87,0xafed2e99,0x1fd91648,
0x2fd4afbc,0xa9f12b05,0xad962f91,0x26a1a44e,0x2aaaae3f,0xa76528d5,0x251528d5,0x2993a875,0xafe62eb5,0xaddc2dba,0x2fffaf6e,0xaed02eb5,
0xae3f2fbc,0xae1f2dfe,0x2d27af30,0xaf022ee9,0x9fd92b5e,0xae5e2e3f,0xa44ea875,0xaf302f1a,0x2d96a993,0xae992e7c,0xae992c32,0xaf5a2f46,
0x299329f1,0xa76525db,0x251525db,0x2aaa1648,0x28d52934,0xaf02acd8,0x230e244e,0x2fa02dfe,0x28142875,0xaf91aff8,0x1fd9217e,0x2ee92ff4,
0x26a12765,0xaa4eaddc,0x16481cb6,0x26a12cb0,0xaf02af46,0xab5eae7c,0xab5eac32,0xa30e2993,0xae5eaeb5,0x2b059648,0xa934aa4e,0xaee9ac5d,
0xad96adfe,0x2fdd2e5e,0xa5dba814,0xaf5aaffc,0xacb0ad27,0x2ddc2faf,0x9cb6a30e,0xa765ad27,0x2fd42f91,0x2f6e2fed,0x2dba2e5e,0xa6a1ad4d,
0x2fff2ff8,0x25152d00,0x2c322d00,0x2ddc28d5,0x2faf2fe6,0xae1fa993,0x28d52aaa,0x2faf2fc9,0x2ee92f5a,0xaf91afdd,0x1fd925db,0x28142d96,
0xacd8ab5e,0xaf91ad00,0xaf30afaf,0x2c072f1a,0xaeb5addc,0xad96afc9,0xad96ae7c,0xac879cb6,0xafc9af5a,0x2993a6a1,0xaaaaac87,0xafe6af5a,
0xaff4affc,0x2ff82e5e,0xa17ea814,0xa875adfe,0x9fd9a875,0x2c07a17e,0x2fed2ff8,0xadfeaff4,0x29f12515,0x2fdd2f46,0x2eb52f80,0x29f1a765,
0x2ddc2c87,0x25152d96,0x2c322d96,0x2fff2eb5,0x2fa02ee9,0xaf02ab05,0x230e2934,0x28d52e5e,0x2d962ee9,0x25db2dfe,0xafddaf30,0x2f5a2fbc,
0x27652bb7,0xaf46ab5e,0xaf80aff8,0xa5152bb7,0xa8d59cb6,0xad00afc9,0xad00ae7c,0xaff8addc,0xadfeac5d,0x2cd89648,0xa44eaa4e,0xa934aeb5,
0xaff8afc9,0xae3fafff,0x2f022d72,0xaff8ae7c,0xadfeaf5a,0x2c07a5db,0x2fed2fdd,0x9fd9ad96,0xa6a1ac07,0x2f6e2f91,0x2dba2f30,0x2fd42cd8,
0x2aaa230e,0xa7652b5e,0x25152b5e,0x29932f02,0x2e7c2c5d,0x2fff2d96,0xad72a9f1,0x2fc92c5d,0x2ff42fbc,0x217e2dfe,0xaff8af30,0x28752ee9,
0x2d4d2f1a,0xafedad00,0xae5eafaf,0xaf91ab5e,0x96482993,0xa5dbae7c,0xa5dbac32,0xa9f1af46,0xaddc9648,0xafe6a6a1,0xaed0a6a1,0x2fff2a4e,
0xad27affc,0x2d00ac07,0xabb7afbc,0xae1f2934,0x2e5e230e,0x1fd92fa0,0x2f3028d5,0x244eaf02,0x2c872fe6,0xadbaaf46,0x2a4e2f80,0x2c872fc9,
0x230ead72,0x2d27ac32,0x2d27a515,0xafaf9cb6,0x2fbc2e99,0x9fd92f6e,0x2d4d3000,0x2cd8ac87,0xaa4e2b05,0xac5dafbc,0xaeb5a44e,0x96482f91,
0xaed0afa0,0x2f802d00,0xaaaaafaf,0xacb0afa0,0x2c872ffc,0x16482fbc,0xa9f12c07,0x2e99a934,0xaf80a8d5,0xac32afaf,0xae7cafaf,0xaaaa2e1f,
0xa30eaed0,0x2f1a2d72,0x2e1f9cb6,0xa30eafe6,0x2fed2dba,0xaffca6a1,0x2b052fd4,0x2cd82f6e,0xafbcae1f,0xad4daf02,0x1fd9ae3f,0xacd82d27,
0x2c87a993,0x2f5a2cb0,0x2f5a2ed0,0x26a1af46,0x2cb03000,0xafffa5db,0xad7226a1,0x27653000,0xafafa934,0x2f1aa814,0xab5eafed,0xad00af30,
0x2f30230e,0x2fed28d5,0x28142fa0,0x2934af02,0x16482ed0,0xafd41cb6,0xafddad72,0x16482fe6,0xaf46aeb5,0x2ed0a9f1,0x2cb0a9f1,0xa993afdd,
0x2e1fa44e,0xad002d4d,0x2bb72ffc,0x2d272ee9,0xaa4e2cd8,0xaeb52b05,0xac5daffc,0x96482fed,0xacb0aff4,0x2d72ad27,0x2fff2b5e,0xa765aff4,
0x2ff82aaa,0xabb72e7c,0xabb72c32,0x2b5e2f80,0xab052c87,0x2814af6e,0xac07b000,0xad4dae99,0xa8d5afe6,0x2875af80,0x2e3f2f46,0xa8d5afc9,
0x2f912dba,0xa44e2fd4,0xafbca6a1,0x2b052f6e,0xae99244e,0x9648affc,0x29f1ad4d,0xac87aee9,0x1cb6af02,0x25152ff8,0x2c322ff8,0x2d722e3f,
0x2ed02e99,0x2aaa2f5a,0xaf80ad96,0x2cb02e99,0xafafa44e,0xab5eaf30,0x2f1a9fd9,0xad00ae5e,0x2b05ad27,0x2c072f02,0xa8142e3f,0x2d4d2e1f,
0x29f12fff,0xac5daed0,0xac5dafe6,0xad96addc,0xaf46aa4e,0xac32ac87,0xae7cac87,0x29932dba,0x2f1a2b05,0xa8752fed,0x2e3f2cd8,0x2b5eaffc,
0xaee9abb7,0x2f30ae1f,0xadfead27,0xafbc2d00,0x2eb52c32,0xaf6e1cb6,0x2dba2d72,0x2eb52515,0x2fafa993,0x2fa0a515,0x2fa02765,0xad00aaaa,
0xafed26a1,0xa934ad96,0xaf30a9f1,0xa8142fd4,0x30009fd9,0xac872fed,0x2e992c07,0x2f6eadfe,0xafe6a17e,0x2fffabb7,0xaddcad00,0xaed0a17e,
0xac5d2f30,0xaf5a2e5e,0xb000244e,0x2eb51fd9,0x2ddcae1f,0x2e7c230e,0x2fc9230e,0x1cb6af1a,0xaf022cb0,0x217eaf46,0xaf1aa993,0xaf022ed0,
0x2fbca9f1,0xaf302e99,0x2dfe2c87,0x2ee91648,0xa44eafa0,0x2b05aff4,0x2f91abb7,0xafbc28d5,0xa6a12fff,0xb0002c32,0xb0002515,0x25db2ddc,
0x2c32af6e,0x2aaa2c5d,0x2f8025db,0x2e7caf6e,0xae3f2dfe,0x2d27afed,0xae1fac07,0xaf021fd9,0x2dfe2bb7,0x28142d27,0xae5e2e1f,0x2ffcad00,
0xaa4eae7c,0x2e99af80,0x2fd4aaaa,0xaa4eac32,0x9cb62fdd,0xae7c9648,0xafc99648,0xaddc2fd4,0x2b5eafbc,0xa8752f91,0x2e3f2b05,0x2f1aa44e,
0xb0002814,0xae991fd9,0x2c87af91,0xaf6e2ee9,0x2ed02875,0xa9932fa0,0xaf462d27,0x2cb02875,0xab5eaddc,0x2ff4ac32,0x2ff4a515,0x2d27afff,
0x9fd92fd4,0xa44ead96,0xae5ea9f1,0xaf3026a1,0x2e1faed0,0x2ff4addc,0xa8752fff,0x2e1fafe6,0xaffc29f1,0xa814ac87,0x2e5eae99,0xadfe9648,
0x2eb52814,0xaf5a2f30,0xb0002934,0xac5d2fed,0xa993ae3f,0x2c3228d5,0x2e7c28d5,0x2f46a875,0xa5152fd4,0xad723000,0x9cb6af5a,0xac322fd4,
0x2e3faee9,0x2e1f9fd9,0xad272f91,0x2f02a814,0xaffc28d5,0x2cd8aff4,0x2fedabb7,0x2b05afa0,0x2d962aaa,0xae992515,0xae99a765,0xaf5a2993,
0x1cb6adba,0x2cb0aeb5,0x2765aeb5,0xaddc2f6e,0xaff82d4d,0xa30ea814,0xafaf2c07,0xa17e2b05,0xa44e2e3f,0xadfe2b5e,0xa9342f1a,0x2cd8a875,
0x2fddacb0,0xb0002f80,0x2f6eaaaa,0x2fddaed0,0x2d001cb6,0x217e2765,0x217e2cb0,0x2bb7addc,0x2ee9afdd,0x2d4daa4e,0x2ffcadba,0xa44ea5db,
0xa9f1a934,0x2fd4aee9,0x26a1ae5e,0xad962b05,0xafc92f1a,0x2f46aff4,0xaf802bb7,0xafe62f1a,0xafdd2d4d,0xadba2c07,0xaa4ea814,0xa5db2b05,
0xaaaa2f1a,0xafc92f02,0xafe62f02,0x2993a17e,0x2e3fa765,0xafa02fff,0xa17e2d72,0x2e3facb0,0x2e5eb000,0xad4d2eb5,0x2f91ac5d,0x2fedaf5a,
0x2ee9aff8,0x2ffcafaf,0x2d4da30e,0xa44ea17e,0xa5dbaaaa,0x2f6eafe6,0x2f6eafc9,0xac5d2993,0xafe62dba,0x2d72ae99,0x9cb6ac5d,0xaed02dba,
0xabb72f30,0x28d5ac07,0xafa02cd8,0xaff42f91,0xa9342e3f,0xae5e2f1a,0xaee92b5e,0x2b05a875,0x2dbaa765,0xac5d2d72,0xae992fff,0x2dbaacb0,
0x2f80afd4,0xa7652a4e,0x25152a4e,0x2f46ae99,0x217eacd8,0x230e1fd9,0x2fafad4d,0x2ff8afbc,0xa9f1a44e,0x26a1a934,0x2fd4adfe,0xad962cd8,
0xafe62e3f,0x9cb6a17e,0x2d72afa0,0xaed02e3f,0xad272f80,0xa8752515,0xa875a765,0xafa02f46,0x293425db,0xac072a4e,0xafbc2dba,0xaffc2fdd,
0x2f1aacb0,0x2bb7aaaa,0xaff42f80,0x2f1aaed0,0x2f30b000,0x2cd8ac5d,0xac072eb5,0x2f91af5a,0x25dbacd8,0x2dbaad4d,0x2a4e1fd9,0x2fddafbc,
0xad722875,0x2e7cae1f,0x2fc9ae1f,0x2fffaff4,0xafc92fdd,0xaf802f6e,0x2f46b000,0xafe62fdd,0xabb72e5e,0xafa02f91,0x28d5ad4d,0xaff42fed,
0x2934217e,0xafbc2faf,0xac07230e,0xaffc2ff8,0x2f5aad72,0xafd42fc9,0xafd42e7c,0xb0002fff,0x9cb69648,0xacb0a6a1,0xa765a6a1,0x2ddc2a4e,
0xa17e9fd9,0xaff4aee9,0xa875a814,0x2ff82f91,0xa44ea30e,0xadfeafa0,0xa934a8d5,0x2cd82f02,0xa5dba515,0x9648aaaa,0xa9f1a993,0xa5db2765,
0xa30e9cb6,0xad27a765,0xad27acb0,0x2faf2ddc,0xa814a5db,0xaffcaf5a,0xadfead96,0x2e5e2fdd,0xaa4ea934,0xac5daee9,0xaeb5ae5e,0x96482b05,
0xac32ab5e,0x2993a30e,0xaf46af02,0xae7cab5e,0xa5db9fd9,0xad96a814,0xaf5aaee9,0x2fdd2f91,0xaaaaa8d5,0xafc9afaf,0xafe6afaf,0x29932e1f,
0xad00ac32,0xa8d5addc,0xaff8afff,0xad00a515,0xae5eadba,0x2d4d26a1,0xaf91afd4,0xafedaf6e,0xa814a17e,0xadfea875,0xaffcaff4,0x2e5e2ff8,
0xac87aaaa,0xaf5aafe6,0xaf5aafc9,0xa6a12993,0xae7cad96,0x9cb6ac87,0xaddcaeb5,0xafc9ad96,0xafafaf30,0x2f1a2c07,0xab5eacd8,0xad00af91,
0xa934a30e,0xae5ea8d5,0xaee9afa0,0x2b052f02,0xad96ac32,0xaeb5afff,0xac87addc,0xad96a515,0xaf80aeb5,0x2765a9f1,0xa515a9f1,0xaf46afdd,
0xaff8afed,0x2ff42dfe,0x28751fd9,0x217eac07,0xaa4ea44e,0xaeb5a934,0xac5dadfe,0x96482cd8,0xae7cad00,0xaddcaff8,0x9cb6a8d5,0xafc9ad00,
0xaff8af80,0x2bb7a515,0x2bb72765,0xab5eaf46,0xaf30afdd,0x2fbc2f5a,0x2ee92d96,0x2dfe25db,0xab5ea515,0xaf02a993,0xa30eaaaa,0xab5e2765,
0xaf30adba,0xacd8afd4,0x2c0726a1,0xaf91af6e,0xafddafed,0x2d961fd9,0x2f5a2dfe,0x25dbac07,0xad72af02,0x2e7c2ff8,0x2fc92ff8,0x2fff2e3f,
0xac32a5db,0xaf46a9f1,0x29939648,0xae7ca5db,0xafafae5e,0xab5eaf91,0x2f1a2d4d,0xad00afed,0xaf30aff8,0x2ee92875,0x2fbc2ff4,0x2dfe217e,
0xa9f1ad72,0x2c5d2fc9,0x2c5d2e7c,0x2d962fff,0xaf80aa4e,0xafc9ac87,0xafe6ac87,0x2f462dba,0xa8d5af30,0x2f02a44e,0xa30eae5e,0xafa09fd9,
0x2fbc2bb7,0xa9342e1f,0x2ffc2d27,0x2c07ad00,0x26a12ed0,0xaa4eafff,0x16482ddc,0x26a12fe6,0xafafaaaa,0xafa0acb0,0xafa0aed0,0x2d002f80,
0xa44eaeb5,0x2f919648,0x2b05aa4e,0xafbcac5d,0x30002d4d,0xac872cd8,0x2e992fbc,0x2f6e9fd9,0xa5152d27,0x9cb6afaf,0xad72230e,0xac322d27,
0xafd4ab05,0xaf6eacd8,0xadbaafed,0x26a12ffc,0x1cb6ae1f,0x2fe6230e,0x2ed0230e,0xad72af1a,0x2faf2e7c,0xae1f2aaa,0x28d52f80,0x2faf2c32,
0xac0729f1,0x2934ae99,0xaffcac87,0xafbc9648,0xafedab5e,0xaf30ad00,0xa934afaf,0xa8142f1a,0x26a1ad72,0x30002765,0x30002cb0,0xa5dbafff,
0x2ed02f5a,0xaf4626a1,0xa9932c87,0x2cb02f5a,0xae3f1fd9,0x2d27acd8,0xae1fafbc,0xaf02ad4d,0xaffcabb7,0xaee9ad27,0x244eae1f,0xad4d2d00,
0x29f1acb0,0x2fdd2993,0x2eb52f46,0x29f1aed0,0x2d722fdd,0xafe69648,0xaed09648,0x9cb62fd4,0xafa0a814,0x2f02a934,0xa30eaf30,0xa8d5afed,
0xb000ac07,0xae99ad4d,0x2c87ab05,0xaf6e2814,0x2c32abb7,0x2f802b5e,0x2aaa2ff8,0x2e7cabb7,0x2b5e2fff,0xaff4a765,0xaff4acb0,0xad272d72,
0xaffcac5d,0x2fed9648,0x2cd8aa4e,0x2b05aeb5,0xaff8ac32,0xae3fad72,0x2f029cb6,0xaff8a515,0x2d4da9f1,0x2ee92c87,0xa44e2e99,0x2ffc1648,
0x26a12fbc,0xaf6eab05,0xadbaaf91,0xafd4244e,0xaf46ae3f,0x2fc928d5,0x2fe628d5,0x2f80a875,0xafe6ac5d,0xaddcad96,0x2fff29f1,0xaed0ac5d,
0x2e3fa814,0x2e1f2d4d,0xad272b05,0x2f022c07,0x9fd92f1a,0xae5ead00,0xa44eafaf,0xaf30ab5e,0xad96af80,0x2e992cb0,0x2e992ed0,0x2f5a2aaa,
0xad72adba,0xa515aeb5,0xac32aeb5,0x9cb62f6e,0x2d272dfe,0xad002fbc,0x2bb72ee9,0x2e1faf30,0xacd8ae3f,0x2ffcab5e,0xab05af1a,0xafed2875,
0x2c872e7c,0xadbaa993,0x2a4e2f46,0x2c872c32,0xad00addc,0xa17eaed0,0xa17eafe6,0xabb72fff,0x2c072e99,0xadfe2f6e,0x9fd93000,0x2fedac87,
0xa9f1af30,0x2fd4a814,0x26a1afed,0xad96a934,0x27652fa0,0xaaaaad00,0xa9932faf,0xa5152fa0,0xac87adfe,0x9648aee9,0x29f1afbc,0xae992f30,
0x29932f1a,0xaed02f02,0xacb02f02,0x2f46a17e,0xa30eafc9,0x2f1a9cb6,0x2e1faddc,0xa30eae7c,0xa44e3000,0x9fd9aeb5,0xaf302c5d,0xae5e2f5a,
0xac07ae1f,0x1fd9af02,0x2dfeae3f,0xafed2d27,0x25db2f80,0xaf6e2e7c,0xaf6e2c32,0x2c5d2aaa,0x2515b000,0x2ddc25db,0x2fffa6a1,0x2c32b000,
0xabb72f91,0x28d5afbc,0xafa0a44e,0xaff42b05,0xab05ae3f,0x244eaf1a,0x2fbcab5e,0xaf912875,0x16482fc9,0xafd42ddc,0xafdd1cb6,0x16482e7c,
0x2aaaafd4,0x2c322a4e,0x2e7c2a4e,0x2f80ae99,0xae1f2e5e,0x2d00affc,0xabb7adfe,0xad27a814,0xa9f1ae5e,0x26a1af30,0x2fd49fd9,0xad96a44e,
0xa5152ff4,0xafff2d27,0xaddcab5e,0xac322ff4,0x2d27af46,0x28752cb0,0x28752ed0,0x2fa0a993,0xaf912c87,0x2ee9af6e,0x2814b000,0x1fd9ae99,
0xa8d5ae7c,0x2875af46,0x2e3f2993,0xa8d5ac32,0xa9343000,0xafed2c5d,0xa814aeb5,0xaf302f5a,0x2e99ae5e,0x16482dfe,0xa9f12ffc,0x2c872814,
0xafff2875,0x2fe6ae1f,0x2ed0ae1f,0x2ddcaff4,0xa765ae99,0x2993af5a,0x2aaa2d96,0x2515ae99,0xabb72fed,0xafa02b05,0x28d5affc,0xaff42cd8,
0x2f91ad27,0xa8142f02,0xaee92e3f,0x9fd92e1f,0xaf5a9cb6,0x2fd4ac32,0x2fd4a515,0x3000ad72,0x2aaaaf6e,0x2ed0afdd,0x2cb0afdd,0xaf803000,
0xaf1a2934,0x2875acd8,0xae3f244e,0xab5e2dfe,0xac072faf,0xab05217e,0xad4d2ff8,0x2814230e,0x2eb5a765,0xaf6e2ddc,0x2dba9cb6,0x2eb5acb0,
0x2bb7af80,0x2f1aafe6,0x2f1aafc9,0xaff42f46,0xae5e26a1,0x2b05ad96,0xa934a9f1,0xaee92fd4,0xadba2ffc,0xa5dba44e,0xafdd2ee9,0xaa4e2d4d,
0x2cb0217e,0xaddc2bb7,0x1cb62d00,0x2765217e,0x2c5daf91,0x2f5aafed,0x3000ae5e,0xaeb52d4d,0xad72217e,0x2cb0ae3f,0x2765ae3f,0xafff2fa0,
0xaf022fe6,0x217ea993,0xaf1a2aaa,0xaf022fc9,0x28142a4e,0xab0525db,0xad4d2fdd,0xac072dba,0x2cd8afa0,0x2f91aff4,0x2f30abb7,0xac0728d5,
0xac5d9cb6,0x2dbaaed0,0x2dbaafe6,0xae992d72,0xafc92f6e,0x2993ac5d,0xaaaaa5db,0xafe62f6e,0xa30e2d4d,0xa17ea44e,0xaff82ee9,0xafaf2ffc,
0x2d4dafaf,0x2fbcaff8,0x2cd8a17e,0x9fd9a30e,0xaa4ea515,0x2e99af46,0x2fd4af80,0xaa4e2765,0xafff2e99,0x2cb0adba,0x2765adba,0xad722c5d,
0xab5e2ee9,0x2875ab05,0xae3f2934,0xaf1a2e5e,0x2dbaafbc,0x2fddaffc,0x25db2934,0x2a4eac07,0xa765a875,0x2f46afa0,0x2f80ad27,0x2515a875,
0xafa02d72,0x2e3faed0,0x2e3fafe6,0xa17e9cb6,0xadfe2fd4,0x2cd8ad96,0xa44ea9f1,0xa93426a1,0x2e1fafc9,0x2ff4afff,0xa8752d72,0x2e1fae7c,
0x9fd9aa4e,0x2fbcafdd,0x2cd8a5db,0x2d4dadba,0xaeb52c07,0x2f5aaf91,0x3000af30,0x2c5dacd8,0xaf802ff4,0x2ed0af1a,0x2cb0af1a,0x2aaaabb7,
0x2e7cafd4,0x2fffb000,0xad722f5a,0x2fc9afd4,0x230eac07,0x2ff8affc,0x217e2934,0x2fafafbc,0xad4d28d5,0x2fedaff4,0x2e5eabb7,0x2f91afa0,
0xb0002f46,0x2fddafe6,0x2fddafc9,0x2f6eaf80,0xaaaaaa4e,0xaed0ac87,0xacb0ac87,0x2f802dba,0xab5eab05,0xafafafed,0xad00acd8,0x2f1a2ffc,
0xac07abb7,0xab05ae1f,0xad4dad27,0x28142d00,0xac5dac32,0x29f19cb6,0xad96ad72,0xac5da515,0xafafaf80,0xafa0afe6,0xafa0afc9,0x2d002f46,
0xafedafd4,0xa934adba,0xaf30af6e,0xa81426a1,0xb000affc,0x2c87244e,0xae99aee9,0xaf6ead4d,0xafe6aff8,0x2fff2f02,0xaddcae3f,0xaed0aff8,
0xaeb5af30,0xaa4eae5e,0x9648a44e,0xac5d9fd9,0xad72ae1f,0x2cb0230e,0x2765230e,0xafffaf1a,0xabb7acb0,0x2ff82f46,0x2b5e2993,0xabb7aed0,
0xa814a9f1,0x2b052e99,0x2d4d2c87,0x2c071648,0xa44ea8d5,0x2b05a30e,0x2f912f02,0xafbcafa0,0x26a11cb6,0x30002ed0,0x30002fe6,0xa5dbad72,
0x2c3229f1,0x2aaa2eb5,0x2f802fdd,0x2e7c29f1,0x2e3f2d4d,0xad27a44e,0x2e1f2ee9,0x2f022ffc,0x2d4d2bb7,0x2fbc2d27,0x2cd82e1f,0x9fd9ad00,
0x2f5a2e7c,0x2c872f80,0x26a12aaa,0x2f5a2c32,0x2fff2fdd,0xacb09648,0xa7659648,0x2d722fd4,0x2f1a2fbc,0xafafaf91,0xad00ab05,0xab5e244e,
0x30002fbc,0x2e992ffc,0xac87a934,0x2f6e2c07,0x2ed02faf,0xa99328d5,0xaf46ae1f,0x2cb02faf,0x2b5e2d72,0xaff4aed0,0xaff4afe6,0xad279cb6,
0x9fd926a1,0xa44eadba,0xae5eaf6e,0xaf30afd4,0x2d272ed0,0x230e2ddc,0xafafafff,0x2d272fe6,0x1fd929f1,0xafbcac87,0xacd8ae99,0xad4d9648,
0xac5da814,0xaa4eaf30,0x9648a934,0xaeb5afed,0xaf80ae3f,0x2ed028d5,0x2cb028d5,0x2aaaa875,0xa51526a1,0xad721648,0x9cb6aa4e,0xac3226a1,
0xae3fac07,0xae1faffc,0x2d272934,0xaf02afbc,0xaffcafa0,0x2cd8a30e,0x2fed2f02,0x2b05a8d5,0xad96af46,0x2e992fe6,0x2e992fc9,0x2f5a2f80,
0xafffadba,0xae7caeb5,0xafc9aeb5,0x2d722f6e,0x217ead4d,0x2ff42814,0x2875ac07,0xaff8ab05,0x2fed2e3f,0xad4d2b5e,0x2f912f1a,0x2e5ea875,
0xa5db2cb0,0x9648af80,0xa9f12aaa,0xa5db2ed0,0xad00afff,0xa17eafc9,0xa17eae7c,0xabb72d72,0x2ee925db,0x2d4d2f5a,0x2ffc2d96,0xa44eafdd,
0x29f12f91,0xafd4ac07,0xa6a12cd8,0x2d962f30,0xafc9ab5e,0x2f46a30e,0xaf80af02,0xafe6ab5e,0x25dbad4d,0x2d96ac07,0x2f5a2814,0xafddab05,
0x2f462f1a,0xa7652f02,0x25152f02,0x2f80a17e,0xad002765,0xa8d5afff,0xaff8ad72,0xad002cb0,0xacd8b000,0x2dfe2eb5,0x2934ac5d,0x244eaf5a,
0x2ee9217e,0x2ffc2875,0x2d4d2ff4,0xa44eaff8,0x25db2f46,0xaf6e2515,0xaf6ea765,0x2c5d2f80,0xafe6ad96,0x2d72ac87,0x9cb6aeb5,0xaed0ad96,
0x2bb7ab05,0xa8d52ee9,0x2fa02e5e,0x2ff42934,0x2f912e3f,0x2cd82f1a,0xac072b5e,0x2f30a875,0xad962765,0xaeb5ad72,0xac87afff,0xad962cb0,
0xa993afd4,0x2fc92a4e,0x2fe62a4e,0x2aaaae99,0x2ff82cd8,0xaff49fd9,0xa8752d4d,0xa17e2fbc,0x29f12fed,0xa6a12f91,0xafd4ad4d,0x2d962e5e,
0xafe6ad00,0x9cb6aff8,0x2d72a8d5,0xaed0ad00,0x2d27a993,0x28752fe6,0x28752fc9,0x2fa02aaa,0x29342fdd,0xac07af5a,0xafbcad96,0xaffca5db,
0xab5e2cb0,0xaf022aaa,0xa30eaf80,0xab5e2ed0,0xab05b000,0x2e5eac5d,0x2ee92eb5,0x2934af5a,0x2fdd2cd8,0xad962d4d,0xaf5a9fd9,0xa5db2fbc,
0xaddc2875,0x2cb0ae1f,0x2765ae1f,0x1cb6aff4,0xafc9a5db,0xaf80a9f1,0x2f469648,0xafe6a5db,0x2bb7acd8,0x2fa02934,0xa8d52dfe,0x2ff4244e,
0x29342ff8,0xafbca875,0xac07aff4,0xaffca17e,0xaf5aaddc,0x2fd42765,0x2fd42cb0,0x30001cb6,0xa993af6e,0x2765afdd,0xa515afdd,0xaaaa3000,
0x28d52f91,0xaf022e5e,0x230e2fed,0x2fa0ad4d,0xa814afaf,0x2f91a17e,0x9fd9aff8,0xaee9a30e,0x26a12fc9,0xaa4ead72,0x16482fff,0x26a12e7c,
0x2bb7af46,0x2f1aae7c,0x2f1aac32,0xaff42993,0xacd82eb5,0xaf301648,0xaf912a4e,0x2c072c5d,0x2dbaadfe,0x25db2e5e,0x2fdda814,0x2a4eaffc,
0xae7c2d27,0x2d72afaf,0xafff230e,0xafc92d27,0x2fd4a934,0x2f6ea44e,0x2dba2cd8,0xa6a1adfe,0xafff217e,0xa515ae3f,0xac32ae3f,0xaddc2fa0,
0x2faf2515,0xae1f2f80,0x28d52f46,0x2fafa765,0xaee9aa4e,0x2f91a5db,0x9fd9afdd,0xa814adba,0x2e5e2b5e,0x29342d00,0xab052faf,0x2ee9af1a,
0xac5daddc,0x2dbaafc9,0x2dbaae7c,0xae999cb6,0x27652f5a,0xaf8026a1,0xaf462c87,0xa5152f5a,0x230eaffc,0x217e2e5e,0x2ff8a814,0x2fafadfe,
0x1fd92faf,0xac072ff8,0xafed217e,0x2dfe230e,0x29f1afe6,0x2fddaaaa,0x2eb52993,0x29f1afc9,0xaddc2e99,0xa515adba,0xac32adba,0xafff2c5d,
0x2fa0ac07,0xaf022f30,0x230e2f91,0x28d52cd8,0xadba2ee9,0xafdd2dfe,0xa5dbaf30,0xaa4e2fbc,0x2fc9abb7,0x2aaa2b5e,0xa9932ff8,0x2fe6abb7,
0xafa09cb6,0x2e3fafc9,0x2e3fae7c,0xa17eaddc,0x2d4d2c5d,0xae5e1648,0xafed2a4e,0xaf912eb5,0xaff82765,0xae3f1cb6,0x2f02addc,0xaff82cb0,
0x2dfe2a4e,0xac072fdd,0xafed25db,0x1fd92dba,0xa6a1aee9,0x2f6ea934,0x2dba2b05,0x2fd4ae5e,0xaaaa2ff4,0x2765af1a,0xa515af1a,0xa993abb7,
0xacb0ac5d,0x9cb6ad96,0x2ddc29f1,0xa765ac5d,0xa30e2fbc,0xaff82dfe,0xa17eaf30,0xafaf2ee9,0x2dfeaf1a,0x244e2d00,0xacd82faf,0x29342b5e,
0xb0002993,0x2fddae7c,0x2fddac32,0x2f6eaf46,0x2ddcb000,0x2fe6afd4,0x2ed0afd4,0xafff2f5a,0xad279fd9,0x2d00aee9,0xabb7a814,0xae1f2f91,
0xae5e2ff4,0x9fd9a8d5,0xaf302fa0,0xa44e2bb7,0x2c872515,0xadba2aaa,0x2a4e2993,0x2c87a765,0x2ff4ad72,0x2e1fac32,0x2e1fa515,0xa8759cb6,
0x2814ae99,0x2ffcaf6e,0x2dfeb000,0xae5e2c87,0xaf5a2b05,0x2eb5afbc,0xac5da44e,0xb0002f91,0xac322fa0,0x2993ad00,0xaf462faf,0xae7c2fa0,
0x2c871fd9,0x16482814,0xa9f12ee9,0x2e99af91,0x2f80afa0,0x2c32a875,0x2e7ca875,0x2aaaad27,0xa30eac32,0x2f1aaddc,0x2e1fafff,0xa30ea515,
0xafed2d96,0x2ffcafd4,0xab05a6a1,0xacd829f1,0xa8142e1f,0xadfe2f02,0xaffc2e3f,0x2e5ead27,0x2e99a993,0xaa4e2cb0,0xaa4e2ed0,0x2fd4af46,
0x2e7cb000,0x1cb625db,0x2ddca6a1,0x2fc9b000,0xa875a934,0x2b5ea814,0x2f1aafed,0x2e3faf30,0xaf302ff4,0xafed2fa0,0xa814a8d5,0xa9342bb7,
0x16482c32,0xafd42fff,0xafdd2ddc,0x16482515,0x2f46ac5d,0xaed02f6e,0xacb02f6e,0x2993a5db,0x2e1fafed,0xad002dfe,0x2bb71fd9,0x2d27ac07,
0xaf5a2cd8,0xac5d2b05,0x2eb5affc,0xb0002fed,0xae7c2ff4,0xaddc2d27,0x9cb6ab5e,0xafc92ff4,0x217e2aaa,0xaf022e7c,0xaf022c32,0xaf1a2f80,
0x2f30ac87,0xafbc2f6e,0xaee93000,0xadfe2e99,0xa8d5a515,0x2875a993,0x2e3faaaa,0xa8d52765,0xaf912d96,0x244ea6a1,0x2fbcafd4,0xab0529f1,
0xae992fed,0x96489fd9,0x29f1adfe,0xac872c07,0x9cb62bb7,0xa515217e,0xac32217e,0xad722d00,0x2c32ae99,0x2f46af5a,0xa9932d96,0x2e7cae99,
0xa875a44e,0x2f1aaf30,0x2b5e9fd9,0x2e3fae5e,0xaf302d27,0x2ee9af02,0x2fbcae3f,0x2dfeae1f,0xaf6e2fff,0x2eb5aed0,0x2eb5afe6,0x2dbaaddc,
0xaddcadba,0xafe6aeb5,0xaed0aeb5,0x2fff2f6e,0xae1fadfe,0xae3fafbc,0xaf02aee9,0x2d272f30,0xae5eae3f,0x9fd9ab5e,0xaf30af1a,0xa44e2875,
0xae99ae7c,0x2d962993,0xaf5aaf46,0xae99ac32,0xad00ad72,0xa17eac32,0xa17ea515,0xabb79cb6,0xac07ac87,0x2dfe29f1,0x1fd99648,0xafedae99,
0xa9f1ab05,0x2fd42fbc,0x26a1244e,0xad96af91,0xa765a8d5,0x2aaa2e3f,0x29932875,0x2515a8d5,0x2e992dfe,0x30002ee9,0x2f6e2fbc,0xac87af30,
0x2f802f1a,0x2c322f02,0x2e7c2f02,0x2aaaa17e,0x2ff42fc9,0xab5e1cb6,0x2d272ddc,0x2ff42e7c,0x2fed3000,0xaffcaeb5,0x2b052c5d,0x2cd82f5a,
0x2c072d27,0x9fd92bb7,0xadfead00,0x2fed2e1f,0x25db2993,0xaf6eacb0,0xaf6eaed0,0x2c5d2f46,0xa5151648,0xaddcafdd,0xafffafd4,0xac321648,
0xabb7a934,0x28d5a814,0xafa0afed,0xaff4af30,0xaf30ae3f,0xafedaf1a,0xa814ab5e,0xa9342875,0xb000afc9,0xa6a1addc,0x25db9cb6,0xb000ae7c,
0xaf46afd4,0x2ed02a4e,0x2cb02a4e,0xa993ae99,0xad27ae5e,0x2e3f2ffc,0x2f022dfe,0x2e1f2814,0xa9f1acd8,0x26a1ab05,0x2fd42ffc,0xad96afed,
0x2515a30e,0x2fff2e1f,0x2ddc2f1a,0x2c32a30e,0x2d272aaa,0x28752e7c,0x28752c32,0x2fa02f80,0x2f912e99,0xaee9a9f1,0xa8141648,0x9fd92c87,
0x2fa02e7c,0x2faf2f46,0xad00a993,0x2fa02c32,0x2f913000,0xa44e2c5d,0xafbcaeb5,0x2b052f5a,0x2c872e5e,0xb000adfe,0xaf6eaffc,0xae99a814,
0x9cb62875,0xa515ae1f,0xac32ae1f,0xad72aff4,0x27652c87,0xa9932a4e,0xaaaaadba,0xa5152c87,0xabb7a44e,0xafa0af30,0x28d59fd9,0xaff4ae5e,
0xaf91ae1f,0x2814abb7,0x2ee92d00,0x1fd9ad27,0xaf5aafff,0x2fd42ed0,0x2fd42fe6,0x30002ddc,0xaf46af6e,0xac32afdd,0xae7cafdd,0x29933000,
0x2b5ea934,0x2faf2cd8,0x2d00a44e,0xaf1aadfe,0x2ee92faf,0xaf30217e,0x2dfe2ff8,0x2fbc230e,0xac5d2765,0x29f1addc,0xad961cb6,0xac5d2cb0,
0x2bb7a993,0x2f1aa515,0x2f1a2765,0xaff4aaaa,0x2e5e2fd4,0xab052dba,0x29342f6e,0x2ee9a6a1,0xadba1fd9,0xa5dbafed,0xafddac07,0xaa4e2dfe,
0xacb0aff8,0x2ddc2f02,0x9cb6ae3f,0xa765aff8,0x2eb52f91,0x2a4e2fed,0x16482e5e,0x2c5dad4d,0xaddc217e,0xae7cae3f,0xafc9ae3f,0x9cb62fa0,
0xabb7afe6,0x2ff82993,0x2b5eaaaa,0xabb7afc9,0x2fbc2a4e,0xaf3025db,0x2dfe2fdd,0x2ee92dba,0xacd828d5,0xaf91230e,0xaf30af02,0x2c072fa0,
0xac5dafff,0x2dbaac32,0x2dbaa515,0xae99addc,0x2fc929f1,0xa9932eb5,0x2aaa2fdd,0x2fe629f1,0xa30e2dfe,0xa17eafed,0xaff8ac07,0xafaf1fd9,
0xadfeafaf,0xa814aff8,0x2e5ea17e,0xaffca30e,0x2f5a2515,0x2c872f46,0x26a12f80,0x2f5aa765,0x9cb62e99,0xae7cadba,0xafc9adba,0xaddc2c5d,
0xaf1aaee9,0x2faf2b05,0x2d00a934,0x2b5eae5e,0x2dbaa814,0x2fdd9fd9,0x25db2f91,0x2a4eaee9,0x27652faf,0xaf4628d5,0xaf80ae1f,0xa5152faf,
0xafa0addc,0x2e3fac32,0x2e3fa515,0xa17eafff,0x2dfea6a1,0xacd82dba,0x244e2f6e,0x29342fd4,0x2d272fc9,0x230e2fff,0xafafad72,0x2d272e7c,
0xaffcaa4e,0xa814afdd,0x2e5ea5db,0xadfeadba,0x2c5dac07,0x2a4e2f91,0x16482f30,0x2eb52cd8,0x29932ff4,0xac32af1a,0xae7caf1a,0xaf46abb7,
0xae7c26a1,0xafff1648,0x2d72aa4e,0xafc926a1,0x230eaee9,0x2ff89fd9,0x217e2f91,0x2fafa814,0x2d4d2fa0,0xafed230e,0xae5eaf02,0xaf9128d5,
0xb000aaaa,0x2fdda515,0x2fdd2765,0x2f6ea993,0x1cb6b000,0x2cb0afd4,0x2765afd4,0xaddc2f5a,0xa17e2ffc,0xaff42c07,0xa8752fbc,0x2ff8a934,
0x244eaff4,0x2dfe28d5,0x2934afa0,0xacd8abb7,0xa5db2fe6,0x9648af46,0xa9f12f80,0xa5db2fc9,0x2ff41cb6,0x2e1f2765,0x2e1f2cb0,0xa875addc,
0xafbca5db,0x1fd9af5a,0xad4dad96,0xacd82fdd,0x2f5a2934,0xaeb52ee9,0x2c5d2e5e,0x3000ab05,0xaed0ab5e,0x2f80a30e,0xaaaaaf02,0xacb0ab5e,
0xa5db2ffc,0xad962fbc,0xaf5a2c07,0x2fdda934,0x2aaaafa0,0x2fc9a875,0x2fe6a875,0xa993ad27,0xad002ed0,0xa8d5ad72,0xaff81cb6,0xad002fe6,
0x2e5ead96,0xad4d2fd4,0x2f9126a1,0x2feda9f1,0xafbca17e,0xad4da875,0x1fd9aff4,0xacd82ff8,0x2e992aaa,0xaa4e2fe6,0xaa4e2fc9,0x2fd4a993,
0xacb0ad96,0x2fffac87,0x2d72aeb5,0xa765ad96,0x28752f30,0xab5eac07,0xaf1a2cd8,0xae3f2f91,0x2934aff4,0x2e5eafa0,0x2ee928d5,0xab05abb7,
0xad962ed0,0xaeb51cb6,0xac87ad72,0xad962fe6,0x2f80ac5d,0xa7652f6e,0x25152f6e,0x2f46a5db,0xaff8244e,0x2ff4ad4d,0x2875affc,0x217eaee9,
0x2f5a244e,0x2c5d2934,0xaeb52dfe,0x3000acd8,0xacb0ad00,0x2d72aff8,0x2fffa8d5,0xa765ad00,0x217e2f80,0xaf022515,0xaf02a765,0xaf1a2f46,
0x2b05afdd,0xa8142f5a,0x2c072d96,0x2d4d25db,0xab5e2fe6,0xaf022f80,0xa30eaf46,0xab5e2fc9,0x2f30ad96,0x2cd826a1,0xac072fd4,0x2f91a9f1,
0xafdd244e,0x2d96affc,0x2f5aad4d,0x25dbaee9,0x2d722bb7,0xae7c217e,0xafc9217e,0xafff2d00,0xaed0a5db,0xaaaaa9f1,0x2f809648,0xacb0a5db,
0x28752e5e,0xaf1a2f91,0xab5ead4d,0xae3f2fed,0x2b05aff8,0x2c072875,0xa8142ff4,0x2d4d217e,0xaf6e2d72,0x2eb5afc9,0x2eb5ae7c,0x2dbaafff,
0x2f80af5a,0x2fc9ae99,0x2fe6ae99,0xaf462d96,0xa8d5ab05,0x2f02afed,0xa30eacd8,0xafa02ffc,0xafbc2f02,0x2934ad27,0xaffc2e1f,0xac072e3f,
0x26a12c32,0xaa4e1cb6,0x16482d72,0x26a12515,0x28752aaa,0xa8d52cb0,0xa8d52ed0,0x2e3faf80,0x2fedaeb5,0x29349648,0x2f30aa4e,0x2814ac5d,
0x1648ad4d,0x2e99acd8,0x2c87afbc,0xa9f11fd9,0xafe62d27,0x2fffafaf,0xaddc230e,0xaed02d27,0xafd42f30,0xaf6e2e5e,0xadba244e,0x26a11fd9,
0x9cb62d27,0xafe62ff4,0xaed02ff4,0x2d72ab5e,0x2fafacb0,0xae1f2f46,0x28d52993,0x2fafaed0,0x2c07af6e,0xa9342c87,0x2ffcae99,0x2fbcb000,
0xa44eab5e,0x2b05ad00,0x2f91afaf,0xafbc2f1a,0xafd42d72,0x1648a765,0x1648acb0,0xafdd2fff,0xac322f5a,0xaaaa26a1,0xaf802c87,0xae7c2f5a,
0x2d009fd9,0xae1f2cd8,0xad272fbc,0xabb72d4d,0x2ffcaf02,0x2ee9ae1f,0xa44e2d27,0x2d4dae3f,0x29f1ae7c,0x2fddaf80,0x2eb5aaaa,0x29f1ac32,
0xad7225db,0x2fe6b000,0x2ed0b000,0x1cb6a6a1,0xafa02fbc,0x2f02af91,0xa30eab05,0xa8d5244e,0x96482c07,0xac872d4d,0xae992b05,0x29f1a814,
0x2ed0abb7,0xa9932b5e,0xaf462ff8,0x2cb0abb7,0x2f1aafff,0xa30e2765,0xa30e2cb0,0x2e1fad72,0x1fd9ac5d,0x244e9648,0x2e5eaa4e,0x2f30aeb5,
0xaff82ed0,0xae3f2ddc,0x2f02afff,0xaff82fe6,0xad4d2f6e,0xaee92e99,0x244eac87,0xaffc3000,0x26a12814,0xaf6e2f30,0xadba2934,0xafd42fed,
0x2f46ad00,0xafc92fa0,0xafe62fa0,0xaf802faf,0x2515ac5d,0x2d72ad96,0x1cb629f1,0x2c32ac5d,0xad002814,0x2d27ad4d,0x2e1fab05,0x2bb7ac07,
0xaffc2f1a,0x2cd8ad00,0x2fedafaf,0x2b05ab5e,0xadba2f80,0x2c87acb0,0x2c87aed0,0x2a4eaaaa,0xaf80af6e,0xafc9afdd,0xafe6afdd,0x2f463000,
0xafa0af91,0xabb7ae5e,0xaff4afed,0x28d52d4d,0xafbcafaf,0x2934a17e,0xaffcaff8,0xac07a30e,0xafd4afc9,0x2f5a2d72,0xb000afff,0xafd4ae7c,
0x2bb72aaa,0x2f1a2cb0,0x2f1a2ed0,0xaff4af80,0x2cd82c5d,0x2f303000,0x2f912f5a,0xac07aeb5,0x2dba2d4d,0x25db2cd8,0x2fdd2fbc,0x2a4e9fd9,
0x2e7c2e1f,0xad72a875,0x2fff2ff4,0x2fc92e1f,0x26a12934,0xa9f1244e,0xad96acd8,0x2fd42dfe,0x9cb6217e,0xafe6ae3f,0xaed0ae3f,0x2d722fa0,
0xa875a515,0xad27af80,0xafa0af46,0xa8752765,0xac07aa4e,0x2934a5db,0xaffcafdd,0xafbcadba,0xae5eaf1a,0xa934ae3f,0x2b052875,0xaee9ab5e,
0xac5dad72,0x2dba2765,0x2dba2cb0,0xae99afff,0xa765aa4e,0x2f802fd4,0x2f462e99,0x2515aa4e,0x230e9fd9,0x217e2cd8,0x2ff82fbc,0x2faf2d4d,
0x2ffc2faf,0x2ee92ff8,0xa44e217e,0x2d4d230e,0x2f6e2fe6,0xa5db2aaa,0xac5da993,0x2f6e2fc9,0x2d722e99,0xafe6adba,0xaed0adba,0x9cb62c5d,
0x28d52c07,0xabb7af30,0xaff4af91,0xafa0acd8,0xadbaac07,0xafddad4d,0xa5dbab05,0xaa4e2814,0xafc9af02,0xaaaaaf1a,0x2993217e,0xafe6af02,
0xafa0afff,0x2e3f2765,0x2e3f2cb0,0xa17ead72,0xad4daeb5,0x2e5e3000,0x2fed2f5a,0x2f912c5d,0x217ea765,0x2d009cb6,0x2bb72ddc,0x217eacb0,
0x2d4d2a4e,0x2ee92fdd,0xa44e25db,0x2ffc2dba,0x2fd42ee9,0xa9f12934,0xad96ab05,0x26a12e5e,0x2f462ff4,0xafc9af1a,0xafe6af1a,0xaf80abb7,
0x2cb02eb5,0x1cb62dba,0xaddcaf6e,0x27652eb5,0xa30e2814,0xaff8ad4d,0xa17eab05,0xafafac07,0xadfeab5e,0xa44eae3f,0x2cd82875,0xa934af1a,
0xb000af80,0x2fdd2cb0,0x2fdd2ed0,0x2f6e2aaa,0xad72b000,0xa515afd4,0xac32afd4,0x9cb62f5a,0x2e1f1fd9,0x2e3f2ee9,0x2f022814,0xad27af91,
0x2cd82ff4,0xaffca8d5,0x2b052fa0,0x2fed2bb7,0xae99a515,0x2d96aaaa,0xaf5aa993,0xae992765,0x2ff42ddc,0x2e1f2ed0,0x2e1f2fe6,0xa875afff,
0xa8142c87,0xaffca9f1,0xadfe1648,0x2e5e2e99,0xaf5aaf30,0x2eb5a814,0xac5dafed,0xb000a934,0x2c32a8d5,0xa9932e3f,0x2f462875,0x2e7ca8d5,
0xae999fd9,0xb000a814,0xaf6eaee9,0x2c872f91,0xa993afa0,0x2ed0a875,0x2cb0a875,0xaf46ad27,0x2ff42c32,0xab5e2ddc,0x2d272fff,0x2ff42515,
0xa44e2d96,0x9fd9afd4,0xaf30a6a1,0xae5e29f1,0x2814ad27,0x2dfeabb7,0x2ffc2d00,0xae5eae1f,0x2e992f80,0xaa4e2e7c,0xaa4e2c32,0x2fd42aaa,
0xae7c1648,0x9cb6afdd,0xaddcafd4,0xafc91648,0xa875af91,0x2b5e2fbc,0x2f1a244e,0x2e3fab05,0x2b052ff4,0xa44e2fa0,0xafbca8d5,0x2f912bb7,
0xb000ac32,0xa6a1afff,0x25dbaddc,0xb000a515,0x2aaaac5d,0x2c322f6e,0x2e7c2f6e,0x2f80a5db,0x2d272fed,0xae3fadfe,0xaf029fd9,0xae1f2c07,
0xaf5aae5e,0xac5daf30,0x2eb59fd9,0xb000a44e,0x2e7ca30e,0x2ddc2e1f,0x1cb62f1a,0x2fc9a30e,0x217e2f46,0xaf02acb0,0xaf02aed0,0xaf1a2993,
0xaf30ae99,0x2fbc29f1,0x2ee99648,0x2dfeac87,0x2fa02515,0x2faf2993,0xad002aaa,0x2fa0a765,0xa9342d96,0xafeda6a1,0xa814afd4,0xaf3029f1,
0xac87afed,0x30001fd9,0x2f6e2dfe,0x2e99ac07,0x2fff2bb7,0xafe6217e,0xaed0217e,0xaddc2d00,0xac322c87,0xaf462a4e,0x2993adba,0xae7c2c87,
0xa875afed,0x2f1aab05,0x2b5e2ffc,0x2e3facd8,0x2f302e1f,0xaee92bb7,0xafbcad00,0xadfe2d27,0xaf6e9cb6,0x2eb5ac32,0x2eb5a515,0x2dbaad72,
0x2aaaaf5a,0x2ed0ae99,0x2cb0ae99,0xaf802d96,0xab5e2f30,0xafaf244e,0xad002e5e,0x2f1a1fd9,0x2c07af02,0x2b052d27,0x2d4dae1f,0xa814ae3f,
0xac5d2ed0,0x29f1afff,0xad962ddc,0xac5d2fe6,0x28752f80,0xa8d52fe6,0xa8d52fc9,0x2e3faf46,0xa44eafd4,0x2f91adba,0x2b05af6e,0xafbc26a1,
0x96482ffc,0xae99a44e,0xac872ee9,0x29f12d4d,0x2515aff8,0x1cb62f02,0x2d72ae3f,0x2c32aff8,0xaeb5ab05,0xaa4eacd8,0x9648afed,0xac5d2ffc,
0x2d722d27,0xacb02ff4,0xa7652ff4,0x2fffab5e,0xabb7ae7c,0x2ff8aaaa,0x2b5eaf80,0xabb7ac32,0x28142f6e,0xab05ac87,0xad4d2e99,0xac073000,
0x2feda8d5,0x2f30a30e,0x29342f02,0x2814afa0,0xafd49cb6,0x1648aed0,0x1648afe6,0xafdd2d72,0x2ed029f1,0xaf462eb5,0xa9932fdd,0x2cb029f1,
0xad00ad4d,0x2e1f244e,0x2d27aee9,0x2bb7affc,0xad4d2f02,0xafbc2e1f,0xacd8ad27,0x1fd92e3f,0x2f5aacb0,0x2c872993,0x26a12f46,0x2f5aaed0,
0xafff25db,0x2cb0b000,0x2765b000,0xad72a6a1,0x2f1a2814,0xafaf2934,0xad002f30,0xab5e2fed,0x1648afbc,0x2c87affc,0x2e992934,0xa9f1ac07,
0xac322faf,0xaf8028d5,0xaaaaae1f,0xae7c2faf,0x2f1aad72,0xa30e2ed0,0xa30e2fe6,0x2e1f1cb6,0xaffc26a1,0x2fedadba,0x2cd8af6e,0x2b05afd4,
0x2d272c32,0x230e2d72,0xafaf1cb6,0x2d272515,0x9fd9af6e,0x2fbcae99,0x2cd82c87,0x2d4db000,0xac5d2fbc,0xaa4eab05,0x9648af91,0xaeb5244e,
0x2f80ad00,0xaed02fa0,0xacb02fa0,0xaaaa2faf,0xafe626a1,0xaddc1648,0x2fffaa4e,0xaed026a1,0x2d002c07,0xad272ffc,0xae1fa934,0xabb72fbc,
0x1fd9afa0,0x2e5ea30e,0x244e2f02,0x2f30a8d5,0xadba2f46,0x2c87afe6,0x2c87afc9,0x2a4eaf80,0x2fffad96,0x2e7cac5d,0x2fc9ac5d,0xad7229f1,
0x217eadfe,0x2ff4afbc,0x2875aee9,0xaff82f30,0xafed2d00,0x2d4daf1a,0xaf912b5e,0xae5e2faf,0xa5db2e7c,0x9648a993,0xa9f12f46,0xa5db2c32,
0xae3f2fff,0xaff82fc9,0xaff82e7c,0x2f02ad72,0x2c0725db,0xadfe2f5a,0x9fd92d96,0x2fedafdd,0x2f6eaf91,0xa6a12c07,0x2fd4acd8,0x2dbaaf30,
0xa765ab5e,0x2aaaa30e,0x2993af02,0x2515ab5e,0x25dbadfe,0x2d96aee9,0x2f5aafbc,0xafdd2f30,0xaf462b5e,0x2765abb7,0xa515abb7,0xaf802ff8,
0xad002fc9,0xa8d51cb6,0xaff82ddc,0xad002e7c,0x2cd81648,0xadfe2c5d,0xa9342eb5,0xa44e2a4e,0x2c07217e,0x9fd92875,0xadfe2ff4,0x2fedaff8,
0x2fddaf46,0x29f1a515,0x29f12765,0x2eb5af80,0x2515ad96,0x2ddcac87,0x2fffaeb5,0x2c32ad96,0xaf022b05,0x2fa0aee9,0x28d5ae5e,0x230ea934,
0xaf912d00,0xacd82b5e,0x2c07af1a,0xaf302faf,0xad962fc9,0xaeb52ddc,0xac871cb6,0xad962e7c,0x299326a1,0xafc92f5a,0xafe62f5a,0xaaaa2c87,
0x2ff8ae5e,0xaff42ffc,0xa8752dfe,0xa17e2814,0x2f6eafed,0x2fd4af91,0xa6a12d4d,0x2dbaae5e,0x2515ad00,0x2fffaff8,0x2ddca8d5,0x2c32ad00,
0xae1f2993,0x2fafafe6,0x2fafafc9,0x28d5aaaa,0xaf912fdd,0x2ee9af5a,0x2814ad96,0x1fd9a5db,0xab5e2e7c,0xaf022f46,0xa30ea993,0xab5e2c32,
0x2b051648,0xae5e2eb5,0xaee92c5d,0xa9342a4e,0x2fddae5e,0xad962dfe,0xaf5a2ffc,0xa5db2814,0x2ddcafaf,0xacb02d27,0xa7652d27,0x9cb6230e,
0xa765a5db,0x2993a9f1,0x2aaa9648,0x2515a5db,0xaf022cd8,0x28d5a934,0x2fa0adfe,0x230ea44e,0xaf912ff8,0x2814a875,0x2ee9aff4,0x1fd9a17e,
0xaa4e2ddc,0x26a1a765,0x26a1acb0,0x16489cb6,0x9d7f9e49,0xaddcaeb3,0x12480000,0x22ad0000,0x9bdb9cb6,0xac2ead04,0x18b61648,0x290226ad,
0x98b69a49,0xa902aaaf,0x1bdb1a49,0x2c2e2aaf,0x92489648,0xa2ada6ad,0x1d7f1cb6,0x2ddc2d04,0xa420a4b7,0xae8daf7f,0x18b60000,0x23760000,
0xa1e4a312,0xacacad9c,0x1f121cb6,0x29992777,0x9f12a0b6,0xa999ab78,0x21e420b6,0x2cac2b78,0x98b69cb6,0xa376a777,0x24202312,0x2e8d2d9c,
0xa6e0a7db,0xaf3fb025,0x1bdb0000,0x24200000,0xa4e9a5e4,0xad2aae34,0x21e41fdb,0x2a312820,0xa1e4a3db,0xaa31ac21,0x24e923db,0x2d2a2c21,
0x9bdb9fdb,0xa420a820,0x26e025e4,0x2f3f2e34,0xa8d0a980,0xaff2b08c,0x1d7f0000,0x24840000,0xa6e0a820,0xada9aecd,0x2420217f,0x2ac82885,
0xa420a580,0xaac8ac86,0x26e02580,0x2da92c86,0x9d7fa17f,0xa484a885,0x28d02820,0x2ff22ecd,0xaa31ab13,0xb052b0f3,0x1f120000,0x24e90000,
0xa86ba94e,0xae28af65,0x254d2312,0x2b5f28e9,0xa54da712,0xab5faceb,0x286b2712,0x2e282ceb,0x9f12a312,0xa4e9a8e9,0x2a31294e,0x30522f65,
0xab91ac54,0xb0acb15a,0x20520000,0x254d0000,0xa967aa7c,0xaea7affe,0x267b2452,0x2bf6294e,0xa67ba852,0xabf6ad50,0x29672852,0x2ea72d50,
0xa052a452,0xa54da94e,0x2b912a7c,0x30ac2ffe,0xac79ad1e,0xb106b1c1,0x211b0000,0x25b20000,0xaa63abab,0xaf26b04c,0x27a9251b,0x2c4729b3,
0xa7a9a91c,0xac47adb6,0x2a63291c,0x2f262db6,0xa11ba51b,0xa5b2a9b3,0x2c792bab,0x3106304c,0xad2aade8,0xb160b229,0x21e40000,0x26170000,
0xab5fac6d,0xafa5b099,0x286b25e4,0x2c932a17,0xa86ba9e5,0xac93ae1b,0x2b5f29e5,0x2fa52e1b,0xa1e4a5e4,0xa617aa17,0x2d2a2c6d,0x31603099,
0xb1bbb292,0xb44fb4f6,0x267b0000,0x28d00000,0xb012b0e6,0xb216b357,0x2cde2a7c,0x2f3f2cd2,0xacdeae80,0xaf3fb0d9,0x30122e80,0x321630d9,
0xa67baa7c,0xa8d0acd2,0x31bb30e6,0x344f3357,0xb216b2fb,0xb47eb52d,0x26e00000,0x29020000,0xb052b133,0xb257b3a7,0x2d2a2ae1,0x2f8c2d04,
0xad2aaee6,0xaf8cb10c,0x30522ee6,0x3257310c,0xa6e0aae1,0xa902ad04,0x32163133,0x347e33a7,0xb271b364,0xb4aeb565,0x27440000,0x29350000,
0xb092b181,0xb298b3f7,0x2d762b46,0x2fd82d37,0xad76af4c,0xafd8b140,0x30922f4c,0x32983140,0xa744ab46,0xa935ad37,0x32713181,0x34ae33f7,
0xb2cdb3cf,0xb4deb59d,0x27a90000,0x29670000,0xb0d2b1ce,0xb2dab423,0x2dc22bab,0x30122d6a,0xadc2afb2,0xb012b174,0x30d22fb2,0x32da3174,
0xa7a9abab,0xa967ad6a,0x32cd31ce,0x34de3423,0xb329b41d,0xb50eb5d6,0x28070000,0x29990000,0xb113b21c,0xb31cb44c,0x2e0e2c08,0x30392d9c,
0xae0eb00c,0xb039b1a7,0x3113300c,0x331c31a7,0xa807ac08,0xa999ad9c,0x3329321c,0x350e344c,0xb386b453,0xb53fb60f,0x28390000,0x29cc0000,
0xb153b26b,0xb35eb474,0x2e5a2c3a,0x305f2dcf,0xae5ab03f,0xb05fb1db,0x3153303f,0x335e31db,0xa839ac3a,0xa9ccadcf,0x3386326b,0x353f3474,
0xb3e3b489,0xb570b649,0x286b0000,0x29fe0000,0xb194b2b9,0xb3a0b49d,0x2ea72c6d,0x30852e02,0xaea7b072,0xb085b20f,0x31943072,0x33a0320f,
0xa86bac6d,0xa9feae02,0x33e332b9,0x3570349d,0xb420b4bf,0xb5a1b683,0x289e0000,0x2a310000,0xb1d5b308,0xb3e3b4c6,0x2ef32c9f,0x30ac2e34,
0xaef3b0a5,0xb0acb243,0x31d530a5,0x33e33243,0xa89eac9f,0xaa31ae34,0x34203308,0x35a134c6,0xb5d2b6be,0xb76fb857,0x2a630000,0x2bf60000,
0xb413b4ef,0xb523b642,0x30d22e67,0x32092ffe,0xb0d2b278,0xb209b40f,0x34133278,0x3523340f,0xaa63ae67,0xabf6affe,0x35d234ef,0x376f3642,
0xb604b6fa,0xb7a5b878,0x2a950000,0x2c140000,0xb434b519,0xb546b66d,0x30f92e9a,0x32303019,0xb0f9b2ac,0xb230b42a,0x343432ac,0x3546342a,
0xaa95ae9a,0xac14b019,0x36043519,0x37a5366d,0xb637b736,0xb7dbb899,0x2ac80000,0x2c2e0000,0xb456b542,0xb569b699,0x31202ecd,0x32573032,
0xb120b2e1,0xb257b445,0x345632e1,0x35693445,0xaac8aecd,0xac2eb032,0x36373542,0x37db3699,0xb66ab773,0xb809b8bb,0x2afa0000,0x2c470000,
0xb478b56c,0xb58cb6c6,0x31462f00,0x327e304c,0xb146b315,0xb27eb460,0x34783315,0x358c3460,0xaafaaf00,0xac47b04c,0x366a356c,0x380936c6,
0xb69db7b0,0xb825b8dd,0x2b2d0000,0x2c600000,0xb49ab596,0xb5afb6f2,0x316d2f32,0x32a53065,0xb16db34a,0xb2a5b47b,0x349a334a,0x35af347b,
0xab2daf32,0xac60b065,0x369d3596,0x382536f2,0xb6d1b7ee,0xb841b8ff,0x2b5f0000,0x2c790000,0xb4bcb5c1,0xb5d2b71f,0x31942f65,0x32cd307f,
0xb194b37f,0xb2cdb496,0x34bc337f,0x35d23496,0xab5faf65,0xac79b07f,0x36d135c1,0x3841371f,0xb705b817,0xb85db923,0x2b910000,0x2c930000,
0xb4deb5eb,0xb5f6b74d,0x31bb2f98,0x32f43099,0xb1bbb3b4,0xb2f4b4b1,0x34de33b4,0x35f634b1,0xab91af98,0xac93b099,0x370535eb,0x385d374d,
0xb73ab837,0xb87ab946,0x2bc40000,0x2cac0000,0xb500b616,0xb61ab77a,0x31e22fcb,0x331c30b2,0xb1e2b3e9,0xb31cb4cd,0x350033e9,0x361a34cd,
0xabc4afcb,0xacacb0b2,0x373a3616,0x387a377a,0xb897b96b,0xb98dbaa6,0x2cc50000,0x2d900000,0xb63eb7a8,0xb767b895,0x334330cc,0x3442319a,
0xb343b4e8,0xb442b5c8,0x363e34e8,0x376735c8,0xacc5b0cc,0xad90b19a,0x389737a8,0x398d3895,0xb8b4b990,0xb9aebad1,0x2cde0000,0x2da90000,
0xb662b7d7,0xb78db8ae,0x336b30e6,0x345631b4,0xb36bb504,0xb456b5e4,0x36623504,0x378d35e4,0xacdeb0e6,0xada9b1b4,0x38b437d7,0x39ae38ae,
0xb8d2b9b5,0xb9cfbafd,0x2cf80000,0x2dc20000,0xb687b803,0xb7b4b8c7,0x339330ff,0x346a31ce,0xb393b51f,0xb46ab601,0x3687351f,0x37b43601,
0xacf8b0ff,0xadc2b1ce,0x38d23803,0x39cf38c7,0xb8f0b9dc,0xb9f1bb29,0x2d110000,0x2ddc0000,0xb6acb81b,0xb7dbb8e1,0x33bb3119,0x347e31e8,
0xb3bbb53b,0xb47eb61e,0x36ac353b,0x37db361e,0xad11b119,0xaddcb1e8,0x38f0381b,0x39f138e1,0xb90fba02,0xba14bb57,0x2d2a0000,0x2df50000,
0xb6d1b833,0xb801b8fb,0x33e33133,0x34933202,0xb3e3b557,0xb493b63a,0x36d13557,0x3801363a,0xad2ab133,0xadf5b202,0x390f3833,0x3a1438fb,
0xb92eba2a,0xba37bb86,0x2d440000,0x2e0e0000,0xb6f6b84b,0xb815b915,0x3405314d,0x34a7321c,0xb405b573,0xb4a7b657,0x36f63573,0x38153657,
0xad44b14d,0xae0eb21c,0x392e384b,0x3a373915,0xb94dba53,0xba5abbb6,0x2d5d0000,0x2e280000,0xb71bb863,0xb829b930,0x34193167,0x34bc3236,
0xb419b58f,0xb4bcb675,0x371b358f,0x38293675,0xad5db167,0xae28b236,0x394d3863,0x3a5a3930,0xb96dba7c,0xba7ebbe7,0x2d760000,0x2e410000,
0xb741b87c,0xb83db94b,0x342e3181,0x34d03250,0xb42eb5ab,0xb4d0b692,0x374135ab,0x383d3692,0xad76b181,0xae41b250,0x396d387c,0x3a7e394b,
0xa17fa248,0xb1cfb2a1,0x16480000,0x26ad0000,0x9fdba0b6,0xb029b0fd,0x1cb61a48,0x2d002aac,0x9cb69e48,0xad00aeaa,0x1fdb1e48,0x30292eaa,
0x96489a48,0xa6adaaac,0x217f20b6,0x31cf30fd,0xa81fa8b6,0xb27cb365,0x1cb60000,0x27760000,0xa5e4a711,0xb0a6b191,0x231120b6,0x2d972b75,
0xa311a4b6,0xad97af72,0x25e424b6,0x30a62f72,0x9cb6a0b6,0xa776ab75,0x281f2711,0x327c3191,0xaadeabd9,0xb328b414,0x1fdb0000,0x281f0000,
0xa8e8a9e3,0xb122b226,0x25e423db,0x2e2d2c1f,0xa5e4a7da,0xae2db01d,0x28e827da,0x3122301d,0x9fdba3db,0xa81fac1f,0x2ade29e3,0x33283226,
0xaccead7e,0xb3d3b475,0x217f0000,0x28840000,0xaadeac1f,0xb19eb2b9,0x281f257f,0x2ec32c83,0xa81fa97f,0xaec3b080,0x2ade297f,0x319e3080,
0xa17fa57f,0xa884ac83,0x2cce2c1f,0x33d332b9,0xae2daf0e,0xb43eb4d5,0x23110000,0x28e80000,0xac6aad4c,0xb219b34c,0x294d2711,0x2f592ce7,
0xa94dab11,0xaf59b0e4,0x2c6a2b11,0x321930e4,0xa311a711,0xa8e8ace7,0x2e2d2d4c,0x343e334c,0xaf8bb04e,0xb493b534,0x24520000,0x294d0000,
0xad65ae78,0xb294b3df,0x2a7a2852,0x2fef2d4c,0xaa7aac51,0xafefb147,0x2d652c51,0x32943147,0xa452a852,0xa94dad4c,0x2f8b2e78,0x349333df,
0xb074b115,0xb4e7b593,0x251b0000,0x29b10000,0xae5fafa4,0xb30fb438,0x2ba7291b,0x30422db0,0xaba7ad1a,0xb042b1aa,0x2e5f2d1a,0x330f31aa,
0xa51ba91b,0xa9b1adb0,0x30742fa4,0x34e73438,0xb122b1db,0xb53ab5f1,0x25e40000,0x2a160000,0xaf59b067,0xb389b481,0x2c6a29e3,0x308d2e14,
0xac6aade2,0xb08db20d,0x2f592de2,0x3389320d,0xa5e4a9e3,0xaa16ae14,0x31223067,0x353a3481,0xb58db64e,0xb805b887,0x2a7a0000,0x2cce0000,
0xb402b4c9,0xb5dfb6f9,0x30d72e78,0x332830cb,0xb0d7b26f,0xb328b4bd,0x3402326f,0x35df34bd,0xaa7aae78,0xacceb0cb,0x358d34c9,0x380536f9,
0xb5dfb6aa,0xb82ab8b0,0x2ade0000,0x2d000000,0xb43eb511,0xb61ab73d,0x31222edc,0x337130fd,0xb122b2d2,0xb371b4ed,0x343e32d2,0x361a34ed,
0xaadeaedc,0xad00b0fd,0x35df3511,0x382a373d,0xb631b705,0xb850b8d8,0x2b430000,0x2d330000,0xb47bb558,0xb654b780,0x316c2f40,0x33ba312e,
0xb16cb334,0xb3bab51d,0x347b3334,0x3654351d,0xab43af40,0xad33b12e,0x36313558,0x38503780,0xb682b75e,0xb874b900,0x2ba70000,0x2d650000,
0xb4b7b59f,0xb68db7c2,0x31b62fa4,0x34023160,0xb1b6b396,0xb402b54c,0x34b73396,0x368d354c,0xaba7afa4,0xad65b160,0x3682359f,0x387437c2,
0xb6d2b7b7,0xb899b927,0x2c060000,0x2d970000,0xb4f3b5e5,0xb6c6b802,0x32013004,0x34263191,0xb201b3f7,0xb426b57c,0x34f333f7,0x36c6357c,
0xac06b004,0xad97b191,0x36d235e5,0x38993802,0xb721b807,0xb8bcb94d,0x2c380000,0x2dc90000,0xb52fb62b,0xb6ffb822,0x324b3036,0x344b31c3,
0xb24bb42c,0xb44bb5ab,0x352f342c,0x36ff35ab,0xac38b036,0xadc9b1c3,0x3721362b,0x38bc3822,0xb76fb832,0xb8e0b972,0x2c6a0000,0x2dfb0000,
0xb56ab670,0xb737b842,0x32943067,0x346f31f4,0xb294b45d,0xb46fb5da,0x356a345d,0x373735da,0xac6ab067,0xadfbb1f4,0x376f3670,0x38e03842,
0xb7bdb85d,0xb902b996,0x2c9c0000,0x2e2d0000,0xb5a5b6b5,0xb76fb862,0x32de3099,0x34933226,0xb2deb48d,0xb493b608,0x35a5348d,0x376f3608,
0xac9cb099,0xae2db226,0x37bd36b5,0x39023862,0xb924b9ba,0xba1dbab5,0x2e5f0000,0x2fef0000,0xb7a6b881,0xb8a8b96d,0x34b73257,0x35d433df,
0xb4b7b637,0xb5d4b7a1,0x37a63637,0x38a837a1,0xae5fb257,0xafefb3df,0x39243881,0x3a1d396d,0xb946b9dc,0xba39bad0,0x2e910000,0x30100000,
0xb7ddb8a0,0xb8c1b989,0x34db3288,0x35f73408,0xb4dbb665,0xb5f7b7cd,0x37dd3665,0x38c137cd,0xae91b288,0xb010b408,0x394638a0,0x3a393989,
0xb966b9fe,0xba54bae9,0x2ec30000,0x30290000,0xb80ab8bf,0xb8dbb9a4,0x34ff32b9,0x361a3420,0xb4ffb693,0xb61ab7f9,0x380a3693,0x38db37f9,
0xaec3b2b9,0xb029b420,0x396638bf,0x3a5439a4,0xb986ba1f,0xba6fbb02,0x2ef50000,0x30420000,0xb825b8dd,0xb8f3b9be,0x352332ea,0x363c3438,
0xb523b6c1,0xb63cb812,0x382536c1,0x38f33812,0xaef5b2ea,0xb042b438,0x398638dd,0x3a6f39be,0xb9a6ba3f,0xba89bb1a,0x2f270000,0x305b0000,
0xb840b8fb,0xb90cb9d8,0x3546331b,0x365f3451,0xb546b6ee,0xb65fb828,0x384036ee,0x390c3828,0xaf27b31b,0xb05bb451,0x39a638fb,0x3a8939d8,
0xb9c5ba5e,0xbaa2bb30,0x2f590000,0x30740000,0xb85ab918,0xb924b9f2,0x356a334c,0x36823469,0xb56ab71b,0xb682b83d,0x385a371b,0x3924383d,
0xaf59b34c,0xb074b469,0x39c53918,0x3aa239f2,0xb9e3ba7c,0xbababb46,0x2f8b0000,0x308d0000,0xb874b935,0xb93cba0b,0x358d337d,0x36a43481,
0xb58db748,0xb6a4b852,0x38743748,0x393c3852,0xaf8bb37d,0xb08db481,0x39e33935,0x3aba3a0b,0xba00ba99,0xbad1bb5a,0x2fbd0000,0x30a60000,
0xb88eb951,0xb954ba23,0x35b133ae,0x36c63499,0xb5b1b775,0xb6c6b867,0x388e3775,0x39543867,0xafbdb3ae,0xb0a6b499,0x3a003951,0x3ad13a23,
0xbae8bb6e,0xbb7fbbdd,0x30be0000,0x31850000,0xb96bba3b,0xba19bae6,0x36e834b1,0x37f33570,0xb6e8b87c,0xb7f3b91d,0x396b387c,0x3a19391d,
0xb0beb4b1,0xb185b570,0x3ae83a3b,0x3b7f3ae6,0xbafebb80,0xbb8ebbe6,0x30d70000,0x319e0000,0xb982ba52,0xba2dbaf9,0x370a34c9,0x380a3587,
0xb70ab891,0xb80ab930,0x39823891,0x3a2d3930,0xb0d7b4c9,0xb19eb587,0x3afe3a52,0x3b8e3af9,0xbb13bb91,0xbb9cbbed,0x30f00000,0x31b60000,
0xb999ba69,0xba41bb0b,0x372c34e1,0x381a359f,0xb72cb8a6,0xb81ab943,0x399938a6,0x3a413943,0xb0f0b4e1,0xb1b6b59f,0x3b133a69,0x3b9c3b0b,
0xbb27bba0,0xbba9bbf4,0x31090000,0x31cf0000,0xb9afba7f,0xba54bb1d,0x374e34f9,0x382a35b6,0xb74eb8ba,0xb82ab956,0x39af38ba,0x3a543956,
0xb109b4f9,0xb1cfb5b6,0x3b273a7f,0x3ba93b1d,0xbb3abbaf,0xbbb5bbf8,0x31220000,0x31e80000,0xb9c5ba95,0xba67bb2e,0x376f3511,0x383a35ce,
0xb76fb8ce,0xb83ab969,0x39c538ce,0x3a673969,0xb122b511,0xb1e8b5ce,0x3b3a3a95,0x3bb53b2e,0xbb4cbbbc,0xbbc0bbfc,0x313b0000,0x32010000,
0xb9dabaaa,0xba7abb3e,0x37903529,0x384a35e5,0xb790b8e2,0xb84ab97b,0x39da38e2,0x3a7a397b,0xb13bb529,0xb201b5e5,0x3b4c3aaa,0x3bc03b3e,
0xbb5ebbc9,0xbbcbbbff,0x31530000,0x32190000,0xb9f0babf,0xba8cbb4e,0x37b23540,0x385a35fd,0xb7b2b8f6,0xb85ab98d,0x39f038f6,0x3a8c398d,
0xb153b540,0xb219b5fd,0x3b5e3abf,0x3bcb3b4e,0xbb6fbbd4,0xbbd4bc00,0x316c0000,0x32320000,0xba04bad3,0xba9ebb5d,0x37d23558,0x386a3614,
0xb7d2b909,0xb86ab99f,0x3a043909,0x3a9e399f,0xb16cb558,0xb232b614,0x3b6f3ad3,0x3bd43b5d,0x0,0x0,0x0,0x0,
0x2e1f0000,0x336431a8,0x33643400,0x2e1f31a8,0x31a80000,0x31a83400,0xb1a80000,0xb1a8b400,0x33640000,0xae1f31a8,0xae1fb400,0x336431a8,
0x34000000,0xb4000000,0x34000000,0xb4000000,0x33640000,0xae1fb1a8,0xae1f3400,0x3364b1a8,0x31a80000,0x31a8b400,0xb1a80000,0xb1a83400,
0x2e1f0000,0x3364b1a8,0x3364b400,0x2e1fb1a8,0x0,0x0,0x0,0x0,0xae1f0000,0xb36431a8,0xb3643400,0xae1f31a8,
0xb1a80000,0xb1a83400,0x31a80000,0x31a8b400,0xb3640000,0x2e1f31a8,0x2e1fb400,0xb36431a8,0xb4000000,0x34000000,0xb4000000,0x34000000,
0xb3640000,0x2e1fb1a8,0x2e1f3400,0xb364b1a8,0xb1a80000,0xb1a8b400,0x31a80000,0x31a83400,0xae1f0000,0xb364b1a8,0xb364b400,0xae1fb1a8,
0x0,0x0,0x0,0x0,0xae1f0000,0xb364b1a8,0xb364b400,0xae1fb1a8,0x31a80000,0x31a83400,0xb1a80000,0xb1a8b400,
0xb3640000,0x2e1fb1a8,0x2e1f3400,0xb364b1a8,0x34000000,0xb4000000,0x34000000,0xb4000000,0xb3640000,0x2e1f31a8,0x2e1fb400,0xb36431a8,
0x31a80000,0x31a8b400,0xb1a80000,0xb1a83400,0xae1f0000,0xb36431a8,0xb3643400,0xae1f31a8,0x0,0x0,0x0,0x0,
0x2e1f0000,0x3364b1a8,0x3364b400,0x2e1fb1a8,0xb1a80000,0xb1a83400,0x31a80000,0x31a8b400,0x33640000,0xae1fb1a8,0xae1f3400,0x3364b1a8,
0xb4000000,0x34000000,0xb4000000,0x34000000,0x33640000,0xae1f31a8,0xae1fb400,0x336431a8,0xb1a80000,0xb1a8b400,0x31a80000,0x31a83400,
0x2e1f0000,0x336431a8,0x33643400,0x2e1f31a8,0x34003400,0x34003400,0x34003400,0x34003400,0x33643400,0x2e1f31a8,0xae1f0000,0xb364b1a8,
0x31a83400,0xb1a80000,0xb1a8b400,0x31a80000,0x2e1f3400,0xb364b1a8,0x33640000,0xae1f31a8,0x3400,0xb400,0x3400,0xb400,
0xae1f3400,0x3364b1a8,0xb3640000,0x2e1f31a8,0xb1a83400,0x31a80000,0x31a8b400,0xb1a80000,0xb3643400,0xae1f31a8,0x2e1f0000,0x3364b1a8,
0xb4003400,0xb4003400,0xb4003400,0xb4003400,0xb3643400,0xae1f31a8,0x2e1f0000,0x3364b1a8,0xb1a83400,0x31a80000,0x31a8b400,0xb1a80000,
0xae1f3400,0x3364b1a8,0xb3640000,0x2e1f31a8,0x3400,0xb400,0x3400,0xb400,0x2e1f3400,0xb364b1a8,0x33640000,0xae1f31a8,
0x31a83400,0xb1a80000,0xb1a8b400,0x31a80000,0x33643400,0x2e1f31a8,0xae1f0000,0xb364b1a8,0x34003400,0x34003400,0x34003400,0x34003400,
0xb364b400,0xae1fb1a8,0x2e1f0000,0x336431a8,0x31a83400,0xb1a80000,0xb1a8b400,0x31a80000,0xae1fb400,0x336431a8,0xb3640000,0x2e1fb1a8,
0x3400,0xb400,0x3400,0xb400,0x2e1fb400,0xb36431a8,0x33640000,0xae1fb1a8,0xb1a83400,0x31a80000,0x31a8b400,0xb1a80000,
0x3364b400,0x2e1fb1a8,0xae1f0000,0xb36431a8,0xb4003400,0xb4003400,0xb4003400,0xb4003400,0x3364b400,0x2e1fb1a8,0xae1f0000,0xb36431a8,
0xb1a83400,0x31a80000,0x31a8b400,0xb1a80000,0x2e1fb400,0xb36431a8,0x33640000,0xae1fb1a8,0x3400,0xb400,0x3400,0xb400,
0xae1fb400,0x336431a8,0xb3640000,0x2e1fb1a8,0x31a83400,0xb1a80000,0xb1a8b400,0x31a80000,0xb364b400,0xae1fb1a8,0x2e1f0000,0x336431a8,
0x0,0x0,0x0,0x0,0xae1f0000,0xb364b1a8,0xb364b400,0xae1fb1a8,0xb1a80000,0xb1a8b400,0x31a80000,0x31a83400,
0xb3640000,0x2e1fb1a8,0x2e1f3400,0xb364b1a8,0xb4000000,0x34000000,0xb4000000,0x34000000,0xb3640000,0x2e1f31a8,0x2e1fb400,0xb36431a8,
0xb1a80000,0xb1a83400,0x31a80000,0x31a8b400,0xae1f0000,0xb36431a8,0xb3643400,0xae1f31a8,0x0,0x0,0x0,0x0,
0x2e1f0000,0x3364b1a8,0x3364b400,0x2e1fb1a8,0x31a80000,0x31a8b400,0xb1a80000,0xb1a83400,0x33640000,0xae1fb1a8,0xae1f3400,0x3364b1a8,
0x34000000,0xb4000000,0x34000000,0xb4000000,0x33640000,0xae1f31a8,0xae1fb400,0x336431a8,0x31a80000,0x31a83400,0xb1a80000,0xb1a8b400,
0x2e1f0000,0x336431a8,0x33643400,0x2e1f31a8,0x0,0x0,0x0,0x0,0x2e1f0000,0x336431a8,0x33643400,0x2e1f31a8,
0xb1a80000,0xb1a8b400,0x31a80000,0x31a83400,0x33640000,0xae1f31a8,0xae1fb400,0x336431a8,0xb4000000,0x34000000,0xb4000000,0x34000000,
0x33640000,0xae1fb1a8,0xae1f3400,0x3364b1a8,0xb1a80000,0xb1a83400,0x31a80000,0x31a8b400,0x2e1f0000,0x3364b1a8,0x3364b400,0x2e1fb1a8,
0x0,0x0,0x0,0x0,0xae1f0000,0xb36431a8,0xb3643400,0xae1f31a8,0x31a80000,0x31a8b400,0xb1a80000,0xb1a83400,
0xb3640000,0x2e1f31a8,0x2e1fb400,0xb36431a8,0x34000000,0xb4000000,0x34000000,0xb4000000,0xb3640000,0x2e1fb1a8,0x2e1f3400,0xb364b1a8,
0x31a80000,0x31a83400,0xb1a80000,0xb1a8b400,0xae1f0000,0xb364b1a8,0xb364b400,0xae1fb1a8,
};

typedef CUresult (*EncodeFn)(CUtensorMap*, CUtensorMapDataType, cuuint32_t, void*, const cuuint64_t*, const cuuint64_t*,
                             const cuuint32_t*, const cuuint32_t*, CUtensorMapInterleave, CUtensorMapSwizzle,
                             CUtensorMapL2promotion, CUtensorMapFloatOOBfill);

}

extern "C" void kernel_launch(void* const* d_in, const int* in_sizes, int n_in, void* d_out, int out_size) {
    Params p;
    p.x = (const __nv_bfloat16*)d_in[0];
    p.lar = (const __nv_bfloat16*)d_in[1];
    p.aim = (const __nv_bfloat16*)d_in[2];
    p.cr = (const __nv_bfloat16*)d_in[3];
    p.ci = (const __nv_bfloat16*)d_in[4];
    p.logdt = (const __nv_bfloat16*)d_in[5];
    p.dskip = (const __nv_bfloat16*)d_in[6];
    p.wr = (const __nv_bfloat16*)d_in[8];
    p.out = (__nv_bfloat16*)d_out;
    cudaGetSymbolAddress((void**)&p.sc, g_scratch);
    cudaGetSymbolAddress((void**)&p.tab, g_tab);

    void* fn = nullptr;
    cudaDriverEntryPointQueryResult qr;
    cudaGetDriverEntryPoint("cuTensorMapEncodeTiled", &fn, cudaEnableDefault, &qr);
    EncodeFn enc = (EncodeFn)fn;
    CUtensorMap tm_x, tm_g, tm_d, tm_o;
    const cuuint32_t es[5] = {1, 1, 1, 1, 1};
    {
        const cuuint64_t gd[5] = {1024, 4, 128, 2, 2}, gs[4] = {4096, 32768, 2048, 16384};
        const cuuint32_t bx[5] = {16, 4, 64, 1, 1};
        enc(&tm_x, CU_TENSOR_MAP_DATA_TYPE_BFLOAT16, 5, d_in[0], gd, gs, bx, es, CU_TENSOR_MAP_INTERLEAVE_NONE,
            CU_TENSOR_MAP_SWIZZLE_32B, CU_TENSOR_MAP_L2_PROMOTION_NONE, CU_TENSOR_MAP_FLOAT_OOB_FILL_NONE);
        const cuuint32_t bo[5] = {16, 4, 16, 1, 1};
        enc(&tm_o, CU_TENSOR_MAP_DATA_TYPE_BFLOAT16, 5, d_out, gd, gs, bo, es, CU_TENSOR_MAP_INTERLEAVE_NONE,
            CU_TENSOR_MAP_SWIZZLE_32B, CU_TENSOR_MAP_L2_PROMOTION_NONE, CU_TENSOR_MAP_FLOAT_OOB_FILL_NONE);
    }
    {
        char *wg = (char*)d_in[9], *wu = (char*)d_in[10];
        p.up_first = wu < wg;
        const cuuint64_t gd[3] = {3584, 1024, 2}, gs[2] = {7168, (cuuint64_t)(p.up_first ? wg - wu : wu - wg)};
        const cuuint32_t bx[3] = {64, 32, 2};
        enc(&tm_g, CU_TENSOR_MAP_DATA_TYPE_BFLOAT16, 3, p.up_first ? wu : wg, gd, gs, bx, es, CU_TENSOR_MAP_INTERLEAVE_NONE,
            CU_TENSOR_MAP_SWIZZLE_128B, CU_TENSOR_MAP_L2_PROMOTION_NONE, CU_TENSOR_MAP_FLOAT_OOB_FILL_NONE);
    }
    {
        const cuuint64_t gd[3] = {1024, 3584, 1}, gs[2] = {2048, 2048 * 3584};
        const cuuint32_t bx[3] = {64, 64, 1};
        enc(&tm_d, CU_TENSOR_MAP_DATA_TYPE_BFLOAT16, 3, d_in[11], gd, gs, bx, es, CU_TENSOR_MAP_INTERLEAVE_NONE,
            CU_TENSOR_MAP_SWIZZLE_128B, CU_TENSOR_MAP_L2_PROMOTION_NONE, CU_TENSOR_MAP_FLOAT_OOB_FILL_NONE);
    }
    cudaFuncSetAttribute(fused_kernel, cudaFuncAttributeMaxDynamicSharedMemorySize, SM_TOTAL + 256);
    fused_kernel<<<128, NTHREADS, SM_TOTAL + 256>>>(p, tm_x, tm_g, tm_d, tm_o);
}
```

```cpp
#include <cuda_runtime.h>
#include <cuda.h>
#include <cuda_bf16.h>
#include <cuda_fp16.h>
#include <stdint.h>

#define TG(i)
#define TS(i)
#define TSL(i)

#define TSW 0
#define SDELAY 2000
#define EDELAY 800
#define FILL 0xA2100
#define STSLEEP 200
#define IDEPTH 4

namespace {

constexpr int NTHREADS = 512;
constexpr int SPIN_LIMIT = 1 << 16;

constexpr int SM_SLAB = 0;
constexpr int SM_RING = 32768;
constexpr int SUB     = 1088;
constexpr int SM_K    = SM_RING + 10 * 8192;
constexpr int SM_S    = SM_K + 32 * SUB;
constexpr int SM_U    = SM_S + 32 * SUB;
constexpr int SM_F2   = SM_U + 32 * SUB;
constexpr int SM_XSEL = SM_F2 + 1536;
constexpr int SM_PAIR = SM_XSEL + 4096;
constexpr int SM_H    = SM_PAIR + 2048;
constexpr int SM_KEYS = SM_H + 1024;
constexpr int SM_TOK  = SM_KEYS + 64;
constexpr int SM_FIX  = SM_TOK + 16;
constexpr int SM_XRAW = SM_FIX + 32;
constexpr int SM_SCL  = SM_XRAW + 32;
constexpr int SM_BAR  = SM_SCL + 16;
constexpr int SM_RED  = SM_XSEL;
constexpr int SM_TAB  = SM_RING + 7 * 8192;
constexpr int B_FULL = 0, B_ROW = 24, B_STG = 32, B_SLAB = 36, B_TOK = 38, B_UFREE = 39, B_FIX = 40, B_PAIR = 41,
              B_TAB = 42, B_TFREE = 43, B_KFREE = 44, B_KEYS = 45, B_U = 46, B_PEER = 48, NBAR = 52;
constexpr int SM_TOTAL = SM_BAR + NBAR * 8;
static_assert(SM_TOTAL + 256 <= 232448, "smem");
__device__ __forceinline__ uint32_t chunk_off(int n) { return SM_RING + (n < 14 ? n : n - 14) * 8192; }
constexpr int KP = 272;

struct Scratch {
    uint4 stats[1024];
    uint32_t part[128 * 56 * 16];
    uint32_t epoch;
};
__device__ Scratch g_scratch;

struct Params {
    const __nv_bfloat16 *lar, *aim, *cr, *ci, *logdt, *dskip;
    const __nv_bfloat16 *x, *wr;
    __nv_bfloat16* out;
    Scratch* sc;
    const uint4* tab;
    int up_first;
};

__device__ __forceinline__ uint4 ldg128(const void* p) {
    uint4 v; asm volatile("ld.global.nc.v4.u32 {%0,%1,%2,%3}, [%4];" : "=r"(v.x), "=r"(v.y), "=r"(v.z), "=r"(v.w) : "l"(p)); return v;
}
__device__ __forceinline__ uint4 ld_relaxed128(const void* p) {
    uint4 v;
    asm volatile("{ .reg .b128 t; ld.relaxed.gpu.global.b128 t, [%4]; mov.b128 {%0,%1,%2,%3}, t; }"
                 : "=r"(v.x), "=r"(v.y), "=r"(v.z), "=r"(v.w) : "l"(p) : "memory");
    return v;
}
__device__ __forceinline__ void st_relaxed128(void* p, uint4 v) {
    asm volatile("{ .reg .b128 t; mov.b128 t, {%1,%2,%3,%4}; st.relaxed.gpu.global.b128 [%0], t; }"
                 :: "l"(p), "r"(v.x), "r"(v.y), "r"(v.z), "r"(v.w) : "memory");
}
__device__ __forceinline__ void st_relaxed32(void* p, uint32_t v) {
    asm volatile("st.relaxed.gpu.global.u32 [%0], %1;" :: "l"(p), "r"(v) : "memory");
}
__device__ __forceinline__ uint32_t lds32(uint32_t a) { uint32_t v; asm volatile("ld.shared.u32 %0, [%1];" : "=r"(v) : "r"(a)); return v; }
__device__ __forceinline__ uint32_t lds16(uint32_t a) { uint32_t v; asm volatile("ld.shared.u16 %0, [%1];" : "=r"(v) : "r"(a)); return v; }
__device__ __forceinline__ uint2 lds64(uint32_t a) { uint2 v; asm volatile("ld.shared.v2.u32 {%0,%1}, [%2];" : "=r"(v.x), "=r"(v.y) : "r"(a)); return v; }
__device__ __forceinline__ uint4 lds128(uint32_t a) {
    uint4 v; asm volatile("ld.shared.v4.u32 {%0,%1,%2,%3}, [%4];" : "=r"(v.x), "=r"(v.y), "=r"(v.z), "=r"(v.w) : "r"(a)); return v;
}
__device__ __forceinline__ void sts16(uint32_t a, uint32_t v) { asm volatile("st.shared.u16 [%0], %1;" :: "r"(a), "h"((uint16_t)v) : "memory"); }
__device__ __forceinline__ void sts32(uint32_t a, uint32_t v) { asm volatile("st.shared.u32 [%0], %1;" :: "r"(a), "r"(v) : "memory"); }
__device__ __forceinline__ void sts64(uint32_t a, uint32_t x, uint32_t y) { asm volatile("st.shared.v2.u32 [%0], {%1,%2};" :: "r"(a), "r"(x), "r"(y) : "memory"); }
__device__ __forceinline__ void sts128(uint32_t a, uint32_t x, uint32_t y, uint32_t z, uint32_t w) {
    asm volatile("st.shared.v4.u32 [%0], {%1,%2,%3,%4};" :: "r"(a), "r"(x), "r"(y), "r"(z), "r"(w) : "memory");
}
__device__ __forceinline__ void ldsm4(uint32_t a, uint32_t& r0, uint32_t& r1, uint32_t& r2, uint32_t& r3) {
    asm volatile("ldmatrix.sync.aligned.m8n8.x4.shared.b16 {%0,%1,%2,%3}, [%4];" : "=r"(r0), "=r"(r1), "=r"(r2), "=r"(r3) : "r"(a));
}
__device__ __forceinline__ void mma_f16(float (&d)[4], uint32_t a0, uint32_t a1, uint32_t a2, uint32_t a3, uint32_t b0, uint32_t b1) {
    asm("mma.sync.aligned.m16n8k16.row.col.f32.f16.f16.f32 {%0,%1,%2,%3}, {%4,%5,%6,%7}, {%8,%9}, {%0,%1,%2,%3};"
        : "+f"(d[0]), "+f"(d[1]), "+f"(d[2]), "+f"(d[3]) : "r"(a0), "r"(a1), "r"(a2), "r"(a3), "r"(b0), "r"(b1));
}
__device__ __forceinline__ void mma_bf16(float (&d)[4], uint32_t a0, uint32_t a1, uint32_t a2, uint32_t a3, uint32_t b0, uint32_t b1) {
    asm("mma.sync.aligned.m16n8k16.row.col.f32.bf16.bf16.f32 {%0,%1,%2,%3}, {%4,%5,%6,%7}, {%8,%9}, {%0,%1,%2,%3};"
        : "+f"(d[0]), "+f"(d[1]), "+f"(d[2]), "+f"(d[3]) : "r"(a0), "r"(a1), "r"(a2), "r"(a3), "r"(b0), "r"(b1));
}
__device__ __forceinline__ uint32_t prmt(uint32_t a, uint32_t b, uint32_t s) { uint32_t d; asm("prmt.b32 %0, %1, %2, %3;" : "=r"(d) : "r"(a), "r"(b), "r"(s)); return d; }
__device__ __forceinline__ uint32_t pack_h(float lo, float hi) { uint32_t d; asm("cvt.rn.f16x2.f32 %0, %1, %2;" : "=r"(d) : "f"(hi), "f"(lo)); return d; }
__device__ __forceinline__ uint32_t pack_b(float lo, float hi) { uint32_t d; asm("cvt.rn.bf16x2.f32 %0, %1, %2;" : "=r"(d) : "f"(hi), "f"(lo)); return d; }
__device__ __forceinline__ float blo(uint32_t v) { return __uint_as_float(v << 16); }
__device__ __forceinline__ float bhi(uint32_t v) { return __uint_as_float(v & 0xFFFF0000u); }
__device__ __forceinline__ float rb(float v) { return blo(pack_b(v, v)); }
__device__ __forceinline__ uint32_t bsub2(uint32_t a, uint32_t b) { uint32_t d; asm("sub.rn.bf16x2 %0, %1, %2;" : "=r"(d) : "r"(a), "r"(b)); return d; }
__device__ __forceinline__ uint32_t badd2(uint32_t a, uint32_t b) { uint32_t d; asm("add.rn.bf16x2 %0, %1, %2;" : "=r"(d) : "r"(a), "r"(b)); return d; }
__device__ __forceinline__ uint32_t bmul2(uint32_t a, uint32_t b) { uint32_t d; asm("mul.rn.bf16x2 %0, %1, %2;" : "=r"(d) : "r"(a), "r"(b)); return d; }
__device__ __forceinline__ uint32_t bfma2(uint32_t a, uint32_t b, uint32_t c) { uint32_t d; asm("fma.rn.bf16x2 %0, %1, %2, %3;" : "=r"(d) : "r"(a), "r"(b), "r"(c)); return d; }
__device__ __forceinline__ uint32_t dup_lo(uint32_t v) { uint32_t d; asm("{ .reg .b16 l, h; mov.b32 {l, h}, %1; mov.b32 %0, {l, l}; }" : "=r"(d) : "r"(v)); return d; }
__device__ __forceinline__ uint32_t dup_hi(uint32_t v) { uint32_t d; asm("{ .reg .b16 l, h; mov.b32 {l, h}, %1; mov.b32 %0, {h, h}; }" : "=r"(d) : "r"(v)); return d; }
__device__ __forceinline__ uint32_t norm2(uint32_t x, uint32_t m, uint32_t hi, uint32_t lo) {
    uint32_t a = bsub2(x, m);
    return bfma2(a, hi, bmul2(a, lo));
}
__device__ __forceinline__ float ex2(float v) { float d; asm("ex2.approx.ftz.f32 %0, %1;" : "=f"(d) : "f"(v)); return d; }
__device__ __forceinline__ float rcp(float v) { float d; asm("rcp.approx.ftz.f32 %0, %1;" : "=f"(d) : "f"(v)); return d; }
__device__ __forceinline__ float sigmoidf_(float v) { return rcp(1.0f + ex2(-1.4426950408889634f * v)); }
__device__ __forceinline__ float siluf_(float v) { return v * sigmoidf_(v); }

__device__ __forceinline__ void mbar_init(uint32_t a, int n) { asm volatile("mbarrier.init.shared::cta.b64 [%0], %1;" :: "r"(a), "r"(n) : "memory"); }
__device__ __forceinline__ void mbar_expect(uint32_t a, int tx) { asm volatile("mbarrier.arrive.expect_tx.shared::cta.b64 _, [%0], %1;" :: "r"(a), "r"(tx) : "memory"); }
__device__ __forceinline__ void mbar_arrive(uint32_t a) { asm volatile("mbarrier.arrive.shared::cta.b64 _, [%0];" :: "r"(a) : "memory"); }
__device__ __forceinline__ bool mbar_try(uint32_t a) {
    uint32_t d; asm volatile("{ .reg .pred p; mbarrier.try_wait.parity.shared::cta.b64 p, [%1], 0; selp.u32 %0, 1, 0, p; }" : "=r"(d) : "r"(a) : "memory"); return d;
}
__device__ __forceinline__ void mbar_wait(uint32_t a) {
    if (__builtin_expect(!mbar_try(a), 0)) {
        int n = SPIN_LIMIT;
        while (!mbar_try(a) && --n) {}
    }
}
__device__ __forceinline__ bool mbar_test(uint32_t a) {
    uint32_t d; asm volatile("{ .reg .pred p; mbarrier.test_wait.parity.shared::cta.b64 p, [%1], 0; selp.u32 %0, 1, 0, p; }" : "=r"(d) : "r"(a) : "memory"); return d;
}
__device__ __forceinline__ void mbar_arrive_peer(uint32_t a) { asm volatile("mbarrier.arrive.relaxed.cluster.shared::cluster.b64 _, [%0];" :: "r"(a) : "memory"); }
__device__ __forceinline__ uint32_t mapa(uint32_t a, uint32_t rank) { uint32_t d; asm("mapa.shared::cluster.u32 %0, %1, %2;" : "=r"(d) : "r"(a), "r"(rank)); return d; }
__device__ __forceinline__ void st_async2(uint32_t a, uint32_t x, uint32_t y, uint32_t bar) {
    asm volatile("st.async.weak.shared::cluster.mbarrier::complete_tx::bytes.v2.b32 [%0], {%1,%2}, [%3];" :: "r"(a), "r"(x), "r"(y), "r"(bar) : "memory");
}
__device__ __forceinline__ void st_async4(uint32_t a, uint32_t x, uint32_t y, uint32_t z, uint32_t w, uint32_t bar) {
    asm volatile("st.async.weak.shared::cluster.mbarrier::complete_tx::bytes.v4.b32 [%0], {%1,%2,%3,%4}, [%5];"
                 :: "r"(a), "r"(x), "r"(y), "r"(z), "r"(w), "r"(bar) : "memory");
}
__device__ __forceinline__ void stsm4(uint32_t a, uint32_t r0, uint32_t r1, uint32_t r2, uint32_t r3) {
    asm volatile("stmatrix.sync.aligned.m8n8.x4.shared.b16 [%0], {%1,%2,%3,%4};" :: "r"(a), "r"(r0), "r"(r1), "r"(r2), "r"(r3) : "memory");
}
__device__ __forceinline__ void proxy_fence() { asm volatile("fence.proxy.async.shared::cta;" ::: "memory"); }
__device__ __forceinline__ void bar_sync(int id, int n) { asm volatile("bar.sync %0, %1;" :: "r"(id), "r"(n) : "memory"); }
__device__ __forceinline__ void bar_arrive(int id, int n) { asm volatile("bar.arrive %0, %1;" :: "r"(id), "r"(n) : "memory"); }
__device__ __forceinline__ void cluster_arrive() { asm volatile("barrier.cluster.arrive.relaxed.aligned;" ::: "memory"); }
__device__ __forceinline__ void cluster_wait() { asm volatile("barrier.cluster.wait.aligned;" ::: "memory"); }
__device__ __forceinline__ void tma3d(uint32_t dst, const CUtensorMap* tm, int c0, int c1, uint32_t bar, uint64_t pol) {
    asm volatile("cp.async.bulk.tensor.3d.shared::cluster.global.mbarrier::complete_tx::bytes.L2::cache_hint [%0], [%1, {%3, %4, %6}], [%2], %5;"
                 :: "r"(dst), "l"(tm), "r"(bar), "r"(c0), "r"(c1), "l"(pol), "r"(0) : "memory");
}
__device__ __forceinline__ bool elect() {
    uint32_t p; asm volatile("{ .reg .pred p; elect.sync _|p, 0xFFFFFFFF; selp.u32 %0, 1, 0, p; }" : "=r"(p)); return p;
}

struct cf { float r, i; };
__device__ __forceinline__ cf cmul(cf a, cf b) { return {a.r * b.r - a.i * b.i, a.r * b.i + a.i * b.r}; }
__device__ __forceinline__ cf csq(cf a) { return {a.r * a.r - a.i * a.i, (a.r + a.r) * a.i}; }
__device__ __forceinline__ cf cexp_(float a2, float b) { float m = ex2(a2); return {m * __cosf(b), m * __sinf(b)}; }
struct hc { uint32_t r, i; };
__device__ __forceinline__ hc pk(cf a, cf b) { return {pack_h(a.r, b.r), pack_h(a.i, b.i)}; }
__device__ __forceinline__ hc hmulc(hc a, hc b) {
    const __half2 ar = *reinterpret_cast<__half2*>(&a.r), ai = *reinterpret_cast<__half2*>(&a.i);
    const __half2 br = *reinterpret_cast<__half2*>(&b.r), bi = *reinterpret_cast<__half2*>(&b.i);
    const __half2 r = __hfma2(ar, br, __hneg2(__hmul2_rn(ai, bi))), i = __hfma2(ar, bi, __hmul2_rn(ai, br));
    return {*reinterpret_cast<const uint32_t*>(&r), *reinterpret_cast<const uint32_t*>(&i)};
}
__device__ __forceinline__ void sth(uint32_t a, hc v) { sts32(a, v.r); sts32(a + 128, v.i); }
__device__ __forceinline__ uint32_t cpy(uint32_t v, uint32_t z) { uint32_t d; asm("xor.b32 %0, %1, %2;" : "=r"(d) : "r"(v), "r"(z)); return d; }
__device__ __forceinline__ void sched_fence() { asm volatile("pmevent 0;" ::: "memory"); }
__device__ __forceinline__ float tanh_(float v) { float d; asm("tanh.approx.f32 %0, %1;" : "=f"(d) : "f"(v)); return d; }
__device__ __forceinline__ float silu2(float h) {
    return h * rcp(fmaf(ex2(-2.8853900817779268f * h), 0.5f, 0.5f));
}
__device__ __forceinline__ uint32_t hfma2_(uint32_t a, uint32_t b, uint32_t c) { uint32_t d; asm("fma.rn.f16x2 %0, %1, %2, %3;" : "=r"(d) : "r"(a), "r"(b), "r"(c)); return d; }
__device__ __forceinline__ uint32_t hfms2_(uint32_t a, uint32_t b, uint32_t c) {
    uint32_t d; asm("{ .reg .b32 t; neg.f16x2 t, %1; fma.rn.f16x2 %0, t, %2, %3; }" : "=r"(d) : "r"(a), "r"(b), "r"(c)); return d;
}

__device__ __forceinline__ uint64_t bdesc(uint32_t addr, uint32_t sbo) {
    return (uint64_t)((addr & 0x3FFFFu) >> 4) | ((uint64_t)(128 >> 4) << 16) | ((uint64_t)(sbo >> 4) << 32);
}
__device__ __forceinline__ void wg_h(uint32_t (&d)[16], const uint32_t* a, const uint32_t* b, uint64_t d0, uint64_t d1, uint64_t d2, uint64_t d3) {
    asm volatile(
        "wgmma.mma_async.sync.aligned.m64n64k16.f16.f16.f16 {%0,%1,%2,%3,%4,%5,%6,%7,%8,%9,%10,%11,%12,%13,%14,%15}, {%16,%17,%18,%19}, %32, 0, 1, 1, 1;\n"
        "wgmma.mma_async.sync.aligned.m64n64k16.f16.f16.f16 {%0,%1,%2,%3,%4,%5,%6,%7,%8,%9,%10,%11,%12,%13,%14,%15}, {%20,%21,%22,%23}, %33, 1, 1, 1, 1;\n"
        "wgmma.mma_async.sync.aligned.m64n64k16.f16.f16.f16 {%0,%1,%2,%3,%4,%5,%6,%7,%8,%9,%10,%11,%12,%13,%14,%15}, {%24,%25,%26,%27}, %34, 1, 1, 1, 1;\n"
        "wgmma.mma_async.sync.aligned.m64n64k16.f16.f16.f16 {%0,%1,%2,%3,%4,%5,%6,%7,%8,%9,%10,%11,%12,%13,%14,%15}, {%28,%29,%30,%31}, %35, 1, 1, 1, 1;\n"
        : "=r"(d[0]), "=r"(d[1]), "=r"(d[2]), "=r"(d[3]), "=r"(d[4]), "=r"(d[5]), "=r"(d[6]), "=r"(d[7]), "=r"(d[8]), "=r"(d[9]), "=r"(d[10]), "=r"(d[11]), "=r"(d[12]), "=r"(d[13]), "=r"(d[14]), "=r"(d[15])
        : "r"(a[0]), "r"(a[1]), "r"(a[2]), "r"(a[3]), "r"(a[4]), "r"(a[5]), "r"(a[6]), "r"(a[7]), "r"(b[0]), "r"(b[1]), "r"(b[2]), "r"(b[3]), "r"(b[4]), "r"(b[5]), "r"(b[6]), "r"(b[7]), "l"(d0), "l"(d1), "l"(d2), "l"(d3));
}
__device__ __forceinline__ void wg_f0(float (&d)[32], const uint32_t* a, const uint32_t* b, uint64_t d0, uint64_t d1, uint64_t d2, uint64_t d3) {
    asm volatile(
        "wgmma.mma_async.sync.aligned.m64n64k16.f32.f16.f16 {%0,%1,%2,%3,%4,%5,%6,%7,%8,%9,%10,%11,%12,%13,%14,%15,%16,%17,%18,%19,%20,%21,%22,%23,%24,%25,%26,%27,%28,%29,%30,%31}, {%32,%33,%34,%35}, %48, 0, 1, 1, 1;\n"
        "wgmma.mma_async.sync.aligned.m64n64k16.f32.f16.f16 {%0,%1,%2,%3,%4,%5,%6,%7,%8,%9,%10,%11,%12,%13,%14,%15,%16,%17,%18,%19,%20,%21,%22,%23,%24,%25,%26,%27,%28,%29,%30,%31}, {%36,%37,%38,%39}, %49, 1, 1, 1, 1;\n"
        "wgmma.mma_async.sync.aligned.m64n64k16.f32.f16.f16 {%0,%1,%2,%3,%4,%5,%6,%7,%8,%9,%10,%11,%12,%13,%14,%15,%16,%17,%18,%19,%20,%21,%22,%23,%24,%25,%26,%27,%28,%29,%30,%31}, {%40,%41,%42,%43}, %50, 1, 1, 1, 1;\n"
        "wgmma.mma_async.sync.aligned.m64n64k16.f32.f16.f16 {%0,%1,%2,%3,%4,%5,%6,%7,%8,%9,%10,%11,%12,%13,%14,%15,%16,%17,%18,%19,%20,%21,%22,%23,%24,%25,%26,%27,%28,%29,%30,%31}, {%44,%45,%46,%47}, %51, 1, 1, 1, 1;\n"
        : "=f"(d[0]), "=f"(d[1]), "=f"(d[2]), "=f"(d[3]), "=f"(d[4]), "=f"(d[5]), "=f"(d[6]), "=f"(d[7]), "=f"(d[8]), "=f"(d[9]), "=f"(d[10]), "=f"(d[11]), "=f"(d[12]), "=f"(d[13]), "=f"(d[14]), "=f"(d[15]), "=f"(d[16]), "=f"(d[17]), "=f"(d[18]), "=f"(d[19]), "=f"(d[20]), "=f"(d[21]), "=f"(d[22]), "=f"(d[23]), "=f"(d[24]), "=f"(d[25]), "=f"(d[26]), "=f"(d[27]), "=f"(d[28]), "=f"(d[29]), "=f"(d[30]), "=f"(d[31])
        : "r"(a[0]), "r"(a[1]), "r"(a[2]), "r"(a[3]), "r"(a[4]), "r"(a[5]), "r"(a[6]), "r"(a[7]), "r"(b[0]), "r"(b[1]), "r"(b[2]), "r"(b[3]), "r"(b[4]), "r"(b[5]), "r"(b[6]), "r"(b[7]), "l"(d0), "l"(d1), "l"(d2), "l"(d3));
}
__device__ __forceinline__ void wg_f1(float (&d)[32], const uint32_t* a, const uint32_t* b, uint64_t d0, uint64_t d1, uint64_t d2, uint64_t d3) {
    asm volatile(
        "wgmma.mma_async.sync.aligned.m64n64k16.f32.f16.f16 {%0,%1,%2,%3,%4,%5,%6,%7,%8,%9,%10,%11,%12,%13,%14,%15,%16,%17,%18,%19,%20,%21,%22,%23,%24,%25,%26,%27,%28,%29,%30,%31}, {%32,%33,%34,%35}, %48, 1, 1, 1, 1;\n"
        "wgmma.mma_async.sync.aligned.m64n64k16.f32.f16.f16 {%0,%1,%2,%3,%4,%5,%6,%7,%8,%9,%10,%11,%12,%13,%14,%15,%16,%17,%18,%19,%20,%21,%22,%23,%24,%25,%26,%27,%28,%29,%30,%31}, {%36,%37,%38,%39}, %49, 1, 1, 1, 1;\n"
        "wgmma.mma_async.sync.aligned.m64n64k16.f32.f16.f16 {%0,%1,%2,%3,%4,%5,%6,%7,%8,%9,%10,%11,%12,%13,%14,%15,%16,%17,%18,%19,%20,%21,%22,%23,%24,%25,%26,%27,%28,%29,%30,%31}, {%40,%41,%42,%43}, %50, 1, 1, 1, 1;\n"
        "wgmma.mma_async.sync.aligned.m64n64k16.f32.f16.f16 {%0,%1,%2,%3,%4,%5,%6,%7,%8,%9,%10,%11,%12,%13,%14,%15,%16,%17,%18,%19,%20,%21,%22,%23,%24,%25,%26,%27,%28,%29,%30,%31}, {%44,%45,%46,%47}, %51, 1, 1, 1, 1;\n"
        : "+f"(d[0]), "+f"(d[1]), "+f"(d[2]), "+f"(d[3]), "+f"(d[4]), "+f"(d[5]), "+f"(d[6]), "+f"(d[7]), "+f"(d[8]), "+f"(d[9]), "+f"(d[10]), "+f"(d[11]), "+f"(d[12]), "+f"(d[13]), "+f"(d[14]), "+f"(d[15]), "+f"(d[16]), "+f"(d[17]), "+f"(d[18]), "+f"(d[19]), "+f"(d[20]), "+f"(d[21]), "+f"(d[22]), "+f"(d[23]), "+f"(d[24]), "+f"(d[25]), "+f"(d[26]), "+f"(d[27]), "+f"(d[28]), "+f"(d[29]), "+f"(d[30]), "+f"(d[31])
        : "r"(a[0]), "r"(a[1]), "r"(a[2]), "r"(a[3]), "r"(a[4]), "r"(a[5]), "r"(a[6]), "r"(a[7]), "r"(b[0]), "r"(b[1]), "r"(b[2]), "r"(b[3]), "r"(b[4]), "r"(b[5]), "r"(b[6]), "r"(b[7]), "l"(d0), "l"(d1), "l"(d2), "l"(d3));
}
__device__ __forceinline__ void wg_s(uint32_t* d, const uint32_t* a, const uint32_t* b, uint64_t d0, uint64_t d1) {
    asm volatile(
        "wgmma.mma_async.sync.aligned.m64n32k16.f16.f16.f16 {%0,%1,%2,%3,%4,%5,%6,%7}, {%8,%9,%10,%11}, %16, 0, 1, 1, 1;\n"
        "wgmma.mma_async.sync.aligned.m64n32k16.f16.f16.f16 {%0,%1,%2,%3,%4,%5,%6,%7}, {%12,%13,%14,%15}, %17, 1, 1, 1, 1;\n"
        : "=r"(d[0]), "=r"(d[1]), "=r"(d[2]), "=r"(d[3]), "=r"(d[4]), "=r"(d[5]), "=r"(d[6]), "=r"(d[7])
        : "r"(a[0]), "r"(a[1]), "r"(a[2]), "r"(a[3]), "r"(b[0]), "r"(b[1]), "r"(b[2]), "r"(b[3]), "l"(d0), "l"(d1));
}
template <int ACC> __device__ __forceinline__ void wg_w(float (&d)[4], uint64_t da, uint64_t db) {
    asm volatile("wgmma.mma_async.sync.aligned.m64n8k16.f32.bf16.bf16 {%0,%1,%2,%3}, %4, %5, %6, 1, 1, 1, 0;"
                 : "+f"(d[0]), "+f"(d[1]), "+f"(d[2]), "+f"(d[3]) : "l"(da), "l"(db), "n"(ACC));
}
__device__ __forceinline__ void wg_w0(float (&d)[4], uint64_t da, uint64_t db) {
    asm volatile("wgmma.mma_async.sync.aligned.m64n8k16.f32.bf16.bf16 {%0,%1,%2,%3}, %4, %5, 0, 1, 1, 1, 0;"
                 : "=f"(d[0]), "=f"(d[1]), "=f"(d[2]), "=f"(d[3]) : "l"(da), "l"(db));
}
__device__ __forceinline__ void wg_fence() { asm volatile("wgmma.fence.sync.aligned;" ::: "memory"); }
__device__ __forceinline__ void wg_commit() { asm volatile("wgmma.commit_group.sync.aligned;" ::: "memory"); }
template <int N> __device__ __forceinline__ void wg_wait() { asm volatile("wgmma.wait_group.sync.aligned %0;" :: "n"(N) : "memory"); }
__device__ __forceinline__ void touch(uint32_t& r) { asm volatile("" : "+r"(r) :: "memory"); }
__device__ __forceinline__ void touch(float& r) { asm volatile("" : "+f"(r) :: "memory"); }
template <class T, int N> __device__ __forceinline__ void touch(T (&r)[N]) {
#pragma unroll
    for (int i = 0; i < N; i++) touch(r[i]);
}

__global__ void __cluster_dims__(2, 1, 1) __launch_bounds__(NTHREADS, 1)
fused_kernel(const Params p, const __grid_constant__ CUtensorMap tm_x, const __grid_constant__ CUtensorMap tm_g,
             const __grid_constant__ CUtensorMap tm_d)
{
    extern __shared__ __align__(1024) uint8_t smem_raw[];
    const uint32_t sm = (uint32_t)__cvta_generic_to_shared(smem_raw);
    const uint32_t bars = sm + SM_BAR;
    const int tid = threadIdx.x, lane = tid & 31;
    const int g = lane >> 2, q = lane & 3;
    const int c = blockIdx.x, rank = c & 1, G = c >> 1;

    if (tid < 256) {
        uint2 lar4, aim4, cr4, ci4;
        uint32_t ldt_raw, dsk_raw;
        {
            const uint32_t i = c * 256 + tid;
            asm volatile("ld.global.nc.v2.u32 {%0,%1}, [%10]; ld.global.nc.v2.u32 {%2,%3}, [%11]; ld.global.nc.u16 %8, [%14];\n"
                         "ld.global.nc.v2.u32 {%4,%5}, [%12]; ld.global.nc.v2.u32 {%6,%7}, [%13]; ld.global.nc.u16 %9, [%15];"
                         : "=r"(lar4.x), "=r"(lar4.y), "=r"(aim4.x), "=r"(aim4.y), "=r"(cr4.x), "=r"(cr4.y), "=r"(ci4.x), "=r"(ci4.y), "=r"(ldt_raw), "=r"(dsk_raw)
                         : "l"(p.lar + i * 4), "l"(p.aim + i * 4), "l"(p.cr + i * 4), "l"(p.ci + i * 4), "l"(p.logdt + (i >> 5)), "l"(p.dskip + (i >> 5)));
        }
        cluster_arrive();
        sched_fence();
        const int warp = __shfl_sync(0xFFFFFFFFu, tid >> 5, 0);
        const float logdt = blo(ldt_raw), dsk = blo(dsk_raw);
        asm volatile("setmaxnreg.inc.sync.aligned.u32 168;");
        const int wgi = warp >> 2, w = warp & 3;
        const uint32_t wb = sm + SM_K + (w < 2 ? 16 * w + 8 * wgi : 16 + 16 * wgi + 8 * w) * SUB;
        sth(wb + lane * 4, hc{0x3C003C00u, 0u});

        const float dt = rb(expf(logdt));
        float outscale, cs, dn;
        {
            uint32_t m0 = __vmaxu2(__vmaxu2(cr4.x & 0x7FFF7FFFu, cr4.y & 0x7FFF7FFFu), __vmaxu2(ci4.x & 0x7FFF7FFFu, ci4.y & 0x7FFF7FFFu));
            uint32_t m1 = max(m0 & 0xFFFFu, m0 >> 16);
            float cmax = blo(__reduce_max_sync(0xFFFFFFFFu, m1));
            const float sc = fminf(fmaxf(fmaxf(2.0f * dt * cmax, fabsf(dsk) * (1.0f / 1024.0f)), 1e-30f), 1e30f);
            outscale = __uint_as_float(__float_as_uint(sc) & 0x7F800000u);
            const float inv = __uint_as_float(0x7F000000u - __float_as_uint(outscale));
            cs = 2.0f * dt * inv;
            dn = dsk * inv;
        }
        if (warp == TSW) TSL(39);
        uint32_t fc[16], fs[16], ta[4], tb[4];
        float kacc[2][3][4];
#pragma unroll
        for (int i = 0; i < 2; i++)
#pragma unroll
            for (int j = 0; j < 3; j++) kacc[i][j][0] = kacc[i][j][1] = kacc[i][j][2] = kacc[i][j][3] = 0.f;
        if (lane == 0) kacc[0][0][0] = dn;
        {
            const uint32_t st = wb + lane * 4;
            const uint32_t zk = lds32(wb + 128);
            const uint32_t la = wb + ((lane & 8) ? 29 : (lane & 7)) * KP + (lane >> 4) * 128;
            const uint32_t lo = wb + ((lane >> 3) & 1) * 128 + (lane >> 4) * 16;
            const uint32_t lb = lo + (8 + (lane & 7)) * KP, lb2 = lo + (24 + min(lane & 7, 4)) * KP, lm = lo + 30 * KP;
#pragma unroll 1
            for (int s = 0; s < 2; s++) {
                const uint32_t wl = s ? lar4.y : lar4.x, wa = s ? aim4.y : aim4.x, wr_ = s ? cr4.y : cr4.x, wi = s ? ci4.y : ci4.x;
                const uint32_t ea = pack_b(ex2(blo(wl) * 1.4426950408889634f), ex2(bhi(wl) * 1.4426950408889634f));
                const float a2[2] = {-(blo(ea) * dt) * 1.4426950408889634f, -(bhi(ea) * dt) * 1.4426950408889634f};
                const float b[2] = {blo(wa) * dt, bhi(wa) * dt};
                {
                    cf z8[2], z16[2], z32[2], z64[2], z128[2];
#pragma unroll
                    for (int e = 0; e < 2; e++) {
                        z8[e] = cexp_(a2[e] * 8.f, b[e] * 8.f);
                        z16[e] = csq(z8[e]); z32[e] = csq(z16[e]); z64[e] = csq(z32[e]); z128[e] = csq(z64[e]);
                    }
                    const hc r1 = pk(z8[0], z8[1]), r2 = pk(z16[0], z16[1]), r3 = hmulc(r1, r2), r4 = pk(z32[0], z32[1]);
                    sth(st + 1 * KP, r1); sth(st + 2 * KP, r2); sth(st + 3 * KP, r3); sth(st + 4 * KP, r4);
                    sth(st + 5 * KP, hmulc(r1, r4)); sth(st + 6 * KP, hmulc(r2, r4)); sth(st + 7 * KP, hmulc(r3, r4));
                    sth(st + 29 * KP, pk(z64[0], z64[1])); sth(st + 30 * KP, pk(z128[0], z128[1]));
                }
                {
                    cf C[2], z2[2], z4[2], v2[2], v4[2], c1[2], d1[2];
#pragma unroll
                    for (int e = 0; e < 2; e++) {
                        C[e] = {(e ? bhi(wr_) : blo(wr_)) * cs, (e ? bhi(wi) : blo(wi)) * -cs};
                        const cf z = cexp_(a2[e], -b[e]);
                        const cf v = cexp_(a2[e] * 256.f, b[e] * -256.f);
                        z2[e] = csq(z); z4[e] = csq(z2[e]); v2[e] = csq(v); v4[e] = csq(v2[e]);
                        c1[e] = cmul(C[e], z); d1[e] = cmul(C[e], v);
                    }
                    const hc l0 = pk(C[0], C[1]), l1 = pk(c1[0], c1[1]), e1 = pk(d1[0], d1[1]);
                    const hc h = pk(z2[0], z2[1]), f = pk(z4[0], z4[1]), w = pk(v2[0], v2[1]), y = pk(v4[0], v4[1]);
                    const hc l2 = hmulc(l0, h), l3 = hmulc(l1, h), e2 = hmulc(l0, w), e3 = hmulc(e1, w), e4 = hmulc(l0, y), g2 = hmulc(e1, h);
                    sth(st + 8 * KP, l0); sth(st + 9 * KP, l1); sth(st + 10 * KP, l2); sth(st + 11 * KP, l3);
                    sth(st + 12 * KP, hmulc(l0, f)); sth(st + 13 * KP, hmulc(l1, f)); sth(st + 14 * KP, hmulc(l2, f)); sth(st + 15 * KP, hmulc(l3, f));
                    sth(st + 16 * KP, e1);
                    sth(st + 17 * KP, g2);
                    sth(st + 18 * KP, hmulc(e1, f));
                    sth(st + 19 * KP, hmulc(g2, f));
                    sth(st + 20 * KP, e2);
                    sth(st + 21 * KP, hmulc(e2, f));
                    sth(st + 22 * KP, e3);
                    sth(st + 23 * KP, hmulc(e3, f));
                    sth(st + 24 * KP, e4);
                    sth(st + 25 * KP, hmulc(e1, y));
                    sth(st + 26 * KP, hmulc(e2, y));
                    sth(st + 27 * KP, hmulc(e3, y));
                    sth(st + 28 * KP, hmulc(e4, y));
                }
                __syncwarp();
                if (warp == TSW) TSL(s ? 34 : 27);
                if (s == 1 && lane == 0) mbar_arrive(bars + B_TFREE * 8 + (tb[3] & zk));
#pragma unroll
                for (int kp = 0; kp < 4; kp++) {
                    uint32_t bb[3][4], m2[4];
                    ldsm4(lm + kp * 32, m2[0], m2[1], m2[2], m2[3]);
                    ldsm4(lb + kp * 32, bb[0][0], bb[0][1], bb[0][2], bb[0][3]);
                    ldsm4(lb + 8 * KP + kp * 32, bb[1][0], bb[1][1], bb[1][2], bb[1][3]);
                    ldsm4(lb2 + kp * 32, bb[2][0], bb[2][1], bb[2][2], bb[2][3]);
#pragma unroll
                    for (int k2 = 0; k2 < 2; k2++) {
                        hc v0, m1;
                        ldsm4(la + kp * 32 + k2 * 16, v0.r, m1.r, v0.i, m1.i);
                        const hc mm = {m2[2 * k2], m2[2 * k2 + 1]};
                        const hc v1 = hmulc(v0, m1), v2 = hmulc(v0, mm), v3 = hmulc(v1, mm);
                        v0.r = cpy(v0.r, zk); v0.i = cpy(v0.i, zk);
#pragma unroll
                        for (int nt = 0; nt < 3; nt++) {
                            mma_f16(kacc[0][nt], v0.r, v1.r, v0.i, v1.i, bb[nt][2 * k2], bb[nt][2 * k2 + 1]);
                            mma_f16(kacc[1][nt], v2.r, v3.r, v2.i, v3.i, bb[nt][2 * k2], bb[nt][2 * k2 + 1]);
                        }
                    }
                }
                __syncwarp();
                if (warp == TSW) TSL(s ? 40 : 33);
                if (s == 0) {
                    cluster_wait();
                    mbar_wait(bars + B_TAB * 8);
#pragma unroll
                    for (int i = 0; i < 10; i++) {
                        const uint4 u = lds128(sm + SM_TAB + i * 2048 + (tid & 127) * 16);
                        uint32_t* t = i < 4 ? fc + 4 * i : i < 8 ? fs + 4 * (i - 4) : i == 8 ? ta : tb;
                        t[0] = u.x; t[1] = u.y; t[2] = u.z; t[3] = u.w;
                    }
                }
            }
        }
        TSL(1);
        bar_sync(10 + wgi, 128);
        {
            const uint32_t tb_ = sm + SM_S + (16 * wgi + w) * SUB;
            const uint32_t seg = sm + SM_K + (2 * warp + (lane & 1)) * SUB + (lane >> 1) * 16;
            uint32_t v0[4];
#pragma unroll
            for (int m = 0; m < 4; m++) {
                constexpr float S = 1.0f / 512.0f;
                const float (&k0)[4] = kacc[m >> 1][0], (&k1)[4] = kacc[m >> 1][1], (&k2)[4] = kacc[m >> 1][2];
                const int R = 8 * m + g, o = 2 * (m & 1);
                v0[m] = pack_h(k0[o] * S, k0[o + 1] * S);
                sts32(tb_ + (q < 2 ? 4 * R + 2 * q : 64 * q + 2 * R) * 2, pack_h(k1[o] * S, k1[o + 1] * S));
                const uint32_t v2 = pack_h(k2[o] * S, k2[o + 1] * S);
                if (q < 2 || (m == 0 && lane == 2)) sts16(tb_ + (256 + 64 * q + R) * 2, v2);
                if (q < 2) sts16(tb_ + (288 + 64 * q + R) * 2, v2 >> 16);
            }
            stsm4(seg, v0[0], v0[1], v0[2], v0[3]);
            if (lane == 0) sts16(sm + SM_SCL + warp * 2, __float_as_uint(32768.0f * outscale) >> 16);
            __syncwarp();
            const uint2 l1 = lds64(tb_ + lane * 8);
            const uint32_t l1n = lds16(tb_ + lane * 8 + 8);
            uint32_t l2[2], l2n[2], l3[4], l3n[4];
#pragma unroll
            for (int i = 0; i < 2; i++) { l2[i] = lds32(tb_ + 256 + i * 128 + lane * 4); l2n[i] = lds16(tb_ + 260 + i * 128 + lane * 4); }
#pragma unroll
            for (int i = 0; i < 4; i++) { l3[i] = lds16(tb_ + 512 + i * 64 + lane * 2); l3n[i] = lds16(tb_ + 514 + i * 64 + lane * 2); }
            sts128(seg + 256, prmt(l1.x, 0, 0x1010), prmt(l1.x, l1.y, 0x5432), prmt(l1.y, 0, 0x1010), prmt(l1.y, l1n, 0x5432));
#pragma unroll
            for (int i = 0; i < 2; i++) sts128(seg + 512 + i * 256, prmt(l2[i], 0, 0x1010), l2[i], prmt(l2[i], 0, 0x3232), prmt(l2n[i], 0, 0x1010));
            const uint32_t s3 = (lane & 1) ? 0x5454 : 0x5410;
#pragma unroll
            for (int i = 0; i < 4; i++) {
                const uint32_t vv = prmt(l3[i], 0, 0x1010);
                sts128(seg + 16 * SUB + i * 256, vv, vv, prmt(l3[i], l3n[i], s3), prmt(l3n[i], 0, 0x1010));
            }
        }
        proxy_fence();
        TSL(2);
        bar_sync(10 + wgi, 128);
        const uint64_t dre = bdesc(sm + SM_F2 + 512, 256), dim = bdesc(sm + SM_F2, 256);
        uint32_t k0[32], k1[32];
#pragma unroll
        for (int b = 0; b < 2; b++) {
            const uint64_t d1 = bdesc(sm + SM_K + (16 * b + 8 * wgi) * SUB, SUB);
            uint32_t re[16], im[16];
            if (b == 0 && wgi == 1) bar_sync(5, 256);
            wg_fence();
            wg_h(re, fc, fc + 8, d1, d1 + 16, d1 + 32, d1 + 48);
            wg_h(im, fs, fs + 8, d1, d1 + 16, d1 + 32, d1 + 48);
            wg_commit();
            if (b == 0 && wgi == 0) bar_arrive(5, 256);
            wg_wait<0>();
            touch(re); touch(im);
            if (b == 1 && lane == 0) mbar_arrive(bars + B_KFREE * 8);
            uint32_t (&kk)[32] = b ? k1 : k0;
#pragma unroll
            for (int hh = 0; hh < 2; hh++) {
#pragma unroll
                for (int i = 8 * hh; i < 8 * hh + 8; i++) {
                    re[i] = hfma2_(ta[i & 3], im[i], re[i]); im[i] = hfms2_(tb[i & 3], re[i], im[i]); re[i] = hfma2_(ta[i & 3], im[i], re[i]);
                }
                wg_fence();
                wg_s(kk + 16 * hh, re + 8 * hh, im + 8 * hh, dre, dim);
                wg_s(kk + 16 * hh + 8, re + 8 * hh + 4, im + 8 * hh + 4, dre, dim);
                wg_commit();
            }
            wg_wait<0>();
            touch(kk);
        }
        if (warp == TSW) TSL(35);
        asm volatile("setmaxnreg.inc.sync.aligned.u32 184;");
        touch(k1);
        {
            const uint32_t sg = (g & 1) ? 0xBC00BC00u : 0x3C003C00u;
#pragma unroll
            for (int i = 0; i < 16; i++) {
                const int r = 8 * (i >> 2) + (i & 3);
                k1[r] = hfms2_(sg, k0[r + 4], k1[r]); k1[r + 4] = hfma2_(sg, k0[r], k1[r + 4]);
            }
            touch(k1);
        }
        const uint32_t rowo = (16 * w + (lane & 15)) * 16;
        const uint32_t peer = mapa(sm, rank ^ 1), so = SM_U + 8 * wgi * SUB + w * 1024 + (8 * q + (g ^ (2 * q))) * 16;
        const uint2 sc = lds64(sm + SM_SCL + wgi * 8);
#pragma unroll 1
        for (int b = 0; b < 2; b++) {
            const uint32_t zb = sm + SM_S + 16 * wgi * SUB;
            constexpr int zi = 8 * SUB;
            uint32_t re[16], im[16], su[2][16], z[2][16], y[2][16];
            auto twiddle = [&](int hh) {
#pragma unroll
                for (int i = 8 * hh; i < 8 * hh + 8; i++) {
                    re[i] = hfma2_(ta[i & 3], im[i], re[i]); im[i] = hfms2_(tb[i & 3], re[i], im[i]); re[i] = hfma2_(ta[i & 3], im[i], re[i]);
                    touch(re[i]); touch(im[i]);
                }
            };
            auto dft16 = [&](int hh) {
                wg_fence();
                wg_s(su[hh], re + 8 * hh, im + 8 * hh, dre, dim); wg_s(su[hh] + 8, re + 8 * hh + 4, im + 8 * hh + 4, dre, dim);
                wg_commit();
                sched_fence();
            };
            auto product = [&](int hh) {
                if (b == 0) {
#pragma unroll
                    for (int i = 0; i < 8; i++) {
                        const int r = 8 * (i >> 2) + (i & 3), kr = 16 * hh + r;
                        const hc u = {su[hh][r], su[hh][r + 4]};
                        const hc t = hmulc(u, hc{k0[kr], k0[kr + 4]}), pp = hmulc(u, hc{k1[kr], k1[kr + 4]});
                        z[hh][r] = t.r; z[hh][r + 4] = t.i; k1[kr] = pp.r; k1[kr + 4] = pp.i;
                        touch(k1[kr]); touch(k1[kr + 4]);
                    }
                } else {
#pragma unroll
                    for (int i = 0; i < 8; i++) {
                        const int r = 8 * (i >> 2) + (i & 3), kr = 16 * hh + r;
                        const hc u = {su[hh][r], su[hh][r + 4]};
                        z[hh][r] = hfms2_(u.i, k0[kr + 4], hfma2_(u.r, k0[kr], k1[kr]));
                        z[hh][r + 4] = hfma2_(u.i, k0[kr], hfma2_(u.r, k0[kr + 4], k1[kr + 4]));
                    }
                }
                touch(z[hh]);
            };
            auto idft16 = [&](int hh) {
                wg_fence();
                wg_s(y[hh], z[hh] + 4, z[hh], dre, dim); wg_s(y[hh] + 8, z[hh] + 12, z[hh] + 8, dre, dim);
                wg_commit();
                sched_fence();
            };
            auto untwiddle = [&](int hh) {
#pragma unroll
                for (int i = 0; i < 2; i++) {
                    uint32_t* const yi = y[hh] + 8 * i, * const yr = yi + 4;
#pragma unroll
                    for (int n = 0; n < 4; n++) {
                        yr[n] = hfms2_(ta[n], yi[n], yr[n]); yi[n] = hfma2_(tb[n], yr[n], yi[n]); yr[n] = hfms2_(ta[n], yi[n], yr[n]);
                    }
                    const uint32_t a = zb + (4 * hh + 2 * i + (lane >> 4)) * SUB + rowo;
                    stsm4(a, yr[0], yr[1], yr[2], yr[3]);
                    stsm4(a + zi, yi[0], yi[1], yi[2], yi[3]);
                }
            };
            auto done = [&]() { sched_fence(); wg_wait<0>(); };
            {
                const uint64_t d1 = bdesc(sm + SM_U + (16 * b + 8 * wgi) * SUB, SUB);
                mbar_wait(bars + (B_U + b) * 8);
                proxy_fence();
                if (b == 0) { TSL(3); if (wgi == 1) bar_sync(9, 256); }
                wg_fence();
                wg_h(re, fc, fc + 8, d1, d1 + 16, d1 + 32, d1 + 48);
                wg_h(im, fs, fs + 8, d1, d1 + 16, d1 + 32, d1 + 48);
                wg_commit();
                if (b == 0 && wgi == 0) bar_arrive(9, 256);
                wg_wait<0>();
                touch(re); touch(im);
            }
            if (lane == 0) mbar_arrive_peer(peer + SM_BAR + (B_PEER + 2 * wgi + b) * 8);
            twiddle(0); twiddle(1); dft16(0); dft16(1);
            wg_wait<1>(); touch(su[0]);
            product(0); done(); touch(su[1]); idft16(0);
            product(1); done(); touch(y[0]); idft16(1);
            bar_sync(10 + wgi, 128);
            untwiddle(0); done(); touch(y[1]);
            untwiddle(1);
            proxy_fence();
            if (warp == TSW) TSL(36 + b);
            bar_sync(10 + wgi, 128);
            float acc[32];
            const uint64_t d4 = bdesc(zb, SUB);
            wg_fence();
            wg_f0(acc, fc, fc + 8, d4, d4 + 16, d4 + 32, d4 + 48);
            wg_f1(acc, fs, fs + 8, d4 + zi / 16, d4 + zi / 16 + 16, d4 + zi / 16 + 32, d4 + zi / 16 + 48);
            wg_commit();
            mbar_wait(bars + (B_PEER + 2 * wgi + b) * 8);
            wg_wait<0>();
            touch(acc);
            uint32_t s[2][2][4];
#pragma unroll
            for (int i = 0; i < 8; i++) {
                s[i >> 2][(i >> 1) & 1][2 * (i & 1)] = bmul2(pack_b(acc[i], acc[8 + i]), sc.x);
                s[i >> 2][(i >> 1) & 1][2 * (i & 1) + 1] = bmul2(pack_b(acc[16 + i], acc[24 + i]), sc.y);
            }
            const uint32_t sb = SM_BAR + (B_STG + b) * 8;
#pragma unroll
            for (int j = 0; j < 2; j++)
                if (j == rank) {
#pragma unroll
                    for (int hi = 0; hi < 2; hi++) {
                        const uint32_t (&r)[4] = s[1 - j][hi], (&l)[4] = s[j][hi];
                        st_async4(peer + so + 16 * b * SUB + hi * 512, r[0], r[1], r[2], r[3], peer + sb);
                        sts128(sm + so + (16 * b + 4) * SUB + 64 + hi * 512, l[0], l[1], l[2], l[3]);
                    }
                }
            __syncwarp();
            if (lane == 0) mbar_arrive(sm + sb);
            if (warp == TSW) TSL(5 + b);
        }
        TSL(7);
    } else {
    const int warp = __shfl_sync(0xFFFFFFFFu, tid >> 5, 0);
    if (warp < 12) {
        const int v = warp - 8;
        cluster_arrive();
        const uint32_t xs = sm + SM_U + v * 8192;
        if (elect()) {
#pragma unroll
            for (int r = 0; r < 2; r++) mbar_init(bars + (B_ROW + 2 * v + r) * 8, 1);
            asm volatile("fence.mbarrier_init.release.cluster;" ::: "memory");
#pragma unroll
            for (int e = 0; e < 2; e++) {
                if (e) { const int t0_ = clock(); while ((int)clock() - t0_ < EDELAY) __nanosleep(40); }
                mbar_expect(bars + (B_ROW + 2 * v + e) * 8, 4096);
#pragma unroll
                for (int r = 0; r < 2; r++)
                    asm volatile("cp.async.bulk.shared::cluster.global.mbarrier::complete_tx::bytes [%0], [%1], 2048, [%2];"
                                 :: "r"(xs + e * 4096 + r * 2048), "l"(p.x + (size_t)(128 * (c & 15) + 32 * v + 16 * r + 2 * (c >> 4) + e) * 1024),
                                    "r"(bars + (B_ROW + 2 * v + e) * 8) : "memory");
            }
        }
        __syncwarp();
        uint4 w4[4];
#pragma unroll
        for (int k = 0; k < 4; k++) w4[k] = ldg128(reinterpret_cast<const uint4*>(p.wr) + 32 * k + lane);
        {
            constexpr uint32_t ONE = 0x3F803F80u;
            const uint32_t zr = p.up_first >> 1;
            uint4 w5[4];
#pragma unroll
            for (int k = 0; k < 4; k++) {
                w5[k].x = w4[k].x + zr; w5[k].y = w4[k].y + zr; w5[k].z = w4[k].z + zr; w5[k].w = w4[k].w + zr;
                w4[k].x = cpy(w4[k].x, zr); w4[k].y = cpy(w4[k].y, zr); w4[k].z = cpy(w4[k].z, zr); w4[k].w = cpy(w4[k].w, zr);
            }
            const bool od = g & 1;
#pragma unroll 1
            for (int r2 = 0; r2 < 2; r2++) {
                mbar_wait(bars + (B_ROW + 2 * v + r2) * 8);
                TSL(r2 ? 43 : 0);
                float s1[2][4] = {}, q0[2][4] = {};
#pragma unroll
                for (int k = 0; k < 4; k++)
#pragma unroll
                    for (int r = 0; r < 2; r++) {
                        const uint4 x = lds128(xs + r2 * 4096 + r * 2048 + k * 512 + lane * 16);
                        const uint4& ww = r ? w5[k] : w4[k];
                        mma_bf16(q0[r], cpy(x.x, zr), ww.x, cpy(x.y, zr), ww.y, x.x, x.y);
                        mma_bf16(s1[r], x.x, x.y, x.z, x.w, ONE, ONE);
                        mma_bf16(q0[r], cpy(x.z, zr), ww.z, cpy(x.w, zr), ww.w, x.z, x.w);
                    }
#pragma unroll
                for (int r = 0; r < 2; r++)
                    if (q == (g >> 1))
                        sts128(sm + SM_RED + (4 * v + r2 + 2 * r) * 144 + g * 16, __float_as_uint(od ? q0[r][1] : q0[r][0]),
                               __float_as_uint(od ? q0[r][3] : q0[r][2]), __float_as_uint(s1[r][0]), __float_as_uint(s1[r][2]));
            }
            bar_arrive(7, 160);
        }
        TSL(8);
        bar_sync(6, 160);
        const uint32_t tag = lds32(sm + SM_TOK + 8);
        cluster_wait();
        asm volatile("setmaxnreg.dec.sync.aligned.u32 96;");
        const uint32_t peer = mapa(sm, rank ^ 1);
        if (v == 0 && lane == 0) mbar_arrive_peer(peer + SM_BAR + B_UFREE * 8);
        {
            uint4 st[8] = {};
            const uint4* src = p.sc->stats + rank * 512 + 16 * v + (lane >> 1);
            const uint32_t tb = ((tag & 1) << 15) | ((tag >> 1) << 31);
#pragma unroll
            for (int i = 0; i < 8; i++) st[i].y = ~tb;
            int it = 0;
            bool ok;
            if (warp == 8) TSL(44);
            do {
                uint32_t bad = 0;
#pragma unroll
                for (int i = 0; i < 8; i++)
                    asm volatile("{ .reg .pred p; .reg .b128 t; setp.ne.u32 p, %5, 0; mov.b128 t, {%0,%1,%2,%3};\n"
                                 "@p ld.relaxed.gpu.global.b128 t, [%4]; mov.b128 {%0,%1,%2,%3}, t; }"
                                 : "+r"(st[i].x), "+r"(st[i].y), "+r"(st[i].z), "+r"(st[i].w)
                                 : "l"(src + (i >> 2) * 64 + (i & 3) * 128), "r"((st[i].y ^ tb) & 0x80008000u) : "memory");
#pragma unroll
                for (int i = 0; i < 8; i++) bad |= st[i].y ^ tb;
                ok = __all_sync(0xFFFFFFFFu, (bad & 0x80008000u) == 0);
                if (warp == 8 && it == 0) TSL(45);
            } while (!ok && ++it < SPIN_LIMIT);
            TSL(11); TG(31);
            uint32_t h1[4], h2[4];
#pragma unroll
            for (int i = 0; i < 4; i++) { h1[i] = max(st[i].w, st[i + 4].w); h2[i] = min(st[i].w, st[i + 4].w); }
#pragma unroll
            for (int n = 2; n > 0; n >>= 1)
#pragma unroll
                for (int i = 0; i < n; i++) { h2[i] = __vimax3_u32(min(h1[i], h1[i + n]), h2[i], h2[i + n]); h1[i] = max(h1[i], h1[i + n]); }
            const uint32_t w1 = __reduce_max_sync(0xFFFFFFFFu, h1[0]);
            const uint32_t w2 = __reduce_max_sync(0xFFFFFFFFu, h1[0] == w1 ? h2[0] : h1[0]);
            if (lane < 2) { const uint32_t dst = mapa(sm, lane); st_async2(dst + SM_KEYS + rank * 32 + v * 8, w1, w2, dst + SM_BAR + B_KEYS * 8); }
#pragma unroll
            for (int i = 0; i < 8; i++) { st[i].y = bmul2(st[i].y & 0x7FFF7FFFu, 0x3F003F00u); st[i].z = bmul2(st[i].z, 0x3F003F00u); }
            const uint32_t xo = sm + SM_SLAB + v * 512 + lane * 16;
            const bool own = (lane & 1) == rank;
            uint32_t n[8][4];
            auto normalise = [&](int b) {
#pragma unroll
                for (int i = 0; i < 8; i++) {
                    const uint4 x = lds128(xo + b * 16384 + (i & 1) * 8192 + (i >> 1) * 2048);
                    const uint4& t = st[i >> 1];
                    const uint32_t m = (i & 1) ? dup_hi(t.x) : dup_lo(t.x), hi = (i & 1) ? dup_hi(t.y) : dup_lo(t.y), lo = (i & 1) ? dup_hi(t.z) : dup_lo(t.z);
                    n[i][0] = norm2(x.x, m, hi, lo); n[i][1] = norm2(x.y, m, hi, lo); n[i][2] = norm2(x.z, m, hi, lo); n[i][3] = norm2(x.w, m, hi, lo);
                }
#pragma unroll
                for (int i = 0; i < 4; i++) { const uint4 t = st[i]; st[i] = st[4 + i]; st[4 + i] = t; }
            };
            mbar_wait(bars + B_UFREE * 8);
#pragma unroll 1
            for (int b = 0; b < 2; b++) {
                mbar_wait(bars + (B_SLAB + b) * 8);
                TSL(b ? 38 : 10);
                normalise(b);
                const uint32_t ua = SM_U + (16 * b + rank) * SUB + (16 * v + (lane >> 1)) * 16;
#pragma unroll
                for (int cc = 0; cc < 8; cc++) {
                    uint32_t o[4];
#pragma unroll
                    for (int i = 0; i < 4; i++)
                        o[i] = (cc & 1) ? pack_h(bhi(n[2 * i][cc >> 1]), bhi(n[2 * i + 1][cc >> 1])) : pack_h(blo(n[2 * i][cc >> 1]), blo(n[2 * i + 1][cc >> 1]));
                    const uint32_t dst = own ? mapa(sm, rank) : peer;
                    st_async4(dst + ua + 2 * cc * SUB, o[0], o[1], o[2], o[3], dst + SM_BAR + (B_U + b) * 8);
                }
                TSL(b ? 41 : 12);
            }
            const uint32_t stg = sm + SM_U + (own ? 4 * SUB + 64 : 0) + v * 1024 + (lane >> 4) * 512;
            const int tl = 256 * v + 16 * (lane >> 1) + 8 * rank;
            __nv_bfloat16* const op = p.out + (size_t)tl * 1024 + G * 16 + (lane & 1) * 8;
            mbar_wait(bars + B_TOK * 8);
            const uint2 tr = lds64(sm + SM_TOK);
#pragma unroll 1
            for (int b = 0; b < 2; b++) {
                normalise(b);
#pragma unroll
                for (int i = 0; i < 8; i++) {
#pragma unroll
                    for (int k = 0; k < 4; k++) n[i][k] = pack_b(silu2(blo(n[i][k])), silu2(bhi(n[i][k])));
                    touch(n[i]);
                    if (i & 1) sched_fence();
                }
                const int d0 = tr.x - tl - 1024 * b, d1 = tr.y - tl - 1024 * b;
                const uint32_t skip = ((d0 & ~7) ? 0u : 1u << d0) | ((d1 & ~7) ? 0u : 1u << d1);
                mbar_wait(bars + (B_STG + b) * 8);
                if (skip) {
#pragma unroll 1
                    for (int k = 0; k < 2; k++) {
                        const int d = k ? d1 : d0;
                        if (!(d & ~7)) {
                            const uint32_t a = stg + 16 * b * SUB + (4 * (d & 6) + (((lane >> 1) & 7) ^ (d & 6))) * 16 + (d & 1) * 8, dst = mapa(sm, k);
                            const uint2 s0 = lds64(a), s1 = lds64(a + 8 * SUB);
                            st_async4(dst + SM_FIX + (lane & 1) * 16, s0.x, s0.y, s1.x, s1.y, dst + SM_BAR + B_FIX * 8);
                        }
                    }
                }
                __syncwarp();
#pragma unroll
                for (int i = 0; i < 4; i++) {
                    const uint32_t a = stg + 16 * b * SUB + (8 * i + (((lane >> 1) & 7) ^ (2 * i))) * 16;
                    const uint4 r0 = lds128(a), r1 = lds128(a + 8 * SUB);
#pragma unroll
                    for (int e = 0; e < 2; e++) {
                        const uint4 x = lds128(xo + b * 16384 + e * 8192 + i * 2048);
                        const uint32_t s0 = e ? r0.z : r0.x, s1 = e ? r0.w : r0.y, s2 = e ? r1.z : r1.x, s3 = e ? r1.w : r1.y;
                        const uint32_t (&gt)[4] = n[2 * i + e];
                        asm volatile("{ .reg .pred p; setp.eq.u32 p, %5, 0; @p st.global.v4.u32 [%0], {%1,%2,%3,%4}; }"
                                     :: "l"(op + (size_t)(1024 * b + 2 * i + e) * 1024), "r"(badd2(x.x, bmul2(s0, gt[0]))), "r"(badd2(x.y, bmul2(s1, gt[1]))),
                                        "r"(badd2(x.z, bmul2(s2, gt[2]))), "r"(badd2(x.w, bmul2(s3, gt[3]))), "r"(skip & (1u << (2 * i + e))) : "memory");
                    }
                    if (b == 0 && i < 3) __nanosleep(STSLEEP);
                }
                TSL(b ? 23 : 22);
            }
            TSL(17); TG(30);
        }
    } else {
        const int v = warp - 12;
        if (lane == 0) {
            if (v == 1) {
                mbar_init(bars + B_TAB * 8, 1); mbar_init(bars + B_TFREE * 8, 8); mbar_init(bars + B_KFREE * 8, 8); mbar_init(bars + B_KEYS * 8, 1);
                mbar_expect(bars + B_TAB * 8, 20480 + 1536); mbar_expect(bars + B_KEYS * 8, 64);
            } else if (v == 0) {
                mbar_init(bars + B_SLAB * 8, 1); mbar_init(bars + (B_SLAB + 1) * 8, 1); mbar_init(bars + B_TOK * 8, 2); mbar_init(bars + B_UFREE * 8, 1);
                mbar_expect(bars + B_SLAB * 8, 16384); mbar_expect(bars + (B_SLAB + 1) * 8, 16384);
            } else {
                mbar_init(bars + (B_STG + v - 2) * 8, 9); mbar_init(bars + (B_FIX + v - 2) * 8, 1);
                mbar_init(bars + (B_U + v - 2) * 8, 1); mbar_expect(bars + (B_U + v - 2) * 8, 16384);
                mbar_expect(bars + (B_STG + v - 2) * 8, 8192); mbar_expect(bars + (B_FIX + v - 2) * 8, v == 2 ? 32 : 2048);
            }
            mbar_init(bars + (B_PEER + v) * 8, 4);
#pragma unroll
            for (int i = 0; i < 6; i++) mbar_init(bars + (B_FULL + 6 * v + i) * 8, 1);
            asm volatile("fence.mbarrier_init.release.cluster;" ::: "memory");
        }
        __syncwarp();
        cluster_arrive();
        asm volatile("setmaxnreg.dec.sync.aligned.u32 48;");
        uint64_t pol; asm volatile("createpolicy.fractional.L2::evict_first.b64 %0, 1.0;" : "=l"(pol));
        auto load_chunk = [&](int n) {
            const bool gu = n < 16;
            mbar_expect(bars + (B_FULL + n) * 8, 8192);
            tma3d(sm + chunk_off(n), gu ? &tm_g : &tm_d, gu ? G * 64 : rank * 512 + (n - 16) * 64, gu ? rank * 512 + n * 32 : G * 64, bars + (B_FULL + n) * 8, pol);
        };
        uint32_t* const my_part = p.sc->part + ((2 * (32 * rank + v) + (q & 1)) * 56 + G) * 16 + g + 8 * (q >> 1);
        if (G < 56) {
#pragma unroll
            for (int n = 0; n < 8; n++) st_relaxed32(my_part + n * 8 * 56 * 16, 0);
        }
        cluster_wait();
        const bool lead = elect();
        bool kpend = G < 56 && v == 1;
        auto load_k = [&]() { if (lead) { load_chunk(10); load_chunk(11); load_chunk(12); load_chunk(13); } kpend = false; TSL(21); };
        uint32_t key = 0;
        if (v == 0) {
            TSL(19);
            asm volatile("prefetch.tensormap [%0];" :: "l"(&tm_x) : "memory");
            asm volatile("prefetch.tensormap [%0];" :: "l"(&tm_g) : "memory");
            { const int t0_ = clock(); while ((int)clock() - t0_ < SDELAY) __nanosleep(40); }
            if (lead) {
                int n = 0;
#pragma unroll 1
                for (int i = 0; i < 5; i++) {
                    if (G < 56) {
#pragma unroll 1
                        for (; n < ((FILL >> (4 * i)) & 15); n++) {
                            if (n >= IDEPTH) mbar_wait(bars + (B_FULL + n - IDEPTH) * 8);
                            if (n == 7) mbar_wait(bars + B_TFREE * 8);
                            load_chunk(n);
                        }
                    }
                    if (i < 4)
                        asm volatile("cp.async.bulk.tensor.4d.shared::cluster.global.mbarrier::complete_tx::bytes [%0], [%1, {%3, %4, %5, %6}], [%2];"
                                     :: "r"(sm + SM_SLAB + (i & 1) * 16384 + (i >> 1) * 8192), "l"(&tm_x), "r"(bars + (B_SLAB + (i & 1)) * 8),
                                        "r"(G * 16), "r"(64 * (i & 1)), "r"(4 * rank), "r"(i >> 1) : "memory");
                }
            }
            __syncwarp();
            TSL(20);
        } else if (v == 1) {
            if (lead) {
                asm volatile("cp.async.bulk.shared::cluster.global.mbarrier::complete_tx::bytes [%0], [%1], 20480, [%2];"
                             :: "r"(sm + SM_TAB), "l"(p.tab), "r"(bars + B_TAB * 8) : "memory");
                asm volatile("cp.async.bulk.shared::cluster.global.mbarrier::complete_tx::bytes [%0], [%1], 1536, [%2];"
                             :: "r"(sm + SM_F2), "l"(p.tab + 1280), "r"(bars + B_TAB * 8) : "memory");
                asm volatile("prefetch.tensormap [%0];" :: "l"(&tm_d) : "memory");
            }
            mbar_wait(bars + B_TFREE * 8);
            for (int it = 0; kpend && it < 16 * SPIN_LIMIT && !mbar_test(bars + B_TOK * 8); it++) {
                if (mbar_test(bars + B_KFREE * 8)) load_k(); else __nanosleep(60);
            }
        } else {
            const int sw = v - 2;
            if (sw == 0) {
                uint32_t tag;
                uint4* const my_stats = p.sc->stats + c * 8 + (lane >> 2);
                asm volatile("ld.relaxed.gpu.global.u32 %0, [%1];" : "=r"(tag) : "l"(&p.sc->epoch) : "memory");
                float ws = 0.f;
#pragma unroll
                for (int k = 0; k < 4; k++) {
                    const uint4 w = ldg128(reinterpret_cast<const uint4*>(p.wr) + 32 * k + lane);
                    ws += (blo(w.x) + bhi(w.x)) + (blo(w.y) + bhi(w.y)) + (blo(w.z) + bhi(w.z)) + (blo(w.w) + bhi(w.w));
                }
                if (q == 0) st_relaxed128(my_stats, make_uint4(0, 0, 0, 0));
                tag = tag % 3 + 1;
                sts32(sm + SM_TOK + 8, tag);
                bar_arrive(6, 160);
#pragma unroll
                for (int o = 1; o < 32; o <<= 1) ws += __shfl_xor_sync(0xFFFFFFFFu, ws, o);
                const uint32_t tb = ((tag & 1) << 15) | ((tag >> 1) << 31);
                const uint32_t ra = sm + SM_RED + (lane >> 1) * 144 + (lane & 1) * 64;
                const uint32_t kidx = 0xFFFF - (128 * (c & 15) + 16 * (lane >> 2) + 2 * (c >> 4) + ((lane >> 1) & 1));
                touch(ws);
                bar_sync(7, 160);
                const uint4 a0 = lds128(ra), a1 = lds128(ra + 16), a2 = lds128(ra + 32), a3 = lds128(ra + 48);
#define F(v) __uint_as_float(v)
                float ss = (F(a0.x) + F(a1.x)) + (F(a2.x) + F(a3.x)), dw = (F(a0.y) + F(a1.y)) + (F(a2.y) + F(a3.y));
                float sx = ((F(a0.z) + F(a1.z)) + (F(a2.z) + F(a3.z))) + ((F(a0.w) + F(a1.w)) + (F(a2.w) + F(a3.w)));
#undef F
                ss += __shfl_xor_sync(0xFFFFFFFFu, ss, 1); dw += __shfl_xor_sync(0xFFFFFFFFu, dw, 1); sx += __shfl_xor_sync(0xFFFFFFFFu, sx, 1);
                const float mean = sx * (1.0f / 1024.0f);
                const float var = fmaxf(ss * (1.0f / 1024.0f) - mean * mean, 0.f);
                const float m = rb(mean);
                float sd; asm("sqrt.approx.ftz.f32 %0, %1;" : "=f"(sd) : "f"(rb(rb(var) + 1e-5f)));
                const float rs = rcp(rb(sd));
                const float hi = rb(rs);
                const uint32_t p0 = pack_b(m, hi), p1 = pack_b(rs - hi, rs * (dw - m * ws));
                const uint32_t o0 = __shfl_xor_sync(0xFFFFFFFFu, p0, 2), o1 = __shfl_xor_sync(0xFFFFFFFFu, p1, 2);
                const uint32_t kr = ((p1 ^ (p1 >> 31 ? 0xFFFF0000u : 0x80000000u)) & 0xFFFF0000u) | kidx;
                const uint32_t k1 = __reduce_max_sync(0xFFFFFFFFu, kr), k2 = __reduce_max_sync(0xFFFFFFFFu, kr == k1 ? 0u : kr);
                if (q == 0) st_relaxed128(my_stats, make_uint4(prmt(p0, o0, 0x5410), (prmt(p0, o0, 0x7632) & 0x7FFF7FFFu) | tb,
                                                               prmt(p1, o1, 0x5410), lane == 0 ? k1 : lane == 4 ? k2 : 0u));
                TSL(9);
            }
            mbar_wait(bars + B_KEYS * 8);
            const uint32_t kk = lane < 16 ? lds32(sm + SM_KEYS + lane * 4) : 0u;
            const uint32_t m1 = __reduce_max_sync(0xFFFFFFFFu, kk);
            const uint32_t m2 = __reduce_max_sync(0xFFFFFFFFu, kk == m1 ? 0u : kk);
            key = sw ? m2 : m1;
            const int t = (0xFFFF - (key & 0xFFFF)) & 2047;
            {
                const uint4* row = reinterpret_cast<const uint4*>(p.x + (size_t)t * 1024) + lane;
                uint4 xr[4];
#pragma unroll
                for (int i = 0; i < 4; i++) xr[i] = ldg128(row + 32 * i);
                const uint4 stk = ld_relaxed128(p.sc->stats + ((t >> 1) & 7) * 128 + (t >> 4));
                if (lane == 0) {
                    sts32(sm + SM_TOK + 4 * sw, t);
                    if (c == 0 && sw == 0) st_relaxed32(&p.sc->epoch, lds32(sm + SM_TOK + 8));
                }
                const uint32_t se = (t & 1) ? 0x3232 : 0x1010;
                const uint32_t m = prmt(stk.x, 0, se), hi = prmt(stk.y, 0, se) & 0x7FFF7FFFu, lo = prmt(stk.z, 0, se);
                const uint32_t a = sm + SM_XSEL + lane * 32 + sw * 16;
#pragma unroll
                for (int i = 0; i < 4; i++) {
                    sts128(a + i * 1024, norm2(xr[i].x, m, hi, lo), norm2(xr[i].y, m, hi, lo), norm2(xr[i].z, m, hi, lo), norm2(xr[i].w, m, hi, lo));
                    if (sw == rank && 16 * i + (lane >> 1) == G) sts128(sm + SM_XRAW + (lane & 1) * 16, xr[i].x, xr[i].y, xr[i].z, xr[i].w);
                }
                proxy_fence();
                __syncwarp();
                if (lane == 0) mbar_arrive(bars + B_TOK * 8);
                TSL(42);
            }
        }
        mbar_wait(bars + B_TOK * 8);
        const uint32_t tag = lds32(sm + SM_TOK + 8);
        {
            if (G < 56) {
                const uint64_t dw = (uint64_t)((sm & 0x3FFFFu) >> 4) | (1ull << 16) | (64ull << 32) | (1ull << 62);
                const uint64_t dx = (uint64_t)(((sm + SM_XSEL + rank * 2048) & 0x3FFFFu) >> 4) | (2ull << 16) | (8ull << 32);
                const uint64_t dh = (uint64_t)(((sm + SM_H) & 0x3FFFFu) >> 4) | (8ull << 16) | (8ull << 32);
                float ag[4] = {0, 0, 0, 0}, au[4] = {0, 0, 0, 0};
                touch(ag); touch(au);
                TSL(13);
                auto issue = [&](int n) {
                    const uint64_t a = dw + (chunk_off(n) >> 4), a2 = a + 512, b = dx + n * 8;
                    mbar_wait(bars + (B_FULL + n) * 8);
                    mbar_wait(bars + (B_FULL + n + 1) * 8);
                    wg_fence();
                    wg_w<1>(ag, a, b); wg_w<1>(au, a + 256, b); wg_w<1>(ag, a + 128, b + 4); wg_w<1>(au, a + 384, b + 4);
                    wg_w<1>(ag, a2, b + 8); wg_w<1>(au, a2 + 256, b + 8); wg_w<1>(ag, a2 + 128, b + 12); wg_w<1>(au, a2 + 384, b + 12);
                    wg_commit();
                };
                issue(0);
#pragma unroll 1
                for (int n = 2; n < 16; n += 2) {
                    if (n < 10) { issue(n); wg_wait<1>(); } else wg_wait<0>();
                    if (n <= 10) {
                        bar_sync(4, 128);
                        if (v == (n & 2) && lead) { load_chunk(n + 12); load_chunk(n + 13); }
                        __syncwarp();
                        if (kpend) {
                            if (n == 10) mbar_wait(bars + B_KFREE * 8);
                            if (mbar_test(bars + B_KFREE * 8)) load_k();
                        }
                        if (n == 10) TSL(4);
                    }
                    if (n >= 10) issue(n);
                }
                wg_wait<0>();
                touch(ag); touch(au);
                TSL(14);
                if (q == 0) {
#pragma unroll
                    for (int r = 0; r < 2; r++) {
                        const uint32_t dst = mapa(sm, r), o = dst + SM_PAIR + rank * 1024 + v * 256 + g * 32;
                        st_async4(o, __float_as_uint(ag[0]), __float_as_uint(ag[1]), __float_as_uint(ag[2]), __float_as_uint(ag[3]), dst + SM_BAR + B_PAIR * 8);
                        st_async4(o + 16, __float_as_uint(au[0]), __float_as_uint(au[1]), __float_as_uint(au[2]), __float_as_uint(au[3]), dst + SM_BAR + B_PAIR * 8);
                    }
                }
                mbar_wait(bars + B_PAIR * 8);
                {
                    const uint32_t o = sm + SM_PAIR + v * 256 + g * 32 + q * 4, og = o + (p.up_first ? 16 : 0), ou = o + (p.up_first ? 0 : 16);
                    const float gs = rb(__uint_as_float(lds32(og)) + __uint_as_float(lds32(og + 1024)));
                    const float us = rb(__uint_as_float(lds32(ou)) + __uint_as_float(lds32(ou + 1024)));
                    const float hv = rb(siluf_(gs)) * us;
                    const uint32_t hd = sm + SM_H + (2 * v + (q >> 1)) * 128 + (q & 1) * 32 + g * 2, hb = pack_b(hv, hv);
                    sts16(hd, hb); sts16(hd + 64, hb);
                }
                proxy_fence();
                bar_sync(4, 128);
                TSL(15);
#pragma unroll 1
                for (int n = 0; n < 8; n += 2) {
                    const uint64_t a = dw + (chunk_off(16 + n) >> 4);
                    mbar_wait(bars + (B_FULL + 16 + n) * 8);
                    mbar_wait(bars + (B_FULL + 17 + n) * 8);
                    if (n == 6) TSL(24);
                    float d[4], e[4];
                    wg_fence();
                    wg_w0(d, a, dh); wg_w0(e, a + 512, dh); wg_w<1>(d, a + 128, dh + 16); wg_w<1>(e, a + 640, dh + 16);
                    wg_w<1>(d, a + 256, dh + 32); wg_w<1>(e, a + 768, dh + 32); wg_w<1>(d, a + 384, dh + 48); wg_w<1>(e, a + 896, dh + 48);
                    wg_commit();
                    wg_wait<0>();
                    touch(d); touch(e);
                    st_relaxed32(my_part + n * 8 * 56 * 16, (__float_as_uint((q & 2) ? d[2] : d[0]) & ~3u) | tag);
                    st_relaxed32(my_part + (n + 1) * 8 * 56 * 16, (__float_as_uint((q & 2) ? e[2] : e[0]) & ~3u) | tag);
                }
                TSL(16);
            } else {
                mbar_wait(bars + B_STG * 8);
            }
            if (v == 2 + rank) {
                const int t = (0xFFFF - (key & 0xFFFF)) & 2047;
                const int col = 4 * q + 2 * (lane >> 4) + ((lane >> 3) & 1), d = G * 16 + col;
                const float r = __uint_as_float((key & 0x80000000u) ? (key & 0x7FFF0000u) : (~key & 0xFFFF0000u));
                const float sg = rb(sigmoidf_(r));
                const float xn = blo(lds16(sm + SM_XSEL + (d >> 3) * 32 + rank * 16 + (d & 7) * 2));
                const float xv = blo(lds16(sm + SM_XRAW + col * 2));
                const uint4* src = reinterpret_cast<const uint4*>(p.sc->part) + c * 224 + lane;
                float s0 = 0, s1 = 0, s2 = 0, s3 = 0;
                {
                    uint4 pv[7];
                    int it = 0;
                    bool ok;
                    do {
                        uint32_t bad = 0;
#pragma unroll
                        for (int i = 0; i < 7; i++) pv[i] = ld_relaxed128(src + 32 * i);
#pragma unroll
                        for (int i = 0; i < 7; i++) bad |= (pv[i].x ^ tag) | (pv[i].y ^ tag) | (pv[i].z ^ tag) | (pv[i].w ^ tag);
                        ok = __all_sync(0xFFFFFFFFu, (bad & 3) == 0);
                    } while (!ok && ++it < SPIN_LIMIT);
#pragma unroll
                    for (int i = 0; i < 7; i++) {
                        s0 += __uint_as_float(pv[i].x); s1 += __uint_as_float(pv[i].y); s2 += __uint_as_float(pv[i].z); s3 += __uint_as_float(pv[i].w);
                    }
                }
                TSL(25);
                const bool u16 = lane & 16, u8 = lane & 8;
                const float y0 = (u16 ? s2 : s0) + __shfl_xor_sync(0xFFFFFFFFu, u16 ? s0 : s2, 16);
                const float y1 = (u16 ? s3 : s1) + __shfl_xor_sync(0xFFFFFFFFu, u16 ? s1 : s3, 16);
                float y = (u8 ? y1 : y0) + __shfl_xor_sync(0xFFFFFFFFu, u8 ? y0 : y1, 8);
                y += __shfl_xor_sync(0xFFFFFFFFu, y, 4);
                const float z = rb(xn + rb(rb(y) * sg));
                const float gt = rb(siluf_(z));
                mbar_wait(bars + B_FIX * 8);
                const float o = xv + rb(blo(lds16(sm + SM_FIX + col * 2)) * gt);
                if (!(lane & 4)) p.out[(size_t)t * 1024 + d] = __float2bfloat16(o);
                TSL(26); TG(29);
            }
        }
    }
    }
}

__device__ __align__(128) const uint32_t g_tab[5504] = {
0x2fff3000,0x2e7c2fd4,0x2fc92fd4,0xad72af5a,0x2ff82ffc,0x230e2c07,0x2faf2fbc,0x217ea934,0x2fed2ff4,0xad4da8d5,0x2f912fa0,0x2e5e2bb7,
0x2fdd2fe6,0xb000af46,0x2f6e2f80,0x2fdd2fc9,0x2ff42fff,0x2e1f2fc9,0x2e1f2e7c,0xa875ad72,0x2fbc2fdd,0x9fd92a4e,0x2d4d2dba,0x2cd825db,
0x2f5a2f91,0xaeb5ac07,0x2c5d2cd8,0x30002f30,0x2ed02f1a,0xaf80aff4,0x2aaa2bb7,0x2cb02f1a,0x2fdd2ffc,0x2dba2fbc,0x2a4e2c07,0x25dba934,
0x2f462fa0,0xa7652875,0x25152875,0x2f802d27,0x2e3f2ed0,0xafa0ad72,0xa17e1cb6,0x2e3f2fe6,0x2cd82d96,0xadfeafd4,0xa934a6a1,0xa44e29f1,
0x2fbc2ff8,0x2d4d2faf,0x9fd9230e,0x2cd8217e,0x2e992f46,0xaa4e2515,0xaa4ea765,0x2fd42f80,0x2cb02dba,0xafffae99,0xad72ac5d,0x27652dba,
0x28752b05,0xab5eaee9,0xaf1aae5e,0xae3fa934,0x2f912ff4,0x2cd82fa0,0xac07a8d5,0x2f302bb7,0x2dba2ed0,0xac5d1cb6,0xae99ad72,0x2dba2fe6,
0x29932c5d,0xafc9af6e,0xafe6af6e,0xaaaa25db,0xa17e244e,0xa30ead4d,0xafafaffc,0xaff8aee9,0x2f5a2fed,0x2c5d2f91,0xaeb5ad4d,0x30002e5e,
0x2cb02e3f,0xad72a17e,0xafffafa0,0x27652e3f,0x217e2993,0xaf02afe6,0xaf02afc9,0xaf1aaaaa,0xab05a5db,0x2814aa4e,0xac07adba,0xad4dafdd,
0x2f1a2fe6,0x2bb72f80,0xaff4af46,0x2f1a2fc9,0x2b052d96,0xae5ea6a1,0xaee9afd4,0xa93429f1,0xa5db244e,0xadbaaffc,0xaa4ead4d,0xafddaee9,
0xaddcabb7,0x2cb0a17e,0x2765a17e,0x1cb6ad00,0x2ed02fdd,0x2aaa2f6e,0xaf80b000,0x2cb02fdd,0x28752cd8,0xaf1aa934,0xab5eadfe,0xae3fa44e,
0xab05a17e,0xac07afaf,0x2814a30e,0xad4daff8,0xaf6eaddc,0x2eb52765,0x2eb52cb0,0x2dba1cb6,0x29932f5a,0xa7652e99,0x25152e99,0x2aaaad96,
0xafa0ab05,0xabb7afed,0xaff4acd8,0x28d52ffc,0xa814af02,0x2f912d27,0x9fd9ae1f,0xaee9ae3f,0x2fd42c32,0xaf5a1cb6,0x30002d72,0x2fd42515,
0x28752f46,0xa8d52e7c,0xa8d52c32,0x2e3fa993,0xafedac5d,0xa934b000,0xaf30af5a,0xa8142eb5,0x1648adfe,0x2e992e5e,0x2c87a814,0xa9f1affc,
0x2fe62e1f,0xafffa875,0x2ddc2ff4,0x2ed02e1f,0x26a12f30,0xa9f12e5e,0xad96244e,0x2fd41fd9,0xafffad27,0xa515aff4,0xac32aff4,0xaddc2b5e,
0x2875acb0,0x2d272f46,0x2fa02993,0x2875aed0,0x2ee92f6e,0xaf91ac87,0x1fd92e99,0x28143000,0x244e2f1a,0xab052e3f,0xaf91a875,0x2fbc2b5e,
0xafd4addc,0x1648afc9,0x1648ae7c,0xafdd9cb6,0x2c32aa4e,0x2aaa2fd4,0x2f802e99,0x2e7caa4e,0x2d002ffc,0xae1fae5e,0xad272814,0xabb72dfe,
0x1fd92f02,0xac072e1f,0xafedad27,0x2dfe2e3f,0xaf6eae7c,0x25dbaf80,0x2c5daaaa,0xaf6eac32,0x2ddca5db,0x25153000,0x2c323000,0x2fff26a1,
0x28d52fbc,0xabb7af91,0xaff4ab05,0xafa0244e,0x96482ee9,0xac872dfe,0xae99af30,0x29f12fbc,0xaed0af02,0x2993af1a,0x2f46217e,0xacb0af02,
0x2f1a1cb6,0xa30e2fc9,0xa30e2e7c,0x2e1f2ddc,0x9fd92eb5,0xa44eb000,0xae5eaf5a,0xaf30ac5d,0xa17e2ed0,0xad002ddc,0xabb7afff,0xa17e2fe6,
0xadfeaf6e,0x2c07ae99,0x2fed2c87,0x9fd9b000,0x2fd42814,0xa9f12f30,0xad962934,0x26a12fed,0xaaaa2d00,0x2765afa0,0xa515afa0,0xa993afaf,
0xa5152eb5,0xad722dba,0x9cb6af6e,0xac322eb5,0xad00afbc,0x2d27adfe,0x2e1f2f30,0x2bb7aee9,0x2ffc2b5e,0xacd82e3f,0xafeda875,0xab052f1a,
0xadba2993,0x2c87ae7c,0x2c87ac32,0x2a4eaf46,0xaddc2d96,0xafe62c5d,0xaed02c5d,0x2fffa9f1,0x2e1fad4d,0x2e3f2814,0x2f02ac07,0xad27ab05,
0xae5e2d00,0x9fd9af1a,0xaf302b5e,0xa44e2faf,0x2e99acb0,0xad962f80,0x2f5aaaaa,0x2e99aed0,0xae3f2d72,0xaff82c32,0xaff82515,0x2f021cb6,
0x2ee9ac87,0x2d4d29f1,0x2ffc9648,0xa44eae99,0xaf6e2b05,0x26a1afbc,0xafd4a44e,0xadba2f91,0x2fc9a8d5,0xaf462e3f,0x2f802875,0x2fe6a8d5,
0xae992d4d,0xb0002c07,0xaf6ea814,0x2c872b05,0x2f80ab5e,0x2c322bb7,0x2e7c2bb7,0x2aaaaff8,0xaff42765,0x2b5eafff,0xad27ad72,0xaff42cb0,
0x2fed1648,0xaffc2c5d,0x2b052eb5,0x2cd82a4e,0xaee92d27,0xaffc2bb7,0xad4dad00,0x244e2e1f,0x2fdda993,0x29f12cb0,0x29f12ed0,0x2eb5af46,
0xafe61648,0x2d72afdd,0x9cb6afd4,0xaed01648,0x2f022934,0xafa02814,0xa8d52fed,0xa30e2f30,0xaf302d00,0xafed2b5e,0xa814af1a,0xa9342faf,
0x3000a765,0x26a12d72,0xa5db2fff,0x3000acb0,0xaf46a6a1,0x2ed0af5a,0x2cb0af5a,0xa993ac87,0x2d272cd8,0xae3f9fd9,0xaf022d4d,0xae1f2fbc,
0xaf6e2cd8,0xafd42b05,0x26a1affc,0xadba2fed,0x2fe6a30e,0x1cb62e1f,0xad722f1a,0x2ed0a30e,0xae1faaaa,0x2fafae7c,0x2fafac32,0x28d5af80,
0x29342e99,0xac07a9f1,0xafbc1648,0xaffc2c87,0xafa02cb0,0xafaf2aaa,0x2d00af80,0xafa02ed0,0x2f911648,0xa44e2eb5,0xafbc2c5d,0x2b052a4e,
0xac87acd8,0x3000ad4d,0x2f6e1fd9,0x2e99afbc,0x9cb62faf,0xa515ad27,0xac32ad27,0xad72a30e,0xafc92c87,0xaf802a4e,0x2f46adba,0xafe62c87,
0x2f02244e,0xa8d52f30,0xafa01fd9,0xa30e2e5e,0xa934ae1f,0x2fbcabb7,0x2c072d00,0x2ffcad27,0xaa4e2fff,0x26a1aed0,0x26a1afe6,0x1648addc,
0xaf4629f1,0xac3225db,0xae7c25db,0x29931648,0xab5e2f91,0xafaf2e5e,0xad002fed,0x2f1aad4d,0x2ee9a875,0xaf302ff8,0x2dfea17e,0x2fbcaff4,
0x2c5dafc9,0xa9f12d72,0x2d96afff,0x2c5dae7c,0xaf022993,0xab5e2515,0xab5ea765,0xa30e2aaa,0xacd82fd4,0xaf302dba,0xaf912f6e,0x2c07a6a1,
0x2d969fd9,0xafdd2fed,0x25db2c07,0x2f5aadfe,0x2e7caff8,0xad722f02,0x2fffae3f,0x2fc9aff8,0xaeb52934,0xaa4e244e,0x9648acd8,0xac5d2dfe,
0xaddc2ff8,0xae7c2d00,0xafc92d00,0x9cb628d5,0x2bb72515,0xaff82f80,0xab5e2f46,0x2bb7a765,0x2fbcaf5a,0xaf302fdd,0x2dfea5db,0x2ee9ad96,
0xae5e28d5,0xa934230e,0x2b05af02,0xaee92fa0,0xaeb52fff,0xad962c32,0xad962515,0xac872ddc,0x276529f1,0xaf802eb5,0xaf462fdd,0xa51529f1,
0x2ff4adfe,0xaff82fed,0x217e2c07,0x28759fd9,0xadfe2875,0xa814217e,0x2e5eaff8,0xaffc2ff4,0xaf5a2fe6,0xac872aaa,0xa6a1a993,0xaf5a2fc9,
0x9cb62c87,0xae7c2d96,0xafc92d96,0xaddc2eb5,0x2f1aac07,0xafaf2f30,0xad002f91,0xab5e2cd8,0xad962814,0xa5db1fd9,0x2fddaf91,0xaf5a2ee9,
0xafc92faf,0xaaaa28d5,0x2993ae1f,0xafe62faf,0xa8d52ddc,0xad002c32,0xad002515,0xaff82fff,0x2d4da6a1,0xae5e2dba,0xafed2f6e,0xaf912fd4,
0xad272765,0xa30e1cb6,0x2fafaddc,0xad272cb0,0xaffc2f5a,0xa81425db,0x2e5eafdd,0xadfe2d96,0xac5d2ee9,0xaa4e2934,0x9648ab05,0xaeb52e5e,
0x2993230e,0xac322b5e,0xae7c2b5e,0xaf462f02,0xacb026a1,0x9cb61648,0x2ddcaa4e,0xa76526a1,0xaff42ee9,0xa17e1fd9,0x2ff8af91,0xa8752814,
0xadfe2fa0,0xa44e230e,0x2cd8af02,0xa93428d5,0x96482aaa,0xa5db2515,0xa5dba765,0xa9f12993,0x2f462f5a,0x2c322e99,0x2e7c2e99,0xa993ad96,
0x2f1a2f30,0xa875244e,0x2e3f2e5e,0x2b5e1fd9,0x2ee92f02,0xaf30ad27,0x2dfe2e1f,0x2fbc2e3f,0x2eb52ed0,0xaf6eafff,0x2dba2ddc,0x2eb52fe6,
0x28752993,0xa8d52515,0xa8d5a765,0x2e3f2aaa,0x244e26a1,0xaf91ad96,0xab05a9f1,0x2fbc2fd4,0x96481fd9,0xae99afed,0xac87ac07,0x29f12dfe,
0xa515a17e,0x9cb6abb7,0xad72ad00,0xac32a17e,0xac5dab05,0xaf5aacd8,0xb000afed,0x2eb52ffc,0xaddcad27,0xae7caff4,0xafc9aff4,0x9cb62b5e,
0xaf02ae7c,0x217eaaaa,0xaf1aaf80,0xaf02ac32,0xafbcaf6e,0x2f302c87,0xadfeae99,0xaee9b000,0xafedafa0,0xaf30aff4,0xa934abb7,0xa81428d5,
0xafd4afff,0x1648ac32,0x1648a515,0xafddaddc,0xaed0af6e,0x2f462c5d,0x299325db,0xacb0af6e,0xad00adfe,0x2e1f2fed,0x2d272c07,0x2bb79fd9,
0xadfeaf02,0xa814ae1f,0x2e5e2d27,0xaffcae3f,0xaa4eacb0,0x2e992993,0x2fd42f46,0xaa4eaed0,0x1cb6a5db,0x2e7c3000,0x2fc93000,0x2ddc26a1,
0x2b5e2814,0xa8752934,0x2e3f2f30,0x2f1a2fed,0x1648a814,0x2c879fd9,0x2e992f91,0xa9f1aee9,0x2c322875,0x2f802fa0,0x2aaa2d27,0x2e7c2875,
0x2f1a2ddc,0xa30e2c32,0xa30e2515,0x2e1f2fff,0x2ffc2fd4,0xafedad96,0xacd8a9f1,0xab0526a1,0x2e1f2c32,0x2ff42d72,0xa8751cb6,0x2e1f2515,
0x2ffc2f6e,0x28142e99,0xae5eac87,0x2dfe3000,0x2eb52fbc,0xaf5aab05,0xb000af91,0xac5d244e,0x29932d00,0xac32afa0,0xae7cafa0,0xaf46afaf,
0x2fe62fd4,0x2ddc3000,0xafffaf5a,0x2ed02fd4,0x2d002ee9,0xad271fd9,0xae1faf91,0xabb72814,0x9fd928d5,0xae5eaff4,0xa44eabb7,0xaf30afa0,
0xadbaaaaa,0x2c87a515,0x2c872765,0x2a4ea993,0x9cb62d96,0xacb02c5d,0xa7652c5d,0x2ddca9f1,0xaff8adfe,0xa30eafbc,0xafafaee9,0xa17e2f30,
0x244ead00,0x2dfe2f1a,0x2934ab5e,0xacd8afaf,0x2fdd2e7c,0xb000a993,0x2f6e2f46,0x2fdd2c32,0xae3f9cb6,0xaff8a765,0xaff8acb0,0x2f022ddc,
0xac07afdd,0x2dfeaa4e,0x1fd9adba,0xafeda5db,0x2f6e2934,0xa6a12ee9,0x2fd42e5e,0x2dbaab05,0x27652f1a,0xaaaaaff4,0xa9932bb7,0xa5152f1a,
0xafddadfe,0xadbaaee9,0xaa4eafbc,0xa5db2f30,0x2aaaab5e,0x2fc92bb7,0x2fe62bb7,0xa993aff8,0x2e3f2fc9,0xafa01cb6,0xa17e2ddc,0x2e3f2e7c,
0xae5e9648,0x2d4dac5d,0xaf91aeb5,0xafedaa4e,0xac07aff8,0x1fd9afaf,0x2dfea30e,0xafeda17e,0x2fdd2aaa,0x29f12fe6,0x29f12fc9,0x2eb5a993,
0xa5152dba,0xaddcae99,0xafffac5d,0xac322dba,0xaf02af30,0x2fa02c07,0x28d5acd8,0x230eaf91,0x2934ad00,0x2e5eab5e,0x2ee92f1a,0xab05afaf,
0x2dba2fc9,0xac5d2ddc,0xae991cb6,0x2dba2e7c,0xaf80a6a1,0x2765af5a,0xa515af5a,0xaf46ac87,0x217eae5e,0x230e2ffc,0x2faf2dfe,0x2ff82814,
0x2f6e244e,0x2fd42934,0xa6a12dfe,0x2dbaacd8,0xa5152e3f,0xafffa17e,0xaddcafa0,0xac322e3f,0xae1faf80,0x2fafa515,0x2faf2765,0x28d5af46,
0x2f9125db,0xaee92a4e,0xa8142dba,0x9fd92fdd,0x2f1a2e7c,0x2bb72f46,0xaff4a993,0x2f1a2c32,0xaf309648,0xacd8aeb5,0x2c07ac5d,0xaf91aa4e,
0x25dbae5e,0x2dba2dfe,0x2a4e2ffc,0x2fdd2814,0x2d722faf,0xae7cad27,0xafc9ad27,0xafffa30e,0x27652fdd,0xa9932f6e,0xaaaab000,0xa5152fdd,
0xaf02ae5e,0x28d5af91,0x2fa02d4d,0x230eafed,0x2f91217e,0xa8142faf,0xaee9230e,0x9fd92ff8,0xaa4e2d72,0x26a1afc9,0x26a1ae7c,0x1648afff,
0xaf8029f1,0xafc925db,0xafe625db,0x2f461648,0x2fa0a934,0x2bb72cd8,0x2ff4a44e,0xa8d5adfe,0xafbc2875,0x2934aff8,0xaffc217e,0xac072ff4,
0x2fd4a765,0xaf5a2ddc,0x30009cb6,0x2fd4acb0,0xaf02aaaa,0xab5eacb0,0xab5eaed0,0xa30e2f80,0x2e5e2c5d,0xab053000,0x29342f5a,0x2ee9aeb5,
0xad96ad4d,0x2fddacd8,0xa5dbafbc,0xaf5a1fd9,0x2cb02e1f,0xaddca875,0x1cb62ff4,0x27652e1f,0xa6a1af91,0x29f1afed,0x2d96ae5e,0xafd42d4d,
0x9cb62ff8,0xafe62d00,0xaed02d00,0x2d7228d5,0x2875afe6,0x2d272993,0x2fa0aaaa,0x2875afc9,0xac072f5a,0x2934afdd,0xaffc25db,0xafbc2d96,
0x2cd8af1a,0x2f91ae3f,0x2f302875,0xac07ab5e,0xaeb52d72,0xad96a765,0xad96acb0,0xac872fff,0x2fc9aa4e,0xa9932fd4,0x2aaa2e99,0x2fe6aa4e,
0xaff41fd9,0x2ff8acd8,0xa17eafbc,0xa875ad4d,0x2ffca875,0x2ee9a17e,0xa44e2ff8,0x2d4daff4,0xaf6ea515,0x25dbaf46,0x2c5daf80,0xaf6e2765,
0x2d722c87,0xafe62d96,0xaed02d96,0x9cb62eb5,0xa8d5aee9,0x2bb72b05,0x2ff4a934,0x2fa0ae5e,0x2d962c07,0x25db2d4d,0xafdd2b05,0x2f5aa814,
0xa765af02,0x2f46af1a,0x2f80217e,0x2515af02,0xa8d52fff,0xad00a765,0xad00acb0,0xaff82d72,0x2dfeaeb5,0xacd83000,0x244e2f5a,0x29342c5d,
0xa17e2fc9,0xad002fff,0xabb7ad72,0xa17e2e7c,0x2d4daf5a,0x2ee9a5db,0xa44e2fdd,0x2ffcad96,0xafd42c07,0x29f1af91,0x2d96af30,0xa6a1acd8,
0x2f46230e,0xafc92b5e,0xafe62b5e,0xaf802f02,0xae7c2eb5,0xafff2dba,0x2d72af6e,0xafc92eb5,0x2ff4a814,0x217e2d4d,0xaff82b05,0x28752c07,
0xad4dab5e,0x2fedae3f,0x2e5e2875,0x2f91af1a,0x96482f80,0xa5dbacb0,0xa5dbaed0,0xa9f1aaaa,0xad729648,0xa515a6a1,0xac32a6a1,0x9cb62a4e,
0xae1f2ffc,0xae3f2c07,0xaf022fbc,0x2d27a934,0x2cd8230e,0xaffc2fa0,0x2b0528d5,0x2fedaf02,0x2e99afe6,0xad962f46,0x2f5aaf80,0x2e99afc9,
0x230eaddc,0x2d27aed0,0x2d27afe6,0xafaf2fff,0xafbc2c87,0x1fd9a9f1,0xad4d1648,0xacd82e99,0xaa4e2f30,0xac5d2814,0xaeb52fed,0x96482934,
0x2ed0a8d5,0xaf802e3f,0x2aaa2875,0x2cb0a8d5,0x2e99affc,0x3000afbc,0x2f6eac07,0xac872934,0xa993a8d5,0x2ed0afaf,0x2cb0afaf,0xaf462e1f,
0xaff42ed0,0x2b5ead72,0xad271cb6,0xaff42fe6,0xa44e2dba,0x9fd9a6a1,0xaf302fd4,0xae5e2f6e,0x2fbcad27,0x2d4dabb7,0x9fd92d00,0x2cd8ae1f,
0x2c87af80,0x2f5aae7c,0x2f5aac32,0x26a1aaaa,0xacb01648,0x2fffafdd,0x2d72afd4,0xa7651648,0xafaf2f91,0x2f1aafbc,0xab5ea44e,0xad002b05,
0x2b05230e,0xa44e28d5,0xafbc2fa0,0x2f91af02,0x3000aed0,0x26a19cb6,0xa5db2d72,0x3000afe6,0x2aaaaeb5,0x2c32a9f1,0x2e7ca9f1,0x2f80afdd,
0xad27244e,0x2e3fad4d,0x2f02affc,0x2e1faee9,0xaa4e2e5e,0xaeb52f30,0xac5d1fd9,0x9648244e,0x2cb0a30e,0xad722e1f,0xafff2f1a,0x2765a30e,
0x2ff8af46,0xabb72cb0,0xabb72ed0,0x2b5ea993,0x2b05ae99,0xa81429f1,0x2c079648,0x2d4dac87,0xafa02fe6,0xafaf2f80,0x2d00af46,0xafa02fc9,
0xa9342dba,0xafed2fd4,0xa814a6a1,0xaf302f6e,0x2c87a44e,0xb0002ffc,0xaf6e2d4d,0xae992ee9,0x2fffaf02,0xafe62ff8,0xaed02ff8,0xaddc2e3f,
0xaed02c87,0xaaaa2a4e,0x2f80adba,0xacb02c87,0xafaf2fed,0xab5e2b05,0x2f1aaffc,0xad002cd8,0xab052e1f,0xac072bb7,0x2814ad00,0xad4d2d27,
0x29f11cb6,0xac5d2c32,0xac5d2515,0xad962d72,0x2d722d96,0x25152c5d,0x2c322c5d,0x1cb6a9f1,0x2d272d4d,0xad00a814,0x2bb72c07,0x2e1f2b05,
0x2cd82d00,0xaffcaf1a,0x2b052b5e,0x2fed2faf,0x2c872cb0,0xadbaaf80,0x2a4e2aaa,0x2c872ed0,0xae3faddc,0xaff8aed0,0xaff8afe6,0x2f022fff,
0xaee9ae99,0xad4daf6e,0xaffcb000,0x244e2c87,0xaf6eaf30,0x26a1a814,0xafd4afed,0xadbaa934,0xafc9afa0,0x2f462d00,0xaf80afaf,0xafe6afa0,
0xac87ad4d,0x9648ac07,0x29f12814,0xae99ab05,0xa993ab5e,0x2ed02bb7,0x2cb02bb7,0xaf46aff8,0xa30ea765,0x2f1a2fff,0x2e1f2d72,0xa30eacb0,
0x244e1648,0x1fd92c5d,0x2f302eb5,0x2e5e2a4e,0x2ee92e1f,0x2ffc2f02,0x2d4d2e3f,0xa44ead27,0x2fdd2f80,0x29f12e7c,0x29f12c32,0x2eb52aaa,
0x2fe63000,0xad72a5db,0x1cb626a1,0x2ed03000,0x2f022f91,0xafa0afbc,0xa8d5a44e,0xa30e2b05,0x2b052d00,0xa44e2b5e,0xafbcaf1a,0x2f912faf,
0x16482765,0xafd4ad72,0xafddafff,0x16482cb0,0xaaaaa6a1,0xac32af5a,0xae7caf5a,0xaf80ac87,0xae1facd8,0x2d001fd9,0xabb7ad4d,0xad27afbc,
0xaf6eae5e,0xafd4af30,0x26a19fd9,0xadbaa44e,0xafe6aff4,0x9cb6ad27,0x2d722b5e,0xaed0aff4,0xae1faf46,0x2faf2cb0,0x2faf2ed0,0x28d5a993,
0xa934ac87,0x2c072f6e,0x2fbc3000,0x2ffc2e99,0xa8d5acb0,0x2875aaaa,0x2e3f2f80,0xa8d5aed0,0x29341648,0x2fed2eb5,0x28142c5d,0x2f302a4e,
0x2e992cd8,0x16482d4d,0xa9f19fd9,0x2c872fbc,0x2fff2faf,0xafe6ad27,0xaed0ad27,0xaddca30e,0x2fc92e99,0x2f802f5a,0xaf46ad96,0x2fe62e99,
0x2f022fed,0xa8d52b05,0xafa0affc,0xa30e2cd8,0x29342d27,0xafbcaf02,0xac07ae3f,0xaffcae1f,0xaa4e9cb6,0x26a1ac32,0x26a1a515,0x1648ad72,
0xaaaa29f1,0xaed025db,0xacb025db,0x2f801648,0xaf1aaf91,0x2875ae5e,0xae3fafed,0xab5e2d4d,0x2c07a875,0x2b052ff8,0x2d4da17e,0xa814aff4,
0x2eb52fc9,0xaf6ead72,0x2dba2fff,0x2eb52e7c,0xaf02af80,0xab5eafe6,0xab5eafc9,0xa30e2f46,0x2cd8a6a1,0x2f302d96,0x2f9129f1,0xac07afd4,
0x2d962ffc,0xafdda44e,0x25db2ee9,0x2f5a2d4d,0xae7ca17e,0x2d72abb7,0xafffad00,0xafc9a17e,0x2c5da934,0x2f5aa44e,0x30002cd8,0xaeb5adfe,
0x2d722ff8,0xacb02d00,0xa7652d00,0x2fff28d5,0xaf02a515,0x217eaf80,0xaf1aaf46,0xaf022765,0xa814af5a,0x2b052fdd,0x2d4da5db,0x2c07ad96,
0x2e5e2fa0,0x29342ff4,0xab052bb7,0x2ee9a8d5,0xaeb59cb6,0xad96aed0,0xad96afe6,0xac872d72,0xa765af6e,0x2f802c5d,0x2f4625db,0x2515af6e,
0x2ff42d4d,0xaff8a44e,0x217e2ee9,0x28752ffc,0xad4d2875,0xafbc217e,0xacd8aff8,0x1fd92ff4,0xaa4eafe6,0x2e99aaaa,0x2fd42993,0xaa4eafc9,
0x2fff2c87,0xacb02d96,0xa7652d96,0x2d722eb5,0xab5e2c07,0x2875af30,0xae3faf91,0xaf1aacd8,0xad96afbc,0xa5dbaffc,0x2fdd2934,0xaf5aac07,
0x2fc92875,0x2aaa2fa0,0xa9932d27,0x2fe62875,0xa8d52d72,0xad00aed0,0xad00afe6,0xaff89cb6,0xad4dafd4,0x2e5e2d96,0x2fed29f1,0x2f91a6a1,
0x2e1fa765,0x2ff49cb6,0xa8752ddc,0x2e1facb0,0x1fd92f5a,0xafbc25db,0xacd8afdd,0xad4d2d96,0xaeb5aee9,0x2f5aa934,0x30002b05,0x2c5dae5e,
0x2f80230e,0xaed02b5e,0xacb02b5e,0xaaaa2f02,0x2cb02fd4,0x1cb63000,0xaddcaf5a,0x27652fd4,0xaff4ac07,0xa17eaffc,0x2ff82934,0xa875afbc,
0x2dfea8d5,0x244e2ff4,0xacd82bb7,0x29342fa0,0x96482f46,0xa5dbafe6,0xa5dbafc9,0xa9f1af80,0xafff9648,0xae7ca6a1,0xafc9a6a1,0x2d722a4e,
0x2ff81fd9,0x230e2ee9,0x2faf2814,0x217eaf91,0xafeda30e,0x2d4dafa0,0xaf91a8d5,0xae5e2f02,0x2fdd2515,0xb0002aaa,0x2f6e2993,0x2fdda765,
0x230eafff,0x2d27afc9,0x2d27ae7c,0xafaf2d72,0xa8142fdd,0xaffc2a4e,0xadfe2dba,0x2e5e25db,0x2a4eaf91,0x2c5d2c07,0x2eb5acd8,0x1648af30,
0xac322f1a,0x2993aff4,0xaf462bb7,0xae7c2f1a,0x2fdd1fd9,0x2dba2814,0x2a4e2ee9,0x25dbaf91,0xaf46a8d5,0x2765afaf,0xa515afaf,0xaf802e1f,
0x2e3f2c32,0xafa02ddc,0xa17e2fff,0x2e3f2515,0xacd8adba,0x2dfe26a1,0x2934afd4,0x244eaf6e,0xa8142ff8,0xadfe2faf,0xaffc230e,0x2e5e217e,
0x2c87af46,0x2f5aa515,0x2f5a2765,0x26a1af80,0xae7c2dba,0x9cb6ae99,0xaddcac5d,0xafc92dba,0x2fafab05,0xaf1a2ee9,0x2b5e2e5e,0x2d002934,
0xaf91a30e,0xacd8a8d5,0x2c07afa0,0xaf302f02,0x2dba2c32,0xac5d2fff,0xae992ddc,0x2dba2515,0xa993aeb5,0x2fc9a9f1,0x2fe6a9f1,0x2aaaafdd,
0xa17e2fed,0xa30eadfe,0xafaf9fd9,0xaff82c07,0x2a4eafed,0x2eb5af91,0x2c5d2d4d,0x1648ae5e,0xae7c2e3f,0xaddca17e,0x9cb6afa0,0xafc92e3f,
0x2ff8a993,0xabb72fe6,0xabb72fc9,0x2b5e2aaa,0xaf30a5db,0x2fbcaa4e,0x2ee9adba,0x2dfeafdd,0x2f1a2515,0x2bb72993,0xaff42aaa,0x2f1aa765,
0xab05adba,0x2e5eafd4,0x2ee926a1,0x2934af6e,0xa5db2fed,0xadba9fd9,0xaa4eadfe,0xafdd2c07,0x2ddcaf02,0xacb02ff8,0xa7652ff8,0x9cb62e3f,
0xac322fdd,0xaf462f6e,0x2993b000,0xae7c2fdd,0x2fafacd8,0x2b5e2934,0xaf1a2dfe,0x2d00244e,0xaf30a17e,0x2ee9afaf,0x2fbca30e,0x2dfeaff8,
0x29f12ddc,0xac5da765,0xac5dacb0,0xad969cb6,0xa993aa4e,0x2765ac87,0xa515ac87,0xaaaa2dba,0xafa02f30,0xabb7244e,0xaff42e5e,0x28d51fd9,
0x28142bb7,0xaf912e1f,0x1fd92d27,0x2ee9ad00,0x2fd4aed0,0xaf5a2fff,0x3000addc,0x2fd4afe6,0x2fafaf46,0x2fa0ae7c,0x2fa0ac32,0xad002993,
0xa44eac5d,0x2f91b000,0x2b05af5a,0xafbc2eb5,0xb0002dfe,0x2c87ae5e,0xae992814,0xaf6e2ffc,0xa5152e1f,0x9cb6a875,0xad722ff4,0xac322e1f,
0x26a12b05,0xa9f12cd8,0xad962fed,0x2fd4affc,0x2fffae1f,0x2515230e,0x2c32230e,0x2ddcaf1a,0x2875ae7c,0x2d27aaaa,0x2fa0af80,0x2875ac32,
0xaee929f1,0x2f91ae99,0x9fd9ac87,0xa8149648,0xafed2f1a,0xaf302e3f,0xa934a875,0xa8142b5e,0xa6a12ddc,0xb0002fc9,0xb0002e7c,0x25db1cb6,
0x2ed0aa4e,0xaf462fd4,0xa9932e99,0x2cb0aa4e,0x2e3faffc,0xad272e5e,0x2e1fa814,0x2f02adfe,0x9fd9abb7,0x2c07ad27,0x2fedae1f,0xadfe2d00,
0xaf6e2cb0,0x25dba993,0x2c5daf46,0xaf6e2ed0,0xaddc2fdd,0xa5159648,0xac329648,0xafff2fd4,0x28d52814,0xabb72934,0xaff42f30,0xafa02fed,
0x3000aee9,0x2e99adfe,0xac872f30,0x2f6eafbc,0x2c32af02,0x2f80af1a,0x2aaa217e,0x2e7caf02,0xab5e9cb6,0x2ff4afc9,0x2ff4ae7c,0x2d27addc,
0xaffc2eb5,0x2fedb000,0x2cd8af5a,0x2b05ac5d,0xa17e2c32,0xad002d72,0xabb71cb6,0xa17e2515,0x2dfea9f1,0xac072c87,0xafed2e99,0x1fd91648,
0x2fd4afbc,0xa9f12b05,0xad962f91,0x26a1a44e,0x2aaaae3f,0xa76528d5,0x251528d5,0x2993a875,0xafe62eb5,0xaddc2dba,0x2fffaf6e,0xaed02eb5,
0xae3f2fbc,0xae1f2dfe,0x2d27af30,0xaf022ee9,0x9fd92b5e,0xae5e2e3f,0xa44ea875,0xaf302f1a,0x2d96a993,0xae992e7c,0xae992c32,0xaf5a2f46,
0x299329f1,0xa76525db,0x251525db,0x2aaa1648,0x28d52934,0xaf02acd8,0x230e244e,0x2fa02dfe,0x28142875,0xaf91aff8,0x1fd9217e,0x2ee92ff4,
0x26a12765,0xaa4eaddc,0x16481cb6,0x26a12cb0,0xaf02af46,0xab5eae7c,0xab5eac32,0xa30e2993,0xae5eaeb5,0x2b059648,0xa934aa4e,0xaee9ac5d,
0xad96adfe,0x2fdd2e5e,0xa5dba814,0xaf5aaffc,0xacb0ad27,0x2ddc2faf,0x9cb6a30e,0xa765ad27,0x2fd42f91,0x2f6e2fed,0x2dba2e5e,0xa6a1ad4d,
0x2fff2ff8,0x25152d00,0x2c322d00,0x2ddc28d5,0x2faf2fe6,0xae1fa993,0x28d52aaa,0x2faf2fc9,0x2ee92f5a,0xaf91afdd,0x1fd925db,0x28142d96,
0xacd8ab5e,0xaf91ad00,0xaf30afaf,0x2c072f1a,0xaeb5addc,0xad96afc9,0xad96ae7c,0xac879cb6,0xafc9af5a,0x2993a6a1,0xaaaaac87,0xafe6af5a,
0xaff4affc,0x2ff82e5e,0xa17ea814,0xa875adfe,0x9fd9a875,0x2c07a17e,0x2fed2ff8,0xadfeaff4,0x29f12515,0x2fdd2f46,0x2eb52f80,0x29f1a765,
0x2ddc2c87,0x25152d96,0x2c322d96,0x2fff2eb5,0x2fa02ee9,0xaf02ab05,0x230e2934,0x28d52e5e,0x2d962ee9,0x25db2dfe,0xafddaf30,0x2f5a2fbc,
0x27652bb7,0xaf46ab5e,0xaf80aff8,0xa5152bb7,0xa8d59cb6,0xad00afc9,0xad00ae7c,0xaff8addc,0xadfeac5d,0x2cd89648,0xa44eaa4e,0xa934aeb5,
0xaff8afc9,0xae3fafff,0x2f022d72,0xaff8ae7c,0xadfeaf5a,0x2c07a5db,0x2fed2fdd,0x9fd9ad96,0xa6a1ac07,0x2f6e2f91,0x2dba2f30,0x2fd42cd8,
0x2aaa230e,0xa7652b5e,0x25152b5e,0x29932f02,0x2e7c2c5d,0x2fff2d96,0xad72a9f1,0x2fc92c5d,0x2ff42fbc,0x217e2dfe,0xaff8af30,0x28752ee9,
0x2d4d2f1a,0xafedad00,0xae5eafaf,0xaf91ab5e,0x96482993,0xa5dbae7c,0xa5dbac32,0xa9f1af46,0xaddc9648,0xafe6a6a1,0xaed0a6a1,0x2fff2a4e,
0xad27affc,0x2d00ac07,0xabb7afbc,0xae1f2934,0x2e5e230e,0x1fd92fa0,0x2f3028d5,0x244eaf02,0x2c872fe6,0xadbaaf46,0x2a4e2f80,0x2c872fc9,
0x230ead72,0x2d27ac32,0x2d27a515,0xafaf9cb6,0x2fbc2e99,0x9fd92f6e,0x2d4d3000,0x2cd8ac87,0xaa4e2b05,0xac5dafbc,0xaeb5a44e,0x96482f91,
0xaed0afa0,0x2f802d00,0xaaaaafaf,0xacb0afa0,0x2c872ffc,0x16482fbc,0xa9f12c07,0x2e99a934,0xaf80a8d5,0xac32afaf,0xae7cafaf,0xaaaa2e1f,
0xa30eaed0,0x2f1a2d72,0x2e1f9cb6,0xa30eafe6,0x2fed2dba,0xaffca6a1,0x2b052fd4,0x2cd82f6e,0xafbcae1f,0xad4daf02,0x1fd9ae3f,0xacd82d27,
0x2c87a993,0x2f5a2cb0,0x2f5a2ed0,0x26a1af46,0x2cb03000,0xafffa5db,0xad7226a1,0x27653000,0xafafa934,0x2f1aa814,0xab5eafed,0xad00af30,
0x2f30230e,0x2fed28d5,0x28142fa0,0x2934af02,0x16482ed0,0xafd41cb6,0xafddad72,0x16482fe6,0xaf46aeb5,0x2ed0a9f1,0x2cb0a9f1,0xa993afdd,
0x2e1fa44e,0xad002d4d,0x2bb72ffc,0x2d272ee9,0xaa4e2cd8,0xaeb52b05,0xac5daffc,0x96482fed,0xacb0aff4,0x2d72ad27,0x2fff2b5e,0xa765aff4,
0x2ff82aaa,0xabb72e7c,0xabb72c32,0x2b5e2f80,0xab052c87,0x2814af6e,0xac07b000,0xad4dae99,0xa8d5afe6,0x2875af80,0x2e3f2f46,0xa8d5afc9,
0x2f912dba,0xa44e2fd4,0xafbca6a1,0x2b052f6e,0xae99244e,0x9648affc,0x29f1ad4d,0xac87aee9,0x1cb6af02,0x25152ff8,0x2c322ff8,0x2d722e3f,
0x2ed02e99,0x2aaa2f5a,0xaf80ad96,0x2cb02e99,0xafafa44e,0xab5eaf30,0x2f1a9fd9,0xad00ae5e,0x2b05ad27,0x2c072f02,0xa8142e3f,0x2d4d2e1f,
0x29f12fff,0xac5daed0,0xac5dafe6,0xad96addc,0xaf46aa4e,0xac32ac87,0xae7cac87,0x29932dba,0x2f1a2b05,0xa8752fed,0x2e3f2cd8,0x2b5eaffc,
0xaee9abb7,0x2f30ae1f,0xadfead27,0xafbc2d00,0x2eb52c32,0xaf6e1cb6,0x2dba2d72,0x2eb52515,0x2fafa993,0x2fa0a515,0x2fa02765,0xad00aaaa,
0xafed26a1,0xa934ad96,0xaf30a9f1,0xa8142fd4,0x30009fd9,0xac872fed,0x2e992c07,0x2f6eadfe,0xafe6a17e,0x2fffabb7,0xaddcad00,0xaed0a17e,
0xac5d2f30,0xaf5a2e5e,0xb000244e,0x2eb51fd9,0x2ddcae1f,0x2e7c230e,0x2fc9230e,0x1cb6af1a,0xaf022cb0,0x217eaf46,0xaf1aa993,0xaf022ed0,
0x2fbca9f1,0xaf302e99,0x2dfe2c87,0x2ee91648,0xa44eafa0,0x2b05aff4,0x2f91abb7,0xafbc28d5,0xa6a12fff,0xb0002c32,0xb0002515,0x25db2ddc,
0x2c32af6e,0x2aaa2c5d,0x2f8025db,0x2e7caf6e,0xae3f2dfe,0x2d27afed,0xae1fac07,0xaf021fd9,0x2dfe2bb7,0x28142d27,0xae5e2e1f,0x2ffcad00,
0xaa4eae7c,0x2e99af80,0x2fd4aaaa,0xaa4eac32,0x9cb62fdd,0xae7c9648,0xafc99648,0xaddc2fd4,0x2b5eafbc,0xa8752f91,0x2e3f2b05,0x2f1aa44e,
0xb0002814,0xae991fd9,0x2c87af91,0xaf6e2ee9,0x2ed02875,0xa9932fa0,0xaf462d27,0x2cb02875,0xab5eaddc,0x2ff4ac32,0x2ff4a515,0x2d27afff,
0x9fd92fd4,0xa44ead96,0xae5ea9f1,0xaf3026a1,0x2e1faed0,0x2ff4addc,0xa8752fff,0x2e1fafe6,0xaffc29f1,0xa814ac87,0x2e5eae99,0xadfe9648,
0x2eb52814,0xaf5a2f30,0xb0002934,0xac5d2fed,0xa993ae3f,0x2c3228d5,0x2e7c28d5,0x2f46a875,0xa5152fd4,0xad723000,0x9cb6af5a,0xac322fd4,
0x2e3faee9,0x2e1f9fd9,0xad272f91,0x2f02a814,0xaffc28d5,0x2cd8aff4,0x2fedabb7,0x2b05afa0,0x2d962aaa,0xae992515,0xae99a765,0xaf5a2993,
0x1cb6adba,0x2cb0aeb5,0x2765aeb5,0xaddc2f6e,0xaff82d4d,0xa30ea814,0xafaf2c07,0xa17e2b05,0xa44e2e3f,0xadfe2b5e,0xa9342f1a,0x2cd8a875,
0x2fddacb0,0xb0002f80,0x2f6eaaaa,0x2fddaed0,0x2d001cb6,0x217e2765,0x217e2cb0,0x2bb7addc,0x2ee9afdd,0x2d4daa4e,0x2ffcadba,0xa44ea5db,
0xa9f1a934,0x2fd4aee9,0x26a1ae5e,0xad962b05,0xafc92f1a,0x2f46aff4,0xaf802bb7,0xafe62f1a,0xafdd2d4d,0xadba2c07,0xaa4ea814,0xa5db2b05,
0xaaaa2f1a,0xafc92f02,0xafe62f02,0x2993a17e,0x2e3fa765,0xafa02fff,0xa17e2d72,0x2e3facb0,0x2e5eb000,0xad4d2eb5,0x2f91ac5d,0x2fedaf5a,
0x2ee9aff8,0x2ffcafaf,0x2d4da30e,0xa44ea17e,0xa5dbaaaa,0x2f6eafe6,0x2f6eafc9,0xac5d2993,0xafe62dba,0x2d72ae99,0x9cb6ac5d,0xaed02dba,
0xabb72f30,0x28d5ac07,0xafa02cd8,0xaff42f91,0xa9342e3f,0xae5e2f1a,0xaee92b5e,0x2b05a875,0x2dbaa765,0xac5d2d72,0xae992fff,0x2dbaacb0,
0x2f80afd4,0xa7652a4e,0x25152a4e,0x2f46ae99,0x217eacd8,0x230e1fd9,0x2fafad4d,0x2ff8afbc,0xa9f1a44e,0x26a1a934,0x2fd4adfe,0xad962cd8,
0xafe62e3f,0x9cb6a17e,0x2d72afa0,0xaed02e3f,0xad272f80,0xa8752515,0xa875a765,0xafa02f46,0x293425db,0xac072a4e,0xafbc2dba,0xaffc2fdd,
0x2f1aacb0,0x2bb7aaaa,0xaff42f80,0x2f1aaed0,0x2f30b000,0x2cd8ac5d,0xac072eb5,0x2f91af5a,0x25dbacd8,0x2dbaad4d,0x2a4e1fd9,0x2fddafbc,
0xad722875,0x2e7cae1f,0x2fc9ae1f,0x2fffaff4,0xafc92fdd,0xaf802f6e,0x2f46b000,0xafe62fdd,0xabb72e5e,0xafa02f91,0x28d5ad4d,0xaff42fed,
0x2934217e,0xafbc2faf,0xac07230e,0xaffc2ff8,0x2f5aad72,0xafd42fc9,0xafd42e7c,0xb0002fff,0x9cb69648,0xacb0a6a1,0xa765a6a1,0x2ddc2a4e,
0xa17e9fd9,0xaff4aee9,0xa875a814,0x2ff82f91,0xa44ea30e,0xadfeafa0,0xa934a8d5,0x2cd82f02,0xa5dba515,0x9648aaaa,0xa9f1a993,0xa5db2765,
0xa30e9cb6,0xad27a765,0xad27acb0,0x2faf2ddc,0xa814a5db,0xaffcaf5a,0xadfead96,0x2e5e2fdd,0xaa4ea934,0xac5daee9,0xaeb5ae5e,0x96482b05,
0xac32ab5e,0x2993a30e,0xaf46af02,0xae7cab5e,0xa5db9fd9,0xad96a814,0xaf5aaee9,0x2fdd2f91,0xaaaaa8d5,0xafc9afaf,0xafe6afaf,0x29932e1f,
0xad00ac32,0xa8d5addc,0xaff8afff,0xad00a515,0xae5eadba,0x2d4d26a1,0xaf91afd4,0xafedaf6e,0xa814a17e,0xadfea875,0xaffcaff4,0x2e5e2ff8,
0xac87aaaa,0xaf5aafe6,0xaf5aafc9,0xa6a12993,0xae7cad96,0x9cb6ac87,0xaddcaeb5,0xafc9ad96,0xafafaf30,0x2f1a2c07,0xab5eacd8,0xad00af91,
0xa934a30e,0xae5ea8d5,0xaee9afa0,0x2b052f02,0xad96ac32,0xaeb5afff,0xac87addc,0xad96a515,0xaf80aeb5,0x2765a9f1,0xa515a9f1,0xaf46afdd,
0xaff8afed,0x2ff42dfe,0x28751fd9,0x217eac07,0xaa4ea44e,0xaeb5a934,0xac5dadfe,0x96482cd8,0xae7cad00,0xaddcaff8,0x9cb6a8d5,0xafc9ad00,
0xaff8af80,0x2bb7a515,0x2bb72765,0xab5eaf46,0xaf30afdd,0x2fbc2f5a,0x2ee92d96,0x2dfe25db,0xab5ea515,0xaf02a993,0xa30eaaaa,0xab5e2765,
0xaf30adba,0xacd8afd4,0x2c0726a1,0xaf91af6e,0xafddafed,0x2d961fd9,0x2f5a2dfe,0x25dbac07,0xad72af02,0x2e7c2ff8,0x2fc92ff8,0x2fff2e3f,
0xac32a5db,0xaf46a9f1,0x29939648,0xae7ca5db,0xafafae5e,0xab5eaf91,0x2f1a2d4d,0xad00afed,0xaf30aff8,0x2ee92875,0x2fbc2ff4,0x2dfe217e,
0xa9f1ad72,0x2c5d2fc9,0x2c5d2e7c,0x2d962fff,0xaf80aa4e,0xafc9ac87,0xafe6ac87,0x2f462dba,0xa8d5af30,0x2f02a44e,0xa30eae5e,0xafa09fd9,
0x2fbc2bb7,0xa9342e1f,0x2ffc2d27,0x2c07ad00,0x26a12ed0,0xaa4eafff,0x16482ddc,0x26a12fe6,0xafafaaaa,0xafa0acb0,0xafa0aed0,0x2d002f80,
0xa44eaeb5,0x2f919648,0x2b05aa4e,0xafbcac5d,0x30002d4d,0xac872cd8,0x2e992fbc,0x2f6e9fd9,0xa5152d27,0x9cb6afaf,0xad72230e,0xac322d27,
0xafd4ab05,0xaf6eacd8,0xadbaafed,0x26a12ffc,0x1cb6ae1f,0x2fe6230e,0x2ed0230e,0xad72af1a,0x2faf2e7c,0xae1f2aaa,0x28d52f80,0x2faf2c32,
0xac0729f1,0x2934ae99,0xaffcac87,0xafbc9648,0xafedab5e,0xaf30ad00,0xa934afaf,0xa8142f1a,0x26a1ad72,0x30002765,0x30002cb0,0xa5dbafff,
0x2ed02f5a,0xaf4626a1,0xa9932c87,0x2cb02f5a,0xae3f1fd9,0x2d27acd8,0xae1fafbc,0xaf02ad4d,0xaffcabb7,0xaee9ad27,0x244eae1f,0xad4d2d00,
0x29f1acb0,0x2fdd2993,0x2eb52f46,0x29f1aed0,0x2d722fdd,0xafe69648,0xaed09648,0x9cb62fd4,0xafa0a814,0x2f02a934,0xa30eaf30,0xa8d5afed,
0xb000ac07,0xae99ad4d,0x2c87ab05,0xaf6e2814,0x2c32abb7,0x2f802b5e,0x2aaa2ff8,0x2e7cabb7,0x2b5e2fff,0xaff4a765,0xaff4acb0,0xad272d72,
0xaffcac5d,0x2fed9648,0x2cd8aa4e,0x2b05aeb5,0xaff8ac32,0xae3fad72,0x2f029cb6,0xaff8a515,0x2d4da9f1,0x2ee92c87,0xa44e2e99,0x2ffc1648,
0x26a12fbc,0xaf6eab05,0xadbaaf91,0xafd4244e,0xaf46ae3f,0x2fc928d5,0x2fe628d5,0x2f80a875,0xafe6ac5d,0xaddcad96,0x2fff29f1,0xaed0ac5d,
0x2e3fa814,0x2e1f2d4d,0xad272b05,0x2f022c07,0x9fd92f1a,0xae5ead00,0xa44eafaf,0xaf30ab5e,0xad96af80,0x2e992cb0,0x2e992ed0,0x2f5a2aaa,
0xad72adba,0xa515aeb5,0xac32aeb5,0x9cb62f6e,0x2d272dfe,0xad002fbc,0x2bb72ee9,0x2e1faf30,0xacd8ae3f,0x2ffcab5e,0xab05af1a,0xafed2875,
0x2c872e7c,0xadbaa993,0x2a4e2f46,0x2c872c32,0xad00addc,0xa17eaed0,0xa17eafe6,0xabb72fff,0x2c072e99,0xadfe2f6e,0x9fd93000,0x2fedac87,
0xa9f1af30,0x2fd4a814,0x26a1afed,0xad96a934,0x27652fa0,0xaaaaad00,0xa9932faf,0xa5152fa0,0xac87adfe,0x9648aee9,0x29f1afbc,0xae992f30,
0x29932f1a,0xaed02f02,0xacb02f02,0x2f46a17e,0xa30eafc9,0x2f1a9cb6,0x2e1faddc,0xa30eae7c,0xa44e3000,0x9fd9aeb5,0xaf302c5d,0xae5e2f5a,
0xac07ae1f,0x1fd9af02,0x2dfeae3f,0xafed2d27,0x25db2f80,0xaf6e2e7c,0xaf6e2c32,0x2c5d2aaa,0x2515b000,0x2ddc25db,0x2fffa6a1,0x2c32b000,
0xabb72f91,0x28d5afbc,0xafa0a44e,0xaff42b05,0xab05ae3f,0x244eaf1a,0x2fbcab5e,0xaf912875,0x16482fc9,0xafd42ddc,0xafdd1cb6,0x16482e7c,
0x2aaaafd4,0x2c322a4e,0x2e7c2a4e,0x2f80ae99,0xae1f2e5e,0x2d00affc,0xabb7adfe,0xad27a814,0xa9f1ae5e,0x26a1af30,0x2fd49fd9,0xad96a44e,
0xa5152ff4,0xafff2d27,0xaddcab5e,0xac322ff4,0x2d27af46,0x28752cb0,0x28752ed0,0x2fa0a993,0xaf912c87,0x2ee9af6e,0x2814b000,0x1fd9ae99,
0xa8d5ae7c,0x2875af46,0x2e3f2993,0xa8d5ac32,0xa9343000,0xafed2c5d,0xa814aeb5,0xaf302f5a,0x2e99ae5e,0x16482dfe,0xa9f12ffc,0x2c872814,
0xafff2875,0x2fe6ae1f,0x2ed0ae1f,0x2ddcaff4,0xa765ae99,0x2993af5a,0x2aaa2d96,0x2515ae99,0xabb72fed,0xafa02b05,0x28d5affc,0xaff42cd8,
0x2f91ad27,0xa8142f02,0xaee92e3f,0x9fd92e1f,0xaf5a9cb6,0x2fd4ac32,0x2fd4a515,0x3000ad72,0x2aaaaf6e,0x2ed0afdd,0x2cb0afdd,0xaf803000,
0xaf1a2934,0x2875acd8,0xae3f244e,0xab5e2dfe,0xac072faf,0xab05217e,0xad4d2ff8,0x2814230e,0x2eb5a765,0xaf6e2ddc,0x2dba9cb6,0x2eb5acb0,
0x2bb7af80,0x2f1aafe6,0x2f1aafc9,0xaff42f46,0xae5e26a1,0x2b05ad96,0xa934a9f1,0xaee92fd4,0xadba2ffc,0xa5dba44e,0xafdd2ee9,0xaa4e2d4d,
0x2cb0217e,0xaddc2bb7,0x1cb62d00,0x2765217e,0x2c5daf91,0x2f5aafed,0x3000ae5e,0xaeb52d4d,0xad72217e,0x2cb0ae3f,0x2765ae3f,0xafff2fa0,
0xaf022fe6,0x217ea993,0xaf1a2aaa,0xaf022fc9,0x28142a4e,0xab0525db,0xad4d2fdd,0xac072dba,0x2cd8afa0,0x2f91aff4,0x2f30abb7,0xac0728d5,
0xac5d9cb6,0x2dbaaed0,0x2dbaafe6,0xae992d72,0xafc92f6e,0x2993ac5d,0xaaaaa5db,0xafe62f6e,0xa30e2d4d,0xa17ea44e,0xaff82ee9,0xafaf2ffc,
0x2d4dafaf,0x2fbcaff8,0x2cd8a17e,0x9fd9a30e,0xaa4ea515,0x2e99af46,0x2fd4af80,0xaa4e2765,0xafff2e99,0x2cb0adba,0x2765adba,0xad722c5d,
0xab5e2ee9,0x2875ab05,0xae3f2934,0xaf1a2e5e,0x2dbaafbc,0x2fddaffc,0x25db2934,0x2a4eac07,0xa765a875,0x2f46afa0,0x2f80ad27,0x2515a875,
0xafa02d72,0x2e3faed0,0x2e3fafe6,0xa17e9cb6,0xadfe2fd4,0x2cd8ad96,0xa44ea9f1,0xa93426a1,0x2e1fafc9,0x2ff4afff,0xa8752d72,0x2e1fae7c,
0x9fd9aa4e,0x2fbcafdd,0x2cd8a5db,0x2d4dadba,0xaeb52c07,0x2f5aaf91,0x3000af30,0x2c5dacd8,0xaf802ff4,0x2ed0af1a,0x2cb0af1a,0x2aaaabb7,
0x2e7cafd4,0x2fffb000,0xad722f5a,0x2fc9afd4,0x230eac07,0x2ff8affc,0x217e2934,0x2fafafbc,0xad4d28d5,0x2fedaff4,0x2e5eabb7,0x2f91afa0,
0xb0002f46,0x2fddafe6,0x2fddafc9,0x2f6eaf80,0xaaaaaa4e,0xaed0ac87,0xacb0ac87,0x2f802dba,0xab5eab05,0xafafafed,0xad00acd8,0x2f1a2ffc,
0xac07abb7,0xab05ae1f,0xad4dad27,0x28142d00,0xac5dac32,0x29f19cb6,0xad96ad72,0xac5da515,0xafafaf80,0xafa0afe6,0xafa0afc9,0x2d002f46,
0xafedafd4,0xa934adba,0xaf30af6e,0xa81426a1,0xb000affc,0x2c87244e,0xae99aee9,0xaf6ead4d,0xafe6aff8,0x2fff2f02,0xaddcae3f,0xaed0aff8,
0xaeb5af30,0xaa4eae5e,0x9648a44e,0xac5d9fd9,0xad72ae1f,0x2cb0230e,0x2765230e,0xafffaf1a,0xabb7acb0,0x2ff82f46,0x2b5e2993,0xabb7aed0,
0xa814a9f1,0x2b052e99,0x2d4d2c87,0x2c071648,0xa44ea8d5,0x2b05a30e,0x2f912f02,0xafbcafa0,0x26a11cb6,0x30002ed0,0x30002fe6,0xa5dbad72,
0x2c3229f1,0x2aaa2eb5,0x2f802fdd,0x2e7c29f1,0x2e3f2d4d,0xad27a44e,0x2e1f2ee9,0x2f022ffc,0x2d4d2bb7,0x2fbc2d27,0x2cd82e1f,0x9fd9ad00,
0x2f5a2e7c,0x2c872f80,0x26a12aaa,0x2f5a2c32,0x2fff2fdd,0xacb09648,0xa7659648,0x2d722fd4,0x2f1a2fbc,0xafafaf91,0xad00ab05,0xab5e244e,
0x30002fbc,0x2e992ffc,0xac87a934,0x2f6e2c07,0x2ed02faf,0xa99328d5,0xaf46ae1f,0x2cb02faf,0x2b5e2d72,0xaff4aed0,0xaff4afe6,0xad279cb6,
0x9fd926a1,0xa44eadba,0xae5eaf6e,0xaf30afd4,0x2d272ed0,0x230e2ddc,0xafafafff,0x2d272fe6,0x1fd929f1,0xafbcac87,0xacd8ae99,0xad4d9648,
0xac5da814,0xaa4eaf30,0x9648a934,0xaeb5afed,0xaf80ae3f,0x2ed028d5,0x2cb028d5,0x2aaaa875,0xa51526a1,0xad721648,0x9cb6aa4e,0xac3226a1,
0xae3fac07,0xae1faffc,0x2d272934,0xaf02afbc,0xaffcafa0,0x2cd8a30e,0x2fed2f02,0x2b05a8d5,0xad96af46,0x2e992fe6,0x2e992fc9,0x2f5a2f80,
0xafffadba,0xae7caeb5,0xafc9aeb5,0x2d722f6e,0x217ead4d,0x2ff42814,0x2875ac07,0xaff8ab05,0x2fed2e3f,0xad4d2b5e,0x2f912f1a,0x2e5ea875,
0xa5db2cb0,0x9648af80,0xa9f12aaa,0xa5db2ed0,0xad00afff,0xa17eafc9,0xa17eae7c,0xabb72d72,0x2ee925db,0x2d4d2f5a,0x2ffc2d96,0xa44eafdd,
0x29f12f91,0xafd4ac07,0xa6a12cd8,0x2d962f30,0xafc9ab5e,0x2f46a30e,0xaf80af02,0xafe6ab5e,0x25dbad4d,0x2d96ac07,0x2f5a2814,0xafddab05,
0x2f462f1a,0xa7652f02,0x25152f02,0x2f80a17e,0xad002765,0xa8d5afff,0xaff8ad72,0xad002cb0,0xacd8b000,0x2dfe2eb5,0x2934ac5d,0x244eaf5a,
0x2ee9217e,0x2ffc2875,0x2d4d2ff4,0xa44eaff8,0x25db2f46,0xaf6e2515,0xaf6ea765,0x2c5d2f80,0xafe6ad96,0x2d72ac87,0x9cb6aeb5,0xaed0ad96,
0x2bb7ab05,0xa8d52ee9,0x2fa02e5e,0x2ff42934,0x2f912e3f,0x2cd82f1a,0xac072b5e,0x2f30a875,0xad962765,0xaeb5ad72,0xac87afff,0xad962cb0,
0xa993afd4,0x2fc92a4e,0x2fe62a4e,0x2aaaae99,0x2ff82cd8,0xaff49fd9,0xa8752d4d,0xa17e2fbc,0x29f12fed,0xa6a12f91,0xafd4ad4d,0x2d962e5e,
0xafe6ad00,0x9cb6aff8,0x2d72a8d5,0xaed0ad00,0x2d27a993,0x28752fe6,0x28752fc9,0x2fa02aaa,0x29342fdd,0xac07af5a,0xafbcad96,0xaffca5db,
0xab5e2cb0,0xaf022aaa,0xa30eaf80,0xab5e2ed0,0xab05b000,0x2e5eac5d,0x2ee92eb5,0x2934af5a,0x2fdd2cd8,0xad962d4d,0xaf5a9fd9,0xa5db2fbc,
0xaddc2875,0x2cb0ae1f,0x2765ae1f,0x1cb6aff4,0xafc9a5db,0xaf80a9f1,0x2f469648,0xafe6a5db,0x2bb7acd8,0x2fa02934,0xa8d52dfe,0x2ff4244e,
0x29342ff8,0xafbca875,0xac07aff4,0xaffca17e,0xaf5aaddc,0x2fd42765,0x2fd42cb0,0x30001cb6,0xa993af6e,0x2765afdd,0xa515afdd,0xaaaa3000,
0x28d52f91,0xaf022e5e,0x230e2fed,0x2fa0ad4d,0xa814afaf,0x2f91a17e,0x9fd9aff8,0xaee9a30e,0x26a12fc9,0xaa4ead72,0x16482fff,0x26a12e7c,
0x2bb7af46,0x2f1aae7c,0x2f1aac32,0xaff42993,0xacd82eb5,0xaf301648,0xaf912a4e,0x2c072c5d,0x2dbaadfe,0x25db2e5e,0x2fdda814,0x2a4eaffc,
0xae7c2d27,0x2d72afaf,0xafff230e,0xafc92d27,0x2fd4a934,0x2f6ea44e,0x2dba2cd8,0xa6a1adfe,0xafff217e,0xa515ae3f,0xac32ae3f,0xaddc2fa0,
0x2faf2515,0xae1f2f80,0x28d52f46,0x2fafa765,0xaee9aa4e,0x2f91a5db,0x9fd9afdd,0xa814adba,0x2e5e2b5e,0x29342d00,0xab052faf,0x2ee9af1a,
0xac5daddc,0x2dbaafc9,0x2dbaae7c,0xae999cb6,0x27652f5a,0xaf8026a1,0xaf462c87,0xa5152f5a,0x230eaffc,0x217e2e5e,0x2ff8a814,0x2fafadfe,
0x1fd92faf,0xac072ff8,0xafed217e,0x2dfe230e,0x29f1afe6,0x2fddaaaa,0x2eb52993,0x29f1afc9,0xaddc2e99,0xa515adba,0xac32adba,0xafff2c5d,
0x2fa0ac07,0xaf022f30,0x230e2f91,0x28d52cd8,0xadba2ee9,0xafdd2dfe,0xa5dbaf30,0xaa4e2fbc,0x2fc9abb7,0x2aaa2b5e,0xa9932ff8,0x2fe6abb7,
0xafa09cb6,0x2e3fafc9,0x2e3fae7c,0xa17eaddc,0x2d4d2c5d,0xae5e1648,0xafed2a4e,0xaf912eb5,0xaff82765,0xae3f1cb6,0x2f02addc,0xaff82cb0,
0x2dfe2a4e,0xac072fdd,0xafed25db,0x1fd92dba,0xa6a1aee9,0x2f6ea934,0x2dba2b05,0x2fd4ae5e,0xaaaa2ff4,0x2765af1a,0xa515af1a,0xa993abb7,
0xacb0ac5d,0x9cb6ad96,0x2ddc29f1,0xa765ac5d,0xa30e2fbc,0xaff82dfe,0xa17eaf30,0xafaf2ee9,0x2dfeaf1a,0x244e2d00,0xacd82faf,0x29342b5e,
0xb0002993,0x2fddae7c,0x2fddac32,0x2f6eaf46,0x2ddcb000,0x2fe6afd4,0x2ed0afd4,0xafff2f5a,0xad279fd9,0x2d00aee9,0xabb7a814,0xae1f2f91,
0xae5e2ff4,0x9fd9a8d5,0xaf302fa0,0xa44e2bb7,0x2c872515,0xadba2aaa,0x2a4e2993,0x2c87a765,0x2ff4ad72,0x2e1fac32,0x2e1fa515,0xa8759cb6,
0x2814ae99,0x2ffcaf6e,0x2dfeb000,0xae5e2c87,0xaf5a2b05,0x2eb5afbc,0xac5da44e,0xb0002f91,0xac322fa0,0x2993ad00,0xaf462faf,0xae7c2fa0,
0x2c871fd9,0x16482814,0xa9f12ee9,0x2e99af91,0x2f80afa0,0x2c32a875,0x2e7ca875,0x2aaaad27,0xa30eac32,0x2f1aaddc,0x2e1fafff,0xa30ea515,
0xafed2d96,0x2ffcafd4,0xab05a6a1,0xacd829f1,0xa8142e1f,0xadfe2f02,0xaffc2e3f,0x2e5ead27,0x2e99a993,0xaa4e2cb0,0xaa4e2ed0,0x2fd4af46,
0x2e7cb000,0x1cb625db,0x2ddca6a1,0x2fc9b000,0xa875a934,0x2b5ea814,0x2f1aafed,0x2e3faf30,0xaf302ff4,0xafed2fa0,0xa814a8d5,0xa9342bb7,
0x16482c32,0xafd42fff,0xafdd2ddc,0x16482515,0x2f46ac5d,0xaed02f6e,0xacb02f6e,0x2993a5db,0x2e1fafed,0xad002dfe,0x2bb71fd9,0x2d27ac07,
0xaf5a2cd8,0xac5d2b05,0x2eb5affc,0xb0002fed,0xae7c2ff4,0xaddc2d27,0x9cb6ab5e,0xafc92ff4,0x217e2aaa,0xaf022e7c,0xaf022c32,0xaf1a2f80,
0x2f30ac87,0xafbc2f6e,0xaee93000,0xadfe2e99,0xa8d5a515,0x2875a993,0x2e3faaaa,0xa8d52765,0xaf912d96,0x244ea6a1,0x2fbcafd4,0xab0529f1,
0xae992fed,0x96489fd9,0x29f1adfe,0xac872c07,0x9cb62bb7,0xa515217e,0xac32217e,0xad722d00,0x2c32ae99,0x2f46af5a,0xa9932d96,0x2e7cae99,
0xa875a44e,0x2f1aaf30,0x2b5e9fd9,0x2e3fae5e,0xaf302d27,0x2ee9af02,0x2fbcae3f,0x2dfeae1f,0xaf6e2fff,0x2eb5aed0,0x2eb5afe6,0x2dbaaddc,
0xaddcadba,0xafe6aeb5,0xaed0aeb5,0x2fff2f6e,0xae1fadfe,0xae3fafbc,0xaf02aee9,0x2d272f30,0xae5eae3f,0x9fd9ab5e,0xaf30af1a,0xa44e2875,
0xae99ae7c,0x2d962993,0xaf5aaf46,0xae99ac32,0xad00ad72,0xa17eac32,0xa17ea515,0xabb79cb6,0xac07ac87,0x2dfe29f1,0x1fd99648,0xafedae99,
0xa9f1ab05,0x2fd42fbc,0x26a1244e,0xad96af91,0xa765a8d5,0x2aaa2e3f,0x29932875,0x2515a8d5,0x2e992dfe,0x30002ee9,0x2f6e2fbc,0xac87af30,
0x2f802f1a,0x2c322f02,0x2e7c2f02,0x2aaaa17e,0x2ff42fc9,0xab5e1cb6,0x2d272ddc,0x2ff42e7c,0x2fed3000,0xaffcaeb5,0x2b052c5d,0x2cd82f5a,
0x2c072d27,0x9fd92bb7,0xadfead00,0x2fed2e1f,0x25db2993,0xaf6eacb0,0xaf6eaed0,0x2c5d2f46,0xa5151648,0xaddcafdd,0xafffafd4,0xac321648,
0xabb7a934,0x28d5a814,0xafa0afed,0xaff4af30,0xaf30ae3f,0xafedaf1a,0xa814ab5e,0xa9342875,0xb000afc9,0xa6a1addc,0x25db9cb6,0xb000ae7c,
0xaf46afd4,0x2ed02a4e,0x2cb02a4e,0xa993ae99,0xad27ae5e,0x2e3f2ffc,0x2f022dfe,0x2e1f2814,0xa9f1acd8,0x26a1ab05,0x2fd42ffc,0xad96afed,
0x2515a30e,0x2fff2e1f,0x2ddc2f1a,0x2c32a30e,0x2d272aaa,0x28752e7c,0x28752c32,0x2fa02f80,0x2f912e99,0xaee9a9f1,0xa8141648,0x9fd92c87,
0x2fa02e7c,0x2faf2f46,0xad00a993,0x2fa02c32,0x2f913000,0xa44e2c5d,0xafbcaeb5,0x2b052f5a,0x2c872e5e,0xb000adfe,0xaf6eaffc,0xae99a814,
0x9cb62875,0xa515ae1f,0xac32ae1f,0xad72aff4,0x27652c87,0xa9932a4e,0xaaaaadba,0xa5152c87,0xabb7a44e,0xafa0af30,0x28d59fd9,0xaff4ae5e,
0xaf91ae1f,0x2814abb7,0x2ee92d00,0x1fd9ad27,0xaf5aafff,0x2fd42ed0,0x2fd42fe6,0x30002ddc,0xaf46af6e,0xac32afdd,0xae7cafdd,0x29933000,
0x2b5ea934,0x2faf2cd8,0x2d00a44e,0xaf1aadfe,0x2ee92faf,0xaf30217e,0x2dfe2ff8,0x2fbc230e,0xac5d2765,0x29f1addc,0xad961cb6,0xac5d2cb0,
0x2bb7a993,0x2f1aa515,0x2f1a2765,0xaff4aaaa,0x2e5e2fd4,0xab052dba,0x29342f6e,0x2ee9a6a1,0xadba1fd9,0xa5dbafed,0xafddac07,0xaa4e2dfe,
0xacb0aff8,0x2ddc2f02,0x9cb6ae3f,0xa765aff8,0x2eb52f91,0x2a4e2fed,0x16482e5e,0x2c5dad4d,0xaddc217e,0xae7cae3f,0xafc9ae3f,0x9cb62fa0,
0xabb7afe6,0x2ff82993,0x2b5eaaaa,0xabb7afc9,0x2fbc2a4e,0xaf3025db,0x2dfe2fdd,0x2ee92dba,0xacd828d5,0xaf91230e,0xaf30af02,0x2c072fa0,
0xac5dafff,0x2dbaac32,0x2dbaa515,0xae99addc,0x2fc929f1,0xa9932eb5,0x2aaa2fdd,0x2fe629f1,0xa30e2dfe,0xa17eafed,0xaff8ac07,0xafaf1fd9,
0xadfeafaf,0xa814aff8,0x2e5ea17e,0xaffca30e,0x2f5a2515,0x2c872f46,0x26a12f80,0x2f5aa765,0x9cb62e99,0xae7cadba,0xafc9adba,0xaddc2c5d,
0xaf1aaee9,0x2faf2b05,0x2d00a934,0x2b5eae5e,0x2dbaa814,0x2fdd9fd9,0x25db2f91,0x2a4eaee9,0x27652faf,0xaf4628d5,0xaf80ae1f,0xa5152faf,
0xafa0addc,0x2e3fac32,0x2e3fa515,0xa17eafff,0x2dfea6a1,0xacd82dba,0x244e2f6e,0x29342fd4,0x2d272fc9,0x230e2fff,0xafafad72,0x2d272e7c,
0xaffcaa4e,0xa814afdd,0x2e5ea5db,0xadfeadba,0x2c5dac07,0x2a4e2f91,0x16482f30,0x2eb52cd8,0x29932ff4,0xac32af1a,0xae7caf1a,0xaf46abb7,
0xae7c26a1,0xafff1648,0x2d72aa4e,0xafc926a1,0x230eaee9,0x2ff89fd9,0x217e2f91,0x2fafa814,0x2d4d2fa0,0xafed230e,0xae5eaf02,0xaf9128d5,
0xb000aaaa,0x2fdda515,0x2fdd2765,0x2f6ea993,0x1cb6b000,0x2cb0afd4,0x2765afd4,0xaddc2f5a,0xa17e2ffc,0xaff42c07,0xa8752fbc,0x2ff8a934,
0x244eaff4,0x2dfe28d5,0x2934afa0,0xacd8abb7,0xa5db2fe6,0x9648af46,0xa9f12f80,0xa5db2fc9,0x2ff41cb6,0x2e1f2765,0x2e1f2cb0,0xa875addc,
0xafbca5db,0x1fd9af5a,0xad4dad96,0xacd82fdd,0x2f5a2934,0xaeb52ee9,0x2c5d2e5e,0x3000ab05,0xaed0ab5e,0x2f80a30e,0xaaaaaf02,0xacb0ab5e,
0xa5db2ffc,0xad962fbc,0xaf5a2c07,0x2fdda934,0x2aaaafa0,0x2fc9a875,0x2fe6a875,0xa993ad27,0xad002ed0,0xa8d5ad72,0xaff81cb6,0xad002fe6,
0x2e5ead96,0xad4d2fd4,0x2f9126a1,0x2feda9f1,0xafbca17e,0xad4da875,0x1fd9aff4,0xacd82ff8,0x2e992aaa,0xaa4e2fe6,0xaa4e2fc9,0x2fd4a993,
0xacb0ad96,0x2fffac87,0x2d72aeb5,0xa765ad96,0x28752f30,0xab5eac07,0xaf1a2cd8,0xae3f2f91,0x2934aff4,0x2e5eafa0,0x2ee928d5,0xab05abb7,
0xad962ed0,0xaeb51cb6,0xac87ad72,0xad962fe6,0x2f80ac5d,0xa7652f6e,0x25152f6e,0x2f46a5db,0xaff8244e,0x2ff4ad4d,0x2875affc,0x217eaee9,
0x2f5a244e,0x2c5d2934,0xaeb52dfe,0x3000acd8,0xacb0ad00,0x2d72aff8,0x2fffa8d5,0xa765ad00,0x217e2f80,0xaf022515,0xaf02a765,0xaf1a2f46,
0x2b05afdd,0xa8142f5a,0x2c072d96,0x2d4d25db,0xab5e2fe6,0xaf022f80,0xa30eaf46,0xab5e2fc9,0x2f30ad96,0x2cd826a1,0xac072fd4,0x2f91a9f1,
0xafdd244e,0x2d96affc,0x2f5aad4d,0x25dbaee9,0x2d722bb7,0xae7c217e,0xafc9217e,0xafff2d00,0xaed0a5db,0xaaaaa9f1,0x2f809648,0xacb0a5db,
0x28752e5e,0xaf1a2f91,0xab5ead4d,0xae3f2fed,0x2b05aff8,0x2c072875,0xa8142ff4,0x2d4d217e,0xaf6e2d72,0x2eb5afc9,0x2eb5ae7c,0x2dbaafff,
0x2f80af5a,0x2fc9ae99,0x2fe6ae99,0xaf462d96,0xa8d5ab05,0x2f02afed,0xa30eacd8,0xafa02ffc,0xafbc2f02,0x2934ad27,0xaffc2e1f,0xac072e3f,
0x26a12c32,0xaa4e1cb6,0x16482d72,0x26a12515,0x28752aaa,0xa8d52cb0,0xa8d52ed0,0x2e3faf80,0x2fedaeb5,0x29349648,0x2f30aa4e,0x2814ac5d,
0x1648ad4d,0x2e99acd8,0x2c87afbc,0xa9f11fd9,0xafe62d27,0x2fffafaf,0xaddc230e,0xaed02d27,0xafd42f30,0xaf6e2e5e,0xadba244e,0x26a11fd9,
0x9cb62d27,0xafe62ff4,0xaed02ff4,0x2d72ab5e,0x2fafacb0,0xae1f2f46,0x28d52993,0x2fafaed0,0x2c07af6e,0xa9342c87,0x2ffcae99,0x2fbcb000,
0xa44eab5e,0x2b05ad00,0x2f91afaf,0xafbc2f1a,0xafd42d72,0x1648a765,0x1648acb0,0xafdd2fff,0xac322f5a,0xaaaa26a1,0xaf802c87,0xae7c2f5a,
0x2d009fd9,0xae1f2cd8,0xad272fbc,0xabb72d4d,0x2ffcaf02,0x2ee9ae1f,0xa44e2d27,0x2d4dae3f,0x29f1ae7c,0x2fddaf80,0x2eb5aaaa,0x29f1ac32,
0xad7225db,0x2fe6b000,0x2ed0b000,0x1cb6a6a1,0xafa02fbc,0x2f02af91,0xa30eab05,0xa8d5244e,0x96482c07,0xac872d4d,0xae992b05,0x29f1a814,
0x2ed0abb7,0xa9932b5e,0xaf462ff8,0x2cb0abb7,0x2f1aafff,0xa30e2765,0xa30e2cb0,0x2e1fad72,0x1fd9ac5d,0x244e9648,0x2e5eaa4e,0x2f30aeb5,
0xaff82ed0,0xae3f2ddc,0x2f02afff,0xaff82fe6,0xad4d2f6e,0xaee92e99,0x244eac87,0xaffc3000,0x26a12814,0xaf6e2f30,0xadba2934,0xafd42fed,
0x2f46ad00,0xafc92fa0,0xafe62fa0,0xaf802faf,0x2515ac5d,0x2d72ad96,0x1cb629f1,0x2c32ac5d,0xad002814,0x2d27ad4d,0x2e1fab05,0x2bb7ac07,
0xaffc2f1a,0x2cd8ad00,0x2fedafaf,0x2b05ab5e,0xadba2f80,0x2c87acb0,0x2c87aed0,0x2a4eaaaa,0xaf80af6e,0xafc9afdd,0xafe6afdd,0x2f463000,
0xafa0af91,0xabb7ae5e,0xaff4afed,0x28d52d4d,0xafbcafaf,0x2934a17e,0xaffcaff8,0xac07a30e,0xafd4afc9,0x2f5a2d72,0xb000afff,0xafd4ae7c,
0x2bb72aaa,0x2f1a2cb0,0x2f1a2ed0,0xaff4af80,0x2cd82c5d,0x2f303000,0x2f912f5a,0xac07aeb5,0x2dba2d4d,0x25db2cd8,0x2fdd2fbc,0x2a4e9fd9,
0x2e7c2e1f,0xad72a875,0x2fff2ff4,0x2fc92e1f,0x26a12934,0xa9f1244e,0xad96acd8,0x2fd42dfe,0x9cb6217e,0xafe6ae3f,0xaed0ae3f,0x2d722fa0,
0xa875a515,0xad27af80,0xafa0af46,0xa8752765,0xac07aa4e,0x2934a5db,0xaffcafdd,0xafbcadba,0xae5eaf1a,0xa934ae3f,0x2b052875,0xaee9ab5e,
0xac5dad72,0x2dba2765,0x2dba2cb0,0xae99afff,0xa765aa4e,0x2f802fd4,0x2f462e99,0x2515aa4e,0x230e9fd9,0x217e2cd8,0x2ff82fbc,0x2faf2d4d,
0x2ffc2faf,0x2ee92ff8,0xa44e217e,0x2d4d230e,0x2f6e2fe6,0xa5db2aaa,0xac5da993,0x2f6e2fc9,0x2d722e99,0xafe6adba,0xaed0adba,0x9cb62c5d,
0x28d52c07,0xabb7af30,0xaff4af91,0xafa0acd8,0xadbaac07,0xafddad4d,0xa5dbab05,0xaa4e2814,0xafc9af02,0xaaaaaf1a,0x2993217e,0xafe6af02,
0xafa0afff,0x2e3f2765,0x2e3f2cb0,0xa17ead72,0xad4daeb5,0x2e5e3000,0x2fed2f5a,0x2f912c5d,0x217ea765,0x2d009cb6,0x2bb72ddc,0x217eacb0,
0x2d4d2a4e,0x2ee92fdd,0xa44e25db,0x2ffc2dba,0x2fd42ee9,0xa9f12934,0xad96ab05,0x26a12e5e,0x2f462ff4,0xafc9af1a,0xafe6af1a,0xaf80abb7,
0x2cb02eb5,0x1cb62dba,0xaddcaf6e,0x27652eb5,0xa30e2814,0xaff8ad4d,0xa17eab05,0xafafac07,0xadfeab5e,0xa44eae3f,0x2cd82875,0xa934af1a,
0xb000af80,0x2fdd2cb0,0x2fdd2ed0,0x2f6e2aaa,0xad72b000,0xa515afd4,0xac32afd4,0x9cb62f5a,0x2e1f1fd9,0x2e3f2ee9,0x2f022814,0xad27af91,
0x2cd82ff4,0xaffca8d5,0x2b052fa0,0x2fed2bb7,0xae99a515,0x2d96aaaa,0xaf5aa993,0xae992765,0x2ff42ddc,0x2e1f2ed0,0x2e1f2fe6,0xa875afff,
0xa8142c87,0xaffca9f1,0xadfe1648,0x2e5e2e99,0xaf5aaf30,0x2eb5a814,0xac5dafed,0xb000a934,0x2c32a8d5,0xa9932e3f,0x2f462875,0x2e7ca8d5,
0xae999fd9,0xb000a814,0xaf6eaee9,0x2c872f91,0xa993afa0,0x2ed0a875,0x2cb0a875,0xaf46ad27,0x2ff42c32,0xab5e2ddc,0x2d272fff,0x2ff42515,
0xa44e2d96,0x9fd9afd4,0xaf30a6a1,0xae5e29f1,0x2814ad27,0x2dfeabb7,0x2ffc2d00,0xae5eae1f,0x2e992f80,0xaa4e2e7c,0xaa4e2c32,0x2fd42aaa,
0xae7c1648,0x9cb6afdd,0xaddcafd4,0xafc91648,0xa875af91,0x2b5e2fbc,0x2f1a244e,0x2e3fab05,0x2b052ff4,0xa44e2fa0,0xafbca8d5,0x2f912bb7,
0xb000ac32,0xa6a1afff,0x25dbaddc,0xb000a515,0x2aaaac5d,0x2c322f6e,0x2e7c2f6e,0x2f80a5db,0x2d272fed,0xae3fadfe,0xaf029fd9,0xae1f2c07,
0xaf5aae5e,0xac5daf30,0x2eb59fd9,0xb000a44e,0x2e7ca30e,0x2ddc2e1f,0x1cb62f1a,0x2fc9a30e,0x217e2f46,0xaf02acb0,0xaf02aed0,0xaf1a2993,
0xaf30ae99,0x2fbc29f1,0x2ee99648,0x2dfeac87,0x2fa02515,0x2faf2993,0xad002aaa,0x2fa0a765,0xa9342d96,0xafeda6a1,0xa814afd4,0xaf3029f1,
0xac87afed,0x30001fd9,0x2f6e2dfe,0x2e99ac07,0x2fff2bb7,0xafe6217e,0xaed0217e,0xaddc2d00,0xac322c87,0xaf462a4e,0x2993adba,0xae7c2c87,
0xa875afed,0x2f1aab05,0x2b5e2ffc,0x2e3facd8,0x2f302e1f,0xaee92bb7,0xafbcad00,0xadfe2d27,0xaf6e9cb6,0x2eb5ac32,0x2eb5a515,0x2dbaad72,
0x2aaaaf5a,0x2ed0ae99,0x2cb0ae99,0xaf802d96,0xab5e2f30,0xafaf244e,0xad002e5e,0x2f1a1fd9,0x2c07af02,0x2b052d27,0x2d4dae1f,0xa814ae3f,
0xac5d2ed0,0x29f1afff,0xad962ddc,0xac5d2fe6,0x28752f80,0xa8d52fe6,0xa8d52fc9,0x2e3faf46,0xa44eafd4,0x2f91adba,0x2b05af6e,0xafbc26a1,
0x96482ffc,0xae99a44e,0xac872ee9,0x29f12d4d,0x2515aff8,0x1cb62f02,0x2d72ae3f,0x2c32aff8,0xaeb5ab05,0xaa4eacd8,0x9648afed,0xac5d2ffc,
0x2d722d27,0xacb02ff4,0xa7652ff4,0x2fffab5e,0xabb7ae7c,0x2ff8aaaa,0x2b5eaf80,0xabb7ac32,0x28142f6e,0xab05ac87,0xad4d2e99,0xac073000,
0x2feda8d5,0x2f30a30e,0x29342f02,0x2814afa0,0xafd49cb6,0x1648aed0,0x1648afe6,0xafdd2d72,0x2ed029f1,0xaf462eb5,0xa9932fdd,0x2cb029f1,
0xad00ad4d,0x2e1f244e,0x2d27aee9,0x2bb7affc,0xad4d2f02,0xafbc2e1f,0xacd8ad27,0x1fd92e3f,0x2f5aacb0,0x2c872993,0x26a12f46,0x2f5aaed0,
0xafff25db,0x2cb0b000,0x2765b000,0xad72a6a1,0x2f1a2814,0xafaf2934,0xad002f30,0xab5e2fed,0x1648afbc,0x2c87affc,0x2e992934,0xa9f1ac07,
0xac322faf,0xaf8028d5,0xaaaaae1f,0xae7c2faf,0x2f1aad72,0xa30e2ed0,0xa30e2fe6,0x2e1f1cb6,0xaffc26a1,0x2fedadba,0x2cd8af6e,0x2b05afd4,
0x2d272c32,0x230e2d72,0xafaf1cb6,0x2d272515,0x9fd9af6e,0x2fbcae99,0x2cd82c87,0x2d4db000,0xac5d2fbc,0xaa4eab05,0x9648af91,0xaeb5244e,
0x2f80ad00,0xaed02fa0,0xacb02fa0,0xaaaa2faf,0xafe626a1,0xaddc1648,0x2fffaa4e,0xaed026a1,0x2d002c07,0xad272ffc,0xae1fa934,0xabb72fbc,
0x1fd9afa0,0x2e5ea30e,0x244e2f02,0x2f30a8d5,0xadba2f46,0x2c87afe6,0x2c87afc9,0x2a4eaf80,0x2fffad96,0x2e7cac5d,0x2fc9ac5d,0xad7229f1,
0x217eadfe,0x2ff4afbc,0x2875aee9,0xaff82f30,0xafed2d00,0x2d4daf1a,0xaf912b5e,0xae5e2faf,0xa5db2e7c,0x9648a993,0xa9f12f46,0xa5db2c32,
0xae3f2fff,0xaff82fc9,0xaff82e7c,0x2f02ad72,0x2c0725db,0xadfe2f5a,0x9fd92d96,0x2fedafdd,0x2f6eaf91,0xa6a12c07,0x2fd4acd8,0x2dbaaf30,
0xa765ab5e,0x2aaaa30e,0x2993af02,0x2515ab5e,0x25dbadfe,0x2d96aee9,0x2f5aafbc,0xafdd2f30,0xaf462b5e,0x2765abb7,0xa515abb7,0xaf802ff8,
0xad002fc9,0xa8d51cb6,0xaff82ddc,0xad002e7c,0x2cd81648,0xadfe2c5d,0xa9342eb5,0xa44e2a4e,0x2c07217e,0x9fd92875,0xadfe2ff4,0x2fedaff8,
0x2fddaf46,0x29f1a515,0x29f12765,0x2eb5af80,0x2515ad96,0x2ddcac87,0x2fffaeb5,0x2c32ad96,0xaf022b05,0x2fa0aee9,0x28d5ae5e,0x230ea934,
0xaf912d00,0xacd82b5e,0x2c07af1a,0xaf302faf,0xad962fc9,0xaeb52ddc,0xac871cb6,0xad962e7c,0x299326a1,0xafc92f5a,0xafe62f5a,0xaaaa2c87,
0x2ff8ae5e,0xaff42ffc,0xa8752dfe,0xa17e2814,0x2f6eafed,0x2fd4af91,0xa6a12d4d,0x2dbaae5e,0x2515ad00,0x2fffaff8,0x2ddca8d5,0x2c32ad00,
0xae1f2993,0x2fafafe6,0x2fafafc9,0x28d5aaaa,0xaf912fdd,0x2ee9af5a,0x2814ad96,0x1fd9a5db,0xab5e2e7c,0xaf022f46,0xa30ea993,0xab5e2c32,
0x2b051648,0xae5e2eb5,0xaee92c5d,0xa9342a4e,0x2fddae5e,0xad962dfe,0xaf5a2ffc,0xa5db2814,0x2ddcafaf,0xacb02d27,0xa7652d27,0x9cb6230e,
0xa765a5db,0x2993a9f1,0x2aaa9648,0x2515a5db,0xaf022cd8,0x28d5a934,0x2fa0adfe,0x230ea44e,0xaf912ff8,0x2814a875,0x2ee9aff4,0x1fd9a17e,
0xaa4e2ddc,0x26a1a765,0x26a1acb0,0x16489cb6,0x9d7f9e49,0xaddcaeb3,0x12480000,0x22ad0000,0x9bdb9cb6,0xac2ead04,0x18b61648,0x290226ad,
0x98b69a49,0xa902aaaf,0x1bdb1a49,0x2c2e2aaf,0x92489648,0xa2ada6ad,0x1d7f1cb6,0x2ddc2d04,0xa420a4b7,0xae8daf7f,0x18b60000,0x23760000,
0xa1e4a312,0xacacad9c,0x1f121cb6,0x29992777,0x9f12a0b6,0xa999ab78,0x21e420b6,0x2cac2b78,0x98b69cb6,0xa376a777,0x24202312,0x2e8d2d9c,
0xa6e0a7db,0xaf3fb025,0x1bdb0000,0x24200000,0xa4e9a5e4,0xad2aae34,0x21e41fdb,0x2a312820,0xa1e4a3db,0xaa31ac21,0x24e923db,0x2d2a2c21,
0x9bdb9fdb,0xa420a820,0x26e025e4,0x2f3f2e34,0xa8d0a980,0xaff2b08c,0x1d7f0000,0x24840000,0xa6e0a820,0xada9aecd,0x2420217f,0x2ac82885,
0xa420a580,0xaac8ac86,0x26e02580,0x2da92c86,0x9d7fa17f,0xa484a885,0x28d02820,0x2ff22ecd,0xaa31ab13,0xb052b0f3,0x1f120000,0x24e90000,
0xa86ba94e,0xae28af65,0x254d2312,0x2b5f28e9,0xa54da712,0xab5faceb,0x286b2712,0x2e282ceb,0x9f12a312,0xa4e9a8e9,0x2a31294e,0x30522f65,
0xab91ac54,0xb0acb15a,0x20520000,0x254d0000,0xa967aa7c,0xaea7affe,0x267b2452,0x2bf6294e,0xa67ba852,0xabf6ad50,0x29672852,0x2ea72d50,
0xa052a452,0xa54da94e,0x2b912a7c,0x30ac2ffe,0xac79ad1e,0xb106b1c1,0x211b0000,0x25b20000,0xaa63abab,0xaf26b04c,0x27a9251b,0x2c4729b3,
0xa7a9a91c,0xac47adb6,0x2a63291c,0x2f262db6,0xa11ba51b,0xa5b2a9b3,0x2c792bab,0x3106304c,0xad2aade8,0xb160b229,0x21e40000,0x26170000,
0xab5fac6d,0xafa5b099,0x286b25e4,0x2c932a17,0xa86ba9e5,0xac93ae1b,0x2b5f29e5,0x2fa52e1b,0xa1e4a5e4,0xa617aa17,0x2d2a2c6d,0x31603099,
0xb1bbb292,0xb44fb4f6,0x267b0000,0x28d00000,0xb012b0e6,0xb216b357,0x2cde2a7c,0x2f3f2cd2,0xacdeae80,0xaf3fb0d9,0x30122e80,0x321630d9,
0xa67baa7c,0xa8d0acd2,0x31bb30e6,0x344f3357,0xb216b2fb,0xb47eb52d,0x26e00000,0x29020000,0xb052b133,0xb257b3a7,0x2d2a2ae1,0x2f8c2d04,
0xad2aaee6,0xaf8cb10c,0x30522ee6,0x3257310c,0xa6e0aae1,0xa902ad04,0x32163133,0x347e33a7,0xb271b364,0xb4aeb565,0x27440000,0x29350000,
0xb092b181,0xb298b3f7,0x2d762b46,0x2fd82d37,0xad76af4c,0xafd8b140,0x30922f4c,0x32983140,0xa744ab46,0xa935ad37,0x32713181,0x34ae33f7,
0xb2cdb3cf,0xb4deb59d,0x27a90000,0x29670000,0xb0d2b1ce,0xb2dab423,0x2dc22bab,0x30122d6a,0xadc2afb2,0xb012b174,0x30d22fb2,0x32da3174,
0xa7a9abab,0xa967ad6a,0x32cd31ce,0x34de3423,0xb329b41d,0xb50eb5d6,0x28070000,0x29990000,0xb113b21c,0xb31cb44c,0x2e0e2c08,0x30392d9c,
0xae0eb00c,0xb039b1a7,0x3113300c,0x331c31a7,0xa807ac08,0xa999ad9c,0x3329321c,0x350e344c,0xb386b453,0xb53fb60f,0x28390000,0x29cc0000,
0xb153b26b,0xb35eb474,0x2e5a2c3a,0x305f2dcf,0xae5ab03f,0xb05fb1db,0x3153303f,0x335e31db,0xa839ac3a,0xa9ccadcf,0x3386326b,0x353f3474,
0xb3e3b489,0xb570b649,0x286b0000,0x29fe0000,0xb194b2b9,0xb3a0b49d,0x2ea72c6d,0x30852e02,0xaea7b072,0xb085b20f,0x31943072,0x33a0320f,
0xa86bac6d,0xa9feae02,0x33e332b9,0x3570349d,0xb420b4bf,0xb5a1b683,0x289e0000,0x2a310000,0xb1d5b308,0xb3e3b4c6,0x2ef32c9f,0x30ac2e34,
0xaef3b0a5,0xb0acb243,0x31d530a5,0x33e33243,0xa89eac9f,0xaa31ae34,0x34203308,0x35a134c6,0xb5d2b6be,0xb76fb857,0x2a630000,0x2bf60000,
0xb413b4ef,0xb523b642,0x30d22e67,0x32092ffe,0xb0d2b278,0xb209b40f,0x34133278,0x3523340f,0xaa63ae67,0xabf6affe,0x35d234ef,0x376f3642,
0xb604b6fa,0xb7a5b878,0x2a950000,0x2c140000,0xb434b519,0xb546b66d,0x30f92e9a,0x32303019,0xb0f9b2ac,0xb230b42a,0x343432ac,0x3546342a,
0xaa95ae9a,0xac14b019,0x36043519,0x37a5366d,0xb637b736,0xb7dbb899,0x2ac80000,0x2c2e0000,0xb456b542,0xb569b699,0x31202ecd,0x32573032,
0xb120b2e1,0xb257b445,0x345632e1,0x35693445,0xaac8aecd,0xac2eb032,0x36373542,0x37db3699,0xb66ab773,0xb809b8bb,0x2afa0000,0x2c470000,
0xb478b56c,0xb58cb6c6,0x31462f00,0x327e304c,0xb146b315,0xb27eb460,0x34783315,0x358c3460,0xaafaaf00,0xac47b04c,0x366a356c,0x380936c6,
0xb69db7b0,0xb825b8dd,0x2b2d0000,0x2c600000,0xb49ab596,0xb5afb6f2,0x316d2f32,0x32a53065,0xb16db34a,0xb2a5b47b,0x349a334a,0x35af347b,
0xab2daf32,0xac60b065,0x369d3596,0x382536f2,0xb6d1b7ee,0xb841b8ff,0x2b5f0000,0x2c790000,0xb4bcb5c1,0xb5d2b71f,0x31942f65,0x32cd307f,
0xb194b37f,0xb2cdb496,0x34bc337f,0x35d23496,0xab5faf65,0xac79b07f,0x36d135c1,0x3841371f,0xb705b817,0xb85db923,0x2b910000,0x2c930000,
0xb4deb5eb,0xb5f6b74d,0x31bb2f98,0x32f43099,0xb1bbb3b4,0xb2f4b4b1,0x34de33b4,0x35f634b1,0xab91af98,0xac93b099,0x370535eb,0x385d374d,
0xb73ab837,0xb87ab946,0x2bc40000,0x2cac0000,0xb500b616,0xb61ab77a,0x31e22fcb,0x331c30b2,0xb1e2b3e9,0xb31cb4cd,0x350033e9,0x361a34cd,
0xabc4afcb,0xacacb0b2,0x373a3616,0x387a377a,0xb897b96b,0xb98dbaa6,0x2cc50000,0x2d900000,0xb63eb7a8,0xb767b895,0x334330cc,0x3442319a,
0xb343b4e8,0xb442b5c8,0x363e34e8,0x376735c8,0xacc5b0cc,0xad90b19a,0x389737a8,0x398d3895,0xb8b4b990,0xb9aebad1,0x2cde0000,0x2da90000,
0xb662b7d7,0xb78db8ae,0x336b30e6,0x345631b4,0xb36bb504,0xb456b5e4,0x36623504,0x378d35e4,0xacdeb0e6,0xada9b1b4,0x38b437d7,0x39ae38ae,
0xb8d2b9b5,0xb9cfbafd,0x2cf80000,0x2dc20000,0xb687b803,0xb7b4b8c7,0x339330ff,0x346a31ce,0xb393b51f,0xb46ab601,0x3687351f,0x37b43601,
0xacf8b0ff,0xadc2b1ce,0x38d23803,0x39cf38c7,0xb8f0b9dc,0xb9f1bb29,0x2d110000,0x2ddc0000,0xb6acb81b,0xb7dbb8e1,0x33bb3119,0x347e31e8,
0xb3bbb53b,0xb47eb61e,0x36ac353b,0x37db361e,0xad11b119,0xaddcb1e8,0x38f0381b,0x39f138e1,0xb90fba02,0xba14bb57,0x2d2a0000,0x2df50000,
0xb6d1b833,0xb801b8fb,0x33e33133,0x34933202,0xb3e3b557,0xb493b63a,0x36d13557,0x3801363a,0xad2ab133,0xadf5b202,0x390f3833,0x3a1438fb,
0xb92eba2a,0xba37bb86,0x2d440000,0x2e0e0000,0xb6f6b84b,0xb815b915,0x3405314d,0x34a7321c,0xb405b573,0xb4a7b657,0x36f63573,0x38153657,
0xad44b14d,0xae0eb21c,0x392e384b,0x3a373915,0xb94dba53,0xba5abbb6,0x2d5d0000,0x2e280000,0xb71bb863,0xb829b930,0x34193167,0x34bc3236,
0xb419b58f,0xb4bcb675,0x371b358f,0x38293675,0xad5db167,0xae28b236,0x394d3863,0x3a5a3930,0xb96dba7c,0xba7ebbe7,0x2d760000,0x2e410000,
0xb741b87c,0xb83db94b,0x342e3181,0x34d03250,0xb42eb5ab,0xb4d0b692,0x374135ab,0x383d3692,0xad76b181,0xae41b250,0x396d387c,0x3a7e394b,
0xa17fa248,0xb1cfb2a1,0x16480000,0x26ad0000,0x9fdba0b6,0xb029b0fd,0x1cb61a48,0x2d002aac,0x9cb69e48,0xad00aeaa,0x1fdb1e48,0x30292eaa,
0x96489a48,0xa6adaaac,0x217f20b6,0x31cf30fd,0xa81fa8b6,0xb27cb365,0x1cb60000,0x27760000,0xa5e4a711,0xb0a6b191,0x231120b6,0x2d972b75,
0xa311a4b6,0xad97af72,0x25e424b6,0x30a62f72,0x9cb6a0b6,0xa776ab75,0x281f2711,0x327c3191,0xaadeabd9,0xb328b414,0x1fdb0000,0x281f0000,
0xa8e8a9e3,0xb122b226,0x25e423db,0x2e2d2c1f,0xa5e4a7da,0xae2db01d,0x28e827da,0x3122301d,0x9fdba3db,0xa81fac1f,0x2ade29e3,0x33283226,
0xaccead7e,0xb3d3b475,0x217f0000,0x28840000,0xaadeac1f,0xb19eb2b9,0x281f257f,0x2ec32c83,0xa81fa97f,0xaec3b080,0x2ade297f,0x319e3080,
0xa17fa57f,0xa884ac83,0x2cce2c1f,0x33d332b9,0xae2daf0e,0xb43eb4d5,0x23110000,0x28e80000,0xac6aad4c,0xb219b34c,0x294d2711,0x2f592ce7,
0xa94dab11,0xaf59b0e4,0x2c6a2b11,0x321930e4,0xa311a711,0xa8e8ace7,0x2e2d2d4c,0x343e334c,0xaf8bb04e,0xb493b534,0x24520000,0x294d0000,
0xad65ae78,0xb294b3df,0x2a7a2852,0x2fef2d4c,0xaa7aac51,0xafefb147,0x2d652c51,0x32943147,0xa452a852,0xa94dad4c,0x2f8b2e78,0x349333df,
0xb074b115,0xb4e7b593,0x251b0000,0x29b10000,0xae5fafa4,0xb30fb438,0x2ba7291b,0x30422db0,0xaba7ad1a,0xb042b1aa,0x2e5f2d1a,0x330f31aa,
0xa51ba91b,0xa9b1adb0,0x30742fa4,0x34e73438,0xb122b1db,0xb53ab5f1,0x25e40000,0x2a160000,0xaf59b067,0xb389b481,0x2c6a29e3,0x308d2e14,
0xac6aade2,0xb08db20d,0x2f592de2,0x3389320d,0xa5e4a9e3,0xaa16ae14,0x31223067,0x353a3481,0xb58db64e,0xb805b887,0x2a7a0000,0x2cce0000,
0xb402b4c9,0xb5dfb6f9,0x30d72e78,0x332830cb,0xb0d7b26f,0xb328b4bd,0x3402326f,0x35df34bd,0xaa7aae78,0xacceb0cb,0x358d34c9,0x380536f9,
0xb5dfb6aa,0xb82ab8b0,0x2ade0000,0x2d000000,0xb43eb511,0xb61ab73d,0x31222edc,0x337130fd,0xb122b2d2,0xb371b4ed,0x343e32d2,0x361a34ed,
0xaadeaedc,0xad00b0fd,0x35df3511,0x382a373d,0xb631b705,0xb850b8d8,0x2b430000,0x2d330000,0xb47bb558,0xb654b780,0x316c2f40,0x33ba312e,
0xb16cb334,0xb3bab51d,0x347b3334,0x3654351d,0xab43af40,0xad33b12e,0x36313558,0x38503780,0xb682b75e,0xb874b900,0x2ba70000,0x2d650000,
0xb4b7b59f,0xb68db7c2,0x31b62fa4,0x34023160,0xb1b6b396,0xb402b54c,0x34b73396,0x368d354c,0xaba7afa4,0xad65b160,0x3682359f,0x387437c2,
0xb6d2b7b7,0xb899b927,0x2c060000,0x2d970000,0xb4f3b5e5,0xb6c6b802,0x32013004,0x34263191,0xb201b3f7,0xb426b57c,0x34f333f7,0x36c6357c,
0xac06b004,0xad97b191,0x36d235e5,0x38993802,0xb721b807,0xb8bcb94d,0x2c380000,0x2dc90000,0xb52fb62b,0xb6ffb822,0x324b3036,0x344b31c3,
0xb24bb42c,0xb44bb5ab,0x352f342c,0x36ff35ab,0xac38b036,0xadc9b1c3,0x3721362b,0x38bc3822,0xb76fb832,0xb8e0b972,0x2c6a0000,0x2dfb0000,
0xb56ab670,0xb737b842,0x32943067,0x346f31f4,0xb294b45d,0xb46fb5da,0x356a345d,0x373735da,0xac6ab067,0xadfbb1f4,0x376f3670,0x38e03842,
0xb7bdb85d,0xb902b996,0x2c9c0000,0x2e2d0000,0xb5a5b6b5,0xb76fb862,0x32de3099,0x34933226,0xb2deb48d,0xb493b608,0x35a5348d,0x376f3608,
0xac9cb099,0xae2db226,0x37bd36b5,0x39023862,0xb924b9ba,0xba1dbab5,0x2e5f0000,0x2fef0000,0xb7a6b881,0xb8a8b96d,0x34b73257,0x35d433df,
0xb4b7b637,0xb5d4b7a1,0x37a63637,0x38a837a1,0xae5fb257,0xafefb3df,0x39243881,0x3a1d396d,0xb946b9dc,0xba39bad0,0x2e910000,0x30100000,
0xb7ddb8a0,0xb8c1b989,0x34db3288,0x35f73408,0xb4dbb665,0xb5f7b7cd,0x37dd3665,0x38c137cd,0xae91b288,0xb010b408,0x394638a0,0x3a393989,
0xb966b9fe,0xba54bae9,0x2ec30000,0x30290000,0xb80ab8bf,0xb8dbb9a4,0x34ff32b9,0x361a3420,0xb4ffb693,0xb61ab7f9,0x380a3693,0x38db37f9,
0xaec3b2b9,0xb029b420,0x396638bf,0x3a5439a4,0xb986ba1f,0xba6fbb02,0x2ef50000,0x30420000,0xb825b8dd,0xb8f3b9be,0x352332ea,0x363c3438,
0xb523b6c1,0xb63cb812,0x382536c1,0x38f33812,0xaef5b2ea,0xb042b438,0x398638dd,0x3a6f39be,0xb9a6ba3f,0xba89bb1a,0x2f270000,0x305b0000,
0xb840b8fb,0xb90cb9d8,0x3546331b,0x365f3451,0xb546b6ee,0xb65fb828,0x384036ee,0x390c3828,0xaf27b31b,0xb05bb451,0x39a638fb,0x3a8939d8,
0xb9c5ba5e,0xbaa2bb30,0x2f590000,0x30740000,0xb85ab918,0xb924b9f2,0x356a334c,0x36823469,0xb56ab71b,0xb682b83d,0x385a371b,0x3924383d,
0xaf59b34c,0xb074b469,0x39c53918,0x3aa239f2,0xb9e3ba7c,0xbababb46,0x2f8b0000,0x308d0000,0xb874b935,0xb93cba0b,0x358d337d,0x36a43481,
0xb58db748,0xb6a4b852,0x38743748,0x393c3852,0xaf8bb37d,0xb08db481,0x39e33935,0x3aba3a0b,0xba00ba99,0xbad1bb5a,0x2fbd0000,0x30a60000,
0xb88eb951,0xb954ba23,0x35b133ae,0x36c63499,0xb5b1b775,0xb6c6b867,0x388e3775,0x39543867,0xafbdb3ae,0xb0a6b499,0x3a003951,0x3ad13a23,
0xbae8bb6e,0xbb7fbbdd,0x30be0000,0x31850000,0xb96bba3b,0xba19bae6,0x36e834b1,0x37f33570,0xb6e8b87c,0xb7f3b91d,0x396b387c,0x3a19391d,
0xb0beb4b1,0xb185b570,0x3ae83a3b,0x3b7f3ae6,0xbafebb80,0xbb8ebbe6,0x30d70000,0x319e0000,0xb982ba52,0xba2dbaf9,0x370a34c9,0x380a3587,
0xb70ab891,0xb80ab930,0x39823891,0x3a2d3930,0xb0d7b4c9,0xb19eb587,0x3afe3a52,0x3b8e3af9,0xbb13bb91,0xbb9cbbed,0x30f00000,0x31b60000,
0xb999ba69,0xba41bb0b,0x372c34e1,0x381a359f,0xb72cb8a6,0xb81ab943,0x399938a6,0x3a413943,0xb0f0b4e1,0xb1b6b59f,0x3b133a69,0x3b9c3b0b,
0xbb27bba0,0xbba9bbf4,0x31090000,0x31cf0000,0xb9afba7f,0xba54bb1d,0x374e34f9,0x382a35b6,0xb74eb8ba,0xb82ab956,0x39af38ba,0x3a543956,
0xb109b4f9,0xb1cfb5b6,0x3b273a7f,0x3ba93b1d,0xbb3abbaf,0xbbb5bbf8,0x31220000,0x31e80000,0xb9c5ba95,0xba67bb2e,0x376f3511,0x383a35ce,
0xb76fb8ce,0xb83ab969,0x39c538ce,0x3a673969,0xb122b511,0xb1e8b5ce,0x3b3a3a95,0x3bb53b2e,0xbb4cbbbc,0xbbc0bbfc,0x313b0000,0x32010000,
0xb9dabaaa,0xba7abb3e,0x37903529,0x384a35e5,0xb790b8e2,0xb84ab97b,0x39da38e2,0x3a7a397b,0xb13bb529,0xb201b5e5,0x3b4c3aaa,0x3bc03b3e,
0xbb5ebbc9,0xbbcbbbff,0x31530000,0x32190000,0xb9f0babf,0xba8cbb4e,0x37b23540,0x385a35fd,0xb7b2b8f6,0xb85ab98d,0x39f038f6,0x3a8c398d,
0xb153b540,0xb219b5fd,0x3b5e3abf,0x3bcb3b4e,0xbb6fbbd4,0xbbd4bc00,0x316c0000,0x32320000,0xba04bad3,0xba9ebb5d,0x37d23558,0x386a3614,
0xb7d2b909,0xb86ab99f,0x3a043909,0x3a9e399f,0xb16cb558,0xb232b614,0x3b6f3ad3,0x3bd43b5d,0x0,0x0,0x0,0x0,
0x2e1f0000,0x336431a8,0x33643400,0x2e1f31a8,0x31a80000,0x31a83400,0xb1a80000,0xb1a8b400,0x33640000,0xae1f31a8,0xae1fb400,0x336431a8,
0x34000000,0xb4000000,0x34000000,0xb4000000,0x33640000,0xae1fb1a8,0xae1f3400,0x3364b1a8,0x31a80000,0x31a8b400,0xb1a80000,0xb1a83400,
0x2e1f0000,0x3364b1a8,0x3364b400,0x2e1fb1a8,0x0,0x0,0x0,0x0,0xae1f0000,0xb36431a8,0xb3643400,0xae1f31a8,
0xb1a80000,0xb1a83400,0x31a80000,0x31a8b400,0xb3640000,0x2e1f31a8,0x2e1fb400,0xb36431a8,0xb4000000,0x34000000,0xb4000000,0x34000000,
0xb3640000,0x2e1fb1a8,0x2e1f3400,0xb364b1a8,0xb1a80000,0xb1a8b400,0x31a80000,0x31a83400,0xae1f0000,0xb364b1a8,0xb364b400,0xae1fb1a8,
0x0,0x0,0x0,0x0,0xae1f0000,0xb364b1a8,0xb364b400,0xae1fb1a8,0x31a80000,0x31a83400,0xb1a80000,0xb1a8b400,
0xb3640000,0x2e1fb1a8,0x2e1f3400,0xb364b1a8,0x34000000,0xb4000000,0x34000000,0xb4000000,0xb3640000,0x2e1f31a8,0x2e1fb400,0xb36431a8,
0x31a80000,0x31a8b400,0xb1a80000,0xb1a83400,0xae1f0000,0xb36431a8,0xb3643400,0xae1f31a8,0x0,0x0,0x0,0x0,
0x2e1f0000,0x3364b1a8,0x3364b400,0x2e1fb1a8,0xb1a80000,0xb1a83400,0x31a80000,0x31a8b400,0x33640000,0xae1fb1a8,0xae1f3400,0x3364b1a8,
0xb4000000,0x34000000,0xb4000000,0x34000000,0x33640000,0xae1f31a8,0xae1fb400,0x336431a8,0xb1a80000,0xb1a8b400,0x31a80000,0x31a83400,
0x2e1f0000,0x336431a8,0x33643400,0x2e1f31a8,0x34003400,0x34003400,0x34003400,0x34003400,0x33643400,0x2e1f31a8,0xae1f0000,0xb364b1a8,
0x31a83400,0xb1a80000,0xb1a8b400,0x31a80000,0x2e1f3400,0xb364b1a8,0x33640000,0xae1f31a8,0x3400,0xb400,0x3400,0xb400,
0xae1f3400,0x3364b1a8,0xb3640000,0x2e1f31a8,0xb1a83400,0x31a80000,0x31a8b400,0xb1a80000,0xb3643400,0xae1f31a8,0x2e1f0000,0x3364b1a8,
0xb4003400,0xb4003400,0xb4003400,0xb4003400,0xb3643400,0xae1f31a8,0x2e1f0000,0x3364b1a8,0xb1a83400,0x31a80000,0x31a8b400,0xb1a80000,
0xae1f3400,0x3364b1a8,0xb3640000,0x2e1f31a8,0x3400,0xb400,0x3400,0xb400,0x2e1f3400,0xb364b1a8,0x33640000,0xae1f31a8,
0x31a83400,0xb1a80000,0xb1a8b400,0x31a80000,0x33643400,0x2e1f31a8,0xae1f0000,0xb364b1a8,0x34003400,0x34003400,0x34003400,0x34003400,
0xb364b400,0xae1fb1a8,0x2e1f0000,0x336431a8,0x31a83400,0xb1a80000,0xb1a8b400,0x31a80000,0xae1fb400,0x336431a8,0xb3640000,0x2e1fb1a8,
0x3400,0xb400,0x3400,0xb400,0x2e1fb400,0xb36431a8,0x33640000,0xae1fb1a8,0xb1a83400,0x31a80000,0x31a8b400,0xb1a80000,
0x3364b400,0x2e1fb1a8,0xae1f0000,0xb36431a8,0xb4003400,0xb4003400,0xb4003400,0xb4003400,0x3364b400,0x2e1fb1a8,0xae1f0000,0xb36431a8,
0xb1a83400,0x31a80000,0x31a8b400,0xb1a80000,0x2e1fb400,0xb36431a8,0x33640000,0xae1fb1a8,0x3400,0xb400,0x3400,0xb400,
0xae1fb400,0x336431a8,0xb3640000,0x2e1fb1a8,0x31a83400,0xb1a80000,0xb1a8b400,0x31a80000,0xb364b400,0xae1fb1a8,0x2e1f0000,0x336431a8,
0x0,0x0,0x0,0x0,0xae1f0000,0xb364b1a8,0xb364b400,0xae1fb1a8,0xb1a80000,0xb1a8b400,0x31a80000,0x31a83400,
0xb3640000,0x2e1fb1a8,0x2e1f3400,0xb364b1a8,0xb4000000,0x34000000,0xb4000000,0x34000000,0xb3640000,0x2e1f31a8,0x2e1fb400,0xb36431a8,
0xb1a80000,0xb1a83400,0x31a80000,0x31a8b400,0xae1f0000,0xb36431a8,0xb3643400,0xae1f31a8,0x0,0x0,0x0,0x0,
0x2e1f0000,0x3364b1a8,0x3364b400,0x2e1fb1a8,0x31a80000,0x31a8b400,0xb1a80000,0xb1a83400,0x33640000,0xae1fb1a8,0xae1f3400,0x3364b1a8,
0x34000000,0xb4000000,0x34000000,0xb4000000,0x33640000,0xae1f31a8,0xae1fb400,0x336431a8,0x31a80000,0x31a83400,0xb1a80000,0xb1a8b400,
0x2e1f0000,0x336431a8,0x33643400,0x2e1f31a8,0x0,0x0,0x0,0x0,0x2e1f0000,0x336431a8,0x33643400,0x2e1f31a8,
0xb1a80000,0xb1a8b400,0x31a80000,0x31a83400,0x33640000,0xae1f31a8,0xae1fb400,0x336431a8,0xb4000000,0x34000000,0xb4000000,0x34000000,
0x33640000,0xae1fb1a8,0xae1f3400,0x3364b1a8,0xb1a80000,0xb1a83400,0x31a80000,0x31a8b400,0x2e1f0000,0x3364b1a8,0x3364b400,0x2e1fb1a8,
0x0,0x0,0x0,0x0,0xae1f0000,0xb36431a8,0xb3643400,0xae1f31a8,0x31a80000,0x31a8b400,0xb1a80000,0xb1a83400,
0xb3640000,0x2e1f31a8,0x2e1fb400,0xb36431a8,0x34000000,0xb4000000,0x34000000,0xb4000000,0xb3640000,0x2e1fb1a8,0x2e1f3400,0xb364b1a8,
0x31a80000,0x31a83400,0xb1a80000,0xb1a8b400,0xae1f0000,0xb364b1a8,0xb364b400,0xae1fb1a8,
};

typedef CUresult (*EncodeFn)(CUtensorMap*, CUtensorMapDataType, cuuint32_t, void*, const cuuint64_t*, const cuuint64_t*,
                             const cuuint32_t*, const cuuint32_t*, CUtensorMapInterleave, CUtensorMapSwizzle,
                             CUtensorMapL2promotion, CUtensorMapFloatOOBfill);

}

extern "C" void kernel_launch(void* const* d_in, const int* in_sizes, int n_in, void* d_out, int out_size) {
    Params p;
    p.x = (const __nv_bfloat16*)d_in[0];
    p.lar = (const __nv_bfloat16*)d_in[1];
    p.aim = (const __nv_bfloat16*)d_in[2];
    p.cr = (const __nv_bfloat16*)d_in[3];
    p.ci = (const __nv_bfloat16*)d_in[4];
    p.logdt = (const __nv_bfloat16*)d_in[5];
    p.dskip = (const __nv_bfloat16*)d_in[6];
    p.wr = (const __nv_bfloat16*)d_in[8];
    p.out = (__nv_bfloat16*)d_out;
    cudaGetSymbolAddress((void**)&p.sc, g_scratch);
    cudaGetSymbolAddress((void**)&p.tab, g_tab);

    void* fn = nullptr;
    cudaDriverEntryPointQueryResult qr;
    cudaGetDriverEntryPoint("cuTensorMapEncodeTiled", &fn, cudaEnableDefault, &qr);
    EncodeFn enc = (EncodeFn)fn;
    CUtensorMap tm_x, tm_g, tm_d;
    const cuuint32_t es[5] = {1, 1, 1, 1, 1};
    {
        const cuuint64_t gd[4] = {1024, 128, 8, 2}, gs[3] = {32768, 4096, 2048};
        const cuuint32_t bx[4] = {16, 64, 4, 1};
        enc(&tm_x, CU_TENSOR_MAP_DATA_TYPE_BFLOAT16, 4, d_in[0], gd, gs, bx, es, CU_TENSOR_MAP_INTERLEAVE_NONE,
            CU_TENSOR_MAP_SWIZZLE_NONE, CU_TENSOR_MAP_L2_PROMOTION_NONE, CU_TENSOR_MAP_FLOAT_OOB_FILL_NONE);
    }
    {
        char *wg = (char*)d_in[9], *wu = (char*)d_in[10];
        p.up_first = wu < wg;
        const cuuint64_t gd[3] = {3584, 1024, 2}, gs[2] = {7168, (cuuint64_t)(p.up_first ? wg - wu : wu - wg)};
        const cuuint32_t bx[3] = {64, 32, 2};
        enc(&tm_g, CU_TENSOR_MAP_DATA_TYPE_BFLOAT16, 3, p.up_first ? wu : wg, gd, gs, bx, es, CU_TENSOR_MAP_INTERLEAVE_NONE,
            CU_TENSOR_MAP_SWIZZLE_128B, CU_TENSOR_MAP_L2_PROMOTION_NONE, CU_TENSOR_MAP_FLOAT_OOB_FILL_NONE);
    }
    {
        const cuuint64_t gd[3] = {1024, 3584, 1}, gs[2] = {2048, 2048 * 3584};
        const cuuint32_t bx[3] = {64, 64, 1};
        enc(&tm_d, CU_TENSOR_MAP_DATA_TYPE_BFLOAT16, 3, d_in[11], gd, gs, bx, es, CU_TENSOR_MAP_INTERLEAVE_NONE,
            CU_TENSOR_MAP_SWIZZLE_128B, CU_TENSOR_MAP_L2_PROMOTION_NONE, CU_TENSOR_MAP_FLOAT_OOB_FILL_NONE);
    }
    cudaFuncSetAttribute(fused_kernel, cudaFuncAttributeMaxDynamicSharedMemorySize, SM_TOTAL + 256);
    fused_kernel<<<128, NTHREADS, SM_TOTAL + 256>>>(p, tm_x, tm_g, tm_d);
}
```

```cpp
#include <cuda_runtime.h>
#include <cuda.h>
#include <cuda_bf16.h>
#include <cuda_fp16.h>
#include <stdint.h>

#define TG(i)
#define TS(i)
#define TSL(i)

#define TSW 0
#define SDELAY 2000
#define EDELAY 800
#define FILL 0xA3210
#define PDELAY 400
#define POLL_LD "ld.relaxed.gpu.global.b128"
#define IDEPTH 4

namespace {

constexpr int NTHREADS = 512;
constexpr int SPIN_LIMIT = 1 << 16;

constexpr int SM_SLAB = 0;
constexpr int SM_RING = 32768;
constexpr int SUB     = 1088;
constexpr int SM_K    = SM_RING + 10 * 8192;
constexpr int SM_S    = SM_K + 32 * SUB;
constexpr int SM_U    = SM_S + 32 * SUB;
constexpr int SM_F2   = SM_U + 32 * SUB;
constexpr int SM_XSEL = SM_F2 + 1536;
constexpr int SM_PAIR = SM_XSEL + 4096;
constexpr int SM_H    = SM_PAIR + 2048;
constexpr int SM_KEYS = SM_H + 1024;
constexpr int SM_TOK  = SM_KEYS + 64;
constexpr int SM_FIX  = SM_TOK + 16;
constexpr int SM_XRAW = SM_FIX + 32;
constexpr int SM_SCL  = SM_XRAW + 64;
constexpr int SM_BAR  = SM_SCL + 16;
constexpr int SM_RED  = SM_XSEL;
constexpr int SM_TAB  = SM_RING + 7 * 8192;
constexpr int B_FULL = 0, B_ROW = 24, B_STG = 32, B_SLAB = 36, B_TOK = 38, B_UFREE = 39, B_FIX = 40, B_PAIR = 41,
              B_TAB = 42, B_TFREE = 43, B_KFREE = 44, B_U = 46, B_PEER = 48, NBAR = 52;
constexpr int SM_TOTAL = SM_BAR + NBAR * 8;
static_assert(SM_TOTAL + 256 <= 232448, "smem");
__device__ __forceinline__ uint32_t chunk_off(int n) { return SM_RING + (n < 14 ? n : n - 14) * 8192; }
constexpr int KP = 272;

struct Scratch {
    uint4 stats[1024];
    uint32_t part[128 * 56 * 16];
    uint32_t epoch;
};
__device__ Scratch g_scratch;

struct Params {
    const __nv_bfloat16 *lar, *aim, *cr, *ci, *logdt, *dskip;
    const __nv_bfloat16 *x, *wr;
    __nv_bfloat16* out;
    Scratch* sc;
    const uint4* tab;
    int up_first;
};

__device__ __forceinline__ uint4 ldg128(const void* p) {
    uint4 v; asm volatile("ld.global.nc.v4.u32 {%0,%1,%2,%3}, [%4];" : "=r"(v.x), "=r"(v.y), "=r"(v.z), "=r"(v.w) : "l"(p)); return v;
}
__device__ __forceinline__ uint4 ld_relaxed128(const void* p) {
    uint4 v;
    asm volatile("{ .reg .b128 t; ld.relaxed.gpu.global.b128 t, [%4]; mov.b128 {%0,%1,%2,%3}, t; }"
                 : "=r"(v.x), "=r"(v.y), "=r"(v.z), "=r"(v.w) : "l"(p) : "memory");
    return v;
}
__device__ __forceinline__ void st_relaxed128(void* p, uint4 v) {
    asm volatile("{ .reg .b128 t; mov.b128 t, {%1,%2,%3,%4}; st.relaxed.gpu.global.b128 [%0], t; }"
                 :: "l"(p), "r"(v.x), "r"(v.y), "r"(v.z), "r"(v.w) : "memory");
}
__device__ __forceinline__ void st_relaxed32(void* p, uint32_t v) {
    asm volatile("st.relaxed.gpu.global.u32 [%0], %1;" :: "l"(p), "r"(v) : "memory");
}
__device__ __forceinline__ uint32_t lds32(uint32_t a) { uint32_t v; asm volatile("ld.shared.u32 %0, [%1];" : "=r"(v) : "r"(a)); return v; }
__device__ __forceinline__ uint32_t lds16(uint32_t a) { uint32_t v; asm volatile("ld.shared.u16 %0, [%1];" : "=r"(v) : "r"(a)); return v; }
__device__ __forceinline__ uint2 lds64(uint32_t a) { uint2 v; asm volatile("ld.shared.v2.u32 {%0,%1}, [%2];" : "=r"(v.x), "=r"(v.y) : "r"(a)); return v; }
__device__ __forceinline__ uint4 lds128(uint32_t a) {
    uint4 v; asm volatile("ld.shared.v4.u32 {%0,%1,%2,%3}, [%4];" : "=r"(v.x), "=r"(v.y), "=r"(v.z), "=r"(v.w) : "r"(a)); return v;
}
__device__ __forceinline__ void sts16(uint32_t a, uint32_t v) { asm volatile("st.shared.u16 [%0], %1;" :: "r"(a), "h"((uint16_t)v) : "memory"); }
__device__ __forceinline__ void sts32(uint32_t a, uint32_t v) { asm volatile("st.shared.u32 [%0], %1;" :: "r"(a), "r"(v) : "memory"); }
__device__ __forceinline__ void sts64(uint32_t a, uint32_t x, uint32_t y) { asm volatile("st.shared.v2.u32 [%0], {%1,%2};" :: "r"(a), "r"(x), "r"(y) : "memory"); }
__device__ __forceinline__ void sts128(uint32_t a, uint32_t x, uint32_t y, uint32_t z, uint32_t w) {
    asm volatile("st.shared.v4.u32 [%0], {%1,%2,%3,%4};" :: "r"(a), "r"(x), "r"(y), "r"(z), "r"(w) : "memory");
}
__device__ __forceinline__ void ldsm4(uint32_t a, uint32_t& r0, uint32_t& r1, uint32_t& r2, uint32_t& r3) {
    asm volatile("ldmatrix.sync.aligned.m8n8.x4.shared.b16 {%0,%1,%2,%3}, [%4];" : "=r"(r0), "=r"(r1), "=r"(r2), "=r"(r3) : "r"(a));
}
__device__ __forceinline__ void mma_f16(float (&d)[4], uint32_t a0, uint32_t a1, uint32_t a2, uint32_t a3, uint32_t b0, uint32_t b1) {
    asm("mma.sync.aligned.m16n8k16.row.col.f32.f16.f16.f32 {%0,%1,%2,%3}, {%4,%5,%6,%7}, {%8,%9}, {%0,%1,%2,%3};"
        : "+f"(d[0]), "+f"(d[1]), "+f"(d[2]), "+f"(d[3]) : "r"(a0), "r"(a1), "r"(a2), "r"(a3), "r"(b0), "r"(b1));
}
__device__ __forceinline__ void mma_bf16(float (&d)[4], uint32_t a0, uint32_t a1, uint32_t a2, uint32_t a3, uint32_t b0, uint32_t b1) {
    asm("mma.sync.aligned.m16n8k16.row.col.f32.bf16.bf16.f32 {%0,%1,%2,%3}, {%4,%5,%6,%7}, {%8,%9}, {%0,%1,%2,%3};"
        : "+f"(d[0]), "+f"(d[1]), "+f"(d[2]), "+f"(d[3]) : "r"(a0), "r"(a1), "r"(a2), "r"(a3), "r"(b0), "r"(b1));
}
__device__ __forceinline__ uint32_t prmt(uint32_t a, uint32_t b, uint32_t s) { uint32_t d; asm("prmt.b32 %0, %1, %2, %3;" : "=r"(d) : "r"(a), "r"(b), "r"(s)); return d; }
__device__ __forceinline__ uint32_t pack_h(float lo, float hi) { uint32_t d; asm("cvt.rn.f16x2.f32 %0, %1, %2;" : "=r"(d) : "f"(hi), "f"(lo)); return d; }
__device__ __forceinline__ uint32_t pack_b(float lo, float hi) { uint32_t d; asm("cvt.rn.bf16x2.f32 %0, %1, %2;" : "=r"(d) : "f"(hi), "f"(lo)); return d; }
__device__ __forceinline__ float blo(uint32_t v) { return __uint_as_float(v << 16); }
__device__ __forceinline__ float bhi(uint32_t v) { return __uint_as_float(v & 0xFFFF0000u); }
__device__ __forceinline__ float rb(float v) { return blo(pack_b(v, v)); }
__device__ __forceinline__ uint32_t bsub2(uint32_t a, uint32_t b) { uint32_t d; asm("sub.rn.bf16x2 %0, %1, %2;" : "=r"(d) : "r"(a), "r"(b)); return d; }
__device__ __forceinline__ uint32_t badd2(uint32_t a, uint32_t b) { uint32_t d; asm("add.rn.bf16x2 %0, %1, %2;" : "=r"(d) : "r"(a), "r"(b)); return d; }
__device__ __forceinline__ uint32_t bmul2(uint32_t a, uint32_t b) { uint32_t d; asm("mul.rn.bf16x2 %0, %1, %2;" : "=r"(d) : "r"(a), "r"(b)); return d; }
__device__ __forceinline__ uint32_t bfma2(uint32_t a, uint32_t b, uint32_t c) { uint32_t d; asm("fma.rn.bf16x2 %0, %1, %2, %3;" : "=r"(d) : "r"(a), "r"(b), "r"(c)); return d; }
__device__ __forceinline__ uint32_t dup_lo(uint32_t v) { uint32_t d; asm("{ .reg .b16 l, h; mov.b32 {l, h}, %1; mov.b32 %0, {l, l}; }" : "=r"(d) : "r"(v)); return d; }
__device__ __forceinline__ uint32_t dup_hi(uint32_t v) { uint32_t d; asm("{ .reg .b16 l, h; mov.b32 {l, h}, %1; mov.b32 %0, {h, h}; }" : "=r"(d) : "r"(v)); return d; }
__device__ __forceinline__ uint32_t norm2(uint32_t x, uint32_t m, uint32_t hi, uint32_t lo) {
    uint32_t a = bsub2(x, m);
    return bfma2(a, hi, bmul2(a, lo));
}
__device__ __forceinline__ float ex2(float v) { float d; asm("ex2.approx.ftz.f32 %0, %1;" : "=f"(d) : "f"(v)); return d; }
__device__ __forceinline__ float rcp(float v) { float d; asm("rcp.approx.ftz.f32 %0, %1;" : "=f"(d) : "f"(v)); return d; }
__device__ __forceinline__ float sigmoidf_(float v) { return rcp(1.0f + ex2(-1.4426950408889634f * v)); }
__device__ __forceinline__ float siluf_(float v) { return v * sigmoidf_(v); }

__device__ __forceinline__ void mbar_init(uint32_t a, int n) { asm volatile("mbarrier.init.shared::cta.b64 [%0], %1;" :: "r"(a), "r"(n) : "memory"); }
__device__ __forceinline__ void mbar_expect(uint32_t a, int tx) { asm volatile("mbarrier.arrive.expect_tx.shared::cta.b64 _, [%0], %1;" :: "r"(a), "r"(tx) : "memory"); }
__device__ __forceinline__ void mbar_arrive(uint32_t a) { asm volatile("mbarrier.arrive.shared::cta.b64 _, [%0];" :: "r"(a) : "memory"); }
__device__ __forceinline__ bool mbar_try(uint32_t a) {
    uint32_t d; asm volatile("{ .reg .pred p; mbarrier.try_wait.parity.shared::cta.b64 p, [%1], 0; selp.u32 %0, 1, 0, p; }" : "=r"(d) : "r"(a) : "memory"); return d;
}
__device__ __forceinline__ void mbar_wait(uint32_t a) {
    if (__builtin_expect(!mbar_try(a), 0)) {
        int n = SPIN_LIMIT;
        while (!mbar_try(a) && --n) {}
    }
}
__device__ __forceinline__ void mbar_arrive_peer(uint32_t a) { asm volatile("mbarrier.arrive.relaxed.cluster.shared::cluster.b64 _, [%0];" :: "r"(a) : "memory"); }
__device__ __forceinline__ uint32_t mapa(uint32_t a, uint32_t rank) { uint32_t d; asm("mapa.shared::cluster.u32 %0, %1, %2;" : "=r"(d) : "r"(a), "r"(rank)); return d; }
__device__ __forceinline__ void st_async2(uint32_t a, uint32_t x, uint32_t y, uint32_t bar) {
    asm volatile("st.async.weak.shared::cluster.mbarrier::complete_tx::bytes.v2.b32 [%0], {%1,%2}, [%3];" :: "r"(a), "r"(x), "r"(y), "r"(bar) : "memory");
}
__device__ __forceinline__ void st_async4(uint32_t a, uint32_t x, uint32_t y, uint32_t z, uint32_t w, uint32_t bar) {
    asm volatile("st.async.weak.shared::cluster.mbarrier::complete_tx::bytes.v4.b32 [%0], {%1,%2,%3,%4}, [%5];"
                 :: "r"(a), "r"(x), "r"(y), "r"(z), "r"(w), "r"(bar) : "memory");
}
__device__ __forceinline__ void stsm4(uint32_t a, uint32_t r0, uint32_t r1, uint32_t r2, uint32_t r3) {
    asm volatile("stmatrix.sync.aligned.m8n8.x4.shared.b16 [%0], {%1,%2,%3,%4};" :: "r"(a), "r"(r0), "r"(r1), "r"(r2), "r"(r3) : "memory");
}
__device__ __forceinline__ void proxy_fence() { asm volatile("fence.proxy.async.shared::cta;" ::: "memory"); }
__device__ __forceinline__ void bar_sync(int id, int n) { asm volatile("bar.sync %0, %1;" :: "r"(id), "r"(n) : "memory"); }
__device__ __forceinline__ void bar_arrive(int id, int n) { asm volatile("bar.arrive %0, %1;" :: "r"(id), "r"(n) : "memory"); }
__device__ __forceinline__ void cluster_arrive() { asm volatile("barrier.cluster.arrive.relaxed.aligned;" ::: "memory"); }
__device__ __forceinline__ void cluster_wait() { asm volatile("barrier.cluster.wait.aligned;" ::: "memory"); }
__device__ __forceinline__ void tma3d(uint32_t dst, const CUtensorMap* tm, int c0, int c1, uint32_t bar, uint64_t pol) {
    asm volatile("cp.async.bulk.tensor.3d.shared::cluster.global.mbarrier::complete_tx::bytes.L2::cache_hint [%0], [%1, {%3, %4, %6}], [%2], %5;"
                 :: "r"(dst), "l"(tm), "r"(bar), "r"(c0), "r"(c1), "l"(pol), "r"(0) : "memory");
}
__device__ __forceinline__ bool elect() {
    uint32_t p; asm volatile("{ .reg .pred p; elect.sync _|p, 0xFFFFFFFF; selp.u32 %0, 1, 0, p; }" : "=r"(p)); return p;
}

struct cf { float r, i; };
__device__ __forceinline__ cf cmul(cf a, cf b) { return {a.r * b.r - a.i * b.i, a.r * b.i + a.i * b.r}; }
__device__ __forceinline__ cf csq(cf a) { return {a.r * a.r - a.i * a.i, (a.r + a.r) * a.i}; }
__device__ __forceinline__ cf cexp_(float a2, float b) { float m = ex2(a2); return {m * __cosf(b), m * __sinf(b)}; }
struct hc { uint32_t r, i; };
__device__ __forceinline__ hc pk(cf a, cf b) { return {pack_h(a.r, b.r), pack_h(a.i, b.i)}; }
__device__ __forceinline__ hc hmulc(hc a, hc b) {
    const __half2 ar = *reinterpret_cast<__half2*>(&a.r), ai = *reinterpret_cast<__half2*>(&a.i);
    const __half2 br = *reinterpret_cast<__half2*>(&b.r), bi = *reinterpret_cast<__half2*>(&b.i);
    const __half2 r = __hfma2(ar, br, __hneg2(__hmul2_rn(ai, bi))), i = __hfma2(ar, bi, __hmul2_rn(ai, br));
    return {*reinterpret_cast<const uint32_t*>(&r), *reinterpret_cast<const uint32_t*>(&i)};
}
__device__ __forceinline__ void sth(uint32_t a, hc v) { sts32(a, v.r); sts32(a + 128, v.i); }
__device__ __forceinline__ uint32_t cpy(uint32_t v, uint32_t z) { uint32_t d; asm("xor.b32 %0, %1, %2;" : "=r"(d) : "r"(v), "r"(z)); return d; }
__device__ __forceinline__ void sched_fence() { asm volatile("pmevent 0;" ::: "memory"); }
__device__ __forceinline__ float tanh_(float v) { float d; asm("tanh.approx.f32 %0, %1;" : "=f"(d) : "f"(v)); return d; }
__device__ __forceinline__ float silu2(float h) {
    return h * rcp(fmaf(ex2(-2.8853900817779268f * h), 0.5f, 0.5f));
}
__device__ __forceinline__ uint32_t hfma2_(uint32_t a, uint32_t b, uint32_t c) { uint32_t d; asm("fma.rn.f16x2 %0, %1, %2, %3;" : "=r"(d) : "r"(a), "r"(b), "r"(c)); return d; }
__device__ __forceinline__ uint32_t hfms2_(uint32_t a, uint32_t b, uint32_t c) {
    uint32_t d; asm("{ .reg .b32 t; neg.f16x2 t, %1; fma.rn.f16x2 %0, t, %2, %3; }" : "=r"(d) : "r"(a), "r"(b), "r"(c)); return d;
}

__device__ __forceinline__ uint64_t bdesc(uint32_t addr, uint32_t sbo) {
    return (uint64_t)((addr & 0x3FFFFu) >> 4) | ((uint64_t)(128 >> 4) << 16) | ((uint64_t)(sbo >> 4) << 32);
}
__device__ __forceinline__ void wg_h(uint32_t (&d)[16], const uint32_t* a, const uint32_t* b, uint64_t d0, uint64_t d1, uint64_t d2, uint64_t d3) {
    asm volatile(
        "wgmma.mma_async.sync.aligned.m64n64k16.f16.f16.f16 {%0,%1,%2,%3,%4,%5,%6,%7,%8,%9,%10,%11,%12,%13,%14,%15}, {%16,%17,%18,%19}, %32, 0, 1, 1, 1;\n"
        "wgmma.mma_async.sync.aligned.m64n64k16.f16.f16.f16 {%0,%1,%2,%3,%4,%5,%6,%7,%8,%9,%10,%11,%12,%13,%14,%15}, {%20,%21,%22,%23}, %33, 1, 1, 1, 1;\n"
        "wgmma.mma_async.sync.aligned.m64n64k16.f16.f16.f16 {%0,%1,%2,%3,%4,%5,%6,%7,%8,%9,%10,%11,%12,%13,%14,%15}, {%24,%25,%26,%27}, %34, 1, 1, 1, 1;\n"
        "wgmma.mma_async.sync.aligned.m64n64k16.f16.f16.f16 {%0,%1,%2,%3,%4,%5,%6,%7,%8,%9,%10,%11,%12,%13,%14,%15}, {%28,%29,%30,%31}, %35, 1, 1, 1, 1;\n"
        : "=r"(d[0]), "=r"(d[1]), "=r"(d[2]), "=r"(d[3]), "=r"(d[4]), "=r"(d[5]), "=r"(d[6]), "=r"(d[7]), "=r"(d[8]), "=r"(d[9]), "=r"(d[10]), "=r"(d[11]), "=r"(d[12]), "=r"(d[13]), "=r"(d[14]), "=r"(d[15])
        : "r"(a[0]), "r"(a[1]), "r"(a[2]), "r"(a[3]), "r"(a[4]), "r"(a[5]), "r"(a[6]), "r"(a[7]), "r"(b[0]), "r"(b[1]), "r"(b[2]), "r"(b[3]), "r"(b[4]), "r"(b[5]), "r"(b[6]), "r"(b[7]), "l"(d0), "l"(d1), "l"(d2), "l"(d3));
}
__device__ __forceinline__ void wg_f0(float (&d)[32], const uint32_t* a, const uint32_t* b, uint64_t d0, uint64_t d1, uint64_t d2, uint64_t d3) {
    asm volatile(
        "wgmma.mma_async.sync.aligned.m64n64k16.f32.f16.f16 {%0,%1,%2,%3,%4,%5,%6,%7,%8,%9,%10,%11,%12,%13,%14,%15,%16,%17,%18,%19,%20,%21,%22,%23,%24,%25,%26,%27,%28,%29,%30,%31}, {%32,%33,%34,%35}, %48, 0, 1, 1, 1;\n"
        "wgmma.mma_async.sync.aligned.m64n64k16.f32.f16.f16 {%0,%1,%2,%3,%4,%5,%6,%7,%8,%9,%10,%11,%12,%13,%14,%15,%16,%17,%18,%19,%20,%21,%22,%23,%24,%25,%26,%27,%28,%29,%30,%31}, {%36,%37,%38,%39}, %49, 1, 1, 1, 1;\n"
        "wgmma.mma_async.sync.aligned.m64n64k16.f32.f16.f16 {%0,%1,%2,%3,%4,%5,%6,%7,%8,%9,%10,%11,%12,%13,%14,%15,%16,%17,%18,%19,%20,%21,%22,%23,%24,%25,%26,%27,%28,%29,%30,%31}, {%40,%41,%42,%43}, %50, 1, 1, 1, 1;\n"
        "wgmma.mma_async.sync.aligned.m64n64k16.f32.f16.f16 {%0,%1,%2,%3,%4,%5,%6,%7,%8,%9,%10,%11,%12,%13,%14,%15,%16,%17,%18,%19,%20,%21,%22,%23,%24,%25,%26,%27,%28,%29,%30,%31}, {%44,%45,%46,%47}, %51, 1, 1, 1, 1;\n"
        : "=f"(d[0]), "=f"(d[1]), "=f"(d[2]), "=f"(d[3]), "=f"(d[4]), "=f"(d[5]), "=f"(d[6]), "=f"(d[7]), "=f"(d[8]), "=f"(d[9]), "=f"(d[10]), "=f"(d[11]), "=f"(d[12]), "=f"(d[13]), "=f"(d[14]), "=f"(d[15]), "=f"(d[16]), "=f"(d[17]), "=f"(d[18]), "=f"(d[19]), "=f"(d[20]), "=f"(d[21]), "=f"(d[22]), "=f"(d[23]), "=f"(d[24]), "=f"(d[25]), "=f"(d[26]), "=f"(d[27]), "=f"(d[28]), "=f"(d[29]), "=f"(d[30]), "=f"(d[31])
        : "r"(a[0]), "r"(a[1]), "r"(a[2]), "r"(a[3]), "r"(a[4]), "r"(a[5]), "r"(a[6]), "r"(a[7]), "r"(b[0]), "r"(b[1]), "r"(b[2]), "r"(b[3]), "r"(b[4]), "r"(b[5]), "r"(b[6]), "r"(b[7]), "l"(d0), "l"(d1), "l"(d2), "l"(d3));
}
__device__ __forceinline__ void wg_f1(float (&d)[32], const uint32_t* a, const uint32_t* b, uint64_t d0, uint64_t d1, uint64_t d2, uint64_t d3) {
    asm volatile(
        "wgmma.mma_async.sync.aligned.m64n64k16.f32.f16.f16 {%0,%1,%2,%3,%4,%5,%6,%7,%8,%9,%10,%11,%12,%13,%14,%15,%16,%17,%18,%19,%20,%21,%22,%23,%24,%25,%26,%27,%28,%29,%30,%31}, {%32,%33,%34,%35}, %48, 1, 1, 1, 1;\n"
        "wgmma.mma_async.sync.aligned.m64n64k16.f32.f16.f16 {%0,%1,%2,%3,%4,%5,%6,%7,%8,%9,%10,%11,%12,%13,%14,%15,%16,%17,%18,%19,%20,%21,%22,%23,%24,%25,%26,%27,%28,%29,%30,%31}, {%36,%37,%38,%39}, %49, 1, 1, 1, 1;\n"
        "wgmma.mma_async.sync.aligned.m64n64k16.f32.f16.f16 {%0,%1,%2,%3,%4,%5,%6,%7,%8,%9,%10,%11,%12,%13,%14,%15,%16,%17,%18,%19,%20,%21,%22,%23,%24,%25,%26,%27,%28,%29,%30,%31}, {%40,%41,%42,%43}, %50, 1, 1, 1, 1;\n"
        "wgmma.mma_async.sync.aligned.m64n64k16.f32.f16.f16 {%0,%1,%2,%3,%4,%5,%6,%7,%8,%9,%10,%11,%12,%13,%14,%15,%16,%17,%18,%19,%20,%21,%22,%23,%24,%25,%26,%27,%28,%29,%30,%31}, {%44,%45,%46,%47}, %51, 1, 1, 1, 1;\n"
        : "+f"(d[0]), "+f"(d[1]), "+f"(d[2]), "+f"(d[3]), "+f"(d[4]), "+f"(d[5]), "+f"(d[6]), "+f"(d[7]), "+f"(d[8]), "+f"(d[9]), "+f"(d[10]), "+f"(d[11]), "+f"(d[12]), "+f"(d[13]), "+f"(d[14]), "+f"(d[15]), "+f"(d[16]), "+f"(d[17]), "+f"(d[18]), "+f"(d[19]), "+f"(d[20]), "+f"(d[21]), "+f"(d[22]), "+f"(d[23]), "+f"(d[24]), "+f"(d[25]), "+f"(d[26]), "+f"(d[27]), "+f"(d[28]), "+f"(d[29]), "+f"(d[30]), "+f"(d[31])
        : "r"(a[0]), "r"(a[1]), "r"(a[2]), "r"(a[3]), "r"(a[4]), "r"(a[5]), "r"(a[6]), "r"(a[7]), "r"(b[0]), "r"(b[1]), "r"(b[2]), "r"(b[3]), "r"(b[4]), "r"(b[5]), "r"(b[6]), "r"(b[7]), "l"(d0), "l"(d1), "l"(d2), "l"(d3));
}
__device__ __forceinline__ void wg_s(uint32_t* d, const uint32_t* a, const uint32_t* b, uint64_t d0, uint64_t d1) {
    asm volatile(
        "wgmma.mma_async.sync.aligned.m64n32k16.f16.f16.f16 {%0,%1,%2,%3,%4,%5,%6,%7}, {%8,%9,%10,%11}, %16, 0, 1, 1, 1;\n"
        "wgmma.mma_async.sync.aligned.m64n32k16.f16.f16.f16 {%0,%1,%2,%3,%4,%5,%6,%7}, {%12,%13,%14,%15}, %17, 1, 1, 1, 1;\n"
        : "=r"(d[0]), "=r"(d[1]), "=r"(d[2]), "=r"(d[3]), "=r"(d[4]), "=r"(d[5]), "=r"(d[6]), "=r"(d[7])
        : "r"(a[0]), "r"(a[1]), "r"(a[2]), "r"(a[3]), "r"(b[0]), "r"(b[1]), "r"(b[2]), "r"(b[3]), "l"(d0), "l"(d1));
}
template <int ACC> __device__ __forceinline__ void wg_w(float (&d)[4], uint64_t da, uint64_t db) {
    asm volatile("wgmma.mma_async.sync.aligned.m64n8k16.f32.bf16.bf16 {%0,%1,%2,%3}, %4, %5, %6, 1, 1, 1, 0;"
                 : "+f"(d[0]), "+f"(d[1]), "+f"(d[2]), "+f"(d[3]) : "l"(da), "l"(db), "n"(ACC));
}
__device__ __forceinline__ void wg_w0(float (&d)[4], uint64_t da, uint64_t db) {
    asm volatile("wgmma.mma_async.sync.aligned.m64n8k16.f32.bf16.bf16 {%0,%1,%2,%3}, %4, %5, 0, 1, 1, 1, 0;"
                 : "=f"(d[0]), "=f"(d[1]), "=f"(d[2]), "=f"(d[3]) : "l"(da), "l"(db));
}
__device__ __forceinline__ void wg_fence() { asm volatile("wgmma.fence.sync.aligned;" ::: "memory"); }
__device__ __forceinline__ void wg_commit() { asm volatile("wgmma.commit_group.sync.aligned;" ::: "memory"); }
template <int N> __device__ __forceinline__ void wg_wait() { asm volatile("wgmma.wait_group.sync.aligned %0;" :: "n"(N) : "memory"); }
__device__ __forceinline__ void touch(uint32_t& r) { asm volatile("" : "+r"(r) :: "memory"); }
__device__ __forceinline__ void touch(float& r) { asm volatile("" : "+f"(r) :: "memory"); }
template <class T, int N> __device__ __forceinline__ void touch(T (&r)[N]) {
#pragma unroll
    for (int i = 0; i < N; i++) touch(r[i]);
}

__global__ void __cluster_dims__(2, 1, 1) __launch_bounds__(NTHREADS, 1)
fused_kernel(const Params p, const __grid_constant__ CUtensorMap tm_x, const __grid_constant__ CUtensorMap tm_g,
             const __grid_constant__ CUtensorMap tm_d)
{
    extern __shared__ __align__(1024) uint8_t smem_raw[];
    const uint32_t sm = (uint32_t)__cvta_generic_to_shared(smem_raw);
    const uint32_t bars = sm + SM_BAR;
    const int tid = threadIdx.x, lane = tid & 31;
    const int g = lane >> 2, q = lane & 3;
    const int c = blockIdx.x, rank = c & 1, G = c >> 1;

    if (tid < 256) {
        uint2 lar4, aim4, cr4, ci4;
        uint32_t ldt_raw, dsk_raw;
        {
            const uint32_t i = c * 256 + tid;
            asm volatile("ld.global.nc.v2.u32 {%0,%1}, [%10]; ld.global.nc.v2.u32 {%2,%3}, [%11]; ld.global.nc.u16 %8, [%14];\n"
                         "ld.global.nc.v2.u32 {%4,%5}, [%12]; ld.global.nc.v2.u32 {%6,%7}, [%13]; ld.global.nc.u16 %9, [%15];"
                         : "=r"(lar4.x), "=r"(lar4.y), "=r"(aim4.x), "=r"(aim4.y), "=r"(cr4.x), "=r"(cr4.y), "=r"(ci4.x), "=r"(ci4.y), "=r"(ldt_raw), "=r"(dsk_raw)
                         : "l"(p.lar + i * 4), "l"(p.aim + i * 4), "l"(p.cr + i * 4), "l"(p.ci + i * 4), "l"(p.logdt + (i >> 5)), "l"(p.dskip + (i >> 5)));
        }
        cluster_arrive();
        sched_fence();
        const int warp = __shfl_sync(0xFFFFFFFFu, tid >> 5, 0);
        const float logdt = blo(ldt_raw), dsk = blo(dsk_raw);
        asm volatile("setmaxnreg.inc.sync.aligned.u32 168;");
        {
            const uint32_t z = (uint32_t)(uintptr_t)p.lar & 1;
            lar4.x = cpy(lar4.x, z); lar4.y = cpy(lar4.y, z); aim4.x = cpy(aim4.x, z); aim4.y = cpy(aim4.y, z);
            cr4.x = cpy(cr4.x, z); cr4.y = cpy(cr4.y, z); ci4.x = cpy(ci4.x, z); ci4.y = cpy(ci4.y, z);
        }
        const int wgi = warp >> 2, w = warp & 3;
        const uint32_t wb = sm + SM_K + (w < 2 ? 16 * w + 8 * wgi : 16 + 16 * wgi + 8 * w) * SUB;
        sth(wb + lane * 4, hc{0x3C003C00u, 0u});

        const float dt = rb(expf(logdt));
        float outscale, cs, dn;
        {
            uint32_t m0 = __vmaxu2(__vmaxu2(cr4.x & 0x7FFF7FFFu, cr4.y & 0x7FFF7FFFu), __vmaxu2(ci4.x & 0x7FFF7FFFu, ci4.y & 0x7FFF7FFFu));
            uint32_t m1 = max(m0 & 0xFFFFu, m0 >> 16);
            float cmax = blo(__reduce_max_sync(0xFFFFFFFFu, m1));
            const float sc = fminf(fmaxf(fmaxf(2.0f * dt * cmax, fabsf(dsk) * (1.0f / 1024.0f)), 1e-30f), 1e30f);
            outscale = __uint_as_float(__float_as_uint(sc) & 0x7F800000u);
            const float inv = __uint_as_float(0x7F000000u - __float_as_uint(outscale));
            cs = 2.0f * dt * inv;
            dn = dsk * inv;
        }
        if (warp == TSW) TSL(39);
        uint32_t fc[16], fs[16], ta[4], tb[4];
        float kacc[2][3][4];
#pragma unroll
        for (int i = 0; i < 2; i++)
#pragma unroll
            for (int j = 0; j < 3; j++) kacc[i][j][0] = kacc[i][j][1] = kacc[i][j][2] = kacc[i][j][3] = 0.f;
        if (lane == 0) kacc[0][0][0] = dn;
        {
            const uint32_t st = wb + lane * 4;
            const uint32_t zk = lds32(wb + 128);
            const uint32_t la = wb + ((lane & 8) ? 29 : (lane & 7)) * KP + (lane >> 4) * 128;
            const uint32_t lo = wb + ((lane >> 3) & 1) * 128 + (lane >> 4) * 16;
            const uint32_t lb = lo + (8 + (lane & 7)) * KP, lb2 = lo + (24 + min(lane & 7, 4)) * KP, lm = lo + 30 * KP;
#pragma unroll 1
            for (int s = 0; s < 2; s++) {
                const uint32_t wl = s ? lar4.y : lar4.x, wa = s ? aim4.y : aim4.x, wr_ = s ? cr4.y : cr4.x, wi = s ? ci4.y : ci4.x;
                const uint32_t ea = pack_b(ex2(blo(wl) * 1.4426950408889634f), ex2(bhi(wl) * 1.4426950408889634f));
                const float a2[2] = {-(blo(ea) * dt) * 1.4426950408889634f, -(bhi(ea) * dt) * 1.4426950408889634f};
                const float b[2] = {blo(wa) * dt, bhi(wa) * dt};
                {
                    cf z8[2], z16[2], z32[2], z64[2], z128[2];
#pragma unroll
                    for (int e = 0; e < 2; e++) {
                        z8[e] = cexp_(a2[e] * 8.f, b[e] * 8.f);
                        z16[e] = csq(z8[e]); z32[e] = csq(z16[e]); z64[e] = csq(z32[e]); z128[e] = csq(z64[e]);
                    }
                    const hc r1 = pk(z8[0], z8[1]), r2 = pk(z16[0], z16[1]), r3 = hmulc(r1, r2), r4 = pk(z32[0], z32[1]);
                    sth(st + 1 * KP, r1); sth(st + 2 * KP, r2); sth(st + 3 * KP, r3); sth(st + 4 * KP, r4);
                    sth(st + 5 * KP, hmulc(r1, r4)); sth(st + 6 * KP, hmulc(r2, r4)); sth(st + 7 * KP, hmulc(r3, r4));
                    sth(st + 29 * KP, pk(z64[0], z64[1])); sth(st + 30 * KP, pk(z128[0], z128[1]));
                }
                {
                    cf C[2], z2[2], z4[2], v2[2], v4[2], c1[2], d1[2];
#pragma unroll
                    for (int e = 0; e < 2; e++) {
                        C[e] = {(e ? bhi(wr_) : blo(wr_)) * cs, (e ? bhi(wi) : blo(wi)) * -cs};
                        const cf z = cexp_(a2[e], -b[e]);
                        const cf v = cexp_(a2[e] * 256.f, b[e] * -256.f);
                        z2[e] = csq(z); z4[e] = csq(z2[e]); v2[e] = csq(v); v4[e] = csq(v2[e]);
                        c1[e] = cmul(C[e], z); d1[e] = cmul(C[e], v);
                    }
                    const hc l0 = pk(C[0], C[1]), l1 = pk(c1[0], c1[1]), e1 = pk(d1[0], d1[1]);
                    const hc h = pk(z2[0], z2[1]), f = pk(z4[0], z4[1]), w = pk(v2[0], v2[1]), y = pk(v4[0], v4[1]);
                    const hc l2 = hmulc(l0, h), l3 = hmulc(l1, h), e2 = hmulc(l0, w), e3 = hmulc(e1, w), e4 = hmulc(l0, y), g2 = hmulc(e1, h);
                    sth(st + 8 * KP, l0); sth(st + 9 * KP, l1); sth(st + 10 * KP, l2); sth(st + 11 * KP, l3);
                    sth(st + 12 * KP, hmulc(l0, f)); sth(st + 13 * KP, hmulc(l1, f)); sth(st + 14 * KP, hmulc(l2, f)); sth(st + 15 * KP, hmulc(l3, f));
                    sth(st + 16 * KP, e1);
                    sth(st + 17 * KP, g2);
                    sth(st + 18 * KP, hmulc(e1, f));
                    sth(st + 19 * KP, hmulc(g2, f));
                    sth(st + 20 * KP, e2);
                    sth(st + 21 * KP, hmulc(e2, f));
                    sth(st + 22 * KP, e3);
                    sth(st + 23 * KP, hmulc(e3, f));
                    sth(st + 24 * KP, e4);
                    sth(st + 25 * KP, hmulc(e1, y));
                    sth(st + 26 * KP, hmulc(e2, y));
                    sth(st + 27 * KP, hmulc(e3, y));
                    sth(st + 28 * KP, hmulc(e4, y));
                }
                __syncwarp();
                if (warp == TSW && s == 0) TSL(27);
                if (s == 1 && lane == 0) mbar_arrive(bars + B_TFREE * 8 + (tb[3] & zk));
#pragma unroll
                for (int kp = 0; kp < 4; kp++) {
                    uint32_t bb[3][4], m2[4];
                    ldsm4(lm + kp * 32, m2[0], m2[1], m2[2], m2[3]);
                    ldsm4(lb + kp * 32, bb[0][0], bb[0][1], bb[0][2], bb[0][3]);
                    ldsm4(lb + 8 * KP + kp * 32, bb[1][0], bb[1][1], bb[1][2], bb[1][3]);
                    ldsm4(lb2 + kp * 32, bb[2][0], bb[2][1], bb[2][2], bb[2][3]);
#pragma unroll
                    for (int k2 = 0; k2 < 2; k2++) {
                        hc v0, m1;
                        ldsm4(la + kp * 32 + k2 * 16, v0.r, m1.r, v0.i, m1.i);
                        const hc mm = {m2[2 * k2], m2[2 * k2 + 1]};
                        const hc v1 = hmulc(v0, m1), v2 = hmulc(v0, mm), v3 = hmulc(v1, mm);
                        v0.r = cpy(v0.r, zk); v0.i = cpy(v0.i, zk);
#pragma unroll
                        for (int nt = 0; nt < 3; nt++) {
                            mma_f16(kacc[0][nt], v0.r, v1.r, v0.i, v1.i, bb[nt][2 * k2], bb[nt][2 * k2 + 1]);
                            mma_f16(kacc[1][nt], v2.r, v3.r, v2.i, v3.i, bb[nt][2 * k2], bb[nt][2 * k2 + 1]);
                        }
                    }
                }
                __syncwarp();
                if (warp == TSW) TSL(s ? 40 : 33);
                if (s == 0) {
                    cluster_wait();
                    mbar_wait(bars + B_TAB * 8);
#pragma unroll
                    for (int i = 0; i < 10; i++) {
                        const uint4 u = lds128(sm + SM_TAB + i * 2048 + (tid & 127) * 16);
                        uint32_t* t = i < 4 ? fc + 4 * i : i < 8 ? fs + 4 * (i - 4) : i == 8 ? ta : tb;
                        t[0] = u.x; t[1] = u.y; t[2] = u.z; t[3] = u.w;
                    }
                }
            }
        }
        TSL(1);
        bar_sync(10 + wgi, 128);
        {
            const uint32_t tb_ = sm + SM_S + (16 * wgi + w) * SUB;
            const uint32_t seg = sm + SM_K + (2 * warp + (lane & 1)) * SUB + (lane >> 1) * 16;
            uint32_t v0[4];
#pragma unroll
            for (int m = 0; m < 4; m++) {
                constexpr float S = 1.0f / 512.0f;
                const float (&k0)[4] = kacc[m >> 1][0], (&k1)[4] = kacc[m >> 1][1], (&k2)[4] = kacc[m >> 1][2];
                const int R = 8 * m + g, o = 2 * (m & 1);
                v0[m] = pack_h(k0[o] * S, k0[o + 1] * S);
                sts32(tb_ + (q < 2 ? 4 * R + 2 * q : 64 * q + 2 * R) * 2, pack_h(k1[o] * S, k1[o + 1] * S));
                const uint32_t v2 = pack_h(k2[o] * S, k2[o + 1] * S);
                if (q < 2 || (m == 0 && lane == 2)) sts16(tb_ + (256 + 64 * q + R) * 2, v2);
                if (q < 2) sts16(tb_ + (288 + 64 * q + R) * 2, v2 >> 16);
            }
            stsm4(seg, v0[0], v0[1], v0[2], v0[3]);
            if (lane == 0) sts16(sm + SM_SCL + warp * 2, __float_as_uint(32768.0f * outscale) >> 16);
            __syncwarp();
            const uint2 l1 = lds64(tb_ + lane * 8);
            const uint32_t l1n = lds16(tb_ + lane * 8 + 8);
            uint32_t l2[2], l2n[2], l3[4], l3n[4];
#pragma unroll
            for (int i = 0; i < 2; i++) { l2[i] = lds32(tb_ + 256 + i * 128 + lane * 4); l2n[i] = lds16(tb_ + 260 + i * 128 + lane * 4); }
#pragma unroll
            for (int i = 0; i < 4; i++) { l3[i] = lds16(tb_ + 512 + i * 64 + lane * 2); l3n[i] = lds16(tb_ + 514 + i * 64 + lane * 2); }
            sts128(seg + 256, prmt(l1.x, 0, 0x1010), prmt(l1.x, l1.y, 0x5432), prmt(l1.y, 0, 0x1010), prmt(l1.y, l1n, 0x5432));
#pragma unroll
            for (int i = 0; i < 2; i++) sts128(seg + 512 + i * 256, prmt(l2[i], 0, 0x1010), l2[i], prmt(l2[i], 0, 0x3232), prmt(l2n[i], 0, 0x1010));
            const uint32_t s3 = (lane & 1) ? 0x5454 : 0x5410;
#pragma unroll
            for (int i = 0; i < 4; i++) {
                const uint32_t vv = prmt(l3[i], 0, 0x1010);
                sts128(seg + 16 * SUB + i * 256, vv, vv, prmt(l3[i], l3n[i], s3), prmt(l3n[i], 0, 0x1010));
            }
        }
        proxy_fence();
        TSL(2);
        bar_sync(10 + wgi, 128);
        const uint64_t dre = bdesc(sm + SM_F2 + 512, 256), dim = bdesc(sm + SM_F2, 256);
        uint32_t k0[32], k1[32];
#pragma unroll
        for (int b = 0; b < 2; b++) {
            const uint64_t d1 = bdesc(sm + SM_K + (16 * b + 8 * wgi) * SUB, SUB);
            uint32_t re[16], im[16];
            if (b == 0 && wgi == 1) bar_sync(5, 256);
            wg_fence();
            wg_h(re, fc, fc + 8, d1, d1 + 16, d1 + 32, d1 + 48);
            wg_h(im, fs, fs + 8, d1, d1 + 16, d1 + 32, d1 + 48);
            wg_commit();
            if (b == 0 && wgi == 0) bar_arrive(5, 256);
            wg_wait<0>();
            touch(re); touch(im);
            if (b == 1 && lane == 0) mbar_arrive(bars + B_KFREE * 8);
            uint32_t (&kk)[32] = b ? k1 : k0;
#pragma unroll
            for (int hh = 0; hh < 2; hh++) {
#pragma unroll
                for (int i = 8 * hh; i < 8 * hh + 8; i++) {
                    re[i] = hfma2_(ta[i & 3], im[i], re[i]); im[i] = hfms2_(tb[i & 3], re[i], im[i]); re[i] = hfma2_(ta[i & 3], im[i], re[i]);
                }
                wg_fence();
                wg_s(kk + 16 * hh, re + 8 * hh, im + 8 * hh, dre, dim);
                wg_s(kk + 16 * hh + 8, re + 8 * hh + 4, im + 8 * hh + 4, dre, dim);
                wg_commit();
            }
            wg_wait<0>();
            touch(kk);
        }
        if (warp == TSW) TSL(35);
        asm volatile("setmaxnreg.inc.sync.aligned.u32 184;");
        touch(k1);
        {
            const uint32_t sg = (g & 1) ? 0xBC00BC00u : 0x3C003C00u;
#pragma unroll
            for (int i = 0; i < 16; i++) {
                const int r = 8 * (i >> 2) + (i & 3);
                k1[r] = hfms2_(sg, k0[r + 4], k1[r]); k1[r + 4] = hfma2_(sg, k0[r], k1[r + 4]);
            }
            touch(k1);
        }
        const uint32_t rowo = (16 * w + (lane & 15)) * 16;
        const uint32_t peer = mapa(sm, rank ^ 1), so = SM_U + 8 * wgi * SUB + w * 1024 + (8 * q + (g ^ (2 * q))) * 16;
        const uint2 sc = lds64(sm + SM_SCL + wgi * 8);
#pragma unroll 1
        for (int b = 0; b < 2; b++) {
            const uint32_t zb = sm + SM_S + 16 * wgi * SUB;
            constexpr int zi = 8 * SUB;
            uint32_t re[16], im[16], su[2][16], z[2][16], y[2][16];
            auto twiddle = [&](int hh) {
#pragma unroll
                for (int i = 8 * hh; i < 8 * hh + 8; i++) {
                    re[i] = hfma2_(ta[i & 3], im[i], re[i]); im[i] = hfms2_(tb[i & 3], re[i], im[i]); re[i] = hfma2_(ta[i & 3], im[i], re[i]);
                    touch(re[i]); touch(im[i]);
                }
            };
            auto dft16 = [&](int hh) {
                wg_fence();
                wg_s(su[hh], re + 8 * hh, im + 8 * hh, dre, dim); wg_s(su[hh] + 8, re + 8 * hh + 4, im + 8 * hh + 4, dre, dim);
                wg_commit();
                sched_fence();
            };
            auto product = [&](int hh) {
                if (b == 0) {
#pragma unroll
                    for (int i = 0; i < 8; i++) {
                        const int r = 8 * (i >> 2) + (i & 3), kr = 16 * hh + r;
                        const hc u = {su[hh][r], su[hh][r + 4]};
                        const hc t = hmulc(u, hc{k0[kr], k0[kr + 4]}), pp = hmulc(u, hc{k1[kr], k1[kr + 4]});
                        z[hh][r] = t.r; z[hh][r + 4] = t.i; k1[kr] = pp.r; k1[kr + 4] = pp.i;
                        touch(k1[kr]); touch(k1[kr + 4]);
                    }
                } else {
#pragma unroll
                    for (int i = 0; i < 8; i++) {
                        const int r = 8 * (i >> 2) + (i & 3), kr = 16 * hh + r;
                        const hc u = {su[hh][r], su[hh][r + 4]};
                        z[hh][r] = hfms2_(u.i, k0[kr + 4], hfma2_(u.r, k0[kr], k1[kr]));
                        z[hh][r + 4] = hfma2_(u.i, k0[kr], hfma2_(u.r, k0[kr + 4], k1[kr + 4]));
                    }
                }
                touch(z[hh]);
            };
            auto idft16 = [&](int hh) {
                wg_fence();
                wg_s(y[hh], z[hh] + 4, z[hh], dre, dim); wg_s(y[hh] + 8, z[hh] + 12, z[hh] + 8, dre, dim);
                wg_commit();
                sched_fence();
            };
            auto untwiddle = [&](int hh) {
#pragma unroll
                for (int i = 0; i < 2; i++) {
                    uint32_t* const yi = y[hh] + 8 * i, * const yr = yi + 4;
#pragma unroll
                    for (int n = 0; n < 4; n++) {
                        yr[n] = hfms2_(ta[n], yi[n], yr[n]); yi[n] = hfma2_(tb[n], yr[n], yi[n]); yr[n] = hfms2_(ta[n], yi[n], yr[n]);
                    }
                    const uint32_t a = zb + (4 * hh + 2 * i + (lane >> 4)) * SUB + rowo;
                    stsm4(a, yr[0], yr[1], yr[2], yr[3]);
                    stsm4(a + zi, yi[0], yi[1], yi[2], yi[3]);
                }
            };
            auto done = [&]() { sched_fence(); wg_wait<0>(); };
            {
                const uint64_t d1 = bdesc(sm + SM_U + (16 * b + 8 * wgi) * SUB, SUB);
                mbar_wait(bars + (B_U + b) * 8);
                proxy_fence();
                if (b == 0) { TSL(3); if (wgi == 1) bar_sync(9, 256); }
                wg_fence();
                wg_h(re, fc, fc + 8, d1, d1 + 16, d1 + 32, d1 + 48);
                wg_h(im, fs, fs + 8, d1, d1 + 16, d1 + 32, d1 + 48);
                wg_commit();
                if (b == 0 && wgi == 0) bar_arrive(9, 256);
                wg_wait<0>();
                touch(re); touch(im);
            }
            if (lane == 0) mbar_arrive_peer(peer + SM_BAR + (B_PEER + 2 * wgi + b) * 8);
            twiddle(0); twiddle(1); dft16(0); dft16(1);
            wg_wait<1>(); touch(su[0]);
            product(0); done(); touch(su[1]); idft16(0);
            product(1); done(); touch(y[0]); idft16(1);
            bar_sync(10 + wgi, 128);
            untwiddle(0); done(); touch(y[1]);
            untwiddle(1);
            proxy_fence();
            if (warp == TSW) TSL(36 + b);
            bar_sync(10 + wgi, 128);
            float acc[32];
            const uint64_t d4 = bdesc(zb, SUB);
            wg_fence();
            wg_f0(acc, fc, fc + 8, d4, d4 + 16, d4 + 32, d4 + 48);
            wg_f1(acc, fs, fs + 8, d4 + zi / 16, d4 + zi / 16 + 16, d4 + zi / 16 + 32, d4 + zi / 16 + 48);
            wg_commit();
            mbar_wait(bars + (B_PEER + 2 * wgi + b) * 8);
            wg_wait<0>();
            touch(acc);
            uint32_t s[2][2][4];
#pragma unroll
            for (int i = 0; i < 8; i++) {
                s[i >> 2][(i >> 1) & 1][2 * (i & 1)] = bmul2(pack_b(acc[i], acc[8 + i]), sc.x);
                s[i >> 2][(i >> 1) & 1][2 * (i & 1) + 1] = bmul2(pack_b(acc[16 + i], acc[24 + i]), sc.y);
            }
            const uint32_t sb = SM_BAR + (B_STG + b) * 8;
#pragma unroll
            for (int j = 0; j < 2; j++)
                if (j == rank) {
#pragma unroll
                    for (int hi = 0; hi < 2; hi++) {
                        const uint32_t (&r)[4] = s[1 - j][hi], (&l)[4] = s[j][hi];
                        st_async4(peer + so + 16 * b * SUB + hi * 512, r[0], r[1], r[2], r[3], peer + sb);
                        sts128(sm + so + (16 * b + 4) * SUB + 64 + hi * 512, l[0], l[1], l[2], l[3]);
                    }
                }
            __syncwarp();
            if (lane == 0) mbar_arrive(sm + sb);
            if (warp == TSW) TSL(5 + b);
        }
        TSL(7);
    } else {
    const int warp = __shfl_sync(0xFFFFFFFFu, tid >> 5, 0);
    if (warp < 12) {
        const int v = warp - 8;
        cluster_arrive();
        const uint32_t xs = sm + SM_U + v * 8192;
        if (elect()) {
#pragma unroll
            for (int r = 0; r < 2; r++) mbar_init(bars + (B_ROW + 2 * v + r) * 8, 1);
            asm volatile("fence.mbarrier_init.release.cluster;" ::: "memory");
#pragma unroll
            for (int e = 0; e < 2; e++) {
                if (e) { const int t0_ = clock(); while ((int)clock() - t0_ < EDELAY) __nanosleep(40); }
                mbar_expect(bars + (B_ROW + 2 * v + e) * 8, 4096);
#pragma unroll
                for (int r = 0; r < 2; r++)
                    asm volatile("cp.async.bulk.shared::cluster.global.mbarrier::complete_tx::bytes [%0], [%1], 2048, [%2];"
                                 :: "r"(xs + e * 4096 + r * 2048), "l"(p.x + (size_t)(128 * (c & 15) + 32 * v + 16 * r + 2 * (c >> 4) + e) * 1024),
                                    "r"(bars + (B_ROW + 2 * v + e) * 8) : "memory");
            }
        }
        __syncwarp();
        uint4 w4[4];
#pragma unroll
        for (int k = 0; k < 4; k++) w4[k] = ldg128(reinterpret_cast<const uint4*>(p.wr) + 32 * k + lane);
        {
            constexpr uint32_t ONE = 0x3F803F80u;
            const uint32_t zr = p.up_first >> 1;
            uint4 w5[4];
#pragma unroll
            for (int k = 0; k < 4; k++) {
                w5[k].x = w4[k].x + zr; w5[k].y = w4[k].y + zr; w5[k].z = w4[k].z + zr; w5[k].w = w4[k].w + zr;
                w4[k].x = cpy(w4[k].x, zr); w4[k].y = cpy(w4[k].y, zr); w4[k].z = cpy(w4[k].z, zr); w4[k].w = cpy(w4[k].w, zr);
            }
            const bool od = g & 1;
#pragma unroll 1
            for (int r2 = 0; r2 < 2; r2++) {
                mbar_wait(bars + (B_ROW + 2 * v + r2) * 8);
                TSL(43);
                float s1[2][4] = {}, q0[2][4] = {};
#pragma unroll
                for (int k = 0; k < 4; k++)
#pragma unroll
                    for (int r = 0; r < 2; r++) {
                        const uint4 x = lds128(xs + r2 * 4096 + r * 2048 + k * 512 + lane * 16);
                        const uint4& ww = r ? w5[k] : w4[k];
                        mma_bf16(q0[r], cpy(x.x, zr), ww.x, cpy(x.y, zr), ww.y, x.x, x.y);
                        mma_bf16(s1[r], x.x, x.y, x.z, x.w, ONE, ONE);
                        mma_bf16(q0[r], cpy(x.z, zr), ww.z, cpy(x.w, zr), ww.w, x.z, x.w);
                    }
#pragma unroll
                for (int r = 0; r < 2; r++)
                    if (q == (g >> 1))
                        sts128(sm + SM_RED + (4 * v + r2 + 2 * r) * 144 + g * 16, __float_as_uint(od ? q0[r][1] : q0[r][0]),
                               __float_as_uint(od ? q0[r][3] : q0[r][2]), __float_as_uint(s1[r][0]), __float_as_uint(s1[r][2]));
            }
            bar_arrive(7, 160);
        }
        TSL(8);
        bar_sync(6, 160);
        const uint32_t tag = lds32(sm + SM_TOK + 8);
        cluster_wait();
        asm volatile("setmaxnreg.dec.sync.aligned.u32 96;");
        const uint32_t peer = mapa(sm, rank ^ 1);
        if (v == 0 && lane == 0) mbar_arrive_peer(peer + SM_BAR + B_UFREE * 8);
        {
            uint4 st[8] = {};
            const uint4* src = p.sc->stats + rank * 512 + 16 * v + (lane >> 1);
            const uint32_t tb = ((tag & 1) << 15) | ((tag >> 1) << 31);
#pragma unroll
            for (int i = 0; i < 8; i++) st[i].z = ~tb;
            int it = 0;
            bool ok;
            bar_sync(3, 192);
            if (warp == 8) TSL(44);
            do {
                uint32_t bad = 0;
#pragma unroll
                for (int i = 0; i < 8; i++)
                    asm volatile("{ .reg .pred p; .reg .b128 t; setp.ne.u32 p, %5, 0; mov.b128 t, {%0,%1,%2,%3};\n"
                                 "@p " POLL_LD " t, [%4]; mov.b128 {%0,%1,%2,%3}, t; }"
                                 : "+r"(st[i].x), "+r"(st[i].y), "+r"(st[i].z), "+r"(st[i].w)
                                 : "l"(src + (i >> 2) * 64 + (i & 3) * 128), "r"((st[i].z ^ tb) & 0x80008000u) : "memory");
#pragma unroll
                for (int i = 0; i < 8; i++) bad |= st[i].z ^ tb;
                ok = __all_sync(0xFFFFFFFFu, (bad & 0x80008000u) == 0);
                if (warp == 8 && it == 0) TSL(45);
            } while (!ok && ++it < SPIN_LIMIT);
            TSL(11); TG(31);
#pragma unroll
            for (int i = 0; i < 8; i++) { st[i].z = bmul2(st[i].z & 0x7FFF7FFFu, 0x3F003F00u); st[i].y = bmul2(st[i].y, 0x3F003F00u); }
            const uint32_t xo = sm + SM_SLAB + v * 512 + lane * 16;
            const bool own = (lane & 1) == rank;
            uint32_t n[8][4];
            auto normalise = [&](int b, int i) {
#pragma unroll
                for (int e = 0; e < 2; e++) {
                    const uint4 x = lds128(xo + b * 16384 + e * 8192 + i * 2048);
                    const uint32_t m = e ? dup_hi(st[i].x) : dup_lo(st[i].x), hi = e ? dup_hi(st[i].z) : dup_lo(st[i].z), lo = e ? dup_hi(st[i].y) : dup_lo(st[i].y);
                    uint32_t (&r)[4] = n[2 * i + e];
                    r[0] = norm2(x.x, m, hi, lo); r[1] = norm2(x.y, m, hi, lo); r[2] = norm2(x.z, m, hi, lo); r[3] = norm2(x.w, m, hi, lo);
                }
                const uint4 t = st[i]; st[i] = st[4 + i]; st[4 + i] = t;
            };
            mbar_wait(bars + B_UFREE * 8);
#pragma unroll 1
            for (int b = 0; b < 2; b++) {
                mbar_wait(bars + (B_SLAB + b) * 8);
                TSL(b ? 38 : 10);
#pragma unroll
                for (int i = 0; i < 4; i++) normalise(b, i);
                const uint32_t ua = SM_U + (16 * b + rank) * SUB + (16 * v + (lane >> 1)) * 16;
#pragma unroll
                for (int cc = 0; cc < 8; cc++) {
                    uint32_t o[4];
#pragma unroll
                    for (int i = 0; i < 4; i++)
                        o[i] = (cc & 1) ? pack_h(bhi(n[2 * i][cc >> 1]), bhi(n[2 * i + 1][cc >> 1])) : pack_h(blo(n[2 * i][cc >> 1]), blo(n[2 * i + 1][cc >> 1]));
                    const uint32_t dst = own ? mapa(sm, rank) : peer;
                    st_async4(dst + ua + 2 * cc * SUB, o[0], o[1], o[2], o[3], dst + SM_BAR + (B_U + b) * 8);
                }
                TSL(b ? 41 : 12);
            }
            const uint32_t stg = sm + SM_U + (own ? 4 * SUB + 64 : 0) + v * 1024 + (lane >> 4) * 512;
            const int tl = 256 * v + 16 * (lane >> 1) + 8 * rank;
            __nv_bfloat16* const op = p.out + (size_t)tl * 1024 + G * 16 + (lane & 1) * 8;
#pragma unroll 1
            for (int b = -1; b < 2; b++) {
                uint32_t skip = 0;
                if (b >= 0) {
                    mbar_wait(bars + B_TOK * 8);
                    const uint2 tr = lds64(sm + SM_TOK);
                    const int d0 = tr.x - tl - 1024 * b, d1 = tr.y - tl - 1024 * b;
                    skip = ((d0 & ~7) ? 0u : 1u << d0) | ((d1 & ~7) ? 0u : 1u << d1);
                    mbar_wait(bars + (B_STG + b) * 8);
                    if (skip) {
#pragma unroll 1
                        for (int k = 0; k < 2; k++) {
                            const int d = k ? d1 : d0;
                            if (!(d & ~7)) {
                                const uint32_t a = stg + 16 * b * SUB + (4 * (d & 6) + (((lane >> 1) & 7) ^ (d & 6))) * 16 + (d & 1) * 8, dst = mapa(sm, k);
                                const uint2 s0 = lds64(a), s1 = lds64(a + 8 * SUB);
                                st_async4(dst + SM_FIX + (lane & 1) * 16, s0.x, s0.y, s1.x, s1.y, dst + SM_BAR + B_FIX * 8);
                            }
                        }
                    }
                    __syncwarp();
                }
#pragma unroll
                for (int i = 0; i < 4; i++) {
                    if (b >= 0) {
                        const uint32_t a = stg + 16 * b * SUB + (8 * i + (((lane >> 1) & 7) ^ (2 * i))) * 16;
                        const uint4 r0 = lds128(a), r1 = lds128(a + 8 * SUB);
#pragma unroll
                        for (int e = 0; e < 2; e++) {
                            const uint4 x = lds128(xo + b * 16384 + e * 8192 + i * 2048);
                            const uint32_t s0 = e ? r0.z : r0.x, s1 = e ? r0.w : r0.y, s2 = e ? r1.z : r1.x, s3 = e ? r1.w : r1.y;
                            const uint32_t (&gt)[4] = n[2 * i + e];
                            asm volatile("{ .reg .pred p; setp.eq.u32 p, %5, 0; @p st.global.v4.u32 [%0], {%1,%2,%3,%4}; }"
                                         :: "l"(op + (size_t)(1024 * b + 2 * i + e) * 1024), "r"(badd2(x.x, bmul2(s0, gt[0]))), "r"(badd2(x.y, bmul2(s1, gt[1]))),
                                            "r"(badd2(x.z, bmul2(s2, gt[2]))), "r"(badd2(x.w, bmul2(s3, gt[3]))), "r"(skip & (1u << (2 * i + e))) : "memory");
                        }
                    }
                    if (b < 1) {
                        normalise(b + 1, i);
#pragma unroll
                        for (int k = 0; k < 8; k++) { uint32_t& r = n[2 * i + (k >> 2)][k & 3]; r = pack_b(silu2(blo(r)), silu2(bhi(r))); }
                    }
                }
                TSL(b < 0 ? 0 : b ? 23 : 22);
            }
            TSL(17); TG(30);
        }
    } else {
        const int v = warp - 12;
        if (lane == 0) {
            if (v == 1) {
                mbar_init(bars + B_TAB * 8, 1); mbar_init(bars + B_TFREE * 8, 8); mbar_init(bars + B_KFREE * 8, 8);
                mbar_expect(bars + B_TAB * 8, 20480 + 1536);
            } else if (v == 0) {
                mbar_init(bars + B_SLAB * 8, 1); mbar_init(bars + (B_SLAB + 1) * 8, 1); mbar_init(bars + B_TOK * 8, 2); mbar_init(bars + B_UFREE * 8, 1);
                mbar_expect(bars + B_SLAB * 8, 16384); mbar_expect(bars + (B_SLAB + 1) * 8, 16384);
            } else {
                mbar_init(bars + (B_STG + v - 2) * 8, 9); mbar_init(bars + (B_FIX + v - 2) * 8, 1);
                mbar_init(bars + (B_U + v - 2) * 8, 1); mbar_expect(bars + (B_U + v - 2) * 8, 16384);
                mbar_expect(bars + (B_STG + v - 2) * 8, 8192); mbar_expect(bars + (B_FIX + v - 2) * 8, v == 2 ? 32 : 2048);
            }
            mbar_init(bars + (B_PEER + v) * 8, 4);
#pragma unroll
            for (int i = 0; i < 6; i++) mbar_init(bars + (B_FULL + 6 * v + i) * 8, 1);
            asm volatile("fence.mbarrier_init.release.cluster;" ::: "memory");
        }
        __syncwarp();
        cluster_arrive();
        asm volatile("setmaxnreg.dec.sync.aligned.u32 48;");
        uint64_t pol; asm volatile("createpolicy.fractional.L2::evict_first.b64 %0, 1.0;" : "=l"(pol));
        auto load_chunk = [&](int n) {
            const bool gu = n < 16;
            mbar_expect(bars + (B_FULL + n) * 8, 8192);
            tma3d(sm + chunk_off(n), gu ? &tm_g : &tm_d, gu ? G * 64 : rank * 512 + (n - 16) * 64, gu ? rank * 512 + n * 32 : G * 64, bars + (B_FULL + n) * 8, pol);
        };
        uint32_t* const my_part = p.sc->part + ((2 * (32 * rank + v) + (q & 1)) * 56 + G) * 16 + g + 8 * (q >> 1);
        if (G < 56) {
#pragma unroll
            for (int n = 0; n < 8; n++) st_relaxed32(my_part + n * 8 * 56 * 16, 0);
        }
        cluster_wait();
        const bool lead = elect();
        uint32_t key = 0;
        if (v == 0) {
            asm volatile("prefetch.tensormap [%0];" :: "l"(&tm_x) : "memory");
            asm volatile("prefetch.tensormap [%0];" :: "l"(&tm_g) : "memory");
            { const int t0_ = clock(); while ((int)clock() - t0_ < SDELAY) __nanosleep(40); }
            if (lead) {
                int n = 0;
#pragma unroll 1
                for (int i = 0; i < 5; i++) {
                    if (G < 56) {
#pragma unroll 1
                        for (; n < ((FILL >> (4 * i)) & 15); n++) {
                            if (n >= IDEPTH) mbar_wait(bars + (B_FULL + n - IDEPTH) * 8);
                            if (n == 7) mbar_wait(bars + B_TFREE * 8);
                            load_chunk(n);
                        }
                    }
                    if (i < 4)
                        asm volatile("cp.async.bulk.tensor.4d.shared::cluster.global.mbarrier::complete_tx::bytes [%0], [%1, {%3, %4, %5, %6}], [%2];"
                                     :: "r"(sm + SM_SLAB + (i & 1) * 16384 + (i >> 1) * 8192), "l"(&tm_x), "r"(bars + (B_SLAB + (i & 1)) * 8),
                                        "r"(G * 16), "r"(64 * (i & 1)), "r"(4 * rank), "r"(i >> 1) : "memory");
                }
                TS(20);
                if (G < 56) {
                    mbar_wait(bars + B_KFREE * 8);
#pragma unroll 1
                    for (; n < 14; n++) load_chunk(n);
                }
                TS(21);
            }
            __syncwarp();
        } else if (v == 1) {
            if (lead) {
                asm volatile("cp.async.bulk.shared::cluster.global.mbarrier::complete_tx::bytes [%0], [%1], 20480, [%2];"
                             :: "r"(sm + SM_TAB), "l"(p.tab), "r"(bars + B_TAB * 8) : "memory");
                asm volatile("cp.async.bulk.shared::cluster.global.mbarrier::complete_tx::bytes [%0], [%1], 1536, [%2];"
                             :: "r"(sm + SM_F2), "l"(p.tab + 1280), "r"(bars + B_TAB * 8) : "memory");
                asm volatile("prefetch.tensormap [%0];" :: "l"(&tm_d) : "memory");
            }
        } else {
            const int sw = v - 2;
            if (sw == 0) {
                uint32_t tag;
                uint4* const my_stats = p.sc->stats + c * 8 + (lane >> 2);
                asm volatile("ld.relaxed.gpu.global.u32 %0, [%1];" : "=r"(tag) : "l"(&p.sc->epoch) : "memory");
                float ws = 0.f;
#pragma unroll
                for (int k = 0; k < 4; k++) {
                    const uint4 w = ldg128(reinterpret_cast<const uint4*>(p.wr) + 32 * k + lane);
                    ws += (blo(w.x) + bhi(w.x)) + (blo(w.y) + bhi(w.y)) + (blo(w.z) + bhi(w.z)) + (blo(w.w) + bhi(w.w));
                }
                if (q == 0) st_relaxed128(my_stats, make_uint4(0, 0, 0, 0));
                tag = tag % 3 + 1;
                sts32(sm + SM_TOK + 8, tag);
                bar_arrive(6, 160);
#pragma unroll
                for (int o = 1; o < 32; o <<= 1) ws += __shfl_xor_sync(0xFFFFFFFFu, ws, o);
                const uint32_t tb = ((tag & 1) << 15) | ((tag >> 1) << 31);
                const uint32_t ra = sm + SM_RED + (lane >> 1) * 144 + (lane & 1) * 64;
                const uint32_t kidx = 0xFFFF - (128 * (c & 15) + 16 * (lane >> 2) + 2 * (c >> 4) + ((lane >> 1) & 1));
                touch(ws);
                bar_sync(7, 160);
                const uint4 a0 = lds128(ra), a1 = lds128(ra + 16), a2 = lds128(ra + 32), a3 = lds128(ra + 48);
#define F(v) __uint_as_float(v)
                float ss = (F(a0.x) + F(a1.x)) + (F(a2.x) + F(a3.x)), dw = (F(a0.y) + F(a1.y)) + (F(a2.y) + F(a3.y));
                float sx = ((F(a0.z) + F(a1.z)) + (F(a2.z) + F(a3.z))) + ((F(a0.w) + F(a1.w)) + (F(a2.w) + F(a3.w)));
#undef F
                ss += __shfl_xor_sync(0xFFFFFFFFu, ss, 1); dw += __shfl_xor_sync(0xFFFFFFFFu, dw, 1); sx += __shfl_xor_sync(0xFFFFFFFFu, sx, 1);
                const float mean = sx * (1.0f / 1024.0f);
                const float var = fmaxf(ss * (1.0f / 1024.0f) - mean * mean, 0.f);
                const float m = rb(mean);
                float sd; asm("sqrt.approx.ftz.f32 %0, %1;" : "=f"(sd) : "f"(rb(rb(var) + 1e-5f)));
                const float rs = rcp(rb(sd));
                const float hi = rb(rs);
                const uint32_t p0 = pack_b(m, hi), p1 = pack_b(rs - hi, rs * (dw - m * ws));
                const uint32_t o0 = __shfl_xor_sync(0xFFFFFFFFu, p0, 2), o1 = __shfl_xor_sync(0xFFFFFFFFu, p1, 2);
                const uint32_t kr = ((p1 ^ (p1 >> 31 ? 0xFFFF0000u : 0x80000000u)) & 0xFFFF0000u) | kidx;
                const uint32_t k1 = __reduce_max_sync(0xFFFFFFFFu, kr), k2 = __reduce_max_sync(0xFFFFFFFFu, kr == k1 ? 0u : kr);
                if (q == 0) st_relaxed128(my_stats, make_uint4(prmt(p0, o0, 0x5410), prmt(p1, o1, 0x5410),
                                                               (prmt(p0, o0, 0x7632) & 0x7FFF7FFFu) | tb, lane == 0 ? k1 : k2));
                TSL(9);
                { const int t0_ = clock(); while ((int)clock() - t0_ < PDELAY) __nanosleep(20); }
            }
            bar_sync(3, 192);
            const uint32_t tg = lds32(sm + SM_TOK + 8), tb = ((tg & 1) << 15) | ((tg >> 1) << 31);
            {
                const uint32_t* src = &p.sc->stats[(sw * 64 + (lane >> 1)) * 8 + (lane & 1)].z;
                uint2 kz[4];
#pragma unroll
                for (int i = 0; i < 4; i++) kz[i] = make_uint2(~tb, 0);
                int it = 0;
                bool ok;
                do {
#pragma unroll
                    for (int i = 0; i < 4; i++)
                        asm volatile("{ .reg .pred p; .reg .b64 t; setp.ne.u32 p, %3, 0; mov.b64 t, {%0,%1};\n"
                                     "@p ld.relaxed.gpu.global.b64 t, [%2]; mov.b64 {%0,%1}, t; }"
                                     : "+r"(kz[i].x), "+r"(kz[i].y) : "l"(src + i * 512), "r"((kz[i].x ^ tb) & 0x80008000u) : "memory");
                    ok = __all_sync(0xFFFFFFFFu, (((kz[0].x ^ tb) | (kz[1].x ^ tb) | (kz[2].x ^ tb) | (kz[3].x ^ tb)) & 0x80008000u) == 0);
                } while (!ok && ++it < SPIN_LIMIT);
                const uint32_t a1 = max(kz[0].y, kz[1].y), b1 = max(kz[2].y, kz[3].y);
                const uint32_t h1 = max(a1, b1), h2 = __vimax3_u32(min(a1, b1), min(kz[0].y, kz[1].y), min(kz[2].y, kz[3].y));
                const uint32_t w1 = __reduce_max_sync(0xFFFFFFFFu, h1), w2 = __reduce_max_sync(0xFFFFFFFFu, h1 == w1 ? h2 : h1);
                sts64(sm + SM_KEYS + sw * 8, w1, w2);
                bar_sync(8, 64);
                const uint2 o = lds64(sm + SM_KEYS + 8 - sw * 8);
                key = sw ? __vimax3_u32(min(w1, o.x), w2, o.y) : max(w1, o.x);
                TSL(19);
            }
            const int t = (0xFFFF - (key & 0xFFFF)) & 2047;
            {
                const uint4* row = reinterpret_cast<const uint4*>(p.x + (size_t)t * 1024);
                uint4 xr[3];
                xr[0] = ldg128(row + 64 * rank + lane); xr[1] = ldg128(row + 64 * rank + 32 + lane); xr[2] = ldg128(row + 2 * G + (lane & 1));
                uint4 stk;
                int it = 0;
                do stk = ld_relaxed128(p.sc->stats + ((t >> 1) & 7) * 128 + (t >> 4)); while (((stk.z ^ tb) & 0x80008000u) && ++it < SPIN_LIMIT);
                if (lane == 0) {
                    sts32(sm + SM_TOK + 4 * sw, t);
                    if (c == 0 && sw == 0) st_relaxed32(&p.sc->epoch, tg);
                }
                const uint32_t se = (t & 1) ? 0x3232 : 0x1010;
                const uint32_t m = prmt(stk.x, 0, se), hi = prmt(stk.z, 0, se) & 0x7FFF7FFFu, lo = prmt(stk.y, 0, se);
                const uint32_t a = sm + SM_XSEL + lane * 32 + sw * 16;
#pragma unroll
                for (int i = 0; i < 2; i++)
                    sts128(a + i * 1024, norm2(xr[i].x, m, hi, lo), norm2(xr[i].y, m, hi, lo), norm2(xr[i].z, m, hi, lo), norm2(xr[i].w, m, hi, lo));
                proxy_fence();
                __syncwarp();
                if (lane == 0) mbar_arrive(bars + B_TOK * 8);
                if (sw == rank && lane < 2) {
                    sts128(sm + SM_XRAW + lane * 16, xr[2].x, xr[2].y, xr[2].z, xr[2].w);
                    sts128(sm + SM_XRAW + 32 + lane * 16, norm2(xr[2].x, m, hi, lo), norm2(xr[2].y, m, hi, lo), norm2(xr[2].z, m, hi, lo), norm2(xr[2].w, m, hi, lo));
                }
                __syncwarp();
                TSL(42);
            }
        }
        mbar_wait(bars + B_TOK * 8);
        const uint32_t tag = lds32(sm + SM_TOK + 8);
        {
            if (G < 56) {
                const uint64_t dw = (uint64_t)((sm & 0x3FFFFu) >> 4) | (1ull << 16) | (64ull << 32) | (1ull << 62);
                const uint64_t dx = (uint64_t)(((sm + SM_XSEL) & 0x3FFFFu) >> 4) | (2ull << 16) | (8ull << 32);
                const uint64_t dh = (uint64_t)(((sm + SM_H) & 0x3FFFFu) >> 4) | (8ull << 16) | (8ull << 32);
                float ag[4] = {0, 0, 0, 0}, au[4] = {0, 0, 0, 0};
                touch(ag); touch(au);
                TSL(13);
                auto issue = [&](int n) {
                    const uint64_t a = dw + (chunk_off(n) >> 4), a2 = a + 512, b = dx + n * 8;
                    mbar_wait(bars + (B_FULL + n) * 8);
                    mbar_wait(bars + (B_FULL + n + 1) * 8);
                    wg_fence();
                    wg_w<1>(ag, a, b); wg_w<1>(au, a + 256, b); wg_w<1>(ag, a + 128, b + 4); wg_w<1>(au, a + 384, b + 4);
                    wg_w<1>(ag, a2, b + 8); wg_w<1>(au, a2 + 256, b + 8); wg_w<1>(ag, a2 + 128, b + 12); wg_w<1>(au, a2 + 384, b + 12);
                    wg_commit();
                };
#pragma unroll 1
                for (int n = 0; n < 16; n += 2) {
                    issue(n);
                    if (n == 2 || n == 4 || n == 10) { wg_wait<1>(); bar_sync(4, 128); }
                    if ((n == 2 || n == 4 || n >= 10) && v == ((n >> 1) & 3) && lead) {
                        const int m = n + (n < 10 ? 12 : 8);
                        load_chunk(m); load_chunk(m + 1);
                    }
                    __syncwarp();
                    if (n == 8) TSL(4);
                    if (n == 14) TSL(34);
                }
                wg_wait<0>();
                touch(ag); touch(au);
                TSL(14);
                if (q == 0) {
#pragma unroll
                    for (int r = 0; r < 2; r++) {
                        const uint32_t dst = mapa(sm, r), o = dst + SM_PAIR + rank * 1024 + v * 256 + g * 32;
                        st_async4(o, __float_as_uint(ag[0]), __float_as_uint(ag[1]), __float_as_uint(ag[2]), __float_as_uint(ag[3]), dst + SM_BAR + B_PAIR * 8);
                        st_async4(o + 16, __float_as_uint(au[0]), __float_as_uint(au[1]), __float_as_uint(au[2]), __float_as_uint(au[3]), dst + SM_BAR + B_PAIR * 8);
                    }
                }
                mbar_wait(bars + B_PAIR * 8);
                {
                    const uint32_t o = sm + SM_PAIR + v * 256 + g * 32 + q * 4, og = o + (p.up_first ? 16 : 0), ou = o + (p.up_first ? 0 : 16);
                    const float gs = rb(__uint_as_float(lds32(og)) + __uint_as_float(lds32(og + 1024)));
                    const float us = rb(__uint_as_float(lds32(ou)) + __uint_as_float(lds32(ou + 1024)));
                    const float hv = rb(siluf_(gs)) * us;
                    const uint32_t hd = sm + SM_H + (2 * v + (q >> 1)) * 128 + (q & 1) * 32 + g * 2, hb = pack_b(hv, hv);
                    sts16(hd, hb); sts16(hd + 64, hb);
                }
                proxy_fence();
                bar_sync(4, 128);
                TSL(15);
#pragma unroll 1
                for (int n = 0; n < 8; n += 2) {
                    const uint64_t a = dw + (chunk_off(16 + n) >> 4);
                    mbar_wait(bars + (B_FULL + 16 + n) * 8);
                    mbar_wait(bars + (B_FULL + 17 + n) * 8);
                    if (n == 6) TSL(24);
                    float d[4], e[4];
                    wg_fence();
                    wg_w0(d, a, dh); wg_w0(e, a + 512, dh); wg_w<1>(d, a + 128, dh + 16); wg_w<1>(e, a + 640, dh + 16);
                    wg_w<1>(d, a + 256, dh + 32); wg_w<1>(e, a + 768, dh + 32); wg_w<1>(d, a + 384, dh + 48); wg_w<1>(e, a + 896, dh + 48);
                    wg_commit();
                    wg_wait<0>();
                    touch(d); touch(e);
                    st_relaxed32(my_part + n * 8 * 56 * 16, (__float_as_uint((q & 2) ? d[2] : d[0]) & ~3u) | tag);
                    st_relaxed32(my_part + (n + 1) * 8 * 56 * 16, (__float_as_uint((q & 2) ? e[2] : e[0]) & ~3u) | tag);
                }
                TSL(16);
            } else {
                mbar_wait(bars + B_STG * 8);
            }
            if (v == 2 + rank) {
                const int t = (0xFFFF - (key & 0xFFFF)) & 2047;
                const int col = 4 * q + 2 * (lane >> 4) + ((lane >> 3) & 1), d = G * 16 + col;
                const float r = __uint_as_float((key & 0x80000000u) ? (key & 0x7FFF0000u) : (~key & 0xFFFF0000u));
                const float sg = rb(sigmoidf_(r));
                const float xn = blo(lds16(sm + SM_XRAW + 32 + col * 2));
                const float xv = blo(lds16(sm + SM_XRAW + col * 2));
                const uint4* src = reinterpret_cast<const uint4*>(p.sc->part) + c * 224 + lane;
                float s0 = 0, s1 = 0, s2 = 0, s3 = 0;
                {
                    uint4 pv[7];
                    int it = 0;
                    bool ok;
                    do {
                        uint32_t bad = 0;
#pragma unroll
                        for (int i = 0; i < 7; i++) pv[i] = ld_relaxed128(src + 32 * i);
#pragma unroll
                        for (int i = 0; i < 7; i++) bad |= (pv[i].x ^ tag) | (pv[i].y ^ tag) | (pv[i].z ^ tag) | (pv[i].w ^ tag);
                        ok = __all_sync(0xFFFFFFFFu, (bad & 3) == 0);
                    } while (!ok && ++it < SPIN_LIMIT);
#pragma unroll
                    for (int i = 0; i < 7; i++) {
                        s0 += __uint_as_float(pv[i].x); s1 += __uint_as_float(pv[i].y); s2 += __uint_as_float(pv[i].z); s3 += __uint_as_float(pv[i].w);
                    }
                }
                TSL(25);
                const bool u16 = lane & 16, u8 = lane & 8;
                const float y0 = (u16 ? s2 : s0) + __shfl_xor_sync(0xFFFFFFFFu, u16 ? s0 : s2, 16);
                const float y1 = (u16 ? s3 : s1) + __shfl_xor_sync(0xFFFFFFFFu, u16 ? s1 : s3, 16);
                float y = (u8 ? y1 : y0) + __shfl_xor_sync(0xFFFFFFFFu, u8 ? y0 : y1, 8);
                y += __shfl_xor_sync(0xFFFFFFFFu, y, 4);
                const float z = rb(xn + rb(rb(y) * sg));
                const float gt = rb(siluf_(z));
                mbar_wait(bars + B_FIX * 8);
                const float o = xv + rb(blo(lds16(sm + SM_FIX + col * 2)) * gt);
                if (!(lane & 4)) p.out[(size_t)t * 1024 + d] = __float2bfloat16(o);
                TSL(26); TG(29);
            }
        }
    }
    }
}

__device__ __align__(128) const uint32_t g_tab[5504] = {
0x2fff3000,0x2e7c2fd4,0x2fc92fd4,0xad72af5a,0x2ff82ffc,0x230e2c07,0x2faf2fbc,0x217ea934,0x2fed2ff4,0xad4da8d5,0x2f912fa0,0x2e5e2bb7,
0x2fdd2fe6,0xb000af46,0x2f6e2f80,0x2fdd2fc9,0x2ff42fff,0x2e1f2fc9,0x2e1f2e7c,0xa875ad72,0x2fbc2fdd,0x9fd92a4e,0x2d4d2dba,0x2cd825db,
0x2f5a2f91,0xaeb5ac07,0x2c5d2cd8,0x30002f30,0x2ed02f1a,0xaf80aff4,0x2aaa2bb7,0x2cb02f1a,0x2fdd2ffc,0x2dba2fbc,0x2a4e2c07,0x25dba934,
0x2f462fa0,0xa7652875,0x25152875,0x2f802d27,0x2e3f2ed0,0xafa0ad72,0xa17e1cb6,0x2e3f2fe6,0x2cd82d96,0xadfeafd4,0xa934a6a1,0xa44e29f1,
0x2fbc2ff8,0x2d4d2faf,0x9fd9230e,0x2cd8217e,0x2e992f46,0xaa4e2515,0xaa4ea765,0x2fd42f80,0x2cb02dba,0xafffae99,0xad72ac5d,0x27652dba,
0x28752b05,0xab5eaee9,0xaf1aae5e,0xae3fa934,0x2f912ff4,0x2cd82fa0,0xac07a8d5,0x2f302bb7,0x2dba2ed0,0xac5d1cb6,0xae99ad72,0x2dba2fe6,
0x29932c5d,0xafc9af6e,0xafe6af6e,0xaaaa25db,0xa17e244e,0xa30ead4d,0xafafaffc,0xaff8aee9,0x2f5a2fed,0x2c5d2f91,0xaeb5ad4d,0x30002e5e,
0x2cb02e3f,0xad72a17e,0xafffafa0,0x27652e3f,0x217e2993,0xaf02afe6,0xaf02afc9,0xaf1aaaaa,0xab05a5db,0x2814aa4e,0xac07adba,0xad4dafdd,
0x2f1a2fe6,0x2bb72f80,0xaff4af46,0x2f1a2fc9,0x2b052d96,0xae5ea6a1,0xaee9afd4,0xa93429f1,0xa5db244e,0xadbaaffc,0xaa4ead4d,0xafddaee9,
0xaddcabb7,0x2cb0a17e,0x2765a17e,0x1cb6ad00,0x2ed02fdd,0x2aaa2f6e,0xaf80b000,0x2cb02fdd,0x28752cd8,0xaf1aa934,0xab5eadfe,0xae3fa44e,
0xab05a17e,0xac07afaf,0x2814a30e,0xad4daff8,0xaf6eaddc,0x2eb52765,0x2eb52cb0,0x2dba1cb6,0x29932f5a,0xa7652e99,0x25152e99,0x2aaaad96,
0xafa0ab05,0xabb7afed,0xaff4acd8,0x28d52ffc,0xa814af02,0x2f912d27,0x9fd9ae1f,0xaee9ae3f,0x2fd42c32,0xaf5a1cb6,0x30002d72,0x2fd42515,
0x28752f46,0xa8d52e7c,0xa8d52c32,0x2e3fa993,0xafedac5d,0xa934b000,0xaf30af5a,0xa8142eb5,0x1648adfe,0x2e992e5e,0x2c87a814,0xa9f1affc,
0x2fe62e1f,0xafffa875,0x2ddc2ff4,0x2ed02e1f,0x26a12f30,0xa9f12e5e,0xad96244e,0x2fd41fd9,0xafffad27,0xa515aff4,0xac32aff4,0xaddc2b5e,
0x2875acb0,0x2d272f46,0x2fa02993,0x2875aed0,0x2ee92f6e,0xaf91ac87,0x1fd92e99,0x28143000,0x244e2f1a,0xab052e3f,0xaf91a875,0x2fbc2b5e,
0xafd4addc,0x1648afc9,0x1648ae7c,0xafdd9cb6,0x2c32aa4e,0x2aaa2fd4,0x2f802e99,0x2e7caa4e,0x2d002ffc,0xae1fae5e,0xad272814,0xabb72dfe,
0x1fd92f02,0xac072e1f,0xafedad27,0x2dfe2e3f,0xaf6eae7c,0x25dbaf80,0x2c5daaaa,0xaf6eac32,0x2ddca5db,0x25153000,0x2c323000,0x2fff26a1,
0x28d52fbc,0xabb7af91,0xaff4ab05,0xafa0244e,0x96482ee9,0xac872dfe,0xae99af30,0x29f12fbc,0xaed0af02,0x2993af1a,0x2f46217e,0xacb0af02,
0x2f1a1cb6,0xa30e2fc9,0xa30e2e7c,0x2e1f2ddc,0x9fd92eb5,0xa44eb000,0xae5eaf5a,0xaf30ac5d,0xa17e2ed0,0xad002ddc,0xabb7afff,0xa17e2fe6,
0xadfeaf6e,0x2c07ae99,0x2fed2c87,0x9fd9b000,0x2fd42814,0xa9f12f30,0xad962934,0x26a12fed,0xaaaa2d00,0x2765afa0,0xa515afa0,0xa993afaf,
0xa5152eb5,0xad722dba,0x9cb6af6e,0xac322eb5,0xad00afbc,0x2d27adfe,0x2e1f2f30,0x2bb7aee9,0x2ffc2b5e,0xacd82e3f,0xafeda875,0xab052f1a,
0xadba2993,0x2c87ae7c,0x2c87ac32,0x2a4eaf46,0xaddc2d96,0xafe62c5d,0xaed02c5d,0x2fffa9f1,0x2e1fad4d,0x2e3f2814,0x2f02ac07,0xad27ab05,
0xae5e2d00,0x9fd9af1a,0xaf302b5e,0xa44e2faf,0x2e99acb0,0xad962f80,0x2f5aaaaa,0x2e99aed0,0xae3f2d72,0xaff82c32,0xaff82515,0x2f021cb6,
0x2ee9ac87,0x2d4d29f1,0x2ffc9648,0xa44eae99,0xaf6e2b05,0x26a1afbc,0xafd4a44e,0xadba2f91,0x2fc9a8d5,0xaf462e3f,0x2f802875,0x2fe6a8d5,
0xae992d4d,0xb0002c07,0xaf6ea814,0x2c872b05,0x2f80ab5e,0x2c322bb7,0x2e7c2bb7,0x2aaaaff8,0xaff42765,0x2b5eafff,0xad27ad72,0xaff42cb0,
0x2fed1648,0xaffc2c5d,0x2b052eb5,0x2cd82a4e,0xaee92d27,0xaffc2bb7,0xad4dad00,0x244e2e1f,0x2fdda993,0x29f12cb0,0x29f12ed0,0x2eb5af46,
0xafe61648,0x2d72afdd,0x9cb6afd4,0xaed01648,0x2f022934,0xafa02814,0xa8d52fed,0xa30e2f30,0xaf302d00,0xafed2b5e,0xa814af1a,0xa9342faf,
0x3000a765,0x26a12d72,0xa5db2fff,0x3000acb0,0xaf46a6a1,0x2ed0af5a,0x2cb0af5a,0xa993ac87,0x2d272cd8,0xae3f9fd9,0xaf022d4d,0xae1f2fbc,
0xaf6e2cd8,0xafd42b05,0x26a1affc,0xadba2fed,0x2fe6a30e,0x1cb62e1f,0xad722f1a,0x2ed0a30e,0xae1faaaa,0x2fafae7c,0x2fafac32,0x28d5af80,
0x29342e99,0xac07a9f1,0xafbc1648,0xaffc2c87,0xafa02cb0,0xafaf2aaa,0x2d00af80,0xafa02ed0,0x2f911648,0xa44e2eb5,0xafbc2c5d,0x2b052a4e,
0xac87acd8,0x3000ad4d,0x2f6e1fd9,0x2e99afbc,0x9cb62faf,0xa515ad27,0xac32ad27,0xad72a30e,0xafc92c87,0xaf802a4e,0x2f46adba,0xafe62c87,
0x2f02244e,0xa8d52f30,0xafa01fd9,0xa30e2e5e,0xa934ae1f,0x2fbcabb7,0x2c072d00,0x2ffcad27,0xaa4e2fff,0x26a1aed0,0x26a1afe6,0x1648addc,
0xaf4629f1,0xac3225db,0xae7c25db,0x29931648,0xab5e2f91,0xafaf2e5e,0xad002fed,0x2f1aad4d,0x2ee9a875,0xaf302ff8,0x2dfea17e,0x2fbcaff4,
0x2c5dafc9,0xa9f12d72,0x2d96afff,0x2c5dae7c,0xaf022993,0xab5e2515,0xab5ea765,0xa30e2aaa,0xacd82fd4,0xaf302dba,0xaf912f6e,0x2c07a6a1,
0x2d969fd9,0xafdd2fed,0x25db2c07,0x2f5aadfe,0x2e7caff8,0xad722f02,0x2fffae3f,0x2fc9aff8,0xaeb52934,0xaa4e244e,0x9648acd8,0xac5d2dfe,
0xaddc2ff8,0xae7c2d00,0xafc92d00,0x9cb628d5,0x2bb72515,0xaff82f80,0xab5e2f46,0x2bb7a765,0x2fbcaf5a,0xaf302fdd,0x2dfea5db,0x2ee9ad96,
0xae5e28d5,0xa934230e,0x2b05af02,0xaee92fa0,0xaeb52fff,0xad962c32,0xad962515,0xac872ddc,0x276529f1,0xaf802eb5,0xaf462fdd,0xa51529f1,
0x2ff4adfe,0xaff82fed,0x217e2c07,0x28759fd9,0xadfe2875,0xa814217e,0x2e5eaff8,0xaffc2ff4,0xaf5a2fe6,0xac872aaa,0xa6a1a993,0xaf5a2fc9,
0x9cb62c87,0xae7c2d96,0xafc92d96,0xaddc2eb5,0x2f1aac07,0xafaf2f30,0xad002f91,0xab5e2cd8,0xad962814,0xa5db1fd9,0x2fddaf91,0xaf5a2ee9,
0xafc92faf,0xaaaa28d5,0x2993ae1f,0xafe62faf,0xa8d52ddc,0xad002c32,0xad002515,0xaff82fff,0x2d4da6a1,0xae5e2dba,0xafed2f6e,0xaf912fd4,
0xad272765,0xa30e1cb6,0x2fafaddc,0xad272cb0,0xaffc2f5a,0xa81425db,0x2e5eafdd,0xadfe2d96,0xac5d2ee9,0xaa4e2934,0x9648ab05,0xaeb52e5e,
0x2993230e,0xac322b5e,0xae7c2b5e,0xaf462f02,0xacb026a1,0x9cb61648,0x2ddcaa4e,0xa76526a1,0xaff42ee9,0xa17e1fd9,0x2ff8af91,0xa8752814,
0xadfe2fa0,0xa44e230e,0x2cd8af02,0xa93428d5,0x96482aaa,0xa5db2515,0xa5dba765,0xa9f12993,0x2f462f5a,0x2c322e99,0x2e7c2e99,0xa993ad96,
0x2f1a2f30,0xa875244e,0x2e3f2e5e,0x2b5e1fd9,0x2ee92f02,0xaf30ad27,0x2dfe2e1f,0x2fbc2e3f,0x2eb52ed0,0xaf6eafff,0x2dba2ddc,0x2eb52fe6,
0x28752993,0xa8d52515,0xa8d5a765,0x2e3f2aaa,0x244e26a1,0xaf91ad96,0xab05a9f1,0x2fbc2fd4,0x96481fd9,0xae99afed,0xac87ac07,0x29f12dfe,
0xa515a17e,0x9cb6abb7,0xad72ad00,0xac32a17e,0xac5dab05,0xaf5aacd8,0xb000afed,0x2eb52ffc,0xaddcad27,0xae7caff4,0xafc9aff4,0x9cb62b5e,
0xaf02ae7c,0x217eaaaa,0xaf1aaf80,0xaf02ac32,0xafbcaf6e,0x2f302c87,0xadfeae99,0xaee9b000,0xafedafa0,0xaf30aff4,0xa934abb7,0xa81428d5,
0xafd4afff,0x1648ac32,0x1648a515,0xafddaddc,0xaed0af6e,0x2f462c5d,0x299325db,0xacb0af6e,0xad00adfe,0x2e1f2fed,0x2d272c07,0x2bb79fd9,
0xadfeaf02,0xa814ae1f,0x2e5e2d27,0xaffcae3f,0xaa4eacb0,0x2e992993,0x2fd42f46,0xaa4eaed0,0x1cb6a5db,0x2e7c3000,0x2fc93000,0x2ddc26a1,
0x2b5e2814,0xa8752934,0x2e3f2f30,0x2f1a2fed,0x1648a814,0x2c879fd9,0x2e992f91,0xa9f1aee9,0x2c322875,0x2f802fa0,0x2aaa2d27,0x2e7c2875,
0x2f1a2ddc,0xa30e2c32,0xa30e2515,0x2e1f2fff,0x2ffc2fd4,0xafedad96,0xacd8a9f1,0xab0526a1,0x2e1f2c32,0x2ff42d72,0xa8751cb6,0x2e1f2515,
0x2ffc2f6e,0x28142e99,0xae5eac87,0x2dfe3000,0x2eb52fbc,0xaf5aab05,0xb000af91,0xac5d244e,0x29932d00,0xac32afa0,0xae7cafa0,0xaf46afaf,
0x2fe62fd4,0x2ddc3000,0xafffaf5a,0x2ed02fd4,0x2d002ee9,0xad271fd9,0xae1faf91,0xabb72814,0x9fd928d5,0xae5eaff4,0xa44eabb7,0xaf30afa0,
0xadbaaaaa,0x2c87a515,0x2c872765,0x2a4ea993,0x9cb62d96,0xacb02c5d,0xa7652c5d,0x2ddca9f1,0xaff8adfe,0xa30eafbc,0xafafaee9,0xa17e2f30,
0x244ead00,0x2dfe2f1a,0x2934ab5e,0xacd8afaf,0x2fdd2e7c,0xb000a993,0x2f6e2f46,0x2fdd2c32,0xae3f9cb6,0xaff8a765,0xaff8acb0,0x2f022ddc,
0xac07afdd,0x2dfeaa4e,0x1fd9adba,0xafeda5db,0x2f6e2934,0xa6a12ee9,0x2fd42e5e,0x2dbaab05,0x27652f1a,0xaaaaaff4,0xa9932bb7,0xa5152f1a,
0xafddadfe,0xadbaaee9,0xaa4eafbc,0xa5db2f30,0x2aaaab5e,0x2fc92bb7,0x2fe62bb7,0xa993aff8,0x2e3f2fc9,0xafa01cb6,0xa17e2ddc,0x2e3f2e7c,
0xae5e9648,0x2d4dac5d,0xaf91aeb5,0xafedaa4e,0xac07aff8,0x1fd9afaf,0x2dfea30e,0xafeda17e,0x2fdd2aaa,0x29f12fe6,0x29f12fc9,0x2eb5a993,
0xa5152dba,0xaddcae99,0xafffac5d,0xac322dba,0xaf02af30,0x2fa02c07,0x28d5acd8,0x230eaf91,0x2934ad00,0x2e5eab5e,0x2ee92f1a,0xab05afaf,
0x2dba2fc9,0xac5d2ddc,0xae991cb6,0x2dba2e7c,0xaf80a6a1,0x2765af5a,0xa515af5a,0xaf46ac87,0x217eae5e,0x230e2ffc,0x2faf2dfe,0x2ff82814,
0x2f6e244e,0x2fd42934,0xa6a12dfe,0x2dbaacd8,0xa5152e3f,0xafffa17e,0xaddcafa0,0xac322e3f,0xae1faf80,0x2fafa515,0x2faf2765,0x28d5af46,
0x2f9125db,0xaee92a4e,0xa8142dba,0x9fd92fdd,0x2f1a2e7c,0x2bb72f46,0xaff4a993,0x2f1a2c32,0xaf309648,0xacd8aeb5,0x2c07ac5d,0xaf91aa4e,
0x25dbae5e,0x2dba2dfe,0x2a4e2ffc,0x2fdd2814,0x2d722faf,0xae7cad27,0xafc9ad27,0xafffa30e,0x27652fdd,0xa9932f6e,0xaaaab000,0xa5152fdd,
0xaf02ae5e,0x28d5af91,0x2fa02d4d,0x230eafed,0x2f91217e,0xa8142faf,0xaee9230e,0x9fd92ff8,0xaa4e2d72,0x26a1afc9,0x26a1ae7c,0x1648afff,
0xaf8029f1,0xafc925db,0xafe625db,0x2f461648,0x2fa0a934,0x2bb72cd8,0x2ff4a44e,0xa8d5adfe,0xafbc2875,0x2934aff8,0xaffc217e,0xac072ff4,
0x2fd4a765,0xaf5a2ddc,0x30009cb6,0x2fd4acb0,0xaf02aaaa,0xab5eacb0,0xab5eaed0,0xa30e2f80,0x2e5e2c5d,0xab053000,0x29342f5a,0x2ee9aeb5,
0xad96ad4d,0x2fddacd8,0xa5dbafbc,0xaf5a1fd9,0x2cb02e1f,0xaddca875,0x1cb62ff4,0x27652e1f,0xa6a1af91,0x29f1afed,0x2d96ae5e,0xafd42d4d,
0x9cb62ff8,0xafe62d00,0xaed02d00,0x2d7228d5,0x2875afe6,0x2d272993,0x2fa0aaaa,0x2875afc9,0xac072f5a,0x2934afdd,0xaffc25db,0xafbc2d96,
0x2cd8af1a,0x2f91ae3f,0x2f302875,0xac07ab5e,0xaeb52d72,0xad96a765,0xad96acb0,0xac872fff,0x2fc9aa4e,0xa9932fd4,0x2aaa2e99,0x2fe6aa4e,
0xaff41fd9,0x2ff8acd8,0xa17eafbc,0xa875ad4d,0x2ffca875,0x2ee9a17e,0xa44e2ff8,0x2d4daff4,0xaf6ea515,0x25dbaf46,0x2c5daf80,0xaf6e2765,
0x2d722c87,0xafe62d96,0xaed02d96,0x9cb62eb5,0xa8d5aee9,0x2bb72b05,0x2ff4a934,0x2fa0ae5e,0x2d962c07,0x25db2d4d,0xafdd2b05,0x2f5aa814,
0xa765af02,0x2f46af1a,0x2f80217e,0x2515af02,0xa8d52fff,0xad00a765,0xad00acb0,0xaff82d72,0x2dfeaeb5,0xacd83000,0x244e2f5a,0x29342c5d,
0xa17e2fc9,0xad002fff,0xabb7ad72,0xa17e2e7c,0x2d4daf5a,0x2ee9a5db,0xa44e2fdd,0x2ffcad96,0xafd42c07,0x29f1af91,0x2d96af30,0xa6a1acd8,
0x2f46230e,0xafc92b5e,0xafe62b5e,0xaf802f02,0xae7c2eb5,0xafff2dba,0x2d72af6e,0xafc92eb5,0x2ff4a814,0x217e2d4d,0xaff82b05,0x28752c07,
0xad4dab5e,0x2fedae3f,0x2e5e2875,0x2f91af1a,0x96482f80,0xa5dbacb0,0xa5dbaed0,0xa9f1aaaa,0xad729648,0xa515a6a1,0xac32a6a1,0x9cb62a4e,
0xae1f2ffc,0xae3f2c07,0xaf022fbc,0x2d27a934,0x2cd8230e,0xaffc2fa0,0x2b0528d5,0x2fedaf02,0x2e99afe6,0xad962f46,0x2f5aaf80,0x2e99afc9,
0x230eaddc,0x2d27aed0,0x2d27afe6,0xafaf2fff,0xafbc2c87,0x1fd9a9f1,0xad4d1648,0xacd82e99,0xaa4e2f30,0xac5d2814,0xaeb52fed,0x96482934,
0x2ed0a8d5,0xaf802e3f,0x2aaa2875,0x2cb0a8d5,0x2e99affc,0x3000afbc,0x2f6eac07,0xac872934,0xa993a8d5,0x2ed0afaf,0x2cb0afaf,0xaf462e1f,
0xaff42ed0,0x2b5ead72,0xad271cb6,0xaff42fe6,0xa44e2dba,0x9fd9a6a1,0xaf302fd4,0xae5e2f6e,0x2fbcad27,0x2d4dabb7,0x9fd92d00,0x2cd8ae1f,
0x2c87af80,0x2f5aae7c,0x2f5aac32,0x26a1aaaa,0xacb01648,0x2fffafdd,0x2d72afd4,0xa7651648,0xafaf2f91,0x2f1aafbc,0xab5ea44e,0xad002b05,
0x2b05230e,0xa44e28d5,0xafbc2fa0,0x2f91af02,0x3000aed0,0x26a19cb6,0xa5db2d72,0x3000afe6,0x2aaaaeb5,0x2c32a9f1,0x2e7ca9f1,0x2f80afdd,
0xad27244e,0x2e3fad4d,0x2f02affc,0x2e1faee9,0xaa4e2e5e,0xaeb52f30,0xac5d1fd9,0x9648244e,0x2cb0a30e,0xad722e1f,0xafff2f1a,0x2765a30e,
0x2ff8af46,0xabb72cb0,0xabb72ed0,0x2b5ea993,0x2b05ae99,0xa81429f1,0x2c079648,0x2d4dac87,0xafa02fe6,0xafaf2f80,0x2d00af46,0xafa02fc9,
0xa9342dba,0xafed2fd4,0xa814a6a1,0xaf302f6e,0x2c87a44e,0xb0002ffc,0xaf6e2d4d,0xae992ee9,0x2fffaf02,0xafe62ff8,0xaed02ff8,0xaddc2e3f,
0xaed02c87,0xaaaa2a4e,0x2f80adba,0xacb02c87,0xafaf2fed,0xab5e2b05,0x2f1aaffc,0xad002cd8,0xab052e1f,0xac072bb7,0x2814ad00,0xad4d2d27,
0x29f11cb6,0xac5d2c32,0xac5d2515,0xad962d72,0x2d722d96,0x25152c5d,0x2c322c5d,0x1cb6a9f1,0x2d272d4d,0xad00a814,0x2bb72c07,0x2e1f2b05,
0x2cd82d00,0xaffcaf1a,0x2b052b5e,0x2fed2faf,0x2c872cb0,0xadbaaf80,0x2a4e2aaa,0x2c872ed0,0xae3faddc,0xaff8aed0,0xaff8afe6,0x2f022fff,
0xaee9ae99,0xad4daf6e,0xaffcb000,0x244e2c87,0xaf6eaf30,0x26a1a814,0xafd4afed,0xadbaa934,0xafc9afa0,0x2f462d00,0xaf80afaf,0xafe6afa0,
0xac87ad4d,0x9648ac07,0x29f12814,0xae99ab05,0xa993ab5e,0x2ed02bb7,0x2cb02bb7,0xaf46aff8,0xa30ea765,0x2f1a2fff,0x2e1f2d72,0xa30eacb0,
0x244e1648,0x1fd92c5d,0x2f302eb5,0x2e5e2a4e,0x2ee92e1f,0x2ffc2f02,0x2d4d2e3f,0xa44ead27,0x2fdd2f80,0x29f12e7c,0x29f12c32,0x2eb52aaa,
0x2fe63000,0xad72a5db,0x1cb626a1,0x2ed03000,0x2f022f91,0xafa0afbc,0xa8d5a44e,0xa30e2b05,0x2b052d00,0xa44e2b5e,0xafbcaf1a,0x2f912faf,
0x16482765,0xafd4ad72,0xafddafff,0x16482cb0,0xaaaaa6a1,0xac32af5a,0xae7caf5a,0xaf80ac87,0xae1facd8,0x2d001fd9,0xabb7ad4d,0xad27afbc,
0xaf6eae5e,0xafd4af30,0x26a19fd9,0xadbaa44e,0xafe6aff4,0x9cb6ad27,0x2d722b5e,0xaed0aff4,0xae1faf46,0x2faf2cb0,0x2faf2ed0,0x28d5a993,
0xa934ac87,0x2c072f6e,0x2fbc3000,0x2ffc2e99,0xa8d5acb0,0x2875aaaa,0x2e3f2f80,0xa8d5aed0,0x29341648,0x2fed2eb5,0x28142c5d,0x2f302a4e,
0x2e992cd8,0x16482d4d,0xa9f19fd9,0x2c872fbc,0x2fff2faf,0xafe6ad27,0xaed0ad27,0xaddca30e,0x2fc92e99,0x2f802f5a,0xaf46ad96,0x2fe62e99,
0x2f022fed,0xa8d52b05,0xafa0affc,0xa30e2cd8,0x29342d27,0xafbcaf02,0xac07ae3f,0xaffcae1f,0xaa4e9cb6,0x26a1ac32,0x26a1a515,0x1648ad72,
0xaaaa29f1,0xaed025db,0xacb025db,0x2f801648,0xaf1aaf91,0x2875ae5e,0xae3fafed,0xab5e2d4d,0x2c07a875,0x2b052ff8,0x2d4da17e,0xa814aff4,
0x2eb52fc9,0xaf6ead72,0x2dba2fff,0x2eb52e7c,0xaf02af80,0xab5eafe6,0xab5eafc9,0xa30e2f46,0x2cd8a6a1,0x2f302d96,0x2f9129f1,0xac07afd4,
0x2d962ffc,0xafdda44e,0x25db2ee9,0x2f5a2d4d,0xae7ca17e,0x2d72abb7,0xafffad00,0xafc9a17e,0x2c5da934,0x2f5aa44e,0x30002cd8,0xaeb5adfe,
0x2d722ff8,0xacb02d00,0xa7652d00,0x2fff28d5,0xaf02a515,0x217eaf80,0xaf1aaf46,0xaf022765,0xa814af5a,0x2b052fdd,0x2d4da5db,0x2c07ad96,
0x2e5e2fa0,0x29342ff4,0xab052bb7,0x2ee9a8d5,0xaeb59cb6,0xad96aed0,0xad96afe6,0xac872d72,0xa765af6e,0x2f802c5d,0x2f4625db,0x2515af6e,
0x2ff42d4d,0xaff8a44e,0x217e2ee9,0x28752ffc,0xad4d2875,0xafbc217e,0xacd8aff8,0x1fd92ff4,0xaa4eafe6,0x2e99aaaa,0x2fd42993,0xaa4eafc9,
0x2fff2c87,0xacb02d96,0xa7652d96,0x2d722eb5,0xab5e2c07,0x2875af30,0xae3faf91,0xaf1aacd8,0xad96afbc,0xa5dbaffc,0x2fdd2934,0xaf5aac07,
0x2fc92875,0x2aaa2fa0,0xa9932d27,0x2fe62875,0xa8d52d72,0xad00aed0,0xad00afe6,0xaff89cb6,0xad4dafd4,0x2e5e2d96,0x2fed29f1,0x2f91a6a1,
0x2e1fa765,0x2ff49cb6,0xa8752ddc,0x2e1facb0,0x1fd92f5a,0xafbc25db,0xacd8afdd,0xad4d2d96,0xaeb5aee9,0x2f5aa934,0x30002b05,0x2c5dae5e,
0x2f80230e,0xaed02b5e,0xacb02b5e,0xaaaa2f02,0x2cb02fd4,0x1cb63000,0xaddcaf5a,0x27652fd4,0xaff4ac07,0xa17eaffc,0x2ff82934,0xa875afbc,
0x2dfea8d5,0x244e2ff4,0xacd82bb7,0x29342fa0,0x96482f46,0xa5dbafe6,0xa5dbafc9,0xa9f1af80,0xafff9648,0xae7ca6a1,0xafc9a6a1,0x2d722a4e,
0x2ff81fd9,0x230e2ee9,0x2faf2814,0x217eaf91,0xafeda30e,0x2d4dafa0,0xaf91a8d5,0xae5e2f02,0x2fdd2515,0xb0002aaa,0x2f6e2993,0x2fdda765,
0x230eafff,0x2d27afc9,0x2d27ae7c,0xafaf2d72,0xa8142fdd,0xaffc2a4e,0xadfe2dba,0x2e5e25db,0x2a4eaf91,0x2c5d2c07,0x2eb5acd8,0x1648af30,
0xac322f1a,0x2993aff4,0xaf462bb7,0xae7c2f1a,0x2fdd1fd9,0x2dba2814,0x2a4e2ee9,0x25dbaf91,0xaf46a8d5,0x2765afaf,0xa515afaf,0xaf802e1f,
0x2e3f2c32,0xafa02ddc,0xa17e2fff,0x2e3f2515,0xacd8adba,0x2dfe26a1,0x2934afd4,0x244eaf6e,0xa8142ff8,0xadfe2faf,0xaffc230e,0x2e5e217e,
0x2c87af46,0x2f5aa515,0x2f5a2765,0x26a1af80,0xae7c2dba,0x9cb6ae99,0xaddcac5d,0xafc92dba,0x2fafab05,0xaf1a2ee9,0x2b5e2e5e,0x2d002934,
0xaf91a30e,0xacd8a8d5,0x2c07afa0,0xaf302f02,0x2dba2c32,0xac5d2fff,0xae992ddc,0x2dba2515,0xa993aeb5,0x2fc9a9f1,0x2fe6a9f1,0x2aaaafdd,
0xa17e2fed,0xa30eadfe,0xafaf9fd9,0xaff82c07,0x2a4eafed,0x2eb5af91,0x2c5d2d4d,0x1648ae5e,0xae7c2e3f,0xaddca17e,0x9cb6afa0,0xafc92e3f,
0x2ff8a993,0xabb72fe6,0xabb72fc9,0x2b5e2aaa,0xaf30a5db,0x2fbcaa4e,0x2ee9adba,0x2dfeafdd,0x2f1a2515,0x2bb72993,0xaff42aaa,0x2f1aa765,
0xab05adba,0x2e5eafd4,0x2ee926a1,0x2934af6e,0xa5db2fed,0xadba9fd9,0xaa4eadfe,0xafdd2c07,0x2ddcaf02,0xacb02ff8,0xa7652ff8,0x9cb62e3f,
0xac322fdd,0xaf462f6e,0x2993b000,0xae7c2fdd,0x2fafacd8,0x2b5e2934,0xaf1a2dfe,0x2d00244e,0xaf30a17e,0x2ee9afaf,0x2fbca30e,0x2dfeaff8,
0x29f12ddc,0xac5da765,0xac5dacb0,0xad969cb6,0xa993aa4e,0x2765ac87,0xa515ac87,0xaaaa2dba,0xafa02f30,0xabb7244e,0xaff42e5e,0x28d51fd9,
0x28142bb7,0xaf912e1f,0x1fd92d27,0x2ee9ad00,0x2fd4aed0,0xaf5a2fff,0x3000addc,0x2fd4afe6,0x2fafaf46,0x2fa0ae7c,0x2fa0ac32,0xad002993,
0xa44eac5d,0x2f91b000,0x2b05af5a,0xafbc2eb5,0xb0002dfe,0x2c87ae5e,0xae992814,0xaf6e2ffc,0xa5152e1f,0x9cb6a875,0xad722ff4,0xac322e1f,
0x26a12b05,0xa9f12cd8,0xad962fed,0x2fd4affc,0x2fffae1f,0x2515230e,0x2c32230e,0x2ddcaf1a,0x2875ae7c,0x2d27aaaa,0x2fa0af80,0x2875ac32,
0xaee929f1,0x2f91ae99,0x9fd9ac87,0xa8149648,0xafed2f1a,0xaf302e3f,0xa934a875,0xa8142b5e,0xa6a12ddc,0xb0002fc9,0xb0002e7c,0x25db1cb6,
0x2ed0aa4e,0xaf462fd4,0xa9932e99,0x2cb0aa4e,0x2e3faffc,0xad272e5e,0x2e1fa814,0x2f02adfe,0x9fd9abb7,0x2c07ad27,0x2fedae1f,0xadfe2d00,
0xaf6e2cb0,0x25dba993,0x2c5daf46,0xaf6e2ed0,0xaddc2fdd,0xa5159648,0xac329648,0xafff2fd4,0x28d52814,0xabb72934,0xaff42f30,0xafa02fed,
0x3000aee9,0x2e99adfe,0xac872f30,0x2f6eafbc,0x2c32af02,0x2f80af1a,0x2aaa217e,0x2e7caf02,0xab5e9cb6,0x2ff4afc9,0x2ff4ae7c,0x2d27addc,
0xaffc2eb5,0x2fedb000,0x2cd8af5a,0x2b05ac5d,0xa17e2c32,0xad002d72,0xabb71cb6,0xa17e2515,0x2dfea9f1,0xac072c87,0xafed2e99,0x1fd91648,
0x2fd4afbc,0xa9f12b05,0xad962f91,0x26a1a44e,0x2aaaae3f,0xa76528d5,0x251528d5,0x2993a875,0xafe62eb5,0xaddc2dba,0x2fffaf6e,0xaed02eb5,
0xae3f2fbc,0xae1f2dfe,0x2d27af30,0xaf022ee9,0x9fd92b5e,0xae5e2e3f,0xa44ea875,0xaf302f1a,0x2d96a993,0xae992e7c,0xae992c32,0xaf5a2f46,
0x299329f1,0xa76525db,0x251525db,0x2aaa1648,0x28d52934,0xaf02acd8,0x230e244e,0x2fa02dfe,0x28142875,0xaf91aff8,0x1fd9217e,0x2ee92ff4,
0x26a12765,0xaa4eaddc,0x16481cb6,0x26a12cb0,0xaf02af46,0xab5eae7c,0xab5eac32,0xa30e2993,0xae5eaeb5,0x2b059648,0xa934aa4e,0xaee9ac5d,
0xad96adfe,0x2fdd2e5e,0xa5dba814,0xaf5aaffc,0xacb0ad27,0x2ddc2faf,0x9cb6a30e,0xa765ad27,0x2fd42f91,0x2f6e2fed,0x2dba2e5e,0xa6a1ad4d,
0x2fff2ff8,0x25152d00,0x2c322d00,0x2ddc28d5,0x2faf2fe6,0xae1fa993,0x28d52aaa,0x2faf2fc9,0x2ee92f5a,0xaf91afdd,0x1fd925db,0x28142d96,
0xacd8ab5e,0xaf91ad00,0xaf30afaf,0x2c072f1a,0xaeb5addc,0xad96afc9,0xad96ae7c,0xac879cb6,0xafc9af5a,0x2993a6a1,0xaaaaac87,0xafe6af5a,
0xaff4affc,0x2ff82e5e,0xa17ea814,0xa875adfe,0x9fd9a875,0x2c07a17e,0x2fed2ff8,0xadfeaff4,0x29f12515,0x2fdd2f46,0x2eb52f80,0x29f1a765,
0x2ddc2c87,0x25152d96,0x2c322d96,0x2fff2eb5,0x2fa02ee9,0xaf02ab05,0x230e2934,0x28d52e5e,0x2d962ee9,0x25db2dfe,0xafddaf30,0x2f5a2fbc,
0x27652bb7,0xaf46ab5e,0xaf80aff8,0xa5152bb7,0xa8d59cb6,0xad00afc9,0xad00ae7c,0xaff8addc,0xadfeac5d,0x2cd89648,0xa44eaa4e,0xa934aeb5,
0xaff8afc9,0xae3fafff,0x2f022d72,0xaff8ae7c,0xadfeaf5a,0x2c07a5db,0x2fed2fdd,0x9fd9ad96,0xa6a1ac07,0x2f6e2f91,0x2dba2f30,0x2fd42cd8,
0x2aaa230e,0xa7652b5e,0x25152b5e,0x29932f02,0x2e7c2c5d,0x2fff2d96,0xad72a9f1,0x2fc92c5d,0x2ff42fbc,0x217e2dfe,0xaff8af30,0x28752ee9,
0x2d4d2f1a,0xafedad00,0xae5eafaf,0xaf91ab5e,0x96482993,0xa5dbae7c,0xa5dbac32,0xa9f1af46,0xaddc9648,0xafe6a6a1,0xaed0a6a1,0x2fff2a4e,
0xad27affc,0x2d00ac07,0xabb7afbc,0xae1f2934,0x2e5e230e,0x1fd92fa0,0x2f3028d5,0x244eaf02,0x2c872fe6,0xadbaaf46,0x2a4e2f80,0x2c872fc9,
0x230ead72,0x2d27ac32,0x2d27a515,0xafaf9cb6,0x2fbc2e99,0x9fd92f6e,0x2d4d3000,0x2cd8ac87,0xaa4e2b05,0xac5dafbc,0xaeb5a44e,0x96482f91,
0xaed0afa0,0x2f802d00,0xaaaaafaf,0xacb0afa0,0x2c872ffc,0x16482fbc,0xa9f12c07,0x2e99a934,0xaf80a8d5,0xac32afaf,0xae7cafaf,0xaaaa2e1f,
0xa30eaed0,0x2f1a2d72,0x2e1f9cb6,0xa30eafe6,0x2fed2dba,0xaffca6a1,0x2b052fd4,0x2cd82f6e,0xafbcae1f,0xad4daf02,0x1fd9ae3f,0xacd82d27,
0x2c87a993,0x2f5a2cb0,0x2f5a2ed0,0x26a1af46,0x2cb03000,0xafffa5db,0xad7226a1,0x27653000,0xafafa934,0x2f1aa814,0xab5eafed,0xad00af30,
0x2f30230e,0x2fed28d5,0x28142fa0,0x2934af02,0x16482ed0,0xafd41cb6,0xafddad72,0x16482fe6,0xaf46aeb5,0x2ed0a9f1,0x2cb0a9f1,0xa993afdd,
0x2e1fa44e,0xad002d4d,0x2bb72ffc,0x2d272ee9,0xaa4e2cd8,0xaeb52b05,0xac5daffc,0x96482fed,0xacb0aff4,0x2d72ad27,0x2fff2b5e,0xa765aff4,
0x2ff82aaa,0xabb72e7c,0xabb72c32,0x2b5e2f80,0xab052c87,0x2814af6e,0xac07b000,0xad4dae99,0xa8d5afe6,0x2875af80,0x2e3f2f46,0xa8d5afc9,
0x2f912dba,0xa44e2fd4,0xafbca6a1,0x2b052f6e,0xae99244e,0x9648affc,0x29f1ad4d,0xac87aee9,0x1cb6af02,0x25152ff8,0x2c322ff8,0x2d722e3f,
0x2ed02e99,0x2aaa2f5a,0xaf80ad96,0x2cb02e99,0xafafa44e,0xab5eaf30,0x2f1a9fd9,0xad00ae5e,0x2b05ad27,0x2c072f02,0xa8142e3f,0x2d4d2e1f,
0x29f12fff,0xac5daed0,0xac5dafe6,0xad96addc,0xaf46aa4e,0xac32ac87,0xae7cac87,0x29932dba,0x2f1a2b05,0xa8752fed,0x2e3f2cd8,0x2b5eaffc,
0xaee9abb7,0x2f30ae1f,0xadfead27,0xafbc2d00,0x2eb52c32,0xaf6e1cb6,0x2dba2d72,0x2eb52515,0x2fafa993,0x2fa0a515,0x2fa02765,0xad00aaaa,
0xafed26a1,0xa934ad96,0xaf30a9f1,0xa8142fd4,0x30009fd9,0xac872fed,0x2e992c07,0x2f6eadfe,0xafe6a17e,0x2fffabb7,0xaddcad00,0xaed0a17e,
0xac5d2f30,0xaf5a2e5e,0xb000244e,0x2eb51fd9,0x2ddcae1f,0x2e7c230e,0x2fc9230e,0x1cb6af1a,0xaf022cb0,0x217eaf46,0xaf1aa993,0xaf022ed0,
0x2fbca9f1,0xaf302e99,0x2dfe2c87,0x2ee91648,0xa44eafa0,0x2b05aff4,0x2f91abb7,0xafbc28d5,0xa6a12fff,0xb0002c32,0xb0002515,0x25db2ddc,
0x2c32af6e,0x2aaa2c5d,0x2f8025db,0x2e7caf6e,0xae3f2dfe,0x2d27afed,0xae1fac07,0xaf021fd9,0x2dfe2bb7,0x28142d27,0xae5e2e1f,0x2ffcad00,
0xaa4eae7c,0x2e99af80,0x2fd4aaaa,0xaa4eac32,0x9cb62fdd,0xae7c9648,0xafc99648,0xaddc2fd4,0x2b5eafbc,0xa8752f91,0x2e3f2b05,0x2f1aa44e,
0xb0002814,0xae991fd9,0x2c87af91,0xaf6e2ee9,0x2ed02875,0xa9932fa0,0xaf462d27,0x2cb02875,0xab5eaddc,0x2ff4ac32,0x2ff4a515,0x2d27afff,
0x9fd92fd4,0xa44ead96,0xae5ea9f1,0xaf3026a1,0x2e1faed0,0x2ff4addc,0xa8752fff,0x2e1fafe6,0xaffc29f1,0xa814ac87,0x2e5eae99,0xadfe9648,
0x2eb52814,0xaf5a2f30,0xb0002934,0xac5d2fed,0xa993ae3f,0x2c3228d5,0x2e7c28d5,0x2f46a875,0xa5152fd4,0xad723000,0x9cb6af5a,0xac322fd4,
0x2e3faee9,0x2e1f9fd9,0xad272f91,0x2f02a814,0xaffc28d5,0x2cd8aff4,0x2fedabb7,0x2b05afa0,0x2d962aaa,0xae992515,0xae99a765,0xaf5a2993,
0x1cb6adba,0x2cb0aeb5,0x2765aeb5,0xaddc2f6e,0xaff82d4d,0xa30ea814,0xafaf2c07,0xa17e2b05,0xa44e2e3f,0xadfe2b5e,0xa9342f1a,0x2cd8a875,
0x2fddacb0,0xb0002f80,0x2f6eaaaa,0x2fddaed0,0x2d001cb6,0x217e2765,0x217e2cb0,0x2bb7addc,0x2ee9afdd,0x2d4daa4e,0x2ffcadba,0xa44ea5db,
0xa9f1a934,0x2fd4aee9,0x26a1ae5e,0xad962b05,0xafc92f1a,0x2f46aff4,0xaf802bb7,0xafe62f1a,0xafdd2d4d,0xadba2c07,0xaa4ea814,0xa5db2b05,
0xaaaa2f1a,0xafc92f02,0xafe62f02,0x2993a17e,0x2e3fa765,0xafa02fff,0xa17e2d72,0x2e3facb0,0x2e5eb000,0xad4d2eb5,0x2f91ac5d,0x2fedaf5a,
0x2ee9aff8,0x2ffcafaf,0x2d4da30e,0xa44ea17e,0xa5dbaaaa,0x2f6eafe6,0x2f6eafc9,0xac5d2993,0xafe62dba,0x2d72ae99,0x9cb6ac5d,0xaed02dba,
0xabb72f30,0x28d5ac07,0xafa02cd8,0xaff42f91,0xa9342e3f,0xae5e2f1a,0xaee92b5e,0x2b05a875,0x2dbaa765,0xac5d2d72,0xae992fff,0x2dbaacb0,
0x2f80afd4,0xa7652a4e,0x25152a4e,0x2f46ae99,0x217eacd8,0x230e1fd9,0x2fafad4d,0x2ff8afbc,0xa9f1a44e,0x26a1a934,0x2fd4adfe,0xad962cd8,
0xafe62e3f,0x9cb6a17e,0x2d72afa0,0xaed02e3f,0xad272f80,0xa8752515,0xa875a765,0xafa02f46,0x293425db,0xac072a4e,0xafbc2dba,0xaffc2fdd,
0x2f1aacb0,0x2bb7aaaa,0xaff42f80,0x2f1aaed0,0x2f30b000,0x2cd8ac5d,0xac072eb5,0x2f91af5a,0x25dbacd8,0x2dbaad4d,0x2a4e1fd9,0x2fddafbc,
0xad722875,0x2e7cae1f,0x2fc9ae1f,0x2fffaff4,0xafc92fdd,0xaf802f6e,0x2f46b000,0xafe62fdd,0xabb72e5e,0xafa02f91,0x28d5ad4d,0xaff42fed,
0x2934217e,0xafbc2faf,0xac07230e,0xaffc2ff8,0x2f5aad72,0xafd42fc9,0xafd42e7c,0xb0002fff,0x9cb69648,0xacb0a6a1,0xa765a6a1,0x2ddc2a4e,
0xa17e9fd9,0xaff4aee9,0xa875a814,0x2ff82f91,0xa44ea30e,0xadfeafa0,0xa934a8d5,0x2cd82f02,0xa5dba515,0x9648aaaa,0xa9f1a993,0xa5db2765,
0xa30e9cb6,0xad27a765,0xad27acb0,0x2faf2ddc,0xa814a5db,0xaffcaf5a,0xadfead96,0x2e5e2fdd,0xaa4ea934,0xac5daee9,0xaeb5ae5e,0x96482b05,
0xac32ab5e,0x2993a30e,0xaf46af02,0xae7cab5e,0xa5db9fd9,0xad96a814,0xaf5aaee9,0x2fdd2f91,0xaaaaa8d5,0xafc9afaf,0xafe6afaf,0x29932e1f,
0xad00ac32,0xa8d5addc,0xaff8afff,0xad00a515,0xae5eadba,0x2d4d26a1,0xaf91afd4,0xafedaf6e,0xa814a17e,0xadfea875,0xaffcaff4,0x2e5e2ff8,
0xac87aaaa,0xaf5aafe6,0xaf5aafc9,0xa6a12993,0xae7cad96,0x9cb6ac87,0xaddcaeb5,0xafc9ad96,0xafafaf30,0x2f1a2c07,0xab5eacd8,0xad00af91,
0xa934a30e,0xae5ea8d5,0xaee9afa0,0x2b052f02,0xad96ac32,0xaeb5afff,0xac87addc,0xad96a515,0xaf80aeb5,0x2765a9f1,0xa515a9f1,0xaf46afdd,
0xaff8afed,0x2ff42dfe,0x28751fd9,0x217eac07,0xaa4ea44e,0xaeb5a934,0xac5dadfe,0x96482cd8,0xae7cad00,0xaddcaff8,0x9cb6a8d5,0xafc9ad00,
0xaff8af80,0x2bb7a515,0x2bb72765,0xab5eaf46,0xaf30afdd,0x2fbc2f5a,0x2ee92d96,0x2dfe25db,0xab5ea515,0xaf02a993,0xa30eaaaa,0xab5e2765,
0xaf30adba,0xacd8afd4,0x2c0726a1,0xaf91af6e,0xafddafed,0x2d961fd9,0x2f5a2dfe,0x25dbac07,0xad72af02,0x2e7c2ff8,0x2fc92ff8,0x2fff2e3f,
0xac32a5db,0xaf46a9f1,0x29939648,0xae7ca5db,0xafafae5e,0xab5eaf91,0x2f1a2d4d,0xad00afed,0xaf30aff8,0x2ee92875,0x2fbc2ff4,0x2dfe217e,
0xa9f1ad72,0x2c5d2fc9,0x2c5d2e7c,0x2d962fff,0xaf80aa4e,0xafc9ac87,0xafe6ac87,0x2f462dba,0xa8d5af30,0x2f02a44e,0xa30eae5e,0xafa09fd9,
0x2fbc2bb7,0xa9342e1f,0x2ffc2d27,0x2c07ad00,0x26a12ed0,0xaa4eafff,0x16482ddc,0x26a12fe6,0xafafaaaa,0xafa0acb0,0xafa0aed0,0x2d002f80,
0xa44eaeb5,0x2f919648,0x2b05aa4e,0xafbcac5d,0x30002d4d,0xac872cd8,0x2e992fbc,0x2f6e9fd9,0xa5152d27,0x9cb6afaf,0xad72230e,0xac322d27,
0xafd4ab05,0xaf6eacd8,0xadbaafed,0x26a12ffc,0x1cb6ae1f,0x2fe6230e,0x2ed0230e,0xad72af1a,0x2faf2e7c,0xae1f2aaa,0x28d52f80,0x2faf2c32,
0xac0729f1,0x2934ae99,0xaffcac87,0xafbc9648,0xafedab5e,0xaf30ad00,0xa934afaf,0xa8142f1a,0x26a1ad72,0x30002765,0x30002cb0,0xa5dbafff,
0x2ed02f5a,0xaf4626a1,0xa9932c87,0x2cb02f5a,0xae3f1fd9,0x2d27acd8,0xae1fafbc,0xaf02ad4d,0xaffcabb7,0xaee9ad27,0x244eae1f,0xad4d2d00,
0x29f1acb0,0x2fdd2993,0x2eb52f46,0x29f1aed0,0x2d722fdd,0xafe69648,0xaed09648,0x9cb62fd4,0xafa0a814,0x2f02a934,0xa30eaf30,0xa8d5afed,
0xb000ac07,0xae99ad4d,0x2c87ab05,0xaf6e2814,0x2c32abb7,0x2f802b5e,0x2aaa2ff8,0x2e7cabb7,0x2b5e2fff,0xaff4a765,0xaff4acb0,0xad272d72,
0xaffcac5d,0x2fed9648,0x2cd8aa4e,0x2b05aeb5,0xaff8ac32,0xae3fad72,0x2f029cb6,0xaff8a515,0x2d4da9f1,0x2ee92c87,0xa44e2e99,0x2ffc1648,
0x26a12fbc,0xaf6eab05,0xadbaaf91,0xafd4244e,0xaf46ae3f,0x2fc928d5,0x2fe628d5,0x2f80a875,0xafe6ac5d,0xaddcad96,0x2fff29f1,0xaed0ac5d,
0x2e3fa814,0x2e1f2d4d,0xad272b05,0x2f022c07,0x9fd92f1a,0xae5ead00,0xa44eafaf,0xaf30ab5e,0xad96af80,0x2e992cb0,0x2e992ed0,0x2f5a2aaa,
0xad72adba,0xa515aeb5,0xac32aeb5,0x9cb62f6e,0x2d272dfe,0xad002fbc,0x2bb72ee9,0x2e1faf30,0xacd8ae3f,0x2ffcab5e,0xab05af1a,0xafed2875,
0x2c872e7c,0xadbaa993,0x2a4e2f46,0x2c872c32,0xad00addc,0xa17eaed0,0xa17eafe6,0xabb72fff,0x2c072e99,0xadfe2f6e,0x9fd93000,0x2fedac87,
0xa9f1af30,0x2fd4a814,0x26a1afed,0xad96a934,0x27652fa0,0xaaaaad00,0xa9932faf,0xa5152fa0,0xac87adfe,0x9648aee9,0x29f1afbc,0xae992f30,
0x29932f1a,0xaed02f02,0xacb02f02,0x2f46a17e,0xa30eafc9,0x2f1a9cb6,0x2e1faddc,0xa30eae7c,0xa44e3000,0x9fd9aeb5,0xaf302c5d,0xae5e2f5a,
0xac07ae1f,0x1fd9af02,0x2dfeae3f,0xafed2d27,0x25db2f80,0xaf6e2e7c,0xaf6e2c32,0x2c5d2aaa,0x2515b000,0x2ddc25db,0x2fffa6a1,0x2c32b000,
0xabb72f91,0x28d5afbc,0xafa0a44e,0xaff42b05,0xab05ae3f,0x244eaf1a,0x2fbcab5e,0xaf912875,0x16482fc9,0xafd42ddc,0xafdd1cb6,0x16482e7c,
0x2aaaafd4,0x2c322a4e,0x2e7c2a4e,0x2f80ae99,0xae1f2e5e,0x2d00affc,0xabb7adfe,0xad27a814,0xa9f1ae5e,0x26a1af30,0x2fd49fd9,0xad96a44e,
0xa5152ff4,0xafff2d27,0xaddcab5e,0xac322ff4,0x2d27af46,0x28752cb0,0x28752ed0,0x2fa0a993,0xaf912c87,0x2ee9af6e,0x2814b000,0x1fd9ae99,
0xa8d5ae7c,0x2875af46,0x2e3f2993,0xa8d5ac32,0xa9343000,0xafed2c5d,0xa814aeb5,0xaf302f5a,0x2e99ae5e,0x16482dfe,0xa9f12ffc,0x2c872814,
0xafff2875,0x2fe6ae1f,0x2ed0ae1f,0x2ddcaff4,0xa765ae99,0x2993af5a,0x2aaa2d96,0x2515ae99,0xabb72fed,0xafa02b05,0x28d5affc,0xaff42cd8,
0x2f91ad27,0xa8142f02,0xaee92e3f,0x9fd92e1f,0xaf5a9cb6,0x2fd4ac32,0x2fd4a515,0x3000ad72,0x2aaaaf6e,0x2ed0afdd,0x2cb0afdd,0xaf803000,
0xaf1a2934,0x2875acd8,0xae3f244e,0xab5e2dfe,0xac072faf,0xab05217e,0xad4d2ff8,0x2814230e,0x2eb5a765,0xaf6e2ddc,0x2dba9cb6,0x2eb5acb0,
0x2bb7af80,0x2f1aafe6,0x2f1aafc9,0xaff42f46,0xae5e26a1,0x2b05ad96,0xa934a9f1,0xaee92fd4,0xadba2ffc,0xa5dba44e,0xafdd2ee9,0xaa4e2d4d,
0x2cb0217e,0xaddc2bb7,0x1cb62d00,0x2765217e,0x2c5daf91,0x2f5aafed,0x3000ae5e,0xaeb52d4d,0xad72217e,0x2cb0ae3f,0x2765ae3f,0xafff2fa0,
0xaf022fe6,0x217ea993,0xaf1a2aaa,0xaf022fc9,0x28142a4e,0xab0525db,0xad4d2fdd,0xac072dba,0x2cd8afa0,0x2f91aff4,0x2f30abb7,0xac0728d5,
0xac5d9cb6,0x2dbaaed0,0x2dbaafe6,0xae992d72,0xafc92f6e,0x2993ac5d,0xaaaaa5db,0xafe62f6e,0xa30e2d4d,0xa17ea44e,0xaff82ee9,0xafaf2ffc,
0x2d4dafaf,0x2fbcaff8,0x2cd8a17e,0x9fd9a30e,0xaa4ea515,0x2e99af46,0x2fd4af80,0xaa4e2765,0xafff2e99,0x2cb0adba,0x2765adba,0xad722c5d,
0xab5e2ee9,0x2875ab05,0xae3f2934,0xaf1a2e5e,0x2dbaafbc,0x2fddaffc,0x25db2934,0x2a4eac07,0xa765a875,0x2f46afa0,0x2f80ad27,0x2515a875,
0xafa02d72,0x2e3faed0,0x2e3fafe6,0xa17e9cb6,0xadfe2fd4,0x2cd8ad96,0xa44ea9f1,0xa93426a1,0x2e1fafc9,0x2ff4afff,0xa8752d72,0x2e1fae7c,
0x9fd9aa4e,0x2fbcafdd,0x2cd8a5db,0x2d4dadba,0xaeb52c07,0x2f5aaf91,0x3000af30,0x2c5dacd8,0xaf802ff4,0x2ed0af1a,0x2cb0af1a,0x2aaaabb7,
0x2e7cafd4,0x2fffb000,0xad722f5a,0x2fc9afd4,0x230eac07,0x2ff8affc,0x217e2934,0x2fafafbc,0xad4d28d5,0x2fedaff4,0x2e5eabb7,0x2f91afa0,
0xb0002f46,0x2fddafe6,0x2fddafc9,0x2f6eaf80,0xaaaaaa4e,0xaed0ac87,0xacb0ac87,0x2f802dba,0xab5eab05,0xafafafed,0xad00acd8,0x2f1a2ffc,
0xac07abb7,0xab05ae1f,0xad4dad27,0x28142d00,0xac5dac32,0x29f19cb6,0xad96ad72,0xac5da515,0xafafaf80,0xafa0afe6,0xafa0afc9,0x2d002f46,
0xafedafd4,0xa934adba,0xaf30af6e,0xa81426a1,0xb000affc,0x2c87244e,0xae99aee9,0xaf6ead4d,0xafe6aff8,0x2fff2f02,0xaddcae3f,0xaed0aff8,
0xaeb5af30,0xaa4eae5e,0x9648a44e,0xac5d9fd9,0xad72ae1f,0x2cb0230e,0x2765230e,0xafffaf1a,0xabb7acb0,0x2ff82f46,0x2b5e2993,0xabb7aed0,
0xa814a9f1,0x2b052e99,0x2d4d2c87,0x2c071648,0xa44ea8d5,0x2b05a30e,0x2f912f02,0xafbcafa0,0x26a11cb6,0x30002ed0,0x30002fe6,0xa5dbad72,
0x2c3229f1,0x2aaa2eb5,0x2f802fdd,0x2e7c29f1,0x2e3f2d4d,0xad27a44e,0x2e1f2ee9,0x2f022ffc,0x2d4d2bb7,0x2fbc2d27,0x2cd82e1f,0x9fd9ad00,
0x2f5a2e7c,0x2c872f80,0x26a12aaa,0x2f5a2c32,0x2fff2fdd,0xacb09648,0xa7659648,0x2d722fd4,0x2f1a2fbc,0xafafaf91,0xad00ab05,0xab5e244e,
0x30002fbc,0x2e992ffc,0xac87a934,0x2f6e2c07,0x2ed02faf,0xa99328d5,0xaf46ae1f,0x2cb02faf,0x2b5e2d72,0xaff4aed0,0xaff4afe6,0xad279cb6,
0x9fd926a1,0xa44eadba,0xae5eaf6e,0xaf30afd4,0x2d272ed0,0x230e2ddc,0xafafafff,0x2d272fe6,0x1fd929f1,0xafbcac87,0xacd8ae99,0xad4d9648,
0xac5da814,0xaa4eaf30,0x9648a934,0xaeb5afed,0xaf80ae3f,0x2ed028d5,0x2cb028d5,0x2aaaa875,0xa51526a1,0xad721648,0x9cb6aa4e,0xac3226a1,
0xae3fac07,0xae1faffc,0x2d272934,0xaf02afbc,0xaffcafa0,0x2cd8a30e,0x2fed2f02,0x2b05a8d5,0xad96af46,0x2e992fe6,0x2e992fc9,0x2f5a2f80,
0xafffadba,0xae7caeb5,0xafc9aeb5,0x2d722f6e,0x217ead4d,0x2ff42814,0x2875ac07,0xaff8ab05,0x2fed2e3f,0xad4d2b5e,0x2f912f1a,0x2e5ea875,
0xa5db2cb0,0x9648af80,0xa9f12aaa,0xa5db2ed0,0xad00afff,0xa17eafc9,0xa17eae7c,0xabb72d72,0x2ee925db,0x2d4d2f5a,0x2ffc2d96,0xa44eafdd,
0x29f12f91,0xafd4ac07,0xa6a12cd8,0x2d962f30,0xafc9ab5e,0x2f46a30e,0xaf80af02,0xafe6ab5e,0x25dbad4d,0x2d96ac07,0x2f5a2814,0xafddab05,
0x2f462f1a,0xa7652f02,0x25152f02,0x2f80a17e,0xad002765,0xa8d5afff,0xaff8ad72,0xad002cb0,0xacd8b000,0x2dfe2eb5,0x2934ac5d,0x244eaf5a,
0x2ee9217e,0x2ffc2875,0x2d4d2ff4,0xa44eaff8,0x25db2f46,0xaf6e2515,0xaf6ea765,0x2c5d2f80,0xafe6ad96,0x2d72ac87,0x9cb6aeb5,0xaed0ad96,
0x2bb7ab05,0xa8d52ee9,0x2fa02e5e,0x2ff42934,0x2f912e3f,0x2cd82f1a,0xac072b5e,0x2f30a875,0xad962765,0xaeb5ad72,0xac87afff,0xad962cb0,
0xa993afd4,0x2fc92a4e,0x2fe62a4e,0x2aaaae99,0x2ff82cd8,0xaff49fd9,0xa8752d4d,0xa17e2fbc,0x29f12fed,0xa6a12f91,0xafd4ad4d,0x2d962e5e,
0xafe6ad00,0x9cb6aff8,0x2d72a8d5,0xaed0ad00,0x2d27a993,0x28752fe6,0x28752fc9,0x2fa02aaa,0x29342fdd,0xac07af5a,0xafbcad96,0xaffca5db,
0xab5e2cb0,0xaf022aaa,0xa30eaf80,0xab5e2ed0,0xab05b000,0x2e5eac5d,0x2ee92eb5,0x2934af5a,0x2fdd2cd8,0xad962d4d,0xaf5a9fd9,0xa5db2fbc,
0xaddc2875,0x2cb0ae1f,0x2765ae1f,0x1cb6aff4,0xafc9a5db,0xaf80a9f1,0x2f469648,0xafe6a5db,0x2bb7acd8,0x2fa02934,0xa8d52dfe,0x2ff4244e,
0x29342ff8,0xafbca875,0xac07aff4,0xaffca17e,0xaf5aaddc,0x2fd42765,0x2fd42cb0,0x30001cb6,0xa993af6e,0x2765afdd,0xa515afdd,0xaaaa3000,
0x28d52f91,0xaf022e5e,0x230e2fed,0x2fa0ad4d,0xa814afaf,0x2f91a17e,0x9fd9aff8,0xaee9a30e,0x26a12fc9,0xaa4ead72,0x16482fff,0x26a12e7c,
0x2bb7af46,0x2f1aae7c,0x2f1aac32,0xaff42993,0xacd82eb5,0xaf301648,0xaf912a4e,0x2c072c5d,0x2dbaadfe,0x25db2e5e,0x2fdda814,0x2a4eaffc,
0xae7c2d27,0x2d72afaf,0xafff230e,0xafc92d27,0x2fd4a934,0x2f6ea44e,0x2dba2cd8,0xa6a1adfe,0xafff217e,0xa515ae3f,0xac32ae3f,0xaddc2fa0,
0x2faf2515,0xae1f2f80,0x28d52f46,0x2fafa765,0xaee9aa4e,0x2f91a5db,0x9fd9afdd,0xa814adba,0x2e5e2b5e,0x29342d00,0xab052faf,0x2ee9af1a,
0xac5daddc,0x2dbaafc9,0x2dbaae7c,0xae999cb6,0x27652f5a,0xaf8026a1,0xaf462c87,0xa5152f5a,0x230eaffc,0x217e2e5e,0x2ff8a814,0x2fafadfe,
0x1fd92faf,0xac072ff8,0xafed217e,0x2dfe230e,0x29f1afe6,0x2fddaaaa,0x2eb52993,0x29f1afc9,0xaddc2e99,0xa515adba,0xac32adba,0xafff2c5d,
0x2fa0ac07,0xaf022f30,0x230e2f91,0x28d52cd8,0xadba2ee9,0xafdd2dfe,0xa5dbaf30,0xaa4e2fbc,0x2fc9abb7,0x2aaa2b5e,0xa9932ff8,0x2fe6abb7,
0xafa09cb6,0x2e3fafc9,0x2e3fae7c,0xa17eaddc,0x2d4d2c5d,0xae5e1648,0xafed2a4e,0xaf912eb5,0xaff82765,0xae3f1cb6,0x2f02addc,0xaff82cb0,
0x2dfe2a4e,0xac072fdd,0xafed25db,0x1fd92dba,0xa6a1aee9,0x2f6ea934,0x2dba2b05,0x2fd4ae5e,0xaaaa2ff4,0x2765af1a,0xa515af1a,0xa993abb7,
0xacb0ac5d,0x9cb6ad96,0x2ddc29f1,0xa765ac5d,0xa30e2fbc,0xaff82dfe,0xa17eaf30,0xafaf2ee9,0x2dfeaf1a,0x244e2d00,0xacd82faf,0x29342b5e,
0xb0002993,0x2fddae7c,0x2fddac32,0x2f6eaf46,0x2ddcb000,0x2fe6afd4,0x2ed0afd4,0xafff2f5a,0xad279fd9,0x2d00aee9,0xabb7a814,0xae1f2f91,
0xae5e2ff4,0x9fd9a8d5,0xaf302fa0,0xa44e2bb7,0x2c872515,0xadba2aaa,0x2a4e2993,0x2c87a765,0x2ff4ad72,0x2e1fac32,0x2e1fa515,0xa8759cb6,
0x2814ae99,0x2ffcaf6e,0x2dfeb000,0xae5e2c87,0xaf5a2b05,0x2eb5afbc,0xac5da44e,0xb0002f91,0xac322fa0,0x2993ad00,0xaf462faf,0xae7c2fa0,
0x2c871fd9,0x16482814,0xa9f12ee9,0x2e99af91,0x2f80afa0,0x2c32a875,0x2e7ca875,0x2aaaad27,0xa30eac32,0x2f1aaddc,0x2e1fafff,0xa30ea515,
0xafed2d96,0x2ffcafd4,0xab05a6a1,0xacd829f1,0xa8142e1f,0xadfe2f02,0xaffc2e3f,0x2e5ead27,0x2e99a993,0xaa4e2cb0,0xaa4e2ed0,0x2fd4af46,
0x2e7cb000,0x1cb625db,0x2ddca6a1,0x2fc9b000,0xa875a934,0x2b5ea814,0x2f1aafed,0x2e3faf30,0xaf302ff4,0xafed2fa0,0xa814a8d5,0xa9342bb7,
0x16482c32,0xafd42fff,0xafdd2ddc,0x16482515,0x2f46ac5d,0xaed02f6e,0xacb02f6e,0x2993a5db,0x2e1fafed,0xad002dfe,0x2bb71fd9,0x2d27ac07,
0xaf5a2cd8,0xac5d2b05,0x2eb5affc,0xb0002fed,0xae7c2ff4,0xaddc2d27,0x9cb6ab5e,0xafc92ff4,0x217e2aaa,0xaf022e7c,0xaf022c32,0xaf1a2f80,
0x2f30ac87,0xafbc2f6e,0xaee93000,0xadfe2e99,0xa8d5a515,0x2875a993,0x2e3faaaa,0xa8d52765,0xaf912d96,0x244ea6a1,0x2fbcafd4,0xab0529f1,
0xae992fed,0x96489fd9,0x29f1adfe,0xac872c07,0x9cb62bb7,0xa515217e,0xac32217e,0xad722d00,0x2c32ae99,0x2f46af5a,0xa9932d96,0x2e7cae99,
0xa875a44e,0x2f1aaf30,0x2b5e9fd9,0x2e3fae5e,0xaf302d27,0x2ee9af02,0x2fbcae3f,0x2dfeae1f,0xaf6e2fff,0x2eb5aed0,0x2eb5afe6,0x2dbaaddc,
0xaddcadba,0xafe6aeb5,0xaed0aeb5,0x2fff2f6e,0xae1fadfe,0xae3fafbc,0xaf02aee9,0x2d272f30,0xae5eae3f,0x9fd9ab5e,0xaf30af1a,0xa44e2875,
0xae99ae7c,0x2d962993,0xaf5aaf46,0xae99ac32,0xad00ad72,0xa17eac32,0xa17ea515,0xabb79cb6,0xac07ac87,0x2dfe29f1,0x1fd99648,0xafedae99,
0xa9f1ab05,0x2fd42fbc,0x26a1244e,0xad96af91,0xa765a8d5,0x2aaa2e3f,0x29932875,0x2515a8d5,0x2e992dfe,0x30002ee9,0x2f6e2fbc,0xac87af30,
0x2f802f1a,0x2c322f02,0x2e7c2f02,0x2aaaa17e,0x2ff42fc9,0xab5e1cb6,0x2d272ddc,0x2ff42e7c,0x2fed3000,0xaffcaeb5,0x2b052c5d,0x2cd82f5a,
0x2c072d27,0x9fd92bb7,0xadfead00,0x2fed2e1f,0x25db2993,0xaf6eacb0,0xaf6eaed0,0x2c5d2f46,0xa5151648,0xaddcafdd,0xafffafd4,0xac321648,
0xabb7a934,0x28d5a814,0xafa0afed,0xaff4af30,0xaf30ae3f,0xafedaf1a,0xa814ab5e,0xa9342875,0xb000afc9,0xa6a1addc,0x25db9cb6,0xb000ae7c,
0xaf46afd4,0x2ed02a4e,0x2cb02a4e,0xa993ae99,0xad27ae5e,0x2e3f2ffc,0x2f022dfe,0x2e1f2814,0xa9f1acd8,0x26a1ab05,0x2fd42ffc,0xad96afed,
0x2515a30e,0x2fff2e1f,0x2ddc2f1a,0x2c32a30e,0x2d272aaa,0x28752e7c,0x28752c32,0x2fa02f80,0x2f912e99,0xaee9a9f1,0xa8141648,0x9fd92c87,
0x2fa02e7c,0x2faf2f46,0xad00a993,0x2fa02c32,0x2f913000,0xa44e2c5d,0xafbcaeb5,0x2b052f5a,0x2c872e5e,0xb000adfe,0xaf6eaffc,0xae99a814,
0x9cb62875,0xa515ae1f,0xac32ae1f,0xad72aff4,0x27652c87,0xa9932a4e,0xaaaaadba,0xa5152c87,0xabb7a44e,0xafa0af30,0x28d59fd9,0xaff4ae5e,
0xaf91ae1f,0x2814abb7,0x2ee92d00,0x1fd9ad27,0xaf5aafff,0x2fd42ed0,0x2fd42fe6,0x30002ddc,0xaf46af6e,0xac32afdd,0xae7cafdd,0x29933000,
0x2b5ea934,0x2faf2cd8,0x2d00a44e,0xaf1aadfe,0x2ee92faf,0xaf30217e,0x2dfe2ff8,0x2fbc230e,0xac5d2765,0x29f1addc,0xad961cb6,0xac5d2cb0,
0x2bb7a993,0x2f1aa515,0x2f1a2765,0xaff4aaaa,0x2e5e2fd4,0xab052dba,0x29342f6e,0x2ee9a6a1,0xadba1fd9,0xa5dbafed,0xafddac07,0xaa4e2dfe,
0xacb0aff8,0x2ddc2f02,0x9cb6ae3f,0xa765aff8,0x2eb52f91,0x2a4e2fed,0x16482e5e,0x2c5dad4d,0xaddc217e,0xae7cae3f,0xafc9ae3f,0x9cb62fa0,
0xabb7afe6,0x2ff82993,0x2b5eaaaa,0xabb7afc9,0x2fbc2a4e,0xaf3025db,0x2dfe2fdd,0x2ee92dba,0xacd828d5,0xaf91230e,0xaf30af02,0x2c072fa0,
0xac5dafff,0x2dbaac32,0x2dbaa515,0xae99addc,0x2fc929f1,0xa9932eb5,0x2aaa2fdd,0x2fe629f1,0xa30e2dfe,0xa17eafed,0xaff8ac07,0xafaf1fd9,
0xadfeafaf,0xa814aff8,0x2e5ea17e,0xaffca30e,0x2f5a2515,0x2c872f46,0x26a12f80,0x2f5aa765,0x9cb62e99,0xae7cadba,0xafc9adba,0xaddc2c5d,
0xaf1aaee9,0x2faf2b05,0x2d00a934,0x2b5eae5e,0x2dbaa814,0x2fdd9fd9,0x25db2f91,0x2a4eaee9,0x27652faf,0xaf4628d5,0xaf80ae1f,0xa5152faf,
0xafa0addc,0x2e3fac32,0x2e3fa515,0xa17eafff,0x2dfea6a1,0xacd82dba,0x244e2f6e,0x29342fd4,0x2d272fc9,0x230e2fff,0xafafad72,0x2d272e7c,
0xaffcaa4e,0xa814afdd,0x2e5ea5db,0xadfeadba,0x2c5dac07,0x2a4e2f91,0x16482f30,0x2eb52cd8,0x29932ff4,0xac32af1a,0xae7caf1a,0xaf46abb7,
0xae7c26a1,0xafff1648,0x2d72aa4e,0xafc926a1,0x230eaee9,0x2ff89fd9,0x217e2f91,0x2fafa814,0x2d4d2fa0,0xafed230e,0xae5eaf02,0xaf9128d5,
0xb000aaaa,0x2fdda515,0x2fdd2765,0x2f6ea993,0x1cb6b000,0x2cb0afd4,0x2765afd4,0xaddc2f5a,0xa17e2ffc,0xaff42c07,0xa8752fbc,0x2ff8a934,
0x244eaff4,0x2dfe28d5,0x2934afa0,0xacd8abb7,0xa5db2fe6,0x9648af46,0xa9f12f80,0xa5db2fc9,0x2ff41cb6,0x2e1f2765,0x2e1f2cb0,0xa875addc,
0xafbca5db,0x1fd9af5a,0xad4dad96,0xacd82fdd,0x2f5a2934,0xaeb52ee9,0x2c5d2e5e,0x3000ab05,0xaed0ab5e,0x2f80a30e,0xaaaaaf02,0xacb0ab5e,
0xa5db2ffc,0xad962fbc,0xaf5a2c07,0x2fdda934,0x2aaaafa0,0x2fc9a875,0x2fe6a875,0xa993ad27,0xad002ed0,0xa8d5ad72,0xaff81cb6,0xad002fe6,
0x2e5ead96,0xad4d2fd4,0x2f9126a1,0x2feda9f1,0xafbca17e,0xad4da875,0x1fd9aff4,0xacd82ff8,0x2e992aaa,0xaa4e2fe6,0xaa4e2fc9,0x2fd4a993,
0xacb0ad96,0x2fffac87,0x2d72aeb5,0xa765ad96,0x28752f30,0xab5eac07,0xaf1a2cd8,0xae3f2f91,0x2934aff4,0x2e5eafa0,0x2ee928d5,0xab05abb7,
0xad962ed0,0xaeb51cb6,0xac87ad72,0xad962fe6,0x2f80ac5d,0xa7652f6e,0x25152f6e,0x2f46a5db,0xaff8244e,0x2ff4ad4d,0x2875affc,0x217eaee9,
0x2f5a244e,0x2c5d2934,0xaeb52dfe,0x3000acd8,0xacb0ad00,0x2d72aff8,0x2fffa8d5,0xa765ad00,0x217e2f80,0xaf022515,0xaf02a765,0xaf1a2f46,
0x2b05afdd,0xa8142f5a,0x2c072d96,0x2d4d25db,0xab5e2fe6,0xaf022f80,0xa30eaf46,0xab5e2fc9,0x2f30ad96,0x2cd826a1,0xac072fd4,0x2f91a9f1,
0xafdd244e,0x2d96affc,0x2f5aad4d,0x25dbaee9,0x2d722bb7,0xae7c217e,0xafc9217e,0xafff2d00,0xaed0a5db,0xaaaaa9f1,0x2f809648,0xacb0a5db,
0x28752e5e,0xaf1a2f91,0xab5ead4d,0xae3f2fed,0x2b05aff8,0x2c072875,0xa8142ff4,0x2d4d217e,0xaf6e2d72,0x2eb5afc9,0x2eb5ae7c,0x2dbaafff,
0x2f80af5a,0x2fc9ae99,0x2fe6ae99,0xaf462d96,0xa8d5ab05,0x2f02afed,0xa30eacd8,0xafa02ffc,0xafbc2f02,0x2934ad27,0xaffc2e1f,0xac072e3f,
0x26a12c32,0xaa4e1cb6,0x16482d72,0x26a12515,0x28752aaa,0xa8d52cb0,0xa8d52ed0,0x2e3faf80,0x2fedaeb5,0x29349648,0x2f30aa4e,0x2814ac5d,
0x1648ad4d,0x2e99acd8,0x2c87afbc,0xa9f11fd9,0xafe62d27,0x2fffafaf,0xaddc230e,0xaed02d27,0xafd42f30,0xaf6e2e5e,0xadba244e,0x26a11fd9,
0x9cb62d27,0xafe62ff4,0xaed02ff4,0x2d72ab5e,0x2fafacb0,0xae1f2f46,0x28d52993,0x2fafaed0,0x2c07af6e,0xa9342c87,0x2ffcae99,0x2fbcb000,
0xa44eab5e,0x2b05ad00,0x2f91afaf,0xafbc2f1a,0xafd42d72,0x1648a765,0x1648acb0,0xafdd2fff,0xac322f5a,0xaaaa26a1,0xaf802c87,0xae7c2f5a,
0x2d009fd9,0xae1f2cd8,0xad272fbc,0xabb72d4d,0x2ffcaf02,0x2ee9ae1f,0xa44e2d27,0x2d4dae3f,0x29f1ae7c,0x2fddaf80,0x2eb5aaaa,0x29f1ac32,
0xad7225db,0x2fe6b000,0x2ed0b000,0x1cb6a6a1,0xafa02fbc,0x2f02af91,0xa30eab05,0xa8d5244e,0x96482c07,0xac872d4d,0xae992b05,0x29f1a814,
0x2ed0abb7,0xa9932b5e,0xaf462ff8,0x2cb0abb7,0x2f1aafff,0xa30e2765,0xa30e2cb0,0x2e1fad72,0x1fd9ac5d,0x244e9648,0x2e5eaa4e,0x2f30aeb5,
0xaff82ed0,0xae3f2ddc,0x2f02afff,0xaff82fe6,0xad4d2f6e,0xaee92e99,0x244eac87,0xaffc3000,0x26a12814,0xaf6e2f30,0xadba2934,0xafd42fed,
0x2f46ad00,0xafc92fa0,0xafe62fa0,0xaf802faf,0x2515ac5d,0x2d72ad96,0x1cb629f1,0x2c32ac5d,0xad002814,0x2d27ad4d,0x2e1fab05,0x2bb7ac07,
0xaffc2f1a,0x2cd8ad00,0x2fedafaf,0x2b05ab5e,0xadba2f80,0x2c87acb0,0x2c87aed0,0x2a4eaaaa,0xaf80af6e,0xafc9afdd,0xafe6afdd,0x2f463000,
0xafa0af91,0xabb7ae5e,0xaff4afed,0x28d52d4d,0xafbcafaf,0x2934a17e,0xaffcaff8,0xac07a30e,0xafd4afc9,0x2f5a2d72,0xb000afff,0xafd4ae7c,
0x2bb72aaa,0x2f1a2cb0,0x2f1a2ed0,0xaff4af80,0x2cd82c5d,0x2f303000,0x2f912f5a,0xac07aeb5,0x2dba2d4d,0x25db2cd8,0x2fdd2fbc,0x2a4e9fd9,
0x2e7c2e1f,0xad72a875,0x2fff2ff4,0x2fc92e1f,0x26a12934,0xa9f1244e,0xad96acd8,0x2fd42dfe,0x9cb6217e,0xafe6ae3f,0xaed0ae3f,0x2d722fa0,
0xa875a515,0xad27af80,0xafa0af46,0xa8752765,0xac07aa4e,0x2934a5db,0xaffcafdd,0xafbcadba,0xae5eaf1a,0xa934ae3f,0x2b052875,0xaee9ab5e,
0xac5dad72,0x2dba2765,0x2dba2cb0,0xae99afff,0xa765aa4e,0x2f802fd4,0x2f462e99,0x2515aa4e,0x230e9fd9,0x217e2cd8,0x2ff82fbc,0x2faf2d4d,
0x2ffc2faf,0x2ee92ff8,0xa44e217e,0x2d4d230e,0x2f6e2fe6,0xa5db2aaa,0xac5da993,0x2f6e2fc9,0x2d722e99,0xafe6adba,0xaed0adba,0x9cb62c5d,
0x28d52c07,0xabb7af30,0xaff4af91,0xafa0acd8,0xadbaac07,0xafddad4d,0xa5dbab05,0xaa4e2814,0xafc9af02,0xaaaaaf1a,0x2993217e,0xafe6af02,
0xafa0afff,0x2e3f2765,0x2e3f2cb0,0xa17ead72,0xad4daeb5,0x2e5e3000,0x2fed2f5a,0x2f912c5d,0x217ea765,0x2d009cb6,0x2bb72ddc,0x217eacb0,
0x2d4d2a4e,0x2ee92fdd,0xa44e25db,0x2ffc2dba,0x2fd42ee9,0xa9f12934,0xad96ab05,0x26a12e5e,0x2f462ff4,0xafc9af1a,0xafe6af1a,0xaf80abb7,
0x2cb02eb5,0x1cb62dba,0xaddcaf6e,0x27652eb5,0xa30e2814,0xaff8ad4d,0xa17eab05,0xafafac07,0xadfeab5e,0xa44eae3f,0x2cd82875,0xa934af1a,
0xb000af80,0x2fdd2cb0,0x2fdd2ed0,0x2f6e2aaa,0xad72b000,0xa515afd4,0xac32afd4,0x9cb62f5a,0x2e1f1fd9,0x2e3f2ee9,0x2f022814,0xad27af91,
0x2cd82ff4,0xaffca8d5,0x2b052fa0,0x2fed2bb7,0xae99a515,0x2d96aaaa,0xaf5aa993,0xae992765,0x2ff42ddc,0x2e1f2ed0,0x2e1f2fe6,0xa875afff,
0xa8142c87,0xaffca9f1,0xadfe1648,0x2e5e2e99,0xaf5aaf30,0x2eb5a814,0xac5dafed,0xb000a934,0x2c32a8d5,0xa9932e3f,0x2f462875,0x2e7ca8d5,
0xae999fd9,0xb000a814,0xaf6eaee9,0x2c872f91,0xa993afa0,0x2ed0a875,0x2cb0a875,0xaf46ad27,0x2ff42c32,0xab5e2ddc,0x2d272fff,0x2ff42515,
0xa44e2d96,0x9fd9afd4,0xaf30a6a1,0xae5e29f1,0x2814ad27,0x2dfeabb7,0x2ffc2d00,0xae5eae1f,0x2e992f80,0xaa4e2e7c,0xaa4e2c32,0x2fd42aaa,
0xae7c1648,0x9cb6afdd,0xaddcafd4,0xafc91648,0xa875af91,0x2b5e2fbc,0x2f1a244e,0x2e3fab05,0x2b052ff4,0xa44e2fa0,0xafbca8d5,0x2f912bb7,
0xb000ac32,0xa6a1afff,0x25dbaddc,0xb000a515,0x2aaaac5d,0x2c322f6e,0x2e7c2f6e,0x2f80a5db,0x2d272fed,0xae3fadfe,0xaf029fd9,0xae1f2c07,
0xaf5aae5e,0xac5daf30,0x2eb59fd9,0xb000a44e,0x2e7ca30e,0x2ddc2e1f,0x1cb62f1a,0x2fc9a30e,0x217e2f46,0xaf02acb0,0xaf02aed0,0xaf1a2993,
0xaf30ae99,0x2fbc29f1,0x2ee99648,0x2dfeac87,0x2fa02515,0x2faf2993,0xad002aaa,0x2fa0a765,0xa9342d96,0xafeda6a1,0xa814afd4,0xaf3029f1,
0xac87afed,0x30001fd9,0x2f6e2dfe,0x2e99ac07,0x2fff2bb7,0xafe6217e,0xaed0217e,0xaddc2d00,0xac322c87,0xaf462a4e,0x2993adba,0xae7c2c87,
0xa875afed,0x2f1aab05,0x2b5e2ffc,0x2e3facd8,0x2f302e1f,0xaee92bb7,0xafbcad00,0xadfe2d27,0xaf6e9cb6,0x2eb5ac32,0x2eb5a515,0x2dbaad72,
0x2aaaaf5a,0x2ed0ae99,0x2cb0ae99,0xaf802d96,0xab5e2f30,0xafaf244e,0xad002e5e,0x2f1a1fd9,0x2c07af02,0x2b052d27,0x2d4dae1f,0xa814ae3f,
0xac5d2ed0,0x29f1afff,0xad962ddc,0xac5d2fe6,0x28752f80,0xa8d52fe6,0xa8d52fc9,0x2e3faf46,0xa44eafd4,0x2f91adba,0x2b05af6e,0xafbc26a1,
0x96482ffc,0xae99a44e,0xac872ee9,0x29f12d4d,0x2515aff8,0x1cb62f02,0x2d72ae3f,0x2c32aff8,0xaeb5ab05,0xaa4eacd8,0x9648afed,0xac5d2ffc,
0x2d722d27,0xacb02ff4,0xa7652ff4,0x2fffab5e,0xabb7ae7c,0x2ff8aaaa,0x2b5eaf80,0xabb7ac32,0x28142f6e,0xab05ac87,0xad4d2e99,0xac073000,
0x2feda8d5,0x2f30a30e,0x29342f02,0x2814afa0,0xafd49cb6,0x1648aed0,0x1648afe6,0xafdd2d72,0x2ed029f1,0xaf462eb5,0xa9932fdd,0x2cb029f1,
0xad00ad4d,0x2e1f244e,0x2d27aee9,0x2bb7affc,0xad4d2f02,0xafbc2e1f,0xacd8ad27,0x1fd92e3f,0x2f5aacb0,0x2c872993,0x26a12f46,0x2f5aaed0,
0xafff25db,0x2cb0b000,0x2765b000,0xad72a6a1,0x2f1a2814,0xafaf2934,0xad002f30,0xab5e2fed,0x1648afbc,0x2c87affc,0x2e992934,0xa9f1ac07,
0xac322faf,0xaf8028d5,0xaaaaae1f,0xae7c2faf,0x2f1aad72,0xa30e2ed0,0xa30e2fe6,0x2e1f1cb6,0xaffc26a1,0x2fedadba,0x2cd8af6e,0x2b05afd4,
0x2d272c32,0x230e2d72,0xafaf1cb6,0x2d272515,0x9fd9af6e,0x2fbcae99,0x2cd82c87,0x2d4db000,0xac5d2fbc,0xaa4eab05,0x9648af91,0xaeb5244e,
0x2f80ad00,0xaed02fa0,0xacb02fa0,0xaaaa2faf,0xafe626a1,0xaddc1648,0x2fffaa4e,0xaed026a1,0x2d002c07,0xad272ffc,0xae1fa934,0xabb72fbc,
0x1fd9afa0,0x2e5ea30e,0x244e2f02,0x2f30a8d5,0xadba2f46,0x2c87afe6,0x2c87afc9,0x2a4eaf80,0x2fffad96,0x2e7cac5d,0x2fc9ac5d,0xad7229f1,
0x217eadfe,0x2ff4afbc,0x2875aee9,0xaff82f30,0xafed2d00,0x2d4daf1a,0xaf912b5e,0xae5e2faf,0xa5db2e7c,0x9648a993,0xa9f12f46,0xa5db2c32,
0xae3f2fff,0xaff82fc9,0xaff82e7c,0x2f02ad72,0x2c0725db,0xadfe2f5a,0x9fd92d96,0x2fedafdd,0x2f6eaf91,0xa6a12c07,0x2fd4acd8,0x2dbaaf30,
0xa765ab5e,0x2aaaa30e,0x2993af02,0x2515ab5e,0x25dbadfe,0x2d96aee9,0x2f5aafbc,0xafdd2f30,0xaf462b5e,0x2765abb7,0xa515abb7,0xaf802ff8,
0xad002fc9,0xa8d51cb6,0xaff82ddc,0xad002e7c,0x2cd81648,0xadfe2c5d,0xa9342eb5,0xa44e2a4e,0x2c07217e,0x9fd92875,0xadfe2ff4,0x2fedaff8,
0x2fddaf46,0x29f1a515,0x29f12765,0x2eb5af80,0x2515ad96,0x2ddcac87,0x2fffaeb5,0x2c32ad96,0xaf022b05,0x2fa0aee9,0x28d5ae5e,0x230ea934,
0xaf912d00,0xacd82b5e,0x2c07af1a,0xaf302faf,0xad962fc9,0xaeb52ddc,0xac871cb6,0xad962e7c,0x299326a1,0xafc92f5a,0xafe62f5a,0xaaaa2c87,
0x2ff8ae5e,0xaff42ffc,0xa8752dfe,0xa17e2814,0x2f6eafed,0x2fd4af91,0xa6a12d4d,0x2dbaae5e,0x2515ad00,0x2fffaff8,0x2ddca8d5,0x2c32ad00,
0xae1f2993,0x2fafafe6,0x2fafafc9,0x28d5aaaa,0xaf912fdd,0x2ee9af5a,0x2814ad96,0x1fd9a5db,0xab5e2e7c,0xaf022f46,0xa30ea993,0xab5e2c32,
0x2b051648,0xae5e2eb5,0xaee92c5d,0xa9342a4e,0x2fddae5e,0xad962dfe,0xaf5a2ffc,0xa5db2814,0x2ddcafaf,0xacb02d27,0xa7652d27,0x9cb6230e,
0xa765a5db,0x2993a9f1,0x2aaa9648,0x2515a5db,0xaf022cd8,0x28d5a934,0x2fa0adfe,0x230ea44e,0xaf912ff8,0x2814a875,0x2ee9aff4,0x1fd9a17e,
0xaa4e2ddc,0x26a1a765,0x26a1acb0,0x16489cb6,0x9d7f9e49,0xaddcaeb3,0x12480000,0x22ad0000,0x9bdb9cb6,0xac2ead04,0x18b61648,0x290226ad,
0x98b69a49,0xa902aaaf,0x1bdb1a49,0x2c2e2aaf,0x92489648,0xa2ada6ad,0x1d7f1cb6,0x2ddc2d04,0xa420a4b7,0xae8daf7f,0x18b60000,0x23760000,
0xa1e4a312,0xacacad9c,0x1f121cb6,0x29992777,0x9f12a0b6,0xa999ab78,0x21e420b6,0x2cac2b78,0x98b69cb6,0xa376a777,0x24202312,0x2e8d2d9c,
0xa6e0a7db,0xaf3fb025,0x1bdb0000,0x24200000,0xa4e9a5e4,0xad2aae34,0x21e41fdb,0x2a312820,0xa1e4a3db,0xaa31ac21,0x24e923db,0x2d2a2c21,
0x9bdb9fdb,0xa420a820,0x26e025e4,0x2f3f2e34,0xa8d0a980,0xaff2b08c,0x1d7f0000,0x24840000,0xa6e0a820,0xada9aecd,0x2420217f,0x2ac82885,
0xa420a580,0xaac8ac86,0x26e02580,0x2da92c86,0x9d7fa17f,0xa484a885,0x28d02820,0x2ff22ecd,0xaa31ab13,0xb052b0f3,0x1f120000,0x24e90000,
0xa86ba94e,0xae28af65,0x254d2312,0x2b5f28e9,0xa54da712,0xab5faceb,0x286b2712,0x2e282ceb,0x9f12a312,0xa4e9a8e9,0x2a31294e,0x30522f65,
0xab91ac54,0xb0acb15a,0x20520000,0x254d0000,0xa967aa7c,0xaea7affe,0x267b2452,0x2bf6294e,0xa67ba852,0xabf6ad50,0x29672852,0x2ea72d50,
0xa052a452,0xa54da94e,0x2b912a7c,0x30ac2ffe,0xac79ad1e,0xb106b1c1,0x211b0000,0x25b20000,0xaa63abab,0xaf26b04c,0x27a9251b,0x2c4729b3,
0xa7a9a91c,0xac47adb6,0x2a63291c,0x2f262db6,0xa11ba51b,0xa5b2a9b3,0x2c792bab,0x3106304c,0xad2aade8,0xb160b229,0x21e40000,0x26170000,
0xab5fac6d,0xafa5b099,0x286b25e4,0x2c932a17,0xa86ba9e5,0xac93ae1b,0x2b5f29e5,0x2fa52e1b,0xa1e4a5e4,0xa617aa17,0x2d2a2c6d,0x31603099,
0xb1bbb292,0xb44fb4f6,0x267b0000,0x28d00000,0xb012b0e6,0xb216b357,0x2cde2a7c,0x2f3f2cd2,0xacdeae80,0xaf3fb0d9,0x30122e80,0x321630d9,
0xa67baa7c,0xa8d0acd2,0x31bb30e6,0x344f3357,0xb216b2fb,0xb47eb52d,0x26e00000,0x29020000,0xb052b133,0xb257b3a7,0x2d2a2ae1,0x2f8c2d04,
0xad2aaee6,0xaf8cb10c,0x30522ee6,0x3257310c,0xa6e0aae1,0xa902ad04,0x32163133,0x347e33a7,0xb271b364,0xb4aeb565,0x27440000,0x29350000,
0xb092b181,0xb298b3f7,0x2d762b46,0x2fd82d37,0xad76af4c,0xafd8b140,0x30922f4c,0x32983140,0xa744ab46,0xa935ad37,0x32713181,0x34ae33f7,
0xb2cdb3cf,0xb4deb59d,0x27a90000,0x29670000,0xb0d2b1ce,0xb2dab423,0x2dc22bab,0x30122d6a,0xadc2afb2,0xb012b174,0x30d22fb2,0x32da3174,
0xa7a9abab,0xa967ad6a,0x32cd31ce,0x34de3423,0xb329b41d,0xb50eb5d6,0x28070000,0x29990000,0xb113b21c,0xb31cb44c,0x2e0e2c08,0x30392d9c,
0xae0eb00c,0xb039b1a7,0x3113300c,0x331c31a7,0xa807ac08,0xa999ad9c,0x3329321c,0x350e344c,0xb386b453,0xb53fb60f,0x28390000,0x29cc0000,
0xb153b26b,0xb35eb474,0x2e5a2c3a,0x305f2dcf,0xae5ab03f,0xb05fb1db,0x3153303f,0x335e31db,0xa839ac3a,0xa9ccadcf,0x3386326b,0x353f3474,
0xb3e3b489,0xb570b649,0x286b0000,0x29fe0000,0xb194b2b9,0xb3a0b49d,0x2ea72c6d,0x30852e02,0xaea7b072,0xb085b20f,0x31943072,0x33a0320f,
0xa86bac6d,0xa9feae02,0x33e332b9,0x3570349d,0xb420b4bf,0xb5a1b683,0x289e0000,0x2a310000,0xb1d5b308,0xb3e3b4c6,0x2ef32c9f,0x30ac2e34,
0xaef3b0a5,0xb0acb243,0x31d530a5,0x33e33243,0xa89eac9f,0xaa31ae34,0x34203308,0x35a134c6,0xb5d2b6be,0xb76fb857,0x2a630000,0x2bf60000,
0xb413b4ef,0xb523b642,0x30d22e67,0x32092ffe,0xb0d2b278,0xb209b40f,0x34133278,0x3523340f,0xaa63ae67,0xabf6affe,0x35d234ef,0x376f3642,
0xb604b6fa,0xb7a5b878,0x2a950000,0x2c140000,0xb434b519,0xb546b66d,0x30f92e9a,0x32303019,0xb0f9b2ac,0xb230b42a,0x343432ac,0x3546342a,
0xaa95ae9a,0xac14b019,0x36043519,0x37a5366d,0xb637b736,0xb7dbb899,0x2ac80000,0x2c2e0000,0xb456b542,0xb569b699,0x31202ecd,0x32573032,
0xb120b2e1,0xb257b445,0x345632e1,0x35693445,0xaac8aecd,0xac2eb032,0x36373542,0x37db3699,0xb66ab773,0xb809b8bb,0x2afa0000,0x2c470000,
0xb478b56c,0xb58cb6c6,0x31462f00,0x327e304c,0xb146b315,0xb27eb460,0x34783315,0x358c3460,0xaafaaf00,0xac47b04c,0x366a356c,0x380936c6,
0xb69db7b0,0xb825b8dd,0x2b2d0000,0x2c600000,0xb49ab596,0xb5afb6f2,0x316d2f32,0x32a53065,0xb16db34a,0xb2a5b47b,0x349a334a,0x35af347b,
0xab2daf32,0xac60b065,0x369d3596,0x382536f2,0xb6d1b7ee,0xb841b8ff,0x2b5f0000,0x2c790000,0xb4bcb5c1,0xb5d2b71f,0x31942f65,0x32cd307f,
0xb194b37f,0xb2cdb496,0x34bc337f,0x35d23496,0xab5faf65,0xac79b07f,0x36d135c1,0x3841371f,0xb705b817,0xb85db923,0x2b910000,0x2c930000,
0xb4deb5eb,0xb5f6b74d,0x31bb2f98,0x32f43099,0xb1bbb3b4,0xb2f4b4b1,0x34de33b4,0x35f634b1,0xab91af98,0xac93b099,0x370535eb,0x385d374d,
0xb73ab837,0xb87ab946,0x2bc40000,0x2cac0000,0xb500b616,0xb61ab77a,0x31e22fcb,0x331c30b2,0xb1e2b3e9,0xb31cb4cd,0x350033e9,0x361a34cd,
0xabc4afcb,0xacacb0b2,0x373a3616,0x387a377a,0xb897b96b,0xb98dbaa6,0x2cc50000,0x2d900000,0xb63eb7a8,0xb767b895,0x334330cc,0x3442319a,
0xb343b4e8,0xb442b5c8,0x363e34e8,0x376735c8,0xacc5b0cc,0xad90b19a,0x389737a8,0x398d3895,0xb8b4b990,0xb9aebad1,0x2cde0000,0x2da90000,
0xb662b7d7,0xb78db8ae,0x336b30e6,0x345631b4,0xb36bb504,0xb456b5e4,0x36623504,0x378d35e4,0xacdeb0e6,0xada9b1b4,0x38b437d7,0x39ae38ae,
0xb8d2b9b5,0xb9cfbafd,0x2cf80000,0x2dc20000,0xb687b803,0xb7b4b8c7,0x339330ff,0x346a31ce,0xb393b51f,0xb46ab601,0x3687351f,0x37b43601,
0xacf8b0ff,0xadc2b1ce,0x38d23803,0x39cf38c7,0xb8f0b9dc,0xb9f1bb29,0x2d110000,0x2ddc0000,0xb6acb81b,0xb7dbb8e1,0x33bb3119,0x347e31e8,
0xb3bbb53b,0xb47eb61e,0x36ac353b,0x37db361e,0xad11b119,0xaddcb1e8,0x38f0381b,0x39f138e1,0xb90fba02,0xba14bb57,0x2d2a0000,0x2df50000,
0xb6d1b833,0xb801b8fb,0x33e33133,0x34933202,0xb3e3b557,0xb493b63a,0x36d13557,0x3801363a,0xad2ab133,0xadf5b202,0x390f3833,0x3a1438fb,
0xb92eba2a,0xba37bb86,0x2d440000,0x2e0e0000,0xb6f6b84b,0xb815b915,0x3405314d,0x34a7321c,0xb405b573,0xb4a7b657,0x36f63573,0x38153657,
0xad44b14d,0xae0eb21c,0x392e384b,0x3a373915,0xb94dba53,0xba5abbb6,0x2d5d0000,0x2e280000,0xb71bb863,0xb829b930,0x34193167,0x34bc3236,
0xb419b58f,0xb4bcb675,0x371b358f,0x38293675,0xad5db167,0xae28b236,0x394d3863,0x3a5a3930,0xb96dba7c,0xba7ebbe7,0x2d760000,0x2e410000,
0xb741b87c,0xb83db94b,0x342e3181,0x34d03250,0xb42eb5ab,0xb4d0b692,0x374135ab,0x383d3692,0xad76b181,0xae41b250,0x396d387c,0x3a7e394b,
0xa17fa248,0xb1cfb2a1,0x16480000,0x26ad0000,0x9fdba0b6,0xb029b0fd,0x1cb61a48,0x2d002aac,0x9cb69e48,0xad00aeaa,0x1fdb1e48,0x30292eaa,
0x96489a48,0xa6adaaac,0x217f20b6,0x31cf30fd,0xa81fa8b6,0xb27cb365,0x1cb60000,0x27760000,0xa5e4a711,0xb0a6b191,0x231120b6,0x2d972b75,
0xa311a4b6,0xad97af72,0x25e424b6,0x30a62f72,0x9cb6a0b6,0xa776ab75,0x281f2711,0x327c3191,0xaadeabd9,0xb328b414,0x1fdb0000,0x281f0000,
0xa8e8a9e3,0xb122b226,0x25e423db,0x2e2d2c1f,0xa5e4a7da,0xae2db01d,0x28e827da,0x3122301d,0x9fdba3db,0xa81fac1f,0x2ade29e3,0x33283226,
0xaccead7e,0xb3d3b475,0x217f0000,0x28840000,0xaadeac1f,0xb19eb2b9,0x281f257f,0x2ec32c83,0xa81fa97f,0xaec3b080,0x2ade297f,0x319e3080,
0xa17fa57f,0xa884ac83,0x2cce2c1f,0x33d332b9,0xae2daf0e,0xb43eb4d5,0x23110000,0x28e80000,0xac6aad4c,0xb219b34c,0x294d2711,0x2f592ce7,
0xa94dab11,0xaf59b0e4,0x2c6a2b11,0x321930e4,0xa311a711,0xa8e8ace7,0x2e2d2d4c,0x343e334c,0xaf8bb04e,0xb493b534,0x24520000,0x294d0000,
0xad65ae78,0xb294b3df,0x2a7a2852,0x2fef2d4c,0xaa7aac51,0xafefb147,0x2d652c51,0x32943147,0xa452a852,0xa94dad4c,0x2f8b2e78,0x349333df,
0xb074b115,0xb4e7b593,0x251b0000,0x29b10000,0xae5fafa4,0xb30fb438,0x2ba7291b,0x30422db0,0xaba7ad1a,0xb042b1aa,0x2e5f2d1a,0x330f31aa,
0xa51ba91b,0xa9b1adb0,0x30742fa4,0x34e73438,0xb122b1db,0xb53ab5f1,0x25e40000,0x2a160000,0xaf59b067,0xb389b481,0x2c6a29e3,0x308d2e14,
0xac6aade2,0xb08db20d,0x2f592de2,0x3389320d,0xa5e4a9e3,0xaa16ae14,0x31223067,0x353a3481,0xb58db64e,0xb805b887,0x2a7a0000,0x2cce0000,
0xb402b4c9,0xb5dfb6f9,0x30d72e78,0x332830cb,0xb0d7b26f,0xb328b4bd,0x3402326f,0x35df34bd,0xaa7aae78,0xacceb0cb,0x358d34c9,0x380536f9,
0xb5dfb6aa,0xb82ab8b0,0x2ade0000,0x2d000000,0xb43eb511,0xb61ab73d,0x31222edc,0x337130fd,0xb122b2d2,0xb371b4ed,0x343e32d2,0x361a34ed,
0xaadeaedc,0xad00b0fd,0x35df3511,0x382a373d,0xb631b705,0xb850b8d8,0x2b430000,0x2d330000,0xb47bb558,0xb654b780,0x316c2f40,0x33ba312e,
0xb16cb334,0xb3bab51d,0x347b3334,0x3654351d,0xab43af40,0xad33b12e,0x36313558,0x38503780,0xb682b75e,0xb874b900,0x2ba70000,0x2d650000,
0xb4b7b59f,0xb68db7c2,0x31b62fa4,0x34023160,0xb1b6b396,0xb402b54c,0x34b73396,0x368d354c,0xaba7afa4,0xad65b160,0x3682359f,0x387437c2,
0xb6d2b7b7,0xb899b927,0x2c060000,0x2d970000,0xb4f3b5e5,0xb6c6b802,0x32013004,0x34263191,0xb201b3f7,0xb426b57c,0x34f333f7,0x36c6357c,
0xac06b004,0xad97b191,0x36d235e5,0x38993802,0xb721b807,0xb8bcb94d,0x2c380000,0x2dc90000,0xb52fb62b,0xb6ffb822,0x324b3036,0x344b31c3,
0xb24bb42c,0xb44bb5ab,0x352f342c,0x36ff35ab,0xac38b036,0xadc9b1c3,0x3721362b,0x38bc3822,0xb76fb832,0xb8e0b972,0x2c6a0000,0x2dfb0000,
0xb56ab670,0xb737b842,0x32943067,0x346f31f4,0xb294b45d,0xb46fb5da,0x356a345d,0x373735da,0xac6ab067,0xadfbb1f4,0x376f3670,0x38e03842,
0xb7bdb85d,0xb902b996,0x2c9c0000,0x2e2d0000,0xb5a5b6b5,0xb76fb862,0x32de3099,0x34933226,0xb2deb48d,0xb493b608,0x35a5348d,0x376f3608,
0xac9cb099,0xae2db226,0x37bd36b5,0x39023862,0xb924b9ba,0xba1dbab5,0x2e5f0000,0x2fef0000,0xb7a6b881,0xb8a8b96d,0x34b73257,0x35d433df,
0xb4b7b637,0xb5d4b7a1,0x37a63637,0x38a837a1,0xae5fb257,0xafefb3df,0x39243881,0x3a1d396d,0xb946b9dc,0xba39bad0,0x2e910000,0x30100000,
0xb7ddb8a0,0xb8c1b989,0x34db3288,0x35f73408,0xb4dbb665,0xb5f7b7cd,0x37dd3665,0x38c137cd,0xae91b288,0xb010b408,0x394638a0,0x3a393989,
0xb966b9fe,0xba54bae9,0x2ec30000,0x30290000,0xb80ab8bf,0xb8dbb9a4,0x34ff32b9,0x361a3420,0xb4ffb693,0xb61ab7f9,0x380a3693,0x38db37f9,
0xaec3b2b9,0xb029b420,0x396638bf,0x3a5439a4,0xb986ba1f,0xba6fbb02,0x2ef50000,0x30420000,0xb825b8dd,0xb8f3b9be,0x352332ea,0x363c3438,
0xb523b6c1,0xb63cb812,0x382536c1,0x38f33812,0xaef5b2ea,0xb042b438,0x398638dd,0x3a6f39be,0xb9a6ba3f,0xba89bb1a,0x2f270000,0x305b0000,
0xb840b8fb,0xb90cb9d8,0x3546331b,0x365f3451,0xb546b6ee,0xb65fb828,0x384036ee,0x390c3828,0xaf27b31b,0xb05bb451,0x39a638fb,0x3a8939d8,
0xb9c5ba5e,0xbaa2bb30,0x2f590000,0x30740000,0xb85ab918,0xb924b9f2,0x356a334c,0x36823469,0xb56ab71b,0xb682b83d,0x385a371b,0x3924383d,
0xaf59b34c,0xb074b469,0x39c53918,0x3aa239f2,0xb9e3ba7c,0xbababb46,0x2f8b0000,0x308d0000,0xb874b935,0xb93cba0b,0x358d337d,0x36a43481,
0xb58db748,0xb6a4b852,0x38743748,0x393c3852,0xaf8bb37d,0xb08db481,0x39e33935,0x3aba3a0b,0xba00ba99,0xbad1bb5a,0x2fbd0000,0x30a60000,
0xb88eb951,0xb954ba23,0x35b133ae,0x36c63499,0xb5b1b775,0xb6c6b867,0x388e3775,0x39543867,0xafbdb3ae,0xb0a6b499,0x3a003951,0x3ad13a23,
0xbae8bb6e,0xbb7fbbdd,0x30be0000,0x31850000,0xb96bba3b,0xba19bae6,0x36e834b1,0x37f33570,0xb6e8b87c,0xb7f3b91d,0x396b387c,0x3a19391d,
0xb0beb4b1,0xb185b570,0x3ae83a3b,0x3b7f3ae6,0xbafebb80,0xbb8ebbe6,0x30d70000,0x319e0000,0xb982ba52,0xba2dbaf9,0x370a34c9,0x380a3587,
0xb70ab891,0xb80ab930,0x39823891,0x3a2d3930,0xb0d7b4c9,0xb19eb587,0x3afe3a52,0x3b8e3af9,0xbb13bb91,0xbb9cbbed,0x30f00000,0x31b60000,
0xb999ba69,0xba41bb0b,0x372c34e1,0x381a359f,0xb72cb8a6,0xb81ab943,0x399938a6,0x3a413943,0xb0f0b4e1,0xb1b6b59f,0x3b133a69,0x3b9c3b0b,
0xbb27bba0,0xbba9bbf4,0x31090000,0x31cf0000,0xb9afba7f,0xba54bb1d,0x374e34f9,0x382a35b6,0xb74eb8ba,0xb82ab956,0x39af38ba,0x3a543956,
0xb109b4f9,0xb1cfb5b6,0x3b273a7f,0x3ba93b1d,0xbb3abbaf,0xbbb5bbf8,0x31220000,0x31e80000,0xb9c5ba95,0xba67bb2e,0x376f3511,0x383a35ce,
0xb76fb8ce,0xb83ab969,0x39c538ce,0x3a673969,0xb122b511,0xb1e8b5ce,0x3b3a3a95,0x3bb53b2e,0xbb4cbbbc,0xbbc0bbfc,0x313b0000,0x32010000,
0xb9dabaaa,0xba7abb3e,0x37903529,0x384a35e5,0xb790b8e2,0xb84ab97b,0x39da38e2,0x3a7a397b,0xb13bb529,0xb201b5e5,0x3b4c3aaa,0x3bc03b3e,
0xbb5ebbc9,0xbbcbbbff,0x31530000,0x32190000,0xb9f0babf,0xba8cbb4e,0x37b23540,0x385a35fd,0xb7b2b8f6,0xb85ab98d,0x39f038f6,0x3a8c398d,
0xb153b540,0xb219b5fd,0x3b5e3abf,0x3bcb3b4e,0xbb6fbbd4,0xbbd4bc00,0x316c0000,0x32320000,0xba04bad3,0xba9ebb5d,0x37d23558,0x386a3614,
0xb7d2b909,0xb86ab99f,0x3a043909,0x3a9e399f,0xb16cb558,0xb232b614,0x3b6f3ad3,0x3bd43b5d,0x0,0x0,0x0,0x0,
0x2e1f0000,0x336431a8,0x33643400,0x2e1f31a8,0x31a80000,0x31a83400,0xb1a80000,0xb1a8b400,0x33640000,0xae1f31a8,0xae1fb400,0x336431a8,
0x34000000,0xb4000000,0x34000000,0xb4000000,0x33640000,0xae1fb1a8,0xae1f3400,0x3364b1a8,0x31a80000,0x31a8b400,0xb1a80000,0xb1a83400,
0x2e1f0000,0x3364b1a8,0x3364b400,0x2e1fb1a8,0x0,0x0,0x0,0x0,0xae1f0000,0xb36431a8,0xb3643400,0xae1f31a8,
0xb1a80000,0xb1a83400,0x31a80000,0x31a8b400,0xb3640000,0x2e1f31a8,0x2e1fb400,0xb36431a8,0xb4000000,0x34000000,0xb4000000,0x34000000,
0xb3640000,0x2e1fb1a8,0x2e1f3400,0xb364b1a8,0xb1a80000,0xb1a8b400,0x31a80000,0x31a83400,0xae1f0000,0xb364b1a8,0xb364b400,0xae1fb1a8,
0x0,0x0,0x0,0x0,0xae1f0000,0xb364b1a8,0xb364b400,0xae1fb1a8,0x31a80000,0x31a83400,0xb1a80000,0xb1a8b400,
0xb3640000,0x2e1fb1a8,0x2e1f3400,0xb364b1a8,0x34000000,0xb4000000,0x34000000,0xb4000000,0xb3640000,0x2e1f31a8,0x2e1fb400,0xb36431a8,
0x31a80000,0x31a8b400,0xb1a80000,0xb1a83400,0xae1f0000,0xb36431a8,0xb3643400,0xae1f31a8,0x0,0x0,0x0,0x0,
0x2e1f0000,0x3364b1a8,0x3364b400,0x2e1fb1a8,0xb1a80000,0xb1a83400,0x31a80000,0x31a8b400,0x33640000,0xae1fb1a8,0xae1f3400,0x3364b1a8,
0xb4000000,0x34000000,0xb4000000,0x34000000,0x33640000,0xae1f31a8,0xae1fb400,0x336431a8,0xb1a80000,0xb1a8b400,0x31a80000,0x31a83400,
0x2e1f0000,0x336431a8,0x33643400,0x2e1f31a8,0x34003400,0x34003400,0x34003400,0x34003400,0x33643400,0x2e1f31a8,0xae1f0000,0xb364b1a8,
0x31a83400,0xb1a80000,0xb1a8b400,0x31a80000,0x2e1f3400,0xb364b1a8,0x33640000,0xae1f31a8,0x3400,0xb400,0x3400,0xb400,
0xae1f3400,0x3364b1a8,0xb3640000,0x2e1f31a8,0xb1a83400,0x31a80000,0x31a8b400,0xb1a80000,0xb3643400,0xae1f31a8,0x2e1f0000,0x3364b1a8,
0xb4003400,0xb4003400,0xb4003400,0xb4003400,0xb3643400,0xae1f31a8,0x2e1f0000,0x3364b1a8,0xb1a83400,0x31a80000,0x31a8b400,0xb1a80000,
0xae1f3400,0x3364b1a8,0xb3640000,0x2e1f31a8,0x3400,0xb400,0x3400,0xb400,0x2e1f3400,0xb364b1a8,0x33640000,0xae1f31a8,
0x31a83400,0xb1a80000,0xb1a8b400,0x31a80000,0x33643400,0x2e1f31a8,0xae1f0000,0xb364b1a8,0x34003400,0x34003400,0x34003400,0x34003400,
0xb364b400,0xae1fb1a8,0x2e1f0000,0x336431a8,0x31a83400,0xb1a80000,0xb1a8b400,0x31a80000,0xae1fb400,0x336431a8,0xb3640000,0x2e1fb1a8,
0x3400,0xb400,0x3400,0xb400,0x2e1fb400,0xb36431a8,0x33640000,0xae1fb1a8,0xb1a83400,0x31a80000,0x31a8b400,0xb1a80000,
0x3364b400,0x2e1fb1a8,0xae1f0000,0xb36431a8,0xb4003400,0xb4003400,0xb4003400,0xb4003400,0x3364b400,0x2e1fb1a8,0xae1f0000,0xb36431a8,
0xb1a83400,0x31a80000,0x31a8b400,0xb1a80000,0x2e1fb400,0xb36431a8,0x33640000,0xae1fb1a8,0x3400,0xb400,0x3400,0xb400,
0xae1fb400,0x336431a8,0xb3640000,0x2e1fb1a8,0x31a83400,0xb1a80000,0xb1a8b400,0x31a80000,0xb364b400,0xae1fb1a8,0x2e1f0000,0x336431a8,
0x0,0x0,0x0,0x0,0xae1f0000,0xb364b1a8,0xb364b400,0xae1fb1a8,0xb1a80000,0xb1a8b400,0x31a80000,0x31a83400,
0xb3640000,0x2e1fb1a8,0x2e1f3400,0xb364b1a8,0xb4000000,0x34000000,0xb4000000,0x34000000,0xb3640000,0x2e1f31a8,0x2e1fb400,0xb36431a8,
0xb1a80000,0xb1a83400,0x31a80000,0x31a8b400,0xae1f0000,0xb36431a8,0xb3643400,0xae1f31a8,0x0,0x0,0x0,0x0,
0x2e1f0000,0x3364b1a8,0x3364b400,0x2e1fb1a8,0x31a80000,0x31a8b400,0xb1a80000,0xb1a83400,0x33640000,0xae1fb1a8,0xae1f3400,0x3364b1a8,
0x34000000,0xb4000000,0x34000000,0xb4000000,0x33640000,0xae1f31a8,0xae1fb400,0x336431a8,0x31a80000,0x31a83400,0xb1a80000,0xb1a8b400,
0x2e1f0000,0x336431a8,0x33643400,0x2e1f31a8,0x0,0x0,0x0,0x0,0x2e1f0000,0x336431a8,0x33643400,0x2e1f31a8,
0xb1a80000,0xb1a8b400,0x31a80000,0x31a83400,0x33640000,0xae1f31a8,0xae1fb400,0x336431a8,0xb4000000,0x34000000,0xb4000000,0x34000000,
0x33640000,0xae1fb1a8,0xae1f3400,0x3364b1a8,0xb1a80000,0xb1a83400,0x31a80000,0x31a8b400,0x2e1f0000,0x3364b1a8,0x3364b400,0x2e1fb1a8,
0x0,0x0,0x0,0x0,0xae1f0000,0xb36431a8,0xb3643400,0xae1f31a8,0x31a80000,0x31a8b400,0xb1a80000,0xb1a83400,
0xb3640000,0x2e1f31a8,0x2e1fb400,0xb36431a8,0x34000000,0xb4000000,0x34000000,0xb4000000,0xb3640000,0x2e1fb1a8,0x2e1f3400,0xb364b1a8,
0x31a80000,0x31a83400,0xb1a80000,0xb1a8b400,0xae1f0000,0xb364b1a8,0xb364b400,0xae1fb1a8,
};

typedef CUresult (*EncodeFn)(CUtensorMap*, CUtensorMapDataType, cuuint32_t, void*, const cuuint64_t*, const cuuint64_t*,
                             const cuuint32_t*, const cuuint32_t*, CUtensorMapInterleave, CUtensorMapSwizzle,
                             CUtensorMapL2promotion, CUtensorMapFloatOOBfill);

}

extern "C" void kernel_launch(void* const* d_in, const int* in_sizes, int n_in, void* d_out, int out_size) {
    Params p;
    p.x = (const __nv_bfloat16*)d_in[0];
    p.lar = (const __nv_bfloat16*)d_in[1];
    p.aim = (const __nv_bfloat16*)d_in[2];
    p.cr = (const __nv_bfloat16*)d_in[3];
    p.ci = (const __nv_bfloat16*)d_in[4];
    p.logdt = (const __nv_bfloat16*)d_in[5];
    p.dskip = (const __nv_bfloat16*)d_in[6];
    p.wr = (const __nv_bfloat16*)d_in[8];
    p.out = (__nv_bfloat16*)d_out;
    cudaGetSymbolAddress((void**)&p.sc, g_scratch);
    cudaGetSymbolAddress((void**)&p.tab, g_tab);

    void* fn = nullptr;
    cudaDriverEntryPointQueryResult qr;
    cudaGetDriverEntryPoint("cuTensorMapEncodeTiled", &fn, cudaEnableDefault, &qr);
    EncodeFn enc = (EncodeFn)fn;
    CUtensorMap tm_x, tm_g, tm_d;
    const cuuint32_t es[5] = {1, 1, 1, 1, 1};
    {
        const cuuint64_t gd[4] = {1024, 128, 8, 2}, gs[3] = {32768, 4096, 2048};
        const cuuint32_t bx[4] = {16, 64, 4, 1};
        enc(&tm_x, CU_TENSOR_MAP_DATA_TYPE_BFLOAT16, 4, d_in[0], gd, gs, bx, es, CU_TENSOR_MAP_INTERLEAVE_NONE,
            CU_TENSOR_MAP_SWIZZLE_NONE, CU_TENSOR_MAP_L2_PROMOTION_NONE, CU_TENSOR_MAP_FLOAT_OOB_FILL_NONE);
    }
    {
        char *wg = (char*)d_in[9], *wu = (char*)d_in[10];
        p.up_first = wu < wg;
        const cuuint64_t gd[3] = {3584, 1024, 2}, gs[2] = {7168, (cuuint64_t)(p.up_first ? wg - wu : wu - wg)};
        const cuuint32_t bx[3] = {64, 32, 2};
        enc(&tm_g, CU_TENSOR_MAP_DATA_TYPE_BFLOAT16, 3, p.up_first ? wu : wg, gd, gs, bx, es, CU_TENSOR_MAP_INTERLEAVE_NONE,
            CU_TENSOR_MAP_SWIZZLE_128B, CU_TENSOR_MAP_L2_PROMOTION_NONE, CU_TENSOR_MAP_FLOAT_OOB_FILL_NONE);
    }
    {
        const cuuint64_t gd[3] = {1024, 3584, 1}, gs[2] = {2048, 2048 * 3584};
        const cuuint32_t bx[3] = {64, 64, 1};
        enc(&tm_d, CU_TENSOR_MAP_DATA_TYPE_BFLOAT16, 3, d_in[11], gd, gs, bx, es, CU_TENSOR_MAP_INTERLEAVE_NONE,
            CU_TENSOR_MAP_SWIZZLE_128B, CU_TENSOR_MAP_L2_PROMOTION_NONE, CU_TENSOR_MAP_FLOAT_OOB_FILL_NONE);
    }
    cudaFuncSetAttribute(fused_kernel, cudaFuncAttributeMaxDynamicSharedMemorySize, SM_TOTAL + 256);
    fused_kernel<<<128, NTHREADS, SM_TOTAL + 256>>>(p, tm_x, tm_g, tm_d);
}
```

```cpp
#include <cuda_runtime.h>
#include <cuda.h>
#include <cuda_bf16.h>
#include <cuda_fp16.h>
#include <stdint.h>

#define TG(i)
#define TS(i)
#define TSL(i)

#define TSW 0
#define SDELAY 1500
#define EDELAY 800
#define FILL 0x52110
#define PDELAY 600
#define POLL_LD "ld.relaxed.gpu.global.b128"
#define IDEPTH 2

namespace {

constexpr int NTHREADS = 512;
constexpr int SPIN_LIMIT = 1 << 16;

constexpr int SM_SLAB = 0;
constexpr int SM_RING = 32768;
constexpr int SUB     = 1088;
constexpr int SM_K    = SM_RING + 10 * 8192;
constexpr int SM_S    = SM_K + 32 * SUB;
constexpr int SM_U    = SM_S + 32 * SUB;
constexpr int SM_F2   = SM_U + 32 * SUB;
constexpr int SM_XSEL = SM_F2 + 1536;
constexpr int SM_PAIR = SM_XSEL + 4096;
constexpr int SM_H    = SM_PAIR + 2048;
constexpr int SM_KEYS = SM_H + 1024;
constexpr int SM_TOK  = SM_KEYS + 64;
constexpr int SM_FIX  = SM_TOK + 16;
constexpr int SM_XRAW = SM_FIX + 32;
constexpr int SM_SCL  = SM_XRAW + 64;
constexpr int SM_BAR  = SM_SCL + 16;
constexpr int SM_RED  = SM_XSEL;
constexpr int SM_TAB  = SM_RING + 7 * 8192;
constexpr int B_FULL = 0, B_ROW = 24, B_STG = 32, B_SLAB = 36, B_TOK = 38, B_UFREE = 39, B_FIX = 40, B_PAIR = 41,
              B_TAB = 42, B_TFREE = 43, B_KFREE = 44, B_U = 46, B_PEER = 48, NBAR = 52;
constexpr int SM_TOTAL = SM_BAR + NBAR * 8;
static_assert(SM_TOTAL + 256 <= 232448, "smem");
__device__ __forceinline__ uint32_t chunk_off(int n) { return SM_RING + (n < 7 ? n : n - 7) * 16384; }
constexpr int KP = 272;

struct Scratch {
    uint4 stats[1024];
    uint32_t part[128 * 56 * 16];
    uint32_t epoch;
};
__device__ Scratch g_scratch;

struct Params {
    const __nv_bfloat16 *lar, *aim, *cr, *ci, *logdt, *dskip;
    const __nv_bfloat16 *x, *wr;
    __nv_bfloat16* out;
    Scratch* sc;
    const uint4* tab;
    int up_first;
};

__device__ __forceinline__ uint4 ldg128(const void* p) {
    uint4 v; asm volatile("ld.global.nc.v4.u32 {%0,%1,%2,%3}, [%4];" : "=r"(v.x), "=r"(v.y), "=r"(v.z), "=r"(v.w) : "l"(p)); return v;
}
__device__ __forceinline__ uint4 ld_relaxed128(const void* p) {
    uint4 v;
    asm volatile("{ .reg .b128 t; ld.relaxed.gpu.global.b128 t, [%4]; mov.b128 {%0,%1,%2,%3}, t; }"
                 : "=r"(v.x), "=r"(v.y), "=r"(v.z), "=r"(v.w) : "l"(p) : "memory");
    return v;
}
__device__ __forceinline__ void st_relaxed128(void* p, uint4 v) {
    asm volatile("{ .reg .b128 t; mov.b128 t, {%1,%2,%3,%4}; st.relaxed.gpu.global.b128 [%0], t; }"
                 :: "l"(p), "r"(v.x), "r"(v.y), "r"(v.z), "r"(v.w) : "memory");
}
__device__ __forceinline__ void st_relaxed32(void* p, uint32_t v) {
    asm volatile("st.relaxed.gpu.global.u32 [%0], %1;" :: "l"(p), "r"(v) : "memory");
}
__device__ __forceinline__ uint32_t lds32(uint32_t a) { uint32_t v; asm volatile("ld.shared.u32 %0, [%1];" : "=r"(v) : "r"(a)); return v; }
__device__ __forceinline__ uint32_t lds16(uint32_t a) { uint32_t v; asm volatile("ld.shared.u16 %0, [%1];" : "=r"(v) : "r"(a)); return v; }
__device__ __forceinline__ uint2 lds64(uint32_t a) { uint2 v; asm volatile("ld.shared.v2.u32 {%0,%1}, [%2];" : "=r"(v.x), "=r"(v.y) : "r"(a)); return v; }
__device__ __forceinline__ uint4 lds128(uint32_t a) {
    uint4 v; asm volatile("ld.shared.v4.u32 {%0,%1,%2,%3}, [%4];" : "=r"(v.x), "=r"(v.y), "=r"(v.z), "=r"(v.w) : "r"(a)); return v;
}
__device__ __forceinline__ void sts16(uint32_t a, uint32_t v) { asm volatile("st.shared.u16 [%0], %1;" :: "r"(a), "h"((uint16_t)v) : "memory"); }
__device__ __forceinline__ void sts32(uint32_t a, uint32_t v) { asm volatile("st.shared.u32 [%0], %1;" :: "r"(a), "r"(v) : "memory"); }
__device__ __forceinline__ void sts64(uint32_t a, uint32_t x, uint32_t y) { asm volatile("st.shared.v2.u32 [%0], {%1,%2};" :: "r"(a), "r"(x), "r"(y) : "memory"); }
__device__ __forceinline__ void sts128(uint32_t a, uint32_t x, uint32_t y, uint32_t z, uint32_t w) {
    asm volatile("st.shared.v4.u32 [%0], {%1,%2,%3,%4};" :: "r"(a), "r"(x), "r"(y), "r"(z), "r"(w) : "memory");
}
__device__ __forceinline__ void ldsm4(uint32_t a, uint32_t& r0, uint32_t& r1, uint32_t& r2, uint32_t& r3) {
    asm volatile("ldmatrix.sync.aligned.m8n8.x4.shared.b16 {%0,%1,%2,%3}, [%4];" : "=r"(r0), "=r"(r1), "=r"(r2), "=r"(r3) : "r"(a));
}
__device__ __forceinline__ void mma_f16(float (&d)[4], uint32_t a0, uint32_t a1, uint32_t a2, uint32_t a3, uint32_t b0, uint32_t b1) {
    asm("mma.sync.aligned.m16n8k16.row.col.f32.f16.f16.f32 {%0,%1,%2,%3}, {%4,%5,%6,%7}, {%8,%9}, {%0,%1,%2,%3};"
        : "+f"(d[0]), "+f"(d[1]), "+f"(d[2]), "+f"(d[3]) : "r"(a0), "r"(a1), "r"(a2), "r"(a3), "r"(b0), "r"(b1));
}
__device__ __forceinline__ void mma_bf16(float (&d)[4], uint32_t a0, uint32_t a1, uint32_t a2, uint32_t a3, uint32_t b0, uint32_t b1) {
    asm("mma.sync.aligned.m16n8k16.row.col.f32.bf16.bf16.f32 {%0,%1,%2,%3}, {%4,%5,%6,%7}, {%8,%9}, {%0,%1,%2,%3};"
        : "+f"(d[0]), "+f"(d[1]), "+f"(d[2]), "+f"(d[3]) : "r"(a0), "r"(a1), "r"(a2), "r"(a3), "r"(b0), "r"(b1));
}
__device__ __forceinline__ uint32_t prmt(uint32_t a, uint32_t b, uint32_t s) { uint32_t d; asm("prmt.b32 %0, %1, %2, %3;" : "=r"(d) : "r"(a), "r"(b), "r"(s)); return d; }
__device__ __forceinline__ uint32_t pack_h(float lo, float hi) { uint32_t d; asm("cvt.rn.f16x2.f32 %0, %1, %2;" : "=r"(d) : "f"(hi), "f"(lo)); return d; }
__device__ __forceinline__ uint32_t pack_b(float lo, float hi) { uint32_t d; asm("cvt.rn.bf16x2.f32 %0, %1, %2;" : "=r"(d) : "f"(hi), "f"(lo)); return d; }
__device__ __forceinline__ float blo(uint32_t v) { return __uint_as_float(v << 16); }
__device__ __forceinline__ float bhi(uint32_t v) { return __uint_as_float(v & 0xFFFF0000u); }
__device__ __forceinline__ float rb(float v) { return blo(pack_b(v, v)); }
__device__ __forceinline__ uint32_t bsub2(uint32_t a, uint32_t b) { uint32_t d; asm("sub.rn.bf16x2 %0, %1, %2;" : "=r"(d) : "r"(a), "r"(b)); return d; }
__device__ __forceinline__ uint32_t badd2(uint32_t a, uint32_t b) { uint32_t d; asm("add.rn.bf16x2 %0, %1, %2;" : "=r"(d) : "r"(a), "r"(b)); return d; }
__device__ __forceinline__ uint32_t bmul2(uint32_t a, uint32_t b) { uint32_t d; asm("mul.rn.bf16x2 %0, %1, %2;" : "=r"(d) : "r"(a), "r"(b)); return d; }
__device__ __forceinline__ uint32_t bfma2(uint32_t a, uint32_t b, uint32_t c) { uint32_t d; asm("fma.rn.bf16x2 %0, %1, %2, %3;" : "=r"(d) : "r"(a), "r"(b), "r"(c)); return d; }
__device__ __forceinline__ uint32_t dup_lo(uint32_t v) { uint32_t d; asm("{ .reg .b16 l, h; mov.b32 {l, h}, %1; mov.b32 %0, {l, l}; }" : "=r"(d) : "r"(v)); return d; }
__device__ __forceinline__ uint32_t dup_hi(uint32_t v) { uint32_t d; asm("{ .reg .b16 l, h; mov.b32 {l, h}, %1; mov.b32 %0, {h, h}; }" : "=r"(d) : "r"(v)); return d; }
__device__ __forceinline__ uint32_t norm2(uint32_t x, uint32_t m, uint32_t hi, uint32_t lo) {
    uint32_t a = bsub2(x, m);
    return bfma2(a, hi, bmul2(a, lo));
}
__device__ __forceinline__ float ex2(float v) { float d; asm("ex2.approx.ftz.f32 %0, %1;" : "=f"(d) : "f"(v)); return d; }
__device__ __forceinline__ float rcp(float v) { float d; asm("rcp.approx.ftz.f32 %0, %1;" : "=f"(d) : "f"(v)); return d; }
__device__ __forceinline__ float sigmoidf_(float v) { return rcp(1.0f + ex2(-1.4426950408889634f * v)); }
__device__ __forceinline__ float siluf_(float v) { return v * sigmoidf_(v); }

__device__ __forceinline__ void mbar_init(uint32_t a, int n) { asm volatile("mbarrier.init.shared::cta.b64 [%0], %1;" :: "r"(a), "r"(n) : "memory"); }
__device__ __forceinline__ void mbar_expect(uint32_t a, int tx) { asm volatile("mbarrier.arrive.expect_tx.shared::cta.b64 _, [%0], %1;" :: "r"(a), "r"(tx) : "memory"); }
__device__ __forceinline__ void mbar_arrive(uint32_t a) { asm volatile("mbarrier.arrive.shared::cta.b64 _, [%0];" :: "r"(a) : "memory"); }
__device__ __forceinline__ bool mbar_try(uint32_t a) {
    uint32_t d; asm volatile("{ .reg .pred p; mbarrier.try_wait.parity.shared::cta.b64 p, [%1], 0; selp.u32 %0, 1, 0, p; }" : "=r"(d) : "r"(a) : "memory"); return d;
}
__device__ __forceinline__ void mbar_wait(uint32_t a) {
    if (__builtin_expect(!mbar_try(a), 0)) {
        int n = SPIN_LIMIT;
        while (!mbar_try(a) && --n) {}
    }
}
__device__ __forceinline__ void mbar_arrive_peer(uint32_t a) { asm volatile("mbarrier.arrive.relaxed.cluster.shared::cluster.b64 _, [%0];" :: "r"(a) : "memory"); }
__device__ __forceinline__ uint32_t mapa(uint32_t a, uint32_t rank) { uint32_t d; asm("mapa.shared::cluster.u32 %0, %1, %2;" : "=r"(d) : "r"(a), "r"(rank)); return d; }
__device__ __forceinline__ void st_async2(uint32_t a, uint32_t x, uint32_t y, uint32_t bar) {
    asm volatile("st.async.weak.shared::cluster.mbarrier::complete_tx::bytes.v2.b32 [%0], {%1,%2}, [%3];" :: "r"(a), "r"(x), "r"(y), "r"(bar) : "memory");
}
__device__ __forceinline__ void st_async4(uint32_t a, uint32_t x, uint32_t y, uint32_t z, uint32_t w, uint32_t bar) {
    asm volatile("st.async.weak.shared::cluster.mbarrier::complete_tx::bytes.v4.b32 [%0], {%1,%2,%3,%4}, [%5];"
                 :: "r"(a), "r"(x), "r"(y), "r"(z), "r"(w), "r"(bar) : "memory");
}
__device__ __forceinline__ void stsm4(uint32_t a, uint32_t r0, uint32_t r1, uint32_t r2, uint32_t r3) {
    asm volatile("stmatrix.sync.aligned.m8n8.x4.shared.b16 [%0], {%1,%2,%3,%4};" :: "r"(a), "r"(r0), "r"(r1), "r"(r2), "r"(r3) : "memory");
}
__device__ __forceinline__ void proxy_fence() { asm volatile("fence.proxy.async.shared::cta;" ::: "memory"); }
__device__ __forceinline__ void bar_sync(int id, int n) { asm volatile("bar.sync %0, %1;" :: "r"(id), "r"(n) : "memory"); }
__device__ __forceinline__ void bar_arrive(int id, int n) { asm volatile("bar.arrive %0, %1;" :: "r"(id), "r"(n) : "memory"); }
__device__ __forceinline__ void cluster_arrive() { asm volatile("barrier.cluster.arrive.relaxed.aligned;" ::: "memory"); }
__device__ __forceinline__ void cluster_wait() { asm volatile("barrier.cluster.wait.aligned;" ::: "memory"); }
__device__ __forceinline__ void tma3d(uint32_t dst, const CUtensorMap* tm, int c0, int c1, int c2, uint32_t bar, uint64_t pol) {
    asm volatile("cp.async.bulk.tensor.3d.shared::cluster.global.mbarrier::complete_tx::bytes.L2::cache_hint [%0], [%1, {%3, %4, %6}], [%2], %5;"
                 :: "r"(dst), "l"(tm), "r"(bar), "r"(c0), "r"(c1), "l"(pol), "r"(c2) : "memory");
}
__device__ __forceinline__ bool elect() {
    uint32_t p; asm volatile("{ .reg .pred p; elect.sync _|p, 0xFFFFFFFF; selp.u32 %0, 1, 0, p; }" : "=r"(p)); return p;
}

struct cf { float r, i; };
__device__ __forceinline__ cf cmul(cf a, cf b) { return {a.r * b.r - a.i * b.i, a.r * b.i + a.i * b.r}; }
__device__ __forceinline__ cf csq(cf a) { return {a.r * a.r - a.i * a.i, (a.r + a.r) * a.i}; }
__device__ __forceinline__ cf cexp_(float a2, float b) { float m = ex2(a2); return {m * __cosf(b), m * __sinf(b)}; }
struct hc { uint32_t r, i; };
__device__ __forceinline__ hc pk(cf a, cf b) { return {pack_h(a.r, b.r), pack_h(a.i, b.i)}; }
__device__ __forceinline__ hc hmulc(hc a, hc b) {
    const __half2 ar = *reinterpret_cast<__half2*>(&a.r), ai = *reinterpret_cast<__half2*>(&a.i);
    const __half2 br = *reinterpret_cast<__half2*>(&b.r), bi = *reinterpret_cast<__half2*>(&b.i);
    const __half2 r = __hfma2(ar, br, __hneg2(__hmul2_rn(ai, bi))), i = __hfma2(ar, bi, __hmul2_rn(ai, br));
    return {*reinterpret_cast<const uint32_t*>(&r), *reinterpret_cast<const uint32_t*>(&i)};
}
__device__ __forceinline__ void sth(uint32_t a, hc v) { sts32(a, v.r); sts32(a + 128, v.i); }
__device__ __forceinline__ uint32_t cpy(uint32_t v, uint32_t z) { uint32_t d; asm("xor.b32 %0, %1, %2;" : "=r"(d) : "r"(v), "r"(z)); return d; }
__device__ __forceinline__ void sched_fence() { asm volatile("pmevent 0;" ::: "memory"); }
__device__ __forceinline__ float tanh_(float v) { float d; asm("tanh.approx.f32 %0, %1;" : "=f"(d) : "f"(v)); return d; }
__device__ __forceinline__ float silu2(float h) {
    return h * rcp(fmaf(ex2(-2.8853900817779268f * h), 0.5f, 0.5f));
}
__device__ __forceinline__ uint32_t hfma2_(uint32_t a, uint32_t b, uint32_t c) { uint32_t d; asm("fma.rn.f16x2 %0, %1, %2, %3;" : "=r"(d) : "r"(a), "r"(b), "r"(c)); return d; }
__device__ __forceinline__ uint32_t hfms2_(uint32_t a, uint32_t b, uint32_t c) {
    uint32_t d; asm("{ .reg .b32 t; neg.f16x2 t, %1; fma.rn.f16x2 %0, t, %2, %3; }" : "=r"(d) : "r"(a), "r"(b), "r"(c)); return d;
}

__device__ __forceinline__ uint64_t bdesc(uint32_t addr, uint32_t sbo) {
    return (uint64_t)((addr & 0x3FFFFu) >> 4) | ((uint64_t)(128 >> 4) << 16) | ((uint64_t)(sbo >> 4) << 32);
}
__device__ __forceinline__ void wg_h(uint32_t (&d)[16], const uint32_t* a, const uint32_t* b, uint64_t d0, uint64_t d1, uint64_t d2, uint64_t d3) {
    asm volatile(
        "wgmma.mma_async.sync.aligned.m64n64k16.f16.f16.f16 {%0,%1,%2,%3,%4,%5,%6,%7,%8,%9,%10,%11,%12,%13,%14,%15}, {%16,%17,%18,%19}, %32, 0, 1, 1, 1;\n"
        "wgmma.mma_async.sync.aligned.m64n64k16.f16.f16.f16 {%0,%1,%2,%3,%4,%5,%6,%7,%8,%9,%10,%11,%12,%13,%14,%15}, {%20,%21,%22,%23}, %33, 1, 1, 1, 1;\n"
        "wgmma.mma_async.sync.aligned.m64n64k16.f16.f16.f16 {%0,%1,%2,%3,%4,%5,%6,%7,%8,%9,%10,%11,%12,%13,%14,%15}, {%24,%25,%26,%27}, %34, 1, 1, 1, 1;\n"
        "wgmma.mma_async.sync.aligned.m64n64k16.f16.f16.f16 {%0,%1,%2,%3,%4,%5,%6,%7,%8,%9,%10,%11,%12,%13,%14,%15}, {%28,%29,%30,%31}, %35, 1, 1, 1, 1;\n"
        : "=r"(d[0]), "=r"(d[1]), "=r"(d[2]), "=r"(d[3]), "=r"(d[4]), "=r"(d[5]), "=r"(d[6]), "=r"(d[7]), "=r"(d[8]), "=r"(d[9]), "=r"(d[10]), "=r"(d[11]), "=r"(d[12]), "=r"(d[13]), "=r"(d[14]), "=r"(d[15])
        : "r"(a[0]), "r"(a[1]), "r"(a[2]), "r"(a[3]), "r"(a[4]), "r"(a[5]), "r"(a[6]), "r"(a[7]), "r"(b[0]), "r"(b[1]), "r"(b[2]), "r"(b[3]), "r"(b[4]), "r"(b[5]), "r"(b[6]), "r"(b[7]), "l"(d0), "l"(d1), "l"(d2), "l"(d3));
}
__device__ __forceinline__ void wg_f0(float (&d)[32], const uint32_t* a, const uint32_t* b, uint64_t d0, uint64_t d1, uint64_t d2, uint64_t d3) {
    asm volatile(
        "wgmma.mma_async.sync.aligned.m64n64k16.f32.f16.f16 {%0,%1,%2,%3,%4,%5,%6,%7,%8,%9,%10,%11,%12,%13,%14,%15,%16,%17,%18,%19,%20,%21,%22,%23,%24,%25,%26,%27,%28,%29,%30,%31}, {%32,%33,%34,%35}, %48, 0, 1, 1, 1;\n"
        "wgmma.mma_async.sync.aligned.m64n64k16.f32.f16.f16 {%0,%1,%2,%3,%4,%5,%6,%7,%8,%9,%10,%11,%12,%13,%14,%15,%16,%17,%18,%19,%20,%21,%22,%23,%24,%25,%26,%27,%28,%29,%30,%31}, {%36,%37,%38,%39}, %49, 1, 1, 1, 1;\n"
        "wgmma.mma_async.sync.aligned.m64n64k16.f32.f16.f16 {%0,%1,%2,%3,%4,%5,%6,%7,%8,%9,%10,%11,%12,%13,%14,%15,%16,%17,%18,%19,%20,%21,%22,%23,%24,%25,%26,%27,%28,%29,%30,%31}, {%40,%41,%42,%43}, %50, 1, 1, 1, 1;\n"
        "wgmma.mma_async.sync.aligned.m64n64k16.f32.f16.f16 {%0,%1,%2,%3,%4,%5,%6,%7,%8,%9,%10,%11,%12,%13,%14,%15,%16,%17,%18,%19,%20,%21,%22,%23,%24,%25,%26,%27,%28,%29,%30,%31}, {%44,%45,%46,%47}, %51, 1, 1, 1, 1;\n"
        : "=f"(d[0]), "=f"(d[1]), "=f"(d[2]), "=f"(d[3]), "=f"(d[4]), "=f"(d[5]), "=f"(d[6]), "=f"(d[7]), "=f"(d[8]), "=f"(d[9]), "=f"(d[10]), "=f"(d[11]), "=f"(d[12]), "=f"(d[13]), "=f"(d[14]), "=f"(d[15]), "=f"(d[16]), "=f"(d[17]), "=f"(d[18]), "=f"(d[19]), "=f"(d[20]), "=f"(d[21]), "=f"(d[22]), "=f"(d[23]), "=f"(d[24]), "=f"(d[25]), "=f"(d[26]), "=f"(d[27]), "=f"(d[28]), "=f"(d[29]), "=f"(d[30]), "=f"(d[31])
        : "r"(a[0]), "r"(a[1]), "r"(a[2]), "r"(a[3]), "r"(a[4]), "r"(a[5]), "r"(a[6]), "r"(a[7]), "r"(b[0]), "r"(b[1]), "r"(b[2]), "r"(b[3]), "r"(b[4]), "r"(b[5]), "r"(b[6]), "r"(b[7]), "l"(d0), "l"(d1), "l"(d2), "l"(d3));
}
__device__ __forceinline__ void wg_f1(float (&d)[32], const uint32_t* a, const uint32_t* b, uint64_t d0, uint64_t d1, uint64_t d2, uint64_t d3) {
    asm volatile(
        "wgmma.mma_async.sync.aligned.m64n64k16.f32.f16.f16 {%0,%1,%2,%3,%4,%5,%6,%7,%8,%9,%10,%11,%12,%13,%14,%15,%16,%17,%18,%19,%20,%21,%22,%23,%24,%25,%26,%27,%28,%29,%30,%31}, {%32,%33,%34,%35}, %48, 1, 1, 1, 1;\n"
        "wgmma.mma_async.sync.aligned.m64n64k16.f32.f16.f16 {%0,%1,%2,%3,%4,%5,%6,%7,%8,%9,%10,%11,%12,%13,%14,%15,%16,%17,%18,%19,%20,%21,%22,%23,%24,%25,%26,%27,%28,%29,%30,%31}, {%36,%37,%38,%39}, %49, 1, 1, 1, 1;\n"
        "wgmma.mma_async.sync.aligned.m64n64k16.f32.f16.f16 {%0,%1,%2,%3,%4,%5,%6,%7,%8,%9,%10,%11,%12,%13,%14,%15,%16,%17,%18,%19,%20,%21,%22,%23,%24,%25,%26,%27,%28,%29,%30,%31}, {%40,%41,%42,%43}, %50, 1, 1, 1, 1;\n"
        "wgmma.mma_async.sync.aligned.m64n64k16.f32.f16.f16 {%0,%1,%2,%3,%4,%5,%6,%7,%8,%9,%10,%11,%12,%13,%14,%15,%16,%17,%18,%19,%20,%21,%22,%23,%24,%25,%26,%27,%28,%29,%30,%31}, {%44,%45,%46,%47}, %51, 1, 1, 1, 1;\n"
        : "+f"(d[0]), "+f"(d[1]), "+f"(d[2]), "+f"(d[3]), "+f"(d[4]), "+f"(d[5]), "+f"(d[6]), "+f"(d[7]), "+f"(d[8]), "+f"(d[9]), "+f"(d[10]), "+f"(d[11]), "+f"(d[12]), "+f"(d[13]), "+f"(d[14]), "+f"(d[15]), "+f"(d[16]), "+f"(d[17]), "+f"(d[18]), "+f"(d[19]), "+f"(d[20]), "+f"(d[21]), "+f"(d[22]), "+f"(d[23]), "+f"(d[24]), "+f"(d[25]), "+f"(d[26]), "+f"(d[27]), "+f"(d[28]), "+f"(d[29]), "+f"(d[30]), "+f"(d[31])
        : "r"(a[0]), "r"(a[1]), "r"(a[2]), "r"(a[3]), "r"(a[4]), "r"(a[5]), "r"(a[6]), "r"(a[7]), "r"(b[0]), "r"(b[1]), "r"(b[2]), "r"(b[3]), "r"(b[4]), "r"(b[5]), "r"(b[6]), "r"(b[7]), "l"(d0), "l"(d1), "l"(d2), "l"(d3));
}
__device__ __forceinline__ void wg_s(uint32_t* d, const uint32_t* a, const uint32_t* b, uint64_t d0, uint64_t d1) {
    asm volatile(
        "wgmma.mma_async.sync.aligned.m64n32k16.f16.f16.f16 {%0,%1,%2,%3,%4,%5,%6,%7}, {%8,%9,%10,%11}, %16, 0, 1, 1, 1;\n"
        "wgmma.mma_async.sync.aligned.m64n32k16.f16.f16.f16 {%0,%1,%2,%3,%4,%5,%6,%7}, {%12,%13,%14,%15}, %17, 1, 1, 1, 1;\n"
        : "=r"(d[0]), "=r"(d[1]), "=r"(d[2]), "=r"(d[3]), "=r"(d[4]), "=r"(d[5]), "=r"(d[6]), "=r"(d[7])
        : "r"(a[0]), "r"(a[1]), "r"(a[2]), "r"(a[3]), "r"(b[0]), "r"(b[1]), "r"(b[2]), "r"(b[3]), "l"(d0), "l"(d1));
}
template <int ACC> __device__ __forceinline__ void wg_w(float (&d)[4], uint64_t da, uint64_t db) {
    asm volatile("wgmma.mma_async.sync.aligned.m64n8k16.f32.bf16.bf16 {%0,%1,%2,%3}, %4, %5, %6, 1, 1, 1, 0;"
                 : "+f"(d[0]), "+f"(d[1]), "+f"(d[2]), "+f"(d[3]) : "l"(da), "l"(db), "n"(ACC));
}
__device__ __forceinline__ void wg_w0(float (&d)[4], uint64_t da, uint64_t db) {
    asm volatile("wgmma.mma_async.sync.aligned.m64n8k16.f32.bf16.bf16 {%0,%1,%2,%3}, %4, %5, 0, 1, 1, 1, 0;"
                 : "=f"(d[0]), "=f"(d[1]), "=f"(d[2]), "=f"(d[3]) : "l"(da), "l"(db));
}
__device__ __forceinline__ void wg_fence() { asm volatile("wgmma.fence.sync.aligned;" ::: "memory"); }
__device__ __forceinline__ void wg_commit() { asm volatile("wgmma.commit_group.sync.aligned;" ::: "memory"); }
template <int N> __device__ __forceinline__ void wg_wait() { asm volatile("wgmma.wait_group.sync.aligned %0;" :: "n"(N) : "memory"); }
__device__ __forceinline__ void touch(uint32_t& r) { asm volatile("" : "+r"(r) :: "memory"); }
__device__ __forceinline__ void touch(float& r) { asm volatile("" : "+f"(r) :: "memory"); }
template <class T, int N> __device__ __forceinline__ void touch(T (&r)[N]) {
#pragma unroll
    for (int i = 0; i < N; i++) touch(r[i]);
}

__global__ void __cluster_dims__(2, 1, 1) __launch_bounds__(NTHREADS, 1)
fused_kernel(const Params p, const __grid_constant__ CUtensorMap tm_x, const __grid_constant__ CUtensorMap tm_g,
             const __grid_constant__ CUtensorMap tm_d)
{
    extern __shared__ __align__(1024) uint8_t smem_raw[];
    const uint32_t sm = (uint32_t)__cvta_generic_to_shared(smem_raw);
    const uint32_t bars = sm + SM_BAR;
    const int tid = threadIdx.x, lane = tid & 31;
    const int g = lane >> 2, q = lane & 3;
    const int c = blockIdx.x, rank = c & 1, G = c >> 1;

    if (tid < 256) {
        uint2 lar4, aim4, cr4, ci4;
        uint32_t ldt_raw, dsk_raw;
        {
            const uint32_t i = c * 256 + tid;
            asm volatile("ld.global.nc.v2.u32 {%0,%1}, [%10]; ld.global.nc.v2.u32 {%2,%3}, [%11]; ld.global.nc.u16 %8, [%14];\n"
                         "ld.global.nc.v2.u32 {%4,%5}, [%12]; ld.global.nc.v2.u32 {%6,%7}, [%13]; ld.global.nc.u16 %9, [%15];"
                         : "=r"(lar4.x), "=r"(lar4.y), "=r"(aim4.x), "=r"(aim4.y), "=r"(cr4.x), "=r"(cr4.y), "=r"(ci4.x), "=r"(ci4.y), "=r"(ldt_raw), "=r"(dsk_raw)
                         : "l"(p.lar + i * 4), "l"(p.aim + i * 4), "l"(p.cr + i * 4), "l"(p.ci + i * 4), "l"(p.logdt + (i >> 5)), "l"(p.dskip + (i >> 5)));
        }
        cluster_arrive();
        sched_fence();
        const int warp = __shfl_sync(0xFFFFFFFFu, tid >> 5, 0);
        const float logdt = blo(ldt_raw), dsk = blo(dsk_raw);
        asm volatile("setmaxnreg.inc.sync.aligned.u32 168;");
        {
            const uint32_t z = (uint32_t)(uintptr_t)p.lar & 1;
            lar4.x = cpy(lar4.x, z); lar4.y = cpy(lar4.y, z); aim4.x = cpy(aim4.x, z); aim4.y = cpy(aim4.y, z);
            cr4.x = cpy(cr4.x, z); cr4.y = cpy(cr4.y, z); ci4.x = cpy(ci4.x, z); ci4.y = cpy(ci4.y, z);
        }
        const int wgi = warp >> 2, w = warp & 3;
        const uint32_t wb = sm + SM_K + (w < 2 ? 16 * w + 8 * wgi : 16 + 16 * wgi + 8 * w) * SUB;
        sth(wb + lane * 4, hc{0x3C003C00u, 0u});

        const float dt = rb(expf(logdt));
        float outscale, cs, dn;
        {
            uint32_t m0 = __vmaxu2(__vmaxu2(cr4.x & 0x7FFF7FFFu, cr4.y & 0x7FFF7FFFu), __vmaxu2(ci4.x & 0x7FFF7FFFu, ci4.y & 0x7FFF7FFFu));
            uint32_t m1 = max(m0 & 0xFFFFu, m0 >> 16);
            float cmax = blo(__reduce_max_sync(0xFFFFFFFFu, m1));
            const float sc = fminf(fmaxf(fmaxf(2.0f * dt * cmax, fabsf(dsk) * (1.0f / 1024.0f)), 1e-30f), 1e30f);
            outscale = __uint_as_float(__float_as_uint(sc) & 0x7F800000u);
            const float inv = __uint_as_float(0x7F000000u - __float_as_uint(outscale));
            cs = 2.0f * dt * inv;
            dn = dsk * inv;
        }
        if (warp == TSW) TSL(39);
        uint32_t fc[16], fs[16], ta[4], tb[4];
        float kacc[2][3][4];
#pragma unroll
        for (int i = 0; i < 2; i++)
#pragma unroll
            for (int j = 0; j < 3; j++) kacc[i][j][0] = kacc[i][j][1] = kacc[i][j][2] = kacc[i][j][3] = 0.f;
        if (lane == 0) kacc[0][0][0] = dn;
        {
            const uint32_t st = wb + lane * 4;
            const uint32_t zk = lds32(wb + 128);
            const uint32_t la = wb + ((lane & 8) ? 29 : (lane & 7)) * KP + (lane >> 4) * 128;
            const uint32_t lo = wb + ((lane >> 3) & 1) * 128 + (lane >> 4) * 16;
            const uint32_t lb = lo + (8 + (lane & 7)) * KP, lb2 = lo + (24 + min(lane & 7, 4)) * KP, lm = lo + 30 * KP;
#pragma unroll 1
            for (int s = 0; s < 2; s++) {
                const uint32_t wl = s ? lar4.y : lar4.x, wa = s ? aim4.y : aim4.x, wr_ = s ? cr4.y : cr4.x, wi = s ? ci4.y : ci4.x;
                const uint32_t ea = pack_b(ex2(blo(wl) * 1.4426950408889634f), ex2(bhi(wl) * 1.4426950408889634f));
                const float a2[2] = {-(blo(ea) * dt) * 1.4426950408889634f, -(bhi(ea) * dt) * 1.4426950408889634f};
                const float b[2] = {blo(wa) * dt, bhi(wa) * dt};
                {
                    cf z8[2], z16[2], z32[2], z64[2], z128[2];
#pragma unroll
                    for (int e = 0; e < 2; e++) {
                        z8[e] = cexp_(a2[e] * 8.f, b[e] * 8.f);
                        z16[e] = csq(z8[e]); z32[e] = csq(z16[e]); z64[e] = csq(z32[e]); z128[e] = csq(z64[e]);
                    }
                    const hc r1 = pk(z8[0], z8[1]), r2 = pk(z16[0], z16[1]), r3 = hmulc(r1, r2), r4 = pk(z32[0], z32[1]);
                    sth(st + 1 * KP, r1); sth(st + 2 * KP, r2); sth(st + 3 * KP, r3); sth(st + 4 * KP, r4);
                    sth(st + 5 * KP, hmulc(r1, r4)); sth(st + 6 * KP, hmulc(r2, r4)); sth(st + 7 * KP, hmulc(r3, r4));
                    sth(st + 29 * KP, pk(z64[0], z64[1])); sth(st + 30 * KP, pk(z128[0], z128[1]));
                }
                {
                    cf C[2], z2[2], z4[2], v2[2], v4[2], c1[2], d1[2];
#pragma unroll
                    for (int e = 0; e < 2; e++) {
                        C[e] = {(e ? bhi(wr_) : blo(wr_)) * cs, (e ? bhi(wi) : blo(wi)) * -cs};
                        const cf z = cexp_(a2[e], -b[e]);
                        const cf v = cexp_(a2[e] * 256.f, b[e] * -256.f);
                        z2[e] = csq(z); z4[e] = csq(z2[e]); v2[e] = csq(v); v4[e] = csq(v2[e]);
                        c1[e] = cmul(C[e], z); d1[e] = cmul(C[e], v);
                    }
                    const hc l0 = pk(C[0], C[1]), l1 = pk(c1[0], c1[1]), e1 = pk(d1[0], d1[1]);
                    const hc h = pk(z2[0], z2[1]), f = pk(z4[0], z4[1]), w = pk(v2[0], v2[1]), y = pk(v4[0], v4[1]);
                    const hc l2 = hmulc(l0, h), l3 = hmulc(l1, h), e2 = hmulc(l0, w), e3 = hmulc(e1, w), e4 = hmulc(l0, y), g2 = hmulc(e1, h);
                    sth(st + 8 * KP, l0); sth(st + 9 * KP, l1); sth(st + 10 * KP, l2); sth(st + 11 * KP, l3);
                    sth(st + 12 * KP, hmulc(l0, f)); sth(st + 13 * KP, hmulc(l1, f)); sth(st + 14 * KP, hmulc(l2, f)); sth(st + 15 * KP, hmulc(l3, f));
                    sth(st + 16 * KP, e1);
                    sth(st + 17 * KP, g2);
                    sth(st + 18 * KP, hmulc(e1, f));
                    sth(st + 19 * KP, hmulc(g2, f));
                    sth(st + 20 * KP, e2);
                    sth(st + 21 * KP, hmulc(e2, f));
                    sth(st + 22 * KP, e3);
                    sth(st + 23 * KP, hmulc(e3, f));
                    sth(st + 24 * KP, e4);
                    sth(st + 25 * KP, hmulc(e1, y));
                    sth(st + 26 * KP, hmulc(e2, y));
                    sth(st + 27 * KP, hmulc(e3, y));
                    sth(st + 28 * KP, hmulc(e4, y));
                }
                __syncwarp();
                if (warp == TSW && s == 0) TSL(27);
                if (s == 1 && lane == 0) mbar_arrive(bars + B_TFREE * 8 + (tb[3] & zk));
#pragma unroll
                for (int kp = 0; kp < 4; kp++) {
                    uint32_t bb[3][4], m2[4];
                    ldsm4(lm + kp * 32, m2[0], m2[1], m2[2], m2[3]);
                    ldsm4(lb + kp * 32, bb[0][0], bb[0][1], bb[0][2], bb[0][3]);
                    ldsm4(lb + 8 * KP + kp * 32, bb[1][0], bb[1][1], bb[1][2], bb[1][3]);
                    ldsm4(lb2 + kp * 32, bb[2][0], bb[2][1], bb[2][2], bb[2][3]);
#pragma unroll
                    for (int k2 = 0; k2 < 2; k2++) {
                        hc v0, m1;
                        ldsm4(la + kp * 32 + k2 * 16, v0.r, m1.r, v0.i, m1.i);
                        const hc mm = {m2[2 * k2], m2[2 * k2 + 1]};
                        const hc v1 = hmulc(v0, m1), v2 = hmulc(v0, mm), v3 = hmulc(v1, mm);
                        v0.r = cpy(v0.r, zk); v0.i = cpy(v0.i, zk);
#pragma unroll
                        for (int nt = 0; nt < 3; nt++) {
                            mma_f16(kacc[0][nt], v0.r, v1.r, v0.i, v1.i, bb[nt][2 * k2], bb[nt][2 * k2 + 1]);
                            mma_f16(kacc[1][nt], v2.r, v3.r, v2.i, v3.i, bb[nt][2 * k2], bb[nt][2 * k2 + 1]);
                        }
                    }
                }
                __syncwarp();
                if (warp == TSW) TSL(s ? 40 : 33);
                if (s == 0) {
                    cluster_wait();
                    mbar_wait(bars + B_TAB * 8);
#pragma unroll
                    for (int i = 0; i < 10; i++) {
                        const uint4 u = lds128(sm + SM_TAB + i * 2048 + (tid & 127) * 16);
                        uint32_t* t = i < 4 ? fc + 4 * i : i < 8 ? fs + 4 * (i - 4) : i == 8 ? ta : tb;
                        t[0] = u.x; t[1] = u.y; t[2] = u.z; t[3] = u.w;
                    }
                }
            }
        }
        TSL(1);
        bar_sync(10 + wgi, 128);
        {
            const uint32_t tb_ = sm + SM_S + (16 * wgi + w) * SUB;
            const uint32_t seg = sm + SM_K + (2 * warp + (lane & 1)) * SUB + (lane >> 1) * 16;
            uint32_t v0[4];
#pragma unroll
            for (int m = 0; m < 4; m++) {
                constexpr float S = 1.0f / 512.0f;
                const float (&k0)[4] = kacc[m >> 1][0], (&k1)[4] = kacc[m >> 1][1], (&k2)[4] = kacc[m >> 1][2];
                const int R = 8 * m + g, o = 2 * (m & 1);
                v0[m] = pack_h(k0[o] * S, k0[o + 1] * S);
                sts32(tb_ + (q < 2 ? 4 * R + 2 * q : 64 * q + 2 * R) * 2, pack_h(k1[o] * S, k1[o + 1] * S));
                const uint32_t v2 = pack_h(k2[o] * S, k2[o + 1] * S);
                if (q < 2 || (m == 0 && lane == 2)) sts16(tb_ + (256 + 64 * q + R) * 2, v2);
                if (q < 2) sts16(tb_ + (288 + 64 * q + R) * 2, v2 >> 16);
            }
            stsm4(seg, v0[0], v0[1], v0[2], v0[3]);
            if (lane == 0) sts16(sm + SM_SCL + warp * 2, __float_as_uint(32768.0f * outscale) >> 16);
            __syncwarp();
            const uint2 l1 = lds64(tb_ + lane * 8);
            const uint32_t l1n = lds16(tb_ + lane * 8 + 8);
            uint32_t l2[2], l2n[2], l3[4], l3n[4];
#pragma unroll
            for (int i = 0; i < 2; i++) { l2[i] = lds32(tb_ + 256 + i * 128 + lane * 4); l2n[i] = lds16(tb_ + 260 + i * 128 + lane * 4); }
#pragma unroll
            for (int i = 0; i < 4; i++) { l3[i] = lds16(tb_ + 512 + i * 64 + lane * 2); l3n[i] = lds16(tb_ + 514 + i * 64 + lane * 2); }
            sts128(seg + 256, prmt(l1.x, 0, 0x1010), prmt(l1.x, l1.y, 0x5432), prmt(l1.y, 0, 0x1010), prmt(l1.y, l1n, 0x5432));
#pragma unroll
            for (int i = 0; i < 2; i++) sts128(seg + 512 + i * 256, prmt(l2[i], 0, 0x1010), l2[i], prmt(l2[i], 0, 0x3232), prmt(l2n[i], 0, 0x1010));
            const uint32_t s3 = (lane & 1) ? 0x5454 : 0x5410;
#pragma unroll
            for (int i = 0; i < 4; i++) {
                const uint32_t vv = prmt(l3[i], 0, 0x1010);
                sts128(seg + 16 * SUB + i * 256, vv, vv, prmt(l3[i], l3n[i], s3), prmt(l3n[i], 0, 0x1010));
            }
        }
        proxy_fence();
        TSL(2);
        bar_sync(10 + wgi, 128);
        const uint64_t dre = bdesc(sm + SM_F2 + 512, 256), dim = bdesc(sm + SM_F2, 256);
        uint32_t k0[32], k1[32];
#pragma unroll
        for (int b = 0; b < 2; b++) {
            const uint64_t d1 = bdesc(sm + SM_K + (16 * b + 8 * wgi) * SUB, SUB);
            uint32_t re[16], im[16];
            if (b == 0 && wgi == 1) bar_sync(5, 256);
            wg_fence();
            wg_h(re, fc, fc + 8, d1, d1 + 16, d1 + 32, d1 + 48);
            wg_h(im, fs, fs + 8, d1, d1 + 16, d1 + 32, d1 + 48);
            wg_commit();
            if (b == 0 && wgi == 0) bar_arrive(5, 256);
            wg_wait<0>();
            touch(re); touch(im);
            if (b == 1 && lane == 0) mbar_arrive(bars + B_KFREE * 8);
            uint32_t (&kk)[32] = b ? k1 : k0;
#pragma unroll
            for (int hh = 0; hh < 2; hh++) {
#pragma unroll
                for (int i = 8 * hh; i < 8 * hh + 8; i++) {
                    re[i] = hfma2_(ta[i & 3], im[i], re[i]); im[i] = hfms2_(tb[i & 3], re[i], im[i]); re[i] = hfma2_(ta[i & 3], im[i], re[i]);
                }
                wg_fence();
                wg_s(kk + 16 * hh, re + 8 * hh, im + 8 * hh, dre, dim);
                wg_s(kk + 16 * hh + 8, re + 8 * hh + 4, im + 8 * hh + 4, dre, dim);
                wg_commit();
            }
            wg_wait<0>();
            touch(kk);
        }
        if (warp == TSW) TSL(35);
        asm volatile("setmaxnreg.inc.sync.aligned.u32 184;");
        touch(k1);
        {
            const uint32_t sg = (g & 1) ? 0xBC00BC00u : 0x3C003C00u;
#pragma unroll
            for (int i = 0; i < 16; i++) {
                const int r = 8 * (i >> 2) + (i & 3);
                k1[r] = hfms2_(sg, k0[r + 4], k1[r]); k1[r + 4] = hfma2_(sg, k0[r], k1[r + 4]);
            }
            touch(k1);
        }
        const uint32_t rowo = (16 * w + (lane & 15)) * 16;
        const uint32_t peer = mapa(sm, rank ^ 1), so = SM_U + 8 * wgi * SUB + w * 1024 + (8 * q + (g ^ (2 * q))) * 16;
        const uint2 sc = lds64(sm + SM_SCL + wgi * 8);
#pragma unroll 1
        for (int b = 0; b < 2; b++) {
            const uint32_t zb = sm + SM_S + 16 * wgi * SUB;
            constexpr int zi = 8 * SUB;
            uint32_t re[16], im[16], su[2][16], z[2][16], y[2][16];
            auto twiddle = [&](int hh) {
#pragma unroll
                for (int i = 8 * hh; i < 8 * hh + 8; i++) {
                    re[i] = hfma2_(ta[i & 3], im[i], re[i]); im[i] = hfms2_(tb[i & 3], re[i], im[i]); re[i] = hfma2_(ta[i & 3], im[i], re[i]);
                    touch(re[i]); touch(im[i]);
                }
            };
            auto dft16 = [&](int hh) {
                wg_fence();
                wg_s(su[hh], re + 8 * hh, im + 8 * hh, dre, dim); wg_s(su[hh] + 8, re + 8 * hh + 4, im + 8 * hh + 4, dre, dim);
                wg_commit();
                sched_fence();
            };
            auto product = [&](int hh) {
                if (b == 0) {
#pragma unroll
                    for (int i = 0; i < 8; i++) {
                        const int r = 8 * (i >> 2) + (i & 3), kr = 16 * hh + r;
                        const hc u = {su[hh][r], su[hh][r + 4]};
                        const hc t = hmulc(u, hc{k0[kr], k0[kr + 4]}), pp = hmulc(u, hc{k1[kr], k1[kr + 4]});
                        z[hh][r] = t.r; z[hh][r + 4] = t.i; k1[kr] = pp.r; k1[kr + 4] = pp.i;
                        touch(k1[kr]); touch(k1[kr + 4]);
                    }
                } else {
#pragma unroll
                    for (int i = 0; i < 8; i++) {
                        const int r = 8 * (i >> 2) + (i & 3), kr = 16 * hh + r;
                        const hc u = {su[hh][r], su[hh][r + 4]};
                        z[hh][r] = hfms2_(u.i, k0[kr + 4], hfma2_(u.r, k0[kr], k1[kr]));
                        z[hh][r + 4] = hfma2_(u.i, k0[kr], hfma2_(u.r, k0[kr + 4], k1[kr + 4]));
                    }
                }
                touch(z[hh]);
            };
            auto idft16 = [&](int hh) {
                wg_fence();
                wg_s(y[hh], z[hh] + 4, z[hh], dre, dim); wg_s(y[hh] + 8, z[hh] + 12, z[hh] + 8, dre, dim);
                wg_commit();
                sched_fence();
            };
            auto untwiddle = [&](int hh) {
#pragma unroll
                for (int i = 0; i < 2; i++) {
                    uint32_t* const yi = y[hh] + 8 * i, * const yr = yi + 4;
#pragma unroll
                    for (int n = 0; n < 4; n++) {
                        yr[n] = hfms2_(ta[n], yi[n], yr[n]); yi[n] = hfma2_(tb[n], yr[n], yi[n]); yr[n] = hfms2_(ta[n], yi[n], yr[n]);
                    }
                    const uint32_t a = zb + (4 * hh + 2 * i + (lane >> 4)) * SUB + rowo;
                    stsm4(a, yr[0], yr[1], yr[2], yr[3]);
                    stsm4(a + zi, yi[0], yi[1], yi[2], yi[3]);
                }
            };
            auto done = [&]() { sched_fence(); wg_wait<0>(); };
            {
                const uint64_t d1 = bdesc(sm + SM_U + (16 * b + 8 * wgi) * SUB, SUB);
                mbar_wait(bars + (B_U + b) * 8);
                proxy_fence();
                if (b == 0) { TSL(3); if (wgi == 1) bar_sync(9, 256); }
                wg_fence();
                wg_h(re, fc, fc + 8, d1, d1 + 16, d1 + 32, d1 + 48);
                wg_h(im, fs, fs + 8, d1, d1 + 16, d1 + 32, d1 + 48);
                wg_commit();
                if (b == 0 && wgi == 0) bar_arrive(9, 256);
                wg_wait<0>();
                touch(re); touch(im);
            }
            if (lane == 0) mbar_arrive_peer(peer + SM_BAR + (B_PEER + 2 * wgi + b) * 8);
            twiddle(0); twiddle(1); dft16(0); dft16(1);
            wg_wait<1>(); touch(su[0]);
            product(0); done(); touch(su[1]); idft16(0);
            product(1); done(); touch(y[0]); idft16(1);
            bar_sync(10 + wgi, 128);
            untwiddle(0); done(); touch(y[1]);
            untwiddle(1);
            proxy_fence();
            if (warp == TSW) TSL(36 + b);
            bar_sync(10 + wgi, 128);
            float acc[32];
            const uint64_t d4 = bdesc(zb, SUB);
            wg_fence();
            wg_f0(acc, fc, fc + 8, d4, d4 + 16, d4 + 32, d4 + 48);
            wg_f1(acc, fs, fs + 8, d4 + zi / 16, d4 + zi / 16 + 16, d4 + zi / 16 + 32, d4 + zi / 16 + 48);
            wg_commit();
            mbar_wait(bars + (B_PEER + 2 * wgi + b) * 8);
            wg_wait<0>();
            touch(acc);
            uint32_t s[2][2][4];
#pragma unroll
            for (int i = 0; i < 8; i++) {
                s[i >> 2][(i >> 1) & 1][2 * (i & 1)] = bmul2(pack_b(acc[i], acc[8 + i]), sc.x);
                s[i >> 2][(i >> 1) & 1][2 * (i & 1) + 1] = bmul2(pack_b(acc[16 + i], acc[24 + i]), sc.y);
            }
            const uint32_t sb = SM_BAR + (B_STG + b) * 8;
#pragma unroll
            for (int j = 0; j < 2; j++)
                if (j == rank) {
#pragma unroll
                    for (int hi = 0; hi < 2; hi++) {
                        const uint32_t (&r)[4] = s[1 - j][hi], (&l)[4] = s[j][hi];
                        st_async4(peer + so + 16 * b * SUB + hi * 512, r[0], r[1], r[2], r[3], peer + sb);
                        sts128(sm + so + (16 * b + 4) * SUB + 64 + hi * 512, l[0], l[1], l[2], l[3]);
                    }
                }
            __syncwarp();
            if (lane == 0) mbar_arrive(sm + sb);
            if (warp == TSW) TSL(5 + b);
        }
        TSL(7);
    } else {
    const int warp = __shfl_sync(0xFFFFFFFFu, tid >> 5, 0);
    if (warp < 12) {
        const int v = warp - 8;
        cluster_arrive();
        const uint32_t xs = sm + SM_U + v * 8192;
        if (elect()) {
#pragma unroll
            for (int r = 0; r < 2; r++) mbar_init(bars + (B_ROW + 2 * v + r) * 8, 1);
            asm volatile("fence.mbarrier_init.release.cluster;" ::: "memory");
#pragma unroll
            for (int e = 0; e < 2; e++) {
                if (e) { const int t0_ = clock(); while ((int)clock() - t0_ < EDELAY) __nanosleep(40); }
                mbar_expect(bars + (B_ROW + 2 * v + e) * 8, 4096);
#pragma unroll
                for (int r = 0; r < 2; r++)
                    asm volatile("cp.async.bulk.shared::cluster.global.mbarrier::complete_tx::bytes [%0], [%1], 2048, [%2];"
                                 :: "r"(xs + e * 4096 + r * 2048), "l"(p.x + (size_t)(128 * (c & 15) + 32 * v + 16 * r + 2 * (c >> 4) + e) * 1024),
                                    "r"(bars + (B_ROW + 2 * v + e) * 8) : "memory");
            }
        }
        __syncwarp();
        uint4 w4[4];
#pragma unroll
        for (int k = 0; k < 4; k++) w4[k] = ldg128(reinterpret_cast<const uint4*>(p.wr) + 32 * k + lane);
        {
            constexpr uint32_t ONE = 0x3F803F80u;
            const uint32_t zr = p.up_first >> 1;
            uint4 w5[4];
#pragma unroll
            for (int k = 0; k < 4; k++) {
                w5[k].x = w4[k].x + zr; w5[k].y = w4[k].y + zr; w5[k].z = w4[k].z + zr; w5[k].w = w4[k].w + zr;
                w4[k].x = cpy(w4[k].x, zr); w4[k].y = cpy(w4[k].y, zr); w4[k].z = cpy(w4[k].z, zr); w4[k].w = cpy(w4[k].w, zr);
            }
            const bool od = g & 1;
#pragma unroll 1
            for (int r2 = 0; r2 < 2; r2++) {
                mbar_wait(bars + (B_ROW + 2 * v + r2) * 8);
                TSL(43);
                float s1[2][4] = {}, q0[2][4] = {};
#pragma unroll
                for (int k = 0; k < 4; k++)
#pragma unroll
                    for (int r = 0; r < 2; r++) {
                        const uint4 x = lds128(xs + r2 * 4096 + r * 2048 + k * 512 + lane * 16);
                        const uint4& ww = r ? w5[k] : w4[k];
                        mma_bf16(q0[r], cpy(x.x, zr), ww.x, cpy(x.y, zr), ww.y, x.x, x.y);
                        mma_bf16(s1[r], x.x, x.y, x.z, x.w, ONE, ONE);
                        mma_bf16(q0[r], cpy(x.z, zr), ww.z, cpy(x.w, zr), ww.w, x.z, x.w);
                    }
#pragma unroll
                for (int r = 0; r < 2; r++)
                    if (q == (g >> 1))
                        sts128(sm + SM_RED + (4 * v + r2 + 2 * r) * 144 + g * 16, __float_as_uint(od ? q0[r][1] : q0[r][0]),
                               __float_as_uint(od ? q0[r][3] : q0[r][2]), __float_as_uint(s1[r][0]), __float_as_uint(s1[r][2]));
            }
            bar_arrive(7, 160);
        }
        TSL(8);
        bar_sync(6, 160);
        const uint32_t tag = lds32(sm + SM_TOK + 8);
        cluster_wait();
        asm volatile("setmaxnreg.dec.sync.aligned.u32 96;");
        const uint32_t peer = mapa(sm, rank ^ 1);
        if (v == 0 && lane == 0) mbar_arrive_peer(peer + SM_BAR + B_UFREE * 8);
        {
            uint4 st[8] = {};
            const uint4* src = p.sc->stats + rank * 512 + 16 * v + (lane >> 1);
            const uint32_t tb = ((tag & 1) << 15) | ((tag >> 1) << 31);
#pragma unroll
            for (int i = 0; i < 8; i++) st[i].z = ~tb;
            int it = 0;
            bool ok;
            bar_sync(3, 192);
            if (warp == 8) TSL(44);
            do {
                uint32_t bad = 0;
#pragma unroll
                for (int i = 0; i < 8; i++)
                    asm volatile("{ .reg .pred p; .reg .b128 t; setp.ne.u32 p, %5, 0; mov.b128 t, {%0,%1,%2,%3};\n"
                                 "@p " POLL_LD " t, [%4]; mov.b128 {%0,%1,%2,%3}, t; }"
                                 : "+r"(st[i].x), "+r"(st[i].y), "+r"(st[i].z), "+r"(st[i].w)
                                 : "l"(src + (i >> 2) * 64 + (i & 3) * 128), "r"((st[i].z ^ tb) & 0x80008000u) : "memory");
#pragma unroll
                for (int i = 0; i < 8; i++) bad |= st[i].z ^ tb;
                ok = __all_sync(0xFFFFFFFFu, (bad & 0x80008000u) == 0);
                if (warp == 8 && it == 0) TSL(45);
            } while (!ok && ++it < SPIN_LIMIT);
            TSL(11); TG(31);
#pragma unroll
            for (int i = 0; i < 8; i++) { st[i].z = bmul2(st[i].z & 0x7FFF7FFFu, 0x3F003F00u); st[i].y = bmul2(st[i].y, 0x3F003F00u); }
            const uint32_t xo = sm + SM_SLAB + v * 512 + lane * 16;
            const bool own = (lane & 1) == rank;
            uint32_t n[8][4];
            auto normalise = [&](int b, int i) {
#pragma unroll
                for (int e = 0; e < 2; e++) {
                    const uint4 x = lds128(xo + b * 16384 + e * 8192 + i * 2048);
                    const uint32_t m = e ? dup_hi(st[i].x) : dup_lo(st[i].x), hi = e ? dup_hi(st[i].z) : dup_lo(st[i].z), lo = e ? dup_hi(st[i].y) : dup_lo(st[i].y);
                    uint32_t (&r)[4] = n[2 * i + e];
                    r[0] = norm2(x.x, m, hi, lo); r[1] = norm2(x.y, m, hi, lo); r[2] = norm2(x.z, m, hi, lo); r[3] = norm2(x.w, m, hi, lo);
                }
                const uint4 t = st[i]; st[i] = st[4 + i]; st[4 + i] = t;
            };
            mbar_wait(bars + B_UFREE * 8);
#pragma unroll 1
            for (int b = 0; b < 2; b++) {
                mbar_wait(bars + (B_SLAB + b) * 8);
                TSL(b ? 38 : 10);
#pragma unroll
                for (int i = 0; i < 4; i++) normalise(b, i);
                const uint32_t ua = SM_U + (16 * b + rank) * SUB + (16 * v + (lane >> 1)) * 16;
#pragma unroll
                for (int cc = 0; cc < 8; cc++) {
                    uint32_t o[4];
#pragma unroll
                    for (int i = 0; i < 4; i++)
                        o[i] = (cc & 1) ? pack_h(bhi(n[2 * i][cc >> 1]), bhi(n[2 * i + 1][cc >> 1])) : pack_h(blo(n[2 * i][cc >> 1]), blo(n[2 * i + 1][cc >> 1]));
                    const uint32_t dst = own ? mapa(sm, rank) : peer;
                    st_async4(dst + ua + 2 * cc * SUB, o[0], o[1], o[2], o[3], dst + SM_BAR + (B_U + b) * 8);
                }
                TSL(b ? 41 : 12);
            }
            const uint32_t stg = sm + SM_U + (own ? 4 * SUB + 64 : 0) + v * 1024 + (lane >> 4) * 512;
            const int tl = 256 * v + 16 * (lane >> 1) + 8 * rank;
            __nv_bfloat16* const op = p.out + (size_t)tl * 1024 + G * 16 + (lane & 1) * 8;
#pragma unroll 1
            for (int b = -1; b < 2; b++) {
                uint32_t skip = 0;
                if (b >= 0) {
                    mbar_wait(bars + B_TOK * 8);
                    const uint2 tr = lds64(sm + SM_TOK);
                    const int d0 = tr.x - tl - 1024 * b, d1 = tr.y - tl - 1024 * b;
                    skip = ((d0 & ~7) ? 0u : 1u << d0) | ((d1 & ~7) ? 0u : 1u << d1);
                    mbar_wait(bars + (B_STG + b) * 8);
                    if (skip) {
#pragma unroll 1
                        for (int k = 0; k < 2; k++) {
                            const int d = k ? d1 : d0;
                            if (!(d & ~7)) {
                                const uint32_t a = stg + 16 * b * SUB + (4 * (d & 6) + (((lane >> 1) & 7) ^ (d & 6))) * 16 + (d & 1) * 8, dst = mapa(sm, k);
                                const uint2 s0 = lds64(a), s1 = lds64(a + 8 * SUB);
                                st_async4(dst + SM_FIX + (lane & 1) * 16, s0.x, s0.y, s1.x, s1.y, dst + SM_BAR + B_FIX * 8);
                            }
                        }
                    }
                    __syncwarp();
                }
#pragma unroll
                for (int i = 0; i < 4; i++) {
                    if (b >= 0) {
                        const uint32_t a = stg + 16 * b * SUB + (8 * i + (((lane >> 1) & 7) ^ (2 * i))) * 16;
                        const uint4 r0 = lds128(a), r1 = lds128(a + 8 * SUB);
#pragma unroll
                        for (int e = 0; e < 2; e++) {
                            const uint4 x = lds128(xo + b * 16384 + e * 8192 + i * 2048);
                            const uint32_t s0 = e ? r0.z : r0.x, s1 = e ? r0.w : r0.y, s2 = e ? r1.z : r1.x, s3 = e ? r1.w : r1.y;
                            const uint32_t (&gt)[4] = n[2 * i + e];
                            asm volatile("{ .reg .pred p; setp.eq.u32 p, %5, 0; @p st.global.v4.u32 [%0], {%1,%2,%3,%4}; }"
                                         :: "l"(op + (size_t)(1024 * b + 2 * i + e) * 1024), "r"(badd2(x.x, bmul2(s0, gt[0]))), "r"(badd2(x.y, bmul2(s1, gt[1]))),
                                            "r"(badd2(x.z, bmul2(s2, gt[2]))), "r"(badd2(x.w, bmul2(s3, gt[3]))), "r"(skip & (1u << (2 * i + e))) : "memory");
                        }
                    }
                    if (b < 1) {
                        normalise(b + 1, i);
#pragma unroll
                        for (int k = 0; k < 8; k++) { uint32_t& r = n[2 * i + (k >> 2)][k & 3]; r = pack_b(silu2(blo(r)), silu2(bhi(r))); }
                    }
                }
                TSL(b < 0 ? 0 : b ? 23 : 22);
            }
            TSL(17); TG(30);
        }
    } else {
        const int v = warp - 12;
        if (lane == 0) {
            if (v == 1) {
                mbar_init(bars + B_TAB * 8, 1); mbar_init(bars + B_TFREE * 8, 8); mbar_init(bars + B_KFREE * 8, 8);
                mbar_expect(bars + B_TAB * 8, 20480 + 1536);
            } else if (v == 0) {
                mbar_init(bars + B_SLAB * 8, 1); mbar_init(bars + (B_SLAB + 1) * 8, 1); mbar_init(bars + B_TOK * 8, 2); mbar_init(bars + B_UFREE * 8, 1);
                mbar_expect(bars + B_SLAB * 8, 16384); mbar_expect(bars + (B_SLAB + 1) * 8, 16384);
            } else {
                mbar_init(bars + (B_STG + v - 2) * 8, 9); mbar_init(bars + (B_FIX + v - 2) * 8, 1);
                mbar_init(bars + (B_U + v - 2) * 8, 1); mbar_expect(bars + (B_U + v - 2) * 8, 16384);
                mbar_expect(bars + (B_STG + v - 2) * 8, 8192); mbar_expect(bars + (B_FIX + v - 2) * 8, v == 2 ? 32 : 2048);
            }
            mbar_init(bars + (B_PEER + v) * 8, 4);
#pragma unroll
            for (int i = 0; i < 3; i++) { mbar_init(bars + (B_FULL + 3 * v + i) * 8, 1); mbar_expect(bars + (B_FULL + 3 * v + i) * 8, 16384); }
            asm volatile("fence.mbarrier_init.release.cluster;" ::: "memory");
        }
        __syncwarp();
        cluster_arrive();
        asm volatile("setmaxnreg.dec.sync.aligned.u32 48;");
        uint64_t pol; asm volatile("createpolicy.fractional.L2::evict_first.b64 %0, 1.0;" : "=l"(pol));
        auto load_chunk = [&](int n) {
            if (n < 8) tma3d(sm + chunk_off(n), &tm_g, G * 64, rank * 512 + n * 64, 0, bars + (B_FULL + n) * 8, pol);
            else tma3d(sm + chunk_off(n), &tm_d, 0, G * 64, rank * 8 + (n - 8) * 2, bars + (B_FULL + n) * 8, pol);
        };
        uint32_t* const my_part = p.sc->part + ((2 * (32 * rank + v) + (q & 1)) * 56 + G) * 16 + g + 8 * (q >> 1);
        if (G < 56) {
#pragma unroll
            for (int n = 0; n < 8; n++) st_relaxed32(my_part + n * 8 * 56 * 16, 0);
        }
        cluster_wait();
        const bool lead = elect();
        uint32_t key = 0;
        if (v == 0) {
            asm volatile("prefetch.tensormap [%0];" :: "l"(&tm_x) : "memory");
            asm volatile("prefetch.tensormap [%0];" :: "l"(&tm_g) : "memory");
            { const int t0_ = clock(); while ((int)clock() - t0_ < SDELAY) __nanosleep(40); }
            if (lead) {
                int n = 0;
#pragma unroll 1
                for (int i = 0; i < 5; i++) {
                    if (G < 56) {
#pragma unroll 1
                        for (; n < ((FILL >> (4 * i)) & 15); n++) {
                            if (n >= IDEPTH) mbar_wait(bars + (B_FULL + n - IDEPTH) * 8);
                            if (n == 3) mbar_wait(bars + B_TFREE * 8);
                            load_chunk(n);
                        }
                    }
                    if (i < 4)
                        asm volatile("cp.async.bulk.tensor.4d.shared::cluster.global.mbarrier::complete_tx::bytes [%0], [%1, {%3, %4, %5, %6}], [%2];"
                                     :: "r"(sm + SM_SLAB + (i & 1) * 16384 + (i >> 1) * 8192), "l"(&tm_x), "r"(bars + (B_SLAB + (i & 1)) * 8),
                                        "r"(G * 16), "r"(64 * (i & 1)), "r"(4 * rank), "r"(i >> 1) : "memory");
                }
                TS(20);
                if (G < 56) {
                    mbar_wait(bars + B_KFREE * 8);
                    load_chunk(5); load_chunk(6);
                }
                TS(21);
            }
            __syncwarp();
        } else if (v == 1) {
            if (lead) {
                asm volatile("cp.async.bulk.shared::cluster.global.mbarrier::complete_tx::bytes [%0], [%1], 20480, [%2];"
                             :: "r"(sm + SM_TAB), "l"(p.tab), "r"(bars + B_TAB * 8) : "memory");
                asm volatile("cp.async.bulk.shared::cluster.global.mbarrier::complete_tx::bytes [%0], [%1], 1536, [%2];"
                             :: "r"(sm + SM_F2), "l"(p.tab + 1280), "r"(bars + B_TAB * 8) : "memory");
                asm volatile("prefetch.tensormap [%0];" :: "l"(&tm_d) : "memory");
            }
        } else {
            const int sw = v - 2;
            if (sw == 0) {
                uint32_t tag;
                uint4* const my_stats = p.sc->stats + c * 8 + (lane >> 2);
                asm volatile("ld.relaxed.gpu.global.u32 %0, [%1];" : "=r"(tag) : "l"(&p.sc->epoch) : "memory");
                float ws = 0.f;
#pragma unroll
                for (int k = 0; k < 4; k++) {
                    const uint4 w = ldg128(reinterpret_cast<const uint4*>(p.wr) + 32 * k + lane);
                    ws += (blo(w.x) + bhi(w.x)) + (blo(w.y) + bhi(w.y)) + (blo(w.z) + bhi(w.z)) + (blo(w.w) + bhi(w.w));
                }
                if (q == 0) st_relaxed128(my_stats, make_uint4(0, 0, 0, 0));
                tag = tag % 3 + 1;
                sts32(sm + SM_TOK + 8, tag);
                bar_arrive(6, 160);
#pragma unroll
                for (int o = 1; o < 32; o <<= 1) ws += __shfl_xor_sync(0xFFFFFFFFu, ws, o);
                const uint32_t tb = ((tag & 1) << 15) | ((tag >> 1) << 31);
                const uint32_t ra = sm + SM_RED + (lane >> 1) * 144 + (lane & 1) * 64;
                const uint32_t kidx = 0xFFFF - (128 * (c & 15) + 16 * (lane >> 2) + 2 * (c >> 4) + ((lane >> 1) & 1));
                touch(ws);
                bar_sync(7, 160);
                const uint4 a0 = lds128(ra), a1 = lds128(ra + 16), a2 = lds128(ra + 32), a3 = lds128(ra + 48);
#define F(v) __uint_as_float(v)
                float ss = (F(a0.x) + F(a1.x)) + (F(a2.x) + F(a3.x)), dw = (F(a0.y) + F(a1.y)) + (F(a2.y) + F(a3.y));
                float sx = ((F(a0.z) + F(a1.z)) + (F(a2.z) + F(a3.z))) + ((F(a0.w) + F(a1.w)) + (F(a2.w) + F(a3.w)));
#undef F
                ss += __shfl_xor_sync(0xFFFFFFFFu, ss, 1); dw += __shfl_xor_sync(0xFFFFFFFFu, dw, 1); sx += __shfl_xor_sync(0xFFFFFFFFu, sx, 1);
                const float mean = sx * (1.0f / 1024.0f);
                const float var = fmaxf(ss * (1.0f / 1024.0f) - mean * mean, 0.f);
                const float m = rb(mean);
                float sd; asm("sqrt.approx.ftz.f32 %0, %1;" : "=f"(sd) : "f"(rb(rb(var) + 1e-5f)));
                const float rs = rcp(rb(sd));
                const float hi = rb(rs);
                const uint32_t p0 = pack_b(m, hi), p1 = pack_b(rs - hi, rs * (dw - m * ws));
                const uint32_t o0 = __shfl_xor_sync(0xFFFFFFFFu, p0, 2), o1 = __shfl_xor_sync(0xFFFFFFFFu, p1, 2);
                const uint32_t kr = ((p1 ^ (p1 >> 31 ? 0xFFFF0000u : 0x80000000u)) & 0xFFFF0000u) | kidx;
                const uint32_t k1 = __reduce_max_sync(0xFFFFFFFFu, kr), k2 = __reduce_max_sync(0xFFFFFFFFu, kr == k1 ? 0u : kr);
                if (q == 0) st_relaxed128(my_stats, make_uint4(prmt(p0, o0, 0x5410), prmt(p1, o1, 0x5410),
                                                               (prmt(p0, o0, 0x7632) & 0x7FFF7FFFu) | tb, lane == 0 ? k1 : k2));
                TSL(9);
                { const int t0_ = clock(); while ((int)clock() - t0_ < PDELAY) __nanosleep(20); }
            }
            bar_sync(3, 192);
            const uint32_t tg = lds32(sm + SM_TOK + 8), tb = ((tg & 1) << 15) | ((tg >> 1) << 31);
            {
                const uint32_t* src = &p.sc->stats[(sw * 64 + (lane >> 1)) * 8 + (lane & 1)].z;
                uint2 kz[4];
#pragma unroll
                for (int i = 0; i < 4; i++) kz[i] = make_uint2(~tb, 0);
                int it = 0;
                bool ok;
                do {
#pragma unroll
                    for (int i = 0; i < 4; i++)
                        asm volatile("{ .reg .pred p; .reg .b64 t; setp.ne.u32 p, %3, 0; mov.b64 t, {%0,%1};\n"
                                     "@p ld.relaxed.gpu.global.b64 t, [%2]; mov.b64 {%0,%1}, t; }"
                                     : "+r"(kz[i].x), "+r"(kz[i].y) : "l"(src + i * 512), "r"((kz[i].x ^ tb) & 0x80008000u) : "memory");
                    ok = __all_sync(0xFFFFFFFFu, (((kz[0].x ^ tb) | (kz[1].x ^ tb) | (kz[2].x ^ tb) | (kz[3].x ^ tb)) & 0x80008000u) == 0);
                } while (!ok && ++it < SPIN_LIMIT);
                const uint32_t a1 = max(kz[0].y, kz[1].y), b1 = max(kz[2].y, kz[3].y);
                const uint32_t h1 = max(a1, b1), h2 = __vimax3_u32(min(a1, b1), min(kz[0].y, kz[1].y), min(kz[2].y, kz[3].y));
                const uint32_t w1 = __reduce_max_sync(0xFFFFFFFFu, h1), w2 = __reduce_max_sync(0xFFFFFFFFu, h1 == w1 ? h2 : h1);
                sts64(sm + SM_KEYS + sw * 8, w1, w2);
                bar_sync(8, 64);
                const uint2 o = lds64(sm + SM_KEYS + 8 - sw * 8);
                key = sw ? __vimax3_u32(min(w1, o.x), w2, o.y) : max(w1, o.x);
                TSL(19);
            }
            const int t = (0xFFFF - (key & 0xFFFF)) & 2047;
            {
                const uint4* row = reinterpret_cast<const uint4*>(p.x + (size_t)t * 1024);
                uint4 xr[3];
                xr[0] = ldg128(row + 64 * rank + lane); xr[1] = ldg128(row + 64 * rank + 32 + lane); xr[2] = ldg128(row + 2 * G + (lane & 1));
                uint4 stk;
                int it = 0;
                do stk = ld_relaxed128(p.sc->stats + ((t >> 1) & 7) * 128 + (t >> 4)); while (((stk.z ^ tb) & 0x80008000u) && ++it < SPIN_LIMIT);
                if (lane == 0) {
                    sts32(sm + SM_TOK + 4 * sw, t);
                    if (c == 0 && sw == 0) st_relaxed32(&p.sc->epoch, tg);
                }
                const uint32_t se = (t & 1) ? 0x3232 : 0x1010;
                const uint32_t m = prmt(stk.x, 0, se), hi = prmt(stk.z, 0, se) & 0x7FFF7FFFu, lo = prmt(stk.y, 0, se);
                const uint32_t a = sm + SM_XSEL + lane * 32 + sw * 16;
#pragma unroll
                for (int i = 0; i < 2; i++)
                    sts128(a + i * 1024, norm2(xr[i].x, m, hi, lo), norm2(xr[i].y, m, hi, lo), norm2(xr[i].z, m, hi, lo), norm2(xr[i].w, m, hi, lo));
                proxy_fence();
                __syncwarp();
                if (lane == 0) mbar_arrive(bars + B_TOK * 8);
                if (sw == rank && lane < 2) {
                    sts128(sm + SM_XRAW + lane * 16, xr[2].x, xr[2].y, xr[2].z, xr[2].w);
                    sts128(sm + SM_XRAW + 32 + lane * 16, norm2(xr[2].x, m, hi, lo), norm2(xr[2].y, m, hi, lo), norm2(xr[2].z, m, hi, lo), norm2(xr[2].w, m, hi, lo));
                }
                __syncwarp();
                TSL(42);
            }
        }
        mbar_wait(bars + B_TOK * 8);
        const uint32_t tag = lds32(sm + SM_TOK + 8);
        {
            if (G < 56) {
                const uint64_t dw = (uint64_t)((sm & 0x3FFFFu) >> 4) | (1ull << 16) | (64ull << 32) | (1ull << 62);
                const uint64_t dx = (uint64_t)(((sm + SM_XSEL) & 0x3FFFFu) >> 4) | (2ull << 16) | (8ull << 32);
                const uint64_t dh = (uint64_t)(((sm + SM_H) & 0x3FFFFu) >> 4) | (8ull << 16) | (8ull << 32);
                const uint64_t dw2 = dw + (tag >> 2);
                float ag[4], au[4];
                TSL(13);
#pragma unroll
                for (int n = 0; n < 8; n++) {
                    const uint64_t a = (n < 7 ? dw : dw2) + (chunk_off(n) >> 4), b = dx + n * 16;
                    mbar_wait(bars + (B_FULL + n) * 8);
                    wg_fence();
                    if (n == 0) { wg_w0(ag, a, b); wg_w0(au, a + 512, b); } else { wg_w<1>(ag, a, b); wg_w<1>(au, a + 512, b); }
#pragma unroll
                    for (int k = 1; k < 4; k++) { wg_w<1>(ag, a + 128 * k, b + 4 * k); wg_w<1>(au, a + 512 + 128 * k, b + 4 * k); }
                    wg_commit();
                    if (n == 1 || n == 2 || n == 5) { wg_wait<1>(); bar_sync(4, 128); }
                    if ((n == 1 || n == 2 || n >= 5) && v == (n & 3)) { if (lead) load_chunk(n + (n < 5 ? 6 : 4)); __syncwarp(); }
                    if (n == 4) TSL(4);
                    if (n == 7) TSL(34);
                }
                wg_wait<0>();
                touch(ag); touch(au);
                TSL(14);
                if (q == 0) {
#pragma unroll
                    for (int r = 0; r < 2; r++) {
                        const uint32_t dst = mapa(sm, r), o = dst + SM_PAIR + rank * 1024 + v * 256 + g * 32;
                        st_async4(o, __float_as_uint(ag[0]), __float_as_uint(ag[1]), __float_as_uint(ag[2]), __float_as_uint(ag[3]), dst + SM_BAR + B_PAIR * 8);
                        st_async4(o + 16, __float_as_uint(au[0]), __float_as_uint(au[1]), __float_as_uint(au[2]), __float_as_uint(au[3]), dst + SM_BAR + B_PAIR * 8);
                    }
                }
                mbar_wait(bars + B_PAIR * 8);
                {
                    const uint32_t o = sm + SM_PAIR + v * 256 + g * 32 + q * 4, og = o + (p.up_first ? 16 : 0), ou = o + (p.up_first ? 0 : 16);
                    const float gs = rb(__uint_as_float(lds32(og)) + __uint_as_float(lds32(og + 1024)));
                    const float us = rb(__uint_as_float(lds32(ou)) + __uint_as_float(lds32(ou + 1024)));
                    const float hv = rb(siluf_(gs)) * us;
                    const uint32_t hd = sm + SM_H + (2 * v + (q >> 1)) * 128 + (q & 1) * 32 + g * 2, hb = pack_b(hv, hv);
                    sts16(hd, hb); sts16(hd + 64, hb);
                }
                proxy_fence();
                bar_sync(4, 128);
                TSL(15);
#pragma unroll
                for (int n = 0; n < 4; n++) {
                    const uint64_t a = dw2 + (chunk_off(8 + n) >> 4);
                    float d[2][4];
                    mbar_wait(bars + (B_FULL + 8 + n) * 8);
                    if (n == 3) TSL(24);
                    wg_fence();
                    wg_w0(d[0], a, dh); wg_w0(d[1], a + 512, dh);
#pragma unroll
                    for (int k = 1; k < 4; k++) { wg_w<1>(d[0], a + 128 * k, dh + 16 * k); wg_w<1>(d[1], a + 512 + 128 * k, dh + 16 * k); }
                    wg_commit();
                    wg_wait<0>();
#pragma unroll
                    for (int i = 0; i < 2; i++) {
                        touch(d[i]);
                        st_relaxed32(my_part + (2 * n + i) * 8 * 56 * 16, (__float_as_uint((q & 2) ? d[i][2] : d[i][0]) & ~3u) | tag);
                    }
                }
                TSL(16);
            } else {
                mbar_wait(bars + B_STG * 8);
            }
            if (v == 2 + rank) {
                const int t = (0xFFFF - (key & 0xFFFF)) & 2047;
                const int col = 4 * q + 2 * (lane >> 4) + ((lane >> 3) & 1), d = G * 16 + col;
                const float r = __uint_as_float((key & 0x80000000u) ? (key & 0x7FFF0000u) : (~key & 0xFFFF0000u));
                const float sg = rb(sigmoidf_(r));
                const float xn = blo(lds16(sm + SM_XRAW + 32 + col * 2));
                const float xv = blo(lds16(sm + SM_XRAW + col * 2));
                const uint4* src = reinterpret_cast<const uint4*>(p.sc->part) + c * 224 + lane;
                float s0 = 0, s1 = 0, s2 = 0, s3 = 0;
                {
                    uint4 pv[7];
                    int it = 0;
                    bool ok;
                    do {
                        uint32_t bad = 0;
#pragma unroll
                        for (int i = 0; i < 7; i++) pv[i] = ld_relaxed128(src + 32 * i);
#pragma unroll
                        for (int i = 0; i < 7; i++) bad |= (pv[i].x ^ tag) | (pv[i].y ^ tag) | (pv[i].z ^ tag) | (pv[i].w ^ tag);
                        ok = __all_sync(0xFFFFFFFFu, (bad & 3) == 0);
                    } while (!ok && ++it < SPIN_LIMIT);
#pragma unroll
                    for (int i = 0; i < 7; i++) {
                        s0 += __uint_as_float(pv[i].x); s1 += __uint_as_float(pv[i].y); s2 += __uint_as_float(pv[i].z); s3 += __uint_as_float(pv[i].w);
                    }
                }
                TSL(25);
                const bool u16 = lane & 16, u8 = lane & 8;
                const float y0 = (u16 ? s2 : s0) + __shfl_xor_sync(0xFFFFFFFFu, u16 ? s0 : s2, 16);
                const float y1 = (u16 ? s3 : s1) + __shfl_xor_sync(0xFFFFFFFFu, u16 ? s1 : s3, 16);
                float y = (u8 ? y1 : y0) + __shfl_xor_sync(0xFFFFFFFFu, u8 ? y0 : y1, 8);
                y += __shfl_xor_sync(0xFFFFFFFFu, y, 4);
                const float z = rb(xn + rb(rb(y) * sg));
                const float gt = rb(siluf_(z));
                mbar_wait(bars + B_FIX * 8);
                const float o = xv + rb(blo(lds16(sm + SM_FIX + col * 2)) * gt);
                if (!(lane & 4)) p.out[(size_t)t * 1024 + d] = __float2bfloat16(o);
                TSL(26); TG(29);
            }
        }
    }
    }
}

__device__ __align__(128) const uint32_t g_tab[5504] = {
0x2fff3000,0x2e7c2fd4,0x2fc92fd4,0xad72af5a,0x2ff82ffc,0x230e2c07,0x2faf2fbc,0x217ea934,0x2fed2ff4,0xad4da8d5,0x2f912fa0,0x2e5e2bb7,
0x2fdd2fe6,0xb000af46,0x2f6e2f80,0x2fdd2fc9,0x2ff42fff,0x2e1f2fc9,0x2e1f2e7c,0xa875ad72,0x2fbc2fdd,0x9fd92a4e,0x2d4d2dba,0x2cd825db,
0x2f5a2f91,0xaeb5ac07,0x2c5d2cd8,0x30002f30,0x2ed02f1a,0xaf80aff4,0x2aaa2bb7,0x2cb02f1a,0x2fdd2ffc,0x2dba2fbc,0x2a4e2c07,0x25dba934,
0x2f462fa0,0xa7652875,0x25152875,0x2f802d27,0x2e3f2ed0,0xafa0ad72,0xa17e1cb6,0x2e3f2fe6,0x2cd82d96,0xadfeafd4,0xa934a6a1,0xa44e29f1,
0x2fbc2ff8,0x2d4d2faf,0x9fd9230e,0x2cd8217e,0x2e992f46,0xaa4e2515,0xaa4ea765,0x2fd42f80,0x2cb02dba,0xafffae99,0xad72ac5d,0x27652dba,
0x28752b05,0xab5eaee9,0xaf1aae5e,0xae3fa934,0x2f912ff4,0x2cd82fa0,0xac07a8d5,0x2f302bb7,0x2dba2ed0,0xac5d1cb6,0xae99ad72,0x2dba2fe6,
0x29932c5d,0xafc9af6e,0xafe6af6e,0xaaaa25db,0xa17e244e,0xa30ead4d,0xafafaffc,0xaff8aee9,0x2f5a2fed,0x2c5d2f91,0xaeb5ad4d,0x30002e5e,
0x2cb02e3f,0xad72a17e,0xafffafa0,0x27652e3f,0x217e2993,0xaf02afe6,0xaf02afc9,0xaf1aaaaa,0xab05a5db,0x2814aa4e,0xac07adba,0xad4dafdd,
0x2f1a2fe6,0x2bb72f80,0xaff4af46,0x2f1a2fc9,0x2b052d96,0xae5ea6a1,0xaee9afd4,0xa93429f1,0xa5db244e,0xadbaaffc,0xaa4ead4d,0xafddaee9,
0xaddcabb7,0x2cb0a17e,0x2765a17e,0x1cb6ad00,0x2ed02fdd,0x2aaa2f6e,0xaf80b000,0x2cb02fdd,0x28752cd8,0xaf1aa934,0xab5eadfe,0xae3fa44e,
0xab05a17e,0xac07afaf,0x2814a30e,0xad4daff8,0xaf6eaddc,0x2eb52765,0x2eb52cb0,0x2dba1cb6,0x29932f5a,0xa7652e99,0x25152e99,0x2aaaad96,
0xafa0ab05,0xabb7afed,0xaff4acd8,0x28d52ffc,0xa814af02,0x2f912d27,0x9fd9ae1f,0xaee9ae3f,0x2fd42c32,0xaf5a1cb6,0x30002d72,0x2fd42515,
0x28752f46,0xa8d52e7c,0xa8d52c32,0x2e3fa993,0xafedac5d,0xa934b000,0xaf30af5a,0xa8142eb5,0x1648adfe,0x2e992e5e,0x2c87a814,0xa9f1affc,
0x2fe62e1f,0xafffa875,0x2ddc2ff4,0x2ed02e1f,0x26a12f30,0xa9f12e5e,0xad96244e,0x2fd41fd9,0xafffad27,0xa515aff4,0xac32aff4,0xaddc2b5e,
0x2875acb0,0x2d272f46,0x2fa02993,0x2875aed0,0x2ee92f6e,0xaf91ac87,0x1fd92e99,0x28143000,0x244e2f1a,0xab052e3f,0xaf91a875,0x2fbc2b5e,
0xafd4addc,0x1648afc9,0x1648ae7c,0xafdd9cb6,0x2c32aa4e,0x2aaa2fd4,0x2f802e99,0x2e7caa4e,0x2d002ffc,0xae1fae5e,0xad272814,0xabb72dfe,
0x1fd92f02,0xac072e1f,0xafedad27,0x2dfe2e3f,0xaf6eae7c,0x25dbaf80,0x2c5daaaa,0xaf6eac32,0x2ddca5db,0x25153000,0x2c323000,0x2fff26a1,
0x28d52fbc,0xabb7af91,0xaff4ab05,0xafa0244e,0x96482ee9,0xac872dfe,0xae99af30,0x29f12fbc,0xaed0af02,0x2993af1a,0x2f46217e,0xacb0af02,
0x2f1a1cb6,0xa30e2fc9,0xa30e2e7c,0x2e1f2ddc,0x9fd92eb5,0xa44eb000,0xae5eaf5a,0xaf30ac5d,0xa17e2ed0,0xad002ddc,0xabb7afff,0xa17e2fe6,
0xadfeaf6e,0x2c07ae99,0x2fed2c87,0x9fd9b000,0x2fd42814,0xa9f12f30,0xad962934,0x26a12fed,0xaaaa2d00,0x2765afa0,0xa515afa0,0xa993afaf,
0xa5152eb5,0xad722dba,0x9cb6af6e,0xac322eb5,0xad00afbc,0x2d27adfe,0x2e1f2f30,0x2bb7aee9,0x2ffc2b5e,0xacd82e3f,0xafeda875,0xab052f1a,
0xadba2993,0x2c87ae7c,0x2c87ac32,0x2a4eaf46,0xaddc2d96,0xafe62c5d,0xaed02c5d,0x2fffa9f1,0x2e1fad4d,0x2e3f2814,0x2f02ac07,0xad27ab05,
0xae5e2d00,0x9fd9af1a,0xaf302b5e,0xa44e2faf,0x2e99acb0,0xad962f80,0x2f5aaaaa,0x2e99aed0,0xae3f2d72,0xaff82c32,0xaff82515,0x2f021cb6,
0x2ee9ac87,0x2d4d29f1,0x2ffc9648,0xa44eae99,0xaf6e2b05,0x26a1afbc,0xafd4a44e,0xadba2f91,0x2fc9a8d5,0xaf462e3f,0x2f802875,0x2fe6a8d5,
0xae992d4d,0xb0002c07,0xaf6ea814,0x2c872b05,0x2f80ab5e,0x2c322bb7,0x2e7c2bb7,0x2aaaaff8,0xaff42765,0x2b5eafff,0xad27ad72,0xaff42cb0,
0x2fed1648,0xaffc2c5d,0x2b052eb5,0x2cd82a4e,0xaee92d27,0xaffc2bb7,0xad4dad00,0x244e2e1f,0x2fdda993,0x29f12cb0,0x29f12ed0,0x2eb5af46,
0xafe61648,0x2d72afdd,0x9cb6afd4,0xaed01648,0x2f022934,0xafa02814,0xa8d52fed,0xa30e2f30,0xaf302d00,0xafed2b5e,0xa814af1a,0xa9342faf,
0x3000a765,0x26a12d72,0xa5db2fff,0x3000acb0,0xaf46a6a1,0x2ed0af5a,0x2cb0af5a,0xa993ac87,0x2d272cd8,0xae3f9fd9,0xaf022d4d,0xae1f2fbc,
0xaf6e2cd8,0xafd42b05,0x26a1affc,0xadba2fed,0x2fe6a30e,0x1cb62e1f,0xad722f1a,0x2ed0a30e,0xae1faaaa,0x2fafae7c,0x2fafac32,0x28d5af80,
0x29342e99,0xac07a9f1,0xafbc1648,0xaffc2c87,0xafa02cb0,0xafaf2aaa,0x2d00af80,0xafa02ed0,0x2f911648,0xa44e2eb5,0xafbc2c5d,0x2b052a4e,
0xac87acd8,0x3000ad4d,0x2f6e1fd9,0x2e99afbc,0x9cb62faf,0xa515ad27,0xac32ad27,0xad72a30e,0xafc92c87,0xaf802a4e,0x2f46adba,0xafe62c87,
0x2f02244e,0xa8d52f30,0xafa01fd9,0xa30e2e5e,0xa934ae1f,0x2fbcabb7,0x2c072d00,0x2ffcad27,0xaa4e2fff,0x26a1aed0,0x26a1afe6,0x1648addc,
0xaf4629f1,0xac3225db,0xae7c25db,0x29931648,0xab5e2f91,0xafaf2e5e,0xad002fed,0x2f1aad4d,0x2ee9a875,0xaf302ff8,0x2dfea17e,0x2fbcaff4,
0x2c5dafc9,0xa9f12d72,0x2d96afff,0x2c5dae7c,0xaf022993,0xab5e2515,0xab5ea765,0xa30e2aaa,0xacd82fd4,0xaf302dba,0xaf912f6e,0x2c07a6a1,
0x2d969fd9,0xafdd2fed,0x25db2c07,0x2f5aadfe,0x2e7caff8,0xad722f02,0x2fffae3f,0x2fc9aff8,0xaeb52934,0xaa4e244e,0x9648acd8,0xac5d2dfe,
0xaddc2ff8,0xae7c2d00,0xafc92d00,0x9cb628d5,0x2bb72515,0xaff82f80,0xab5e2f46,0x2bb7a765,0x2fbcaf5a,0xaf302fdd,0x2dfea5db,0x2ee9ad96,
0xae5e28d5,0xa934230e,0x2b05af02,0xaee92fa0,0xaeb52fff,0xad962c32,0xad962515,0xac872ddc,0x276529f1,0xaf802eb5,0xaf462fdd,0xa51529f1,
0x2ff4adfe,0xaff82fed,0x217e2c07,0x28759fd9,0xadfe2875,0xa814217e,0x2e5eaff8,0xaffc2ff4,0xaf5a2fe6,0xac872aaa,0xa6a1a993,0xaf5a2fc9,
0x9cb62c87,0xae7c2d96,0xafc92d96,0xaddc2eb5,0x2f1aac07,0xafaf2f30,0xad002f91,0xab5e2cd8,0xad962814,0xa5db1fd9,0x2fddaf91,0xaf5a2ee9,
0xafc92faf,0xaaaa28d5,0x2993ae1f,0xafe62faf,0xa8d52ddc,0xad002c32,0xad002515,0xaff82fff,0x2d4da6a1,0xae5e2dba,0xafed2f6e,0xaf912fd4,
0xad272765,0xa30e1cb6,0x2fafaddc,0xad272cb0,0xaffc2f5a,0xa81425db,0x2e5eafdd,0xadfe2d96,0xac5d2ee9,0xaa4e2934,0x9648ab05,0xaeb52e5e,
0x2993230e,0xac322b5e,0xae7c2b5e,0xaf462f02,0xacb026a1,0x9cb61648,0x2ddcaa4e,0xa76526a1,0xaff42ee9,0xa17e1fd9,0x2ff8af91,0xa8752814,
0xadfe2fa0,0xa44e230e,0x2cd8af02,0xa93428d5,0x96482aaa,0xa5db2515,0xa5dba765,0xa9f12993,0x2f462f5a,0x2c322e99,0x2e7c2e99,0xa993ad96,
0x2f1a2f30,0xa875244e,0x2e3f2e5e,0x2b5e1fd9,0x2ee92f02,0xaf30ad27,0x2dfe2e1f,0x2fbc2e3f,0x2eb52ed0,0xaf6eafff,0x2dba2ddc,0x2eb52fe6,
0x28752993,0xa8d52515,0xa8d5a765,0x2e3f2aaa,0x244e26a1,0xaf91ad96,0xab05a9f1,0x2fbc2fd4,0x96481fd9,0xae99afed,0xac87ac07,0x29f12dfe,
0xa515a17e,0x9cb6abb7,0xad72ad00,0xac32a17e,0xac5dab05,0xaf5aacd8,0xb000afed,0x2eb52ffc,0xaddcad27,0xae7caff4,0xafc9aff4,0x9cb62b5e,
0xaf02ae7c,0x217eaaaa,0xaf1aaf80,0xaf02ac32,0xafbcaf6e,0x2f302c87,0xadfeae99,0xaee9b000,0xafedafa0,0xaf30aff4,0xa934abb7,0xa81428d5,
0xafd4afff,0x1648ac32,0x1648a515,0xafddaddc,0xaed0af6e,0x2f462c5d,0x299325db,0xacb0af6e,0xad00adfe,0x2e1f2fed,0x2d272c07,0x2bb79fd9,
0xadfeaf02,0xa814ae1f,0x2e5e2d27,0xaffcae3f,0xaa4eacb0,0x2e992993,0x2fd42f46,0xaa4eaed0,0x1cb6a5db,0x2e7c3000,0x2fc93000,0x2ddc26a1,
0x2b5e2814,0xa8752934,0x2e3f2f30,0x2f1a2fed,0x1648a814,0x2c879fd9,0x2e992f91,0xa9f1aee9,0x2c322875,0x2f802fa0,0x2aaa2d27,0x2e7c2875,
0x2f1a2ddc,0xa30e2c32,0xa30e2515,0x2e1f2fff,0x2ffc2fd4,0xafedad96,0xacd8a9f1,0xab0526a1,0x2e1f2c32,0x2ff42d72,0xa8751cb6,0x2e1f2515,
0x2ffc2f6e,0x28142e99,0xae5eac87,0x2dfe3000,0x2eb52fbc,0xaf5aab05,0xb000af91,0xac5d244e,0x29932d00,0xac32afa0,0xae7cafa0,0xaf46afaf,
0x2fe62fd4,0x2ddc3000,0xafffaf5a,0x2ed02fd4,0x2d002ee9,0xad271fd9,0xae1faf91,0xabb72814,0x9fd928d5,0xae5eaff4,0xa44eabb7,0xaf30afa0,
0xadbaaaaa,0x2c87a515,0x2c872765,0x2a4ea993,0x9cb62d96,0xacb02c5d,0xa7652c5d,0x2ddca9f1,0xaff8adfe,0xa30eafbc,0xafafaee9,0xa17e2f30,
0x244ead00,0x2dfe2f1a,0x2934ab5e,0xacd8afaf,0x2fdd2e7c,0xb000a993,0x2f6e2f46,0x2fdd2c32,0xae3f9cb6,0xaff8a765,0xaff8acb0,0x2f022ddc,
0xac07afdd,0x2dfeaa4e,0x1fd9adba,0xafeda5db,0x2f6e2934,0xa6a12ee9,0x2fd42e5e,0x2dbaab05,0x27652f1a,0xaaaaaff4,0xa9932bb7,0xa5152f1a,
0xafddadfe,0xadbaaee9,0xaa4eafbc,0xa5db2f30,0x2aaaab5e,0x2fc92bb7,0x2fe62bb7,0xa993aff8,0x2e3f2fc9,0xafa01cb6,0xa17e2ddc,0x2e3f2e7c,
0xae5e9648,0x2d4dac5d,0xaf91aeb5,0xafedaa4e,0xac07aff8,0x1fd9afaf,0x2dfea30e,0xafeda17e,0x2fdd2aaa,0x29f12fe6,0x29f12fc9,0x2eb5a993,
0xa5152dba,0xaddcae99,0xafffac5d,0xac322dba,0xaf02af30,0x2fa02c07,0x28d5acd8,0x230eaf91,0x2934ad00,0x2e5eab5e,0x2ee92f1a,0xab05afaf,
0x2dba2fc9,0xac5d2ddc,0xae991cb6,0x2dba2e7c,0xaf80a6a1,0x2765af5a,0xa515af5a,0xaf46ac87,0x217eae5e,0x230e2ffc,0x2faf2dfe,0x2ff82814,
0x2f6e244e,0x2fd42934,0xa6a12dfe,0x2dbaacd8,0xa5152e3f,0xafffa17e,0xaddcafa0,0xac322e3f,0xae1faf80,0x2fafa515,0x2faf2765,0x28d5af46,
0x2f9125db,0xaee92a4e,0xa8142dba,0x9fd92fdd,0x2f1a2e7c,0x2bb72f46,0xaff4a993,0x2f1a2c32,0xaf309648,0xacd8aeb5,0x2c07ac5d,0xaf91aa4e,
0x25dbae5e,0x2dba2dfe,0x2a4e2ffc,0x2fdd2814,0x2d722faf,0xae7cad27,0xafc9ad27,0xafffa30e,0x27652fdd,0xa9932f6e,0xaaaab000,0xa5152fdd,
0xaf02ae5e,0x28d5af91,0x2fa02d4d,0x230eafed,0x2f91217e,0xa8142faf,0xaee9230e,0x9fd92ff8,0xaa4e2d72,0x26a1afc9,0x26a1ae7c,0x1648afff,
0xaf8029f1,0xafc925db,0xafe625db,0x2f461648,0x2fa0a934,0x2bb72cd8,0x2ff4a44e,0xa8d5adfe,0xafbc2875,0x2934aff8,0xaffc217e,0xac072ff4,
0x2fd4a765,0xaf5a2ddc,0x30009cb6,0x2fd4acb0,0xaf02aaaa,0xab5eacb0,0xab5eaed0,0xa30e2f80,0x2e5e2c5d,0xab053000,0x29342f5a,0x2ee9aeb5,
0xad96ad4d,0x2fddacd8,0xa5dbafbc,0xaf5a1fd9,0x2cb02e1f,0xaddca875,0x1cb62ff4,0x27652e1f,0xa6a1af91,0x29f1afed,0x2d96ae5e,0xafd42d4d,
0x9cb62ff8,0xafe62d00,0xaed02d00,0x2d7228d5,0x2875afe6,0x2d272993,0x2fa0aaaa,0x2875afc9,0xac072f5a,0x2934afdd,0xaffc25db,0xafbc2d96,
0x2cd8af1a,0x2f91ae3f,0x2f302875,0xac07ab5e,0xaeb52d72,0xad96a765,0xad96acb0,0xac872fff,0x2fc9aa4e,0xa9932fd4,0x2aaa2e99,0x2fe6aa4e,
0xaff41fd9,0x2ff8acd8,0xa17eafbc,0xa875ad4d,0x2ffca875,0x2ee9a17e,0xa44e2ff8,0x2d4daff4,0xaf6ea515,0x25dbaf46,0x2c5daf80,0xaf6e2765,
0x2d722c87,0xafe62d96,0xaed02d96,0x9cb62eb5,0xa8d5aee9,0x2bb72b05,0x2ff4a934,0x2fa0ae5e,0x2d962c07,0x25db2d4d,0xafdd2b05,0x2f5aa814,
0xa765af02,0x2f46af1a,0x2f80217e,0x2515af02,0xa8d52fff,0xad00a765,0xad00acb0,0xaff82d72,0x2dfeaeb5,0xacd83000,0x244e2f5a,0x29342c5d,
0xa17e2fc9,0xad002fff,0xabb7ad72,0xa17e2e7c,0x2d4daf5a,0x2ee9a5db,0xa44e2fdd,0x2ffcad96,0xafd42c07,0x29f1af91,0x2d96af30,0xa6a1acd8,
0x2f46230e,0xafc92b5e,0xafe62b5e,0xaf802f02,0xae7c2eb5,0xafff2dba,0x2d72af6e,0xafc92eb5,0x2ff4a814,0x217e2d4d,0xaff82b05,0x28752c07,
0xad4dab5e,0x2fedae3f,0x2e5e2875,0x2f91af1a,0x96482f80,0xa5dbacb0,0xa5dbaed0,0xa9f1aaaa,0xad729648,0xa515a6a1,0xac32a6a1,0x9cb62a4e,
0xae1f2ffc,0xae3f2c07,0xaf022fbc,0x2d27a934,0x2cd8230e,0xaffc2fa0,0x2b0528d5,0x2fedaf02,0x2e99afe6,0xad962f46,0x2f5aaf80,0x2e99afc9,
0x230eaddc,0x2d27aed0,0x2d27afe6,0xafaf2fff,0xafbc2c87,0x1fd9a9f1,0xad4d1648,0xacd82e99,0xaa4e2f30,0xac5d2814,0xaeb52fed,0x96482934,
0x2ed0a8d5,0xaf802e3f,0x2aaa2875,0x2cb0a8d5,0x2e99affc,0x3000afbc,0x2f6eac07,0xac872934,0xa993a8d5,0x2ed0afaf,0x2cb0afaf,0xaf462e1f,
0xaff42ed0,0x2b5ead72,0xad271cb6,0xaff42fe6,0xa44e2dba,0x9fd9a6a1,0xaf302fd4,0xae5e2f6e,0x2fbcad27,0x2d4dabb7,0x9fd92d00,0x2cd8ae1f,
0x2c87af80,0x2f5aae7c,0x2f5aac32,0x26a1aaaa,0xacb01648,0x2fffafdd,0x2d72afd4,0xa7651648,0xafaf2f91,0x2f1aafbc,0xab5ea44e,0xad002b05,
0x2b05230e,0xa44e28d5,0xafbc2fa0,0x2f91af02,0x3000aed0,0x26a19cb6,0xa5db2d72,0x3000afe6,0x2aaaaeb5,0x2c32a9f1,0x2e7ca9f1,0x2f80afdd,
0xad27244e,0x2e3fad4d,0x2f02affc,0x2e1faee9,0xaa4e2e5e,0xaeb52f30,0xac5d1fd9,0x9648244e,0x2cb0a30e,0xad722e1f,0xafff2f1a,0x2765a30e,
0x2ff8af46,0xabb72cb0,0xabb72ed0,0x2b5ea993,0x2b05ae99,0xa81429f1,0x2c079648,0x2d4dac87,0xafa02fe6,0xafaf2f80,0x2d00af46,0xafa02fc9,
0xa9342dba,0xafed2fd4,0xa814a6a1,0xaf302f6e,0x2c87a44e,0xb0002ffc,0xaf6e2d4d,0xae992ee9,0x2fffaf02,0xafe62ff8,0xaed02ff8,0xaddc2e3f,
0xaed02c87,0xaaaa2a4e,0x2f80adba,0xacb02c87,0xafaf2fed,0xab5e2b05,0x2f1aaffc,0xad002cd8,0xab052e1f,0xac072bb7,0x2814ad00,0xad4d2d27,
0x29f11cb6,0xac5d2c32,0xac5d2515,0xad962d72,0x2d722d96,0x25152c5d,0x2c322c5d,0x1cb6a9f1,0x2d272d4d,0xad00a814,0x2bb72c07,0x2e1f2b05,
0x2cd82d00,0xaffcaf1a,0x2b052b5e,0x2fed2faf,0x2c872cb0,0xadbaaf80,0x2a4e2aaa,0x2c872ed0,0xae3faddc,0xaff8aed0,0xaff8afe6,0x2f022fff,
0xaee9ae99,0xad4daf6e,0xaffcb000,0x244e2c87,0xaf6eaf30,0x26a1a814,0xafd4afed,0xadbaa934,0xafc9afa0,0x2f462d00,0xaf80afaf,0xafe6afa0,
0xac87ad4d,0x9648ac07,0x29f12814,0xae99ab05,0xa993ab5e,0x2ed02bb7,0x2cb02bb7,0xaf46aff8,0xa30ea765,0x2f1a2fff,0x2e1f2d72,0xa30eacb0,
0x244e1648,0x1fd92c5d,0x2f302eb5,0x2e5e2a4e,0x2ee92e1f,0x2ffc2f02,0x2d4d2e3f,0xa44ead27,0x2fdd2f80,0x29f12e7c,0x29f12c32,0x2eb52aaa,
0x2fe63000,0xad72a5db,0x1cb626a1,0x2ed03000,0x2f022f91,0xafa0afbc,0xa8d5a44e,0xa30e2b05,0x2b052d00,0xa44e2b5e,0xafbcaf1a,0x2f912faf,
0x16482765,0xafd4ad72,0xafddafff,0x16482cb0,0xaaaaa6a1,0xac32af5a,0xae7caf5a,0xaf80ac87,0xae1facd8,0x2d001fd9,0xabb7ad4d,0xad27afbc,
0xaf6eae5e,0xafd4af30,0x26a19fd9,0xadbaa44e,0xafe6aff4,0x9cb6ad27,0x2d722b5e,0xaed0aff4,0xae1faf46,0x2faf2cb0,0x2faf2ed0,0x28d5a993,
0xa934ac87,0x2c072f6e,0x2fbc3000,0x2ffc2e99,0xa8d5acb0,0x2875aaaa,0x2e3f2f80,0xa8d5aed0,0x29341648,0x2fed2eb5,0x28142c5d,0x2f302a4e,
0x2e992cd8,0x16482d4d,0xa9f19fd9,0x2c872fbc,0x2fff2faf,0xafe6ad27,0xaed0ad27,0xaddca30e,0x2fc92e99,0x2f802f5a,0xaf46ad96,0x2fe62e99,
0x2f022fed,0xa8d52b05,0xafa0affc,0xa30e2cd8,0x29342d27,0xafbcaf02,0xac07ae3f,0xaffcae1f,0xaa4e9cb6,0x26a1ac32,0x26a1a515,0x1648ad72,
0xaaaa29f1,0xaed025db,0xacb025db,0x2f801648,0xaf1aaf91,0x2875ae5e,0xae3fafed,0xab5e2d4d,0x2c07a875,0x2b052ff8,0x2d4da17e,0xa814aff4,
0x2eb52fc9,0xaf6ead72,0x2dba2fff,0x2eb52e7c,0xaf02af80,0xab5eafe6,0xab5eafc9,0xa30e2f46,0x2cd8a6a1,0x2f302d96,0x2f9129f1,0xac07afd4,
0x2d962ffc,0xafdda44e,0x25db2ee9,0x2f5a2d4d,0xae7ca17e,0x2d72abb7,0xafffad00,0xafc9a17e,0x2c5da934,0x2f5aa44e,0x30002cd8,0xaeb5adfe,
0x2d722ff8,0xacb02d00,0xa7652d00,0x2fff28d5,0xaf02a515,0x217eaf80,0xaf1aaf46,0xaf022765,0xa814af5a,0x2b052fdd,0x2d4da5db,0x2c07ad96,
0x2e5e2fa0,0x29342ff4,0xab052bb7,0x2ee9a8d5,0xaeb59cb6,0xad96aed0,0xad96afe6,0xac872d72,0xa765af6e,0x2f802c5d,0x2f4625db,0x2515af6e,
0x2ff42d4d,0xaff8a44e,0x217e2ee9,0x28752ffc,0xad4d2875,0xafbc217e,0xacd8aff8,0x1fd92ff4,0xaa4eafe6,0x2e99aaaa,0x2fd42993,0xaa4eafc9,
0x2fff2c87,0xacb02d96,0xa7652d96,0x2d722eb5,0xab5e2c07,0x2875af30,0xae3faf91,0xaf1aacd8,0xad96afbc,0xa5dbaffc,0x2fdd2934,0xaf5aac07,
0x2fc92875,0x2aaa2fa0,0xa9932d27,0x2fe62875,0xa8d52d72,0xad00aed0,0xad00afe6,0xaff89cb6,0xad4dafd4,0x2e5e2d96,0x2fed29f1,0x2f91a6a1,
0x2e1fa765,0x2ff49cb6,0xa8752ddc,0x2e1facb0,0x1fd92f5a,0xafbc25db,0xacd8afdd,0xad4d2d96,0xaeb5aee9,0x2f5aa934,0x30002b05,0x2c5dae5e,
0x2f80230e,0xaed02b5e,0xacb02b5e,0xaaaa2f02,0x2cb02fd4,0x1cb63000,0xaddcaf5a,0x27652fd4,0xaff4ac07,0xa17eaffc,0x2ff82934,0xa875afbc,
0x2dfea8d5,0x244e2ff4,0xacd82bb7,0x29342fa0,0x96482f46,0xa5dbafe6,0xa5dbafc9,0xa9f1af80,0xafff9648,0xae7ca6a1,0xafc9a6a1,0x2d722a4e,
0x2ff81fd9,0x230e2ee9,0x2faf2814,0x217eaf91,0xafeda30e,0x2d4dafa0,0xaf91a8d5,0xae5e2f02,0x2fdd2515,0xb0002aaa,0x2f6e2993,0x2fdda765,
0x230eafff,0x2d27afc9,0x2d27ae7c,0xafaf2d72,0xa8142fdd,0xaffc2a4e,0xadfe2dba,0x2e5e25db,0x2a4eaf91,0x2c5d2c07,0x2eb5acd8,0x1648af30,
0xac322f1a,0x2993aff4,0xaf462bb7,0xae7c2f1a,0x2fdd1fd9,0x2dba2814,0x2a4e2ee9,0x25dbaf91,0xaf46a8d5,0x2765afaf,0xa515afaf,0xaf802e1f,
0x2e3f2c32,0xafa02ddc,0xa17e2fff,0x2e3f2515,0xacd8adba,0x2dfe26a1,0x2934afd4,0x244eaf6e,0xa8142ff8,0xadfe2faf,0xaffc230e,0x2e5e217e,
0x2c87af46,0x2f5aa515,0x2f5a2765,0x26a1af80,0xae7c2dba,0x9cb6ae99,0xaddcac5d,0xafc92dba,0x2fafab05,0xaf1a2ee9,0x2b5e2e5e,0x2d002934,
0xaf91a30e,0xacd8a8d5,0x2c07afa0,0xaf302f02,0x2dba2c32,0xac5d2fff,0xae992ddc,0x2dba2515,0xa993aeb5,0x2fc9a9f1,0x2fe6a9f1,0x2aaaafdd,
0xa17e2fed,0xa30eadfe,0xafaf9fd9,0xaff82c07,0x2a4eafed,0x2eb5af91,0x2c5d2d4d,0x1648ae5e,0xae7c2e3f,0xaddca17e,0x9cb6afa0,0xafc92e3f,
0x2ff8a993,0xabb72fe6,0xabb72fc9,0x2b5e2aaa,0xaf30a5db,0x2fbcaa4e,0x2ee9adba,0x2dfeafdd,0x2f1a2515,0x2bb72993,0xaff42aaa,0x2f1aa765,
0xab05adba,0x2e5eafd4,0x2ee926a1,0x2934af6e,0xa5db2fed,0xadba9fd9,0xaa4eadfe,0xafdd2c07,0x2ddcaf02,0xacb02ff8,0xa7652ff8,0x9cb62e3f,
0xac322fdd,0xaf462f6e,0x2993b000,0xae7c2fdd,0x2fafacd8,0x2b5e2934,0xaf1a2dfe,0x2d00244e,0xaf30a17e,0x2ee9afaf,0x2fbca30e,0x2dfeaff8,
0x29f12ddc,0xac5da765,0xac5dacb0,0xad969cb6,0xa993aa4e,0x2765ac87,0xa515ac87,0xaaaa2dba,0xafa02f30,0xabb7244e,0xaff42e5e,0x28d51fd9,
0x28142bb7,0xaf912e1f,0x1fd92d27,0x2ee9ad00,0x2fd4aed0,0xaf5a2fff,0x3000addc,0x2fd4afe6,0x2fafaf46,0x2fa0ae7c,0x2fa0ac32,0xad002993,
0xa44eac5d,0x2f91b000,0x2b05af5a,0xafbc2eb5,0xb0002dfe,0x2c87ae5e,0xae992814,0xaf6e2ffc,0xa5152e1f,0x9cb6a875,0xad722ff4,0xac322e1f,
0x26a12b05,0xa9f12cd8,0xad962fed,0x2fd4affc,0x2fffae1f,0x2515230e,0x2c32230e,0x2ddcaf1a,0x2875ae7c,0x2d27aaaa,0x2fa0af80,0x2875ac32,
0xaee929f1,0x2f91ae99,0x9fd9ac87,0xa8149648,0xafed2f1a,0xaf302e3f,0xa934a875,0xa8142b5e,0xa6a12ddc,0xb0002fc9,0xb0002e7c,0x25db1cb6,
0x2ed0aa4e,0xaf462fd4,0xa9932e99,0x2cb0aa4e,0x2e3faffc,0xad272e5e,0x2e1fa814,0x2f02adfe,0x9fd9abb7,0x2c07ad27,0x2fedae1f,0xadfe2d00,
0xaf6e2cb0,0x25dba993,0x2c5daf46,0xaf6e2ed0,0xaddc2fdd,0xa5159648,0xac329648,0xafff2fd4,0x28d52814,0xabb72934,0xaff42f30,0xafa02fed,
0x3000aee9,0x2e99adfe,0xac872f30,0x2f6eafbc,0x2c32af02,0x2f80af1a,0x2aaa217e,0x2e7caf02,0xab5e9cb6,0x2ff4afc9,0x2ff4ae7c,0x2d27addc,
0xaffc2eb5,0x2fedb000,0x2cd8af5a,0x2b05ac5d,0xa17e2c32,0xad002d72,0xabb71cb6,0xa17e2515,0x2dfea9f1,0xac072c87,0xafed2e99,0x1fd91648,
0x2fd4afbc,0xa9f12b05,0xad962f91,0x26a1a44e,0x2aaaae3f,0xa76528d5,0x251528d5,0x2993a875,0xafe62eb5,0xaddc2dba,0x2fffaf6e,0xaed02eb5,
0xae3f2fbc,0xae1f2dfe,0x2d27af30,0xaf022ee9,0x9fd92b5e,0xae5e2e3f,0xa44ea875,0xaf302f1a,0x2d96a993,0xae992e7c,0xae992c32,0xaf5a2f46,
0x299329f1,0xa76525db,0x251525db,0x2aaa1648,0x28d52934,0xaf02acd8,0x230e244e,0x2fa02dfe,0x28142875,0xaf91aff8,0x1fd9217e,0x2ee92ff4,
0x26a12765,0xaa4eaddc,0x16481cb6,0x26a12cb0,0xaf02af46,0xab5eae7c,0xab5eac32,0xa30e2993,0xae5eaeb5,0x2b059648,0xa934aa4e,0xaee9ac5d,
0xad96adfe,0x2fdd2e5e,0xa5dba814,0xaf5aaffc,0xacb0ad27,0x2ddc2faf,0x9cb6a30e,0xa765ad27,0x2fd42f91,0x2f6e2fed,0x2dba2e5e,0xa6a1ad4d,
0x2fff2ff8,0x25152d00,0x2c322d00,0x2ddc28d5,0x2faf2fe6,0xae1fa993,0x28d52aaa,0x2faf2fc9,0x2ee92f5a,0xaf91afdd,0x1fd925db,0x28142d96,
0xacd8ab5e,0xaf91ad00,0xaf30afaf,0x2c072f1a,0xaeb5addc,0xad96afc9,0xad96ae7c,0xac879cb6,0xafc9af5a,0x2993a6a1,0xaaaaac87,0xafe6af5a,
0xaff4affc,0x2ff82e5e,0xa17ea814,0xa875adfe,0x9fd9a875,0x2c07a17e,0x2fed2ff8,0xadfeaff4,0x29f12515,0x2fdd2f46,0x2eb52f80,0x29f1a765,
0x2ddc2c87,0x25152d96,0x2c322d96,0x2fff2eb5,0x2fa02ee9,0xaf02ab05,0x230e2934,0x28d52e5e,0x2d962ee9,0x25db2dfe,0xafddaf30,0x2f5a2fbc,
0x27652bb7,0xaf46ab5e,0xaf80aff8,0xa5152bb7,0xa8d59cb6,0xad00afc9,0xad00ae7c,0xaff8addc,0xadfeac5d,0x2cd89648,0xa44eaa4e,0xa934aeb5,
0xaff8afc9,0xae3fafff,0x2f022d72,0xaff8ae7c,0xadfeaf5a,0x2c07a5db,0x2fed2fdd,0x9fd9ad96,0xa6a1ac07,0x2f6e2f91,0x2dba2f30,0x2fd42cd8,
0x2aaa230e,0xa7652b5e,0x25152b5e,0x29932f02,0x2e7c2c5d,0x2fff2d96,0xad72a9f1,0x2fc92c5d,0x2ff42fbc,0x217e2dfe,0xaff8af30,0x28752ee9,
0x2d4d2f1a,0xafedad00,0xae5eafaf,0xaf91ab5e,0x96482993,0xa5dbae7c,0xa5dbac32,0xa9f1af46,0xaddc9648,0xafe6a6a1,0xaed0a6a1,0x2fff2a4e,
0xad27affc,0x2d00ac07,0xabb7afbc,0xae1f2934,0x2e5e230e,0x1fd92fa0,0x2f3028d5,0x244eaf02,0x2c872fe6,0xadbaaf46,0x2a4e2f80,0x2c872fc9,
0x230ead72,0x2d27ac32,0x2d27a515,0xafaf9cb6,0x2fbc2e99,0x9fd92f6e,0x2d4d3000,0x2cd8ac87,0xaa4e2b05,0xac5dafbc,0xaeb5a44e,0x96482f91,
0xaed0afa0,0x2f802d00,0xaaaaafaf,0xacb0afa0,0x2c872ffc,0x16482fbc,0xa9f12c07,0x2e99a934,0xaf80a8d5,0xac32afaf,0xae7cafaf,0xaaaa2e1f,
0xa30eaed0,0x2f1a2d72,0x2e1f9cb6,0xa30eafe6,0x2fed2dba,0xaffca6a1,0x2b052fd4,0x2cd82f6e,0xafbcae1f,0xad4daf02,0x1fd9ae3f,0xacd82d27,
0x2c87a993,0x2f5a2cb0,0x2f5a2ed0,0x26a1af46,0x2cb03000,0xafffa5db,0xad7226a1,0x27653000,0xafafa934,0x2f1aa814,0xab5eafed,0xad00af30,
0x2f30230e,0x2fed28d5,0x28142fa0,0x2934af02,0x16482ed0,0xafd41cb6,0xafddad72,0x16482fe6,0xaf46aeb5,0x2ed0a9f1,0x2cb0a9f1,0xa993afdd,
0x2e1fa44e,0xad002d4d,0x2bb72ffc,0x2d272ee9,0xaa4e2cd8,0xaeb52b05,0xac5daffc,0x96482fed,0xacb0aff4,0x2d72ad27,0x2fff2b5e,0xa765aff4,
0x2ff82aaa,0xabb72e7c,0xabb72c32,0x2b5e2f80,0xab052c87,0x2814af6e,0xac07b000,0xad4dae99,0xa8d5afe6,0x2875af80,0x2e3f2f46,0xa8d5afc9,
0x2f912dba,0xa44e2fd4,0xafbca6a1,0x2b052f6e,0xae99244e,0x9648affc,0x29f1ad4d,0xac87aee9,0x1cb6af02,0x25152ff8,0x2c322ff8,0x2d722e3f,
0x2ed02e99,0x2aaa2f5a,0xaf80ad96,0x2cb02e99,0xafafa44e,0xab5eaf30,0x2f1a9fd9,0xad00ae5e,0x2b05ad27,0x2c072f02,0xa8142e3f,0x2d4d2e1f,
0x29f12fff,0xac5daed0,0xac5dafe6,0xad96addc,0xaf46aa4e,0xac32ac87,0xae7cac87,0x29932dba,0x2f1a2b05,0xa8752fed,0x2e3f2cd8,0x2b5eaffc,
0xaee9abb7,0x2f30ae1f,0xadfead27,0xafbc2d00,0x2eb52c32,0xaf6e1cb6,0x2dba2d72,0x2eb52515,0x2fafa993,0x2fa0a515,0x2fa02765,0xad00aaaa,
0xafed26a1,0xa934ad96,0xaf30a9f1,0xa8142fd4,0x30009fd9,0xac872fed,0x2e992c07,0x2f6eadfe,0xafe6a17e,0x2fffabb7,0xaddcad00,0xaed0a17e,
0xac5d2f30,0xaf5a2e5e,0xb000244e,0x2eb51fd9,0x2ddcae1f,0x2e7c230e,0x2fc9230e,0x1cb6af1a,0xaf022cb0,0x217eaf46,0xaf1aa993,0xaf022ed0,
0x2fbca9f1,0xaf302e99,0x2dfe2c87,0x2ee91648,0xa44eafa0,0x2b05aff4,0x2f91abb7,0xafbc28d5,0xa6a12fff,0xb0002c32,0xb0002515,0x25db2ddc,
0x2c32af6e,0x2aaa2c5d,0x2f8025db,0x2e7caf6e,0xae3f2dfe,0x2d27afed,0xae1fac07,0xaf021fd9,0x2dfe2bb7,0x28142d27,0xae5e2e1f,0x2ffcad00,
0xaa4eae7c,0x2e99af80,0x2fd4aaaa,0xaa4eac32,0x9cb62fdd,0xae7c9648,0xafc99648,0xaddc2fd4,0x2b5eafbc,0xa8752f91,0x2e3f2b05,0x2f1aa44e,
0xb0002814,0xae991fd9,0x2c87af91,0xaf6e2ee9,0x2ed02875,0xa9932fa0,0xaf462d27,0x2cb02875,0xab5eaddc,0x2ff4ac32,0x2ff4a515,0x2d27afff,
0x9fd92fd4,0xa44ead96,0xae5ea9f1,0xaf3026a1,0x2e1faed0,0x2ff4addc,0xa8752fff,0x2e1fafe6,0xaffc29f1,0xa814ac87,0x2e5eae99,0xadfe9648,
0x2eb52814,0xaf5a2f30,0xb0002934,0xac5d2fed,0xa993ae3f,0x2c3228d5,0x2e7c28d5,0x2f46a875,0xa5152fd4,0xad723000,0x9cb6af5a,0xac322fd4,
0x2e3faee9,0x2e1f9fd9,0xad272f91,0x2f02a814,0xaffc28d5,0x2cd8aff4,0x2fedabb7,0x2b05afa0,0x2d962aaa,0xae992515,0xae99a765,0xaf5a2993,
0x1cb6adba,0x2cb0aeb5,0x2765aeb5,0xaddc2f6e,0xaff82d4d,0xa30ea814,0xafaf2c07,0xa17e2b05,0xa44e2e3f,0xadfe2b5e,0xa9342f1a,0x2cd8a875,
0x2fddacb0,0xb0002f80,0x2f6eaaaa,0x2fddaed0,0x2d001cb6,0x217e2765,0x217e2cb0,0x2bb7addc,0x2ee9afdd,0x2d4daa4e,0x2ffcadba,0xa44ea5db,
0xa9f1a934,0x2fd4aee9,0x26a1ae5e,0xad962b05,0xafc92f1a,0x2f46aff4,0xaf802bb7,0xafe62f1a,0xafdd2d4d,0xadba2c07,0xaa4ea814,0xa5db2b05,
0xaaaa2f1a,0xafc92f02,0xafe62f02,0x2993a17e,0x2e3fa765,0xafa02fff,0xa17e2d72,0x2e3facb0,0x2e5eb000,0xad4d2eb5,0x2f91ac5d,0x2fedaf5a,
0x2ee9aff8,0x2ffcafaf,0x2d4da30e,0xa44ea17e,0xa5dbaaaa,0x2f6eafe6,0x2f6eafc9,0xac5d2993,0xafe62dba,0x2d72ae99,0x9cb6ac5d,0xaed02dba,
0xabb72f30,0x28d5ac07,0xafa02cd8,0xaff42f91,0xa9342e3f,0xae5e2f1a,0xaee92b5e,0x2b05a875,0x2dbaa765,0xac5d2d72,0xae992fff,0x2dbaacb0,
0x2f80afd4,0xa7652a4e,0x25152a4e,0x2f46ae99,0x217eacd8,0x230e1fd9,0x2fafad4d,0x2ff8afbc,0xa9f1a44e,0x26a1a934,0x2fd4adfe,0xad962cd8,
0xafe62e3f,0x9cb6a17e,0x2d72afa0,0xaed02e3f,0xad272f80,0xa8752515,0xa875a765,0xafa02f46,0x293425db,0xac072a4e,0xafbc2dba,0xaffc2fdd,
0x2f1aacb0,0x2bb7aaaa,0xaff42f80,0x2f1aaed0,0x2f30b000,0x2cd8ac5d,0xac072eb5,0x2f91af5a,0x25dbacd8,0x2dbaad4d,0x2a4e1fd9,0x2fddafbc,
0xad722875,0x2e7cae1f,0x2fc9ae1f,0x2fffaff4,0xafc92fdd,0xaf802f6e,0x2f46b000,0xafe62fdd,0xabb72e5e,0xafa02f91,0x28d5ad4d,0xaff42fed,
0x2934217e,0xafbc2faf,0xac07230e,0xaffc2ff8,0x2f5aad72,0xafd42fc9,0xafd42e7c,0xb0002fff,0x9cb69648,0xacb0a6a1,0xa765a6a1,0x2ddc2a4e,
0xa17e9fd9,0xaff4aee9,0xa875a814,0x2ff82f91,0xa44ea30e,0xadfeafa0,0xa934a8d5,0x2cd82f02,0xa5dba515,0x9648aaaa,0xa9f1a993,0xa5db2765,
0xa30e9cb6,0xad27a765,0xad27acb0,0x2faf2ddc,0xa814a5db,0xaffcaf5a,0xadfead96,0x2e5e2fdd,0xaa4ea934,0xac5daee9,0xaeb5ae5e,0x96482b05,
0xac32ab5e,0x2993a30e,0xaf46af02,0xae7cab5e,0xa5db9fd9,0xad96a814,0xaf5aaee9,0x2fdd2f91,0xaaaaa8d5,0xafc9afaf,0xafe6afaf,0x29932e1f,
0xad00ac32,0xa8d5addc,0xaff8afff,0xad00a515,0xae5eadba,0x2d4d26a1,0xaf91afd4,0xafedaf6e,0xa814a17e,0xadfea875,0xaffcaff4,0x2e5e2ff8,
0xac87aaaa,0xaf5aafe6,0xaf5aafc9,0xa6a12993,0xae7cad96,0x9cb6ac87,0xaddcaeb5,0xafc9ad96,0xafafaf30,0x2f1a2c07,0xab5eacd8,0xad00af91,
0xa934a30e,0xae5ea8d5,0xaee9afa0,0x2b052f02,0xad96ac32,0xaeb5afff,0xac87addc,0xad96a515,0xaf80aeb5,0x2765a9f1,0xa515a9f1,0xaf46afdd,
0xaff8afed,0x2ff42dfe,0x28751fd9,0x217eac07,0xaa4ea44e,0xaeb5a934,0xac5dadfe,0x96482cd8,0xae7cad00,0xaddcaff8,0x9cb6a8d5,0xafc9ad00,
0xaff8af80,0x2bb7a515,0x2bb72765,0xab5eaf46,0xaf30afdd,0x2fbc2f5a,0x2ee92d96,0x2dfe25db,0xab5ea515,0xaf02a993,0xa30eaaaa,0xab5e2765,
0xaf30adba,0xacd8afd4,0x2c0726a1,0xaf91af6e,0xafddafed,0x2d961fd9,0x2f5a2dfe,0x25dbac07,0xad72af02,0x2e7c2ff8,0x2fc92ff8,0x2fff2e3f,
0xac32a5db,0xaf46a9f1,0x29939648,0xae7ca5db,0xafafae5e,0xab5eaf91,0x2f1a2d4d,0xad00afed,0xaf30aff8,0x2ee92875,0x2fbc2ff4,0x2dfe217e,
0xa9f1ad72,0x2c5d2fc9,0x2c5d2e7c,0x2d962fff,0xaf80aa4e,0xafc9ac87,0xafe6ac87,0x2f462dba,0xa8d5af30,0x2f02a44e,0xa30eae5e,0xafa09fd9,
0x2fbc2bb7,0xa9342e1f,0x2ffc2d27,0x2c07ad00,0x26a12ed0,0xaa4eafff,0x16482ddc,0x26a12fe6,0xafafaaaa,0xafa0acb0,0xafa0aed0,0x2d002f80,
0xa44eaeb5,0x2f919648,0x2b05aa4e,0xafbcac5d,0x30002d4d,0xac872cd8,0x2e992fbc,0x2f6e9fd9,0xa5152d27,0x9cb6afaf,0xad72230e,0xac322d27,
0xafd4ab05,0xaf6eacd8,0xadbaafed,0x26a12ffc,0x1cb6ae1f,0x2fe6230e,0x2ed0230e,0xad72af1a,0x2faf2e7c,0xae1f2aaa,0x28d52f80,0x2faf2c32,
0xac0729f1,0x2934ae99,0xaffcac87,0xafbc9648,0xafedab5e,0xaf30ad00,0xa934afaf,0xa8142f1a,0x26a1ad72,0x30002765,0x30002cb0,0xa5dbafff,
0x2ed02f5a,0xaf4626a1,0xa9932c87,0x2cb02f5a,0xae3f1fd9,0x2d27acd8,0xae1fafbc,0xaf02ad4d,0xaffcabb7,0xaee9ad27,0x244eae1f,0xad4d2d00,
0x29f1acb0,0x2fdd2993,0x2eb52f46,0x29f1aed0,0x2d722fdd,0xafe69648,0xaed09648,0x9cb62fd4,0xafa0a814,0x2f02a934,0xa30eaf30,0xa8d5afed,
0xb000ac07,0xae99ad4d,0x2c87ab05,0xaf6e2814,0x2c32abb7,0x2f802b5e,0x2aaa2ff8,0x2e7cabb7,0x2b5e2fff,0xaff4a765,0xaff4acb0,0xad272d72,
0xaffcac5d,0x2fed9648,0x2cd8aa4e,0x2b05aeb5,0xaff8ac32,0xae3fad72,0x2f029cb6,0xaff8a515,0x2d4da9f1,0x2ee92c87,0xa44e2e99,0x2ffc1648,
0x26a12fbc,0xaf6eab05,0xadbaaf91,0xafd4244e,0xaf46ae3f,0x2fc928d5,0x2fe628d5,0x2f80a875,0xafe6ac5d,0xaddcad96,0x2fff29f1,0xaed0ac5d,
0x2e3fa814,0x2e1f2d4d,0xad272b05,0x2f022c07,0x9fd92f1a,0xae5ead00,0xa44eafaf,0xaf30ab5e,0xad96af80,0x2e992cb0,0x2e992ed0,0x2f5a2aaa,
0xad72adba,0xa515aeb5,0xac32aeb5,0x9cb62f6e,0x2d272dfe,0xad002fbc,0x2bb72ee9,0x2e1faf30,0xacd8ae3f,0x2ffcab5e,0xab05af1a,0xafed2875,
0x2c872e7c,0xadbaa993,0x2a4e2f46,0x2c872c32,0xad00addc,0xa17eaed0,0xa17eafe6,0xabb72fff,0x2c072e99,0xadfe2f6e,0x9fd93000,0x2fedac87,
0xa9f1af30,0x2fd4a814,0x26a1afed,0xad96a934,0x27652fa0,0xaaaaad00,0xa9932faf,0xa5152fa0,0xac87adfe,0x9648aee9,0x29f1afbc,0xae992f30,
0x29932f1a,0xaed02f02,0xacb02f02,0x2f46a17e,0xa30eafc9,0x2f1a9cb6,0x2e1faddc,0xa30eae7c,0xa44e3000,0x9fd9aeb5,0xaf302c5d,0xae5e2f5a,
0xac07ae1f,0x1fd9af02,0x2dfeae3f,0xafed2d27,0x25db2f80,0xaf6e2e7c,0xaf6e2c32,0x2c5d2aaa,0x2515b000,0x2ddc25db,0x2fffa6a1,0x2c32b000,
0xabb72f91,0x28d5afbc,0xafa0a44e,0xaff42b05,0xab05ae3f,0x244eaf1a,0x2fbcab5e,0xaf912875,0x16482fc9,0xafd42ddc,0xafdd1cb6,0x16482e7c,
0x2aaaafd4,0x2c322a4e,0x2e7c2a4e,0x2f80ae99,0xae1f2e5e,0x2d00affc,0xabb7adfe,0xad27a814,0xa9f1ae5e,0x26a1af30,0x2fd49fd9,0xad96a44e,
0xa5152ff4,0xafff2d27,0xaddcab5e,0xac322ff4,0x2d27af46,0x28752cb0,0x28752ed0,0x2fa0a993,0xaf912c87,0x2ee9af6e,0x2814b000,0x1fd9ae99,
0xa8d5ae7c,0x2875af46,0x2e3f2993,0xa8d5ac32,0xa9343000,0xafed2c5d,0xa814aeb5,0xaf302f5a,0x2e99ae5e,0x16482dfe,0xa9f12ffc,0x2c872814,
0xafff2875,0x2fe6ae1f,0x2ed0ae1f,0x2ddcaff4,0xa765ae99,0x2993af5a,0x2aaa2d96,0x2515ae99,0xabb72fed,0xafa02b05,0x28d5affc,0xaff42cd8,
0x2f91ad27,0xa8142f02,0xaee92e3f,0x9fd92e1f,0xaf5a9cb6,0x2fd4ac32,0x2fd4a515,0x3000ad72,0x2aaaaf6e,0x2ed0afdd,0x2cb0afdd,0xaf803000,
0xaf1a2934,0x2875acd8,0xae3f244e,0xab5e2dfe,0xac072faf,0xab05217e,0xad4d2ff8,0x2814230e,0x2eb5a765,0xaf6e2ddc,0x2dba9cb6,0x2eb5acb0,
0x2bb7af80,0x2f1aafe6,0x2f1aafc9,0xaff42f46,0xae5e26a1,0x2b05ad96,0xa934a9f1,0xaee92fd4,0xadba2ffc,0xa5dba44e,0xafdd2ee9,0xaa4e2d4d,
0x2cb0217e,0xaddc2bb7,0x1cb62d00,0x2765217e,0x2c5daf91,0x2f5aafed,0x3000ae5e,0xaeb52d4d,0xad72217e,0x2cb0ae3f,0x2765ae3f,0xafff2fa0,
0xaf022fe6,0x217ea993,0xaf1a2aaa,0xaf022fc9,0x28142a4e,0xab0525db,0xad4d2fdd,0xac072dba,0x2cd8afa0,0x2f91aff4,0x2f30abb7,0xac0728d5,
0xac5d9cb6,0x2dbaaed0,0x2dbaafe6,0xae992d72,0xafc92f6e,0x2993ac5d,0xaaaaa5db,0xafe62f6e,0xa30e2d4d,0xa17ea44e,0xaff82ee9,0xafaf2ffc,
0x2d4dafaf,0x2fbcaff8,0x2cd8a17e,0x9fd9a30e,0xaa4ea515,0x2e99af46,0x2fd4af80,0xaa4e2765,0xafff2e99,0x2cb0adba,0x2765adba,0xad722c5d,
0xab5e2ee9,0x2875ab05,0xae3f2934,0xaf1a2e5e,0x2dbaafbc,0x2fddaffc,0x25db2934,0x2a4eac07,0xa765a875,0x2f46afa0,0x2f80ad27,0x2515a875,
0xafa02d72,0x2e3faed0,0x2e3fafe6,0xa17e9cb6,0xadfe2fd4,0x2cd8ad96,0xa44ea9f1,0xa93426a1,0x2e1fafc9,0x2ff4afff,0xa8752d72,0x2e1fae7c,
0x9fd9aa4e,0x2fbcafdd,0x2cd8a5db,0x2d4dadba,0xaeb52c07,0x2f5aaf91,0x3000af30,0x2c5dacd8,0xaf802ff4,0x2ed0af1a,0x2cb0af1a,0x2aaaabb7,
0x2e7cafd4,0x2fffb000,0xad722f5a,0x2fc9afd4,0x230eac07,0x2ff8affc,0x217e2934,0x2fafafbc,0xad4d28d5,0x2fedaff4,0x2e5eabb7,0x2f91afa0,
0xb0002f46,0x2fddafe6,0x2fddafc9,0x2f6eaf80,0xaaaaaa4e,0xaed0ac87,0xacb0ac87,0x2f802dba,0xab5eab05,0xafafafed,0xad00acd8,0x2f1a2ffc,
0xac07abb7,0xab05ae1f,0xad4dad27,0x28142d00,0xac5dac32,0x29f19cb6,0xad96ad72,0xac5da515,0xafafaf80,0xafa0afe6,0xafa0afc9,0x2d002f46,
0xafedafd4,0xa934adba,0xaf30af6e,0xa81426a1,0xb000affc,0x2c87244e,0xae99aee9,0xaf6ead4d,0xafe6aff8,0x2fff2f02,0xaddcae3f,0xaed0aff8,
0xaeb5af30,0xaa4eae5e,0x9648a44e,0xac5d9fd9,0xad72ae1f,0x2cb0230e,0x2765230e,0xafffaf1a,0xabb7acb0,0x2ff82f46,0x2b5e2993,0xabb7aed0,
0xa814a9f1,0x2b052e99,0x2d4d2c87,0x2c071648,0xa44ea8d5,0x2b05a30e,0x2f912f02,0xafbcafa0,0x26a11cb6,0x30002ed0,0x30002fe6,0xa5dbad72,
0x2c3229f1,0x2aaa2eb5,0x2f802fdd,0x2e7c29f1,0x2e3f2d4d,0xad27a44e,0x2e1f2ee9,0x2f022ffc,0x2d4d2bb7,0x2fbc2d27,0x2cd82e1f,0x9fd9ad00,
0x2f5a2e7c,0x2c872f80,0x26a12aaa,0x2f5a2c32,0x2fff2fdd,0xacb09648,0xa7659648,0x2d722fd4,0x2f1a2fbc,0xafafaf91,0xad00ab05,0xab5e244e,
0x30002fbc,0x2e992ffc,0xac87a934,0x2f6e2c07,0x2ed02faf,0xa99328d5,0xaf46ae1f,0x2cb02faf,0x2b5e2d72,0xaff4aed0,0xaff4afe6,0xad279cb6,
0x9fd926a1,0xa44eadba,0xae5eaf6e,0xaf30afd4,0x2d272ed0,0x230e2ddc,0xafafafff,0x2d272fe6,0x1fd929f1,0xafbcac87,0xacd8ae99,0xad4d9648,
0xac5da814,0xaa4eaf30,0x9648a934,0xaeb5afed,0xaf80ae3f,0x2ed028d5,0x2cb028d5,0x2aaaa875,0xa51526a1,0xad721648,0x9cb6aa4e,0xac3226a1,
0xae3fac07,0xae1faffc,0x2d272934,0xaf02afbc,0xaffcafa0,0x2cd8a30e,0x2fed2f02,0x2b05a8d5,0xad96af46,0x2e992fe6,0x2e992fc9,0x2f5a2f80,
0xafffadba,0xae7caeb5,0xafc9aeb5,0x2d722f6e,0x217ead4d,0x2ff42814,0x2875ac07,0xaff8ab05,0x2fed2e3f,0xad4d2b5e,0x2f912f1a,0x2e5ea875,
0xa5db2cb0,0x9648af80,0xa9f12aaa,0xa5db2ed0,0xad00afff,0xa17eafc9,0xa17eae7c,0xabb72d72,0x2ee925db,0x2d4d2f5a,0x2ffc2d96,0xa44eafdd,
0x29f12f91,0xafd4ac07,0xa6a12cd8,0x2d962f30,0xafc9ab5e,0x2f46a30e,0xaf80af02,0xafe6ab5e,0x25dbad4d,0x2d96ac07,0x2f5a2814,0xafddab05,
0x2f462f1a,0xa7652f02,0x25152f02,0x2f80a17e,0xad002765,0xa8d5afff,0xaff8ad72,0xad002cb0,0xacd8b000,0x2dfe2eb5,0x2934ac5d,0x244eaf5a,
0x2ee9217e,0x2ffc2875,0x2d4d2ff4,0xa44eaff8,0x25db2f46,0xaf6e2515,0xaf6ea765,0x2c5d2f80,0xafe6ad96,0x2d72ac87,0x9cb6aeb5,0xaed0ad96,
0x2bb7ab05,0xa8d52ee9,0x2fa02e5e,0x2ff42934,0x2f912e3f,0x2cd82f1a,0xac072b5e,0x2f30a875,0xad962765,0xaeb5ad72,0xac87afff,0xad962cb0,
0xa993afd4,0x2fc92a4e,0x2fe62a4e,0x2aaaae99,0x2ff82cd8,0xaff49fd9,0xa8752d4d,0xa17e2fbc,0x29f12fed,0xa6a12f91,0xafd4ad4d,0x2d962e5e,
0xafe6ad00,0x9cb6aff8,0x2d72a8d5,0xaed0ad00,0x2d27a993,0x28752fe6,0x28752fc9,0x2fa02aaa,0x29342fdd,0xac07af5a,0xafbcad96,0xaffca5db,
0xab5e2cb0,0xaf022aaa,0xa30eaf80,0xab5e2ed0,0xab05b000,0x2e5eac5d,0x2ee92eb5,0x2934af5a,0x2fdd2cd8,0xad962d4d,0xaf5a9fd9,0xa5db2fbc,
0xaddc2875,0x2cb0ae1f,0x2765ae1f,0x1cb6aff4,0xafc9a5db,0xaf80a9f1,0x2f469648,0xafe6a5db,0x2bb7acd8,0x2fa02934,0xa8d52dfe,0x2ff4244e,
0x29342ff8,0xafbca875,0xac07aff4,0xaffca17e,0xaf5aaddc,0x2fd42765,0x2fd42cb0,0x30001cb6,0xa993af6e,0x2765afdd,0xa515afdd,0xaaaa3000,
0x28d52f91,0xaf022e5e,0x230e2fed,0x2fa0ad4d,0xa814afaf,0x2f91a17e,0x9fd9aff8,0xaee9a30e,0x26a12fc9,0xaa4ead72,0x16482fff,0x26a12e7c,
0x2bb7af46,0x2f1aae7c,0x2f1aac32,0xaff42993,0xacd82eb5,0xaf301648,0xaf912a4e,0x2c072c5d,0x2dbaadfe,0x25db2e5e,0x2fdda814,0x2a4eaffc,
0xae7c2d27,0x2d72afaf,0xafff230e,0xafc92d27,0x2fd4a934,0x2f6ea44e,0x2dba2cd8,0xa6a1adfe,0xafff217e,0xa515ae3f,0xac32ae3f,0xaddc2fa0,
0x2faf2515,0xae1f2f80,0x28d52f46,0x2fafa765,0xaee9aa4e,0x2f91a5db,0x9fd9afdd,0xa814adba,0x2e5e2b5e,0x29342d00,0xab052faf,0x2ee9af1a,
0xac5daddc,0x2dbaafc9,0x2dbaae7c,0xae999cb6,0x27652f5a,0xaf8026a1,0xaf462c87,0xa5152f5a,0x230eaffc,0x217e2e5e,0x2ff8a814,0x2fafadfe,
0x1fd92faf,0xac072ff8,0xafed217e,0x2dfe230e,0x29f1afe6,0x2fddaaaa,0x2eb52993,0x29f1afc9,0xaddc2e99,0xa515adba,0xac32adba,0xafff2c5d,
0x2fa0ac07,0xaf022f30,0x230e2f91,0x28d52cd8,0xadba2ee9,0xafdd2dfe,0xa5dbaf30,0xaa4e2fbc,0x2fc9abb7,0x2aaa2b5e,0xa9932ff8,0x2fe6abb7,
0xafa09cb6,0x2e3fafc9,0x2e3fae7c,0xa17eaddc,0x2d4d2c5d,0xae5e1648,0xafed2a4e,0xaf912eb5,0xaff82765,0xae3f1cb6,0x2f02addc,0xaff82cb0,
0x2dfe2a4e,0xac072fdd,0xafed25db,0x1fd92dba,0xa6a1aee9,0x2f6ea934,0x2dba2b05,0x2fd4ae5e,0xaaaa2ff4,0x2765af1a,0xa515af1a,0xa993abb7,
0xacb0ac5d,0x9cb6ad96,0x2ddc29f1,0xa765ac5d,0xa30e2fbc,0xaff82dfe,0xa17eaf30,0xafaf2ee9,0x2dfeaf1a,0x244e2d00,0xacd82faf,0x29342b5e,
0xb0002993,0x2fddae7c,0x2fddac32,0x2f6eaf46,0x2ddcb000,0x2fe6afd4,0x2ed0afd4,0xafff2f5a,0xad279fd9,0x2d00aee9,0xabb7a814,0xae1f2f91,
0xae5e2ff4,0x9fd9a8d5,0xaf302fa0,0xa44e2bb7,0x2c872515,0xadba2aaa,0x2a4e2993,0x2c87a765,0x2ff4ad72,0x2e1fac32,0x2e1fa515,0xa8759cb6,
0x2814ae99,0x2ffcaf6e,0x2dfeb000,0xae5e2c87,0xaf5a2b05,0x2eb5afbc,0xac5da44e,0xb0002f91,0xac322fa0,0x2993ad00,0xaf462faf,0xae7c2fa0,
0x2c871fd9,0x16482814,0xa9f12ee9,0x2e99af91,0x2f80afa0,0x2c32a875,0x2e7ca875,0x2aaaad27,0xa30eac32,0x2f1aaddc,0x2e1fafff,0xa30ea515,
0xafed2d96,0x2ffcafd4,0xab05a6a1,0xacd829f1,0xa8142e1f,0xadfe2f02,0xaffc2e3f,0x2e5ead27,0x2e99a993,0xaa4e2cb0,0xaa4e2ed0,0x2fd4af46,
0x2e7cb000,0x1cb625db,0x2ddca6a1,0x2fc9b000,0xa875a934,0x2b5ea814,0x2f1aafed,0x2e3faf30,0xaf302ff4,0xafed2fa0,0xa814a8d5,0xa9342bb7,
0x16482c32,0xafd42fff,0xafdd2ddc,0x16482515,0x2f46ac5d,0xaed02f6e,0xacb02f6e,0x2993a5db,0x2e1fafed,0xad002dfe,0x2bb71fd9,0x2d27ac07,
0xaf5a2cd8,0xac5d2b05,0x2eb5affc,0xb0002fed,0xae7c2ff4,0xaddc2d27,0x9cb6ab5e,0xafc92ff4,0x217e2aaa,0xaf022e7c,0xaf022c32,0xaf1a2f80,
0x2f30ac87,0xafbc2f6e,0xaee93000,0xadfe2e99,0xa8d5a515,0x2875a993,0x2e3faaaa,0xa8d52765,0xaf912d96,0x244ea6a1,0x2fbcafd4,0xab0529f1,
0xae992fed,0x96489fd9,0x29f1adfe,0xac872c07,0x9cb62bb7,0xa515217e,0xac32217e,0xad722d00,0x2c32ae99,0x2f46af5a,0xa9932d96,0x2e7cae99,
0xa875a44e,0x2f1aaf30,0x2b5e9fd9,0x2e3fae5e,0xaf302d27,0x2ee9af02,0x2fbcae3f,0x2dfeae1f,0xaf6e2fff,0x2eb5aed0,0x2eb5afe6,0x2dbaaddc,
0xaddcadba,0xafe6aeb5,0xaed0aeb5,0x2fff2f6e,0xae1fadfe,0xae3fafbc,0xaf02aee9,0x2d272f30,0xae5eae3f,0x9fd9ab5e,0xaf30af1a,0xa44e2875,
0xae99ae7c,0x2d962993,0xaf5aaf46,0xae99ac32,0xad00ad72,0xa17eac32,0xa17ea515,0xabb79cb6,0xac07ac87,0x2dfe29f1,0x1fd99648,0xafedae99,
0xa9f1ab05,0x2fd42fbc,0x26a1244e,0xad96af91,0xa765a8d5,0x2aaa2e3f,0x29932875,0x2515a8d5,0x2e992dfe,0x30002ee9,0x2f6e2fbc,0xac87af30,
0x2f802f1a,0x2c322f02,0x2e7c2f02,0x2aaaa17e,0x2ff42fc9,0xab5e1cb6,0x2d272ddc,0x2ff42e7c,0x2fed3000,0xaffcaeb5,0x2b052c5d,0x2cd82f5a,
0x2c072d27,0x9fd92bb7,0xadfead00,0x2fed2e1f,0x25db2993,0xaf6eacb0,0xaf6eaed0,0x2c5d2f46,0xa5151648,0xaddcafdd,0xafffafd4,0xac321648,
0xabb7a934,0x28d5a814,0xafa0afed,0xaff4af30,0xaf30ae3f,0xafedaf1a,0xa814ab5e,0xa9342875,0xb000afc9,0xa6a1addc,0x25db9cb6,0xb000ae7c,
0xaf46afd4,0x2ed02a4e,0x2cb02a4e,0xa993ae99,0xad27ae5e,0x2e3f2ffc,0x2f022dfe,0x2e1f2814,0xa9f1acd8,0x26a1ab05,0x2fd42ffc,0xad96afed,
0x2515a30e,0x2fff2e1f,0x2ddc2f1a,0x2c32a30e,0x2d272aaa,0x28752e7c,0x28752c32,0x2fa02f80,0x2f912e99,0xaee9a9f1,0xa8141648,0x9fd92c87,
0x2fa02e7c,0x2faf2f46,0xad00a993,0x2fa02c32,0x2f913000,0xa44e2c5d,0xafbcaeb5,0x2b052f5a,0x2c872e5e,0xb000adfe,0xaf6eaffc,0xae99a814,
0x9cb62875,0xa515ae1f,0xac32ae1f,0xad72aff4,0x27652c87,0xa9932a4e,0xaaaaadba,0xa5152c87,0xabb7a44e,0xafa0af30,0x28d59fd9,0xaff4ae5e,
0xaf91ae1f,0x2814abb7,0x2ee92d00,0x1fd9ad27,0xaf5aafff,0x2fd42ed0,0x2fd42fe6,0x30002ddc,0xaf46af6e,0xac32afdd,0xae7cafdd,0x29933000,
0x2b5ea934,0x2faf2cd8,0x2d00a44e,0xaf1aadfe,0x2ee92faf,0xaf30217e,0x2dfe2ff8,0x2fbc230e,0xac5d2765,0x29f1addc,0xad961cb6,0xac5d2cb0,
0x2bb7a993,0x2f1aa515,0x2f1a2765,0xaff4aaaa,0x2e5e2fd4,0xab052dba,0x29342f6e,0x2ee9a6a1,0xadba1fd9,0xa5dbafed,0xafddac07,0xaa4e2dfe,
0xacb0aff8,0x2ddc2f02,0x9cb6ae3f,0xa765aff8,0x2eb52f91,0x2a4e2fed,0x16482e5e,0x2c5dad4d,0xaddc217e,0xae7cae3f,0xafc9ae3f,0x9cb62fa0,
0xabb7afe6,0x2ff82993,0x2b5eaaaa,0xabb7afc9,0x2fbc2a4e,0xaf3025db,0x2dfe2fdd,0x2ee92dba,0xacd828d5,0xaf91230e,0xaf30af02,0x2c072fa0,
0xac5dafff,0x2dbaac32,0x2dbaa515,0xae99addc,0x2fc929f1,0xa9932eb5,0x2aaa2fdd,0x2fe629f1,0xa30e2dfe,0xa17eafed,0xaff8ac07,0xafaf1fd9,
0xadfeafaf,0xa814aff8,0x2e5ea17e,0xaffca30e,0x2f5a2515,0x2c872f46,0x26a12f80,0x2f5aa765,0x9cb62e99,0xae7cadba,0xafc9adba,0xaddc2c5d,
0xaf1aaee9,0x2faf2b05,0x2d00a934,0x2b5eae5e,0x2dbaa814,0x2fdd9fd9,0x25db2f91,0x2a4eaee9,0x27652faf,0xaf4628d5,0xaf80ae1f,0xa5152faf,
0xafa0addc,0x2e3fac32,0x2e3fa515,0xa17eafff,0x2dfea6a1,0xacd82dba,0x244e2f6e,0x29342fd4,0x2d272fc9,0x230e2fff,0xafafad72,0x2d272e7c,
0xaffcaa4e,0xa814afdd,0x2e5ea5db,0xadfeadba,0x2c5dac07,0x2a4e2f91,0x16482f30,0x2eb52cd8,0x29932ff4,0xac32af1a,0xae7caf1a,0xaf46abb7,
0xae7c26a1,0xafff1648,0x2d72aa4e,0xafc926a1,0x230eaee9,0x2ff89fd9,0x217e2f91,0x2fafa814,0x2d4d2fa0,0xafed230e,0xae5eaf02,0xaf9128d5,
0xb000aaaa,0x2fdda515,0x2fdd2765,0x2f6ea993,0x1cb6b000,0x2cb0afd4,0x2765afd4,0xaddc2f5a,0xa17e2ffc,0xaff42c07,0xa8752fbc,0x2ff8a934,
0x244eaff4,0x2dfe28d5,0x2934afa0,0xacd8abb7,0xa5db2fe6,0x9648af46,0xa9f12f80,0xa5db2fc9,0x2ff41cb6,0x2e1f2765,0x2e1f2cb0,0xa875addc,
0xafbca5db,0x1fd9af5a,0xad4dad96,0xacd82fdd,0x2f5a2934,0xaeb52ee9,0x2c5d2e5e,0x3000ab05,0xaed0ab5e,0x2f80a30e,0xaaaaaf02,0xacb0ab5e,
0xa5db2ffc,0xad962fbc,0xaf5a2c07,0x2fdda934,0x2aaaafa0,0x2fc9a875,0x2fe6a875,0xa993ad27,0xad002ed0,0xa8d5ad72,0xaff81cb6,0xad002fe6,
0x2e5ead96,0xad4d2fd4,0x2f9126a1,0x2feda9f1,0xafbca17e,0xad4da875,0x1fd9aff4,0xacd82ff8,0x2e992aaa,0xaa4e2fe6,0xaa4e2fc9,0x2fd4a993,
0xacb0ad96,0x2fffac87,0x2d72aeb5,0xa765ad96,0x28752f30,0xab5eac07,0xaf1a2cd8,0xae3f2f91,0x2934aff4,0x2e5eafa0,0x2ee928d5,0xab05abb7,
0xad962ed0,0xaeb51cb6,0xac87ad72,0xad962fe6,0x2f80ac5d,0xa7652f6e,0x25152f6e,0x2f46a5db,0xaff8244e,0x2ff4ad4d,0x2875affc,0x217eaee9,
0x2f5a244e,0x2c5d2934,0xaeb52dfe,0x3000acd8,0xacb0ad00,0x2d72aff8,0x2fffa8d5,0xa765ad00,0x217e2f80,0xaf022515,0xaf02a765,0xaf1a2f46,
0x2b05afdd,0xa8142f5a,0x2c072d96,0x2d4d25db,0xab5e2fe6,0xaf022f80,0xa30eaf46,0xab5e2fc9,0x2f30ad96,0x2cd826a1,0xac072fd4,0x2f91a9f1,
0xafdd244e,0x2d96affc,0x2f5aad4d,0x25dbaee9,0x2d722bb7,0xae7c217e,0xafc9217e,0xafff2d00,0xaed0a5db,0xaaaaa9f1,0x2f809648,0xacb0a5db,
0x28752e5e,0xaf1a2f91,0xab5ead4d,0xae3f2fed,0x2b05aff8,0x2c072875,0xa8142ff4,0x2d4d217e,0xaf6e2d72,0x2eb5afc9,0x2eb5ae7c,0x2dbaafff,
0x2f80af5a,0x2fc9ae99,0x2fe6ae99,0xaf462d96,0xa8d5ab05,0x2f02afed,0xa30eacd8,0xafa02ffc,0xafbc2f02,0x2934ad27,0xaffc2e1f,0xac072e3f,
0x26a12c32,0xaa4e1cb6,0x16482d72,0x26a12515,0x28752aaa,0xa8d52cb0,0xa8d52ed0,0x2e3faf80,0x2fedaeb5,0x29349648,0x2f30aa4e,0x2814ac5d,
0x1648ad4d,0x2e99acd8,0x2c87afbc,0xa9f11fd9,0xafe62d27,0x2fffafaf,0xaddc230e,0xaed02d27,0xafd42f30,0xaf6e2e5e,0xadba244e,0x26a11fd9,
0x9cb62d27,0xafe62ff4,0xaed02ff4,0x2d72ab5e,0x2fafacb0,0xae1f2f46,0x28d52993,0x2fafaed0,0x2c07af6e,0xa9342c87,0x2ffcae99,0x2fbcb000,
0xa44eab5e,0x2b05ad00,0x2f91afaf,0xafbc2f1a,0xafd42d72,0x1648a765,0x1648acb0,0xafdd2fff,0xac322f5a,0xaaaa26a1,0xaf802c87,0xae7c2f5a,
0x2d009fd9,0xae1f2cd8,0xad272fbc,0xabb72d4d,0x2ffcaf02,0x2ee9ae1f,0xa44e2d27,0x2d4dae3f,0x29f1ae7c,0x2fddaf80,0x2eb5aaaa,0x29f1ac32,
0xad7225db,0x2fe6b000,0x2ed0b000,0x1cb6a6a1,0xafa02fbc,0x2f02af91,0xa30eab05,0xa8d5244e,0x96482c07,0xac872d4d,0xae992b05,0x29f1a814,
0x2ed0abb7,0xa9932b5e,0xaf462ff8,0x2cb0abb7,0x2f1aafff,0xa30e2765,0xa30e2cb0,0x2e1fad72,0x1fd9ac5d,0x244e9648,0x2e5eaa4e,0x2f30aeb5,
0xaff82ed0,0xae3f2ddc,0x2f02afff,0xaff82fe6,0xad4d2f6e,0xaee92e99,0x244eac87,0xaffc3000,0x26a12814,0xaf6e2f30,0xadba2934,0xafd42fed,
0x2f46ad00,0xafc92fa0,0xafe62fa0,0xaf802faf,0x2515ac5d,0x2d72ad96,0x1cb629f1,0x2c32ac5d,0xad002814,0x2d27ad4d,0x2e1fab05,0x2bb7ac07,
0xaffc2f1a,0x2cd8ad00,0x2fedafaf,0x2b05ab5e,0xadba2f80,0x2c87acb0,0x2c87aed0,0x2a4eaaaa,0xaf80af6e,0xafc9afdd,0xafe6afdd,0x2f463000,
0xafa0af91,0xabb7ae5e,0xaff4afed,0x28d52d4d,0xafbcafaf,0x2934a17e,0xaffcaff8,0xac07a30e,0xafd4afc9,0x2f5a2d72,0xb000afff,0xafd4ae7c,
0x2bb72aaa,0x2f1a2cb0,0x2f1a2ed0,0xaff4af80,0x2cd82c5d,0x2f303000,0x2f912f5a,0xac07aeb5,0x2dba2d4d,0x25db2cd8,0x2fdd2fbc,0x2a4e9fd9,
0x2e7c2e1f,0xad72a875,0x2fff2ff4,0x2fc92e1f,0x26a12934,0xa9f1244e,0xad96acd8,0x2fd42dfe,0x9cb6217e,0xafe6ae3f,0xaed0ae3f,0x2d722fa0,
0xa875a515,0xad27af80,0xafa0af46,0xa8752765,0xac07aa4e,0x2934a5db,0xaffcafdd,0xafbcadba,0xae5eaf1a,0xa934ae3f,0x2b052875,0xaee9ab5e,
0xac5dad72,0x2dba2765,0x2dba2cb0,0xae99afff,0xa765aa4e,0x2f802fd4,0x2f462e99,0x2515aa4e,0x230e9fd9,0x217e2cd8,0x2ff82fbc,0x2faf2d4d,
0x2ffc2faf,0x2ee92ff8,0xa44e217e,0x2d4d230e,0x2f6e2fe6,0xa5db2aaa,0xac5da993,0x2f6e2fc9,0x2d722e99,0xafe6adba,0xaed0adba,0x9cb62c5d,
0x28d52c07,0xabb7af30,0xaff4af91,0xafa0acd8,0xadbaac07,0xafddad4d,0xa5dbab05,0xaa4e2814,0xafc9af02,0xaaaaaf1a,0x2993217e,0xafe6af02,
0xafa0afff,0x2e3f2765,0x2e3f2cb0,0xa17ead72,0xad4daeb5,0x2e5e3000,0x2fed2f5a,0x2f912c5d,0x217ea765,0x2d009cb6,0x2bb72ddc,0x217eacb0,
0x2d4d2a4e,0x2ee92fdd,0xa44e25db,0x2ffc2dba,0x2fd42ee9,0xa9f12934,0xad96ab05,0x26a12e5e,0x2f462ff4,0xafc9af1a,0xafe6af1a,0xaf80abb7,
0x2cb02eb5,0x1cb62dba,0xaddcaf6e,0x27652eb5,0xa30e2814,0xaff8ad4d,0xa17eab05,0xafafac07,0xadfeab5e,0xa44eae3f,0x2cd82875,0xa934af1a,
0xb000af80,0x2fdd2cb0,0x2fdd2ed0,0x2f6e2aaa,0xad72b000,0xa515afd4,0xac32afd4,0x9cb62f5a,0x2e1f1fd9,0x2e3f2ee9,0x2f022814,0xad27af91,
0x2cd82ff4,0xaffca8d5,0x2b052fa0,0x2fed2bb7,0xae99a515,0x2d96aaaa,0xaf5aa993,0xae992765,0x2ff42ddc,0x2e1f2ed0,0x2e1f2fe6,0xa875afff,
0xa8142c87,0xaffca9f1,0xadfe1648,0x2e5e2e99,0xaf5aaf30,0x2eb5a814,0xac5dafed,0xb000a934,0x2c32a8d5,0xa9932e3f,0x2f462875,0x2e7ca8d5,
0xae999fd9,0xb000a814,0xaf6eaee9,0x2c872f91,0xa993afa0,0x2ed0a875,0x2cb0a875,0xaf46ad27,0x2ff42c32,0xab5e2ddc,0x2d272fff,0x2ff42515,
0xa44e2d96,0x9fd9afd4,0xaf30a6a1,0xae5e29f1,0x2814ad27,0x2dfeabb7,0x2ffc2d00,0xae5eae1f,0x2e992f80,0xaa4e2e7c,0xaa4e2c32,0x2fd42aaa,
0xae7c1648,0x9cb6afdd,0xaddcafd4,0xafc91648,0xa875af91,0x2b5e2fbc,0x2f1a244e,0x2e3fab05,0x2b052ff4,0xa44e2fa0,0xafbca8d5,0x2f912bb7,
0xb000ac32,0xa6a1afff,0x25dbaddc,0xb000a515,0x2aaaac5d,0x2c322f6e,0x2e7c2f6e,0x2f80a5db,0x2d272fed,0xae3fadfe,0xaf029fd9,0xae1f2c07,
0xaf5aae5e,0xac5daf30,0x2eb59fd9,0xb000a44e,0x2e7ca30e,0x2ddc2e1f,0x1cb62f1a,0x2fc9a30e,0x217e2f46,0xaf02acb0,0xaf02aed0,0xaf1a2993,
0xaf30ae99,0x2fbc29f1,0x2ee99648,0x2dfeac87,0x2fa02515,0x2faf2993,0xad002aaa,0x2fa0a765,0xa9342d96,0xafeda6a1,0xa814afd4,0xaf3029f1,
0xac87afed,0x30001fd9,0x2f6e2dfe,0x2e99ac07,0x2fff2bb7,0xafe6217e,0xaed0217e,0xaddc2d00,0xac322c87,0xaf462a4e,0x2993adba,0xae7c2c87,
0xa875afed,0x2f1aab05,0x2b5e2ffc,0x2e3facd8,0x2f302e1f,0xaee92bb7,0xafbcad00,0xadfe2d27,0xaf6e9cb6,0x2eb5ac32,0x2eb5a515,0x2dbaad72,
0x2aaaaf5a,0x2ed0ae99,0x2cb0ae99,0xaf802d96,0xab5e2f30,0xafaf244e,0xad002e5e,0x2f1a1fd9,0x2c07af02,0x2b052d27,0x2d4dae1f,0xa814ae3f,
0xac5d2ed0,0x29f1afff,0xad962ddc,0xac5d2fe6,0x28752f80,0xa8d52fe6,0xa8d52fc9,0x2e3faf46,0xa44eafd4,0x2f91adba,0x2b05af6e,0xafbc26a1,
0x96482ffc,0xae99a44e,0xac872ee9,0x29f12d4d,0x2515aff8,0x1cb62f02,0x2d72ae3f,0x2c32aff8,0xaeb5ab05,0xaa4eacd8,0x9648afed,0xac5d2ffc,
0x2d722d27,0xacb02ff4,0xa7652ff4,0x2fffab5e,0xabb7ae7c,0x2ff8aaaa,0x2b5eaf80,0xabb7ac32,0x28142f6e,0xab05ac87,0xad4d2e99,0xac073000,
0x2feda8d5,0x2f30a30e,0x29342f02,0x2814afa0,0xafd49cb6,0x1648aed0,0x1648afe6,0xafdd2d72,0x2ed029f1,0xaf462eb5,0xa9932fdd,0x2cb029f1,
0xad00ad4d,0x2e1f244e,0x2d27aee9,0x2bb7affc,0xad4d2f02,0xafbc2e1f,0xacd8ad27,0x1fd92e3f,0x2f5aacb0,0x2c872993,0x26a12f46,0x2f5aaed0,
0xafff25db,0x2cb0b000,0x2765b000,0xad72a6a1,0x2f1a2814,0xafaf2934,0xad002f30,0xab5e2fed,0x1648afbc,0x2c87affc,0x2e992934,0xa9f1ac07,
0xac322faf,0xaf8028d5,0xaaaaae1f,0xae7c2faf,0x2f1aad72,0xa30e2ed0,0xa30e2fe6,0x2e1f1cb6,0xaffc26a1,0x2fedadba,0x2cd8af6e,0x2b05afd4,
0x2d272c32,0x230e2d72,0xafaf1cb6,0x2d272515,0x9fd9af6e,0x2fbcae99,0x2cd82c87,0x2d4db000,0xac5d2fbc,0xaa4eab05,0x9648af91,0xaeb5244e,
0x2f80ad00,0xaed02fa0,0xacb02fa0,0xaaaa2faf,0xafe626a1,0xaddc1648,0x2fffaa4e,0xaed026a1,0x2d002c07,0xad272ffc,0xae1fa934,0xabb72fbc,
0x1fd9afa0,0x2e5ea30e,0x244e2f02,0x2f30a8d5,0xadba2f46,0x2c87afe6,0x2c87afc9,0x2a4eaf80,0x2fffad96,0x2e7cac5d,0x2fc9ac5d,0xad7229f1,
0x217eadfe,0x2ff4afbc,0x2875aee9,0xaff82f30,0xafed2d00,0x2d4daf1a,0xaf912b5e,0xae5e2faf,0xa5db2e7c,0x9648a993,0xa9f12f46,0xa5db2c32,
0xae3f2fff,0xaff82fc9,0xaff82e7c,0x2f02ad72,0x2c0725db,0xadfe2f5a,0x9fd92d96,0x2fedafdd,0x2f6eaf91,0xa6a12c07,0x2fd4acd8,0x2dbaaf30,
0xa765ab5e,0x2aaaa30e,0x2993af02,0x2515ab5e,0x25dbadfe,0x2d96aee9,0x2f5aafbc,0xafdd2f30,0xaf462b5e,0x2765abb7,0xa515abb7,0xaf802ff8,
0xad002fc9,0xa8d51cb6,0xaff82ddc,0xad002e7c,0x2cd81648,0xadfe2c5d,0xa9342eb5,0xa44e2a4e,0x2c07217e,0x9fd92875,0xadfe2ff4,0x2fedaff8,
0x2fddaf46,0x29f1a515,0x29f12765,0x2eb5af80,0x2515ad96,0x2ddcac87,0x2fffaeb5,0x2c32ad96,0xaf022b05,0x2fa0aee9,0x28d5ae5e,0x230ea934,
0xaf912d00,0xacd82b5e,0x2c07af1a,0xaf302faf,0xad962fc9,0xaeb52ddc,0xac871cb6,0xad962e7c,0x299326a1,0xafc92f5a,0xafe62f5a,0xaaaa2c87,
0x2ff8ae5e,0xaff42ffc,0xa8752dfe,0xa17e2814,0x2f6eafed,0x2fd4af91,0xa6a12d4d,0x2dbaae5e,0x2515ad00,0x2fffaff8,0x2ddca8d5,0x2c32ad00,
0xae1f2993,0x2fafafe6,0x2fafafc9,0x28d5aaaa,0xaf912fdd,0x2ee9af5a,0x2814ad96,0x1fd9a5db,0xab5e2e7c,0xaf022f46,0xa30ea993,0xab5e2c32,
0x2b051648,0xae5e2eb5,0xaee92c5d,0xa9342a4e,0x2fddae5e,0xad962dfe,0xaf5a2ffc,0xa5db2814,0x2ddcafaf,0xacb02d27,0xa7652d27,0x9cb6230e,
0xa765a5db,0x2993a9f1,0x2aaa9648,0x2515a5db,0xaf022cd8,0x28d5a934,0x2fa0adfe,0x230ea44e,0xaf912ff8,0x2814a875,0x2ee9aff4,0x1fd9a17e,
0xaa4e2ddc,0x26a1a765,0x26a1acb0,0x16489cb6,0x9d7f9e49,0xaddcaeb3,0x12480000,0x22ad0000,0x9bdb9cb6,0xac2ead04,0x18b61648,0x290226ad,
0x98b69a49,0xa902aaaf,0x1bdb1a49,0x2c2e2aaf,0x92489648,0xa2ada6ad,0x1d7f1cb6,0x2ddc2d04,0xa420a4b7,0xae8daf7f,0x18b60000,0x23760000,
0xa1e4a312,0xacacad9c,0x1f121cb6,0x29992777,0x9f12a0b6,0xa999ab78,0x21e420b6,0x2cac2b78,0x98b69cb6,0xa376a777,0x24202312,0x2e8d2d9c,
0xa6e0a7db,0xaf3fb025,0x1bdb0000,0x24200000,0xa4e9a5e4,0xad2aae34,0x21e41fdb,0x2a312820,0xa1e4a3db,0xaa31ac21,0x24e923db,0x2d2a2c21,
0x9bdb9fdb,0xa420a820,0x26e025e4,0x2f3f2e34,0xa8d0a980,0xaff2b08c,0x1d7f0000,0x24840000,0xa6e0a820,0xada9aecd,0x2420217f,0x2ac82885,
0xa420a580,0xaac8ac86,0x26e02580,0x2da92c86,0x9d7fa17f,0xa484a885,0x28d02820,0x2ff22ecd,0xaa31ab13,0xb052b0f3,0x1f120000,0x24e90000,
0xa86ba94e,0xae28af65,0x254d2312,0x2b5f28e9,0xa54da712,0xab5faceb,0x286b2712,0x2e282ceb,0x9f12a312,0xa4e9a8e9,0x2a31294e,0x30522f65,
0xab91ac54,0xb0acb15a,0x20520000,0x254d0000,0xa967aa7c,0xaea7affe,0x267b2452,0x2bf6294e,0xa67ba852,0xabf6ad50,0x29672852,0x2ea72d50,
0xa052a452,0xa54da94e,0x2b912a7c,0x30ac2ffe,0xac79ad1e,0xb106b1c1,0x211b0000,0x25b20000,0xaa63abab,0xaf26b04c,0x27a9251b,0x2c4729b3,
0xa7a9a91c,0xac47adb6,0x2a63291c,0x2f262db6,0xa11ba51b,0xa5b2a9b3,0x2c792bab,0x3106304c,0xad2aade8,0xb160b229,0x21e40000,0x26170000,
0xab5fac6d,0xafa5b099,0x286b25e4,0x2c932a17,0xa86ba9e5,0xac93ae1b,0x2b5f29e5,0x2fa52e1b,0xa1e4a5e4,0xa617aa17,0x2d2a2c6d,0x31603099,
0xb1bbb292,0xb44fb4f6,0x267b0000,0x28d00000,0xb012b0e6,0xb216b357,0x2cde2a7c,0x2f3f2cd2,0xacdeae80,0xaf3fb0d9,0x30122e80,0x321630d9,
0xa67baa7c,0xa8d0acd2,0x31bb30e6,0x344f3357,0xb216b2fb,0xb47eb52d,0x26e00000,0x29020000,0xb052b133,0xb257b3a7,0x2d2a2ae1,0x2f8c2d04,
0xad2aaee6,0xaf8cb10c,0x30522ee6,0x3257310c,0xa6e0aae1,0xa902ad04,0x32163133,0x347e33a7,0xb271b364,0xb4aeb565,0x27440000,0x29350000,
0xb092b181,0xb298b3f7,0x2d762b46,0x2fd82d37,0xad76af4c,0xafd8b140,0x30922f4c,0x32983140,0xa744ab46,0xa935ad37,0x32713181,0x34ae33f7,
0xb2cdb3cf,0xb4deb59d,0x27a90000,0x29670000,0xb0d2b1ce,0xb2dab423,0x2dc22bab,0x30122d6a,0xadc2afb2,0xb012b174,0x30d22fb2,0x32da3174,
0xa7a9abab,0xa967ad6a,0x32cd31ce,0x34de3423,0xb329b41d,0xb50eb5d6,0x28070000,0x29990000,0xb113b21c,0xb31cb44c,0x2e0e2c08,0x30392d9c,
0xae0eb00c,0xb039b1a7,0x3113300c,0x331c31a7,0xa807ac08,0xa999ad9c,0x3329321c,0x350e344c,0xb386b453,0xb53fb60f,0x28390000,0x29cc0000,
0xb153b26b,0xb35eb474,0x2e5a2c3a,0x305f2dcf,0xae5ab03f,0xb05fb1db,0x3153303f,0x335e31db,0xa839ac3a,0xa9ccadcf,0x3386326b,0x353f3474,
0xb3e3b489,0xb570b649,0x286b0000,0x29fe0000,0xb194b2b9,0xb3a0b49d,0x2ea72c6d,0x30852e02,0xaea7b072,0xb085b20f,0x31943072,0x33a0320f,
0xa86bac6d,0xa9feae02,0x33e332b9,0x3570349d,0xb420b4bf,0xb5a1b683,0x289e0000,0x2a310000,0xb1d5b308,0xb3e3b4c6,0x2ef32c9f,0x30ac2e34,
0xaef3b0a5,0xb0acb243,0x31d530a5,0x33e33243,0xa89eac9f,0xaa31ae34,0x34203308,0x35a134c6,0xb5d2b6be,0xb76fb857,0x2a630000,0x2bf60000,
0xb413b4ef,0xb523b642,0x30d22e67,0x32092ffe,0xb0d2b278,0xb209b40f,0x34133278,0x3523340f,0xaa63ae67,0xabf6affe,0x35d234ef,0x376f3642,
0xb604b6fa,0xb7a5b878,0x2a950000,0x2c140000,0xb434b519,0xb546b66d,0x30f92e9a,0x32303019,0xb0f9b2ac,0xb230b42a,0x343432ac,0x3546342a,
0xaa95ae9a,0xac14b019,0x36043519,0x37a5366d,0xb637b736,0xb7dbb899,0x2ac80000,0x2c2e0000,0xb456b542,0xb569b699,0x31202ecd,0x32573032,
0xb120b2e1,0xb257b445,0x345632e1,0x35693445,0xaac8aecd,0xac2eb032,0x36373542,0x37db3699,0xb66ab773,0xb809b8bb,0x2afa0000,0x2c470000,
0xb478b56c,0xb58cb6c6,0x31462f00,0x327e304c,0xb146b315,0xb27eb460,0x34783315,0x358c3460,0xaafaaf00,0xac47b04c,0x366a356c,0x380936c6,
0xb69db7b0,0xb825b8dd,0x2b2d0000,0x2c600000,0xb49ab596,0xb5afb6f2,0x316d2f32,0x32a53065,0xb16db34a,0xb2a5b47b,0x349a334a,0x35af347b,
0xab2daf32,0xac60b065,0x369d3596,0x382536f2,0xb6d1b7ee,0xb841b8ff,0x2b5f0000,0x2c790000,0xb4bcb5c1,0xb5d2b71f,0x31942f65,0x32cd307f,
0xb194b37f,0xb2cdb496,0x34bc337f,0x35d23496,0xab5faf65,0xac79b07f,0x36d135c1,0x3841371f,0xb705b817,0xb85db923,0x2b910000,0x2c930000,
0xb4deb5eb,0xb5f6b74d,0x31bb2f98,0x32f43099,0xb1bbb3b4,0xb2f4b4b1,0x34de33b4,0x35f634b1,0xab91af98,0xac93b099,0x370535eb,0x385d374d,
0xb73ab837,0xb87ab946,0x2bc40000,0x2cac0000,0xb500b616,0xb61ab77a,0x31e22fcb,0x331c30b2,0xb1e2b3e9,0xb31cb4cd,0x350033e9,0x361a34cd,
0xabc4afcb,0xacacb0b2,0x373a3616,0x387a377a,0xb897b96b,0xb98dbaa6,0x2cc50000,0x2d900000,0xb63eb7a8,0xb767b895,0x334330cc,0x3442319a,
0xb343b4e8,0xb442b5c8,0x363e34e8,0x376735c8,0xacc5b0cc,0xad90b19a,0x389737a8,0x398d3895,0xb8b4b990,0xb9aebad1,0x2cde0000,0x2da90000,
0xb662b7d7,0xb78db8ae,0x336b30e6,0x345631b4,0xb36bb504,0xb456b5e4,0x36623504,0x378d35e4,0xacdeb0e6,0xada9b1b4,0x38b437d7,0x39ae38ae,
0xb8d2b9b5,0xb9cfbafd,0x2cf80000,0x2dc20000,0xb687b803,0xb7b4b8c7,0x339330ff,0x346a31ce,0xb393b51f,0xb46ab601,0x3687351f,0x37b43601,
0xacf8b0ff,0xadc2b1ce,0x38d23803,0x39cf38c7,0xb8f0b9dc,0xb9f1bb29,0x2d110000,0x2ddc0000,0xb6acb81b,0xb7dbb8e1,0x33bb3119,0x347e31e8,
0xb3bbb53b,0xb47eb61e,0x36ac353b,0x37db361e,0xad11b119,0xaddcb1e8,0x38f0381b,0x39f138e1,0xb90fba02,0xba14bb57,0x2d2a0000,0x2df50000,
0xb6d1b833,0xb801b8fb,0x33e33133,0x34933202,0xb3e3b557,0xb493b63a,0x36d13557,0x3801363a,0xad2ab133,0xadf5b202,0x390f3833,0x3a1438fb,
0xb92eba2a,0xba37bb86,0x2d440000,0x2e0e0000,0xb6f6b84b,0xb815b915,0x3405314d,0x34a7321c,0xb405b573,0xb4a7b657,0x36f63573,0x38153657,
0xad44b14d,0xae0eb21c,0x392e384b,0x3a373915,0xb94dba53,0xba5abbb6,0x2d5d0000,0x2e280000,0xb71bb863,0xb829b930,0x34193167,0x34bc3236,
0xb419b58f,0xb4bcb675,0x371b358f,0x38293675,0xad5db167,0xae28b236,0x394d3863,0x3a5a3930,0xb96dba7c,0xba7ebbe7,0x2d760000,0x2e410000,
0xb741b87c,0xb83db94b,0x342e3181,0x34d03250,0xb42eb5ab,0xb4d0b692,0x374135ab,0x383d3692,0xad76b181,0xae41b250,0x396d387c,0x3a7e394b,
0xa17fa248,0xb1cfb2a1,0x16480000,0x26ad0000,0x9fdba0b6,0xb029b0fd,0x1cb61a48,0x2d002aac,0x9cb69e48,0xad00aeaa,0x1fdb1e48,0x30292eaa,
0x96489a48,0xa6adaaac,0x217f20b6,0x31cf30fd,0xa81fa8b6,0xb27cb365,0x1cb60000,0x27760000,0xa5e4a711,0xb0a6b191,0x231120b6,0x2d972b75,
0xa311a4b6,0xad97af72,0x25e424b6,0x30a62f72,0x9cb6a0b6,0xa776ab75,0x281f2711,0x327c3191,0xaadeabd9,0xb328b414,0x1fdb0000,0x281f0000,
0xa8e8a9e3,0xb122b226,0x25e423db,0x2e2d2c1f,0xa5e4a7da,0xae2db01d,0x28e827da,0x3122301d,0x9fdba3db,0xa81fac1f,0x2ade29e3,0x33283226,
0xaccead7e,0xb3d3b475,0x217f0000,0x28840000,0xaadeac1f,0xb19eb2b9,0x281f257f,0x2ec32c83,0xa81fa97f,0xaec3b080,0x2ade297f,0x319e3080,
0xa17fa57f,0xa884ac83,0x2cce2c1f,0x33d332b9,0xae2daf0e,0xb43eb4d5,0x23110000,0x28e80000,0xac6aad4c,0xb219b34c,0x294d2711,0x2f592ce7,
0xa94dab11,0xaf59b0e4,0x2c6a2b11,0x321930e4,0xa311a711,0xa8e8ace7,0x2e2d2d4c,0x343e334c,0xaf8bb04e,0xb493b534,0x24520000,0x294d0000,
0xad65ae78,0xb294b3df,0x2a7a2852,0x2fef2d4c,0xaa7aac51,0xafefb147,0x2d652c51,0x32943147,0xa452a852,0xa94dad4c,0x2f8b2e78,0x349333df,
0xb074b115,0xb4e7b593,0x251b0000,0x29b10000,0xae5fafa4,0xb30fb438,0x2ba7291b,0x30422db0,0xaba7ad1a,0xb042b1aa,0x2e5f2d1a,0x330f31aa,
0xa51ba91b,0xa9b1adb0,0x30742fa4,0x34e73438,0xb122b1db,0xb53ab5f1,0x25e40000,0x2a160000,0xaf59b067,0xb389b481,0x2c6a29e3,0x308d2e14,
0xac6aade2,0xb08db20d,0x2f592de2,0x3389320d,0xa5e4a9e3,0xaa16ae14,0x31223067,0x353a3481,0xb58db64e,0xb805b887,0x2a7a0000,0x2cce0000,
0xb402b4c9,0xb5dfb6f9,0x30d72e78,0x332830cb,0xb0d7b26f,0xb328b4bd,0x3402326f,0x35df34bd,0xaa7aae78,0xacceb0cb,0x358d34c9,0x380536f9,
0xb5dfb6aa,0xb82ab8b0,0x2ade0000,0x2d000000,0xb43eb511,0xb61ab73d,0x31222edc,0x337130fd,0xb122b2d2,0xb371b4ed,0x343e32d2,0x361a34ed,
0xaadeaedc,0xad00b0fd,0x35df3511,0x382a373d,0xb631b705,0xb850b8d8,0x2b430000,0x2d330000,0xb47bb558,0xb654b780,0x316c2f40,0x33ba312e,
0xb16cb334,0xb3bab51d,0x347b3334,0x3654351d,0xab43af40,0xad33b12e,0x36313558,0x38503780,0xb682b75e,0xb874b900,0x2ba70000,0x2d650000,
0xb4b7b59f,0xb68db7c2,0x31b62fa4,0x34023160,0xb1b6b396,0xb402b54c,0x34b73396,0x368d354c,0xaba7afa4,0xad65b160,0x3682359f,0x387437c2,
0xb6d2b7b7,0xb899b927,0x2c060000,0x2d970000,0xb4f3b5e5,0xb6c6b802,0x32013004,0x34263191,0xb201b3f7,0xb426b57c,0x34f333f7,0x36c6357c,
0xac06b004,0xad97b191,0x36d235e5,0x38993802,0xb721b807,0xb8bcb94d,0x2c380000,0x2dc90000,0xb52fb62b,0xb6ffb822,0x324b3036,0x344b31c3,
0xb24bb42c,0xb44bb5ab,0x352f342c,0x36ff35ab,0xac38b036,0xadc9b1c3,0x3721362b,0x38bc3822,0xb76fb832,0xb8e0b972,0x2c6a0000,0x2dfb0000,
0xb56ab670,0xb737b842,0x32943067,0x346f31f4,0xb294b45d,0xb46fb5da,0x356a345d,0x373735da,0xac6ab067,0xadfbb1f4,0x376f3670,0x38e03842,
0xb7bdb85d,0xb902b996,0x2c9c0000,0x2e2d0000,0xb5a5b6b5,0xb76fb862,0x32de3099,0x34933226,0xb2deb48d,0xb493b608,0x35a5348d,0x376f3608,
0xac9cb099,0xae2db226,0x37bd36b5,0x39023862,0xb924b9ba,0xba1dbab5,0x2e5f0000,0x2fef0000,0xb7a6b881,0xb8a8b96d,0x34b73257,0x35d433df,
0xb4b7b637,0xb5d4b7a1,0x37a63637,0x38a837a1,0xae5fb257,0xafefb3df,0x39243881,0x3a1d396d,0xb946b9dc,0xba39bad0,0x2e910000,0x30100000,
0xb7ddb8a0,0xb8c1b989,0x34db3288,0x35f73408,0xb4dbb665,0xb5f7b7cd,0x37dd3665,0x38c137cd,0xae91b288,0xb010b408,0x394638a0,0x3a393989,
0xb966b9fe,0xba54bae9,0x2ec30000,0x30290000,0xb80ab8bf,0xb8dbb9a4,0x34ff32b9,0x361a3420,0xb4ffb693,0xb61ab7f9,0x380a3693,0x38db37f9,
0xaec3b2b9,0xb029b420,0x396638bf,0x3a5439a4,0xb986ba1f,0xba6fbb02,0x2ef50000,0x30420000,0xb825b8dd,0xb8f3b9be,0x352332ea,0x363c3438,
0xb523b6c1,0xb63cb812,0x382536c1,0x38f33812,0xaef5b2ea,0xb042b438,0x398638dd,0x3a6f39be,0xb9a6ba3f,0xba89bb1a,0x2f270000,0x305b0000,
0xb840b8fb,0xb90cb9d8,0x3546331b,0x365f3451,0xb546b6ee,0xb65fb828,0x384036ee,0x390c3828,0xaf27b31b,0xb05bb451,0x39a638fb,0x3a8939d8,
0xb9c5ba5e,0xbaa2bb30,0x2f590000,0x30740000,0xb85ab918,0xb924b9f2,0x356a334c,0x36823469,0xb56ab71b,0xb682b83d,0x385a371b,0x3924383d,
0xaf59b34c,0xb074b469,0x39c53918,0x3aa239f2,0xb9e3ba7c,0xbababb46,0x2f8b0000,0x308d0000,0xb874b935,0xb93cba0b,0x358d337d,0x36a43481,
0xb58db748,0xb6a4b852,0x38743748,0x393c3852,0xaf8bb37d,0xb08db481,0x39e33935,0x3aba3a0b,0xba00ba99,0xbad1bb5a,0x2fbd0000,0x30a60000,
0xb88eb951,0xb954ba23,0x35b133ae,0x36c63499,0xb5b1b775,0xb6c6b867,0x388e3775,0x39543867,0xafbdb3ae,0xb0a6b499,0x3a003951,0x3ad13a23,
0xbae8bb6e,0xbb7fbbdd,0x30be0000,0x31850000,0xb96bba3b,0xba19bae6,0x36e834b1,0x37f33570,0xb6e8b87c,0xb7f3b91d,0x396b387c,0x3a19391d,
0xb0beb4b1,0xb185b570,0x3ae83a3b,0x3b7f3ae6,0xbafebb80,0xbb8ebbe6,0x30d70000,0x319e0000,0xb982ba52,0xba2dbaf9,0x370a34c9,0x380a3587,
0xb70ab891,0xb80ab930,0x39823891,0x3a2d3930,0xb0d7b4c9,0xb19eb587,0x3afe3a52,0x3b8e3af9,0xbb13bb91,0xbb9cbbed,0x30f00000,0x31b60000,
0xb999ba69,0xba41bb0b,0x372c34e1,0x381a359f,0xb72cb8a6,0xb81ab943,0x399938a6,0x3a413943,0xb0f0b4e1,0xb1b6b59f,0x3b133a69,0x3b9c3b0b,
0xbb27bba0,0xbba9bbf4,0x31090000,0x31cf0000,0xb9afba7f,0xba54bb1d,0x374e34f9,0x382a35b6,0xb74eb8ba,0xb82ab956,0x39af38ba,0x3a543956,
0xb109b4f9,0xb1cfb5b6,0x3b273a7f,0x3ba93b1d,0xbb3abbaf,0xbbb5bbf8,0x31220000,0x31e80000,0xb9c5ba95,0xba67bb2e,0x376f3511,0x383a35ce,
0xb76fb8ce,0xb83ab969,0x39c538ce,0x3a673969,0xb122b511,0xb1e8b5ce,0x3b3a3a95,0x3bb53b2e,0xbb4cbbbc,0xbbc0bbfc,0x313b0000,0x32010000,
0xb9dabaaa,0xba7abb3e,0x37903529,0x384a35e5,0xb790b8e2,0xb84ab97b,0x39da38e2,0x3a7a397b,0xb13bb529,0xb201b5e5,0x3b4c3aaa,0x3bc03b3e,
0xbb5ebbc9,0xbbcbbbff,0x31530000,0x32190000,0xb9f0babf,0xba8cbb4e,0x37b23540,0x385a35fd,0xb7b2b8f6,0xb85ab98d,0x39f038f6,0x3a8c398d,
0xb153b540,0xb219b5fd,0x3b5e3abf,0x3bcb3b4e,0xbb6fbbd4,0xbbd4bc00,0x316c0000,0x32320000,0xba04bad3,0xba9ebb5d,0x37d23558,0x386a3614,
0xb7d2b909,0xb86ab99f,0x3a043909,0x3a9e399f,0xb16cb558,0xb232b614,0x3b6f3ad3,0x3bd43b5d,0x0,0x0,0x0,0x0,
0x2e1f0000,0x336431a8,0x33643400,0x2e1f31a8,0x31a80000,0x31a83400,0xb1a80000,0xb1a8b400,0x33640000,0xae1f31a8,0xae1fb400,0x336431a8,
0x34000000,0xb4000000,0x34000000,0xb4000000,0x33640000,0xae1fb1a8,0xae1f3400,0x3364b1a8,0x31a80000,0x31a8b400,0xb1a80000,0xb1a83400,
0x2e1f0000,0x3364b1a8,0x3364b400,0x2e1fb1a8,0x0,0x0,0x0,0x0,0xae1f0000,0xb36431a8,0xb3643400,0xae1f31a8,
0xb1a80000,0xb1a83400,0x31a80000,0x31a8b400,0xb3640000,0x2e1f31a8,0x2e1fb400,0xb36431a8,0xb4000000,0x34000000,0xb4000000,0x34000000,
0xb3640000,0x2e1fb1a8,0x2e1f3400,0xb364b1a8,0xb1a80000,0xb1a8b400,0x31a80000,0x31a83400,0xae1f0000,0xb364b1a8,0xb364b400,0xae1fb1a8,
0x0,0x0,0x0,0x0,0xae1f0000,0xb364b1a8,0xb364b400,0xae1fb1a8,0x31a80000,0x31a83400,0xb1a80000,0xb1a8b400,
0xb3640000,0x2e1fb1a8,0x2e1f3400,0xb364b1a8,0x34000000,0xb4000000,0x34000000,0xb4000000,0xb3640000,0x2e1f31a8,0x2e1fb400,0xb36431a8,
0x31a80000,0x31a8b400,0xb1a80000,0xb1a83400,0xae1f0000,0xb36431a8,0xb3643400,0xae1f31a8,0x0,0x0,0x0,0x0,
0x2e1f0000,0x3364b1a8,0x3364b400,0x2e1fb1a8,0xb1a80000,0xb1a83400,0x31a80000,0x31a8b400,0x33640000,0xae1fb1a8,0xae1f3400,0x3364b1a8,
0xb4000000,0x34000000,0xb4000000,0x34000000,0x33640000,0xae1f31a8,0xae1fb400,0x336431a8,0xb1a80000,0xb1a8b400,0x31a80000,0x31a83400,
0x2e1f0000,0x336431a8,0x33643400,0x2e1f31a8,0x34003400,0x34003400,0x34003400,0x34003400,0x33643400,0x2e1f31a8,0xae1f0000,0xb364b1a8,
0x31a83400,0xb1a80000,0xb1a8b400,0x31a80000,0x2e1f3400,0xb364b1a8,0x33640000,0xae1f31a8,0x3400,0xb400,0x3400,0xb400,
0xae1f3400,0x3364b1a8,0xb3640000,0x2e1f31a8,0xb1a83400,0x31a80000,0x31a8b400,0xb1a80000,0xb3643400,0xae1f31a8,0x2e1f0000,0x3364b1a8,
0xb4003400,0xb4003400,0xb4003400,0xb4003400,0xb3643400,0xae1f31a8,0x2e1f0000,0x3364b1a8,0xb1a83400,0x31a80000,0x31a8b400,0xb1a80000,
0xae1f3400,0x3364b1a8,0xb3640000,0x2e1f31a8,0x3400,0xb400,0x3400,0xb400,0x2e1f3400,0xb364b1a8,0x33640000,0xae1f31a8,
0x31a83400,0xb1a80000,0xb1a8b400,0x31a80000,0x33643400,0x2e1f31a8,0xae1f0000,0xb364b1a8,0x34003400,0x34003400,0x34003400,0x34003400,
0xb364b400,0xae1fb1a8,0x2e1f0000,0x336431a8,0x31a83400,0xb1a80000,0xb1a8b400,0x31a80000,0xae1fb400,0x336431a8,0xb3640000,0x2e1fb1a8,
0x3400,0xb400,0x3400,0xb400,0x2e1fb400,0xb36431a8,0x33640000,0xae1fb1a8,0xb1a83400,0x31a80000,0x31a8b400,0xb1a80000,
0x3364b400,0x2e1fb1a8,0xae1f0000,0xb36431a8,0xb4003400,0xb4003400,0xb4003400,0xb4003400,0x3364b400,0x2e1fb1a8,0xae1f0000,0xb36431a8,
0xb1a83400,0x31a80000,0x31a8b400,0xb1a80000,0x2e1fb400,0xb36431a8,0x33640000,0xae1fb1a8,0x3400,0xb400,0x3400,0xb400,
0xae1fb400,0x336431a8,0xb3640000,0x2e1fb1a8,0x31a83400,0xb1a80000,0xb1a8b400,0x31a80000,0xb364b400,0xae1fb1a8,0x2e1f0000,0x336431a8,
0x0,0x0,0x0,0x0,0xae1f0000,0xb364b1a8,0xb364b400,0xae1fb1a8,0xb1a80000,0xb1a8b400,0x31a80000,0x31a83400,
0xb3640000,0x2e1fb1a8,0x2e1f3400,0xb364b1a8,0xb4000000,0x34000000,0xb4000000,0x34000000,0xb3640000,0x2e1f31a8,0x2e1fb400,0xb36431a8,
0xb1a80000,0xb1a83400,0x31a80000,0x31a8b400,0xae1f0000,0xb36431a8,0xb3643400,0xae1f31a8,0x0,0x0,0x0,0x0,
0x2e1f0000,0x3364b1a8,0x3364b400,0x2e1fb1a8,0x31a80000,0x31a8b400,0xb1a80000,0xb1a83400,0x33640000,0xae1fb1a8,0xae1f3400,0x3364b1a8,
0x34000000,0xb4000000,0x34000000,0xb4000000,0x33640000,0xae1f31a8,0xae1fb400,0x336431a8,0x31a80000,0x31a83400,0xb1a80000,0xb1a8b400,
0x2e1f0000,0x336431a8,0x33643400,0x2e1f31a8,0x0,0x0,0x0,0x0,0x2e1f0000,0x336431a8,0x33643400,0x2e1f31a8,
0xb1a80000,0xb1a8b400,0x31a80000,0x31a83400,0x33640000,0xae1f31a8,0xae1fb400,0x336431a8,0xb4000000,0x34000000,0xb4000000,0x34000000,
0x33640000,0xae1fb1a8,0xae1f3400,0x3364b1a8,0xb1a80000,0xb1a83400,0x31a80000,0x31a8b400,0x2e1f0000,0x3364b1a8,0x3364b400,0x2e1fb1a8,
0x0,0x0,0x0,0x0,0xae1f0000,0xb36431a8,0xb3643400,0xae1f31a8,0x31a80000,0x31a8b400,0xb1a80000,0xb1a83400,
0xb3640000,0x2e1f31a8,0x2e1fb400,0xb36431a8,0x34000000,0xb4000000,0x34000000,0xb4000000,0xb3640000,0x2e1fb1a8,0x2e1f3400,0xb364b1a8,
0x31a80000,0x31a83400,0xb1a80000,0xb1a8b400,0xae1f0000,0xb364b1a8,0xb364b400,0xae1fb1a8,
};

typedef CUresult (*EncodeFn)(CUtensorMap*, CUtensorMapDataType, cuuint32_t, void*, const cuuint64_t*, const cuuint64_t*,
                             const cuuint32_t*, const cuuint32_t*, CUtensorMapInterleave, CUtensorMapSwizzle,
                             CUtensorMapL2promotion, CUtensorMapFloatOOBfill);

}

extern "C" void kernel_launch(void* const* d_in, const int* in_sizes, int n_in, void* d_out, int out_size) {
    Params p;
    p.x = (const __nv_bfloat16*)d_in[0];
    p.lar = (const __nv_bfloat16*)d_in[1];
    p.aim = (const __nv_bfloat16*)d_in[2];
    p.cr = (const __nv_bfloat16*)d_in[3];
    p.ci = (const __nv_bfloat16*)d_in[4];
    p.logdt = (const __nv_bfloat16*)d_in[5];
    p.dskip = (const __nv_bfloat16*)d_in[6];
    p.wr = (const __nv_bfloat16*)d_in[8];
    p.out = (__nv_bfloat16*)d_out;
    cudaGetSymbolAddress((void**)&p.sc, g_scratch);
    cudaGetSymbolAddress((void**)&p.tab, g_tab);

    void* fn = nullptr;
    cudaDriverEntryPointQueryResult qr;
    cudaGetDriverEntryPoint("cuTensorMapEncodeTiled", &fn, cudaEnableDefault, &qr);
    EncodeFn enc = (EncodeFn)fn;
    CUtensorMap tm_x, tm_g, tm_d;
    const cuuint32_t es[5] = {1, 1, 1, 1, 1};
    {
        const cuuint64_t gd[4] = {1024, 128, 8, 2}, gs[3] = {32768, 4096, 2048};
        const cuuint32_t bx[4] = {16, 64, 4, 1};
        enc(&tm_x, CU_TENSOR_MAP_DATA_TYPE_BFLOAT16, 4, d_in[0], gd, gs, bx, es, CU_TENSOR_MAP_INTERLEAVE_NONE,
            CU_TENSOR_MAP_SWIZZLE_NONE, CU_TENSOR_MAP_L2_PROMOTION_NONE, CU_TENSOR_MAP_FLOAT_OOB_FILL_NONE);
    }
    {
        char *wg = (char*)d_in[9], *wu = (char*)d_in[10];
        p.up_first = wu < wg;
        const cuuint64_t gd[3] = {3584, 1024, 2}, gs[2] = {7168, (cuuint64_t)(p.up_first ? wg - wu : wu - wg)};
        const cuuint32_t bx[3] = {64, 64, 2};
        enc(&tm_g, CU_TENSOR_MAP_DATA_TYPE_BFLOAT16, 3, p.up_first ? wu : wg, gd, gs, bx, es, CU_TENSOR_MAP_INTERLEAVE_NONE,
            CU_TENSOR_MAP_SWIZZLE_128B, CU_TENSOR_MAP_L2_PROMOTION_NONE, CU_TENSOR_MAP_FLOAT_OOB_FILL_NONE);
    }
    {
        const cuuint64_t gd[3] = {64, 3584, 16}, gs[2] = {2048, 128};
        const cuuint32_t bx[3] = {64, 64, 2};
        enc(&tm_d, CU_TENSOR_MAP_DATA_TYPE_BFLOAT16, 3, d_in[11], gd, gs, bx, es, CU_TENSOR_MAP_INTERLEAVE_NONE,
            CU_TENSOR_MAP_SWIZZLE_128B, CU_TENSOR_MAP_L2_PROMOTION_NONE, CU_TENSOR_MAP_FLOAT_OOB_FILL_NONE);
    }
    cudaFuncSetAttribute(fused_kernel, cudaFuncAttributeMaxDynamicSharedMemorySize, SM_TOTAL + 256);
    fused_kernel<<<128, NTHREADS, SM_TOTAL + 256>>>(p, tm_x, tm_g, tm_d);
}
```

```cpp
#include <cuda_runtime.h>
#include <cuda.h>
#include <cuda_bf16.h>
#include <cuda_fp16.h>
#include <stdint.h>

#define TG(i)
#define TS(i)
#define TSL(i)

#define TSW 0
#define SDELAY 1500
#define EDELAY 800
#define FILL 0x52110
#define STSLEEP 100
#define NPF 3
#define REFILL 0x55421
#define NREP 4
#define GPROMO 0
#define DPROMO 0
#define WPOL "evict_first"
#define PDELAY 600
#define POLL_LD "ld.relaxed.gpu.global.b128"
#define IDEPTH 2

namespace {

constexpr int NTHREADS = 512;
constexpr int SPIN_LIMIT = 1 << 16;

constexpr int SM_SLAB = 0;
constexpr int SM_RING = 32768;
constexpr int SUB     = 1088;
constexpr int SM_K    = SM_RING + 10 * 8192;
constexpr int SM_S    = SM_K + 32 * SUB;
constexpr int SM_U    = SM_S + 32 * SUB;
constexpr int SM_F2   = SM_U + 32 * SUB;
constexpr int SM_XSEL = SM_F2 + 1536;
constexpr int SM_PAIR = SM_XSEL + 4096;
constexpr int SM_H    = SM_PAIR + 2048;
constexpr int SM_KEYS = SM_H + 1024;
constexpr int SM_TOK  = SM_KEYS + 64;
constexpr int SM_FIX  = SM_TOK + 16;
constexpr int SM_XRAW = SM_FIX + 32;
constexpr int SM_SCL  = SM_XRAW + 64;
constexpr int SM_BAR  = SM_SCL + 16;
constexpr int SM_RED  = SM_XSEL;
constexpr int SM_TAB  = SM_RING + 7 * 8192;
constexpr int B_FULL = 0, B_ROW = 24, B_STG = 32, B_SLAB = 36, B_TOK = 38, B_UFREE = 39, B_FIX = 40, B_PAIR = 41,
              B_TAB = 42, B_TFREE = 43, B_KFREE = 44, B_U = 46, B_PEER = 48, NBAR = 52;
constexpr int SM_TOTAL = SM_BAR + NBAR * 8;
static_assert(SM_TOTAL + 256 <= 232448, "smem");
__device__ __forceinline__ uint32_t chunk_off(int n) { return SM_RING + (n < 7 ? n : n - 7) * 16384; }
constexpr int KP = 272;

struct Scratch {
    uint4 stats[4][1032];
    uint32_t part[128 * 56 * 16];
    uint32_t epoch;
};
__device__ Scratch g_scratch;

struct Params {
    const __nv_bfloat16 *lar, *aim, *cr, *ci, *logdt, *dskip;
    const __nv_bfloat16 *x, *wr;
    __nv_bfloat16* out;
    Scratch* sc;
    const uint4* tab;
    int up_first;
};

__device__ __forceinline__ uint4 ldg128(const void* p) {
    uint4 v; asm volatile("ld.global.nc.v4.u32 {%0,%1,%2,%3}, [%4];" : "=r"(v.x), "=r"(v.y), "=r"(v.z), "=r"(v.w) : "l"(p)); return v;
}
__device__ __forceinline__ uint4 ld_relaxed128(const void* p) {
    uint4 v;
    asm volatile("{ .reg .b128 t; ld.relaxed.gpu.global.b128 t, [%4]; mov.b128 {%0,%1,%2,%3}, t; }"
                 : "=r"(v.x), "=r"(v.y), "=r"(v.z), "=r"(v.w) : "l"(p) : "memory");
    return v;
}
__device__ __forceinline__ void st_relaxed128(void* p, uint4 v) {
    asm volatile("{ .reg .b128 t; mov.b128 t, {%1,%2,%3,%4}; st.relaxed.gpu.global.b128 [%0], t; }"
                 :: "l"(p), "r"(v.x), "r"(v.y), "r"(v.z), "r"(v.w) : "memory");
}
__device__ __forceinline__ void st_relaxed32(void* p, uint32_t v) {
    asm volatile("st.relaxed.gpu.global.u32 [%0], %1;" :: "l"(p), "r"(v) : "memory");
}
__device__ __forceinline__ uint32_t lds32(uint32_t a) { uint32_t v; asm volatile("ld.shared.u32 %0, [%1];" : "=r"(v) : "r"(a)); return v; }
__device__ __forceinline__ uint32_t lds16(uint32_t a) { uint32_t v; asm volatile("ld.shared.u16 %0, [%1];" : "=r"(v) : "r"(a)); return v; }
__device__ __forceinline__ uint2 lds64(uint32_t a) { uint2 v; asm volatile("ld.shared.v2.u32 {%0,%1}, [%2];" : "=r"(v.x), "=r"(v.y) : "r"(a)); return v; }
__device__ __forceinline__ uint4 lds128(uint32_t a) {
    uint4 v; asm volatile("ld.shared.v4.u32 {%0,%1,%2,%3}, [%4];" : "=r"(v.x), "=r"(v.y), "=r"(v.z), "=r"(v.w) : "r"(a)); return v;
}
__device__ __forceinline__ void sts16(uint32_t a, uint32_t v) { asm volatile("st.shared.u16 [%0], %1;" :: "r"(a), "h"((uint16_t)v) : "memory"); }
__device__ __forceinline__ void sts32(uint32_t a, uint32_t v) { asm volatile("st.shared.u32 [%0], %1;" :: "r"(a), "r"(v) : "memory"); }
__device__ __forceinline__ void sts64(uint32_t a, uint32_t x, uint32_t y) { asm volatile("st.shared.v2.u32 [%0], {%1,%2};" :: "r"(a), "r"(x), "r"(y) : "memory"); }
__device__ __forceinline__ void sts128(uint32_t a, uint32_t x, uint32_t y, uint32_t z, uint32_t w) {
    asm volatile("st.shared.v4.u32 [%0], {%1,%2,%3,%4};" :: "r"(a), "r"(x), "r"(y), "r"(z), "r"(w) : "memory");
}
__device__ __forceinline__ void ldsm4(uint32_t a, uint32_t& r0, uint32_t& r1, uint32_t& r2, uint32_t& r3) {
    asm volatile("ldmatrix.sync.aligned.m8n8.x4.shared.b16 {%0,%1,%2,%3}, [%4];" : "=r"(r0), "=r"(r1), "=r"(r2), "=r"(r3) : "r"(a));
}
__device__ __forceinline__ void mma_f16(float (&d)[4], uint32_t a0, uint32_t a1, uint32_t a2, uint32_t a3, uint32_t b0, uint32_t b1) {
    asm("mma.sync.aligned.m16n8k16.row.col.f32.f16.f16.f32 {%0,%1,%2,%3}, {%4,%5,%6,%7}, {%8,%9}, {%0,%1,%2,%3};"
        : "+f"(d[0]), "+f"(d[1]), "+f"(d[2]), "+f"(d[3]) : "r"(a0), "r"(a1), "r"(a2), "r"(a3), "r"(b0), "r"(b1));
}
__device__ __forceinline__ void mma_bf16(float (&d)[4], uint32_t a0, uint32_t a1, uint32_t a2, uint32_t a3, uint32_t b0, uint32_t b1) {
    asm("mma.sync.aligned.m16n8k16.row.col.f32.bf16.bf16.f32 {%0,%1,%2,%3}, {%4,%5,%6,%7}, {%8,%9}, {%0,%1,%2,%3};"
        : "+f"(d[0]), "+f"(d[1]), "+f"(d[2]), "+f"(d[3]) : "r"(a0), "r"(a1), "r"(a2), "r"(a3), "r"(b0), "r"(b1));
}
__device__ __forceinline__ uint32_t prmt(uint32_t a, uint32_t b, uint32_t s) { uint32_t d; asm("prmt.b32 %0, %1, %2, %3;" : "=r"(d) : "r"(a), "r"(b), "r"(s)); return d; }
__device__ __forceinline__ uint32_t pack_h(float lo, float hi) { uint32_t d; asm("cvt.rn.f16x2.f32 %0, %1, %2;" : "=r"(d) : "f"(hi), "f"(lo)); return d; }
__device__ __forceinline__ uint32_t pack_b(float lo, float hi) { uint32_t d; asm("cvt.rn.bf16x2.f32 %0, %1, %2;" : "=r"(d) : "f"(hi), "f"(lo)); return d; }
__device__ __forceinline__ float blo(uint32_t v) { return __uint_as_float(v << 16); }
__device__ __forceinline__ float bhi(uint32_t v) { return __uint_as_float(v & 0xFFFF0000u); }
__device__ __forceinline__ float rb(float v) { return blo(pack_b(v, v)); }
__device__ __forceinline__ uint32_t bsub2(uint32_t a, uint32_t b) { uint32_t d; asm("sub.rn.bf16x2 %0, %1, %2;" : "=r"(d) : "r"(a), "r"(b)); return d; }
__device__ __forceinline__ uint32_t badd2(uint32_t a, uint32_t b) { uint32_t d; asm("add.rn.bf16x2 %0, %1, %2;" : "=r"(d) : "r"(a), "r"(b)); return d; }
__device__ __forceinline__ uint32_t bmul2(uint32_t a, uint32_t b) { uint32_t d; asm("mul.rn.bf16x2 %0, %1, %2;" : "=r"(d) : "r"(a), "r"(b)); return d; }
__device__ __forceinline__ uint32_t bfma2(uint32_t a, uint32_t b, uint32_t c) { uint32_t d; asm("fma.rn.bf16x2 %0, %1, %2, %3;" : "=r"(d) : "r"(a), "r"(b), "r"(c)); return d; }
__device__ __forceinline__ uint32_t dup_lo(uint32_t v) { uint32_t d; asm("{ .reg .b16 l, h; mov.b32 {l, h}, %1; mov.b32 %0, {l, l}; }" : "=r"(d) : "r"(v)); return d; }
__device__ __forceinline__ uint32_t dup_hi(uint32_t v) { uint32_t d; asm("{ .reg .b16 l, h; mov.b32 {l, h}, %1; mov.b32 %0, {h, h}; }" : "=r"(d) : "r"(v)); return d; }
__device__ __forceinline__ uint32_t norm2(uint32_t x, uint32_t m, uint32_t hi, uint32_t lo) {
    uint32_t a = bsub2(x, m);
    return bfma2(a, hi, bmul2(a, lo));
}
__device__ __forceinline__ float ex2(float v) { float d; asm("ex2.approx.ftz.f32 %0, %1;" : "=f"(d) : "f"(v)); return d; }
__device__ __forceinline__ float rcp(float v) { float d; asm("rcp.approx.ftz.f32 %0, %1;" : "=f"(d) : "f"(v)); return d; }
__device__ __forceinline__ float sigmoidf_(float v) { return rcp(1.0f + ex2(-1.4426950408889634f * v)); }
__device__ __forceinline__ float siluf_(float v) { return v * sigmoidf_(v); }

__device__ __forceinline__ void mbar_init(uint32_t a, int n) { asm volatile("mbarrier.init.shared::cta.b64 [%0], %1;" :: "r"(a), "r"(n) : "memory"); }
__device__ __forceinline__ void mbar_expect(uint32_t a, int tx) { asm volatile("mbarrier.arrive.expect_tx.shared::cta.b64 _, [%0], %1;" :: "r"(a), "r"(tx) : "memory"); }
__device__ __forceinline__ void mbar_arrive(uint32_t a) { asm volatile("mbarrier.arrive.shared::cta.b64 _, [%0];" :: "r"(a) : "memory"); }
__device__ __forceinline__ bool mbar_try(uint32_t a) {
    uint32_t d; asm volatile("{ .reg .pred p; mbarrier.try_wait.parity.shared::cta.b64 p, [%1], 0; selp.u32 %0, 1, 0, p; }" : "=r"(d) : "r"(a) : "memory"); return d;
}
__device__ __forceinline__ void mbar_wait(uint32_t a) {
    if (__builtin_expect(!mbar_try(a), 0)) {
        int n = SPIN_LIMIT;
        while (!mbar_try(a) && --n) {}
    }
}
__device__ __forceinline__ void mbar_arrive_peer(uint32_t a) { asm volatile("mbarrier.arrive.relaxed.cluster.shared::cluster.b64 _, [%0];" :: "r"(a) : "memory"); }
__device__ __forceinline__ uint32_t mapa(uint32_t a, uint32_t rank) { uint32_t d; asm("mapa.shared::cluster.u32 %0, %1, %2;" : "=r"(d) : "r"(a), "r"(rank)); return d; }
__device__ __forceinline__ void st_async2(uint32_t a, uint32_t x, uint32_t y, uint32_t bar) {
    asm volatile("st.async.weak.shared::cluster.mbarrier::complete_tx::bytes.v2.b32 [%0], {%1,%2}, [%3];" :: "r"(a), "r"(x), "r"(y), "r"(bar) : "memory");
}
__device__ __forceinline__ void st_async4(uint32_t a, uint32_t x, uint32_t y, uint32_t z, uint32_t w, uint32_t bar) {
    asm volatile("st.async.weak.shared::cluster.mbarrier::complete_tx::bytes.v4.b32 [%0], {%1,%2,%3,%4}, [%5];"
                 :: "r"(a), "r"(x), "r"(y), "r"(z), "r"(w), "r"(bar) : "memory");
}
__device__ __forceinline__ void stsm4(uint32_t a, uint32_t r0, uint32_t r1, uint32_t r2, uint32_t r3) {
    asm volatile("stmatrix.sync.aligned.m8n8.x4.shared.b16 [%0], {%1,%2,%3,%4};" :: "r"(a), "r"(r0), "r"(r1), "r"(r2), "r"(r3) : "memory");
}
__device__ __forceinline__ void proxy_fence() { asm volatile("fence.proxy.async.shared::cta;" ::: "memory"); }
__device__ __forceinline__ void bar_sync(int id, int n) { asm volatile("bar.sync %0, %1;" :: "r"(id), "r"(n) : "memory"); }
__device__ __forceinline__ void bar_arrive(int id, int n) { asm volatile("bar.arrive %0, %1;" :: "r"(id), "r"(n) : "memory"); }
__device__ __forceinline__ void cluster_arrive() { asm volatile("barrier.cluster.arrive.relaxed.aligned;" ::: "memory"); }
__device__ __forceinline__ void cluster_wait() { asm volatile("barrier.cluster.wait.aligned;" ::: "memory"); }
__device__ __forceinline__ void tma3d(uint32_t dst, const CUtensorMap* tm, int c0, int c1, int c2, uint32_t bar, uint64_t pol) {
    asm volatile("cp.async.bulk.tensor.3d.shared::cluster.global.mbarrier::complete_tx::bytes.L2::cache_hint [%0], [%1, {%3, %4, %6}], [%2], %5;"
                 :: "r"(dst), "l"(tm), "r"(bar), "r"(c0), "r"(c1), "l"(pol), "r"(c2) : "memory");
}
__device__ __forceinline__ bool elect() {
    uint32_t p; asm volatile("{ .reg .pred p; elect.sync _|p, 0xFFFFFFFF; selp.u32 %0, 1, 0, p; }" : "=r"(p)); return p;
}

struct cf { float r, i; };
__device__ __forceinline__ cf cmul(cf a, cf b) { return {a.r * b.r - a.i * b.i, a.r * b.i + a.i * b.r}; }
__device__ __forceinline__ cf csq(cf a) { return {a.r * a.r - a.i * a.i, (a.r + a.r) * a.i}; }
__device__ __forceinline__ cf cexp_(float a2, float b) { float m = ex2(a2); return {m * __cosf(b), m * __sinf(b)}; }
struct hc { uint32_t r, i; };
__device__ __forceinline__ hc pk(cf a, cf b) { return {pack_h(a.r, b.r), pack_h(a.i, b.i)}; }
__device__ __forceinline__ hc hmulc(hc a, hc b) {
    const __half2 ar = *reinterpret_cast<__half2*>(&a.r), ai = *reinterpret_cast<__half2*>(&a.i);
    const __half2 br = *reinterpret_cast<__half2*>(&b.r), bi = *reinterpret_cast<__half2*>(&b.i);
    const __half2 r = __hfma2(ar, br, __hneg2(__hmul2_rn(ai, bi))), i = __hfma2(ar, bi, __hmul2_rn(ai, br));
    return {*reinterpret_cast<const uint32_t*>(&r), *reinterpret_cast<const uint32_t*>(&i)};
}
__device__ __forceinline__ void sth(uint32_t a, hc v) { sts32(a, v.r); sts32(a + 128, v.i); }
__device__ __forceinline__ uint32_t cpy(uint32_t v, uint32_t z) { uint32_t d; asm("xor.b32 %0, %1, %2;" : "=r"(d) : "r"(v), "r"(z)); return d; }
__device__ __forceinline__ void sched_fence() { asm volatile("pmevent 0;" ::: "memory"); }
__device__ __forceinline__ float tanh_(float v) { float d; asm("tanh.approx.f32 %0, %1;" : "=f"(d) : "f"(v)); return d; }
__device__ __forceinline__ float silu2(float h) {
    return h * rcp(fmaf(ex2(-2.8853900817779268f * h), 0.5f, 0.5f));
}
__device__ __forceinline__ uint32_t hfma2_(uint32_t a, uint32_t b, uint32_t c) { uint32_t d; asm("fma.rn.f16x2 %0, %1, %2, %3;" : "=r"(d) : "r"(a), "r"(b), "r"(c)); return d; }
__device__ __forceinline__ uint32_t hfms2_(uint32_t a, uint32_t b, uint32_t c) {
    uint32_t d; asm("{ .reg .b32 t; neg.f16x2 t, %1; fma.rn.f16x2 %0, t, %2, %3; }" : "=r"(d) : "r"(a), "r"(b), "r"(c)); return d;
}

__device__ __forceinline__ uint64_t bdesc(uint32_t addr, uint32_t sbo) {
    return (uint64_t)((addr & 0x3FFFFu) >> 4) | ((uint64_t)(128 >> 4) << 16) | ((uint64_t)(sbo >> 4) << 32);
}
__device__ __forceinline__ void wg_h(uint32_t (&d)[16], const uint32_t* a, const uint32_t* b, uint64_t d0, uint64_t d1, uint64_t d2, uint64_t d3) {
    asm volatile(
        "wgmma.mma_async.sync.aligned.m64n64k16.f16.f16.f16 {%0,%1,%2,%3,%4,%5,%6,%7,%8,%9,%10,%11,%12,%13,%14,%15}, {%16,%17,%18,%19}, %32, 0, 1, 1, 1;\n"
        "wgmma.mma_async.sync.aligned.m64n64k16.f16.f16.f16 {%0,%1,%2,%3,%4,%5,%6,%7,%8,%9,%10,%11,%12,%13,%14,%15}, {%20,%21,%22,%23}, %33, 1, 1, 1, 1;\n"
        "wgmma.mma_async.sync.aligned.m64n64k16.f16.f16.f16 {%0,%1,%2,%3,%4,%5,%6,%7,%8,%9,%10,%11,%12,%13,%14,%15}, {%24,%25,%26,%27}, %34, 1, 1, 1, 1;\n"
        "wgmma.mma_async.sync.aligned.m64n64k16.f16.f16.f16 {%0,%1,%2,%3,%4,%5,%6,%7,%8,%9,%10,%11,%12,%13,%14,%15}, {%28,%29,%30,%31}, %35, 1, 1, 1, 1;\n"
        : "=r"(d[0]), "=r"(d[1]), "=r"(d[2]), "=r"(d[3]), "=r"(d[4]), "=r"(d[5]), "=r"(d[6]), "=r"(d[7]), "=r"(d[8]), "=r"(d[9]), "=r"(d[10]), "=r"(d[11]), "=r"(d[12]), "=r"(d[13]), "=r"(d[14]), "=r"(d[15])
        : "r"(a[0]), "r"(a[1]), "r"(a[2]), "r"(a[3]), "r"(a[4]), "r"(a[5]), "r"(a[6]), "r"(a[7]), "r"(b[0]), "r"(b[1]), "r"(b[2]), "r"(b[3]), "r"(b[4]), "r"(b[5]), "r"(b[6]), "r"(b[7]), "l"(d0), "l"(d1), "l"(d2), "l"(d3));
}
__device__ __forceinline__ void wg_f0(float (&d)[32], const uint32_t* a, const uint32_t* b, uint64_t d0, uint64_t d1, uint64_t d2, uint64_t d3) {
    asm volatile(
        "wgmma.mma_async.sync.aligned.m64n64k16.f32.f16.f16 {%0,%1,%2,%3,%4,%5,%6,%7,%8,%9,%10,%11,%12,%13,%14,%15,%16,%17,%18,%19,%20,%21,%22,%23,%24,%25,%26,%27,%28,%29,%30,%31}, {%32,%33,%34,%35}, %48, 0, 1, 1, 1;\n"
        "wgmma.mma_async.sync.aligned.m64n64k16.f32.f16.f16 {%0,%1,%2,%3,%4,%5,%6,%7,%8,%9,%10,%11,%12,%13,%14,%15,%16,%17,%18,%19,%20,%21,%22,%23,%24,%25,%26,%27,%28,%29,%30,%31}, {%36,%37,%38,%39}, %49, 1, 1, 1, 1;\n"
        "wgmma.mma_async.sync.aligned.m64n64k16.f32.f16.f16 {%0,%1,%2,%3,%4,%5,%6,%7,%8,%9,%10,%11,%12,%13,%14,%15,%16,%17,%18,%19,%20,%21,%22,%23,%24,%25,%26,%27,%28,%29,%30,%31}, {%40,%41,%42,%43}, %50, 1, 1, 1, 1;\n"
        "wgmma.mma_async.sync.aligned.m64n64k16.f32.f16.f16 {%0,%1,%2,%3,%4,%5,%6,%7,%8,%9,%10,%11,%12,%13,%14,%15,%16,%17,%18,%19,%20,%21,%22,%23,%24,%25,%26,%27,%28,%29,%30,%31}, {%44,%45,%46,%47}, %51, 1, 1, 1, 1;\n"
        : "=f"(d[0]), "=f"(d[1]), "=f"(d[2]), "=f"(d[3]), "=f"(d[4]), "=f"(d[5]), "=f"(d[6]), "=f"(d[7]), "=f"(d[8]), "=f"(d[9]), "=f"(d[10]), "=f"(d[11]), "=f"(d[12]), "=f"(d[13]), "=f"(d[14]), "=f"(d[15]), "=f"(d[16]), "=f"(d[17]), "=f"(d[18]), "=f"(d[19]), "=f"(d[20]), "=f"(d[21]), "=f"(d[22]), "=f"(d[23]), "=f"(d[24]), "=f"(d[25]), "=f"(d[26]), "=f"(d[27]), "=f"(d[28]), "=f"(d[29]), "=f"(d[30]), "=f"(d[31])
        : "r"(a[0]), "r"(a[1]), "r"(a[2]), "r"(a[3]), "r"(a[4]), "r"(a[5]), "r"(a[6]), "r"(a[7]), "r"(b[0]), "r"(b[1]), "r"(b[2]), "r"(b[3]), "r"(b[4]), "r"(b[5]), "r"(b[6]), "r"(b[7]), "l"(d0), "l"(d1), "l"(d2), "l"(d3));
}
__device__ __forceinline__ void wg_f1(float (&d)[32], const uint32_t* a, const uint32_t* b, uint64_t d0, uint64_t d1, uint64_t d2, uint64_t d3) {
    asm volatile(
        "wgmma.mma_async.sync.aligned.m64n64k16.f32.f16.f16 {%0,%1,%2,%3,%4,%5,%6,%7,%8,%9,%10,%11,%12,%13,%14,%15,%16,%17,%18,%19,%20,%21,%22,%23,%24,%25,%26,%27,%28,%29,%30,%31}, {%32,%33,%34,%35}, %48, 1, 1, 1, 1;\n"
        "wgmma.mma_async.sync.aligned.m64n64k16.f32.f16.f16 {%0,%1,%2,%3,%4,%5,%6,%7,%8,%9,%10,%11,%12,%13,%14,%15,%16,%17,%18,%19,%20,%21,%22,%23,%24,%25,%26,%27,%28,%29,%30,%31}, {%36,%37,%38,%39}, %49, 1, 1, 1, 1;\n"
        "wgmma.mma_async.sync.aligned.m64n64k16.f32.f16.f16 {%0,%1,%2,%3,%4,%5,%6,%7,%8,%9,%10,%11,%12,%13,%14,%15,%16,%17,%18,%19,%20,%21,%22,%23,%24,%25,%26,%27,%28,%29,%30,%31}, {%40,%41,%42,%43}, %50, 1, 1, 1, 1;\n"
        "wgmma.mma_async.sync.aligned.m64n64k16.f32.f16.f16 {%0,%1,%2,%3,%4,%5,%6,%7,%8,%9,%10,%11,%12,%13,%14,%15,%16,%17,%18,%19,%20,%21,%22,%23,%24,%25,%26,%27,%28,%29,%30,%31}, {%44,%45,%46,%47}, %51, 1, 1, 1, 1;\n"
        : "+f"(d[0]), "+f"(d[1]), "+f"(d[2]), "+f"(d[3]), "+f"(d[4]), "+f"(d[5]), "+f"(d[6]), "+f"(d[7]), "+f"(d[8]), "+f"(d[9]), "+f"(d[10]), "+f"(d[11]), "+f"(d[12]), "+f"(d[13]), "+f"(d[14]), "+f"(d[15]), "+f"(d[16]), "+f"(d[17]), "+f"(d[18]), "+f"(d[19]), "+f"(d[20]), "+f"(d[21]), "+f"(d[22]), "+f"(d[23]), "+f"(d[24]), "+f"(d[25]), "+f"(d[26]), "+f"(d[27]), "+f"(d[28]), "+f"(d[29]), "+f"(d[30]), "+f"(d[31])
        : "r"(a[0]), "r"(a[1]), "r"(a[2]), "r"(a[3]), "r"(a[4]), "r"(a[5]), "r"(a[6]), "r"(a[7]), "r"(b[0]), "r"(b[1]), "r"(b[2]), "r"(b[3]), "r"(b[4]), "r"(b[5]), "r"(b[6]), "r"(b[7]), "l"(d0), "l"(d1), "l"(d2), "l"(d3));
}
__device__ __forceinline__ void wg_s(uint32_t* d, const uint32_t* a, const uint32_t* b, uint64_t d0, uint64_t d1) {
    asm volatile(
        "wgmma.mma_async.sync.aligned.m64n32k16.f16.f16.f16 {%0,%1,%2,%3,%4,%5,%6,%7}, {%8,%9,%10,%11}, %16, 0, 1, 1, 1;\n"
        "wgmma.mma_async.sync.aligned.m64n32k16.f16.f16.f16 {%0,%1,%2,%3,%4,%5,%6,%7}, {%12,%13,%14,%15}, %17, 1, 1, 1, 1;\n"
        : "=r"(d[0]), "=r"(d[1]), "=r"(d[2]), "=r"(d[3]), "=r"(d[4]), "=r"(d[5]), "=r"(d[6]), "=r"(d[7])
        : "r"(a[0]), "r"(a[1]), "r"(a[2]), "r"(a[3]), "r"(b[0]), "r"(b[1]), "r"(b[2]), "r"(b[3]), "l"(d0), "l"(d1));
}
template <int ACC> __device__ __forceinline__ void wg_w(float (&d)[4], uint64_t da, uint64_t db) {
    asm volatile("wgmma.mma_async.sync.aligned.m64n8k16.f32.bf16.bf16 {%0,%1,%2,%3}, %4, %5, %6, 1, 1, 1, 0;"
                 : "+f"(d[0]), "+f"(d[1]), "+f"(d[2]), "+f"(d[3]) : "l"(da), "l"(db), "n"(ACC));
}
__device__ __forceinline__ void wg_w0(float (&d)[4], uint64_t da, uint64_t db) {
    asm volatile("wgmma.mma_async.sync.aligned.m64n8k16.f32.bf16.bf16 {%0,%1,%2,%3}, %4, %5, 0, 1, 1, 1, 0;"
                 : "=f"(d[0]), "=f"(d[1]), "=f"(d[2]), "=f"(d[3]) : "l"(da), "l"(db));
}
__device__ __forceinline__ void wg_fence() { asm volatile("wgmma.fence.sync.aligned;" ::: "memory"); }
__device__ __forceinline__ void wg_commit() { asm volatile("wgmma.commit_group.sync.aligned;" ::: "memory"); }
template <int N> __device__ __forceinline__ void wg_wait() { asm volatile("wgmma.wait_group.sync.aligned %0;" :: "n"(N) : "memory"); }
__device__ __forceinline__ void touch(uint32_t& r) { asm volatile("" : "+r"(r) :: "memory"); }
__device__ __forceinline__ void touch(float& r) { asm volatile("" : "+f"(r) :: "memory"); }
template <class T, int N> __device__ __forceinline__ void touch(T (&r)[N]) {
#pragma unroll
    for (int i = 0; i < N; i++) touch(r[i]);
}

__global__ void __cluster_dims__(2, 1, 1) __launch_bounds__(NTHREADS, 1)
fused_kernel(const Params p, const __grid_constant__ CUtensorMap tm_x, const __grid_constant__ CUtensorMap tm_g,
             const __grid_constant__ CUtensorMap tm_d)
{
    extern __shared__ __align__(1024) uint8_t smem_raw[];
    const uint32_t sm = (uint32_t)__cvta_generic_to_shared(smem_raw);
    const uint32_t bars = sm + SM_BAR;
    const int tid = threadIdx.x, lane = tid & 31;
    const int g = lane >> 2, q = lane & 3;
    const int c = blockIdx.x, rank = c & 1, G = c >> 1;

    if (tid < 256) {
        uint2 lar4, aim4, cr4, ci4;
        uint32_t ldt_raw, dsk_raw;
        {
            const uint32_t i = c * 256 + tid;
            asm volatile("ld.global.nc.v2.u32 {%0,%1}, [%10]; ld.global.nc.v2.u32 {%2,%3}, [%11]; ld.global.nc.u16 %8, [%14];\n"
                         "ld.global.nc.v2.u32 {%4,%5}, [%12]; ld.global.nc.v2.u32 {%6,%7}, [%13]; ld.global.nc.u16 %9, [%15];"
                         : "=r"(lar4.x), "=r"(lar4.y), "=r"(aim4.x), "=r"(aim4.y), "=r"(cr4.x), "=r"(cr4.y), "=r"(ci4.x), "=r"(ci4.y), "=r"(ldt_raw), "=r"(dsk_raw)
                         : "l"(p.lar + i * 4), "l"(p.aim + i * 4), "l"(p.cr + i * 4), "l"(p.ci + i * 4), "l"(p.logdt + (i >> 5)), "l"(p.dskip + (i >> 5)));
        }
        cluster_arrive();
        sched_fence();
        const int warp = __shfl_sync(0xFFFFFFFFu, tid >> 5, 0);
        const float logdt = blo(ldt_raw), dsk = blo(dsk_raw);
        asm volatile("setmaxnreg.inc.sync.aligned.u32 168;");
        {
            const uint32_t z = (uint32_t)(uintptr_t)p.lar & 1;
            lar4.x = cpy(lar4.x, z); lar4.y = cpy(lar4.y, z); aim4.x = cpy(aim4.x, z); aim4.y = cpy(aim4.y, z);
            cr4.x = cpy(cr4.x, z); cr4.y = cpy(cr4.y, z); ci4.x = cpy(ci4.x, z); ci4.y = cpy(ci4.y, z);
        }
        const int wgi = warp >> 2, w = warp & 3;
        const uint32_t wb = sm + SM_K + (w < 2 ? 16 * w + 8 * wgi : 16 + 16 * wgi + 8 * w) * SUB;
        sth(wb + lane * 4, hc{0x3C003C00u, 0u});

        const float dt = rb(expf(logdt));
        float outscale, cs, dn;
        {
            uint32_t m0 = __vmaxu2(__vmaxu2(cr4.x & 0x7FFF7FFFu, cr4.y & 0x7FFF7FFFu), __vmaxu2(ci4.x & 0x7FFF7FFFu, ci4.y & 0x7FFF7FFFu));
            uint32_t m1 = max(m0 & 0xFFFFu, m0 >> 16);
            float cmax = blo(__reduce_max_sync(0xFFFFFFFFu, m1));
            const float sc = fminf(fmaxf(fmaxf(2.0f * dt * cmax, fabsf(dsk) * (1.0f / 1024.0f)), 1e-30f), 1e30f);
            outscale = __uint_as_float(__float_as_uint(sc) & 0x7F800000u);
            const float inv = __uint_as_float(0x7F000000u - __float_as_uint(outscale));
            cs = 2.0f * dt * inv;
            dn = dsk * inv;
        }
        if (warp == TSW) TSL(39);
        uint32_t fc[16], fs[16], ta[4], tb[4];
        float kacc[2][3][4];
#pragma unroll
        for (int i = 0; i < 2; i++)
#pragma unroll
            for (int j = 0; j < 3; j++) kacc[i][j][0] = kacc[i][j][1] = kacc[i][j][2] = kacc[i][j][3] = 0.f;
        if (lane == 0) kacc[0][0][0] = dn;
        {
            const uint32_t st = wb + lane * 4;
            const uint32_t zk = lds32(wb + 128);
            const uint32_t la = wb + ((lane & 8) ? 29 : (lane & 7)) * KP + (lane >> 4) * 128;
            const uint32_t lo = wb + ((lane >> 3) & 1) * 128 + (lane >> 4) * 16;
            const uint32_t lb = lo + (8 + (lane & 7)) * KP, lb2 = lo + (24 + min(lane & 7, 4)) * KP, lm = lo + 30 * KP;
#pragma unroll 1
            for (int s = 0; s < 2; s++) {
                const uint32_t wl = s ? lar4.y : lar4.x, wa = s ? aim4.y : aim4.x, wr_ = s ? cr4.y : cr4.x, wi = s ? ci4.y : ci4.x;
                const uint32_t ea = pack_b(ex2(blo(wl) * 1.4426950408889634f), ex2(bhi(wl) * 1.4426950408889634f));
                const float a2[2] = {-(blo(ea) * dt) * 1.4426950408889634f, -(bhi(ea) * dt) * 1.4426950408889634f};
                const float b[2] = {blo(wa) * dt, bhi(wa) * dt};
                {
                    cf z8[2], z16[2], z32[2], z64[2], z128[2];
#pragma unroll
                    for (int e = 0; e < 2; e++) {
                        z8[e] = cexp_(a2[e] * 8.f, b[e] * 8.f);
                        z16[e] = csq(z8[e]); z32[e] = csq(z16[e]); z64[e] = csq(z32[e]); z128[e] = csq(z64[e]);
                    }
                    const hc r1 = pk(z8[0], z8[1]), r2 = pk(z16[0], z16[1]), r3 = hmulc(r1, r2), r4 = pk(z32[0], z32[1]);
                    sth(st + 1 * KP, r1); sth(st + 2 * KP, r2); sth(st + 3 * KP, r3); sth(st + 4 * KP, r4);
                    sth(st + 5 * KP, hmulc(r1, r4)); sth(st + 6 * KP, hmulc(r2, r4)); sth(st + 7 * KP, hmulc(r3, r4));
                    sth(st + 29 * KP, pk(z64[0], z64[1])); sth(st + 30 * KP, pk(z128[0], z128[1]));
                }
                {
                    cf C[2], z2[2], z4[2], v2[2], v4[2], c1[2], d1[2];
#pragma unroll
                    for (int e = 0; e < 2; e++) {
                        C[e] = {(e ? bhi(wr_) : blo(wr_)) * cs, (e ? bhi(wi) : blo(wi)) * -cs};
                        const cf z = cexp_(a2[e], -b[e]);
                        const cf v = cexp_(a2[e] * 256.f, b[e] * -256.f);
                        z2[e] = csq(z); z4[e] = csq(z2[e]); v2[e] = csq(v); v4[e] = csq(v2[e]);
                        c1[e] = cmul(C[e], z); d1[e] = cmul(C[e], v);
                    }
                    const hc l0 = pk(C[0], C[1]), l1 = pk(c1[0], c1[1]), e1 = pk(d1[0], d1[1]);
                    const hc h = pk(z2[0], z2[1]), f = pk(z4[0], z4[1]), w = pk(v2[0], v2[1]), y = pk(v4[0], v4[1]);
                    const hc l2 = hmulc(l0, h), l3 = hmulc(l1, h), e2 = hmulc(l0, w), e3 = hmulc(e1, w), e4 = hmulc(l0, y), g2 = hmulc(e1, h);
                    sth(st + 8 * KP, l0); sth(st + 9 * KP, l1); sth(st + 10 * KP, l2); sth(st + 11 * KP, l3);
                    sth(st + 12 * KP, hmulc(l0, f)); sth(st + 13 * KP, hmulc(l1, f)); sth(st + 14 * KP, hmulc(l2, f)); sth(st + 15 * KP, hmulc(l3, f));
                    sth(st + 16 * KP, e1);
                    sth(st + 17 * KP, g2);
                    sth(st + 18 * KP, hmulc(e1, f));
                    sth(st + 19 * KP, hmulc(g2, f));
                    sth(st + 20 * KP, e2);
                    sth(st + 21 * KP, hmulc(e2, f));
                    sth(st + 22 * KP, e3);
                    sth(st + 23 * KP, hmulc(e3, f));
                    sth(st + 24 * KP, e4);
                    sth(st + 25 * KP, hmulc(e1, y));
                    sth(st + 26 * KP, hmulc(e2, y));
                    sth(st + 27 * KP, hmulc(e3, y));
                    sth(st + 28 * KP, hmulc(e4, y));
                }
                __syncwarp();
                if (warp == TSW && s == 0) TSL(27);
                if (s == 1 && lane == 0) mbar_arrive(bars + B_TFREE * 8 + (tb[3] & zk));
#pragma unroll
                for (int kp = 0; kp < 4; kp++) {
                    uint32_t bb[3][4], m2[4];
                    ldsm4(lm + kp * 32, m2[0], m2[1], m2[2], m2[3]);
                    ldsm4(lb + kp * 32, bb[0][0], bb[0][1], bb[0][2], bb[0][3]);
                    ldsm4(lb + 8 * KP + kp * 32, bb[1][0], bb[1][1], bb[1][2], bb[1][3]);
                    ldsm4(lb2 + kp * 32, bb[2][0], bb[2][1], bb[2][2], bb[2][3]);
#pragma unroll
                    for (int k2 = 0; k2 < 2; k2++) {
                        hc v0, m1;
                        ldsm4(la + kp * 32 + k2 * 16, v0.r, m1.r, v0.i, m1.i);
                        const hc mm = {m2[2 * k2], m2[2 * k2 + 1]};
                        const hc v1 = hmulc(v0, m1), v2 = hmulc(v0, mm), v3 = hmulc(v1, mm);
                        v0.r = cpy(v0.r, zk); v0.i = cpy(v0.i, zk);
#pragma unroll
                        for (int nt = 0; nt < 3; nt++) {
                            mma_f16(kacc[0][nt], v0.r, v1.r, v0.i, v1.i, bb[nt][2 * k2], bb[nt][2 * k2 + 1]);
                            mma_f16(kacc[1][nt], v2.r, v3.r, v2.i, v3.i, bb[nt][2 * k2], bb[nt][2 * k2 + 1]);
                        }
                    }
                }
                __syncwarp();
                if (warp == TSW) TSL(s ? 40 : 33);
                if (s == 0) {
                    cluster_wait();
                    mbar_wait(bars + B_TAB * 8);
#pragma unroll
                    for (int i = 0; i < 10; i++) {
                        const uint4 u = lds128(sm + SM_TAB + i * 2048 + (tid & 127) * 16);
                        uint32_t* t = i < 4 ? fc + 4 * i : i < 8 ? fs + 4 * (i - 4) : i == 8 ? ta : tb;
                        t[0] = u.x; t[1] = u.y; t[2] = u.z; t[3] = u.w;
                    }
                }
            }
        }
        TSL(1);
        bar_sync(10 + wgi, 128);
        {
            const uint32_t tb_ = sm + SM_S + (16 * wgi + w) * SUB;
            const uint32_t seg = sm + SM_K + (2 * warp + (lane & 1)) * SUB + (lane >> 1) * 16;
            uint32_t v0[4];
#pragma unroll
            for (int m = 0; m < 4; m++) {
                constexpr float S = 1.0f / 512.0f;
                const float (&k0)[4] = kacc[m >> 1][0], (&k1)[4] = kacc[m >> 1][1], (&k2)[4] = kacc[m >> 1][2];
                const int R = 8 * m + g, o = 2 * (m & 1);
                v0[m] = pack_h(k0[o] * S, k0[o + 1] * S);
                sts32(tb_ + (q < 2 ? 4 * R + 2 * q : 64 * q + 2 * R) * 2, pack_h(k1[o] * S, k1[o + 1] * S));
                const uint32_t v2 = pack_h(k2[o] * S, k2[o + 1] * S);
                if (q < 2 || (m == 0 && lane == 2)) sts16(tb_ + (256 + 64 * q + R) * 2, v2);
                if (q < 2) sts16(tb_ + (288 + 64 * q + R) * 2, v2 >> 16);
            }
            stsm4(seg, v0[0], v0[1], v0[2], v0[3]);
            if (lane == 0) sts16(sm + SM_SCL + warp * 2, __float_as_uint(32768.0f * outscale) >> 16);
            __syncwarp();
            const uint2 l1 = lds64(tb_ + lane * 8);
            const uint32_t l1n = lds16(tb_ + lane * 8 + 8);
            uint32_t l2[2], l2n[2], l3[4], l3n[4];
#pragma unroll
            for (int i = 0; i < 2; i++) { l2[i] = lds32(tb_ + 256 + i * 128 + lane * 4); l2n[i] = lds16(tb_ + 260 + i * 128 + lane * 4); }
#pragma unroll
            for (int i = 0; i < 4; i++) { l3[i] = lds16(tb_ + 512 + i * 64 + lane * 2); l3n[i] = lds16(tb_ + 514 + i * 64 + lane * 2); }
            sts128(seg + 256, prmt(l1.x, 0, 0x1010), prmt(l1.x, l1.y, 0x5432), prmt(l1.y, 0, 0x1010), prmt(l1.y, l1n, 0x5432));
#pragma unroll
            for (int i = 0; i < 2; i++) sts128(seg + 512 + i * 256, prmt(l2[i], 0, 0x1010), l2[i], prmt(l2[i], 0, 0x3232), prmt(l2n[i], 0, 0x1010));
            const uint32_t s3 = (lane & 1) ? 0x5454 : 0x5410;
#pragma unroll
            for (int i = 0; i < 4; i++) {
                const uint32_t vv = prmt(l3[i], 0, 0x1010);
                sts128(seg + 16 * SUB + i * 256, vv, vv, prmt(l3[i], l3n[i], s3), prmt(l3n[i], 0, 0x1010));
            }
        }
        proxy_fence();
        TSL(2);
        bar_sync(10 + wgi, 128);
        const uint64_t dre = bdesc(sm + SM_F2 + 512, 256), dim = bdesc(sm + SM_F2, 256);
        uint32_t k0[32], k1[32];
#pragma unroll
        for (int b = 0; b < 2; b++) {
            const uint64_t d1 = bdesc(sm + SM_K + (16 * b + 8 * wgi) * SUB, SUB);
            uint32_t re[16], im[16];
            if (b == 0 && wgi == 1) bar_sync(5, 256);
            wg_fence();
            wg_h(re, fc, fc + 8, d1, d1 + 16, d1 + 32, d1 + 48);
            wg_h(im, fs, fs + 8, d1, d1 + 16, d1 + 32, d1 + 48);
            wg_commit();
            if (b == 0 && wgi == 0) bar_arrive(5, 256);
            wg_wait<0>();
            touch(re); touch(im);
            if (lane == 0) mbar_arrive(bars + (B_KFREE + b) * 8);
            uint32_t (&kk)[32] = b ? k1 : k0;
#pragma unroll
            for (int hh = 0; hh < 2; hh++) {
#pragma unroll
                for (int i = 8 * hh; i < 8 * hh + 8; i++) {
                    re[i] = hfma2_(ta[i & 3], im[i], re[i]); im[i] = hfms2_(tb[i & 3], re[i], im[i]); re[i] = hfma2_(ta[i & 3], im[i], re[i]);
                }
                wg_fence();
                wg_s(kk + 16 * hh, re + 8 * hh, im + 8 * hh, dre, dim);
                wg_s(kk + 16 * hh + 8, re + 8 * hh + 4, im + 8 * hh + 4, dre, dim);
                wg_commit();
            }
            wg_wait<0>();
            touch(kk);
        }
        if (warp == TSW) TSL(35);
        asm volatile("setmaxnreg.inc.sync.aligned.u32 184;");
        touch(k1);
        {
            const uint32_t sg = (g & 1) ? 0xBC00BC00u : 0x3C003C00u;
#pragma unroll
            for (int i = 0; i < 16; i++) {
                const int r = 8 * (i >> 2) + (i & 3);
                k1[r] = hfms2_(sg, k0[r + 4], k1[r]); k1[r + 4] = hfma2_(sg, k0[r], k1[r + 4]);
            }
            touch(k1);
        }
        const uint32_t rowo = (16 * w + (lane & 15)) * 16;
        const uint32_t peer = mapa(sm, rank ^ 1), so = SM_U + 8 * wgi * SUB + w * 1024 + (8 * q + (g ^ (2 * q))) * 16;
        const uint2 sc = lds64(sm + SM_SCL + wgi * 8);
#pragma unroll 1
        for (int b = 0; b < 2; b++) {
            const uint32_t zb = sm + SM_S + 16 * wgi * SUB;
            constexpr int zi = 8 * SUB;
            uint32_t re[16], im[16], su[2][16], z[2][16], y[2][16];
            auto twiddle = [&](int hh) {
#pragma unroll
                for (int i = 8 * hh; i < 8 * hh + 8; i++) {
                    re[i] = hfma2_(ta[i & 3], im[i], re[i]); im[i] = hfms2_(tb[i & 3], re[i], im[i]); re[i] = hfma2_(ta[i & 3], im[i], re[i]);
                    touch(re[i]); touch(im[i]);
                }
            };
            auto dft16 = [&](int hh) {
                wg_fence();
                wg_s(su[hh], re + 8 * hh, im + 8 * hh, dre, dim); wg_s(su[hh] + 8, re + 8 * hh + 4, im + 8 * hh + 4, dre, dim);
                wg_commit();
                sched_fence();
            };
            auto product = [&](int hh) {
                if (b == 0) {
#pragma unroll
                    for (int i = 0; i < 8; i++) {
                        const int r = 8 * (i >> 2) + (i & 3), kr = 16 * hh + r;
                        const hc u = {su[hh][r], su[hh][r + 4]};
                        const hc t = hmulc(u, hc{k0[kr], k0[kr + 4]}), pp = hmulc(u, hc{k1[kr], k1[kr + 4]});
                        z[hh][r] = t.r; z[hh][r + 4] = t.i; k1[kr] = pp.r; k1[kr + 4] = pp.i;
                        touch(k1[kr]); touch(k1[kr + 4]);
                    }
                } else {
#pragma unroll
                    for (int i = 0; i < 8; i++) {
                        const int r = 8 * (i >> 2) + (i & 3), kr = 16 * hh + r;
                        const hc u = {su[hh][r], su[hh][r + 4]};
                        z[hh][r] = hfms2_(u.i, k0[kr + 4], hfma2_(u.r, k0[kr], k1[kr]));
                        z[hh][r + 4] = hfma2_(u.i, k0[kr], hfma2_(u.r, k0[kr + 4], k1[kr + 4]));
                    }
                }
                touch(z[hh]);
            };
            auto idft16 = [&](int hh) {
                wg_fence();
                wg_s(y[hh], z[hh] + 4, z[hh], dre, dim); wg_s(y[hh] + 8, z[hh] + 12, z[hh] + 8, dre, dim);
                wg_commit();
                sched_fence();
            };
            auto untwiddle = [&](int hh) {
#pragma unroll
                for (int i = 0; i < 2; i++) {
                    uint32_t* const yi = y[hh] + 8 * i, * const yr = yi + 4;
#pragma unroll
                    for (int n = 0; n < 4; n++) {
                        yr[n] = hfms2_(ta[n], yi[n], yr[n]); yi[n] = hfma2_(tb[n], yr[n], yi[n]); yr[n] = hfms2_(ta[n], yi[n], yr[n]);
                    }
                    const uint32_t a = zb + (4 * hh + 2 * i + (lane >> 4)) * SUB + rowo;
                    stsm4(a, yr[0], yr[1], yr[2], yr[3]);
                    stsm4(a + zi, yi[0], yi[1], yi[2], yi[3]);
                }
            };
            auto done = [&]() { sched_fence(); wg_wait<0>(); };
            {
                const uint64_t d1 = bdesc(sm + SM_U + (16 * b + 8 * wgi) * SUB, SUB);
                mbar_wait(bars + (B_U + b) * 8);
                proxy_fence();
                if (b == 0) { TSL(3); if (wgi == 1) bar_sync(9, 256); }
                wg_fence();
                wg_h(re, fc, fc + 8, d1, d1 + 16, d1 + 32, d1 + 48);
                wg_h(im, fs, fs + 8, d1, d1 + 16, d1 + 32, d1 + 48);
                wg_commit();
                if (b == 0 && wgi == 0) bar_arrive(9, 256);
                wg_wait<0>();
                touch(re); touch(im);
            }
            if (lane == 0) mbar_arrive_peer(peer + SM_BAR + (B_PEER + 2 * wgi + b) * 8);
            twiddle(0); twiddle(1); dft16(0); dft16(1);
            wg_wait<1>(); touch(su[0]);
            product(0); done(); touch(su[1]); idft16(0);
            product(1); done(); touch(y[0]); idft16(1);
            bar_sync(10 + wgi, 128);
            untwiddle(0); done(); touch(y[1]);
            untwiddle(1);
            proxy_fence();
            if (warp == TSW) TSL(36 + b);
            bar_sync(10 + wgi, 128);
            float acc[32];
            const uint64_t d4 = bdesc(zb, SUB);
            wg_fence();
            wg_f0(acc, fc, fc + 8, d4, d4 + 16, d4 + 32, d4 + 48);
            wg_f1(acc, fs, fs + 8, d4 + zi / 16, d4 + zi / 16 + 16, d4 + zi / 16 + 32, d4 + zi / 16 + 48);
            wg_commit();
            mbar_wait(bars + (B_PEER + 2 * wgi + b) * 8);
            wg_wait<0>();
            touch(acc);
            uint32_t s[2][2][4];
#pragma unroll
            for (int i = 0; i < 8; i++) {
                s[i >> 2][(i >> 1) & 1][2 * (i & 1)] = bmul2(pack_b(acc[i], acc[8 + i]), sc.x);
                s[i >> 2][(i >> 1) & 1][2 * (i & 1) + 1] = bmul2(pack_b(acc[16 + i], acc[24 + i]), sc.y);
            }
            const uint32_t sb = SM_BAR + (B_STG + b) * 8;
#pragma unroll
            for (int j = 0; j < 2; j++)
                if (j == rank) {
#pragma unroll
                    for (int hi = 0; hi < 2; hi++) {
                        const uint32_t (&r)[4] = s[1 - j][hi], (&l)[4] = s[j][hi];
                        st_async4(peer + so + 16 * b * SUB + hi * 512, r[0], r[1], r[2], r[3], peer + sb);
                        sts128(sm + (so ^ 64) + (16 * b + 4) * SUB + hi * 512, l[0], l[1], l[2], l[3]);
                    }
                }
            __syncwarp();
            if (lane == 0) mbar_arrive(sm + sb);
            if (warp == TSW) TSL(5 + b);
        }
        TSL(7);
    } else {
    const int warp = __shfl_sync(0xFFFFFFFFu, tid >> 5, 0);
    if (warp < 12) {
        const int v = warp - 8;
        cluster_arrive();
        const uint32_t xs = sm + SM_U + v * 8192;
        if (elect()) {
#pragma unroll
            for (int r = 0; r < 2; r++) mbar_init(bars + (B_ROW + 2 * v + r) * 8, 1);
            asm volatile("fence.mbarrier_init.release.cluster;" ::: "memory");
#pragma unroll
            for (int e = 0; e < 2; e++) {
                if (e) { const int t0_ = clock(); while ((int)clock() - t0_ < EDELAY) __nanosleep(40); }
                mbar_expect(bars + (B_ROW + 2 * v + e) * 8, 4096);
#pragma unroll
                for (int r = 0; r < 2; r++)
                    asm volatile("cp.async.bulk.shared::cluster.global.mbarrier::complete_tx::bytes [%0], [%1], 2048, [%2];"
                                 :: "r"(xs + e * 4096 + r * 2048), "l"(p.x + (size_t)(128 * (c & 15) + 32 * v + 16 * r + 2 * (c >> 4) + e) * 1024),
                                    "r"(bars + (B_ROW + 2 * v + e) * 8) : "memory");
            }
        }
        __syncwarp();
        uint4 w4[4];
#pragma unroll
        for (int k = 0; k < 4; k++) w4[k] = ldg128(reinterpret_cast<const uint4*>(p.wr) + 32 * k + lane);
        {
            constexpr uint32_t ONE = 0x3F803F80u;
            const uint32_t zr = p.up_first >> 1;
            uint4 w5[4];
#pragma unroll
            for (int k = 0; k < 4; k++) {
                w5[k].x = w4[k].x + zr; w5[k].y = w4[k].y + zr; w5[k].z = w4[k].z + zr; w5[k].w = w4[k].w + zr;
                w4[k].x = cpy(w4[k].x, zr); w4[k].y = cpy(w4[k].y, zr); w4[k].z = cpy(w4[k].z, zr); w4[k].w = cpy(w4[k].w, zr);
            }
            const bool od = g & 1;
#pragma unroll 1
            for (int r2 = 0; r2 < 2; r2++) {
                mbar_wait(bars + (B_ROW + 2 * v + r2) * 8);
                TSL(43);
                float s1[2][4] = {}, q0[2][4] = {};
#pragma unroll
                for (int k = 0; k < 4; k++)
#pragma unroll
                    for (int r = 0; r < 2; r++) {
                        const uint4 x = lds128(xs + r2 * 4096 + r * 2048 + k * 512 + lane * 16);
                        const uint4& ww = r ? w5[k] : w4[k];
                        mma_bf16(q0[r], cpy(x.x, zr), ww.x, cpy(x.y, zr), ww.y, x.x, x.y);
                        mma_bf16(s1[r], x.x, x.y, x.z, x.w, ONE, ONE);
                        mma_bf16(q0[r], cpy(x.z, zr), ww.z, cpy(x.w, zr), ww.w, x.z, x.w);
                    }
#pragma unroll
                for (int r = 0; r < 2; r++)
                    if (q == (g >> 1))
                        sts128(sm + SM_RED + (4 * v + r2 + 2 * r) * 144 + g * 16, __float_as_uint(od ? q0[r][1] : q0[r][0]),
                               __float_as_uint(od ? q0[r][3] : q0[r][2]), __float_as_uint(s1[r][0]), __float_as_uint(s1[r][2]));
            }
            bar_arrive(7, 160);
        }
        TSL(8);
        bar_sync(6, 160);
        const uint32_t tag = lds32(sm + SM_TOK + 8);
        cluster_wait();
        asm volatile("setmaxnreg.dec.sync.aligned.u32 104;");
        const uint32_t peer = mapa(sm, rank ^ 1);
        if (v == 0 && lane == 0) mbar_arrive_peer(peer + SM_BAR + B_UFREE * 8);
        {
            uint4 st[8] = {};
            const uint4* src = p.sc->stats[G & (NREP - 1)] + rank * 512 + 16 * v + (lane >> 1);
            const uint32_t tb = ((tag & 1) << 15) | ((tag >> 1) << 31);
#pragma unroll
            for (int i = 0; i < 8; i++) st[i].z = ~tb;
            int it = 0;
            bool ok;
            bar_sync(3, 192);
            sched_fence();
            if (warp == 8) TSL(44);
            do {
                uint32_t bad = 0;
#pragma unroll
                for (int i = 0; i < 8; i++)
                    asm volatile("{ .reg .pred p; .reg .b128 t; setp.ne.u32 p, %5, 0; mov.b128 t, {%0,%1,%2,%3};\n"
                                 "@p " POLL_LD " t, [%4]; mov.b128 {%0,%1,%2,%3}, t; }"
                                 : "+r"(st[i].x), "+r"(st[i].y), "+r"(st[i].z), "+r"(st[i].w)
                                 : "l"(src + (i >> 2) * 64 + (i & 3) * 128), "r"((st[i].z ^ tb) & 0x80008000u) : "memory");
#pragma unroll
                for (int i = 0; i < 8; i++) bad |= st[i].z ^ tb;
                ok = __all_sync(0xFFFFFFFFu, (bad & 0x80008000u) == 0);
                if (warp == 8 && it == 0) TSL(45);
            } while (!ok && ++it < SPIN_LIMIT);
            TSL(11); TG(31);
#pragma unroll
            for (int i = 0; i < 8; i++) { st[i].z = bmul2(st[i].z & 0x7FFF7FFFu, 0x3F003F00u); st[i].y = bmul2(st[i].y, 0x3F003F00u); }
            const uint32_t xo = sm + SM_SLAB + v * 512 + lane * 16;
            const bool own = (lane & 1) == rank;
            uint32_t n[2][8][4];
            mbar_wait(bars + B_UFREE * 8);
#pragma unroll
            for (int b = 0; b < 2; b++) {
                mbar_wait(bars + (B_SLAB + b) * 8);
                TSL(b ? 38 : 10);
#pragma unroll
                for (int i = 0; i < 8; i++) {
                    const uint4 x = lds128(xo + b * 16384 + (i & 1) * 8192 + (i >> 1) * 2048);
                    const uint4& t = st[4 * b + (i >> 1)];
                    const uint32_t m = (i & 1) ? dup_hi(t.x) : dup_lo(t.x), hi = (i & 1) ? dup_hi(t.z) : dup_lo(t.z), lo = (i & 1) ? dup_hi(t.y) : dup_lo(t.y);
                    uint32_t (&r)[4] = n[b][i];
                    r[0] = norm2(x.x, m, hi, lo); r[1] = norm2(x.y, m, hi, lo); r[2] = norm2(x.z, m, hi, lo); r[3] = norm2(x.w, m, hi, lo);
                    if (b && (i & 1)) sched_fence();
                }
                const uint32_t ua = SM_U + (16 * b + rank) * SUB + (16 * v + (lane >> 1)) * 16;
#pragma unroll
                for (int cc = 0; cc < 8; cc++) {
                    uint32_t o[4];
#pragma unroll
                    for (int i = 0; i < 4; i++)
                        o[i] = (cc & 1) ? pack_h(bhi(n[b][2 * i][cc >> 1]), bhi(n[b][2 * i + 1][cc >> 1])) : pack_h(blo(n[b][2 * i][cc >> 1]), blo(n[b][2 * i + 1][cc >> 1]));
                    const uint32_t dst = own ? mapa(sm, rank) : peer;
                    st_async4(dst + ua + 2 * cc * SUB, o[0], o[1], o[2], o[3], dst + SM_BAR + (B_U + b) * 8);
                    if (b && (cc & 1)) sched_fence();
                }
                TSL(b ? 41 : 12);
            }
            const uint32_t stg = __shfl_sync(0xFFFFFFFFu, sm + SM_U + (own ? 4 * SUB : 0) + v * 1024 + (lane >> 4) * 512 + (((lane & 14) * 8) ^ (own ? 64 : 0)), lane);
            const int tl = 256 * v + 16 * (lane >> 1) + 8 * rank;
            __nv_bfloat16* const op = p.out + (size_t)tl * 1024 + G * 16 + (lane & 1) * 8;
            const uint32_t zr = p.up_first >> 1;
#pragma unroll 1
            for (int b = 0; b < 2; b++) {
#pragma unroll
                for (int i = 0; i < 32; i++) {
                    const uint32_t r = n[0][i >> 2][i & 3];
                    n[0][i >> 2][i & 3] = n[1][i >> 2][i & 3];
                    n[1][i >> 2][i & 3] = pack_b(silu2(__uint_as_float(prmt(r, zr, 0x1044))), silu2(__uint_as_float(prmt(r, zr, 0x3244))));
                    if ((i & 7) == 7) sched_fence();
                }
            }
            TSL(0);
            mbar_wait(bars + B_TOK * 8);
            const uint2 tr = lds64(sm + SM_TOK);
#pragma unroll
            for (int b = 0; b < 2; b++) {
                const int d0 = tr.x - tl - 1024 * b, d1 = tr.y - tl - 1024 * b;
                uint32_t skip = ((d0 & ~7) ? 0u : 1u << d0) | ((d1 & ~7) ? 0u : 1u << d1);
                uint4 x[8];
                if (b) {
#pragma unroll
                    for (int i = 0; i < 8; i++) x[i] = lds128(xo + b * 16384 + (i & 1) * 8192 + (i >> 1) * 2048);
                }
                mbar_wait(bars + (B_STG + b) * 8);
                if (skip) {
#pragma unroll 1
                    for (int k = 0; k < 2; k++) {
                        const int d = k ? d1 : d0;
                        if (!(d & ~7)) {
                            const uint32_t a = (stg ^ ((d & 6) * 16)) + 16 * b * SUB + (d & 6) * 64 + (d & 1) * 8, dst = mapa(sm, k);
                            const uint2 s0 = lds64(a), s1 = lds64(a + 8 * SUB);
                            st_async4(dst + SM_FIX + (lane & 1) * 16, s0.x, s0.y, s1.x, s1.y, dst + SM_BAR + B_FIX * 8);
                        }
                    }
                }
                __syncwarp();
#pragma unroll
                for (int i = 0; i < 4; i++) {
                    const uint32_t a = (stg ^ (32 * i)) + 16 * b * SUB + 128 * i;
                    const uint4 r0 = lds128(a), r1 = lds128(a + 8 * SUB);
#pragma unroll
                    for (int e = 0; e < 2; e++) {
                        if (!b) x[2 * i + e] = lds128(xo + e * 8192 + i * 2048);
                        const uint4& xx = x[2 * i + e];
                        const uint32_t s0 = e ? r0.z : r0.x, s1 = e ? r0.w : r0.y, s2 = e ? r1.z : r1.x, s3 = e ? r1.w : r1.y;
                        const uint32_t (&gt)[4] = n[b][2 * i + e];
                        asm volatile("{ .reg .pred p; setp.eq.u32 p, %5, 0; @p st.global.v4.u32 [%0], {%1,%2,%3,%4}; }"
                                     :: "l"(op + (size_t)(1024 * b + 2 * i + e) * 1024), "r"(badd2(xx.x, bmul2(s0, gt[0]))), "r"(badd2(xx.y, bmul2(s1, gt[1]))),
                                        "r"(badd2(xx.z, bmul2(s2, gt[2]))), "r"(badd2(xx.w, bmul2(s3, gt[3]))), "r"(skip & (1u << (2 * i + e))) : "memory");
                    }
                    if (!b) { sched_fence(); if (i < 3) __nanosleep(STSLEEP); }
                }
                TSL(b ? 23 : 22);
            }
            TSL(17); TG(30);
        }
    } else {
        const int v = warp - 12;
        if (lane == 0) {
            if (v == 1) {
                mbar_init(bars + B_TAB * 8, 1); mbar_init(bars + B_TFREE * 8, 8); mbar_init(bars + B_KFREE * 8, 8); mbar_init(bars + (B_KFREE + 1) * 8, 8);
                mbar_expect(bars + B_TAB * 8, 20480 + 1536);
            } else if (v == 0) {
                mbar_init(bars + B_SLAB * 8, 1); mbar_init(bars + (B_SLAB + 1) * 8, 1); mbar_init(bars + B_TOK * 8, 2); mbar_init(bars + B_UFREE * 8, 1);
                mbar_expect(bars + B_SLAB * 8, 16384); mbar_expect(bars + (B_SLAB + 1) * 8, 16384);
            } else {
                mbar_init(bars + (B_STG + v - 2) * 8, 9); mbar_init(bars + (B_FIX + v - 2) * 8, 1);
                mbar_init(bars + (B_U + v - 2) * 8, 1); mbar_expect(bars + (B_U + v - 2) * 8, 16384);
                mbar_expect(bars + (B_STG + v - 2) * 8, 8192); mbar_expect(bars + (B_FIX + v - 2) * 8, v == 2 ? 32 : 2048);
            }
            mbar_init(bars + (B_PEER + v) * 8, 4);
#pragma unroll
            for (int i = 0; i < 3; i++) { mbar_init(bars + (B_FULL + 3 * v + i) * 8, 1); mbar_expect(bars + (B_FULL + 3 * v + i) * 8, 16384); }
            asm volatile("fence.mbarrier_init.release.cluster;" ::: "memory");
        }
        __syncwarp();
        cluster_arrive();
        asm volatile("setmaxnreg.dec.sync.aligned.u32 40;");
        uint64_t pol; asm volatile("createpolicy.fractional.L2::" WPOL ".b64 %0, 1.0;" : "=l"(pol));
        auto load_chunk = [&](int n) {
            if (n < 8) tma3d(sm + chunk_off(n), &tm_g, G * 64, rank * 512 + n * 64, 0, bars + (B_FULL + n) * 8, pol);
            else tma3d(sm + chunk_off(n), &tm_d, 0, G * 64, rank * 8 + (n - 8) * 2, bars + (B_FULL + n) * 8, pol);
        };
        uint32_t* const my_part = p.sc->part + ((2 * (32 * rank + v) + (q & 1)) * 56 + G) * 16 + g + 8 * (q >> 1);
        if (G < 56) {
#pragma unroll
            for (int n = 0; n < 8; n++) st_relaxed32(my_part + n * 8 * 56 * 16, 0);
        }
        cluster_wait();
        const bool lead = elect();
        uint32_t key = 0;
        if (v == 0) {
            asm volatile("prefetch.tensormap [%0];" :: "l"(&tm_x) : "memory");
            asm volatile("prefetch.tensormap [%0];" :: "l"(&tm_g) : "memory");
            { const int t0_ = clock(); while ((int)clock() - t0_ < SDELAY) __nanosleep(40); }
            if (lead) {
                int n = 0;
#pragma unroll 1
                for (int i = 0; i < 5; i++) {
                    if (G < 56) {
#pragma unroll 1
                        for (; n < ((FILL >> (4 * i)) & 15); n++) {
                            if (n >= IDEPTH) mbar_wait(bars + (B_FULL + n - IDEPTH) * 8);
                            if (n == 3) mbar_wait(bars + B_TFREE * 8);
                            load_chunk(n);
                        }
                    }
                    if (i < 4)
                        asm volatile("cp.async.bulk.tensor.4d.shared::cluster.global.mbarrier::complete_tx::bytes [%0], [%1, {%3, %4, %5, %6}], [%2];"
                                     :: "r"(sm + SM_SLAB + (i & 1) * 16384 + (i >> 1) * 8192), "l"(&tm_x), "r"(bars + (B_SLAB + (i & 1)) * 8),
                                        "r"(G * 16), "r"(64 * (i & 1)), "r"(4 * rank), "r"(i >> 1) : "memory");
                }
                TS(20);
                if (G < 56) {
#pragma unroll 1
                    for (int i = 0; i < NPF; i++) {
                        if (i < IDEPTH) mbar_wait(bars + (B_FULL + 5 + i - IDEPTH) * 8);
                        asm volatile("cp.async.bulk.prefetch.tensor.3d.L2.global [%0, {%1, %2, %3}];" :: "l"(&tm_g), "r"(G * 64), "r"(rank * 512 + (5 + i) * 64), "r"(0) : "memory");
                    }
                    mbar_wait(bars + B_KFREE * 8); load_chunk(5);
                    mbar_wait(bars + (B_KFREE + 1) * 8); load_chunk(6);
                }
                TS(21);
            }
            __syncwarp();
        } else if (v == 1) {
            if (lead) {
                asm volatile("cp.async.bulk.shared::cluster.global.mbarrier::complete_tx::bytes [%0], [%1], 20480, [%2];"
                             :: "r"(sm + SM_TAB), "l"(p.tab), "r"(bars + B_TAB * 8) : "memory");
                asm volatile("cp.async.bulk.shared::cluster.global.mbarrier::complete_tx::bytes [%0], [%1], 1536, [%2];"
                             :: "r"(sm + SM_F2), "l"(p.tab + 1280), "r"(bars + B_TAB * 8) : "memory");
                asm volatile("prefetch.tensormap [%0];" :: "l"(&tm_d) : "memory");
            }
        } else {
            const int sw = v - 2;
            if (sw == 0) {
                uint32_t tag;
                uint4* const my_stats = p.sc->stats[q] + c * 8 + g;
                asm volatile("ld.relaxed.gpu.global.u32 %0, [%1];" : "=r"(tag) : "l"(&p.sc->epoch) : "memory");
                float ws = 0.f;
#pragma unroll
                for (int k = 0; k < 4; k++) {
                    const uint4 w = ldg128(reinterpret_cast<const uint4*>(p.wr) + 32 * k + lane);
                    ws += (blo(w.x) + bhi(w.x)) + (blo(w.y) + bhi(w.y)) + (blo(w.z) + bhi(w.z)) + (blo(w.w) + bhi(w.w));
                }
                if (q < NREP) st_relaxed128(my_stats, make_uint4(0, 0, 0, 0));
                tag = tag % 3 + 1;
                sts32(sm + SM_TOK + 8, tag);
                bar_arrive(6, 160);
#pragma unroll
                for (int o = 1; o < 32; o <<= 1) ws += __shfl_xor_sync(0xFFFFFFFFu, ws, o);
                const uint32_t tb = ((tag & 1) << 15) | ((tag >> 1) << 31);
                const uint32_t ra = sm + SM_RED + (lane >> 1) * 144 + (lane & 1) * 64;
                const uint32_t kidx = 0xFFFF - (128 * (c & 15) + 16 * (lane >> 2) + 2 * (c >> 4) + ((lane >> 1) & 1));
                touch(ws);
                bar_sync(7, 160);
                const uint4 a0 = lds128(ra), a1 = lds128(ra + 16), a2 = lds128(ra + 32), a3 = lds128(ra + 48);
#define F(v) __uint_as_float(v)
                float ss = (F(a0.x) + F(a1.x)) + (F(a2.x) + F(a3.x)), dw = (F(a0.y) + F(a1.y)) + (F(a2.y) + F(a3.y));
                float sx = ((F(a0.z) + F(a1.z)) + (F(a2.z) + F(a3.z))) + ((F(a0.w) + F(a1.w)) + (F(a2.w) + F(a3.w)));
#undef F
                ss += __shfl_xor_sync(0xFFFFFFFFu, ss, 1); dw += __shfl_xor_sync(0xFFFFFFFFu, dw, 1); sx += __shfl_xor_sync(0xFFFFFFFFu, sx, 1);
                const float mean = sx * (1.0f / 1024.0f);
                const float var = fmaxf(ss * (1.0f / 1024.0f) - mean * mean, 0.f);
                const float m = rb(mean);
                float sd; asm("sqrt.approx.ftz.f32 %0, %1;" : "=f"(sd) : "f"(rb(rb(var) + 1e-5f)));
                const float rs = rcp(rb(sd));
                const float hi = rb(rs);
                const uint32_t p0 = pack_b(m, hi), p1 = pack_b(rs - hi, rs * (dw - m * ws));
                const uint32_t o0 = __shfl_xor_sync(0xFFFFFFFFu, p0, 2), o1 = __shfl_xor_sync(0xFFFFFFFFu, p1, 2);
                const uint32_t kr = ((p1 ^ (p1 >> 31 ? 0xFFFF0000u : 0x80000000u)) & 0xFFFF0000u) | kidx;
                const uint32_t k1 = __reduce_max_sync(0xFFFFFFFFu, kr), k2 = __reduce_max_sync(0xFFFFFFFFu, kr == k1 ? 0u : kr);
                const uint32_t sl = (q & 2) ? 0x1054 : 0x5410;
                if (q < NREP) st_relaxed128(my_stats, make_uint4(prmt(p0, o0, sl), prmt(p1, o1, sl), (prmt(p0, o0, sl + 0x2222) & 0x7FFF7FFFu) | tb, g == 0 ? k1 : k2));
                TSL(9);
                { const int t0_ = clock(); while ((int)clock() - t0_ < PDELAY) __nanosleep(20); }
            }
            bar_sync(3, 192);
            const uint32_t tg = lds32(sm + SM_TOK + 8), tb = ((tg & 1) << 15) | ((tg >> 1) << 31);
            {
                const uint32_t* src = &p.sc->stats[G & (NREP - 1)][(sw * 64 + (lane >> 1)) * 8 + (lane & 1)].z;
                uint2 kz[4];
#pragma unroll
                for (int i = 0; i < 4; i++) kz[i] = make_uint2(~tb, 0);
                int it = 0;
                bool ok;
                do {
#pragma unroll
                    for (int i = 0; i < 4; i++)
                        asm volatile("{ .reg .pred p; .reg .b64 t; setp.ne.u32 p, %3, 0; mov.b64 t, {%0,%1};\n"
                                     "@p ld.relaxed.gpu.global.b64 t, [%2]; mov.b64 {%0,%1}, t; }"
                                     : "+r"(kz[i].x), "+r"(kz[i].y) : "l"(src + i * 512), "r"((kz[i].x ^ tb) & 0x80008000u) : "memory");
                    ok = __all_sync(0xFFFFFFFFu, (((kz[0].x ^ tb) | (kz[1].x ^ tb) | (kz[2].x ^ tb) | (kz[3].x ^ tb)) & 0x80008000u) == 0);
                } while (!ok && ++it < SPIN_LIMIT);
                const uint32_t a1 = max(kz[0].y, kz[1].y), b1 = max(kz[2].y, kz[3].y);
                const uint32_t h1 = max(a1, b1), h2 = __vimax3_u32(min(a1, b1), min(kz[0].y, kz[1].y), min(kz[2].y, kz[3].y));
                const uint32_t w1 = __reduce_max_sync(0xFFFFFFFFu, h1), w2 = __reduce_max_sync(0xFFFFFFFFu, h1 == w1 ? h2 : h1);
                sts64(sm + SM_KEYS + sw * 8, w1, w2);
                bar_sync(8, 64);
                const uint2 o = lds64(sm + SM_KEYS + 8 - sw * 8);
                key = sw ? __vimax3_u32(min(w1, o.x), w2, o.y) : max(w1, o.x);
                TSL(19);
            }
            const int t = (0xFFFF - (key & 0xFFFF)) & 2047;
            {
                const uint4* row = reinterpret_cast<const uint4*>(p.x + (size_t)t * 1024);
                uint4 xr[3];
                xr[0] = ldg128(row + 64 * rank + lane); xr[1] = ldg128(row + 64 * rank + 32 + lane); xr[2] = ldg128(row + 2 * G + (lane & 1));
                uint4 stk;
                int it = 0;
                do stk = ld_relaxed128(p.sc->stats[G & (NREP - 1)] + ((t >> 1) & 7) * 128 + (t >> 4)); while (((stk.z ^ tb) & 0x80008000u) && ++it < SPIN_LIMIT);
                if (lane == 0) {
                    sts32(sm + SM_TOK + 4 * sw, t);
                    if (c == 0 && sw == 0) st_relaxed32(&p.sc->epoch, tg);
                }
                const uint32_t se = (t & 1) ? 0x3232 : 0x1010;
                const uint32_t m = prmt(stk.x, 0, se), hi = prmt(stk.z, 0, se) & 0x7FFF7FFFu, lo = prmt(stk.y, 0, se);
                const uint32_t a = sm + SM_XSEL + lane * 32 + sw * 16;
#pragma unroll
                for (int i = 0; i < 2; i++)
                    sts128(a + i * 1024, norm2(xr[i].x, m, hi, lo), norm2(xr[i].y, m, hi, lo), norm2(xr[i].z, m, hi, lo), norm2(xr[i].w, m, hi, lo));
                proxy_fence();
                __syncwarp();
                if (lane == 0) mbar_arrive(bars + B_TOK * 8);
                if (sw == rank && lane < 2) {
                    sts128(sm + SM_XRAW + lane * 16, xr[2].x, xr[2].y, xr[2].z, xr[2].w);
                    sts128(sm + SM_XRAW + 32 + lane * 16, norm2(xr[2].x, m, hi, lo), norm2(xr[2].y, m, hi, lo), norm2(xr[2].z, m, hi, lo), norm2(xr[2].w, m, hi, lo));
                }
                __syncwarp();
                TSL(42);
            }
        }
        mbar_wait(bars + B_TOK * 8);
        const uint32_t tag = lds32(sm + SM_TOK + 8);
        {
            if (G < 56) {
                const uint64_t dw = (uint64_t)((sm & 0x3FFFFu) >> 4) | (1ull << 16) | (64ull << 32) | (1ull << 62);
                const uint64_t dx = (uint64_t)(((sm + SM_XSEL) & 0x3FFFFu) >> 4) | (2ull << 16) | (8ull << 32);
                const uint64_t dh = (uint64_t)(((sm + SM_H) & 0x3FFFFu) >> 4) | (8ull << 16) | (8ull << 32);
                const uint64_t dw2 = dw + (tag >> 2);
                float ag[4], au[4];
                TSL(13);
#pragma unroll
                for (int n = 0; n < 8; n++) {
                    const uint64_t a = (n < 7 ? dw : dw2) + (chunk_off(n) >> 4), b = dx + n * 16;
                    mbar_wait(bars + (B_FULL + n) * 8);
                    wg_fence();
                    if (n == 0) { wg_w0(ag, a, b); wg_w0(au, a + 512, b); } else { wg_w<1>(ag, a, b); wg_w<1>(au, a + 512, b); }
#pragma unroll
                    for (int k = 1; k < 4; k++) { wg_w<1>(ag, a + 128 * k, b + 4 * k); wg_w<1>(au, a + 512 + 128 * k, b + 4 * k); }
                    wg_commit();
                    bool any = false;
#pragma unroll
                    for (int i = 0; i < 5; i++) any |= ((REFILL >> (4 * i)) & 15) == n;
                    if (any) {
                        if (n <= 5) { wg_wait<1>(); bar_sync(4, 128); }
                        if (v == (n & 3)) {
#pragma unroll
                            for (int i = 0; i < 5; i++) if (((REFILL >> (4 * i)) & 15) == n && lead) load_chunk(7 + i);
                            __syncwarp();
                        }
                    }
                    if (n == 4) TSL(4);
                    if (n == 7) TSL(34);
                }
                wg_wait<0>();
                touch(ag); touch(au);
                TSL(14);
                if (q == 0) {
#pragma unroll
                    for (int r = 0; r < 2; r++) {
                        const uint32_t dst = mapa(sm, r), o = dst + SM_PAIR + rank * 1024 + v * 256 + g * 32;
                        st_async4(o, __float_as_uint(ag[0]), __float_as_uint(ag[1]), __float_as_uint(ag[2]), __float_as_uint(ag[3]), dst + SM_BAR + B_PAIR * 8);
                        st_async4(o + 16, __float_as_uint(au[0]), __float_as_uint(au[1]), __float_as_uint(au[2]), __float_as_uint(au[3]), dst + SM_BAR + B_PAIR * 8);
                    }
                }
                mbar_wait(bars + B_PAIR * 8);
                {
                    const uint32_t o = sm + SM_PAIR + v * 256 + g * 32 + q * 4, og = o + (p.up_first ? 16 : 0), ou = o + (p.up_first ? 0 : 16);
                    const float gs = rb(__uint_as_float(lds32(og)) + __uint_as_float(lds32(og + 1024)));
                    const float us = rb(__uint_as_float(lds32(ou)) + __uint_as_float(lds32(ou + 1024)));
                    const float hv = rb(siluf_(gs)) * us;
                    const uint32_t hd = sm + SM_H + (2 * v + (q >> 1)) * 128 + (q & 1) * 32 + g * 2, hb = pack_b(hv, hv);
                    sts16(hd, hb); sts16(hd + 64, hb);
                }
                proxy_fence();
                bar_sync(4, 128);
                TSL(15);
#pragma unroll
                for (int n = 0; n < 4; n++) {
                    const uint64_t a = dw2 + (chunk_off(8 + n) >> 4);
                    float d[2][4];
                    mbar_wait(bars + (B_FULL + 8 + n) * 8);
                    if (n == 3) TSL(24);
                    wg_fence();
                    wg_w0(d[0], a, dh); wg_w0(d[1], a + 512, dh);
#pragma unroll
                    for (int k = 1; k < 4; k++) { wg_w<1>(d[0], a + 128 * k, dh + 16 * k); wg_w<1>(d[1], a + 512 + 128 * k, dh + 16 * k); }
                    wg_commit();
                    wg_wait<0>();
#pragma unroll
                    for (int i = 0; i < 2; i++) {
                        touch(d[i]);
                        st_relaxed32(my_part + (2 * n + i) * 8 * 56 * 16, (__float_as_uint((q & 2) ? d[i][2] : d[i][0]) & ~3u) | tag);
                    }
                }
                TSL(16);
            } else {
                mbar_wait(bars + B_STG * 8);
            }
            if (v == 2 + rank) {
                const int t = (0xFFFF - (key & 0xFFFF)) & 2047;
                const int col = 4 * q + 2 * (lane >> 4) + ((lane >> 3) & 1), d = G * 16 + col;
                const float r = __uint_as_float((key & 0x80000000u) ? (key & 0x7FFF0000u) : (~key & 0xFFFF0000u));
                const float sg = rb(sigmoidf_(r));
                const uint4* src = reinterpret_cast<const uint4*>(p.sc->part) + c * 224 + lane;
                float s0 = 0, s1 = 0, s2 = 0, s3 = 0;
                {
                    uint4 pv[7];
                    int it = 0;
                    bool ok;
                    do {
                        uint32_t bad = 0;
#pragma unroll
                        for (int i = 0; i < 7; i++) pv[i] = ld_relaxed128(src + 32 * i);
#pragma unroll
                        for (int i = 0; i < 7; i++) bad |= (pv[i].x ^ tag) | (pv[i].y ^ tag) | (pv[i].z ^ tag) | (pv[i].w ^ tag);
                        ok = __all_sync(0xFFFFFFFFu, (bad & 3) == 0);
                    } while (!ok && ++it < SPIN_LIMIT);
#pragma unroll
                    for (int i = 0; i < 7; i++) {
                        s0 += __uint_as_float(pv[i].x); s1 += __uint_as_float(pv[i].y); s2 += __uint_as_float(pv[i].z); s3 += __uint_as_float(pv[i].w);
                    }
                }
                TSL(25);
                const float xn = blo(lds16(sm + SM_XRAW + 32 + col * 2)), xv = blo(lds16(sm + SM_XRAW + col * 2));
                const bool u16 = lane & 16, u8 = lane & 8;
                const float y0 = (u16 ? s2 : s0) + __shfl_xor_sync(0xFFFFFFFFu, u16 ? s0 : s2, 16);
                const float y1 = (u16 ? s3 : s1) + __shfl_xor_sync(0xFFFFFFFFu, u16 ? s1 : s3, 16);
                float y = (u8 ? y1 : y0) + __shfl_xor_sync(0xFFFFFFFFu, u8 ? y0 : y1, 8);
                y += __shfl_xor_sync(0xFFFFFFFFu, y, 4);
                const float z = rb(xn + rb(rb(y) * sg));
                const float gt = rb(siluf_(z));
                mbar_wait(bars + B_FIX * 8);
                const float o = xv + rb(blo(lds16(sm + SM_FIX + col * 2)) * gt);
                if (!(lane & 4)) p.out[(size_t)t * 1024 + d] = __float2bfloat16(o);
                TSL(26); TG(29);
            }
        }
    }
    }
}

__device__ __align__(128) const uint32_t g_tab[5504] = {
0x2fff3000,0x2e7c2fd4,0x2fc92fd4,0xad72af5a,0x2ff82ffc,0x230e2c07,0x2faf2fbc,0x217ea934,0x2fed2ff4,0xad4da8d5,0x2f912fa0,0x2e5e2bb7,
0x2fdd2fe6,0xb000af46,0x2f6e2f80,0x2fdd2fc9,0x2ff42fff,0x2e1f2fc9,0x2e1f2e7c,0xa875ad72,0x2fbc2fdd,0x9fd92a4e,0x2d4d2dba,0x2cd825db,
0x2f5a2f91,0xaeb5ac07,0x2c5d2cd8,0x30002f30,0x2ed02f1a,0xaf80aff4,0x2aaa2bb7,0x2cb02f1a,0x2fdd2ffc,0x2dba2fbc,0x2a4e2c07,0x25dba934,
0x2f462fa0,0xa7652875,0x25152875,0x2f802d27,0x2e3f2ed0,0xafa0ad72,0xa17e1cb6,0x2e3f2fe6,0x2cd82d96,0xadfeafd4,0xa934a6a1,0xa44e29f1,
0x2fbc2ff8,0x2d4d2faf,0x9fd9230e,0x2cd8217e,0x2e992f46,0xaa4e2515,0xaa4ea765,0x2fd42f80,0x2cb02dba,0xafffae99,0xad72ac5d,0x27652dba,
0x28752b05,0xab5eaee9,0xaf1aae5e,0xae3fa934,0x2f912ff4,0x2cd82fa0,0xac07a8d5,0x2f302bb7,0x2dba2ed0,0xac5d1cb6,0xae99ad72,0x2dba2fe6,
0x29932c5d,0xafc9af6e,0xafe6af6e,0xaaaa25db,0xa17e244e,0xa30ead4d,0xafafaffc,0xaff8aee9,0x2f5a2fed,0x2c5d2f91,0xaeb5ad4d,0x30002e5e,
0x2cb02e3f,0xad72a17e,0xafffafa0,0x27652e3f,0x217e2993,0xaf02afe6,0xaf02afc9,0xaf1aaaaa,0xab05a5db,0x2814aa4e,0xac07adba,0xad4dafdd,
0x2f1a2fe6,0x2bb72f80,0xaff4af46,0x2f1a2fc9,0x2b052d96,0xae5ea6a1,0xaee9afd4,0xa93429f1,0xa5db244e,0xadbaaffc,0xaa4ead4d,0xafddaee9,
0xaddcabb7,0x2cb0a17e,0x2765a17e,0x1cb6ad00,0x2ed02fdd,0x2aaa2f6e,0xaf80b000,0x2cb02fdd,0x28752cd8,0xaf1aa934,0xab5eadfe,0xae3fa44e,
0xab05a17e,0xac07afaf,0x2814a30e,0xad4daff8,0xaf6eaddc,0x2eb52765,0x2eb52cb0,0x2dba1cb6,0x29932f5a,0xa7652e99,0x25152e99,0x2aaaad96,
0xafa0ab05,0xabb7afed,0xaff4acd8,0x28d52ffc,0xa814af02,0x2f912d27,0x9fd9ae1f,0xaee9ae3f,0x2fd42c32,0xaf5a1cb6,0x30002d72,0x2fd42515,
0x28752f46,0xa8d52e7c,0xa8d52c32,0x2e3fa993,0xafedac5d,0xa934b000,0xaf30af5a,0xa8142eb5,0x1648adfe,0x2e992e5e,0x2c87a814,0xa9f1affc,
0x2fe62e1f,0xafffa875,0x2ddc2ff4,0x2ed02e1f,0x26a12f30,0xa9f12e5e,0xad96244e,0x2fd41fd9,0xafffad27,0xa515aff4,0xac32aff4,0xaddc2b5e,
0x2875acb0,0x2d272f46,0x2fa02993,0x2875aed0,0x2ee92f6e,0xaf91ac87,0x1fd92e99,0x28143000,0x244e2f1a,0xab052e3f,0xaf91a875,0x2fbc2b5e,
0xafd4addc,0x1648afc9,0x1648ae7c,0xafdd9cb6,0x2c32aa4e,0x2aaa2fd4,0x2f802e99,0x2e7caa4e,0x2d002ffc,0xae1fae5e,0xad272814,0xabb72dfe,
0x1fd92f02,0xac072e1f,0xafedad27,0x2dfe2e3f,0xaf6eae7c,0x25dbaf80,0x2c5daaaa,0xaf6eac32,0x2ddca5db,0x25153000,0x2c323000,0x2fff26a1,
0x28d52fbc,0xabb7af91,0xaff4ab05,0xafa0244e,0x96482ee9,0xac872dfe,0xae99af30,0x29f12fbc,0xaed0af02,0x2993af1a,0x2f46217e,0xacb0af02,
0x2f1a1cb6,0xa30e2fc9,0xa30e2e7c,0x2e1f2ddc,0x9fd92eb5,0xa44eb000,0xae5eaf5a,0xaf30ac5d,0xa17e2ed0,0xad002ddc,0xabb7afff,0xa17e2fe6,
0xadfeaf6e,0x2c07ae99,0x2fed2c87,0x9fd9b000,0x2fd42814,0xa9f12f30,0xad962934,0x26a12fed,0xaaaa2d00,0x2765afa0,0xa515afa0,0xa993afaf,
0xa5152eb5,0xad722dba,0x9cb6af6e,0xac322eb5,0xad00afbc,0x2d27adfe,0x2e1f2f30,0x2bb7aee9,0x2ffc2b5e,0xacd82e3f,0xafeda875,0xab052f1a,
0xadba2993,0x2c87ae7c,0x2c87ac32,0x2a4eaf46,0xaddc2d96,0xafe62c5d,0xaed02c5d,0x2fffa9f1,0x2e1fad4d,0x2e3f2814,0x2f02ac07,0xad27ab05,
0xae5e2d00,0x9fd9af1a,0xaf302b5e,0xa44e2faf,0x2e99acb0,0xad962f80,0x2f5aaaaa,0x2e99aed0,0xae3f2d72,0xaff82c32,0xaff82515,0x2f021cb6,
0x2ee9ac87,0x2d4d29f1,0x2ffc9648,0xa44eae99,0xaf6e2b05,0x26a1afbc,0xafd4a44e,0xadba2f91,0x2fc9a8d5,0xaf462e3f,0x2f802875,0x2fe6a8d5,
0xae992d4d,0xb0002c07,0xaf6ea814,0x2c872b05,0x2f80ab5e,0x2c322bb7,0x2e7c2bb7,0x2aaaaff8,0xaff42765,0x2b5eafff,0xad27ad72,0xaff42cb0,
0x2fed1648,0xaffc2c5d,0x2b052eb5,0x2cd82a4e,0xaee92d27,0xaffc2bb7,0xad4dad00,0x244e2e1f,0x2fdda993,0x29f12cb0,0x29f12ed0,0x2eb5af46,
0xafe61648,0x2d72afdd,0x9cb6afd4,0xaed01648,0x2f022934,0xafa02814,0xa8d52fed,0xa30e2f30,0xaf302d00,0xafed2b5e,0xa814af1a,0xa9342faf,
0x3000a765,0x26a12d72,0xa5db2fff,0x3000acb0,0xaf46a6a1,0x2ed0af5a,0x2cb0af5a,0xa993ac87,0x2d272cd8,0xae3f9fd9,0xaf022d4d,0xae1f2fbc,
0xaf6e2cd8,0xafd42b05,0x26a1affc,0xadba2fed,0x2fe6a30e,0x1cb62e1f,0xad722f1a,0x2ed0a30e,0xae1faaaa,0x2fafae7c,0x2fafac32,0x28d5af80,
0x29342e99,0xac07a9f1,0xafbc1648,0xaffc2c87,0xafa02cb0,0xafaf2aaa,0x2d00af80,0xafa02ed0,0x2f911648,0xa44e2eb5,0xafbc2c5d,0x2b052a4e,
0xac87acd8,0x3000ad4d,0x2f6e1fd9,0x2e99afbc,0x9cb62faf,0xa515ad27,0xac32ad27,0xad72a30e,0xafc92c87,0xaf802a4e,0x2f46adba,0xafe62c87,
0x2f02244e,0xa8d52f30,0xafa01fd9,0xa30e2e5e,0xa934ae1f,0x2fbcabb7,0x2c072d00,0x2ffcad27,0xaa4e2fff,0x26a1aed0,0x26a1afe6,0x1648addc,
0xaf4629f1,0xac3225db,0xae7c25db,0x29931648,0xab5e2f91,0xafaf2e5e,0xad002fed,0x2f1aad4d,0x2ee9a875,0xaf302ff8,0x2dfea17e,0x2fbcaff4,
0x2c5dafc9,0xa9f12d72,0x2d96afff,0x2c5dae7c,0xaf022993,0xab5e2515,0xab5ea765,0xa30e2aaa,0xacd82fd4,0xaf302dba,0xaf912f6e,0x2c07a6a1,
0x2d969fd9,0xafdd2fed,0x25db2c07,0x2f5aadfe,0x2e7caff8,0xad722f02,0x2fffae3f,0x2fc9aff8,0xaeb52934,0xaa4e244e,0x9648acd8,0xac5d2dfe,
0xaddc2ff8,0xae7c2d00,0xafc92d00,0x9cb628d5,0x2bb72515,0xaff82f80,0xab5e2f46,0x2bb7a765,0x2fbcaf5a,0xaf302fdd,0x2dfea5db,0x2ee9ad96,
0xae5e28d5,0xa934230e,0x2b05af02,0xaee92fa0,0xaeb52fff,0xad962c32,0xad962515,0xac872ddc,0x276529f1,0xaf802eb5,0xaf462fdd,0xa51529f1,
0x2ff4adfe,0xaff82fed,0x217e2c07,0x28759fd9,0xadfe2875,0xa814217e,0x2e5eaff8,0xaffc2ff4,0xaf5a2fe6,0xac872aaa,0xa6a1a993,0xaf5a2fc9,
0x9cb62c87,0xae7c2d96,0xafc92d96,0xaddc2eb5,0x2f1aac07,0xafaf2f30,0xad002f91,0xab5e2cd8,0xad962814,0xa5db1fd9,0x2fddaf91,0xaf5a2ee9,
0xafc92faf,0xaaaa28d5,0x2993ae1f,0xafe62faf,0xa8d52ddc,0xad002c32,0xad002515,0xaff82fff,0x2d4da6a1,0xae5e2dba,0xafed2f6e,0xaf912fd4,
0xad272765,0xa30e1cb6,0x2fafaddc,0xad272cb0,0xaffc2f5a,0xa81425db,0x2e5eafdd,0xadfe2d96,0xac5d2ee9,0xaa4e2934,0x9648ab05,0xaeb52e5e,
0x2993230e,0xac322b5e,0xae7c2b5e,0xaf462f02,0xacb026a1,0x9cb61648,0x2ddcaa4e,0xa76526a1,0xaff42ee9,0xa17e1fd9,0x2ff8af91,0xa8752814,
0xadfe2fa0,0xa44e230e,0x2cd8af02,0xa93428d5,0x96482aaa,0xa5db2515,0xa5dba765,0xa9f12993,0x2f462f5a,0x2c322e99,0x2e7c2e99,0xa993ad96,
0x2f1a2f30,0xa875244e,0x2e3f2e5e,0x2b5e1fd9,0x2ee92f02,0xaf30ad27,0x2dfe2e1f,0x2fbc2e3f,0x2eb52ed0,0xaf6eafff,0x2dba2ddc,0x2eb52fe6,
0x28752993,0xa8d52515,0xa8d5a765,0x2e3f2aaa,0x244e26a1,0xaf91ad96,0xab05a9f1,0x2fbc2fd4,0x96481fd9,0xae99afed,0xac87ac07,0x29f12dfe,
0xa515a17e,0x9cb6abb7,0xad72ad00,0xac32a17e,0xac5dab05,0xaf5aacd8,0xb000afed,0x2eb52ffc,0xaddcad27,0xae7caff4,0xafc9aff4,0x9cb62b5e,
0xaf02ae7c,0x217eaaaa,0xaf1aaf80,0xaf02ac32,0xafbcaf6e,0x2f302c87,0xadfeae99,0xaee9b000,0xafedafa0,0xaf30aff4,0xa934abb7,0xa81428d5,
0xafd4afff,0x1648ac32,0x1648a515,0xafddaddc,0xaed0af6e,0x2f462c5d,0x299325db,0xacb0af6e,0xad00adfe,0x2e1f2fed,0x2d272c07,0x2bb79fd9,
0xadfeaf02,0xa814ae1f,0x2e5e2d27,0xaffcae3f,0xaa4eacb0,0x2e992993,0x2fd42f46,0xaa4eaed0,0x1cb6a5db,0x2e7c3000,0x2fc93000,0x2ddc26a1,
0x2b5e2814,0xa8752934,0x2e3f2f30,0x2f1a2fed,0x1648a814,0x2c879fd9,0x2e992f91,0xa9f1aee9,0x2c322875,0x2f802fa0,0x2aaa2d27,0x2e7c2875,
0x2f1a2ddc,0xa30e2c32,0xa30e2515,0x2e1f2fff,0x2ffc2fd4,0xafedad96,0xacd8a9f1,0xab0526a1,0x2e1f2c32,0x2ff42d72,0xa8751cb6,0x2e1f2515,
0x2ffc2f6e,0x28142e99,0xae5eac87,0x2dfe3000,0x2eb52fbc,0xaf5aab05,0xb000af91,0xac5d244e,0x29932d00,0xac32afa0,0xae7cafa0,0xaf46afaf,
0x2fe62fd4,0x2ddc3000,0xafffaf5a,0x2ed02fd4,0x2d002ee9,0xad271fd9,0xae1faf91,0xabb72814,0x9fd928d5,0xae5eaff4,0xa44eabb7,0xaf30afa0,
0xadbaaaaa,0x2c87a515,0x2c872765,0x2a4ea993,0x9cb62d96,0xacb02c5d,0xa7652c5d,0x2ddca9f1,0xaff8adfe,0xa30eafbc,0xafafaee9,0xa17e2f30,
0x244ead00,0x2dfe2f1a,0x2934ab5e,0xacd8afaf,0x2fdd2e7c,0xb000a993,0x2f6e2f46,0x2fdd2c32,0xae3f9cb6,0xaff8a765,0xaff8acb0,0x2f022ddc,
0xac07afdd,0x2dfeaa4e,0x1fd9adba,0xafeda5db,0x2f6e2934,0xa6a12ee9,0x2fd42e5e,0x2dbaab05,0x27652f1a,0xaaaaaff4,0xa9932bb7,0xa5152f1a,
0xafddadfe,0xadbaaee9,0xaa4eafbc,0xa5db2f30,0x2aaaab5e,0x2fc92bb7,0x2fe62bb7,0xa993aff8,0x2e3f2fc9,0xafa01cb6,0xa17e2ddc,0x2e3f2e7c,
0xae5e9648,0x2d4dac5d,0xaf91aeb5,0xafedaa4e,0xac07aff8,0x1fd9afaf,0x2dfea30e,0xafeda17e,0x2fdd2aaa,0x29f12fe6,0x29f12fc9,0x2eb5a993,
0xa5152dba,0xaddcae99,0xafffac5d,0xac322dba,0xaf02af30,0x2fa02c07,0x28d5acd8,0x230eaf91,0x2934ad00,0x2e5eab5e,0x2ee92f1a,0xab05afaf,
0x2dba2fc9,0xac5d2ddc,0xae991cb6,0x2dba2e7c,0xaf80a6a1,0x2765af5a,0xa515af5a,0xaf46ac87,0x217eae5e,0x230e2ffc,0x2faf2dfe,0x2ff82814,
0x2f6e244e,0x2fd42934,0xa6a12dfe,0x2dbaacd8,0xa5152e3f,0xafffa17e,0xaddcafa0,0xac322e3f,0xae1faf80,0x2fafa515,0x2faf2765,0x28d5af46,
0x2f9125db,0xaee92a4e,0xa8142dba,0x9fd92fdd,0x2f1a2e7c,0x2bb72f46,0xaff4a993,0x2f1a2c32,0xaf309648,0xacd8aeb5,0x2c07ac5d,0xaf91aa4e,
0x25dbae5e,0x2dba2dfe,0x2a4e2ffc,0x2fdd2814,0x2d722faf,0xae7cad27,0xafc9ad27,0xafffa30e,0x27652fdd,0xa9932f6e,0xaaaab000,0xa5152fdd,
0xaf02ae5e,0x28d5af91,0x2fa02d4d,0x230eafed,0x2f91217e,0xa8142faf,0xaee9230e,0x9fd92ff8,0xaa4e2d72,0x26a1afc9,0x26a1ae7c,0x1648afff,
0xaf8029f1,0xafc925db,0xafe625db,0x2f461648,0x2fa0a934,0x2bb72cd8,0x2ff4a44e,0xa8d5adfe,0xafbc2875,0x2934aff8,0xaffc217e,0xac072ff4,
0x2fd4a765,0xaf5a2ddc,0x30009cb6,0x2fd4acb0,0xaf02aaaa,0xab5eacb0,0xab5eaed0,0xa30e2f80,0x2e5e2c5d,0xab053000,0x29342f5a,0x2ee9aeb5,
0xad96ad4d,0x2fddacd8,0xa5dbafbc,0xaf5a1fd9,0x2cb02e1f,0xaddca875,0x1cb62ff4,0x27652e1f,0xa6a1af91,0x29f1afed,0x2d96ae5e,0xafd42d4d,
0x9cb62ff8,0xafe62d00,0xaed02d00,0x2d7228d5,0x2875afe6,0x2d272993,0x2fa0aaaa,0x2875afc9,0xac072f5a,0x2934afdd,0xaffc25db,0xafbc2d96,
0x2cd8af1a,0x2f91ae3f,0x2f302875,0xac07ab5e,0xaeb52d72,0xad96a765,0xad96acb0,0xac872fff,0x2fc9aa4e,0xa9932fd4,0x2aaa2e99,0x2fe6aa4e,
0xaff41fd9,0x2ff8acd8,0xa17eafbc,0xa875ad4d,0x2ffca875,0x2ee9a17e,0xa44e2ff8,0x2d4daff4,0xaf6ea515,0x25dbaf46,0x2c5daf80,0xaf6e2765,
0x2d722c87,0xafe62d96,0xaed02d96,0x9cb62eb5,0xa8d5aee9,0x2bb72b05,0x2ff4a934,0x2fa0ae5e,0x2d962c07,0x25db2d4d,0xafdd2b05,0x2f5aa814,
0xa765af02,0x2f46af1a,0x2f80217e,0x2515af02,0xa8d52fff,0xad00a765,0xad00acb0,0xaff82d72,0x2dfeaeb5,0xacd83000,0x244e2f5a,0x29342c5d,
0xa17e2fc9,0xad002fff,0xabb7ad72,0xa17e2e7c,0x2d4daf5a,0x2ee9a5db,0xa44e2fdd,0x2ffcad96,0xafd42c07,0x29f1af91,0x2d96af30,0xa6a1acd8,
0x2f46230e,0xafc92b5e,0xafe62b5e,0xaf802f02,0xae7c2eb5,0xafff2dba,0x2d72af6e,0xafc92eb5,0x2ff4a814,0x217e2d4d,0xaff82b05,0x28752c07,
0xad4dab5e,0x2fedae3f,0x2e5e2875,0x2f91af1a,0x96482f80,0xa5dbacb0,0xa5dbaed0,0xa9f1aaaa,0xad729648,0xa515a6a1,0xac32a6a1,0x9cb62a4e,
0xae1f2ffc,0xae3f2c07,0xaf022fbc,0x2d27a934,0x2cd8230e,0xaffc2fa0,0x2b0528d5,0x2fedaf02,0x2e99afe6,0xad962f46,0x2f5aaf80,0x2e99afc9,
0x230eaddc,0x2d27aed0,0x2d27afe6,0xafaf2fff,0xafbc2c87,0x1fd9a9f1,0xad4d1648,0xacd82e99,0xaa4e2f30,0xac5d2814,0xaeb52fed,0x96482934,
0x2ed0a8d5,0xaf802e3f,0x2aaa2875,0x2cb0a8d5,0x2e99affc,0x3000afbc,0x2f6eac07,0xac872934,0xa993a8d5,0x2ed0afaf,0x2cb0afaf,0xaf462e1f,
0xaff42ed0,0x2b5ead72,0xad271cb6,0xaff42fe6,0xa44e2dba,0x9fd9a6a1,0xaf302fd4,0xae5e2f6e,0x2fbcad27,0x2d4dabb7,0x9fd92d00,0x2cd8ae1f,
0x2c87af80,0x2f5aae7c,0x2f5aac32,0x26a1aaaa,0xacb01648,0x2fffafdd,0x2d72afd4,0xa7651648,0xafaf2f91,0x2f1aafbc,0xab5ea44e,0xad002b05,
0x2b05230e,0xa44e28d5,0xafbc2fa0,0x2f91af02,0x3000aed0,0x26a19cb6,0xa5db2d72,0x3000afe6,0x2aaaaeb5,0x2c32a9f1,0x2e7ca9f1,0x2f80afdd,
0xad27244e,0x2e3fad4d,0x2f02affc,0x2e1faee9,0xaa4e2e5e,0xaeb52f30,0xac5d1fd9,0x9648244e,0x2cb0a30e,0xad722e1f,0xafff2f1a,0x2765a30e,
0x2ff8af46,0xabb72cb0,0xabb72ed0,0x2b5ea993,0x2b05ae99,0xa81429f1,0x2c079648,0x2d4dac87,0xafa02fe6,0xafaf2f80,0x2d00af46,0xafa02fc9,
0xa9342dba,0xafed2fd4,0xa814a6a1,0xaf302f6e,0x2c87a44e,0xb0002ffc,0xaf6e2d4d,0xae992ee9,0x2fffaf02,0xafe62ff8,0xaed02ff8,0xaddc2e3f,
0xaed02c87,0xaaaa2a4e,0x2f80adba,0xacb02c87,0xafaf2fed,0xab5e2b05,0x2f1aaffc,0xad002cd8,0xab052e1f,0xac072bb7,0x2814ad00,0xad4d2d27,
0x29f11cb6,0xac5d2c32,0xac5d2515,0xad962d72,0x2d722d96,0x25152c5d,0x2c322c5d,0x1cb6a9f1,0x2d272d4d,0xad00a814,0x2bb72c07,0x2e1f2b05,
0x2cd82d00,0xaffcaf1a,0x2b052b5e,0x2fed2faf,0x2c872cb0,0xadbaaf80,0x2a4e2aaa,0x2c872ed0,0xae3faddc,0xaff8aed0,0xaff8afe6,0x2f022fff,
0xaee9ae99,0xad4daf6e,0xaffcb000,0x244e2c87,0xaf6eaf30,0x26a1a814,0xafd4afed,0xadbaa934,0xafc9afa0,0x2f462d00,0xaf80afaf,0xafe6afa0,
0xac87ad4d,0x9648ac07,0x29f12814,0xae99ab05,0xa993ab5e,0x2ed02bb7,0x2cb02bb7,0xaf46aff8,0xa30ea765,0x2f1a2fff,0x2e1f2d72,0xa30eacb0,
0x244e1648,0x1fd92c5d,0x2f302eb5,0x2e5e2a4e,0x2ee92e1f,0x2ffc2f02,0x2d4d2e3f,0xa44ead27,0x2fdd2f80,0x29f12e7c,0x29f12c32,0x2eb52aaa,
0x2fe63000,0xad72a5db,0x1cb626a1,0x2ed03000,0x2f022f91,0xafa0afbc,0xa8d5a44e,0xa30e2b05,0x2b052d00,0xa44e2b5e,0xafbcaf1a,0x2f912faf,
0x16482765,0xafd4ad72,0xafddafff,0x16482cb0,0xaaaaa6a1,0xac32af5a,0xae7caf5a,0xaf80ac87,0xae1facd8,0x2d001fd9,0xabb7ad4d,0xad27afbc,
0xaf6eae5e,0xafd4af30,0x26a19fd9,0xadbaa44e,0xafe6aff4,0x9cb6ad27,0x2d722b5e,0xaed0aff4,0xae1faf46,0x2faf2cb0,0x2faf2ed0,0x28d5a993,
0xa934ac87,0x2c072f6e,0x2fbc3000,0x2ffc2e99,0xa8d5acb0,0x2875aaaa,0x2e3f2f80,0xa8d5aed0,0x29341648,0x2fed2eb5,0x28142c5d,0x2f302a4e,
0x2e992cd8,0x16482d4d,0xa9f19fd9,0x2c872fbc,0x2fff2faf,0xafe6ad27,0xaed0ad27,0xaddca30e,0x2fc92e99,0x2f802f5a,0xaf46ad96,0x2fe62e99,
0x2f022fed,0xa8d52b05,0xafa0affc,0xa30e2cd8,0x29342d27,0xafbcaf02,0xac07ae3f,0xaffcae1f,0xaa4e9cb6,0x26a1ac32,0x26a1a515,0x1648ad72,
0xaaaa29f1,0xaed025db,0xacb025db,0x2f801648,0xaf1aaf91,0x2875ae5e,0xae3fafed,0xab5e2d4d,0x2c07a875,0x2b052ff8,0x2d4da17e,0xa814aff4,
0x2eb52fc9,0xaf6ead72,0x2dba2fff,0x2eb52e7c,0xaf02af80,0xab5eafe6,0xab5eafc9,0xa30e2f46,0x2cd8a6a1,0x2f302d96,0x2f9129f1,0xac07afd4,
0x2d962ffc,0xafdda44e,0x25db2ee9,0x2f5a2d4d,0xae7ca17e,0x2d72abb7,0xafffad00,0xafc9a17e,0x2c5da934,0x2f5aa44e,0x30002cd8,0xaeb5adfe,
0x2d722ff8,0xacb02d00,0xa7652d00,0x2fff28d5,0xaf02a515,0x217eaf80,0xaf1aaf46,0xaf022765,0xa814af5a,0x2b052fdd,0x2d4da5db,0x2c07ad96,
0x2e5e2fa0,0x29342ff4,0xab052bb7,0x2ee9a8d5,0xaeb59cb6,0xad96aed0,0xad96afe6,0xac872d72,0xa765af6e,0x2f802c5d,0x2f4625db,0x2515af6e,
0x2ff42d4d,0xaff8a44e,0x217e2ee9,0x28752ffc,0xad4d2875,0xafbc217e,0xacd8aff8,0x1fd92ff4,0xaa4eafe6,0x2e99aaaa,0x2fd42993,0xaa4eafc9,
0x2fff2c87,0xacb02d96,0xa7652d96,0x2d722eb5,0xab5e2c07,0x2875af30,0xae3faf91,0xaf1aacd8,0xad96afbc,0xa5dbaffc,0x2fdd2934,0xaf5aac07,
0x2fc92875,0x2aaa2fa0,0xa9932d27,0x2fe62875,0xa8d52d72,0xad00aed0,0xad00afe6,0xaff89cb6,0xad4dafd4,0x2e5e2d96,0x2fed29f1,0x2f91a6a1,
0x2e1fa765,0x2ff49cb6,0xa8752ddc,0x2e1facb0,0x1fd92f5a,0xafbc25db,0xacd8afdd,0xad4d2d96,0xaeb5aee9,0x2f5aa934,0x30002b05,0x2c5dae5e,
0x2f80230e,0xaed02b5e,0xacb02b5e,0xaaaa2f02,0x2cb02fd4,0x1cb63000,0xaddcaf5a,0x27652fd4,0xaff4ac07,0xa17eaffc,0x2ff82934,0xa875afbc,
0x2dfea8d5,0x244e2ff4,0xacd82bb7,0x29342fa0,0x96482f46,0xa5dbafe6,0xa5dbafc9,0xa9f1af80,0xafff9648,0xae7ca6a1,0xafc9a6a1,0x2d722a4e,
0x2ff81fd9,0x230e2ee9,0x2faf2814,0x217eaf91,0xafeda30e,0x2d4dafa0,0xaf91a8d5,0xae5e2f02,0x2fdd2515,0xb0002aaa,0x2f6e2993,0x2fdda765,
0x230eafff,0x2d27afc9,0x2d27ae7c,0xafaf2d72,0xa8142fdd,0xaffc2a4e,0xadfe2dba,0x2e5e25db,0x2a4eaf91,0x2c5d2c07,0x2eb5acd8,0x1648af30,
0xac322f1a,0x2993aff4,0xaf462bb7,0xae7c2f1a,0x2fdd1fd9,0x2dba2814,0x2a4e2ee9,0x25dbaf91,0xaf46a8d5,0x2765afaf,0xa515afaf,0xaf802e1f,
0x2e3f2c32,0xafa02ddc,0xa17e2fff,0x2e3f2515,0xacd8adba,0x2dfe26a1,0x2934afd4,0x244eaf6e,0xa8142ff8,0xadfe2faf,0xaffc230e,0x2e5e217e,
0x2c87af46,0x2f5aa515,0x2f5a2765,0x26a1af80,0xae7c2dba,0x9cb6ae99,0xaddcac5d,0xafc92dba,0x2fafab05,0xaf1a2ee9,0x2b5e2e5e,0x2d002934,
0xaf91a30e,0xacd8a8d5,0x2c07afa0,0xaf302f02,0x2dba2c32,0xac5d2fff,0xae992ddc,0x2dba2515,0xa993aeb5,0x2fc9a9f1,0x2fe6a9f1,0x2aaaafdd,
0xa17e2fed,0xa30eadfe,0xafaf9fd9,0xaff82c07,0x2a4eafed,0x2eb5af91,0x2c5d2d4d,0x1648ae5e,0xae7c2e3f,0xaddca17e,0x9cb6afa0,0xafc92e3f,
0x2ff8a993,0xabb72fe6,0xabb72fc9,0x2b5e2aaa,0xaf30a5db,0x2fbcaa4e,0x2ee9adba,0x2dfeafdd,0x2f1a2515,0x2bb72993,0xaff42aaa,0x2f1aa765,
0xab05adba,0x2e5eafd4,0x2ee926a1,0x2934af6e,0xa5db2fed,0xadba9fd9,0xaa4eadfe,0xafdd2c07,0x2ddcaf02,0xacb02ff8,0xa7652ff8,0x9cb62e3f,
0xac322fdd,0xaf462f6e,0x2993b000,0xae7c2fdd,0x2fafacd8,0x2b5e2934,0xaf1a2dfe,0x2d00244e,0xaf30a17e,0x2ee9afaf,0x2fbca30e,0x2dfeaff8,
0x29f12ddc,0xac5da765,0xac5dacb0,0xad969cb6,0xa993aa4e,0x2765ac87,0xa515ac87,0xaaaa2dba,0xafa02f30,0xabb7244e,0xaff42e5e,0x28d51fd9,
0x28142bb7,0xaf912e1f,0x1fd92d27,0x2ee9ad00,0x2fd4aed0,0xaf5a2fff,0x3000addc,0x2fd4afe6,0x2fafaf46,0x2fa0ae7c,0x2fa0ac32,0xad002993,
0xa44eac5d,0x2f91b000,0x2b05af5a,0xafbc2eb5,0xb0002dfe,0x2c87ae5e,0xae992814,0xaf6e2ffc,0xa5152e1f,0x9cb6a875,0xad722ff4,0xac322e1f,
0x26a12b05,0xa9f12cd8,0xad962fed,0x2fd4affc,0x2fffae1f,0x2515230e,0x2c32230e,0x2ddcaf1a,0x2875ae7c,0x2d27aaaa,0x2fa0af80,0x2875ac32,
0xaee929f1,0x2f91ae99,0x9fd9ac87,0xa8149648,0xafed2f1a,0xaf302e3f,0xa934a875,0xa8142b5e,0xa6a12ddc,0xb0002fc9,0xb0002e7c,0x25db1cb6,
0x2ed0aa4e,0xaf462fd4,0xa9932e99,0x2cb0aa4e,0x2e3faffc,0xad272e5e,0x2e1fa814,0x2f02adfe,0x9fd9abb7,0x2c07ad27,0x2fedae1f,0xadfe2d00,
0xaf6e2cb0,0x25dba993,0x2c5daf46,0xaf6e2ed0,0xaddc2fdd,0xa5159648,0xac329648,0xafff2fd4,0x28d52814,0xabb72934,0xaff42f30,0xafa02fed,
0x3000aee9,0x2e99adfe,0xac872f30,0x2f6eafbc,0x2c32af02,0x2f80af1a,0x2aaa217e,0x2e7caf02,0xab5e9cb6,0x2ff4afc9,0x2ff4ae7c,0x2d27addc,
0xaffc2eb5,0x2fedb000,0x2cd8af5a,0x2b05ac5d,0xa17e2c32,0xad002d72,0xabb71cb6,0xa17e2515,0x2dfea9f1,0xac072c87,0xafed2e99,0x1fd91648,
0x2fd4afbc,0xa9f12b05,0xad962f91,0x26a1a44e,0x2aaaae3f,0xa76528d5,0x251528d5,0x2993a875,0xafe62eb5,0xaddc2dba,0x2fffaf6e,0xaed02eb5,
0xae3f2fbc,0xae1f2dfe,0x2d27af30,0xaf022ee9,0x9fd92b5e,0xae5e2e3f,0xa44ea875,0xaf302f1a,0x2d96a993,0xae992e7c,0xae992c32,0xaf5a2f46,
0x299329f1,0xa76525db,0x251525db,0x2aaa1648,0x28d52934,0xaf02acd8,0x230e244e,0x2fa02dfe,0x28142875,0xaf91aff8,0x1fd9217e,0x2ee92ff4,
0x26a12765,0xaa4eaddc,0x16481cb6,0x26a12cb0,0xaf02af46,0xab5eae7c,0xab5eac32,0xa30e2993,0xae5eaeb5,0x2b059648,0xa934aa4e,0xaee9ac5d,
0xad96adfe,0x2fdd2e5e,0xa5dba814,0xaf5aaffc,0xacb0ad27,0x2ddc2faf,0x9cb6a30e,0xa765ad27,0x2fd42f91,0x2f6e2fed,0x2dba2e5e,0xa6a1ad4d,
0x2fff2ff8,0x25152d00,0x2c322d00,0x2ddc28d5,0x2faf2fe6,0xae1fa993,0x28d52aaa,0x2faf2fc9,0x2ee92f5a,0xaf91afdd,0x1fd925db,0x28142d96,
0xacd8ab5e,0xaf91ad00,0xaf30afaf,0x2c072f1a,0xaeb5addc,0xad96afc9,0xad96ae7c,0xac879cb6,0xafc9af5a,0x2993a6a1,0xaaaaac87,0xafe6af5a,
0xaff4affc,0x2ff82e5e,0xa17ea814,0xa875adfe,0x9fd9a875,0x2c07a17e,0x2fed2ff8,0xadfeaff4,0x29f12515,0x2fdd2f46,0x2eb52f80,0x29f1a765,
0x2ddc2c87,0x25152d96,0x2c322d96,0x2fff2eb5,0x2fa02ee9,0xaf02ab05,0x230e2934,0x28d52e5e,0x2d962ee9,0x25db2dfe,0xafddaf30,0x2f5a2fbc,
0x27652bb7,0xaf46ab5e,0xaf80aff8,0xa5152bb7,0xa8d59cb6,0xad00afc9,0xad00ae7c,0xaff8addc,0xadfeac5d,0x2cd89648,0xa44eaa4e,0xa934aeb5,
0xaff8afc9,0xae3fafff,0x2f022d72,0xaff8ae7c,0xadfeaf5a,0x2c07a5db,0x2fed2fdd,0x9fd9ad96,0xa6a1ac07,0x2f6e2f91,0x2dba2f30,0x2fd42cd8,
0x2aaa230e,0xa7652b5e,0x25152b5e,0x29932f02,0x2e7c2c5d,0x2fff2d96,0xad72a9f1,0x2fc92c5d,0x2ff42fbc,0x217e2dfe,0xaff8af30,0x28752ee9,
0x2d4d2f1a,0xafedad00,0xae5eafaf,0xaf91ab5e,0x96482993,0xa5dbae7c,0xa5dbac32,0xa9f1af46,0xaddc9648,0xafe6a6a1,0xaed0a6a1,0x2fff2a4e,
0xad27affc,0x2d00ac07,0xabb7afbc,0xae1f2934,0x2e5e230e,0x1fd92fa0,0x2f3028d5,0x244eaf02,0x2c872fe6,0xadbaaf46,0x2a4e2f80,0x2c872fc9,
0x230ead72,0x2d27ac32,0x2d27a515,0xafaf9cb6,0x2fbc2e99,0x9fd92f6e,0x2d4d3000,0x2cd8ac87,0xaa4e2b05,0xac5dafbc,0xaeb5a44e,0x96482f91,
0xaed0afa0,0x2f802d00,0xaaaaafaf,0xacb0afa0,0x2c872ffc,0x16482fbc,0xa9f12c07,0x2e99a934,0xaf80a8d5,0xac32afaf,0xae7cafaf,0xaaaa2e1f,
0xa30eaed0,0x2f1a2d72,0x2e1f9cb6,0xa30eafe6,0x2fed2dba,0xaffca6a1,0x2b052fd4,0x2cd82f6e,0xafbcae1f,0xad4daf02,0x1fd9ae3f,0xacd82d27,
0x2c87a993,0x2f5a2cb0,0x2f5a2ed0,0x26a1af46,0x2cb03000,0xafffa5db,0xad7226a1,0x27653000,0xafafa934,0x2f1aa814,0xab5eafed,0xad00af30,
0x2f30230e,0x2fed28d5,0x28142fa0,0x2934af02,0x16482ed0,0xafd41cb6,0xafddad72,0x16482fe6,0xaf46aeb5,0x2ed0a9f1,0x2cb0a9f1,0xa993afdd,
0x2e1fa44e,0xad002d4d,0x2bb72ffc,0x2d272ee9,0xaa4e2cd8,0xaeb52b05,0xac5daffc,0x96482fed,0xacb0aff4,0x2d72ad27,0x2fff2b5e,0xa765aff4,
0x2ff82aaa,0xabb72e7c,0xabb72c32,0x2b5e2f80,0xab052c87,0x2814af6e,0xac07b000,0xad4dae99,0xa8d5afe6,0x2875af80,0x2e3f2f46,0xa8d5afc9,
0x2f912dba,0xa44e2fd4,0xafbca6a1,0x2b052f6e,0xae99244e,0x9648affc,0x29f1ad4d,0xac87aee9,0x1cb6af02,0x25152ff8,0x2c322ff8,0x2d722e3f,
0x2ed02e99,0x2aaa2f5a,0xaf80ad96,0x2cb02e99,0xafafa44e,0xab5eaf30,0x2f1a9fd9,0xad00ae5e,0x2b05ad27,0x2c072f02,0xa8142e3f,0x2d4d2e1f,
0x29f12fff,0xac5daed0,0xac5dafe6,0xad96addc,0xaf46aa4e,0xac32ac87,0xae7cac87,0x29932dba,0x2f1a2b05,0xa8752fed,0x2e3f2cd8,0x2b5eaffc,
0xaee9abb7,0x2f30ae1f,0xadfead27,0xafbc2d00,0x2eb52c32,0xaf6e1cb6,0x2dba2d72,0x2eb52515,0x2fafa993,0x2fa0a515,0x2fa02765,0xad00aaaa,
0xafed26a1,0xa934ad96,0xaf30a9f1,0xa8142fd4,0x30009fd9,0xac872fed,0x2e992c07,0x2f6eadfe,0xafe6a17e,0x2fffabb7,0xaddcad00,0xaed0a17e,
0xac5d2f30,0xaf5a2e5e,0xb000244e,0x2eb51fd9,0x2ddcae1f,0x2e7c230e,0x2fc9230e,0x1cb6af1a,0xaf022cb0,0x217eaf46,0xaf1aa993,0xaf022ed0,
0x2fbca9f1,0xaf302e99,0x2dfe2c87,0x2ee91648,0xa44eafa0,0x2b05aff4,0x2f91abb7,0xafbc28d5,0xa6a12fff,0xb0002c32,0xb0002515,0x25db2ddc,
0x2c32af6e,0x2aaa2c5d,0x2f8025db,0x2e7caf6e,0xae3f2dfe,0x2d27afed,0xae1fac07,0xaf021fd9,0x2dfe2bb7,0x28142d27,0xae5e2e1f,0x2ffcad00,
0xaa4eae7c,0x2e99af80,0x2fd4aaaa,0xaa4eac32,0x9cb62fdd,0xae7c9648,0xafc99648,0xaddc2fd4,0x2b5eafbc,0xa8752f91,0x2e3f2b05,0x2f1aa44e,
0xb0002814,0xae991fd9,0x2c87af91,0xaf6e2ee9,0x2ed02875,0xa9932fa0,0xaf462d27,0x2cb02875,0xab5eaddc,0x2ff4ac32,0x2ff4a515,0x2d27afff,
0x9fd92fd4,0xa44ead96,0xae5ea9f1,0xaf3026a1,0x2e1faed0,0x2ff4addc,0xa8752fff,0x2e1fafe6,0xaffc29f1,0xa814ac87,0x2e5eae99,0xadfe9648,
0x2eb52814,0xaf5a2f30,0xb0002934,0xac5d2fed,0xa993ae3f,0x2c3228d5,0x2e7c28d5,0x2f46a875,0xa5152fd4,0xad723000,0x9cb6af5a,0xac322fd4,
0x2e3faee9,0x2e1f9fd9,0xad272f91,0x2f02a814,0xaffc28d5,0x2cd8aff4,0x2fedabb7,0x2b05afa0,0x2d962aaa,0xae992515,0xae99a765,0xaf5a2993,
0x1cb6adba,0x2cb0aeb5,0x2765aeb5,0xaddc2f6e,0xaff82d4d,0xa30ea814,0xafaf2c07,0xa17e2b05,0xa44e2e3f,0xadfe2b5e,0xa9342f1a,0x2cd8a875,
0x2fddacb0,0xb0002f80,0x2f6eaaaa,0x2fddaed0,0x2d001cb6,0x217e2765,0x217e2cb0,0x2bb7addc,0x2ee9afdd,0x2d4daa4e,0x2ffcadba,0xa44ea5db,
0xa9f1a934,0x2fd4aee9,0x26a1ae5e,0xad962b05,0xafc92f1a,0x2f46aff4,0xaf802bb7,0xafe62f1a,0xafdd2d4d,0xadba2c07,0xaa4ea814,0xa5db2b05,
0xaaaa2f1a,0xafc92f02,0xafe62f02,0x2993a17e,0x2e3fa765,0xafa02fff,0xa17e2d72,0x2e3facb0,0x2e5eb000,0xad4d2eb5,0x2f91ac5d,0x2fedaf5a,
0x2ee9aff8,0x2ffcafaf,0x2d4da30e,0xa44ea17e,0xa5dbaaaa,0x2f6eafe6,0x2f6eafc9,0xac5d2993,0xafe62dba,0x2d72ae99,0x9cb6ac5d,0xaed02dba,
0xabb72f30,0x28d5ac07,0xafa02cd8,0xaff42f91,0xa9342e3f,0xae5e2f1a,0xaee92b5e,0x2b05a875,0x2dbaa765,0xac5d2d72,0xae992fff,0x2dbaacb0,
0x2f80afd4,0xa7652a4e,0x25152a4e,0x2f46ae99,0x217eacd8,0x230e1fd9,0x2fafad4d,0x2ff8afbc,0xa9f1a44e,0x26a1a934,0x2fd4adfe,0xad962cd8,
0xafe62e3f,0x9cb6a17e,0x2d72afa0,0xaed02e3f,0xad272f80,0xa8752515,0xa875a765,0xafa02f46,0x293425db,0xac072a4e,0xafbc2dba,0xaffc2fdd,
0x2f1aacb0,0x2bb7aaaa,0xaff42f80,0x2f1aaed0,0x2f30b000,0x2cd8ac5d,0xac072eb5,0x2f91af5a,0x25dbacd8,0x2dbaad4d,0x2a4e1fd9,0x2fddafbc,
0xad722875,0x2e7cae1f,0x2fc9ae1f,0x2fffaff4,0xafc92fdd,0xaf802f6e,0x2f46b000,0xafe62fdd,0xabb72e5e,0xafa02f91,0x28d5ad4d,0xaff42fed,
0x2934217e,0xafbc2faf,0xac07230e,0xaffc2ff8,0x2f5aad72,0xafd42fc9,0xafd42e7c,0xb0002fff,0x9cb69648,0xacb0a6a1,0xa765a6a1,0x2ddc2a4e,
0xa17e9fd9,0xaff4aee9,0xa875a814,0x2ff82f91,0xa44ea30e,0xadfeafa0,0xa934a8d5,0x2cd82f02,0xa5dba515,0x9648aaaa,0xa9f1a993,0xa5db2765,
0xa30e9cb6,0xad27a765,0xad27acb0,0x2faf2ddc,0xa814a5db,0xaffcaf5a,0xadfead96,0x2e5e2fdd,0xaa4ea934,0xac5daee9,0xaeb5ae5e,0x96482b05,
0xac32ab5e,0x2993a30e,0xaf46af02,0xae7cab5e,0xa5db9fd9,0xad96a814,0xaf5aaee9,0x2fdd2f91,0xaaaaa8d5,0xafc9afaf,0xafe6afaf,0x29932e1f,
0xad00ac32,0xa8d5addc,0xaff8afff,0xad00a515,0xae5eadba,0x2d4d26a1,0xaf91afd4,0xafedaf6e,0xa814a17e,0xadfea875,0xaffcaff4,0x2e5e2ff8,
0xac87aaaa,0xaf5aafe6,0xaf5aafc9,0xa6a12993,0xae7cad96,0x9cb6ac87,0xaddcaeb5,0xafc9ad96,0xafafaf30,0x2f1a2c07,0xab5eacd8,0xad00af91,
0xa934a30e,0xae5ea8d5,0xaee9afa0,0x2b052f02,0xad96ac32,0xaeb5afff,0xac87addc,0xad96a515,0xaf80aeb5,0x2765a9f1,0xa515a9f1,0xaf46afdd,
0xaff8afed,0x2ff42dfe,0x28751fd9,0x217eac07,0xaa4ea44e,0xaeb5a934,0xac5dadfe,0x96482cd8,0xae7cad00,0xaddcaff8,0x9cb6a8d5,0xafc9ad00,
0xaff8af80,0x2bb7a515,0x2bb72765,0xab5eaf46,0xaf30afdd,0x2fbc2f5a,0x2ee92d96,0x2dfe25db,0xab5ea515,0xaf02a993,0xa30eaaaa,0xab5e2765,
0xaf30adba,0xacd8afd4,0x2c0726a1,0xaf91af6e,0xafddafed,0x2d961fd9,0x2f5a2dfe,0x25dbac07,0xad72af02,0x2e7c2ff8,0x2fc92ff8,0x2fff2e3f,
0xac32a5db,0xaf46a9f1,0x29939648,0xae7ca5db,0xafafae5e,0xab5eaf91,0x2f1a2d4d,0xad00afed,0xaf30aff8,0x2ee92875,0x2fbc2ff4,0x2dfe217e,
0xa9f1ad72,0x2c5d2fc9,0x2c5d2e7c,0x2d962fff,0xaf80aa4e,0xafc9ac87,0xafe6ac87,0x2f462dba,0xa8d5af30,0x2f02a44e,0xa30eae5e,0xafa09fd9,
0x2fbc2bb7,0xa9342e1f,0x2ffc2d27,0x2c07ad00,0x26a12ed0,0xaa4eafff,0x16482ddc,0x26a12fe6,0xafafaaaa,0xafa0acb0,0xafa0aed0,0x2d002f80,
0xa44eaeb5,0x2f919648,0x2b05aa4e,0xafbcac5d,0x30002d4d,0xac872cd8,0x2e992fbc,0x2f6e9fd9,0xa5152d27,0x9cb6afaf,0xad72230e,0xac322d27,
0xafd4ab05,0xaf6eacd8,0xadbaafed,0x26a12ffc,0x1cb6ae1f,0x2fe6230e,0x2ed0230e,0xad72af1a,0x2faf2e7c,0xae1f2aaa,0x28d52f80,0x2faf2c32,
0xac0729f1,0x2934ae99,0xaffcac87,0xafbc9648,0xafedab5e,0xaf30ad00,0xa934afaf,0xa8142f1a,0x26a1ad72,0x30002765,0x30002cb0,0xa5dbafff,
0x2ed02f5a,0xaf4626a1,0xa9932c87,0x2cb02f5a,0xae3f1fd9,0x2d27acd8,0xae1fafbc,0xaf02ad4d,0xaffcabb7,0xaee9ad27,0x244eae1f,0xad4d2d00,
0x29f1acb0,0x2fdd2993,0x2eb52f46,0x29f1aed0,0x2d722fdd,0xafe69648,0xaed09648,0x9cb62fd4,0xafa0a814,0x2f02a934,0xa30eaf30,0xa8d5afed,
0xb000ac07,0xae99ad4d,0x2c87ab05,0xaf6e2814,0x2c32abb7,0x2f802b5e,0x2aaa2ff8,0x2e7cabb7,0x2b5e2fff,0xaff4a765,0xaff4acb0,0xad272d72,
0xaffcac5d,0x2fed9648,0x2cd8aa4e,0x2b05aeb5,0xaff8ac32,0xae3fad72,0x2f029cb6,0xaff8a515,0x2d4da9f1,0x2ee92c87,0xa44e2e99,0x2ffc1648,
0x26a12fbc,0xaf6eab05,0xadbaaf91,0xafd4244e,0xaf46ae3f,0x2fc928d5,0x2fe628d5,0x2f80a875,0xafe6ac5d,0xaddcad96,0x2fff29f1,0xaed0ac5d,
0x2e3fa814,0x2e1f2d4d,0xad272b05,0x2f022c07,0x9fd92f1a,0xae5ead00,0xa44eafaf,0xaf30ab5e,0xad96af80,0x2e992cb0,0x2e992ed0,0x2f5a2aaa,
0xad72adba,0xa515aeb5,0xac32aeb5,0x9cb62f6e,0x2d272dfe,0xad002fbc,0x2bb72ee9,0x2e1faf30,0xacd8ae3f,0x2ffcab5e,0xab05af1a,0xafed2875,
0x2c872e7c,0xadbaa993,0x2a4e2f46,0x2c872c32,0xad00addc,0xa17eaed0,0xa17eafe6,0xabb72fff,0x2c072e99,0xadfe2f6e,0x9fd93000,0x2fedac87,
0xa9f1af30,0x2fd4a814,0x26a1afed,0xad96a934,0x27652fa0,0xaaaaad00,0xa9932faf,0xa5152fa0,0xac87adfe,0x9648aee9,0x29f1afbc,0xae992f30,
0x29932f1a,0xaed02f02,0xacb02f02,0x2f46a17e,0xa30eafc9,0x2f1a9cb6,0x2e1faddc,0xa30eae7c,0xa44e3000,0x9fd9aeb5,0xaf302c5d,0xae5e2f5a,
0xac07ae1f,0x1fd9af02,0x2dfeae3f,0xafed2d27,0x25db2f80,0xaf6e2e7c,0xaf6e2c32,0x2c5d2aaa,0x2515b000,0x2ddc25db,0x2fffa6a1,0x2c32b000,
0xabb72f91,0x28d5afbc,0xafa0a44e,0xaff42b05,0xab05ae3f,0x244eaf1a,0x2fbcab5e,0xaf912875,0x16482fc9,0xafd42ddc,0xafdd1cb6,0x16482e7c,
0x2aaaafd4,0x2c322a4e,0x2e7c2a4e,0x2f80ae99,0xae1f2e5e,0x2d00affc,0xabb7adfe,0xad27a814,0xa9f1ae5e,0x26a1af30,0x2fd49fd9,0xad96a44e,
0xa5152ff4,0xafff2d27,0xaddcab5e,0xac322ff4,0x2d27af46,0x28752cb0,0x28752ed0,0x2fa0a993,0xaf912c87,0x2ee9af6e,0x2814b000,0x1fd9ae99,
0xa8d5ae7c,0x2875af46,0x2e3f2993,0xa8d5ac32,0xa9343000,0xafed2c5d,0xa814aeb5,0xaf302f5a,0x2e99ae5e,0x16482dfe,0xa9f12ffc,0x2c872814,
0xafff2875,0x2fe6ae1f,0x2ed0ae1f,0x2ddcaff4,0xa765ae99,0x2993af5a,0x2aaa2d96,0x2515ae99,0xabb72fed,0xafa02b05,0x28d5affc,0xaff42cd8,
0x2f91ad27,0xa8142f02,0xaee92e3f,0x9fd92e1f,0xaf5a9cb6,0x2fd4ac32,0x2fd4a515,0x3000ad72,0x2aaaaf6e,0x2ed0afdd,0x2cb0afdd,0xaf803000,
0xaf1a2934,0x2875acd8,0xae3f244e,0xab5e2dfe,0xac072faf,0xab05217e,0xad4d2ff8,0x2814230e,0x2eb5a765,0xaf6e2ddc,0x2dba9cb6,0x2eb5acb0,
0x2bb7af80,0x2f1aafe6,0x2f1aafc9,0xaff42f46,0xae5e26a1,0x2b05ad96,0xa934a9f1,0xaee92fd4,0xadba2ffc,0xa5dba44e,0xafdd2ee9,0xaa4e2d4d,
0x2cb0217e,0xaddc2bb7,0x1cb62d00,0x2765217e,0x2c5daf91,0x2f5aafed,0x3000ae5e,0xaeb52d4d,0xad72217e,0x2cb0ae3f,0x2765ae3f,0xafff2fa0,
0xaf022fe6,0x217ea993,0xaf1a2aaa,0xaf022fc9,0x28142a4e,0xab0525db,0xad4d2fdd,0xac072dba,0x2cd8afa0,0x2f91aff4,0x2f30abb7,0xac0728d5,
0xac5d9cb6,0x2dbaaed0,0x2dbaafe6,0xae992d72,0xafc92f6e,0x2993ac5d,0xaaaaa5db,0xafe62f6e,0xa30e2d4d,0xa17ea44e,0xaff82ee9,0xafaf2ffc,
0x2d4dafaf,0x2fbcaff8,0x2cd8a17e,0x9fd9a30e,0xaa4ea515,0x2e99af46,0x2fd4af80,0xaa4e2765,0xafff2e99,0x2cb0adba,0x2765adba,0xad722c5d,
0xab5e2ee9,0x2875ab05,0xae3f2934,0xaf1a2e5e,0x2dbaafbc,0x2fddaffc,0x25db2934,0x2a4eac07,0xa765a875,0x2f46afa0,0x2f80ad27,0x2515a875,
0xafa02d72,0x2e3faed0,0x2e3fafe6,0xa17e9cb6,0xadfe2fd4,0x2cd8ad96,0xa44ea9f1,0xa93426a1,0x2e1fafc9,0x2ff4afff,0xa8752d72,0x2e1fae7c,
0x9fd9aa4e,0x2fbcafdd,0x2cd8a5db,0x2d4dadba,0xaeb52c07,0x2f5aaf91,0x3000af30,0x2c5dacd8,0xaf802ff4,0x2ed0af1a,0x2cb0af1a,0x2aaaabb7,
0x2e7cafd4,0x2fffb000,0xad722f5a,0x2fc9afd4,0x230eac07,0x2ff8affc,0x217e2934,0x2fafafbc,0xad4d28d5,0x2fedaff4,0x2e5eabb7,0x2f91afa0,
0xb0002f46,0x2fddafe6,0x2fddafc9,0x2f6eaf80,0xaaaaaa4e,0xaed0ac87,0xacb0ac87,0x2f802dba,0xab5eab05,0xafafafed,0xad00acd8,0x2f1a2ffc,
0xac07abb7,0xab05ae1f,0xad4dad27,0x28142d00,0xac5dac32,0x29f19cb6,0xad96ad72,0xac5da515,0xafafaf80,0xafa0afe6,0xafa0afc9,0x2d002f46,
0xafedafd4,0xa934adba,0xaf30af6e,0xa81426a1,0xb000affc,0x2c87244e,0xae99aee9,0xaf6ead4d,0xafe6aff8,0x2fff2f02,0xaddcae3f,0xaed0aff8,
0xaeb5af30,0xaa4eae5e,0x9648a44e,0xac5d9fd9,0xad72ae1f,0x2cb0230e,0x2765230e,0xafffaf1a,0xabb7acb0,0x2ff82f46,0x2b5e2993,0xabb7aed0,
0xa814a9f1,0x2b052e99,0x2d4d2c87,0x2c071648,0xa44ea8d5,0x2b05a30e,0x2f912f02,0xafbcafa0,0x26a11cb6,0x30002ed0,0x30002fe6,0xa5dbad72,
0x2c3229f1,0x2aaa2eb5,0x2f802fdd,0x2e7c29f1,0x2e3f2d4d,0xad27a44e,0x2e1f2ee9,0x2f022ffc,0x2d4d2bb7,0x2fbc2d27,0x2cd82e1f,0x9fd9ad00,
0x2f5a2e7c,0x2c872f80,0x26a12aaa,0x2f5a2c32,0x2fff2fdd,0xacb09648,0xa7659648,0x2d722fd4,0x2f1a2fbc,0xafafaf91,0xad00ab05,0xab5e244e,
0x30002fbc,0x2e992ffc,0xac87a934,0x2f6e2c07,0x2ed02faf,0xa99328d5,0xaf46ae1f,0x2cb02faf,0x2b5e2d72,0xaff4aed0,0xaff4afe6,0xad279cb6,
0x9fd926a1,0xa44eadba,0xae5eaf6e,0xaf30afd4,0x2d272ed0,0x230e2ddc,0xafafafff,0x2d272fe6,0x1fd929f1,0xafbcac87,0xacd8ae99,0xad4d9648,
0xac5da814,0xaa4eaf30,0x9648a934,0xaeb5afed,0xaf80ae3f,0x2ed028d5,0x2cb028d5,0x2aaaa875,0xa51526a1,0xad721648,0x9cb6aa4e,0xac3226a1,
0xae3fac07,0xae1faffc,0x2d272934,0xaf02afbc,0xaffcafa0,0x2cd8a30e,0x2fed2f02,0x2b05a8d5,0xad96af46,0x2e992fe6,0x2e992fc9,0x2f5a2f80,
0xafffadba,0xae7caeb5,0xafc9aeb5,0x2d722f6e,0x217ead4d,0x2ff42814,0x2875ac07,0xaff8ab05,0x2fed2e3f,0xad4d2b5e,0x2f912f1a,0x2e5ea875,
0xa5db2cb0,0x9648af80,0xa9f12aaa,0xa5db2ed0,0xad00afff,0xa17eafc9,0xa17eae7c,0xabb72d72,0x2ee925db,0x2d4d2f5a,0x2ffc2d96,0xa44eafdd,
0x29f12f91,0xafd4ac07,0xa6a12cd8,0x2d962f30,0xafc9ab5e,0x2f46a30e,0xaf80af02,0xafe6ab5e,0x25dbad4d,0x2d96ac07,0x2f5a2814,0xafddab05,
0x2f462f1a,0xa7652f02,0x25152f02,0x2f80a17e,0xad002765,0xa8d5afff,0xaff8ad72,0xad002cb0,0xacd8b000,0x2dfe2eb5,0x2934ac5d,0x244eaf5a,
0x2ee9217e,0x2ffc2875,0x2d4d2ff4,0xa44eaff8,0x25db2f46,0xaf6e2515,0xaf6ea765,0x2c5d2f80,0xafe6ad96,0x2d72ac87,0x9cb6aeb5,0xaed0ad96,
0x2bb7ab05,0xa8d52ee9,0x2fa02e5e,0x2ff42934,0x2f912e3f,0x2cd82f1a,0xac072b5e,0x2f30a875,0xad962765,0xaeb5ad72,0xac87afff,0xad962cb0,
0xa993afd4,0x2fc92a4e,0x2fe62a4e,0x2aaaae99,0x2ff82cd8,0xaff49fd9,0xa8752d4d,0xa17e2fbc,0x29f12fed,0xa6a12f91,0xafd4ad4d,0x2d962e5e,
0xafe6ad00,0x9cb6aff8,0x2d72a8d5,0xaed0ad00,0x2d27a993,0x28752fe6,0x28752fc9,0x2fa02aaa,0x29342fdd,0xac07af5a,0xafbcad96,0xaffca5db,
0xab5e2cb0,0xaf022aaa,0xa30eaf80,0xab5e2ed0,0xab05b000,0x2e5eac5d,0x2ee92eb5,0x2934af5a,0x2fdd2cd8,0xad962d4d,0xaf5a9fd9,0xa5db2fbc,
0xaddc2875,0x2cb0ae1f,0x2765ae1f,0x1cb6aff4,0xafc9a5db,0xaf80a9f1,0x2f469648,0xafe6a5db,0x2bb7acd8,0x2fa02934,0xa8d52dfe,0x2ff4244e,
0x29342ff8,0xafbca875,0xac07aff4,0xaffca17e,0xaf5aaddc,0x2fd42765,0x2fd42cb0,0x30001cb6,0xa993af6e,0x2765afdd,0xa515afdd,0xaaaa3000,
0x28d52f91,0xaf022e5e,0x230e2fed,0x2fa0ad4d,0xa814afaf,0x2f91a17e,0x9fd9aff8,0xaee9a30e,0x26a12fc9,0xaa4ead72,0x16482fff,0x26a12e7c,
0x2bb7af46,0x2f1aae7c,0x2f1aac32,0xaff42993,0xacd82eb5,0xaf301648,0xaf912a4e,0x2c072c5d,0x2dbaadfe,0x25db2e5e,0x2fdda814,0x2a4eaffc,
0xae7c2d27,0x2d72afaf,0xafff230e,0xafc92d27,0x2fd4a934,0x2f6ea44e,0x2dba2cd8,0xa6a1adfe,0xafff217e,0xa515ae3f,0xac32ae3f,0xaddc2fa0,
0x2faf2515,0xae1f2f80,0x28d52f46,0x2fafa765,0xaee9aa4e,0x2f91a5db,0x9fd9afdd,0xa814adba,0x2e5e2b5e,0x29342d00,0xab052faf,0x2ee9af1a,
0xac5daddc,0x2dbaafc9,0x2dbaae7c,0xae999cb6,0x27652f5a,0xaf8026a1,0xaf462c87,0xa5152f5a,0x230eaffc,0x217e2e5e,0x2ff8a814,0x2fafadfe,
0x1fd92faf,0xac072ff8,0xafed217e,0x2dfe230e,0x29f1afe6,0x2fddaaaa,0x2eb52993,0x29f1afc9,0xaddc2e99,0xa515adba,0xac32adba,0xafff2c5d,
0x2fa0ac07,0xaf022f30,0x230e2f91,0x28d52cd8,0xadba2ee9,0xafdd2dfe,0xa5dbaf30,0xaa4e2fbc,0x2fc9abb7,0x2aaa2b5e,0xa9932ff8,0x2fe6abb7,
0xafa09cb6,0x2e3fafc9,0x2e3fae7c,0xa17eaddc,0x2d4d2c5d,0xae5e1648,0xafed2a4e,0xaf912eb5,0xaff82765,0xae3f1cb6,0x2f02addc,0xaff82cb0,
0x2dfe2a4e,0xac072fdd,0xafed25db,0x1fd92dba,0xa6a1aee9,0x2f6ea934,0x2dba2b05,0x2fd4ae5e,0xaaaa2ff4,0x2765af1a,0xa515af1a,0xa993abb7,
0xacb0ac5d,0x9cb6ad96,0x2ddc29f1,0xa765ac5d,0xa30e2fbc,0xaff82dfe,0xa17eaf30,0xafaf2ee9,0x2dfeaf1a,0x244e2d00,0xacd82faf,0x29342b5e,
0xb0002993,0x2fddae7c,0x2fddac32,0x2f6eaf46,0x2ddcb000,0x2fe6afd4,0x2ed0afd4,0xafff2f5a,0xad279fd9,0x2d00aee9,0xabb7a814,0xae1f2f91,
0xae5e2ff4,0x9fd9a8d5,0xaf302fa0,0xa44e2bb7,0x2c872515,0xadba2aaa,0x2a4e2993,0x2c87a765,0x2ff4ad72,0x2e1fac32,0x2e1fa515,0xa8759cb6,
0x2814ae99,0x2ffcaf6e,0x2dfeb000,0xae5e2c87,0xaf5a2b05,0x2eb5afbc,0xac5da44e,0xb0002f91,0xac322fa0,0x2993ad00,0xaf462faf,0xae7c2fa0,
0x2c871fd9,0x16482814,0xa9f12ee9,0x2e99af91,0x2f80afa0,0x2c32a875,0x2e7ca875,0x2aaaad27,0xa30eac32,0x2f1aaddc,0x2e1fafff,0xa30ea515,
0xafed2d96,0x2ffcafd4,0xab05a6a1,0xacd829f1,0xa8142e1f,0xadfe2f02,0xaffc2e3f,0x2e5ead27,0x2e99a993,0xaa4e2cb0,0xaa4e2ed0,0x2fd4af46,
0x2e7cb000,0x1cb625db,0x2ddca6a1,0x2fc9b000,0xa875a934,0x2b5ea814,0x2f1aafed,0x2e3faf30,0xaf302ff4,0xafed2fa0,0xa814a8d5,0xa9342bb7,
0x16482c32,0xafd42fff,0xafdd2ddc,0x16482515,0x2f46ac5d,0xaed02f6e,0xacb02f6e,0x2993a5db,0x2e1fafed,0xad002dfe,0x2bb71fd9,0x2d27ac07,
0xaf5a2cd8,0xac5d2b05,0x2eb5affc,0xb0002fed,0xae7c2ff4,0xaddc2d27,0x9cb6ab5e,0xafc92ff4,0x217e2aaa,0xaf022e7c,0xaf022c32,0xaf1a2f80,
0x2f30ac87,0xafbc2f6e,0xaee93000,0xadfe2e99,0xa8d5a515,0x2875a993,0x2e3faaaa,0xa8d52765,0xaf912d96,0x244ea6a1,0x2fbcafd4,0xab0529f1,
0xae992fed,0x96489fd9,0x29f1adfe,0xac872c07,0x9cb62bb7,0xa515217e,0xac32217e,0xad722d00,0x2c32ae99,0x2f46af5a,0xa9932d96,0x2e7cae99,
0xa875a44e,0x2f1aaf30,0x2b5e9fd9,0x2e3fae5e,0xaf302d27,0x2ee9af02,0x2fbcae3f,0x2dfeae1f,0xaf6e2fff,0x2eb5aed0,0x2eb5afe6,0x2dbaaddc,
0xaddcadba,0xafe6aeb5,0xaed0aeb5,0x2fff2f6e,0xae1fadfe,0xae3fafbc,0xaf02aee9,0x2d272f30,0xae5eae3f,0x9fd9ab5e,0xaf30af1a,0xa44e2875,
0xae99ae7c,0x2d962993,0xaf5aaf46,0xae99ac32,0xad00ad72,0xa17eac32,0xa17ea515,0xabb79cb6,0xac07ac87,0x2dfe29f1,0x1fd99648,0xafedae99,
0xa9f1ab05,0x2fd42fbc,0x26a1244e,0xad96af91,0xa765a8d5,0x2aaa2e3f,0x29932875,0x2515a8d5,0x2e992dfe,0x30002ee9,0x2f6e2fbc,0xac87af30,
0x2f802f1a,0x2c322f02,0x2e7c2f02,0x2aaaa17e,0x2ff42fc9,0xab5e1cb6,0x2d272ddc,0x2ff42e7c,0x2fed3000,0xaffcaeb5,0x2b052c5d,0x2cd82f5a,
0x2c072d27,0x9fd92bb7,0xadfead00,0x2fed2e1f,0x25db2993,0xaf6eacb0,0xaf6eaed0,0x2c5d2f46,0xa5151648,0xaddcafdd,0xafffafd4,0xac321648,
0xabb7a934,0x28d5a814,0xafa0afed,0xaff4af30,0xaf30ae3f,0xafedaf1a,0xa814ab5e,0xa9342875,0xb000afc9,0xa6a1addc,0x25db9cb6,0xb000ae7c,
0xaf46afd4,0x2ed02a4e,0x2cb02a4e,0xa993ae99,0xad27ae5e,0x2e3f2ffc,0x2f022dfe,0x2e1f2814,0xa9f1acd8,0x26a1ab05,0x2fd42ffc,0xad96afed,
0x2515a30e,0x2fff2e1f,0x2ddc2f1a,0x2c32a30e,0x2d272aaa,0x28752e7c,0x28752c32,0x2fa02f80,0x2f912e99,0xaee9a9f1,0xa8141648,0x9fd92c87,
0x2fa02e7c,0x2faf2f46,0xad00a993,0x2fa02c32,0x2f913000,0xa44e2c5d,0xafbcaeb5,0x2b052f5a,0x2c872e5e,0xb000adfe,0xaf6eaffc,0xae99a814,
0x9cb62875,0xa515ae1f,0xac32ae1f,0xad72aff4,0x27652c87,0xa9932a4e,0xaaaaadba,0xa5152c87,0xabb7a44e,0xafa0af30,0x28d59fd9,0xaff4ae5e,
0xaf91ae1f,0x2814abb7,0x2ee92d00,0x1fd9ad27,0xaf5aafff,0x2fd42ed0,0x2fd42fe6,0x30002ddc,0xaf46af6e,0xac32afdd,0xae7cafdd,0x29933000,
0x2b5ea934,0x2faf2cd8,0x2d00a44e,0xaf1aadfe,0x2ee92faf,0xaf30217e,0x2dfe2ff8,0x2fbc230e,0xac5d2765,0x29f1addc,0xad961cb6,0xac5d2cb0,
0x2bb7a993,0x2f1aa515,0x2f1a2765,0xaff4aaaa,0x2e5e2fd4,0xab052dba,0x29342f6e,0x2ee9a6a1,0xadba1fd9,0xa5dbafed,0xafddac07,0xaa4e2dfe,
0xacb0aff8,0x2ddc2f02,0x9cb6ae3f,0xa765aff8,0x2eb52f91,0x2a4e2fed,0x16482e5e,0x2c5dad4d,0xaddc217e,0xae7cae3f,0xafc9ae3f,0x9cb62fa0,
0xabb7afe6,0x2ff82993,0x2b5eaaaa,0xabb7afc9,0x2fbc2a4e,0xaf3025db,0x2dfe2fdd,0x2ee92dba,0xacd828d5,0xaf91230e,0xaf30af02,0x2c072fa0,
0xac5dafff,0x2dbaac32,0x2dbaa515,0xae99addc,0x2fc929f1,0xa9932eb5,0x2aaa2fdd,0x2fe629f1,0xa30e2dfe,0xa17eafed,0xaff8ac07,0xafaf1fd9,
0xadfeafaf,0xa814aff8,0x2e5ea17e,0xaffca30e,0x2f5a2515,0x2c872f46,0x26a12f80,0x2f5aa765,0x9cb62e99,0xae7cadba,0xafc9adba,0xaddc2c5d,
0xaf1aaee9,0x2faf2b05,0x2d00a934,0x2b5eae5e,0x2dbaa814,0x2fdd9fd9,0x25db2f91,0x2a4eaee9,0x27652faf,0xaf4628d5,0xaf80ae1f,0xa5152faf,
0xafa0addc,0x2e3fac32,0x2e3fa515,0xa17eafff,0x2dfea6a1,0xacd82dba,0x244e2f6e,0x29342fd4,0x2d272fc9,0x230e2fff,0xafafad72,0x2d272e7c,
0xaffcaa4e,0xa814afdd,0x2e5ea5db,0xadfeadba,0x2c5dac07,0x2a4e2f91,0x16482f30,0x2eb52cd8,0x29932ff4,0xac32af1a,0xae7caf1a,0xaf46abb7,
0xae7c26a1,0xafff1648,0x2d72aa4e,0xafc926a1,0x230eaee9,0x2ff89fd9,0x217e2f91,0x2fafa814,0x2d4d2fa0,0xafed230e,0xae5eaf02,0xaf9128d5,
0xb000aaaa,0x2fdda515,0x2fdd2765,0x2f6ea993,0x1cb6b000,0x2cb0afd4,0x2765afd4,0xaddc2f5a,0xa17e2ffc,0xaff42c07,0xa8752fbc,0x2ff8a934,
0x244eaff4,0x2dfe28d5,0x2934afa0,0xacd8abb7,0xa5db2fe6,0x9648af46,0xa9f12f80,0xa5db2fc9,0x2ff41cb6,0x2e1f2765,0x2e1f2cb0,0xa875addc,
0xafbca5db,0x1fd9af5a,0xad4dad96,0xacd82fdd,0x2f5a2934,0xaeb52ee9,0x2c5d2e5e,0x3000ab05,0xaed0ab5e,0x2f80a30e,0xaaaaaf02,0xacb0ab5e,
0xa5db2ffc,0xad962fbc,0xaf5a2c07,0x2fdda934,0x2aaaafa0,0x2fc9a875,0x2fe6a875,0xa993ad27,0xad002ed0,0xa8d5ad72,0xaff81cb6,0xad002fe6,
0x2e5ead96,0xad4d2fd4,0x2f9126a1,0x2feda9f1,0xafbca17e,0xad4da875,0x1fd9aff4,0xacd82ff8,0x2e992aaa,0xaa4e2fe6,0xaa4e2fc9,0x2fd4a993,
0xacb0ad96,0x2fffac87,0x2d72aeb5,0xa765ad96,0x28752f30,0xab5eac07,0xaf1a2cd8,0xae3f2f91,0x2934aff4,0x2e5eafa0,0x2ee928d5,0xab05abb7,
0xad962ed0,0xaeb51cb6,0xac87ad72,0xad962fe6,0x2f80ac5d,0xa7652f6e,0x25152f6e,0x2f46a5db,0xaff8244e,0x2ff4ad4d,0x2875affc,0x217eaee9,
0x2f5a244e,0x2c5d2934,0xaeb52dfe,0x3000acd8,0xacb0ad00,0x2d72aff8,0x2fffa8d5,0xa765ad00,0x217e2f80,0xaf022515,0xaf02a765,0xaf1a2f46,
0x2b05afdd,0xa8142f5a,0x2c072d96,0x2d4d25db,0xab5e2fe6,0xaf022f80,0xa30eaf46,0xab5e2fc9,0x2f30ad96,0x2cd826a1,0xac072fd4,0x2f91a9f1,
0xafdd244e,0x2d96affc,0x2f5aad4d,0x25dbaee9,0x2d722bb7,0xae7c217e,0xafc9217e,0xafff2d00,0xaed0a5db,0xaaaaa9f1,0x2f809648,0xacb0a5db,
0x28752e5e,0xaf1a2f91,0xab5ead4d,0xae3f2fed,0x2b05aff8,0x2c072875,0xa8142ff4,0x2d4d217e,0xaf6e2d72,0x2eb5afc9,0x2eb5ae7c,0x2dbaafff,
0x2f80af5a,0x2fc9ae99,0x2fe6ae99,0xaf462d96,0xa8d5ab05,0x2f02afed,0xa30eacd8,0xafa02ffc,0xafbc2f02,0x2934ad27,0xaffc2e1f,0xac072e3f,
0x26a12c32,0xaa4e1cb6,0x16482d72,0x26a12515,0x28752aaa,0xa8d52cb0,0xa8d52ed0,0x2e3faf80,0x2fedaeb5,0x29349648,0x2f30aa4e,0x2814ac5d,
0x1648ad4d,0x2e99acd8,0x2c87afbc,0xa9f11fd9,0xafe62d27,0x2fffafaf,0xaddc230e,0xaed02d27,0xafd42f30,0xaf6e2e5e,0xadba244e,0x26a11fd9,
0x9cb62d27,0xafe62ff4,0xaed02ff4,0x2d72ab5e,0x2fafacb0,0xae1f2f46,0x28d52993,0x2fafaed0,0x2c07af6e,0xa9342c87,0x2ffcae99,0x2fbcb000,
0xa44eab5e,0x2b05ad00,0x2f91afaf,0xafbc2f1a,0xafd42d72,0x1648a765,0x1648acb0,0xafdd2fff,0xac322f5a,0xaaaa26a1,0xaf802c87,0xae7c2f5a,
0x2d009fd9,0xae1f2cd8,0xad272fbc,0xabb72d4d,0x2ffcaf02,0x2ee9ae1f,0xa44e2d27,0x2d4dae3f,0x29f1ae7c,0x2fddaf80,0x2eb5aaaa,0x29f1ac32,
0xad7225db,0x2fe6b000,0x2ed0b000,0x1cb6a6a1,0xafa02fbc,0x2f02af91,0xa30eab05,0xa8d5244e,0x96482c07,0xac872d4d,0xae992b05,0x29f1a814,
0x2ed0abb7,0xa9932b5e,0xaf462ff8,0x2cb0abb7,0x2f1aafff,0xa30e2765,0xa30e2cb0,0x2e1fad72,0x1fd9ac5d,0x244e9648,0x2e5eaa4e,0x2f30aeb5,
0xaff82ed0,0xae3f2ddc,0x2f02afff,0xaff82fe6,0xad4d2f6e,0xaee92e99,0x244eac87,0xaffc3000,0x26a12814,0xaf6e2f30,0xadba2934,0xafd42fed,
0x2f46ad00,0xafc92fa0,0xafe62fa0,0xaf802faf,0x2515ac5d,0x2d72ad96,0x1cb629f1,0x2c32ac5d,0xad002814,0x2d27ad4d,0x2e1fab05,0x2bb7ac07,
0xaffc2f1a,0x2cd8ad00,0x2fedafaf,0x2b05ab5e,0xadba2f80,0x2c87acb0,0x2c87aed0,0x2a4eaaaa,0xaf80af6e,0xafc9afdd,0xafe6afdd,0x2f463000,
0xafa0af91,0xabb7ae5e,0xaff4afed,0x28d52d4d,0xafbcafaf,0x2934a17e,0xaffcaff8,0xac07a30e,0xafd4afc9,0x2f5a2d72,0xb000afff,0xafd4ae7c,
0x2bb72aaa,0x2f1a2cb0,0x2f1a2ed0,0xaff4af80,0x2cd82c5d,0x2f303000,0x2f912f5a,0xac07aeb5,0x2dba2d4d,0x25db2cd8,0x2fdd2fbc,0x2a4e9fd9,
0x2e7c2e1f,0xad72a875,0x2fff2ff4,0x2fc92e1f,0x26a12934,0xa9f1244e,0xad96acd8,0x2fd42dfe,0x9cb6217e,0xafe6ae3f,0xaed0ae3f,0x2d722fa0,
0xa875a515,0xad27af80,0xafa0af46,0xa8752765,0xac07aa4e,0x2934a5db,0xaffcafdd,0xafbcadba,0xae5eaf1a,0xa934ae3f,0x2b052875,0xaee9ab5e,
0xac5dad72,0x2dba2765,0x2dba2cb0,0xae99afff,0xa765aa4e,0x2f802fd4,0x2f462e99,0x2515aa4e,0x230e9fd9,0x217e2cd8,0x2ff82fbc,0x2faf2d4d,
0x2ffc2faf,0x2ee92ff8,0xa44e217e,0x2d4d230e,0x2f6e2fe6,0xa5db2aaa,0xac5da993,0x2f6e2fc9,0x2d722e99,0xafe6adba,0xaed0adba,0x9cb62c5d,
0x28d52c07,0xabb7af30,0xaff4af91,0xafa0acd8,0xadbaac07,0xafddad4d,0xa5dbab05,0xaa4e2814,0xafc9af02,0xaaaaaf1a,0x2993217e,0xafe6af02,
0xafa0afff,0x2e3f2765,0x2e3f2cb0,0xa17ead72,0xad4daeb5,0x2e5e3000,0x2fed2f5a,0x2f912c5d,0x217ea765,0x2d009cb6,0x2bb72ddc,0x217eacb0,
0x2d4d2a4e,0x2ee92fdd,0xa44e25db,0x2ffc2dba,0x2fd42ee9,0xa9f12934,0xad96ab05,0x26a12e5e,0x2f462ff4,0xafc9af1a,0xafe6af1a,0xaf80abb7,
0x2cb02eb5,0x1cb62dba,0xaddcaf6e,0x27652eb5,0xa30e2814,0xaff8ad4d,0xa17eab05,0xafafac07,0xadfeab5e,0xa44eae3f,0x2cd82875,0xa934af1a,
0xb000af80,0x2fdd2cb0,0x2fdd2ed0,0x2f6e2aaa,0xad72b000,0xa515afd4,0xac32afd4,0x9cb62f5a,0x2e1f1fd9,0x2e3f2ee9,0x2f022814,0xad27af91,
0x2cd82ff4,0xaffca8d5,0x2b052fa0,0x2fed2bb7,0xae99a515,0x2d96aaaa,0xaf5aa993,0xae992765,0x2ff42ddc,0x2e1f2ed0,0x2e1f2fe6,0xa875afff,
0xa8142c87,0xaffca9f1,0xadfe1648,0x2e5e2e99,0xaf5aaf30,0x2eb5a814,0xac5dafed,0xb000a934,0x2c32a8d5,0xa9932e3f,0x2f462875,0x2e7ca8d5,
0xae999fd9,0xb000a814,0xaf6eaee9,0x2c872f91,0xa993afa0,0x2ed0a875,0x2cb0a875,0xaf46ad27,0x2ff42c32,0xab5e2ddc,0x2d272fff,0x2ff42515,
0xa44e2d96,0x9fd9afd4,0xaf30a6a1,0xae5e29f1,0x2814ad27,0x2dfeabb7,0x2ffc2d00,0xae5eae1f,0x2e992f80,0xaa4e2e7c,0xaa4e2c32,0x2fd42aaa,
0xae7c1648,0x9cb6afdd,0xaddcafd4,0xafc91648,0xa875af91,0x2b5e2fbc,0x2f1a244e,0x2e3fab05,0x2b052ff4,0xa44e2fa0,0xafbca8d5,0x2f912bb7,
0xb000ac32,0xa6a1afff,0x25dbaddc,0xb000a515,0x2aaaac5d,0x2c322f6e,0x2e7c2f6e,0x2f80a5db,0x2d272fed,0xae3fadfe,0xaf029fd9,0xae1f2c07,
0xaf5aae5e,0xac5daf30,0x2eb59fd9,0xb000a44e,0x2e7ca30e,0x2ddc2e1f,0x1cb62f1a,0x2fc9a30e,0x217e2f46,0xaf02acb0,0xaf02aed0,0xaf1a2993,
0xaf30ae99,0x2fbc29f1,0x2ee99648,0x2dfeac87,0x2fa02515,0x2faf2993,0xad002aaa,0x2fa0a765,0xa9342d96,0xafeda6a1,0xa814afd4,0xaf3029f1,
0xac87afed,0x30001fd9,0x2f6e2dfe,0x2e99ac07,0x2fff2bb7,0xafe6217e,0xaed0217e,0xaddc2d00,0xac322c87,0xaf462a4e,0x2993adba,0xae7c2c87,
0xa875afed,0x2f1aab05,0x2b5e2ffc,0x2e3facd8,0x2f302e1f,0xaee92bb7,0xafbcad00,0xadfe2d27,0xaf6e9cb6,0x2eb5ac32,0x2eb5a515,0x2dbaad72,
0x2aaaaf5a,0x2ed0ae99,0x2cb0ae99,0xaf802d96,0xab5e2f30,0xafaf244e,0xad002e5e,0x2f1a1fd9,0x2c07af02,0x2b052d27,0x2d4dae1f,0xa814ae3f,
0xac5d2ed0,0x29f1afff,0xad962ddc,0xac5d2fe6,0x28752f80,0xa8d52fe6,0xa8d52fc9,0x2e3faf46,0xa44eafd4,0x2f91adba,0x2b05af6e,0xafbc26a1,
0x96482ffc,0xae99a44e,0xac872ee9,0x29f12d4d,0x2515aff8,0x1cb62f02,0x2d72ae3f,0x2c32aff8,0xaeb5ab05,0xaa4eacd8,0x9648afed,0xac5d2ffc,
0x2d722d27,0xacb02ff4,0xa7652ff4,0x2fffab5e,0xabb7ae7c,0x2ff8aaaa,0x2b5eaf80,0xabb7ac32,0x28142f6e,0xab05ac87,0xad4d2e99,0xac073000,
0x2feda8d5,0x2f30a30e,0x29342f02,0x2814afa0,0xafd49cb6,0x1648aed0,0x1648afe6,0xafdd2d72,0x2ed029f1,0xaf462eb5,0xa9932fdd,0x2cb029f1,
0xad00ad4d,0x2e1f244e,0x2d27aee9,0x2bb7affc,0xad4d2f02,0xafbc2e1f,0xacd8ad27,0x1fd92e3f,0x2f5aacb0,0x2c872993,0x26a12f46,0x2f5aaed0,
0xafff25db,0x2cb0b000,0x2765b000,0xad72a6a1,0x2f1a2814,0xafaf2934,0xad002f30,0xab5e2fed,0x1648afbc,0x2c87affc,0x2e992934,0xa9f1ac07,
0xac322faf,0xaf8028d5,0xaaaaae1f,0xae7c2faf,0x2f1aad72,0xa30e2ed0,0xa30e2fe6,0x2e1f1cb6,0xaffc26a1,0x2fedadba,0x2cd8af6e,0x2b05afd4,
0x2d272c32,0x230e2d72,0xafaf1cb6,0x2d272515,0x9fd9af6e,0x2fbcae99,0x2cd82c87,0x2d4db000,0xac5d2fbc,0xaa4eab05,0x9648af91,0xaeb5244e,
0x2f80ad00,0xaed02fa0,0xacb02fa0,0xaaaa2faf,0xafe626a1,0xaddc1648,0x2fffaa4e,0xaed026a1,0x2d002c07,0xad272ffc,0xae1fa934,0xabb72fbc,
0x1fd9afa0,0x2e5ea30e,0x244e2f02,0x2f30a8d5,0xadba2f46,0x2c87afe6,0x2c87afc9,0x2a4eaf80,0x2fffad96,0x2e7cac5d,0x2fc9ac5d,0xad7229f1,
0x217eadfe,0x2ff4afbc,0x2875aee9,0xaff82f30,0xafed2d00,0x2d4daf1a,0xaf912b5e,0xae5e2faf,0xa5db2e7c,0x9648a993,0xa9f12f46,0xa5db2c32,
0xae3f2fff,0xaff82fc9,0xaff82e7c,0x2f02ad72,0x2c0725db,0xadfe2f5a,0x9fd92d96,0x2fedafdd,0x2f6eaf91,0xa6a12c07,0x2fd4acd8,0x2dbaaf30,
0xa765ab5e,0x2aaaa30e,0x2993af02,0x2515ab5e,0x25dbadfe,0x2d96aee9,0x2f5aafbc,0xafdd2f30,0xaf462b5e,0x2765abb7,0xa515abb7,0xaf802ff8,
0xad002fc9,0xa8d51cb6,0xaff82ddc,0xad002e7c,0x2cd81648,0xadfe2c5d,0xa9342eb5,0xa44e2a4e,0x2c07217e,0x9fd92875,0xadfe2ff4,0x2fedaff8,
0x2fddaf46,0x29f1a515,0x29f12765,0x2eb5af80,0x2515ad96,0x2ddcac87,0x2fffaeb5,0x2c32ad96,0xaf022b05,0x2fa0aee9,0x28d5ae5e,0x230ea934,
0xaf912d00,0xacd82b5e,0x2c07af1a,0xaf302faf,0xad962fc9,0xaeb52ddc,0xac871cb6,0xad962e7c,0x299326a1,0xafc92f5a,0xafe62f5a,0xaaaa2c87,
0x2ff8ae5e,0xaff42ffc,0xa8752dfe,0xa17e2814,0x2f6eafed,0x2fd4af91,0xa6a12d4d,0x2dbaae5e,0x2515ad00,0x2fffaff8,0x2ddca8d5,0x2c32ad00,
0xae1f2993,0x2fafafe6,0x2fafafc9,0x28d5aaaa,0xaf912fdd,0x2ee9af5a,0x2814ad96,0x1fd9a5db,0xab5e2e7c,0xaf022f46,0xa30ea993,0xab5e2c32,
0x2b051648,0xae5e2eb5,0xaee92c5d,0xa9342a4e,0x2fddae5e,0xad962dfe,0xaf5a2ffc,0xa5db2814,0x2ddcafaf,0xacb02d27,0xa7652d27,0x9cb6230e,
0xa765a5db,0x2993a9f1,0x2aaa9648,0x2515a5db,0xaf022cd8,0x28d5a934,0x2fa0adfe,0x230ea44e,0xaf912ff8,0x2814a875,0x2ee9aff4,0x1fd9a17e,
0xaa4e2ddc,0x26a1a765,0x26a1acb0,0x16489cb6,0x9d7f9e49,0xaddcaeb3,0x12480000,0x22ad0000,0x9bdb9cb6,0xac2ead04,0x18b61648,0x290226ad,
0x98b69a49,0xa902aaaf,0x1bdb1a49,0x2c2e2aaf,0x92489648,0xa2ada6ad,0x1d7f1cb6,0x2ddc2d04,0xa420a4b7,0xae8daf7f,0x18b60000,0x23760000,
0xa1e4a312,0xacacad9c,0x1f121cb6,0x29992777,0x9f12a0b6,0xa999ab78,0x21e420b6,0x2cac2b78,0x98b69cb6,0xa376a777,0x24202312,0x2e8d2d9c,
0xa6e0a7db,0xaf3fb025,0x1bdb0000,0x24200000,0xa4e9a5e4,0xad2aae34,0x21e41fdb,0x2a312820,0xa1e4a3db,0xaa31ac21,0x24e923db,0x2d2a2c21,
0x9bdb9fdb,0xa420a820,0x26e025e4,0x2f3f2e34,0xa8d0a980,0xaff2b08c,0x1d7f0000,0x24840000,0xa6e0a820,0xada9aecd,0x2420217f,0x2ac82885,
0xa420a580,0xaac8ac86,0x26e02580,0x2da92c86,0x9d7fa17f,0xa484a885,0x28d02820,0x2ff22ecd,0xaa31ab13,0xb052b0f3,0x1f120000,0x24e90000,
0xa86ba94e,0xae28af65,0x254d2312,0x2b5f28e9,0xa54da712,0xab5faceb,0x286b2712,0x2e282ceb,0x9f12a312,0xa4e9a8e9,0x2a31294e,0x30522f65,
0xab91ac54,0xb0acb15a,0x20520000,0x254d0000,0xa967aa7c,0xaea7affe,0x267b2452,0x2bf6294e,0xa67ba852,0xabf6ad50,0x29672852,0x2ea72d50,
0xa052a452,0xa54da94e,0x2b912a7c,0x30ac2ffe,0xac79ad1e,0xb106b1c1,0x211b0000,0x25b20000,0xaa63abab,0xaf26b04c,0x27a9251b,0x2c4729b3,
0xa7a9a91c,0xac47adb6,0x2a63291c,0x2f262db6,0xa11ba51b,0xa5b2a9b3,0x2c792bab,0x3106304c,0xad2aade8,0xb160b229,0x21e40000,0x26170000,
0xab5fac6d,0xafa5b099,0x286b25e4,0x2c932a17,0xa86ba9e5,0xac93ae1b,0x2b5f29e5,0x2fa52e1b,0xa1e4a5e4,0xa617aa17,0x2d2a2c6d,0x31603099,
0xb1bbb292,0xb44fb4f6,0x267b0000,0x28d00000,0xb012b0e6,0xb216b357,0x2cde2a7c,0x2f3f2cd2,0xacdeae80,0xaf3fb0d9,0x30122e80,0x321630d9,
0xa67baa7c,0xa8d0acd2,0x31bb30e6,0x344f3357,0xb216b2fb,0xb47eb52d,0x26e00000,0x29020000,0xb052b133,0xb257b3a7,0x2d2a2ae1,0x2f8c2d04,
0xad2aaee6,0xaf8cb10c,0x30522ee6,0x3257310c,0xa6e0aae1,0xa902ad04,0x32163133,0x347e33a7,0xb271b364,0xb4aeb565,0x27440000,0x29350000,
0xb092b181,0xb298b3f7,0x2d762b46,0x2fd82d37,0xad76af4c,0xafd8b140,0x30922f4c,0x32983140,0xa744ab46,0xa935ad37,0x32713181,0x34ae33f7,
0xb2cdb3cf,0xb4deb59d,0x27a90000,0x29670000,0xb0d2b1ce,0xb2dab423,0x2dc22bab,0x30122d6a,0xadc2afb2,0xb012b174,0x30d22fb2,0x32da3174,
0xa7a9abab,0xa967ad6a,0x32cd31ce,0x34de3423,0xb329b41d,0xb50eb5d6,0x28070000,0x29990000,0xb113b21c,0xb31cb44c,0x2e0e2c08,0x30392d9c,
0xae0eb00c,0xb039b1a7,0x3113300c,0x331c31a7,0xa807ac08,0xa999ad9c,0x3329321c,0x350e344c,0xb386b453,0xb53fb60f,0x28390000,0x29cc0000,
0xb153b26b,0xb35eb474,0x2e5a2c3a,0x305f2dcf,0xae5ab03f,0xb05fb1db,0x3153303f,0x335e31db,0xa839ac3a,0xa9ccadcf,0x3386326b,0x353f3474,
0xb3e3b489,0xb570b649,0x286b0000,0x29fe0000,0xb194b2b9,0xb3a0b49d,0x2ea72c6d,0x30852e02,0xaea7b072,0xb085b20f,0x31943072,0x33a0320f,
0xa86bac6d,0xa9feae02,0x33e332b9,0x3570349d,0xb420b4bf,0xb5a1b683,0x289e0000,0x2a310000,0xb1d5b308,0xb3e3b4c6,0x2ef32c9f,0x30ac2e34,
0xaef3b0a5,0xb0acb243,0x31d530a5,0x33e33243,0xa89eac9f,0xaa31ae34,0x34203308,0x35a134c6,0xb5d2b6be,0xb76fb857,0x2a630000,0x2bf60000,
0xb413b4ef,0xb523b642,0x30d22e67,0x32092ffe,0xb0d2b278,0xb209b40f,0x34133278,0x3523340f,0xaa63ae67,0xabf6affe,0x35d234ef,0x376f3642,
0xb604b6fa,0xb7a5b878,0x2a950000,0x2c140000,0xb434b519,0xb546b66d,0x30f92e9a,0x32303019,0xb0f9b2ac,0xb230b42a,0x343432ac,0x3546342a,
0xaa95ae9a,0xac14b019,0x36043519,0x37a5366d,0xb637b736,0xb7dbb899,0x2ac80000,0x2c2e0000,0xb456b542,0xb569b699,0x31202ecd,0x32573032,
0xb120b2e1,0xb257b445,0x345632e1,0x35693445,0xaac8aecd,0xac2eb032,0x36373542,0x37db3699,0xb66ab773,0xb809b8bb,0x2afa0000,0x2c470000,
0xb478b56c,0xb58cb6c6,0x31462f00,0x327e304c,0xb146b315,0xb27eb460,0x34783315,0x358c3460,0xaafaaf00,0xac47b04c,0x366a356c,0x380936c6,
0xb69db7b0,0xb825b8dd,0x2b2d0000,0x2c600000,0xb49ab596,0xb5afb6f2,0x316d2f32,0x32a53065,0xb16db34a,0xb2a5b47b,0x349a334a,0x35af347b,
0xab2daf32,0xac60b065,0x369d3596,0x382536f2,0xb6d1b7ee,0xb841b8ff,0x2b5f0000,0x2c790000,0xb4bcb5c1,0xb5d2b71f,0x31942f65,0x32cd307f,
0xb194b37f,0xb2cdb496,0x34bc337f,0x35d23496,0xab5faf65,0xac79b07f,0x36d135c1,0x3841371f,0xb705b817,0xb85db923,0x2b910000,0x2c930000,
0xb4deb5eb,0xb5f6b74d,0x31bb2f98,0x32f43099,0xb1bbb3b4,0xb2f4b4b1,0x34de33b4,0x35f634b1,0xab91af98,0xac93b099,0x370535eb,0x385d374d,
0xb73ab837,0xb87ab946,0x2bc40000,0x2cac0000,0xb500b616,0xb61ab77a,0x31e22fcb,0x331c30b2,0xb1e2b3e9,0xb31cb4cd,0x350033e9,0x361a34cd,
0xabc4afcb,0xacacb0b2,0x373a3616,0x387a377a,0xb897b96b,0xb98dbaa6,0x2cc50000,0x2d900000,0xb63eb7a8,0xb767b895,0x334330cc,0x3442319a,
0xb343b4e8,0xb442b5c8,0x363e34e8,0x376735c8,0xacc5b0cc,0xad90b19a,0x389737a8,0x398d3895,0xb8b4b990,0xb9aebad1,0x2cde0000,0x2da90000,
0xb662b7d7,0xb78db8ae,0x336b30e6,0x345631b4,0xb36bb504,0xb456b5e4,0x36623504,0x378d35e4,0xacdeb0e6,0xada9b1b4,0x38b437d7,0x39ae38ae,
0xb8d2b9b5,0xb9cfbafd,0x2cf80000,0x2dc20000,0xb687b803,0xb7b4b8c7,0x339330ff,0x346a31ce,0xb393b51f,0xb46ab601,0x3687351f,0x37b43601,
0xacf8b0ff,0xadc2b1ce,0x38d23803,0x39cf38c7,0xb8f0b9dc,0xb9f1bb29,0x2d110000,0x2ddc0000,0xb6acb81b,0xb7dbb8e1,0x33bb3119,0x347e31e8,
0xb3bbb53b,0xb47eb61e,0x36ac353b,0x37db361e,0xad11b119,0xaddcb1e8,0x38f0381b,0x39f138e1,0xb90fba02,0xba14bb57,0x2d2a0000,0x2df50000,
0xb6d1b833,0xb801b8fb,0x33e33133,0x34933202,0xb3e3b557,0xb493b63a,0x36d13557,0x3801363a,0xad2ab133,0xadf5b202,0x390f3833,0x3a1438fb,
0xb92eba2a,0xba37bb86,0x2d440000,0x2e0e0000,0xb6f6b84b,0xb815b915,0x3405314d,0x34a7321c,0xb405b573,0xb4a7b657,0x36f63573,0x38153657,
0xad44b14d,0xae0eb21c,0x392e384b,0x3a373915,0xb94dba53,0xba5abbb6,0x2d5d0000,0x2e280000,0xb71bb863,0xb829b930,0x34193167,0x34bc3236,
0xb419b58f,0xb4bcb675,0x371b358f,0x38293675,0xad5db167,0xae28b236,0x394d3863,0x3a5a3930,0xb96dba7c,0xba7ebbe7,0x2d760000,0x2e410000,
0xb741b87c,0xb83db94b,0x342e3181,0x34d03250,0xb42eb5ab,0xb4d0b692,0x374135ab,0x383d3692,0xad76b181,0xae41b250,0x396d387c,0x3a7e394b,
0xa17fa248,0xb1cfb2a1,0x16480000,0x26ad0000,0x9fdba0b6,0xb029b0fd,0x1cb61a48,0x2d002aac,0x9cb69e48,0xad00aeaa,0x1fdb1e48,0x30292eaa,
0x96489a48,0xa6adaaac,0x217f20b6,0x31cf30fd,0xa81fa8b6,0xb27cb365,0x1cb60000,0x27760000,0xa5e4a711,0xb0a6b191,0x231120b6,0x2d972b75,
0xa311a4b6,0xad97af72,0x25e424b6,0x30a62f72,0x9cb6a0b6,0xa776ab75,0x281f2711,0x327c3191,0xaadeabd9,0xb328b414,0x1fdb0000,0x281f0000,
0xa8e8a9e3,0xb122b226,0x25e423db,0x2e2d2c1f,0xa5e4a7da,0xae2db01d,0x28e827da,0x3122301d,0x9fdba3db,0xa81fac1f,0x2ade29e3,0x33283226,
0xaccead7e,0xb3d3b475,0x217f0000,0x28840000,0xaadeac1f,0xb19eb2b9,0x281f257f,0x2ec32c83,0xa81fa97f,0xaec3b080,0x2ade297f,0x319e3080,
0xa17fa57f,0xa884ac83,0x2cce2c1f,0x33d332b9,0xae2daf0e,0xb43eb4d5,0x23110000,0x28e80000,0xac6aad4c,0xb219b34c,0x294d2711,0x2f592ce7,
0xa94dab11,0xaf59b0e4,0x2c6a2b11,0x321930e4,0xa311a711,0xa8e8ace7,0x2e2d2d4c,0x343e334c,0xaf8bb04e,0xb493b534,0x24520000,0x294d0000,
0xad65ae78,0xb294b3df,0x2a7a2852,0x2fef2d4c,0xaa7aac51,0xafefb147,0x2d652c51,0x32943147,0xa452a852,0xa94dad4c,0x2f8b2e78,0x349333df,
0xb074b115,0xb4e7b593,0x251b0000,0x29b10000,0xae5fafa4,0xb30fb438,0x2ba7291b,0x30422db0,0xaba7ad1a,0xb042b1aa,0x2e5f2d1a,0x330f31aa,
0xa51ba91b,0xa9b1adb0,0x30742fa4,0x34e73438,0xb122b1db,0xb53ab5f1,0x25e40000,0x2a160000,0xaf59b067,0xb389b481,0x2c6a29e3,0x308d2e14,
0xac6aade2,0xb08db20d,0x2f592de2,0x3389320d,0xa5e4a9e3,0xaa16ae14,0x31223067,0x353a3481,0xb58db64e,0xb805b887,0x2a7a0000,0x2cce0000,
0xb402b4c9,0xb5dfb6f9,0x30d72e78,0x332830cb,0xb0d7b26f,0xb328b4bd,0x3402326f,0x35df34bd,0xaa7aae78,0xacceb0cb,0x358d34c9,0x380536f9,
0xb5dfb6aa,0xb82ab8b0,0x2ade0000,0x2d000000,0xb43eb511,0xb61ab73d,0x31222edc,0x337130fd,0xb122b2d2,0xb371b4ed,0x343e32d2,0x361a34ed,
0xaadeaedc,0xad00b0fd,0x35df3511,0x382a373d,0xb631b705,0xb850b8d8,0x2b430000,0x2d330000,0xb47bb558,0xb654b780,0x316c2f40,0x33ba312e,
0xb16cb334,0xb3bab51d,0x347b3334,0x3654351d,0xab43af40,0xad33b12e,0x36313558,0x38503780,0xb682b75e,0xb874b900,0x2ba70000,0x2d650000,
0xb4b7b59f,0xb68db7c2,0x31b62fa4,0x34023160,0xb1b6b396,0xb402b54c,0x34b73396,0x368d354c,0xaba7afa4,0xad65b160,0x3682359f,0x387437c2,
0xb6d2b7b7,0xb899b927,0x2c060000,0x2d970000,0xb4f3b5e5,0xb6c6b802,0x32013004,0x34263191,0xb201b3f7,0xb426b57c,0x34f333f7,0x36c6357c,
0xac06b004,0xad97b191,0x36d235e5,0x38993802,0xb721b807,0xb8bcb94d,0x2c380000,0x2dc90000,0xb52fb62b,0xb6ffb822,0x324b3036,0x344b31c3,
0xb24bb42c,0xb44bb5ab,0x352f342c,0x36ff35ab,0xac38b036,0xadc9b1c3,0x3721362b,0x38bc3822,0xb76fb832,0xb8e0b972,0x2c6a0000,0x2dfb0000,
0xb56ab670,0xb737b842,0x32943067,0x346f31f4,0xb294b45d,0xb46fb5da,0x356a345d,0x373735da,0xac6ab067,0xadfbb1f4,0x376f3670,0x38e03842,
0xb7bdb85d,0xb902b996,0x2c9c0000,0x2e2d0000,0xb5a5b6b5,0xb76fb862,0x32de3099,0x34933226,0xb2deb48d,0xb493b608,0x35a5348d,0x376f3608,
0xac9cb099,0xae2db226,0x37bd36b5,0x39023862,0xb924b9ba,0xba1dbab5,0x2e5f0000,0x2fef0000,0xb7a6b881,0xb8a8b96d,0x34b73257,0x35d433df,
0xb4b7b637,0xb5d4b7a1,0x37a63637,0x38a837a1,0xae5fb257,0xafefb3df,0x39243881,0x3a1d396d,0xb946b9dc,0xba39bad0,0x2e910000,0x30100000,
0xb7ddb8a0,0xb8c1b989,0x34db3288,0x35f73408,0xb4dbb665,0xb5f7b7cd,0x37dd3665,0x38c137cd,0xae91b288,0xb010b408,0x394638a0,0x3a393989,
0xb966b9fe,0xba54bae9,0x2ec30000,0x30290000,0xb80ab8bf,0xb8dbb9a4,0x34ff32b9,0x361a3420,0xb4ffb693,0xb61ab7f9,0x380a3693,0x38db37f9,
0xaec3b2b9,0xb029b420,0x396638bf,0x3a5439a4,0xb986ba1f,0xba6fbb02,0x2ef50000,0x30420000,0xb825b8dd,0xb8f3b9be,0x352332ea,0x363c3438,
0xb523b6c1,0xb63cb812,0x382536c1,0x38f33812,0xaef5b2ea,0xb042b438,0x398638dd,0x3a6f39be,0xb9a6ba3f,0xba89bb1a,0x2f270000,0x305b0000,
0xb840b8fb,0xb90cb9d8,0x3546331b,0x365f3451,0xb546b6ee,0xb65fb828,0x384036ee,0x390c3828,0xaf27b31b,0xb05bb451,0x39a638fb,0x3a8939d8,
0xb9c5ba5e,0xbaa2bb30,0x2f590000,0x30740000,0xb85ab918,0xb924b9f2,0x356a334c,0x36823469,0xb56ab71b,0xb682b83d,0x385a371b,0x3924383d,
0xaf59b34c,0xb074b469,0x39c53918,0x3aa239f2,0xb9e3ba7c,0xbababb46,0x2f8b0000,0x308d0000,0xb874b935,0xb93cba0b,0x358d337d,0x36a43481,
0xb58db748,0xb6a4b852,0x38743748,0x393c3852,0xaf8bb37d,0xb08db481,0x39e33935,0x3aba3a0b,0xba00ba99,0xbad1bb5a,0x2fbd0000,0x30a60000,
0xb88eb951,0xb954ba23,0x35b133ae,0x36c63499,0xb5b1b775,0xb6c6b867,0x388e3775,0x39543867,0xafbdb3ae,0xb0a6b499,0x3a003951,0x3ad13a23,
0xbae8bb6e,0xbb7fbbdd,0x30be0000,0x31850000,0xb96bba3b,0xba19bae6,0x36e834b1,0x37f33570,0xb6e8b87c,0xb7f3b91d,0x396b387c,0x3a19391d,
0xb0beb4b1,0xb185b570,0x3ae83a3b,0x3b7f3ae6,0xbafebb80,0xbb8ebbe6,0x30d70000,0x319e0000,0xb982ba52,0xba2dbaf9,0x370a34c9,0x380a3587,
0xb70ab891,0xb80ab930,0x39823891,0x3a2d3930,0xb0d7b4c9,0xb19eb587,0x3afe3a52,0x3b8e3af9,0xbb13bb91,0xbb9cbbed,0x30f00000,0x31b60000,
0xb999ba69,0xba41bb0b,0x372c34e1,0x381a359f,0xb72cb8a6,0xb81ab943,0x399938a6,0x3a413943,0xb0f0b4e1,0xb1b6b59f,0x3b133a69,0x3b9c3b0b,
0xbb27bba0,0xbba9bbf4,0x31090000,0x31cf0000,0xb9afba7f,0xba54bb1d,0x374e34f9,0x382a35b6,0xb74eb8ba,0xb82ab956,0x39af38ba,0x3a543956,
0xb109b4f9,0xb1cfb5b6,0x3b273a7f,0x3ba93b1d,0xbb3abbaf,0xbbb5bbf8,0x31220000,0x31e80000,0xb9c5ba95,0xba67bb2e,0x376f3511,0x383a35ce,
0xb76fb8ce,0xb83ab969,0x39c538ce,0x3a673969,0xb122b511,0xb1e8b5ce,0x3b3a3a95,0x3bb53b2e,0xbb4cbbbc,0xbbc0bbfc,0x313b0000,0x32010000,
0xb9dabaaa,0xba7abb3e,0x37903529,0x384a35e5,0xb790b8e2,0xb84ab97b,0x39da38e2,0x3a7a397b,0xb13bb529,0xb201b5e5,0x3b4c3aaa,0x3bc03b3e,
0xbb5ebbc9,0xbbcbbbff,0x31530000,0x32190000,0xb9f0babf,0xba8cbb4e,0x37b23540,0x385a35fd,0xb7b2b8f6,0xb85ab98d,0x39f038f6,0x3a8c398d,
0xb153b540,0xb219b5fd,0x3b5e3abf,0x3bcb3b4e,0xbb6fbbd4,0xbbd4bc00,0x316c0000,0x32320000,0xba04bad3,0xba9ebb5d,0x37d23558,0x386a3614,
0xb7d2b909,0xb86ab99f,0x3a043909,0x3a9e399f,0xb16cb558,0xb232b614,0x3b6f3ad3,0x3bd43b5d,0x0,0x0,0x0,0x0,
0x2e1f0000,0x336431a8,0x33643400,0x2e1f31a8,0x31a80000,0x31a83400,0xb1a80000,0xb1a8b400,0x33640000,0xae1f31a8,0xae1fb400,0x336431a8,
0x34000000,0xb4000000,0x34000000,0xb4000000,0x33640000,0xae1fb1a8,0xae1f3400,0x3364b1a8,0x31a80000,0x31a8b400,0xb1a80000,0xb1a83400,
0x2e1f0000,0x3364b1a8,0x3364b400,0x2e1fb1a8,0x0,0x0,0x0,0x0,0xae1f0000,0xb36431a8,0xb3643400,0xae1f31a8,
0xb1a80000,0xb1a83400,0x31a80000,0x31a8b400,0xb3640000,0x2e1f31a8,0x2e1fb400,0xb36431a8,0xb4000000,0x34000000,0xb4000000,0x34000000,
0xb3640000,0x2e1fb1a8,0x2e1f3400,0xb364b1a8,0xb1a80000,0xb1a8b400,0x31a80000,0x31a83400,0xae1f0000,0xb364b1a8,0xb364b400,0xae1fb1a8,
0x0,0x0,0x0,0x0,0xae1f0000,0xb364b1a8,0xb364b400,0xae1fb1a8,0x31a80000,0x31a83400,0xb1a80000,0xb1a8b400,
0xb3640000,0x2e1fb1a8,0x2e1f3400,0xb364b1a8,0x34000000,0xb4000000,0x34000000,0xb4000000,0xb3640000,0x2e1f31a8,0x2e1fb400,0xb36431a8,
0x31a80000,0x31a8b400,0xb1a80000,0xb1a83400,0xae1f0000,0xb36431a8,0xb3643400,0xae1f31a8,0x0,0x0,0x0,0x0,
0x2e1f0000,0x3364b1a8,0x3364b400,0x2e1fb1a8,0xb1a80000,0xb1a83400,0x31a80000,0x31a8b400,0x33640000,0xae1fb1a8,0xae1f3400,0x3364b1a8,
0xb4000000,0x34000000,0xb4000000,0x34000000,0x33640000,0xae1f31a8,0xae1fb400,0x336431a8,0xb1a80000,0xb1a8b400,0x31a80000,0x31a83400,
0x2e1f0000,0x336431a8,0x33643400,0x2e1f31a8,0x34003400,0x34003400,0x34003400,0x34003400,0x33643400,0x2e1f31a8,0xae1f0000,0xb364b1a8,
0x31a83400,0xb1a80000,0xb1a8b400,0x31a80000,0x2e1f3400,0xb364b1a8,0x33640000,0xae1f31a8,0x3400,0xb400,0x3400,0xb400,
0xae1f3400,0x3364b1a8,0xb3640000,0x2e1f31a8,0xb1a83400,0x31a80000,0x31a8b400,0xb1a80000,0xb3643400,0xae1f31a8,0x2e1f0000,0x3364b1a8,
0xb4003400,0xb4003400,0xb4003400,0xb4003400,0xb3643400,0xae1f31a8,0x2e1f0000,0x3364b1a8,0xb1a83400,0x31a80000,0x31a8b400,0xb1a80000,
0xae1f3400,0x3364b1a8,0xb3640000,0x2e1f31a8,0x3400,0xb400,0x3400,0xb400,0x2e1f3400,0xb364b1a8,0x33640000,0xae1f31a8,
0x31a83400,0xb1a80000,0xb1a8b400,0x31a80000,0x33643400,0x2e1f31a8,0xae1f0000,0xb364b1a8,0x34003400,0x34003400,0x34003400,0x34003400,
0xb364b400,0xae1fb1a8,0x2e1f0000,0x336431a8,0x31a83400,0xb1a80000,0xb1a8b400,0x31a80000,0xae1fb400,0x336431a8,0xb3640000,0x2e1fb1a8,
0x3400,0xb400,0x3400,0xb400,0x2e1fb400,0xb36431a8,0x33640000,0xae1fb1a8,0xb1a83400,0x31a80000,0x31a8b400,0xb1a80000,
0x3364b400,0x2e1fb1a8,0xae1f0000,0xb36431a8,0xb4003400,0xb4003400,0xb4003400,0xb4003400,0x3364b400,0x2e1fb1a8,0xae1f0000,0xb36431a8,
0xb1a83400,0x31a80000,0x31a8b400,0xb1a80000,0x2e1fb400,0xb36431a8,0x33640000,0xae1fb1a8,0x3400,0xb400,0x3400,0xb400,
0xae1fb400,0x336431a8,0xb3640000,0x2e1fb1a8,0x31a83400,0xb1a80000,0xb1a8b400,0x31a80000,0xb364b400,0xae1fb1a8,0x2e1f0000,0x336431a8,
0x0,0x0,0x0,0x0,0xae1f0000,0xb364b1a8,0xb364b400,0xae1fb1a8,0xb1a80000,0xb1a8b400,0x31a80000,0x31a83400,
0xb3640000,0x2e1fb1a8,0x2e1f3400,0xb364b1a8,0xb4000000,0x34000000,0xb4000000,0x34000000,0xb3640000,0x2e1f31a8,0x2e1fb400,0xb36431a8,
0xb1a80000,0xb1a83400,0x31a80000,0x31a8b400,0xae1f0000,0xb36431a8,0xb3643400,0xae1f31a8,0x0,0x0,0x0,0x0,
0x2e1f0000,0x3364b1a8,0x3364b400,0x2e1fb1a8,0x31a80000,0x31a8b400,0xb1a80000,0xb1a83400,0x33640000,0xae1fb1a8,0xae1f3400,0x3364b1a8,
0x34000000,0xb4000000,0x34000000,0xb4000000,0x33640000,0xae1f31a8,0xae1fb400,0x336431a8,0x31a80000,0x31a83400,0xb1a80000,0xb1a8b400,
0x2e1f0000,0x336431a8,0x33643400,0x2e1f31a8,0x0,0x0,0x0,0x0,0x2e1f0000,0x336431a8,0x33643400,0x2e1f31a8,
0xb1a80000,0xb1a8b400,0x31a80000,0x31a83400,0x33640000,0xae1f31a8,0xae1fb400,0x336431a8,0xb4000000,0x34000000,0xb4000000,0x34000000,
0x33640000,0xae1fb1a8,0xae1f3400,0x3364b1a8,0xb1a80000,0xb1a83400,0x31a80000,0x31a8b400,0x2e1f0000,0x3364b1a8,0x3364b400,0x2e1fb1a8,
0x0,0x0,0x0,0x0,0xae1f0000,0xb36431a8,0xb3643400,0xae1f31a8,0x31a80000,0x31a8b400,0xb1a80000,0xb1a83400,
0xb3640000,0x2e1f31a8,0x2e1fb400,0xb36431a8,0x34000000,0xb4000000,0x34000000,0xb4000000,0xb3640000,0x2e1fb1a8,0x2e1f3400,0xb364b1a8,
0x31a80000,0x31a83400,0xb1a80000,0xb1a8b400,0xae1f0000,0xb364b1a8,0xb364b400,0xae1fb1a8,
};

typedef CUresult (*EncodeFn)(CUtensorMap*, CUtensorMapDataType, cuuint32_t, void*, const cuuint64_t*, const cuuint64_t*,
                             const cuuint32_t*, const cuuint32_t*, CUtensorMapInterleave, CUtensorMapSwizzle,
                             CUtensorMapL2promotion, CUtensorMapFloatOOBfill);

}

extern "C" void kernel_launch(void* const* d_in, const int* in_sizes, int n_in, void* d_out, int out_size) {
    Params p;
    p.x = (const __nv_bfloat16*)d_in[0];
    p.lar = (const __nv_bfloat16*)d_in[1];
    p.aim = (const __nv_bfloat16*)d_in[2];
    p.cr = (const __nv_bfloat16*)d_in[3];
    p.ci = (const __nv_bfloat16*)d_in[4];
    p.logdt = (const __nv_bfloat16*)d_in[5];
    p.dskip = (const __nv_bfloat16*)d_in[6];
    p.wr = (const __nv_bfloat16*)d_in[8];
    p.out = (__nv_bfloat16*)d_out;
    cudaGetSymbolAddress((void**)&p.sc, g_scratch);
    cudaGetSymbolAddress((void**)&p.tab, g_tab);

    void* fn = nullptr;
    cudaDriverEntryPointQueryResult qr;
    cudaGetDriverEntryPoint("cuTensorMapEncodeTiled", &fn, cudaEnableDefault, &qr);
    EncodeFn enc = (EncodeFn)fn;
    CUtensorMap tm_x, tm_g, tm_d;
    const cuuint32_t es[5] = {1, 1, 1, 1, 1};
    {
        const cuuint64_t gd[4] = {1024, 128, 8, 2}, gs[3] = {32768, 4096, 2048};
        const cuuint32_t bx[4] = {16, 64, 4, 1};
        enc(&tm_x, CU_TENSOR_MAP_DATA_TYPE_BFLOAT16, 4, d_in[0], gd, gs, bx, es, CU_TENSOR_MAP_INTERLEAVE_NONE,
            CU_TENSOR_MAP_SWIZZLE_NONE, CU_TENSOR_MAP_L2_PROMOTION_NONE, CU_TENSOR_MAP_FLOAT_OOB_FILL_NONE);
    }
    {
        char *wg = (char*)d_in[9], *wu = (char*)d_in[10];
        p.up_first = wu < wg;
        const cuuint64_t gd[3] = {3584, 1024, 2}, gs[2] = {7168, (cuuint64_t)(p.up_first ? wg - wu : wu - wg)};
        const cuuint32_t bx[3] = {64, 64, 2};
        enc(&tm_g, CU_TENSOR_MAP_DATA_TYPE_BFLOAT16, 3, p.up_first ? wu : wg, gd, gs, bx, es, CU_TENSOR_MAP_INTERLEAVE_NONE,
            CU_TENSOR_MAP_SWIZZLE_128B, (CUtensorMapL2promotion)GPROMO, CU_TENSOR_MAP_FLOAT_OOB_FILL_NONE);
    }
    {
        const cuuint64_t gd[3] = {64, 3584, 16}, gs[2] = {2048, 128};
        const cuuint32_t bx[3] = {64, 64, 2};
        enc(&tm_d, CU_TENSOR_MAP_DATA_TYPE_BFLOAT16, 3, d_in[11], gd, gs, bx, es, CU_TENSOR_MAP_INTERLEAVE_NONE,
            CU_TENSOR_MAP_SWIZZLE_128B, (CUtensorMapL2promotion)DPROMO, CU_TENSOR_MAP_FLOAT_OOB_FILL_NONE);
    }
    cudaFuncSetAttribute(fused_kernel, cudaFuncAttributeMaxDynamicSharedMemorySize, SM_TOTAL + 256);
    fused_kernel<<<128, NTHREADS, SM_TOTAL + 256>>>(p, tm_x, tm_g, tm_d);
}
```

```cpp
#include <cuda_runtime.h>
#include <cuda.h>
#include <cuda_bf16.h>
#include <cuda_fp16.h>
#include <stdint.h>

#define TG(i)
#define TS(i)
#define TSL(i)

#define TSW 0
#define SDELAY 1500
#define EDELAY 800
#define FILL 0x52110
#define STSLEEP 100
#define NPF 3
#define REFILL 0x55421
#define NREP 4
#define GPROMO 0
#define DPROMO 0
#define WPOL "evict_first"
#define PDELAY 600
#define IDEPTH 2

namespace {

constexpr int NTHREADS = 512;
constexpr int SPIN_LIMIT = 1 << 16;

constexpr int SM_SLAB = 0;
constexpr int SM_RING = 32768;
constexpr int SUB     = 1088;
constexpr int SM_K    = SM_RING + 10 * 8192;
constexpr int SM_S    = SM_K + 32 * SUB;
constexpr int SM_U    = SM_S + 32 * SUB;
constexpr int SM_F2   = SM_U + 32 * SUB;
constexpr int SM_XSEL = SM_F2 + 1536;
constexpr int SM_PAIR = SM_XSEL + 4096;
constexpr int SM_H    = SM_PAIR + 2048;
constexpr int SM_KEYS = SM_H + 1024;
constexpr int SM_TOK  = SM_KEYS + 64;
constexpr int SM_FIX  = SM_TOK + 16;
constexpr int SM_XRAW = SM_FIX + 32;
constexpr int SM_SCL  = SM_XRAW + 64;
constexpr int SM_BAR  = SM_SCL + 16;
constexpr int SM_RED  = SM_XSEL;
constexpr int SM_TAB  = SM_RING + 7 * 8192;
constexpr int B_FULL = 0, B_ROW = 24, B_STG = 32, B_SLAB = 36, B_TOK = 38, B_UFREE = 39, B_FIX = 40, B_PAIR = 41,
              B_TAB = 42, B_TFREE = 43, B_KFREE = 44, B_U = 46, B_PEER = 48, NBAR = 52;
constexpr int SM_TOTAL = SM_BAR + NBAR * 8;
static_assert(SM_TOTAL + 256 <= 232448, "smem");
__device__ __forceinline__ uint32_t chunk_off(int n) { return SM_RING + (n < 7 ? n : n - 7) * 16384; }
constexpr int KP = 272;

struct Scratch {
    uint4 stats[4][1032];
    uint32_t part[128 * 56 * 16];
    uint32_t epoch;
};
__device__ Scratch g_scratch;

struct Params {
    const __nv_bfloat16 *lar, *aim, *cr, *ci, *logdt, *dskip;
    const __nv_bfloat16 *x, *wr;
    __nv_bfloat16* out;
    Scratch* sc;
    const uint4* tab;
    int up_first;
};

__device__ __forceinline__ uint4 ldg128(const void* p) {
    uint4 v; asm volatile("ld.global.nc.v4.u32 {%0,%1,%2,%3}, [%4];" : "=r"(v.x), "=r"(v.y), "=r"(v.z), "=r"(v.w) : "l"(p)); return v;
}
__device__ __forceinline__ uint4 ld_relaxed128(const void* p) {
    uint4 v;
    asm volatile("{ .reg .b128 t; ld.relaxed.gpu.global.b128 t, [%4]; mov.b128 {%0,%1,%2,%3}, t; }"
                 : "=r"(v.x), "=r"(v.y), "=r"(v.z), "=r"(v.w) : "l"(p) : "memory");
    return v;
}
__device__ __forceinline__ void st_relaxed128(void* p, uint4 v) {
    asm volatile("{ .reg .b128 t; mov.b128 t, {%1,%2,%3,%4}; st.relaxed.gpu.global.b128 [%0], t; }"
                 :: "l"(p), "r"(v.x), "r"(v.y), "r"(v.z), "r"(v.w) : "memory");
}
__device__ __forceinline__ void st_relaxed32(void* p, uint32_t v) {
    asm volatile("st.relaxed.gpu.global.u32 [%0], %1;" :: "l"(p), "r"(v) : "memory");
}
__device__ __forceinline__ uint32_t lds32(uint32_t a) { uint32_t v; asm volatile("ld.shared.u32 %0, [%1];" : "=r"(v) : "r"(a)); return v; }
__device__ __forceinline__ uint32_t lds16(uint32_t a) { uint32_t v; asm volatile("ld.shared.u16 %0, [%1];" : "=r"(v) : "r"(a)); return v; }
__device__ __forceinline__ uint2 lds64(uint32_t a) { uint2 v; asm volatile("ld.shared.v2.u32 {%0,%1}, [%2];" : "=r"(v.x), "=r"(v.y) : "r"(a)); return v; }
__device__ __forceinline__ uint4 lds128(uint32_t a) {
    uint4 v; asm volatile("ld.shared.v4.u32 {%0,%1,%2,%3}, [%4];" : "=r"(v.x), "=r"(v.y), "=r"(v.z), "=r"(v.w) : "r"(a)); return v;
}
__device__ __forceinline__ void sts16(uint32_t a, uint32_t v) { asm volatile("st.shared.u16 [%0], %1;" :: "r"(a), "h"((uint16_t)v) : "memory"); }
__device__ __forceinline__ void sts32(uint32_t a, uint32_t v) { asm volatile("st.shared.u32 [%0], %1;" :: "r"(a), "r"(v) : "memory"); }
__device__ __forceinline__ void sts64(uint32_t a, uint32_t x, uint32_t y) { asm volatile("st.shared.v2.u32 [%0], {%1,%2};" :: "r"(a), "r"(x), "r"(y) : "memory"); }
__device__ __forceinline__ void sts128(uint32_t a, uint32_t x, uint32_t y, uint32_t z, uint32_t w) {
    asm volatile("st.shared.v4.u32 [%0], {%1,%2,%3,%4};" :: "r"(a), "r"(x), "r"(y), "r"(z), "r"(w) : "memory");
}
__device__ __forceinline__ void ldsm4(uint32_t a, uint32_t& r0, uint32_t& r1, uint32_t& r2, uint32_t& r3) {
    asm volatile("ldmatrix.sync.aligned.m8n8.x4.shared.b16 {%0,%1,%2,%3}, [%4];" : "=r"(r0), "=r"(r1), "=r"(r2), "=r"(r3) : "r"(a));
}
__device__ __forceinline__ void mma_f16(float (&d)[4], uint32_t a0, uint32_t a1, uint32_t a2, uint32_t a3, uint32_t b0, uint32_t b1) {
    asm("mma.sync.aligned.m16n8k16.row.col.f32.f16.f16.f32 {%0,%1,%2,%3}, {%4,%5,%6,%7}, {%8,%9}, {%0,%1,%2,%3};"
        : "+f"(d[0]), "+f"(d[1]), "+f"(d[2]), "+f"(d[3]) : "r"(a0), "r"(a1), "r"(a2), "r"(a3), "r"(b0), "r"(b1));
}
__device__ __forceinline__ void mma_bf16(float (&d)[4], uint32_t a0, uint32_t a1, uint32_t a2, uint32_t a3, uint32_t b0, uint32_t b1) {
    asm("mma.sync.aligned.m16n8k16.row.col.f32.bf16.bf16.f32 {%0,%1,%2,%3}, {%4,%5,%6,%7}, {%8,%9}, {%0,%1,%2,%3};"
        : "+f"(d[0]), "+f"(d[1]), "+f"(d[2]), "+f"(d[3]) : "r"(a0), "r"(a1), "r"(a2), "r"(a3), "r"(b0), "r"(b1));
}
__device__ __forceinline__ uint32_t prmt(uint32_t a, uint32_t b, uint32_t s) { uint32_t d; asm("prmt.b32 %0, %1, %2, %3;" : "=r"(d) : "r"(a), "r"(b), "r"(s)); return d; }
__device__ __forceinline__ uint32_t pack_h(float lo, float hi) { uint32_t d; asm("cvt.rn.f16x2.f32 %0, %1, %2;" : "=r"(d) : "f"(hi), "f"(lo)); return d; }
__device__ __forceinline__ uint32_t pack_b(float lo, float hi) { uint32_t d; asm("cvt.rn.bf16x2.f32 %0, %1, %2;" : "=r"(d) : "f"(hi), "f"(lo)); return d; }
__device__ __forceinline__ float blo(uint32_t v) { return __uint_as_float(v << 16); }
__device__ __forceinline__ float bhi(uint32_t v) { return __uint_as_float(v & 0xFFFF0000u); }
__device__ __forceinline__ float rb(float v) { return blo(pack_b(v, v)); }
__device__ __forceinline__ uint32_t bsub2(uint32_t a, uint32_t b) { uint32_t d; asm("sub.rn.bf16x2 %0, %1, %2;" : "=r"(d) : "r"(a), "r"(b)); return d; }
__device__ __forceinline__ uint32_t badd2(uint32_t a, uint32_t b) { uint32_t d; asm("add.rn.bf16x2 %0, %1, %2;" : "=r"(d) : "r"(a), "r"(b)); return d; }
__device__ __forceinline__ uint32_t bmul2(uint32_t a, uint32_t b) { uint32_t d; asm("mul.rn.bf16x2 %0, %1, %2;" : "=r"(d) : "r"(a), "r"(b)); return d; }
__device__ __forceinline__ uint32_t bfma2(uint32_t a, uint32_t b, uint32_t c) { uint32_t d; asm("fma.rn.bf16x2 %0, %1, %2, %3;" : "=r"(d) : "r"(a), "r"(b), "r"(c)); return d; }
__device__ __forceinline__ uint32_t dup_lo(uint32_t v) { uint32_t d; asm("{ .reg .b16 l, h; mov.b32 {l, h}, %1; mov.b32 %0, {l, l}; }" : "=r"(d) : "r"(v)); return d; }
__device__ __forceinline__ uint32_t dup_hi(uint32_t v) { uint32_t d; asm("{ .reg .b16 l, h; mov.b32 {l, h}, %1; mov.b32 %0, {h, h}; }" : "=r"(d) : "r"(v)); return d; }
__device__ __forceinline__ uint32_t norm2(uint32_t x, uint32_t m, uint32_t hi, uint32_t lo) {
    uint32_t a = bsub2(x, m);
    return bfma2(a, hi, bmul2(a, lo));
}
__device__ __forceinline__ float ex2(float v) { float d; asm("ex2.approx.ftz.f32 %0, %1;" : "=f"(d) : "f"(v)); return d; }
__device__ __forceinline__ float rcp(float v) { float d; asm("rcp.approx.ftz.f32 %0, %1;" : "=f"(d) : "f"(v)); return d; }
__device__ __forceinline__ float sigmoidf_(float v) { return rcp(1.0f + ex2(-1.4426950408889634f * v)); }
__device__ __forceinline__ float siluf_(float v) { return v * sigmoidf_(v); }

__device__ __forceinline__ void mbar_init(uint32_t a, int n) { asm volatile("mbarrier.init.shared::cta.b64 [%0], %1;" :: "r"(a), "r"(n) : "memory"); }
__device__ __forceinline__ void mbar_expect(uint32_t a, int tx) { asm volatile("mbarrier.arrive.expect_tx.shared::cta.b64 _, [%0], %1;" :: "r"(a), "r"(tx) : "memory"); }
__device__ __forceinline__ void mbar_arrive(uint32_t a) { asm volatile("mbarrier.arrive.shared::cta.b64 _, [%0];" :: "r"(a) : "memory"); }
__device__ __forceinline__ bool mbar_try(uint32_t a) {
    uint32_t d; asm volatile("{ .reg .pred p; mbarrier.try_wait.parity.shared::cta.b64 p, [%1], 0; selp.u32 %0, 1, 0, p; }" : "=r"(d) : "r"(a) : "memory"); return d;
}
__device__ __forceinline__ void mbar_wait(uint32_t a) {
    if (__builtin_expect(!mbar_try(a), 0)) {
        int n = SPIN_LIMIT;
        while (!mbar_try(a) && --n) {}
    }
}
__device__ __forceinline__ void mbar_arrive_peer(uint32_t a) { asm volatile("mbarrier.arrive.relaxed.cluster.shared::cluster.b64 _, [%0];" :: "r"(a) : "memory"); }
__device__ __forceinline__ uint32_t mapa(uint32_t a, uint32_t rank) { uint32_t d; asm("mapa.shared::cluster.u32 %0, %1, %2;" : "=r"(d) : "r"(a), "r"(rank)); return d; }
__device__ __forceinline__ void st_async2(uint32_t a, uint32_t x, uint32_t y, uint32_t bar) {
    asm volatile("st.async.weak.shared::cluster.mbarrier::complete_tx::bytes.v2.b32 [%0], {%1,%2}, [%3];" :: "r"(a), "r"(x), "r"(y), "r"(bar) : "memory");
}
__device__ __forceinline__ void st_async4(uint32_t a, uint32_t x, uint32_t y, uint32_t z, uint32_t w, uint32_t bar) {
    asm volatile("st.async.weak.shared::cluster.mbarrier::complete_tx::bytes.v4.b32 [%0], {%1,%2,%3,%4}, [%5];"
                 :: "r"(a), "r"(x), "r"(y), "r"(z), "r"(w), "r"(bar) : "memory");
}
__device__ __forceinline__ void stsm4(uint32_t a, uint32_t r0, uint32_t r1, uint32_t r2, uint32_t r3) {
    asm volatile("stmatrix.sync.aligned.m8n8.x4.shared.b16 [%0], {%1,%2,%3,%4};" :: "r"(a), "r"(r0), "r"(r1), "r"(r2), "r"(r3) : "memory");
}
__device__ __forceinline__ void proxy_fence() { asm volatile("fence.proxy.async.shared::cta;" ::: "memory"); }
__device__ __forceinline__ void bar_sync(int id, int n) { asm volatile("bar.sync %0, %1;" :: "r"(id), "r"(n) : "memory"); }
__device__ __forceinline__ void bar_arrive(int id, int n) { asm volatile("bar.arrive %0, %1;" :: "r"(id), "r"(n) : "memory"); }
__device__ __forceinline__ void cluster_arrive() { asm volatile("barrier.cluster.arrive.relaxed.aligned;" ::: "memory"); }
__device__ __forceinline__ void cluster_wait() { asm volatile("barrier.cluster.wait.aligned;" ::: "memory"); }
__device__ __forceinline__ void tma3d(uint32_t dst, const CUtensorMap* tm, int c0, int c1, int c2, uint32_t bar, uint64_t pol) {
    asm volatile("cp.async.bulk.tensor.3d.shared::cluster.global.mbarrier::complete_tx::bytes.L2::cache_hint [%0], [%1, {%3, %4, %6}], [%2], %5;"
                 :: "r"(dst), "l"(tm), "r"(bar), "r"(c0), "r"(c1), "l"(pol), "r"(c2) : "memory");
}
__device__ __forceinline__ bool elect() {
    uint32_t p; asm volatile("{ .reg .pred p; elect.sync _|p, 0xFFFFFFFF; selp.u32 %0, 1, 0, p; }" : "=r"(p)); return p;
}

struct cf { float r, i; };
__device__ __forceinline__ cf cmul(cf a, cf b) { return {a.r * b.r - a.i * b.i, a.r * b.i + a.i * b.r}; }
__device__ __forceinline__ cf csq(cf a) { return {a.r * a.r - a.i * a.i, (a.r + a.r) * a.i}; }
__device__ __forceinline__ cf cexp_(float a2, float b) { float m = ex2(a2); return {m * __cosf(b), m * __sinf(b)}; }
struct hc { uint32_t r, i; };
__device__ __forceinline__ hc pk(cf a, cf b) { return {pack_h(a.r, b.r), pack_h(a.i, b.i)}; }
__device__ __forceinline__ hc hmulc(hc a, hc b) {
    const __half2 ar = *reinterpret_cast<__half2*>(&a.r), ai = *reinterpret_cast<__half2*>(&a.i);
    const __half2 br = *reinterpret_cast<__half2*>(&b.r), bi = *reinterpret_cast<__half2*>(&b.i);
    const __half2 r = __hfma2(ar, br, __hneg2(__hmul2_rn(ai, bi))), i = __hfma2(ar, bi, __hmul2_rn(ai, br));
    return {*reinterpret_cast<const uint32_t*>(&r), *reinterpret_cast<const uint32_t*>(&i)};
}
__device__ __forceinline__ void sth(uint32_t a, hc v) { sts32(a, v.r); sts32(a + 128, v.i); }
__device__ __forceinline__ uint32_t cpy(uint32_t v, uint32_t z) { uint32_t d; asm("xor.b32 %0, %1, %2;" : "=r"(d) : "r"(v), "r"(z)); return d; }
__device__ __forceinline__ uint32_t pin(uint32_t v) { return __shfl_sync(0xFFFFFFFFu, v, threadIdx.x & 31); }
__device__ __forceinline__ void sched_fence() { asm volatile("pmevent 0;" ::: "memory"); }
__device__ __forceinline__ float tanh_(float v) { float d; asm("tanh.approx.f32 %0, %1;" : "=f"(d) : "f"(v)); return d; }
__device__ __forceinline__ float silu2(float h) {
    return h * rcp(fmaf(ex2(-2.8853900817779268f * h), 0.5f, 0.5f));
}
__device__ __forceinline__ uint32_t hfma2_(uint32_t a, uint32_t b, uint32_t c) { uint32_t d; asm("fma.rn.f16x2 %0, %1, %2, %3;" : "=r"(d) : "r"(a), "r"(b), "r"(c)); return d; }
__device__ __forceinline__ uint32_t hfms2_(uint32_t a, uint32_t b, uint32_t c) {
    uint32_t d; asm("{ .reg .b32 t; neg.f16x2 t, %1; fma.rn.f16x2 %0, t, %2, %3; }" : "=r"(d) : "r"(a), "r"(b), "r"(c)); return d;
}

__device__ __forceinline__ uint64_t bdesc(uint32_t addr, uint32_t sbo) {
    return (uint64_t)((addr & 0x3FFFFu) >> 4) | ((uint64_t)(128 >> 4) << 16) | ((uint64_t)(sbo >> 4) << 32);
}
__device__ __forceinline__ void wg_h(uint32_t (&d)[16], const uint32_t* a, const uint32_t* b, uint64_t d0, uint64_t d1, uint64_t d2, uint64_t d3) {
    asm volatile(
        "wgmma.mma_async.sync.aligned.m64n64k16.f16.f16.f16 {%0,%1,%2,%3,%4,%5,%6,%7,%8,%9,%10,%11,%12,%13,%14,%15}, {%16,%17,%18,%19}, %32, 0, 1, 1, 1;\n"
        "wgmma.mma_async.sync.aligned.m64n64k16.f16.f16.f16 {%0,%1,%2,%3,%4,%5,%6,%7,%8,%9,%10,%11,%12,%13,%14,%15}, {%20,%21,%22,%23}, %33, 1, 1, 1, 1;\n"
        "wgmma.mma_async.sync.aligned.m64n64k16.f16.f16.f16 {%0,%1,%2,%3,%4,%5,%6,%7,%8,%9,%10,%11,%12,%13,%14,%15}, {%24,%25,%26,%27}, %34, 1, 1, 1, 1;\n"
        "wgmma.mma_async.sync.aligned.m64n64k16.f16.f16.f16 {%0,%1,%2,%3,%4,%5,%6,%7,%8,%9,%10,%11,%12,%13,%14,%15}, {%28,%29,%30,%31}, %35, 1, 1, 1, 1;\n"
        : "=r"(d[0]), "=r"(d[1]), "=r"(d[2]), "=r"(d[3]), "=r"(d[4]), "=r"(d[5]), "=r"(d[6]), "=r"(d[7]), "=r"(d[8]), "=r"(d[9]), "=r"(d[10]), "=r"(d[11]), "=r"(d[12]), "=r"(d[13]), "=r"(d[14]), "=r"(d[15])
        : "r"(a[0]), "r"(a[1]), "r"(a[2]), "r"(a[3]), "r"(a[4]), "r"(a[5]), "r"(a[6]), "r"(a[7]), "r"(b[0]), "r"(b[1]), "r"(b[2]), "r"(b[3]), "r"(b[4]), "r"(b[5]), "r"(b[6]), "r"(b[7]), "l"(d0), "l"(d1), "l"(d2), "l"(d3));
}
__device__ __forceinline__ void wg_f0(float (&d)[32], const uint32_t* a, const uint32_t* b, uint64_t d0, uint64_t d1, uint64_t d2, uint64_t d3) {
    asm volatile(
        "wgmma.mma_async.sync.aligned.m64n64k16.f32.f16.f16 {%0,%1,%2,%3,%4,%5,%6,%7,%8,%9,%10,%11,%12,%13,%14,%15,%16,%17,%18,%19,%20,%21,%22,%23,%24,%25,%26,%27,%28,%29,%30,%31}, {%32,%33,%34,%35}, %48, 0, 1, 1, 1;\n"
        "wgmma.mma_async.sync.aligned.m64n64k16.f32.f16.f16 {%0,%1,%2,%3,%4,%5,%6,%7,%8,%9,%10,%11,%12,%13,%14,%15,%16,%17,%18,%19,%20,%21,%22,%23,%24,%25,%26,%27,%28,%29,%30,%31}, {%36,%37,%38,%39}, %49, 1, 1, 1, 1;\n"
        "wgmma.mma_async.sync.aligned.m64n64k16.f32.f16.f16 {%0,%1,%2,%3,%4,%5,%6,%7,%8,%9,%10,%11,%12,%13,%14,%15,%16,%17,%18,%19,%20,%21,%22,%23,%24,%25,%26,%27,%28,%29,%30,%31}, {%40,%41,%42,%43}, %50, 1, 1, 1, 1;\n"
        "wgmma.mma_async.sync.aligned.m64n64k16.f32.f16.f16 {%0,%1,%2,%3,%4,%5,%6,%7,%8,%9,%10,%11,%12,%13,%14,%15,%16,%17,%18,%19,%20,%21,%22,%23,%24,%25,%26,%27,%28,%29,%30,%31}, {%44,%45,%46,%47}, %51, 1, 1, 1, 1;\n"
        : "=f"(d[0]), "=f"(d[1]), "=f"(d[2]), "=f"(d[3]), "=f"(d[4]), "=f"(d[5]), "=f"(d[6]), "=f"(d[7]), "=f"(d[8]), "=f"(d[9]), "=f"(d[10]), "=f"(d[11]), "=f"(d[12]), "=f"(d[13]), "=f"(d[14]), "=f"(d[15]), "=f"(d[16]), "=f"(d[17]), "=f"(d[18]), "=f"(d[19]), "=f"(d[20]), "=f"(d[21]), "=f"(d[22]), "=f"(d[23]), "=f"(d[24]), "=f"(d[25]), "=f"(d[26]), "=f"(d[27]), "=f"(d[28]), "=f"(d[29]), "=f"(d[30]), "=f"(d[31])
        : "r"(a[0]), "r"(a[1]), "r"(a[2]), "r"(a[3]), "r"(a[4]), "r"(a[5]), "r"(a[6]), "r"(a[7]), "r"(b[0]), "r"(b[1]), "r"(b[2]), "r"(b[3]), "r"(b[4]), "r"(b[5]), "r"(b[6]), "r"(b[7]), "l"(d0), "l"(d1), "l"(d2), "l"(d3));
}
__device__ __forceinline__ void wg_f1(float (&d)[32], const uint32_t* a, const uint32_t* b, uint64_t d0, uint64_t d1, uint64_t d2, uint64_t d3) {
    asm volatile(
        "wgmma.mma_async.sync.aligned.m64n64k16.f32.f16.f16 {%0,%1,%2,%3,%4,%5,%6,%7,%8,%9,%10,%11,%12,%13,%14,%15,%16,%17,%18,%19,%20,%21,%22,%23,%24,%25,%26,%27,%28,%29,%30,%31}, {%32,%33,%34,%35}, %48, 1, 1, 1, 1;\n"
        "wgmma.mma_async.sync.aligned.m64n64k16.f32.f16.f16 {%0,%1,%2,%3,%4,%5,%6,%7,%8,%9,%10,%11,%12,%13,%14,%15,%16,%17,%18,%19,%20,%21,%22,%23,%24,%25,%26,%27,%28,%29,%30,%31}, {%36,%37,%38,%39}, %49, 1, 1, 1, 1;\n"
        "wgmma.mma_async.sync.aligned.m64n64k16.f32.f16.f16 {%0,%1,%2,%3,%4,%5,%6,%7,%8,%9,%10,%11,%12,%13,%14,%15,%16,%17,%18,%19,%20,%21,%22,%23,%24,%25,%26,%27,%28,%29,%30,%31}, {%40,%41,%42,%43}, %50, 1, 1, 1, 1;\n"
        "wgmma.mma_async.sync.aligned.m64n64k16.f32.f16.f16 {%0,%1,%2,%3,%4,%5,%6,%7,%8,%9,%10,%11,%12,%13,%14,%15,%16,%17,%18,%19,%20,%21,%22,%23,%24,%25,%26,%27,%28,%29,%30,%31}, {%44,%45,%46,%47}, %51, 1, 1, 1, 1;\n"
        : "+f"(d[0]), "+f"(d[1]), "+f"(d[2]), "+f"(d[3]), "+f"(d[4]), "+f"(d[5]), "+f"(d[6]), "+f"(d[7]), "+f"(d[8]), "+f"(d[9]), "+f"(d[10]), "+f"(d[11]), "+f"(d[12]), "+f"(d[13]), "+f"(d[14]), "+f"(d[15]), "+f"(d[16]), "+f"(d[17]), "+f"(d[18]), "+f"(d[19]), "+f"(d[20]), "+f"(d[21]), "+f"(d[22]), "+f"(d[23]), "+f"(d[24]), "+f"(d[25]), "+f"(d[26]), "+f"(d[27]), "+f"(d[28]), "+f"(d[29]), "+f"(d[30]), "+f"(d[31])
        : "r"(a[0]), "r"(a[1]), "r"(a[2]), "r"(a[3]), "r"(a[4]), "r"(a[5]), "r"(a[6]), "r"(a[7]), "r"(b[0]), "r"(b[1]), "r"(b[2]), "r"(b[3]), "r"(b[4]), "r"(b[5]), "r"(b[6]), "r"(b[7]), "l"(d0), "l"(d1), "l"(d2), "l"(d3));
}
__device__ __forceinline__ void wg_s(uint32_t* d, const uint32_t* a, const uint32_t* b, uint64_t d0, uint64_t d1) {
    asm volatile(
        "wgmma.mma_async.sync.aligned.m64n32k16.f16.f16.f16 {%0,%1,%2,%3,%4,%5,%6,%7}, {%8,%9,%10,%11}, %16, 0, 1, 1, 1;\n"
        "wgmma.mma_async.sync.aligned.m64n32k16.f16.f16.f16 {%0,%1,%2,%3,%4,%5,%6,%7}, {%12,%13,%14,%15}, %17, 1, 1, 1, 1;\n"
        : "=r"(d[0]), "=r"(d[1]), "=r"(d[2]), "=r"(d[3]), "=r"(d[4]), "=r"(d[5]), "=r"(d[6]), "=r"(d[7])
        : "r"(a[0]), "r"(a[1]), "r"(a[2]), "r"(a[3]), "r"(b[0]), "r"(b[1]), "r"(b[2]), "r"(b[3]), "l"(d0), "l"(d1));
}
template <int ACC> __device__ __forceinline__ void wg_w(float (&d)[4], uint64_t da, uint64_t db) {
    asm volatile("wgmma.mma_async.sync.aligned.m64n8k16.f32.bf16.bf16 {%0,%1,%2,%3}, %4, %5, %6, 1, 1, 1, 0;"
                 : "+f"(d[0]), "+f"(d[1]), "+f"(d[2]), "+f"(d[3]) : "l"(da), "l"(db), "n"(ACC));
}
__device__ __forceinline__ void wg_w0(float (&d)[4], uint64_t da, uint64_t db) {
    asm volatile("wgmma.mma_async.sync.aligned.m64n8k16.f32.bf16.bf16 {%0,%1,%2,%3}, %4, %5, 0, 1, 1, 1, 0;"
                 : "=f"(d[0]), "=f"(d[1]), "=f"(d[2]), "=f"(d[3]) : "l"(da), "l"(db));
}
__device__ __forceinline__ void wg_fence() { asm volatile("wgmma.fence.sync.aligned;" ::: "memory"); }
__device__ __forceinline__ void wg_commit() { asm volatile("wgmma.commit_group.sync.aligned;" ::: "memory"); }
template <int N> __device__ __forceinline__ void wg_wait() { asm volatile("wgmma.wait_group.sync.aligned %0;" :: "n"(N) : "memory"); }
__device__ __forceinline__ void touch(uint32_t& r) { asm volatile("" : "+r"(r) :: "memory"); }
__device__ __forceinline__ void touch(float& r) { asm volatile("" : "+f"(r) :: "memory"); }
template <class T, int N> __device__ __forceinline__ void touch(T (&r)[N]) {
#pragma unroll
    for (int i = 0; i < N; i++) touch(r[i]);
}

__global__ void __cluster_dims__(2, 1, 1) __launch_bounds__(NTHREADS, 1)
fused_kernel(const Params p, const __grid_constant__ CUtensorMap tm_x, const __grid_constant__ CUtensorMap tm_g,
             const __grid_constant__ CUtensorMap tm_d)
{
    extern __shared__ __align__(1024) uint8_t smem_raw[];
    const uint32_t sm = (uint32_t)__cvta_generic_to_shared(smem_raw);
    const uint32_t bars = sm + SM_BAR;
    const int tid = threadIdx.x, lane = tid & 31;
    const int g = lane >> 2, q = lane & 3;
    const int c = blockIdx.x, rank = c & 1, G = c >> 1;

    if (tid < 256) {
        uint2 lar4, aim4, cr4, ci4;
        uint32_t ldt_raw, dsk_raw;
        {
            const uint32_t i = c * 256 + tid;
            asm volatile("ld.global.nc.v2.u32 {%0,%1}, [%10]; ld.global.nc.v2.u32 {%2,%3}, [%11]; ld.global.nc.u16 %8, [%14];\n"
                         "ld.global.nc.v2.u32 {%4,%5}, [%12]; ld.global.nc.v2.u32 {%6,%7}, [%13]; ld.global.nc.u16 %9, [%15];"
                         : "=r"(lar4.x), "=r"(lar4.y), "=r"(aim4.x), "=r"(aim4.y), "=r"(cr4.x), "=r"(cr4.y), "=r"(ci4.x), "=r"(ci4.y), "=r"(ldt_raw), "=r"(dsk_raw)
                         : "l"(p.lar + i * 4), "l"(p.aim + i * 4), "l"(p.cr + i * 4), "l"(p.ci + i * 4), "l"(p.logdt + (i >> 5)), "l"(p.dskip + (i >> 5)));
        }
        cluster_arrive();
        sched_fence();
        const int warp = __shfl_sync(0xFFFFFFFFu, tid >> 5, 0);
        const float logdt = blo(ldt_raw), dsk = blo(dsk_raw);
        asm volatile("setmaxnreg.inc.sync.aligned.u32 168;");
        const int wgi = warp >> 2, w = warp & 3;
        const uint32_t wb = sm + SM_K + (w < 2 ? 16 * w + 8 * wgi : 16 + 16 * wgi + 8 * w) * SUB;
        sth(wb + lane * 4, hc{0x3C003C00u, 0u});
        const uint32_t tb0 = pin(sm + SM_S + (16 * wgi + w) * SUB + lane * 16), tb1 = pin(sm + SM_S + (16 * wgi + w) * SUB + ((lane + 1) & 31) * 16);
        const uint32_t seg = pin(sm + SM_K + (2 * warp + (lane & 1)) * SUB + (lane >> 1) * 16);
        const uint32_t zst = pin(sm + SM_S + (16 * wgi + (lane >> 4)) * SUB + (16 * w + (lane & 15)) * 16);
        sched_fence();

        {
            const uint32_t z = (uint32_t)(uintptr_t)p.lar & 1;
            lar4.x = cpy(lar4.x, z); lar4.y = cpy(lar4.y, z); aim4.x = cpy(aim4.x, z); aim4.y = cpy(aim4.y, z);
            cr4.x = cpy(cr4.x, z); cr4.y = cpy(cr4.y, z); ci4.x = cpy(ci4.x, z); ci4.y = cpy(ci4.y, z);
        }
        const float dt = rb(expf(logdt));
        float outscale, cs, dn;
        {
            uint32_t m0 = __vmaxu2(__vmaxu2(cr4.x & 0x7FFF7FFFu, cr4.y & 0x7FFF7FFFu), __vmaxu2(ci4.x & 0x7FFF7FFFu, ci4.y & 0x7FFF7FFFu));
            uint32_t m1 = max(m0 & 0xFFFFu, m0 >> 16);
            float cmax = blo(__reduce_max_sync(0xFFFFFFFFu, m1));
            const float sc = fminf(fmaxf(fmaxf(2.0f * dt * cmax, fabsf(dsk) * (1.0f / 1024.0f)), 1e-30f), 1e30f);
            outscale = __uint_as_float(__float_as_uint(sc) & 0x7F800000u);
            const float inv = __uint_as_float(0x7F000000u - __float_as_uint(outscale));
            cs = 2.0f * dt * inv * (1.0f / 512.0f);
            dn = dsk * inv * (1.0f / 512.0f);
            if (lane == 0) sts16(sm + SM_SCL + warp * 2, __float_as_uint(32768.0f * outscale) >> 16);
        }
        if (warp == TSW) TSL(39);
        uint32_t fc[16], fs[16], ta[4], tb[4];
        float kacc[2][3][4];
#pragma unroll
        for (int i = 0; i < 2; i++)
#pragma unroll
            for (int j = 0; j < 3; j++) kacc[i][j][0] = kacc[i][j][1] = kacc[i][j][2] = kacc[i][j][3] = 0.f;
        if (lane == 0) kacc[0][0][0] = dn;
        {
            const uint32_t st = wb + lane * 4;
            const uint32_t zk = lds32(wb + 128);
            const uint32_t la = wb + ((lane & 8) ? 29 : (lane & 7)) * KP + (lane >> 4) * 128;
            const uint32_t lo = wb + ((lane >> 3) & 1) * 128 + (lane >> 4) * 16;
            const uint32_t lb = lo + (8 + (lane & 7)) * KP, lb2 = lo + (24 + min(lane & 7, 4)) * KP, lm = lo + 30 * KP;
#pragma unroll 1
            for (int s = 0; s < 2; s++) {
                const uint32_t wl = s ? lar4.y : lar4.x, wa = s ? aim4.y : aim4.x, wr_ = s ? cr4.y : cr4.x, wi = s ? ci4.y : ci4.x;
                const uint32_t ea = pack_b(ex2(blo(wl) * 1.4426950408889634f), ex2(bhi(wl) * 1.4426950408889634f));
                const float a2[2] = {-(blo(ea) * dt) * 1.4426950408889634f, -(bhi(ea) * dt) * 1.4426950408889634f};
                const float b[2] = {blo(wa) * dt, bhi(wa) * dt};
                {
                    cf z8[2], z16[2], z32[2], z64[2], z128[2];
#pragma unroll
                    for (int e = 0; e < 2; e++) {
                        z8[e] = cexp_(a2[e] * 8.f, b[e] * 8.f);
                        z16[e] = csq(z8[e]); z32[e] = csq(z16[e]); z64[e] = csq(z32[e]); z128[e] = csq(z64[e]);
                    }
                    const hc r1 = pk(z8[0], z8[1]), r2 = pk(z16[0], z16[1]), r3 = hmulc(r1, r2), r4 = pk(z32[0], z32[1]);
                    sth(st + 1 * KP, r1); sth(st + 2 * KP, r2); sth(st + 3 * KP, r3); sth(st + 4 * KP, r4);
                    sth(st + 5 * KP, hmulc(r1, r4)); sth(st + 6 * KP, hmulc(r2, r4)); sth(st + 7 * KP, hmulc(r3, r4));
                    sth(st + 29 * KP, pk(z64[0], z64[1])); sth(st + 30 * KP, pk(z128[0], z128[1]));
                }
                {
                    cf C[2], z2[2], z4[2], v2[2], v4[2], c1[2], d1[2];
#pragma unroll
                    for (int e = 0; e < 2; e++) {
                        C[e] = {(e ? bhi(wr_) : blo(wr_)) * cs, (e ? bhi(wi) : blo(wi)) * -cs};
                        const cf z = cexp_(a2[e], -b[e]);
                        const cf v = cexp_(a2[e] * 256.f, b[e] * -256.f);
                        z2[e] = csq(z); z4[e] = csq(z2[e]); v2[e] = csq(v); v4[e] = csq(v2[e]);
                        c1[e] = cmul(C[e], z); d1[e] = cmul(C[e], v);
                    }
                    const hc l0 = pk(C[0], C[1]), l1 = pk(c1[0], c1[1]), e1 = pk(d1[0], d1[1]);
                    const hc h = pk(z2[0], z2[1]), f = pk(z4[0], z4[1]), w = pk(v2[0], v2[1]), y = pk(v4[0], v4[1]);
                    const hc l2 = hmulc(l0, h), l3 = hmulc(l1, h), e2 = hmulc(l0, w), e3 = hmulc(e1, w), e4 = hmulc(l0, y), g2 = hmulc(e1, h);
                    sth(st + 8 * KP, l0); sth(st + 9 * KP, l1); sth(st + 10 * KP, l2); sth(st + 11 * KP, l3);
                    sth(st + 12 * KP, hmulc(l0, f)); sth(st + 13 * KP, hmulc(l1, f)); sth(st + 14 * KP, hmulc(l2, f)); sth(st + 15 * KP, hmulc(l3, f));
                    sth(st + 16 * KP, e1);
                    sth(st + 17 * KP, g2);
                    sth(st + 18 * KP, hmulc(e1, f));
                    sth(st + 19 * KP, hmulc(g2, f));
                    sth(st + 20 * KP, e2);
                    sth(st + 21 * KP, hmulc(e2, f));
                    sth(st + 22 * KP, e3);
                    sth(st + 23 * KP, hmulc(e3, f));
                    sth(st + 24 * KP, e4);
                    sth(st + 25 * KP, hmulc(e1, y));
                    sth(st + 26 * KP, hmulc(e2, y));
                    sth(st + 27 * KP, hmulc(e3, y));
                    sth(st + 28 * KP, hmulc(e4, y));
                }
                __syncwarp();
                if (warp == TSW && s == 0) TSL(27);
                if (s == 1 && lane == 0) mbar_arrive(bars + B_TFREE * 8 + (tb[3] & zk));
#pragma unroll
                for (int kp = 0; kp < 4; kp++) {
                    uint32_t bb[3][4], m2[4];
                    ldsm4(lm + kp * 32, m2[0], m2[1], m2[2], m2[3]);
                    ldsm4(lb + kp * 32, bb[0][0], bb[0][1], bb[0][2], bb[0][3]);
                    ldsm4(lb + 8 * KP + kp * 32, bb[1][0], bb[1][1], bb[1][2], bb[1][3]);
                    ldsm4(lb2 + kp * 32, bb[2][0], bb[2][1], bb[2][2], bb[2][3]);
#pragma unroll
                    for (int k2 = 0; k2 < 2; k2++) {
                        hc v0, m1;
                        ldsm4(la + kp * 32 + k2 * 16, v0.r, m1.r, v0.i, m1.i);
                        const hc mm = {m2[2 * k2], m2[2 * k2 + 1]};
                        const hc v1 = hmulc(v0, m1), v2 = hmulc(v0, mm), v3 = hmulc(v1, mm);
                        v0.r = cpy(v0.r, zk); v0.i = cpy(v0.i, zk);
#pragma unroll
                        for (int nt = 0; nt < 3; nt++) {
                            mma_f16(kacc[0][nt], v0.r, v1.r, v0.i, v1.i, bb[nt][2 * k2], bb[nt][2 * k2 + 1]);
                            mma_f16(kacc[1][nt], v2.r, v3.r, v2.i, v3.i, bb[nt][2 * k2], bb[nt][2 * k2 + 1]);
                        }
                    }
                }
                __syncwarp();
                if (warp == TSW) TSL(s ? 40 : 33);
                if (s == 0) {
                    cluster_wait();
                    mbar_wait(bars + B_TAB * 8);
#pragma unroll
                    for (int i = 0; i < 10; i++) {
                        const uint4 u = lds128(sm + SM_TAB + i * 2048 + (tid & 127) * 16);
                        uint32_t* t = i < 4 ? fc + 4 * i : i < 8 ? fs + 4 * (i - 4) : i == 8 ? ta : tb;
                        t[0] = u.x; t[1] = u.y; t[2] = u.z; t[3] = u.w;
                    }
                }
            }
        }
        TSL(1);
        bar_sync(10 + wgi, 128);
        {
            uint32_t v[3][4];
#pragma unroll
            for (int i = 0; i < 12; i++) v[i >> 2][i & 3] = pack_h(kacc[(i >> 1) & 1][i >> 2][2 * (i & 1)], kacc[(i >> 1) & 1][i >> 2][2 * (i & 1) + 1]);
            stsm4(tb0, v[1][0], v[1][1], v[1][2], v[1][3]);
            stsm4(tb0 + 512, v[2][0], v[2][1], v[2][2], v[2][3]);
            stsm4(seg, v[0][0], v[0][1], v[0][2], v[0][3]);
            __syncwarp();
            const uint4 a = lds128(tb0), na = lds128(tb1), nb = lds128(tb1 + 512);
            const uint2 b = lds64(tb0 + 512);
            const bool last = lane == 31;
            const uint32_t n1 = last ? na.z : na.x, n2 = last ? na.w : na.z, n3 = last ? nb.x : na.w;
            const uint32_t sn = last ? 0x5432 : 0x3210, n4 = prmt(nb.x, nb.y, sn), n5 = prmt(nb.y, nb.z, sn);
            sts128(seg + 256, prmt(a.x, 0, 0x1010), prmt(a.x, a.y, 0x5432), prmt(a.y, 0, 0x1010), prmt(a.y, n1, 0x5432));
            sts128(seg + 512, prmt(a.z, 0, 0x1010), a.z, prmt(a.z, 0, 0x3232), prmt(n2, 0, 0x1010));
            sts128(seg + 768, prmt(a.w, 0, 0x1010), a.w, prmt(a.w, 0, 0x3232), prmt(n3, 0, 0x1010));
            const uint32_t s3 = (lane & 1) ? 0x5454 : 0x5410;
#pragma unroll
            for (int i = 0; i < 4; i++) {
                const uint32_t cur = (i & 2) ? b.y : b.x, nx = (i & 2) ? n5 : n4, h = (i & 1) * 0x2222;
                const uint32_t vv = prmt(cur, 0, 0x1010 + h);
                sts128(seg + 16 * SUB + i * 256, vv, vv, prmt(cur, nx, s3 + h), prmt(nx, 0, 0x1010 + h));
            }
        }
        proxy_fence();
        TSL(2);
        bar_sync(10 + wgi, 128);
        const uint64_t dre = bdesc(sm + SM_F2 + 512, 256), dim = bdesc(sm + SM_F2, 256);
        uint32_t k0[32], k1[32];
#pragma unroll
        for (int b = 0; b < 2; b++) {
            const uint64_t d1 = bdesc(sm + SM_K + (16 * b + 8 * wgi) * SUB, SUB);
            uint32_t re[16], im[16];
            if (b == 0 && wgi == 1) bar_sync(5, 256);
            wg_fence();
            wg_h(re, fc, fc + 8, d1, d1 + 16, d1 + 32, d1 + 48);
            wg_h(im, fs, fs + 8, d1, d1 + 16, d1 + 32, d1 + 48);
            wg_commit();
            if (b == 0 && wgi == 0) bar_arrive(5, 256);
            wg_wait<0>();
            touch(re); touch(im);
            if (lane == 0) mbar_arrive(bars + (B_KFREE + b) * 8);
            uint32_t (&kk)[32] = b ? k1 : k0;
#pragma unroll
            for (int hh = 0; hh < 2; hh++) {
#pragma unroll
                for (int i = 8 * hh; i < 8 * hh + 8; i++) {
                    re[i] = hfma2_(ta[i & 3], im[i], re[i]); im[i] = hfms2_(tb[i & 3], re[i], im[i]); re[i] = hfma2_(ta[i & 3], im[i], re[i]);
                }
                wg_fence();
                wg_s(kk + 16 * hh, re + 8 * hh, im + 8 * hh, dre, dim);
                wg_s(kk + 16 * hh + 8, re + 8 * hh + 4, im + 8 * hh + 4, dre, dim);
                wg_commit();
            }
            wg_wait<0>();
            touch(kk);
        }
        if (warp == TSW) TSL(35);
        asm volatile("setmaxnreg.inc.sync.aligned.u32 184;");
        touch(k1);
        {
            const uint32_t sg = (g & 1) ? 0xBC00BC00u : 0x3C003C00u;
#pragma unroll
            for (int i = 0; i < 16; i++) {
                const int r = 8 * (i >> 2) + (i & 3);
                k1[r] = hfms2_(sg, k0[r + 4], k1[r]); k1[r + 4] = hfma2_(sg, k0[r], k1[r + 4]);
            }
            touch(k1);
        }
        const uint32_t peer = mapa(sm, rank ^ 1), so = SM_U + 8 * wgi * SUB + w * 1024 + (8 * q + (g ^ (2 * q))) * 16;
        const uint2 sc = lds64(sm + SM_SCL + wgi * 8);
#pragma unroll 1
        for (int b = 0; b < 2; b++) {
            const uint32_t zb = sm + SM_S + 16 * wgi * SUB;
            constexpr int zi = 8 * SUB;
            uint32_t re[16], im[16], su[2][16], z[2][16], y[2][16];
            auto twiddle = [&](int hh) {
#pragma unroll
                for (int i = 8 * hh; i < 8 * hh + 8; i++) {
                    re[i] = hfma2_(ta[i & 3], im[i], re[i]); im[i] = hfms2_(tb[i & 3], re[i], im[i]); re[i] = hfma2_(ta[i & 3], im[i], re[i]);
                    touch(re[i]); touch(im[i]);
                }
            };
            auto dft16 = [&](int hh) {
                wg_fence();
                wg_s(su[hh], re + 8 * hh, im + 8 * hh, dre, dim); wg_s(su[hh] + 8, re + 8 * hh + 4, im + 8 * hh + 4, dre, dim);
                wg_commit();
                sched_fence();
            };
            auto product = [&](int hh) {
                if (b == 0) {
#pragma unroll
                    for (int i = 0; i < 8; i++) {
                        const int r = 8 * (i >> 2) + (i & 3), kr = 16 * hh + r;
                        const hc u = {su[hh][r], su[hh][r + 4]};
                        const hc t = hmulc(u, hc{k0[kr], k0[kr + 4]}), pp = hmulc(u, hc{k1[kr], k1[kr + 4]});
                        z[hh][r] = t.r; z[hh][r + 4] = t.i; k1[kr] = pp.r; k1[kr + 4] = pp.i;
                        touch(k1[kr]); touch(k1[kr + 4]);
                    }
                } else {
#pragma unroll
                    for (int i = 0; i < 8; i++) {
                        const int r = 8 * (i >> 2) + (i & 3), kr = 16 * hh + r;
                        const hc u = {su[hh][r], su[hh][r + 4]};
                        z[hh][r] = hfms2_(u.i, k0[kr + 4], hfma2_(u.r, k0[kr], k1[kr]));
                        z[hh][r + 4] = hfma2_(u.i, k0[kr], hfma2_(u.r, k0[kr + 4], k1[kr + 4]));
                    }
                }
                touch(z[hh]);
            };
            auto idft16 = [&](int hh) {
                wg_fence();
                wg_s(y[hh], z[hh] + 4, z[hh], dre, dim); wg_s(y[hh] + 8, z[hh] + 12, z[hh] + 8, dre, dim);
                wg_commit();
                sched_fence();
            };
            auto untwiddle = [&](int hh) {
#pragma unroll
                for (int i = 0; i < 2; i++) {
                    uint32_t* const yi = y[hh] + 8 * i, * const yr = yi + 4;
#pragma unroll
                    for (int n = 0; n < 4; n++) {
                        yr[n] = hfms2_(ta[n], yi[n], yr[n]); yi[n] = hfma2_(tb[n], yr[n], yi[n]); yr[n] = hfms2_(ta[n], yi[n], yr[n]);
                    }
                    const uint32_t a = zst + (4 * hh + 2 * i) * SUB;
                    stsm4(a, yr[0], yr[1], yr[2], yr[3]);
                    stsm4(a + zi, yi[0], yi[1], yi[2], yi[3]);
                }
            };
            auto done = [&]() { sched_fence(); wg_wait<0>(); };
            {
                const uint64_t d1 = bdesc(sm + SM_U + (16 * b + 8 * wgi) * SUB, SUB);
                mbar_wait(bars + (B_U + b) * 8);
                proxy_fence();
                if (b == 0) { TSL(3); if (wgi == 1) bar_sync(9, 256); }
                wg_fence();
                wg_h(re, fc, fc + 8, d1, d1 + 16, d1 + 32, d1 + 48);
                wg_h(im, fs, fs + 8, d1, d1 + 16, d1 + 32, d1 + 48);
                wg_commit();
                if (b == 0 && wgi == 0) bar_arrive(9, 256);
                wg_wait<0>();
                touch(re); touch(im);
            }
            if (lane == 0) mbar_arrive_peer(peer + SM_BAR + (B_PEER + 2 * wgi + b) * 8);
            twiddle(0); twiddle(1); dft16(0); dft16(1);
            wg_wait<1>(); touch(su[0]);
            product(0); done(); touch(su[1]); idft16(0);
            product(1); done(); touch(y[0]); idft16(1);
            bar_sync(10 + wgi, 128);
            untwiddle(0); done(); touch(y[1]);
            untwiddle(1);
            proxy_fence();
            if (warp == TSW) TSL(36 + b);
            bar_sync(10 + wgi, 128);
            float acc[32];
            const uint64_t d4 = bdesc(zb, SUB);
            wg_fence();
            wg_f0(acc, fc, fc + 8, d4, d4 + 16, d4 + 32, d4 + 48);
            wg_f1(acc, fs, fs + 8, d4 + zi / 16, d4 + zi / 16 + 16, d4 + zi / 16 + 32, d4 + zi / 16 + 48);
            wg_commit();
            mbar_wait(bars + (B_PEER + 2 * wgi + b) * 8);
            wg_wait<0>();
            touch(acc);
            uint32_t s[2][2][4];
#pragma unroll
            for (int i = 0; i < 8; i++) {
                s[i >> 2][(i >> 1) & 1][2 * (i & 1)] = bmul2(pack_b(acc[i], acc[8 + i]), sc.x);
                s[i >> 2][(i >> 1) & 1][2 * (i & 1) + 1] = bmul2(pack_b(acc[16 + i], acc[24 + i]), sc.y);
            }
            const uint32_t sb = SM_BAR + (B_STG + b) * 8;
#pragma unroll
            for (int j = 0; j < 2; j++)
                if (j == rank) {
#pragma unroll
                    for (int hi = 0; hi < 2; hi++) {
                        const uint32_t (&r)[4] = s[1 - j][hi], (&l)[4] = s[j][hi];
                        st_async4(peer + so + 16 * b * SUB + hi * 512, r[0], r[1], r[2], r[3], peer + sb);
                        sts128(sm + (so ^ 64) + (16 * b + 4) * SUB + hi * 512, l[0], l[1], l[2], l[3]);
                    }
                }
            __syncwarp();
            if (lane == 0) mbar_arrive(sm + sb);
            if (warp == TSW) TSL(5 + b);
        }
        TSL(7);
    } else {
    const int warp = __shfl_sync(0xFFFFFFFFu, tid >> 5, 0);
    if (warp < 12) {
        const int v = warp - 8;
        cluster_arrive();
        const uint32_t xs = sm + SM_U + v * 8192;
        if (elect()) {
#pragma unroll
            for (int r = 0; r < 2; r++) mbar_init(bars + (B_ROW + 2 * v + r) * 8, 1);
            asm volatile("fence.mbarrier_init.release.cluster;" ::: "memory");
#pragma unroll
            for (int e = 0; e < 2; e++) {
                if (e) { const int t0_ = clock(); while ((int)clock() - t0_ < EDELAY) __nanosleep(40); }
                mbar_expect(bars + (B_ROW + 2 * v + e) * 8, 4096);
#pragma unroll
                for (int r = 0; r < 2; r++)
                    asm volatile("cp.async.bulk.shared::cluster.global.mbarrier::complete_tx::bytes [%0], [%1], 2048, [%2];"
                                 :: "r"(xs + e * 4096 + r * 2048), "l"(p.x + (size_t)(128 * (c & 15) + 32 * v + 16 * r + 2 * (c >> 4) + e) * 1024),
                                    "r"(bars + (B_ROW + 2 * v + e) * 8) : "memory");
            }
        }
        __syncwarp();
        uint4 w4[4];
#pragma unroll
        for (int k = 0; k < 4; k++) w4[k] = ldg128(reinterpret_cast<const uint4*>(p.wr) + 32 * k + lane);
        {
            constexpr uint32_t ONE = 0x3F803F80u;
            const uint32_t zr = p.up_first >> 1;
            uint4 w5[4];
#pragma unroll
            for (int k = 0; k < 4; k++) {
                w5[k].x = w4[k].x + zr; w5[k].y = w4[k].y + zr; w5[k].z = w4[k].z + zr; w5[k].w = w4[k].w + zr;
                w4[k].x = cpy(w4[k].x, zr); w4[k].y = cpy(w4[k].y, zr); w4[k].z = cpy(w4[k].z, zr); w4[k].w = cpy(w4[k].w, zr);
            }
            const bool od = g & 1;
#pragma unroll 1
            for (int r2 = 0; r2 < 2; r2++) {
                mbar_wait(bars + (B_ROW + 2 * v + r2) * 8);
                TSL(43);
                float s1[2][4] = {}, q0[2][4] = {};
#pragma unroll
                for (int k = 0; k < 4; k++)
#pragma unroll
                    for (int r = 0; r < 2; r++) {
                        const uint4 x = lds128(xs + r2 * 4096 + r * 2048 + k * 512 + lane * 16);
                        const uint4& ww = r ? w5[k] : w4[k];
                        mma_bf16(q0[r], cpy(x.x, zr), ww.x, cpy(x.y, zr), ww.y, x.x, x.y);
                        mma_bf16(s1[r], x.x, x.y, x.z, x.w, ONE, ONE);
                        mma_bf16(q0[r], cpy(x.z, zr), ww.z, cpy(x.w, zr), ww.w, x.z, x.w);
                    }
#pragma unroll
                for (int r = 0; r < 2; r++)
                    if (q == (g >> 1))
                        sts128(sm + SM_RED + (4 * v + r2 + 2 * r) * 144 + g * 16, __float_as_uint(od ? q0[r][1] : q0[r][0]),
                               __float_as_uint(od ? q0[r][3] : q0[r][2]), __float_as_uint(s1[r][0]), __float_as_uint(s1[r][2]));
            }
            bar_arrive(7, 160);
        }
        TSL(8);
        bar_sync(6, 160);
        const uint32_t tag = lds32(sm + SM_TOK + 8);
        cluster_wait();
        asm volatile("setmaxnreg.dec.sync.aligned.u32 104;");
        const uint32_t peer = mapa(sm, rank ^ 1);
        if (v == 0 && lane == 0) mbar_arrive_peer(peer + SM_BAR + B_UFREE * 8);
        {
            uint4 st[8];
            const uint4* src = p.sc->stats[G & (NREP - 1)] + rank * 512 + 16 * v + (lane >> 1);
            const uint32_t tb = ((tag & 1) << 15) | ((tag >> 1) << 31);
            const uint32_t xo = pin(sm + SM_SLAB + v * 512 + lane * 16);
            const uint32_t ub = pin(mapa(bars + B_U * 8, lane & 1)), ud = pin(mapa(sm + SM_U + rank * SUB + (16 * v + (lane >> 1)) * 16, lane & 1));
            bar_sync(3, 192);
            if (warp == 8) TSL(44);
#pragma unroll
            for (int i = 0; i < 8; i++) st[i] = ld_relaxed128(src + (i >> 2) * 64 + (i & 3) * 128);
            uint4 x0[8];
            mbar_wait(bars + B_UFREE * 8);
            mbar_wait(bars + B_SLAB * 8);
#pragma unroll
            for (int i = 0; i < 8; i++) x0[i] = lds128(xo + (i & 1) * 8192 + (i >> 1) * 2048);
            for (int it = 0; it < SPIN_LIMIT; it++) {
                uint32_t bad = 0;
#pragma unroll
                for (int i = 0; i < 8; i++) bad |= st[i].z ^ tb;
                if (__all_sync(0xFFFFFFFFu, (bad & 0x80008000u) == 0)) break;
#pragma unroll
                for (int i = 0; i < 8; i++)
                    if ((st[i].z ^ tb) & 0x80008000u) st[i] = ld_relaxed128(src + (i >> 2) * 64 + (i & 3) * 128);
            }
            TSL(11); TG(31);
#pragma unroll
            for (int i = 0; i < 8; i++) st[i].z &= 0x7FFF7FFFu;
            const bool own = (lane & 1) == rank;
            uint32_t n[2][8][4];
#pragma unroll
            for (int b = 0; b < 2; b++) {
                if (b) mbar_wait(bars + (B_SLAB + 1) * 8);
#pragma unroll
                for (int i = 0; i < 8; i++) {
                    const uint4 x = b ? lds128(xo + 16384 + (i & 1) * 8192 + (i >> 1) * 2048) : x0[i];
                    const uint4& t = st[4 * b + (i >> 1)];
                    const uint32_t m = (i & 1) ? dup_hi(t.x) : dup_lo(t.x), hi = (i & 1) ? dup_hi(t.z) : dup_lo(t.z), lo = (i & 1) ? dup_hi(t.y) : dup_lo(t.y);
                    uint32_t (&r)[4] = n[b][i];
                    r[0] = norm2(x.x, m, hi, lo); r[1] = norm2(x.y, m, hi, lo); r[2] = norm2(x.z, m, hi, lo); r[3] = norm2(x.w, m, hi, lo);
                    if (b && (i & 1)) sched_fence();
                }
#pragma unroll
                for (int cp = 0; cp < 4; cp++) {
                    float f[8][2];
#pragma unroll
                    for (int i = 0; i < 8; i++) { f[i][0] = blo(n[b][i][cp]); f[i][1] = bhi(n[b][i][cp]); }
#pragma unroll
                    for (int h = 0; h < 2; h++)
                        st_async4(ud + (16 * b + 4 * cp + 2 * h) * SUB, pack_h(f[0][h], f[1][h]), pack_h(f[2][h], f[3][h]),
                                  pack_h(f[4][h], f[5][h]), pack_h(f[6][h], f[7][h]), ub + b * 8);
                    if (b) {
#pragma unroll
                        for (int i = 0; i < 8; i++) { n[1][i][cp] = pack_b(silu2(f[i][0]), silu2(f[i][1])); touch(n[1][i][cp]); }
                        sched_fence();
                    }
                }
                TSL(b ? 41 : 12);
            }
            const uint32_t zr = p.up_first >> 1;
#pragma unroll
            for (int i = 0; i < 32; i++) {
                uint32_t& r = n[0][i >> 2][i & 3];
                r = pack_b(silu2(__uint_as_float(prmt(r, zr, 0x1044))), silu2(__uint_as_float(prmt(r, zr, 0x3244))));
                touch(r);
                if ((i & 7) == 7) sched_fence();
            }
            TSL(0);
            const uint32_t stg = pin(sm + SM_U + (own ? 4 * SUB : 0) + v * 1024 + (lane >> 4) * 512 + (((lane & 14) * 8) ^ (own ? 64 : 0)));
            const int tl = pin(256 * v + 16 * (lane >> 1) + 8 * rank);
            __nv_bfloat16* const op = p.out + (size_t)tl * 1024 + G * 16 + (lane & 1) * 8;
            mbar_wait(bars + B_TOK * 8);
            const uint2 tr = lds64(sm + SM_TOK);
#pragma unroll
            for (int b = 0; b < 2; b++) {
                const int d0 = tr.x - tl - 1024 * b, d1 = tr.y - tl - 1024 * b;
                uint32_t skip = ((d0 & ~7) ? 0u : 1u << d0) | ((d1 & ~7) ? 0u : 1u << d1);
                uint4 x[8];
                if (b) {
#pragma unroll
                    for (int i = 0; i < 8; i++) x[i] = lds128(xo + b * 16384 + (i & 1) * 8192 + (i >> 1) * 2048);
                }
                mbar_wait(bars + (B_STG + b) * 8);
                if (skip) {
#pragma unroll 1
                    for (int k = 0; k < 2; k++) {
                        const int d = k ? d1 : d0;
                        if (!(d & ~7)) {
                            const uint32_t a = (stg ^ ((d & 6) * 16)) + 16 * b * SUB + (d & 6) * 64 + (d & 1) * 8, dst = mapa(sm, k);
                            const uint2 s0 = lds64(a), s1 = lds64(a + 8 * SUB);
                            st_async4(dst + SM_FIX + (lane & 1) * 16, s0.x, s0.y, s1.x, s1.y, dst + SM_BAR + B_FIX * 8);
                        }
                    }
                }
                __syncwarp();
#pragma unroll
                for (int i = 0; i < 4; i++) {
                    const uint32_t a = (stg ^ (32 * i)) + 16 * b * SUB + 128 * i;
                    const uint4 r0 = lds128(a), r1 = lds128(a + 8 * SUB);
#pragma unroll
                    for (int e = 0; e < 2; e++) {
                        if (!b) x[2 * i + e] = lds128(xo + e * 8192 + i * 2048);
                        const uint4& xx = x[2 * i + e];
                        const uint32_t s0 = e ? r0.z : r0.x, s1 = e ? r0.w : r0.y, s2 = e ? r1.z : r1.x, s3 = e ? r1.w : r1.y;
                        const uint32_t (&gt)[4] = n[b][2 * i + e];
                        asm volatile("{ .reg .pred p; setp.eq.u32 p, %5, 0; @p st.global.v4.u32 [%0], {%1,%2,%3,%4}; }"
                                     :: "l"(op + (size_t)(1024 * b + 2 * i + e) * 1024), "r"(badd2(xx.x, bmul2(s0, gt[0]))), "r"(badd2(xx.y, bmul2(s1, gt[1]))),
                                        "r"(badd2(xx.z, bmul2(s2, gt[2]))), "r"(badd2(xx.w, bmul2(s3, gt[3]))), "r"(skip & (1u << (2 * i + e))) : "memory");
                    }
                    if (!b) { sched_fence(); if (i < 3) __nanosleep(STSLEEP); }
                }
                TSL(b ? 23 : 22);
            }
            TSL(17); TG(30);
        }
    } else {
        const int v = warp - 12;
        if (lane == 0) {
            if (v == 1) {
                mbar_init(bars + B_TAB * 8, 1); mbar_init(bars + B_TFREE * 8, 8); mbar_init(bars + B_KFREE * 8, 8); mbar_init(bars + (B_KFREE + 1) * 8, 8);
                mbar_expect(bars + B_TAB * 8, 20480 + 1536);
            } else if (v == 0) {
                mbar_init(bars + B_SLAB * 8, 1); mbar_init(bars + (B_SLAB + 1) * 8, 1); mbar_init(bars + B_TOK * 8, 2); mbar_init(bars + B_UFREE * 8, 1);
                mbar_expect(bars + B_SLAB * 8, 16384); mbar_expect(bars + (B_SLAB + 1) * 8, 16384);
            } else {
                mbar_init(bars + (B_STG + v - 2) * 8, 9); mbar_init(bars + (B_FIX + v - 2) * 8, 1);
                mbar_init(bars + (B_U + v - 2) * 8, 1); mbar_expect(bars + (B_U + v - 2) * 8, 16384);
                mbar_expect(bars + (B_STG + v - 2) * 8, 8192); mbar_expect(bars + (B_FIX + v - 2) * 8, v == 2 ? 32 : 2048);
            }
            mbar_init(bars + (B_PEER + v) * 8, 4);
#pragma unroll
            for (int i = 0; i < 3; i++) { mbar_init(bars + (B_FULL + 3 * v + i) * 8, 1); mbar_expect(bars + (B_FULL + 3 * v + i) * 8, 16384); }
            asm volatile("fence.mbarrier_init.release.cluster;" ::: "memory");
        }
        __syncwarp();
        cluster_arrive();
        asm volatile("setmaxnreg.dec.sync.aligned.u32 40;");
        uint64_t pol; asm volatile("createpolicy.fractional.L2::" WPOL ".b64 %0, 1.0;" : "=l"(pol));
        auto load_chunk = [&](int n) {
            if (n < 8) tma3d(sm + chunk_off(n), &tm_g, G * 64, rank * 512 + n * 64, 0, bars + (B_FULL + n) * 8, pol);
            else tma3d(sm + chunk_off(n), &tm_d, 0, G * 64, rank * 8 + (n - 8) * 2, bars + (B_FULL + n) * 8, pol);
        };
        uint32_t* const my_part = p.sc->part + ((2 * (32 * rank + v) + (q & 1)) * 56 + G) * 16 + g + 8 * (q >> 1);
        if (G < 56) {
#pragma unroll
            for (int n = 0; n < 8; n++) st_relaxed32(my_part + n * 8 * 56 * 16, 0);
        }
        cluster_wait();
        const bool lead = elect();
        uint32_t key = 0;
        if (v == 0) {
            asm volatile("prefetch.tensormap [%0];" :: "l"(&tm_x) : "memory");
            asm volatile("prefetch.tensormap [%0];" :: "l"(&tm_g) : "memory");
            { const int t0_ = clock(); while ((int)clock() - t0_ < SDELAY) __nanosleep(40); }
            if (lead) {
                int n = 0;
#pragma unroll 1
                for (int i = 0; i < 5; i++) {
                    if (G < 56) {
#pragma unroll 1
                        for (; n < ((FILL >> (4 * i)) & 15); n++) {
                            if (n >= IDEPTH) mbar_wait(bars + (B_FULL + n - IDEPTH) * 8);
                            if (n == 3) mbar_wait(bars + B_TFREE * 8);
                            load_chunk(n);
                        }
                    }
                    if (i < 4)
                        asm volatile("cp.async.bulk.tensor.4d.shared::cluster.global.mbarrier::complete_tx::bytes [%0], [%1, {%3, %4, %5, %6}], [%2];"
                                     :: "r"(sm + SM_SLAB + (i & 1) * 16384 + (i >> 1) * 8192), "l"(&tm_x), "r"(bars + (B_SLAB + (i & 1)) * 8),
                                        "r"(G * 16), "r"(64 * (i & 1)), "r"(4 * rank), "r"(i >> 1) : "memory");
                }
                TS(20);
                if (G < 56) {
#pragma unroll 1
                    for (int i = 0; i < NPF; i++) {
                        if (i < IDEPTH) mbar_wait(bars + (B_FULL + 5 + i - IDEPTH) * 8);
                        asm volatile("cp.async.bulk.prefetch.tensor.3d.L2.global [%0, {%1, %2, %3}];" :: "l"(&tm_g), "r"(G * 64), "r"(rank * 512 + (5 + i) * 64), "r"(0) : "memory");
                    }
                    mbar_wait(bars + B_KFREE * 8); load_chunk(5);
                    mbar_wait(bars + (B_KFREE + 1) * 8); load_chunk(6);
                }
                TS(21);
            }
            __syncwarp();
        } else if (v == 1) {
            if (lead) {
                asm volatile("cp.async.bulk.shared::cluster.global.mbarrier::complete_tx::bytes [%0], [%1], 20480, [%2];"
                             :: "r"(sm + SM_TAB), "l"(p.tab), "r"(bars + B_TAB * 8) : "memory");
                asm volatile("cp.async.bulk.shared::cluster.global.mbarrier::complete_tx::bytes [%0], [%1], 1536, [%2];"
                             :: "r"(sm + SM_F2), "l"(p.tab + 1280), "r"(bars + B_TAB * 8) : "memory");
                asm volatile("prefetch.tensormap [%0];" :: "l"(&tm_d) : "memory");
            }
        } else {
            const int sw = v - 2;
            if (sw == 0) {
                uint32_t tag;
                uint4* const my_stats = p.sc->stats[q] + c * 8 + g;
                asm volatile("ld.relaxed.gpu.global.u32 %0, [%1];" : "=r"(tag) : "l"(&p.sc->epoch) : "memory");
                float ws = 0.f;
#pragma unroll
                for (int k = 0; k < 4; k++) {
                    const uint4 w = ldg128(reinterpret_cast<const uint4*>(p.wr) + 32 * k + lane);
                    ws += (blo(w.x) + bhi(w.x)) + (blo(w.y) + bhi(w.y)) + (blo(w.z) + bhi(w.z)) + (blo(w.w) + bhi(w.w));
                }
                if (q < NREP) st_relaxed128(my_stats, make_uint4(0, 0, 0, 0));
                tag = tag % 3 + 1;
                sts32(sm + SM_TOK + 8, tag);
                bar_arrive(6, 160);
#pragma unroll
                for (int o = 1; o < 32; o <<= 1) ws += __shfl_xor_sync(0xFFFFFFFFu, ws, o);
                const uint32_t tb = ((tag & 1) << 15) | ((tag >> 1) << 31);
                const uint32_t ra = sm + SM_RED + (lane >> 1) * 144 + (lane & 1) * 64;
                const uint32_t kidx = 0xFFFF - (128 * (c & 15) + 16 * (lane >> 2) + 2 * (c >> 4) + ((lane >> 1) & 1));
                touch(ws);
                bar_sync(7, 160);
                const uint4 a0 = lds128(ra), a1 = lds128(ra + 16), a2 = lds128(ra + 32), a3 = lds128(ra + 48);
#define F(v) __uint_as_float(v)
                float ss = (F(a0.x) + F(a1.x)) + (F(a2.x) + F(a3.x)), dw = (F(a0.y) + F(a1.y)) + (F(a2.y) + F(a3.y));
                float sx = ((F(a0.z) + F(a1.z)) + (F(a2.z) + F(a3.z))) + ((F(a0.w) + F(a1.w)) + (F(a2.w) + F(a3.w)));
#undef F
                ss += __shfl_xor_sync(0xFFFFFFFFu, ss, 1); dw += __shfl_xor_sync(0xFFFFFFFFu, dw, 1); sx += __shfl_xor_sync(0xFFFFFFFFu, sx, 1);
                const float mean = sx * (1.0f / 1024.0f);
                const float var = fmaxf(ss * (1.0f / 1024.0f) - mean * mean, 0.f);
                const float m = rb(mean);
                float sd; asm("sqrt.approx.ftz.f32 %0, %1;" : "=f"(sd) : "f"(rb(rb(var) + 1e-5f)));
                const float rs = rcp(rb(sd));
                const float hi = rb(rs);
                const uint32_t p0 = pack_b(m, 0.5f * hi), p1 = pack_b(0.5f * (rs - hi), rs * (dw - m * ws));
                const uint32_t o0 = __shfl_xor_sync(0xFFFFFFFFu, p0, 2), o1 = __shfl_xor_sync(0xFFFFFFFFu, p1, 2);
                const uint32_t kr = ((p1 ^ (p1 >> 31 ? 0xFFFF0000u : 0x80000000u)) & 0xFFFF0000u) | kidx;
                const uint32_t k1 = __reduce_max_sync(0xFFFFFFFFu, kr), k2 = __reduce_max_sync(0xFFFFFFFFu, kr == k1 ? 0u : kr);
                const uint32_t sl = (q & 2) ? 0x1054 : 0x5410;
                if (q < NREP) st_relaxed128(my_stats, make_uint4(prmt(p0, o0, sl), prmt(p1, o1, sl), (prmt(p0, o0, sl + 0x2222) & 0x7FFF7FFFu) | tb, g == 0 ? k1 : k2));
                TSL(9);
                { const int t0_ = clock(); while ((int)clock() - t0_ < PDELAY) __nanosleep(20); }
            }
            bar_sync(3, 192);
            const uint32_t tg = lds32(sm + SM_TOK + 8), tb = ((tg & 1) << 15) | ((tg >> 1) << 31);
            {
                const uint32_t* src = &p.sc->stats[G & (NREP - 1)][(sw * 64 + (lane >> 1)) * 8 + (lane & 1)].z;
                uint2 kz[4];
#pragma unroll
                for (int i = 0; i < 4; i++) kz[i] = make_uint2(~tb, 0);
                int it = 0;
                bool ok;
                do {
#pragma unroll
                    for (int i = 0; i < 4; i++)
                        asm volatile("{ .reg .pred p; .reg .b64 t; setp.ne.u32 p, %3, 0; mov.b64 t, {%0,%1};\n"
                                     "@p ld.relaxed.gpu.global.b64 t, [%2]; mov.b64 {%0,%1}, t; }"
                                     : "+r"(kz[i].x), "+r"(kz[i].y) : "l"(src + i * 512), "r"((kz[i].x ^ tb) & 0x80008000u) : "memory");
                    ok = __all_sync(0xFFFFFFFFu, (((kz[0].x ^ tb) | (kz[1].x ^ tb) | (kz[2].x ^ tb) | (kz[3].x ^ tb)) & 0x80008000u) == 0);
                } while (!ok && ++it < SPIN_LIMIT);
                const uint32_t a1 = max(kz[0].y, kz[1].y), b1 = max(kz[2].y, kz[3].y);
                const uint32_t h1 = max(a1, b1), h2 = __vimax3_u32(min(a1, b1), min(kz[0].y, kz[1].y), min(kz[2].y, kz[3].y));
                const uint32_t w1 = __reduce_max_sync(0xFFFFFFFFu, h1), w2 = __reduce_max_sync(0xFFFFFFFFu, h1 == w1 ? h2 : h1);
                sts64(sm + SM_KEYS + sw * 8, w1, w2);
                bar_sync(8, 64);
                const uint2 o = lds64(sm + SM_KEYS + 8 - sw * 8);
                key = sw ? __vimax3_u32(min(w1, o.x), w2, o.y) : max(w1, o.x);
                TSL(19);
            }
            const int t = (0xFFFF - (key & 0xFFFF)) & 2047;
            {
                const uint4* row = reinterpret_cast<const uint4*>(p.x + (size_t)t * 1024);
                uint4 xr[3];
                xr[0] = ldg128(row + 64 * rank + lane); xr[1] = ldg128(row + 64 * rank + 32 + lane); xr[2] = ldg128(row + 2 * G + (lane & 1));
                uint4 stk;
                int it = 0;
                do stk = ld_relaxed128(p.sc->stats[G & (NREP - 1)] + ((t >> 1) & 7) * 128 + (t >> 4)); while (((stk.z ^ tb) & 0x80008000u) && ++it < SPIN_LIMIT);
                if (lane == 0) {
                    sts32(sm + SM_TOK + 4 * sw, t);
                    if (c == 0 && sw == 0) st_relaxed32(&p.sc->epoch, tg);
                }
                const uint32_t se = (t & 1) ? 0x3232 : 0x1010;
                const uint32_t m = prmt(stk.x, 0, se), hi = bmul2(prmt(stk.z, 0, se) & 0x7FFF7FFFu, 0x40004000u), lo = bmul2(prmt(stk.y, 0, se), 0x40004000u);
                const uint32_t a = sm + SM_XSEL + lane * 32 + sw * 16;
#pragma unroll
                for (int i = 0; i < 2; i++)
                    sts128(a + i * 1024, norm2(xr[i].x, m, hi, lo), norm2(xr[i].y, m, hi, lo), norm2(xr[i].z, m, hi, lo), norm2(xr[i].w, m, hi, lo));
                proxy_fence();
                __syncwarp();
                if (lane == 0) mbar_arrive(bars + B_TOK * 8);
                if (sw == rank && lane < 2) {
                    sts128(sm + SM_XRAW + lane * 16, xr[2].x, xr[2].y, xr[2].z, xr[2].w);
                    sts128(sm + SM_XRAW + 32 + lane * 16, norm2(xr[2].x, m, hi, lo), norm2(xr[2].y, m, hi, lo), norm2(xr[2].z, m, hi, lo), norm2(xr[2].w, m, hi, lo));
                }
                __syncwarp();
                TSL(42);
            }
        }
        mbar_wait(bars + B_TOK * 8);
        const uint32_t tag = lds32(sm + SM_TOK + 8);
        {
            if (G < 56) {
                const uint64_t dw = (uint64_t)((sm & 0x3FFFFu) >> 4) | (1ull << 16) | (64ull << 32) | (1ull << 62);
                const uint64_t dx = (uint64_t)(((sm + SM_XSEL) & 0x3FFFFu) >> 4) | (2ull << 16) | (8ull << 32);
                const uint64_t dh = (uint64_t)(((sm + SM_H) & 0x3FFFFu) >> 4) | (8ull << 16) | (8ull << 32);
                const uint64_t dw2 = dw + (tag >> 2);
                float ag[4], au[4];
                TSL(13);
#pragma unroll
                for (int n = 0; n < 8; n++) {
                    const uint64_t a = (n < 7 ? dw : dw2) + (chunk_off(n) >> 4), b = dx + n * 16;
                    mbar_wait(bars + (B_FULL + n) * 8);
                    wg_fence();
                    if (n == 0) { wg_w0(ag, a, b); wg_w0(au, a + 512, b); } else { wg_w<1>(ag, a, b); wg_w<1>(au, a + 512, b); }
#pragma unroll
                    for (int k = 1; k < 4; k++) { wg_w<1>(ag, a + 128 * k, b + 4 * k); wg_w<1>(au, a + 512 + 128 * k, b + 4 * k); }
                    wg_commit();
                    bool any = false;
#pragma unroll
                    for (int i = 0; i < 5; i++) any |= ((REFILL >> (4 * i)) & 15) == n;
                    if (any) {
                        if (n <= 5) { wg_wait<1>(); bar_sync(4, 128); }
                        if (v == (n & 3)) {
#pragma unroll
                            for (int i = 0; i < 5; i++) if (((REFILL >> (4 * i)) & 15) == n && lead) load_chunk(7 + i);
                            __syncwarp();
                        }
                    }
                    if (n == 4) TSL(4);
                    if (n == 7) TSL(34);
                }
                wg_wait<0>();
                touch(ag); touch(au);
                TSL(14);
                if (q == 0) {
#pragma unroll
                    for (int r = 0; r < 2; r++) {
                        const uint32_t dst = mapa(sm, r), o = dst + SM_PAIR + rank * 1024 + v * 256 + g * 32;
                        st_async4(o, __float_as_uint(ag[0]), __float_as_uint(ag[1]), __float_as_uint(ag[2]), __float_as_uint(ag[3]), dst + SM_BAR + B_PAIR * 8);
                        st_async4(o + 16, __float_as_uint(au[0]), __float_as_uint(au[1]), __float_as_uint(au[2]), __float_as_uint(au[3]), dst + SM_BAR + B_PAIR * 8);
                    }
                }
                mbar_wait(bars + B_PAIR * 8);
                {
                    const uint32_t o = sm + SM_PAIR + v * 256 + g * 32 + q * 4, og = o + (p.up_first ? 16 : 0), ou = o + (p.up_first ? 0 : 16);
                    const float gs = rb(__uint_as_float(lds32(og)) + __uint_as_float(lds32(og + 1024)));
                    const float us = rb(__uint_as_float(lds32(ou)) + __uint_as_float(lds32(ou + 1024)));
                    const float hv = rb(siluf_(gs)) * us;
                    const uint32_t hd = sm + SM_H + (2 * v + (q >> 1)) * 128 + (q & 1) * 32 + g * 2, hb = pack_b(hv, hv);
                    sts16(hd, hb); sts16(hd + 64, hb);
                }
                proxy_fence();
                bar_sync(4, 128);
                TSL(15);
#pragma unroll
                for (int n = 0; n < 4; n++) {
                    const uint64_t a = dw2 + (chunk_off(8 + n) >> 4);
                    float d[2][4];
                    mbar_wait(bars + (B_FULL + 8 + n) * 8);
                    if (n == 3) TSL(24);
                    wg_fence();
                    wg_w0(d[0], a, dh); wg_w0(d[1], a + 512, dh);
#pragma unroll
                    for (int k = 1; k < 4; k++) { wg_w<1>(d[0], a + 128 * k, dh + 16 * k); wg_w<1>(d[1], a + 512 + 128 * k, dh + 16 * k); }
                    wg_commit();
                    wg_wait<0>();
#pragma unroll
                    for (int i = 0; i < 2; i++) {
                        touch(d[i]);
                        st_relaxed32(my_part + (2 * n + i) * 8 * 56 * 16, (__float_as_uint((q & 2) ? d[i][2] : d[i][0]) & ~3u) | tag);
                    }
                }
                TSL(16);
            } else {
                mbar_wait(bars + B_STG * 8);
            }
            if (v == 2 + rank) {
                const int t = (0xFFFF - (key & 0xFFFF)) & 2047;
                const int col = 4 * q + 2 * (lane >> 4) + ((lane >> 3) & 1), d = G * 16 + col;
                const float r = __uint_as_float((key & 0x80000000u) ? (key & 0x7FFF0000u) : (~key & 0xFFFF0000u));
                const float sg = rb(sigmoidf_(r));
                const uint4* src = reinterpret_cast<const uint4*>(p.sc->part) + c * 224 + lane;
                float s0 = 0, s1 = 0, s2 = 0, s3 = 0;
                {
                    uint4 pv[7];
                    int it = 0;
                    bool ok;
                    do {
                        uint32_t bad = 0;
#pragma unroll
                        for (int i = 0; i < 7; i++) pv[i] = ld_relaxed128(src + 32 * i);
#pragma unroll
                        for (int i = 0; i < 7; i++) bad |= (pv[i].x ^ tag) | (pv[i].y ^ tag) | (pv[i].z ^ tag) | (pv[i].w ^ tag);
                        ok = __all_sync(0xFFFFFFFFu, (bad & 3) == 0);
                    } while (!ok && ++it < SPIN_LIMIT);
#pragma unroll
                    for (int i = 0; i < 7; i++) {
                        s0 += __uint_as_float(pv[i].x); s1 += __uint_as_float(pv[i].y); s2 += __uint_as_float(pv[i].z); s3 += __uint_as_float(pv[i].w);
                    }
                }
                TSL(25);
                const float xn = blo(lds16(sm + SM_XRAW + 32 + col * 2)), xv = blo(lds16(sm + SM_XRAW + col * 2));
                const bool u16 = lane & 16, u8 = lane & 8;
                const float y0 = (u16 ? s2 : s0) + __shfl_xor_sync(0xFFFFFFFFu, u16 ? s0 : s2, 16);
                const float y1 = (u16 ? s3 : s1) + __shfl_xor_sync(0xFFFFFFFFu, u16 ? s1 : s3, 16);
                float y = (u8 ? y1 : y0) + __shfl_xor_sync(0xFFFFFFFFu, u8 ? y0 : y1, 8);
                y += __shfl_xor_sync(0xFFFFFFFFu, y, 4);
                const float z = rb(xn + rb(rb(y) * sg));
                const float gt = rb(siluf_(z));
                mbar_wait(bars + B_FIX * 8);
                const float o = xv + rb(blo(lds16(sm + SM_FIX + col * 2)) * gt);
                if (!(lane & 4)) p.out[(size_t)t * 1024 + d] = __float2bfloat16(o);
                TSL(26); TG(29);
            }
        }
    }
    }
}

__device__ __align__(128) const uint32_t g_tab[5504] = {
0x2fff3000,0x2e7c2fd4,0x2fc92fd4,0xad72af5a,0x2ff82ffc,0x230e2c07,0x2faf2fbc,0x217ea934,0x2fed2ff4,0xad4da8d5,0x2f912fa0,0x2e5e2bb7,
0x2fdd2fe6,0xb000af46,0x2f6e2f80,0x2fdd2fc9,0x2ff42fff,0x2e1f2fc9,0x2e1f2e7c,0xa875ad72,0x2fbc2fdd,0x9fd92a4e,0x2d4d2dba,0x2cd825db,
0x2f5a2f91,0xaeb5ac07,0x2c5d2cd8,0x30002f30,0x2ed02f1a,0xaf80aff4,0x2aaa2bb7,0x2cb02f1a,0x2fdd2ffc,0x2dba2fbc,0x2a4e2c07,0x25dba934,
0x2f462fa0,0xa7652875,0x25152875,0x2f802d27,0x2e3f2ed0,0xafa0ad72,0xa17e1cb6,0x2e3f2fe6,0x2cd82d96,0xadfeafd4,0xa934a6a1,0xa44e29f1,
0x2fbc2ff8,0x2d4d2faf,0x9fd9230e,0x2cd8217e,0x2e992f46,0xaa4e2515,0xaa4ea765,0x2fd42f80,0x2cb02dba,0xafffae99,0xad72ac5d,0x27652dba,
0x28752b05,0xab5eaee9,0xaf1aae5e,0xae3fa934,0x2f912ff4,0x2cd82fa0,0xac07a8d5,0x2f302bb7,0x2dba2ed0,0xac5d1cb6,0xae99ad72,0x2dba2fe6,
0x29932c5d,0xafc9af6e,0xafe6af6e,0xaaaa25db,0xa17e244e,0xa30ead4d,0xafafaffc,0xaff8aee9,0x2f5a2fed,0x2c5d2f91,0xaeb5ad4d,0x30002e5e,
0x2cb02e3f,0xad72a17e,0xafffafa0,0x27652e3f,0x217e2993,0xaf02afe6,0xaf02afc9,0xaf1aaaaa,0xab05a5db,0x2814aa4e,0xac07adba,0xad4dafdd,
0x2f1a2fe6,0x2bb72f80,0xaff4af46,0x2f1a2fc9,0x2b052d96,0xae5ea6a1,0xaee9afd4,0xa93429f1,0xa5db244e,0xadbaaffc,0xaa4ead4d,0xafddaee9,
0xaddcabb7,0x2cb0a17e,0x2765a17e,0x1cb6ad00,0x2ed02fdd,0x2aaa2f6e,0xaf80b000,0x2cb02fdd,0x28752cd8,0xaf1aa934,0xab5eadfe,0xae3fa44e,
0xab05a17e,0xac07afaf,0x2814a30e,0xad4daff8,0xaf6eaddc,0x2eb52765,0x2eb52cb0,0x2dba1cb6,0x29932f5a,0xa7652e99,0x25152e99,0x2aaaad96,
0xafa0ab05,0xabb7afed,0xaff4acd8,0x28d52ffc,0xa814af02,0x2f912d27,0x9fd9ae1f,0xaee9ae3f,0x2fd42c32,0xaf5a1cb6,0x30002d72,0x2fd42515,
0x28752f46,0xa8d52e7c,0xa8d52c32,0x2e3fa993,0xafedac5d,0xa934b000,0xaf30af5a,0xa8142eb5,0x1648adfe,0x2e992e5e,0x2c87a814,0xa9f1affc,
0x2fe62e1f,0xafffa875,0x2ddc2ff4,0x2ed02e1f,0x26a12f30,0xa9f12e5e,0xad96244e,0x2fd41fd9,0xafffad27,0xa515aff4,0xac32aff4,0xaddc2b5e,
0x2875acb0,0x2d272f46,0x2fa02993,0x2875aed0,0x2ee92f6e,0xaf91ac87,0x1fd92e99,0x28143000,0x244e2f1a,0xab052e3f,0xaf91a875,0x2fbc2b5e,
0xafd4addc,0x1648afc9,0x1648ae7c,0xafdd9cb6,0x2c32aa4e,0x2aaa2fd4,0x2f802e99,0x2e7caa4e,0x2d002ffc,0xae1fae5e,0xad272814,0xabb72dfe,
0x1fd92f02,0xac072e1f,0xafedad27,0x2dfe2e3f,0xaf6eae7c,0x25dbaf80,0x2c5daaaa,0xaf6eac32,0x2ddca5db,0x25153000,0x2c323000,0x2fff26a1,
0x28d52fbc,0xabb7af91,0xaff4ab05,0xafa0244e,0x96482ee9,0xac872dfe,0xae99af30,0x29f12fbc,0xaed0af02,0x2993af1a,0x2f46217e,0xacb0af02,
0x2f1a1cb6,0xa30e2fc9,0xa30e2e7c,0x2e1f2ddc,0x9fd92eb5,0xa44eb000,0xae5eaf5a,0xaf30ac5d,0xa17e2ed0,0xad002ddc,0xabb7afff,0xa17e2fe6,
0xadfeaf6e,0x2c07ae99,0x2fed2c87,0x9fd9b000,0x2fd42814,0xa9f12f30,0xad962934,0x26a12fed,0xaaaa2d00,0x2765afa0,0xa515afa0,0xa993afaf,
0xa5152eb5,0xad722dba,0x9cb6af6e,0xac322eb5,0xad00afbc,0x2d27adfe,0x2e1f2f30,0x2bb7aee9,0x2ffc2b5e,0xacd82e3f,0xafeda875,0xab052f1a,
0xadba2993,0x2c87ae7c,0x2c87ac32,0x2a4eaf46,0xaddc2d96,0xafe62c5d,0xaed02c5d,0x2fffa9f1,0x2e1fad4d,0x2e3f2814,0x2f02ac07,0xad27ab05,
0xae5e2d00,0x9fd9af1a,0xaf302b5e,0xa44e2faf,0x2e99acb0,0xad962f80,0x2f5aaaaa,0x2e99aed0,0xae3f2d72,0xaff82c32,0xaff82515,0x2f021cb6,
0x2ee9ac87,0x2d4d29f1,0x2ffc9648,0xa44eae99,0xaf6e2b05,0x26a1afbc,0xafd4a44e,0xadba2f91,0x2fc9a8d5,0xaf462e3f,0x2f802875,0x2fe6a8d5,
0xae992d4d,0xb0002c07,0xaf6ea814,0x2c872b05,0x2f80ab5e,0x2c322bb7,0x2e7c2bb7,0x2aaaaff8,0xaff42765,0x2b5eafff,0xad27ad72,0xaff42cb0,
0x2fed1648,0xaffc2c5d,0x2b052eb5,0x2cd82a4e,0xaee92d27,0xaffc2bb7,0xad4dad00,0x244e2e1f,0x2fdda993,0x29f12cb0,0x29f12ed0,0x2eb5af46,
0xafe61648,0x2d72afdd,0x9cb6afd4,0xaed01648,0x2f022934,0xafa02814,0xa8d52fed,0xa30e2f30,0xaf302d00,0xafed2b5e,0xa814af1a,0xa9342faf,
0x3000a765,0x26a12d72,0xa5db2fff,0x3000acb0,0xaf46a6a1,0x2ed0af5a,0x2cb0af5a,0xa993ac87,0x2d272cd8,0xae3f9fd9,0xaf022d4d,0xae1f2fbc,
0xaf6e2cd8,0xafd42b05,0x26a1affc,0xadba2fed,0x2fe6a30e,0x1cb62e1f,0xad722f1a,0x2ed0a30e,0xae1faaaa,0x2fafae7c,0x2fafac32,0x28d5af80,
0x29342e99,0xac07a9f1,0xafbc1648,0xaffc2c87,0xafa02cb0,0xafaf2aaa,0x2d00af80,0xafa02ed0,0x2f911648,0xa44e2eb5,0xafbc2c5d,0x2b052a4e,
0xac87acd8,0x3000ad4d,0x2f6e1fd9,0x2e99afbc,0x9cb62faf,0xa515ad27,0xac32ad27,0xad72a30e,0xafc92c87,0xaf802a4e,0x2f46adba,0xafe62c87,
0x2f02244e,0xa8d52f30,0xafa01fd9,0xa30e2e5e,0xa934ae1f,0x2fbcabb7,0x2c072d00,0x2ffcad27,0xaa4e2fff,0x26a1aed0,0x26a1afe6,0x1648addc,
0xaf4629f1,0xac3225db,0xae7c25db,0x29931648,0xab5e2f91,0xafaf2e5e,0xad002fed,0x2f1aad4d,0x2ee9a875,0xaf302ff8,0x2dfea17e,0x2fbcaff4,
0x2c5dafc9,0xa9f12d72,0x2d96afff,0x2c5dae7c,0xaf022993,0xab5e2515,0xab5ea765,0xa30e2aaa,0xacd82fd4,0xaf302dba,0xaf912f6e,0x2c07a6a1,
0x2d969fd9,0xafdd2fed,0x25db2c07,0x2f5aadfe,0x2e7caff8,0xad722f02,0x2fffae3f,0x2fc9aff8,0xaeb52934,0xaa4e244e,0x9648acd8,0xac5d2dfe,
0xaddc2ff8,0xae7c2d00,0xafc92d00,0x9cb628d5,0x2bb72515,0xaff82f80,0xab5e2f46,0x2bb7a765,0x2fbcaf5a,0xaf302fdd,0x2dfea5db,0x2ee9ad96,
0xae5e28d5,0xa934230e,0x2b05af02,0xaee92fa0,0xaeb52fff,0xad962c32,0xad962515,0xac872ddc,0x276529f1,0xaf802eb5,0xaf462fdd,0xa51529f1,
0x2ff4adfe,0xaff82fed,0x217e2c07,0x28759fd9,0xadfe2875,0xa814217e,0x2e5eaff8,0xaffc2ff4,0xaf5a2fe6,0xac872aaa,0xa6a1a993,0xaf5a2fc9,
0x9cb62c87,0xae7c2d96,0xafc92d96,0xaddc2eb5,0x2f1aac07,0xafaf2f30,0xad002f91,0xab5e2cd8,0xad962814,0xa5db1fd9,0x2fddaf91,0xaf5a2ee9,
0xafc92faf,0xaaaa28d5,0x2993ae1f,0xafe62faf,0xa8d52ddc,0xad002c32,0xad002515,0xaff82fff,0x2d4da6a1,0xae5e2dba,0xafed2f6e,0xaf912fd4,
0xad272765,0xa30e1cb6,0x2fafaddc,0xad272cb0,0xaffc2f5a,0xa81425db,0x2e5eafdd,0xadfe2d96,0xac5d2ee9,0xaa4e2934,0x9648ab05,0xaeb52e5e,
0x2993230e,0xac322b5e,0xae7c2b5e,0xaf462f02,0xacb026a1,0x9cb61648,0x2ddcaa4e,0xa76526a1,0xaff42ee9,0xa17e1fd9,0x2ff8af91,0xa8752814,
0xadfe2fa0,0xa44e230e,0x2cd8af02,0xa93428d5,0x96482aaa,0xa5db2515,0xa5dba765,0xa9f12993,0x2f462f5a,0x2c322e99,0x2e7c2e99,0xa993ad96,
0x2f1a2f30,0xa875244e,0x2e3f2e5e,0x2b5e1fd9,0x2ee92f02,0xaf30ad27,0x2dfe2e1f,0x2fbc2e3f,0x2eb52ed0,0xaf6eafff,0x2dba2ddc,0x2eb52fe6,
0x28752993,0xa8d52515,0xa8d5a765,0x2e3f2aaa,0x244e26a1,0xaf91ad96,0xab05a9f1,0x2fbc2fd4,0x96481fd9,0xae99afed,0xac87ac07,0x29f12dfe,
0xa515a17e,0x9cb6abb7,0xad72ad00,0xac32a17e,0xac5dab05,0xaf5aacd8,0xb000afed,0x2eb52ffc,0xaddcad27,0xae7caff4,0xafc9aff4,0x9cb62b5e,
0xaf02ae7c,0x217eaaaa,0xaf1aaf80,0xaf02ac32,0xafbcaf6e,0x2f302c87,0xadfeae99,0xaee9b000,0xafedafa0,0xaf30aff4,0xa934abb7,0xa81428d5,
0xafd4afff,0x1648ac32,0x1648a515,0xafddaddc,0xaed0af6e,0x2f462c5d,0x299325db,0xacb0af6e,0xad00adfe,0x2e1f2fed,0x2d272c07,0x2bb79fd9,
0xadfeaf02,0xa814ae1f,0x2e5e2d27,0xaffcae3f,0xaa4eacb0,0x2e992993,0x2fd42f46,0xaa4eaed0,0x1cb6a5db,0x2e7c3000,0x2fc93000,0x2ddc26a1,
0x2b5e2814,0xa8752934,0x2e3f2f30,0x2f1a2fed,0x1648a814,0x2c879fd9,0x2e992f91,0xa9f1aee9,0x2c322875,0x2f802fa0,0x2aaa2d27,0x2e7c2875,
0x2f1a2ddc,0xa30e2c32,0xa30e2515,0x2e1f2fff,0x2ffc2fd4,0xafedad96,0xacd8a9f1,0xab0526a1,0x2e1f2c32,0x2ff42d72,0xa8751cb6,0x2e1f2515,
0x2ffc2f6e,0x28142e99,0xae5eac87,0x2dfe3000,0x2eb52fbc,0xaf5aab05,0xb000af91,0xac5d244e,0x29932d00,0xac32afa0,0xae7cafa0,0xaf46afaf,
0x2fe62fd4,0x2ddc3000,0xafffaf5a,0x2ed02fd4,0x2d002ee9,0xad271fd9,0xae1faf91,0xabb72814,0x9fd928d5,0xae5eaff4,0xa44eabb7,0xaf30afa0,
0xadbaaaaa,0x2c87a515,0x2c872765,0x2a4ea993,0x9cb62d96,0xacb02c5d,0xa7652c5d,0x2ddca9f1,0xaff8adfe,0xa30eafbc,0xafafaee9,0xa17e2f30,
0x244ead00,0x2dfe2f1a,0x2934ab5e,0xacd8afaf,0x2fdd2e7c,0xb000a993,0x2f6e2f46,0x2fdd2c32,0xae3f9cb6,0xaff8a765,0xaff8acb0,0x2f022ddc,
0xac07afdd,0x2dfeaa4e,0x1fd9adba,0xafeda5db,0x2f6e2934,0xa6a12ee9,0x2fd42e5e,0x2dbaab05,0x27652f1a,0xaaaaaff4,0xa9932bb7,0xa5152f1a,
0xafddadfe,0xadbaaee9,0xaa4eafbc,0xa5db2f30,0x2aaaab5e,0x2fc92bb7,0x2fe62bb7,0xa993aff8,0x2e3f2fc9,0xafa01cb6,0xa17e2ddc,0x2e3f2e7c,
0xae5e9648,0x2d4dac5d,0xaf91aeb5,0xafedaa4e,0xac07aff8,0x1fd9afaf,0x2dfea30e,0xafeda17e,0x2fdd2aaa,0x29f12fe6,0x29f12fc9,0x2eb5a993,
0xa5152dba,0xaddcae99,0xafffac5d,0xac322dba,0xaf02af30,0x2fa02c07,0x28d5acd8,0x230eaf91,0x2934ad00,0x2e5eab5e,0x2ee92f1a,0xab05afaf,
0x2dba2fc9,0xac5d2ddc,0xae991cb6,0x2dba2e7c,0xaf80a6a1,0x2765af5a,0xa515af5a,0xaf46ac87,0x217eae5e,0x230e2ffc,0x2faf2dfe,0x2ff82814,
0x2f6e244e,0x2fd42934,0xa6a12dfe,0x2dbaacd8,0xa5152e3f,0xafffa17e,0xaddcafa0,0xac322e3f,0xae1faf80,0x2fafa515,0x2faf2765,0x28d5af46,
0x2f9125db,0xaee92a4e,0xa8142dba,0x9fd92fdd,0x2f1a2e7c,0x2bb72f46,0xaff4a993,0x2f1a2c32,0xaf309648,0xacd8aeb5,0x2c07ac5d,0xaf91aa4e,
0x25dbae5e,0x2dba2dfe,0x2a4e2ffc,0x2fdd2814,0x2d722faf,0xae7cad27,0xafc9ad27,0xafffa30e,0x27652fdd,0xa9932f6e,0xaaaab000,0xa5152fdd,
0xaf02ae5e,0x28d5af91,0x2fa02d4d,0x230eafed,0x2f91217e,0xa8142faf,0xaee9230e,0x9fd92ff8,0xaa4e2d72,0x26a1afc9,0x26a1ae7c,0x1648afff,
0xaf8029f1,0xafc925db,0xafe625db,0x2f461648,0x2fa0a934,0x2bb72cd8,0x2ff4a44e,0xa8d5adfe,0xafbc2875,0x2934aff8,0xaffc217e,0xac072ff4,
0x2fd4a765,0xaf5a2ddc,0x30009cb6,0x2fd4acb0,0xaf02aaaa,0xab5eacb0,0xab5eaed0,0xa30e2f80,0x2e5e2c5d,0xab053000,0x29342f5a,0x2ee9aeb5,
0xad96ad4d,0x2fddacd8,0xa5dbafbc,0xaf5a1fd9,0x2cb02e1f,0xaddca875,0x1cb62ff4,0x27652e1f,0xa6a1af91,0x29f1afed,0x2d96ae5e,0xafd42d4d,
0x9cb62ff8,0xafe62d00,0xaed02d00,0x2d7228d5,0x2875afe6,0x2d272993,0x2fa0aaaa,0x2875afc9,0xac072f5a,0x2934afdd,0xaffc25db,0xafbc2d96,
0x2cd8af1a,0x2f91ae3f,0x2f302875,0xac07ab5e,0xaeb52d72,0xad96a765,0xad96acb0,0xac872fff,0x2fc9aa4e,0xa9932fd4,0x2aaa2e99,0x2fe6aa4e,
0xaff41fd9,0x2ff8acd8,0xa17eafbc,0xa875ad4d,0x2ffca875,0x2ee9a17e,0xa44e2ff8,0x2d4daff4,0xaf6ea515,0x25dbaf46,0x2c5daf80,0xaf6e2765,
0x2d722c87,0xafe62d96,0xaed02d96,0x9cb62eb5,0xa8d5aee9,0x2bb72b05,0x2ff4a934,0x2fa0ae5e,0x2d962c07,0x25db2d4d,0xafdd2b05,0x2f5aa814,
0xa765af02,0x2f46af1a,0x2f80217e,0x2515af02,0xa8d52fff,0xad00a765,0xad00acb0,0xaff82d72,0x2dfeaeb5,0xacd83000,0x244e2f5a,0x29342c5d,
0xa17e2fc9,0xad002fff,0xabb7ad72,0xa17e2e7c,0x2d4daf5a,0x2ee9a5db,0xa44e2fdd,0x2ffcad96,0xafd42c07,0x29f1af91,0x2d96af30,0xa6a1acd8,
0x2f46230e,0xafc92b5e,0xafe62b5e,0xaf802f02,0xae7c2eb5,0xafff2dba,0x2d72af6e,0xafc92eb5,0x2ff4a814,0x217e2d4d,0xaff82b05,0x28752c07,
0xad4dab5e,0x2fedae3f,0x2e5e2875,0x2f91af1a,0x96482f80,0xa5dbacb0,0xa5dbaed0,0xa9f1aaaa,0xad729648,0xa515a6a1,0xac32a6a1,0x9cb62a4e,
0xae1f2ffc,0xae3f2c07,0xaf022fbc,0x2d27a934,0x2cd8230e,0xaffc2fa0,0x2b0528d5,0x2fedaf02,0x2e99afe6,0xad962f46,0x2f5aaf80,0x2e99afc9,
0x230eaddc,0x2d27aed0,0x2d27afe6,0xafaf2fff,0xafbc2c87,0x1fd9a9f1,0xad4d1648,0xacd82e99,0xaa4e2f30,0xac5d2814,0xaeb52fed,0x96482934,
0x2ed0a8d5,0xaf802e3f,0x2aaa2875,0x2cb0a8d5,0x2e99affc,0x3000afbc,0x2f6eac07,0xac872934,0xa993a8d5,0x2ed0afaf,0x2cb0afaf,0xaf462e1f,
0xaff42ed0,0x2b5ead72,0xad271cb6,0xaff42fe6,0xa44e2dba,0x9fd9a6a1,0xaf302fd4,0xae5e2f6e,0x2fbcad27,0x2d4dabb7,0x9fd92d00,0x2cd8ae1f,
0x2c87af80,0x2f5aae7c,0x2f5aac32,0x26a1aaaa,0xacb01648,0x2fffafdd,0x2d72afd4,0xa7651648,0xafaf2f91,0x2f1aafbc,0xab5ea44e,0xad002b05,
0x2b05230e,0xa44e28d5,0xafbc2fa0,0x2f91af02,0x3000aed0,0x26a19cb6,0xa5db2d72,0x3000afe6,0x2aaaaeb5,0x2c32a9f1,0x2e7ca9f1,0x2f80afdd,
0xad27244e,0x2e3fad4d,0x2f02affc,0x2e1faee9,0xaa4e2e5e,0xaeb52f30,0xac5d1fd9,0x9648244e,0x2cb0a30e,0xad722e1f,0xafff2f1a,0x2765a30e,
0x2ff8af46,0xabb72cb0,0xabb72ed0,0x2b5ea993,0x2b05ae99,0xa81429f1,0x2c079648,0x2d4dac87,0xafa02fe6,0xafaf2f80,0x2d00af46,0xafa02fc9,
0xa9342dba,0xafed2fd4,0xa814a6a1,0xaf302f6e,0x2c87a44e,0xb0002ffc,0xaf6e2d4d,0xae992ee9,0x2fffaf02,0xafe62ff8,0xaed02ff8,0xaddc2e3f,
0xaed02c87,0xaaaa2a4e,0x2f80adba,0xacb02c87,0xafaf2fed,0xab5e2b05,0x2f1aaffc,0xad002cd8,0xab052e1f,0xac072bb7,0x2814ad00,0xad4d2d27,
0x29f11cb6,0xac5d2c32,0xac5d2515,0xad962d72,0x2d722d96,0x25152c5d,0x2c322c5d,0x1cb6a9f1,0x2d272d4d,0xad00a814,0x2bb72c07,0x2e1f2b05,
0x2cd82d00,0xaffcaf1a,0x2b052b5e,0x2fed2faf,0x2c872cb0,0xadbaaf80,0x2a4e2aaa,0x2c872ed0,0xae3faddc,0xaff8aed0,0xaff8afe6,0x2f022fff,
0xaee9ae99,0xad4daf6e,0xaffcb000,0x244e2c87,0xaf6eaf30,0x26a1a814,0xafd4afed,0xadbaa934,0xafc9afa0,0x2f462d00,0xaf80afaf,0xafe6afa0,
0xac87ad4d,0x9648ac07,0x29f12814,0xae99ab05,0xa993ab5e,0x2ed02bb7,0x2cb02bb7,0xaf46aff8,0xa30ea765,0x2f1a2fff,0x2e1f2d72,0xa30eacb0,
0x244e1648,0x1fd92c5d,0x2f302eb5,0x2e5e2a4e,0x2ee92e1f,0x2ffc2f02,0x2d4d2e3f,0xa44ead27,0x2fdd2f80,0x29f12e7c,0x29f12c32,0x2eb52aaa,
0x2fe63000,0xad72a5db,0x1cb626a1,0x2ed03000,0x2f022f91,0xafa0afbc,0xa8d5a44e,0xa30e2b05,0x2b052d00,0xa44e2b5e,0xafbcaf1a,0x2f912faf,
0x16482765,0xafd4ad72,0xafddafff,0x16482cb0,0xaaaaa6a1,0xac32af5a,0xae7caf5a,0xaf80ac87,0xae1facd8,0x2d001fd9,0xabb7ad4d,0xad27afbc,
0xaf6eae5e,0xafd4af30,0x26a19fd9,0xadbaa44e,0xafe6aff4,0x9cb6ad27,0x2d722b5e,0xaed0aff4,0xae1faf46,0x2faf2cb0,0x2faf2ed0,0x28d5a993,
0xa934ac87,0x2c072f6e,0x2fbc3000,0x2ffc2e99,0xa8d5acb0,0x2875aaaa,0x2e3f2f80,0xa8d5aed0,0x29341648,0x2fed2eb5,0x28142c5d,0x2f302a4e,
0x2e992cd8,0x16482d4d,0xa9f19fd9,0x2c872fbc,0x2fff2faf,0xafe6ad27,0xaed0ad27,0xaddca30e,0x2fc92e99,0x2f802f5a,0xaf46ad96,0x2fe62e99,
0x2f022fed,0xa8d52b05,0xafa0affc,0xa30e2cd8,0x29342d27,0xafbcaf02,0xac07ae3f,0xaffcae1f,0xaa4e9cb6,0x26a1ac32,0x26a1a515,0x1648ad72,
0xaaaa29f1,0xaed025db,0xacb025db,0x2f801648,0xaf1aaf91,0x2875ae5e,0xae3fafed,0xab5e2d4d,0x2c07a875,0x2b052ff8,0x2d4da17e,0xa814aff4,
0x2eb52fc9,0xaf6ead72,0x2dba2fff,0x2eb52e7c,0xaf02af80,0xab5eafe6,0xab5eafc9,0xa30e2f46,0x2cd8a6a1,0x2f302d96,0x2f9129f1,0xac07afd4,
0x2d962ffc,0xafdda44e,0x25db2ee9,0x2f5a2d4d,0xae7ca17e,0x2d72abb7,0xafffad00,0xafc9a17e,0x2c5da934,0x2f5aa44e,0x30002cd8,0xaeb5adfe,
0x2d722ff8,0xacb02d00,0xa7652d00,0x2fff28d5,0xaf02a515,0x217eaf80,0xaf1aaf46,0xaf022765,0xa814af5a,0x2b052fdd,0x2d4da5db,0x2c07ad96,
0x2e5e2fa0,0x29342ff4,0xab052bb7,0x2ee9a8d5,0xaeb59cb6,0xad96aed0,0xad96afe6,0xac872d72,0xa765af6e,0x2f802c5d,0x2f4625db,0x2515af6e,
0x2ff42d4d,0xaff8a44e,0x217e2ee9,0x28752ffc,0xad4d2875,0xafbc217e,0xacd8aff8,0x1fd92ff4,0xaa4eafe6,0x2e99aaaa,0x2fd42993,0xaa4eafc9,
0x2fff2c87,0xacb02d96,0xa7652d96,0x2d722eb5,0xab5e2c07,0x2875af30,0xae3faf91,0xaf1aacd8,0xad96afbc,0xa5dbaffc,0x2fdd2934,0xaf5aac07,
0x2fc92875,0x2aaa2fa0,0xa9932d27,0x2fe62875,0xa8d52d72,0xad00aed0,0xad00afe6,0xaff89cb6,0xad4dafd4,0x2e5e2d96,0x2fed29f1,0x2f91a6a1,
0x2e1fa765,0x2ff49cb6,0xa8752ddc,0x2e1facb0,0x1fd92f5a,0xafbc25db,0xacd8afdd,0xad4d2d96,0xaeb5aee9,0x2f5aa934,0x30002b05,0x2c5dae5e,
0x2f80230e,0xaed02b5e,0xacb02b5e,0xaaaa2f02,0x2cb02fd4,0x1cb63000,0xaddcaf5a,0x27652fd4,0xaff4ac07,0xa17eaffc,0x2ff82934,0xa875afbc,
0x2dfea8d5,0x244e2ff4,0xacd82bb7,0x29342fa0,0x96482f46,0xa5dbafe6,0xa5dbafc9,0xa9f1af80,0xafff9648,0xae7ca6a1,0xafc9a6a1,0x2d722a4e,
0x2ff81fd9,0x230e2ee9,0x2faf2814,0x217eaf91,0xafeda30e,0x2d4dafa0,0xaf91a8d5,0xae5e2f02,0x2fdd2515,0xb0002aaa,0x2f6e2993,0x2fdda765,
0x230eafff,0x2d27afc9,0x2d27ae7c,0xafaf2d72,0xa8142fdd,0xaffc2a4e,0xadfe2dba,0x2e5e25db,0x2a4eaf91,0x2c5d2c07,0x2eb5acd8,0x1648af30,
0xac322f1a,0x2993aff4,0xaf462bb7,0xae7c2f1a,0x2fdd1fd9,0x2dba2814,0x2a4e2ee9,0x25dbaf91,0xaf46a8d5,0x2765afaf,0xa515afaf,0xaf802e1f,
0x2e3f2c32,0xafa02ddc,0xa17e2fff,0x2e3f2515,0xacd8adba,0x2dfe26a1,0x2934afd4,0x244eaf6e,0xa8142ff8,0xadfe2faf,0xaffc230e,0x2e5e217e,
0x2c87af46,0x2f5aa515,0x2f5a2765,0x26a1af80,0xae7c2dba,0x9cb6ae99,0xaddcac5d,0xafc92dba,0x2fafab05,0xaf1a2ee9,0x2b5e2e5e,0x2d002934,
0xaf91a30e,0xacd8a8d5,0x2c07afa0,0xaf302f02,0x2dba2c32,0xac5d2fff,0xae992ddc,0x2dba2515,0xa993aeb5,0x2fc9a9f1,0x2fe6a9f1,0x2aaaafdd,
0xa17e2fed,0xa30eadfe,0xafaf9fd9,0xaff82c07,0x2a4eafed,0x2eb5af91,0x2c5d2d4d,0x1648ae5e,0xae7c2e3f,0xaddca17e,0x9cb6afa0,0xafc92e3f,
0x2ff8a993,0xabb72fe6,0xabb72fc9,0x2b5e2aaa,0xaf30a5db,0x2fbcaa4e,0x2ee9adba,0x2dfeafdd,0x2f1a2515,0x2bb72993,0xaff42aaa,0x2f1aa765,
0xab05adba,0x2e5eafd4,0x2ee926a1,0x2934af6e,0xa5db2fed,0xadba9fd9,0xaa4eadfe,0xafdd2c07,0x2ddcaf02,0xacb02ff8,0xa7652ff8,0x9cb62e3f,
0xac322fdd,0xaf462f6e,0x2993b000,0xae7c2fdd,0x2fafacd8,0x2b5e2934,0xaf1a2dfe,0x2d00244e,0xaf30a17e,0x2ee9afaf,0x2fbca30e,0x2dfeaff8,
0x29f12ddc,0xac5da765,0xac5dacb0,0xad969cb6,0xa993aa4e,0x2765ac87,0xa515ac87,0xaaaa2dba,0xafa02f30,0xabb7244e,0xaff42e5e,0x28d51fd9,
0x28142bb7,0xaf912e1f,0x1fd92d27,0x2ee9ad00,0x2fd4aed0,0xaf5a2fff,0x3000addc,0x2fd4afe6,0x2fafaf46,0x2fa0ae7c,0x2fa0ac32,0xad002993,
0xa44eac5d,0x2f91b000,0x2b05af5a,0xafbc2eb5,0xb0002dfe,0x2c87ae5e,0xae992814,0xaf6e2ffc,0xa5152e1f,0x9cb6a875,0xad722ff4,0xac322e1f,
0x26a12b05,0xa9f12cd8,0xad962fed,0x2fd4affc,0x2fffae1f,0x2515230e,0x2c32230e,0x2ddcaf1a,0x2875ae7c,0x2d27aaaa,0x2fa0af80,0x2875ac32,
0xaee929f1,0x2f91ae99,0x9fd9ac87,0xa8149648,0xafed2f1a,0xaf302e3f,0xa934a875,0xa8142b5e,0xa6a12ddc,0xb0002fc9,0xb0002e7c,0x25db1cb6,
0x2ed0aa4e,0xaf462fd4,0xa9932e99,0x2cb0aa4e,0x2e3faffc,0xad272e5e,0x2e1fa814,0x2f02adfe,0x9fd9abb7,0x2c07ad27,0x2fedae1f,0xadfe2d00,
0xaf6e2cb0,0x25dba993,0x2c5daf46,0xaf6e2ed0,0xaddc2fdd,0xa5159648,0xac329648,0xafff2fd4,0x28d52814,0xabb72934,0xaff42f30,0xafa02fed,
0x3000aee9,0x2e99adfe,0xac872f30,0x2f6eafbc,0x2c32af02,0x2f80af1a,0x2aaa217e,0x2e7caf02,0xab5e9cb6,0x2ff4afc9,0x2ff4ae7c,0x2d27addc,
0xaffc2eb5,0x2fedb000,0x2cd8af5a,0x2b05ac5d,0xa17e2c32,0xad002d72,0xabb71cb6,0xa17e2515,0x2dfea9f1,0xac072c87,0xafed2e99,0x1fd91648,
0x2fd4afbc,0xa9f12b05,0xad962f91,0x26a1a44e,0x2aaaae3f,0xa76528d5,0x251528d5,0x2993a875,0xafe62eb5,0xaddc2dba,0x2fffaf6e,0xaed02eb5,
0xae3f2fbc,0xae1f2dfe,0x2d27af30,0xaf022ee9,0x9fd92b5e,0xae5e2e3f,0xa44ea875,0xaf302f1a,0x2d96a993,0xae992e7c,0xae992c32,0xaf5a2f46,
0x299329f1,0xa76525db,0x251525db,0x2aaa1648,0x28d52934,0xaf02acd8,0x230e244e,0x2fa02dfe,0x28142875,0xaf91aff8,0x1fd9217e,0x2ee92ff4,
0x26a12765,0xaa4eaddc,0x16481cb6,0x26a12cb0,0xaf02af46,0xab5eae7c,0xab5eac32,0xa30e2993,0xae5eaeb5,0x2b059648,0xa934aa4e,0xaee9ac5d,
0xad96adfe,0x2fdd2e5e,0xa5dba814,0xaf5aaffc,0xacb0ad27,0x2ddc2faf,0x9cb6a30e,0xa765ad27,0x2fd42f91,0x2f6e2fed,0x2dba2e5e,0xa6a1ad4d,
0x2fff2ff8,0x25152d00,0x2c322d00,0x2ddc28d5,0x2faf2fe6,0xae1fa993,0x28d52aaa,0x2faf2fc9,0x2ee92f5a,0xaf91afdd,0x1fd925db,0x28142d96,
0xacd8ab5e,0xaf91ad00,0xaf30afaf,0x2c072f1a,0xaeb5addc,0xad96afc9,0xad96ae7c,0xac879cb6,0xafc9af5a,0x2993a6a1,0xaaaaac87,0xafe6af5a,
0xaff4affc,0x2ff82e5e,0xa17ea814,0xa875adfe,0x9fd9a875,0x2c07a17e,0x2fed2ff8,0xadfeaff4,0x29f12515,0x2fdd2f46,0x2eb52f80,0x29f1a765,
0x2ddc2c87,0x25152d96,0x2c322d96,0x2fff2eb5,0x2fa02ee9,0xaf02ab05,0x230e2934,0x28d52e5e,0x2d962ee9,0x25db2dfe,0xafddaf30,0x2f5a2fbc,
0x27652bb7,0xaf46ab5e,0xaf80aff8,0xa5152bb7,0xa8d59cb6,0xad00afc9,0xad00ae7c,0xaff8addc,0xadfeac5d,0x2cd89648,0xa44eaa4e,0xa934aeb5,
0xaff8afc9,0xae3fafff,0x2f022d72,0xaff8ae7c,0xadfeaf5a,0x2c07a5db,0x2fed2fdd,0x9fd9ad96,0xa6a1ac07,0x2f6e2f91,0x2dba2f30,0x2fd42cd8,
0x2aaa230e,0xa7652b5e,0x25152b5e,0x29932f02,0x2e7c2c5d,0x2fff2d96,0xad72a9f1,0x2fc92c5d,0x2ff42fbc,0x217e2dfe,0xaff8af30,0x28752ee9,
0x2d4d2f1a,0xafedad00,0xae5eafaf,0xaf91ab5e,0x96482993,0xa5dbae7c,0xa5dbac32,0xa9f1af46,0xaddc9648,0xafe6a6a1,0xaed0a6a1,0x2fff2a4e,
0xad27affc,0x2d00ac07,0xabb7afbc,0xae1f2934,0x2e5e230e,0x1fd92fa0,0x2f3028d5,0x244eaf02,0x2c872fe6,0xadbaaf46,0x2a4e2f80,0x2c872fc9,
0x230ead72,0x2d27ac32,0x2d27a515,0xafaf9cb6,0x2fbc2e99,0x9fd92f6e,0x2d4d3000,0x2cd8ac87,0xaa4e2b05,0xac5dafbc,0xaeb5a44e,0x96482f91,
0xaed0afa0,0x2f802d00,0xaaaaafaf,0xacb0afa0,0x2c872ffc,0x16482fbc,0xa9f12c07,0x2e99a934,0xaf80a8d5,0xac32afaf,0xae7cafaf,0xaaaa2e1f,
0xa30eaed0,0x2f1a2d72,0x2e1f9cb6,0xa30eafe6,0x2fed2dba,0xaffca6a1,0x2b052fd4,0x2cd82f6e,0xafbcae1f,0xad4daf02,0x1fd9ae3f,0xacd82d27,
0x2c87a993,0x2f5a2cb0,0x2f5a2ed0,0x26a1af46,0x2cb03000,0xafffa5db,0xad7226a1,0x27653000,0xafafa934,0x2f1aa814,0xab5eafed,0xad00af30,
0x2f30230e,0x2fed28d5,0x28142fa0,0x2934af02,0x16482ed0,0xafd41cb6,0xafddad72,0x16482fe6,0xaf46aeb5,0x2ed0a9f1,0x2cb0a9f1,0xa993afdd,
0x2e1fa44e,0xad002d4d,0x2bb72ffc,0x2d272ee9,0xaa4e2cd8,0xaeb52b05,0xac5daffc,0x96482fed,0xacb0aff4,0x2d72ad27,0x2fff2b5e,0xa765aff4,
0x2ff82aaa,0xabb72e7c,0xabb72c32,0x2b5e2f80,0xab052c87,0x2814af6e,0xac07b000,0xad4dae99,0xa8d5afe6,0x2875af80,0x2e3f2f46,0xa8d5afc9,
0x2f912dba,0xa44e2fd4,0xafbca6a1,0x2b052f6e,0xae99244e,0x9648affc,0x29f1ad4d,0xac87aee9,0x1cb6af02,0x25152ff8,0x2c322ff8,0x2d722e3f,
0x2ed02e99,0x2aaa2f5a,0xaf80ad96,0x2cb02e99,0xafafa44e,0xab5eaf30,0x2f1a9fd9,0xad00ae5e,0x2b05ad27,0x2c072f02,0xa8142e3f,0x2d4d2e1f,
0x29f12fff,0xac5daed0,0xac5dafe6,0xad96addc,0xaf46aa4e,0xac32ac87,0xae7cac87,0x29932dba,0x2f1a2b05,0xa8752fed,0x2e3f2cd8,0x2b5eaffc,
0xaee9abb7,0x2f30ae1f,0xadfead27,0xafbc2d00,0x2eb52c32,0xaf6e1cb6,0x2dba2d72,0x2eb52515,0x2fafa993,0x2fa0a515,0x2fa02765,0xad00aaaa,
0xafed26a1,0xa934ad96,0xaf30a9f1,0xa8142fd4,0x30009fd9,0xac872fed,0x2e992c07,0x2f6eadfe,0xafe6a17e,0x2fffabb7,0xaddcad00,0xaed0a17e,
0xac5d2f30,0xaf5a2e5e,0xb000244e,0x2eb51fd9,0x2ddcae1f,0x2e7c230e,0x2fc9230e,0x1cb6af1a,0xaf022cb0,0x217eaf46,0xaf1aa993,0xaf022ed0,
0x2fbca9f1,0xaf302e99,0x2dfe2c87,0x2ee91648,0xa44eafa0,0x2b05aff4,0x2f91abb7,0xafbc28d5,0xa6a12fff,0xb0002c32,0xb0002515,0x25db2ddc,
0x2c32af6e,0x2aaa2c5d,0x2f8025db,0x2e7caf6e,0xae3f2dfe,0x2d27afed,0xae1fac07,0xaf021fd9,0x2dfe2bb7,0x28142d27,0xae5e2e1f,0x2ffcad00,
0xaa4eae7c,0x2e99af80,0x2fd4aaaa,0xaa4eac32,0x9cb62fdd,0xae7c9648,0xafc99648,0xaddc2fd4,0x2b5eafbc,0xa8752f91,0x2e3f2b05,0x2f1aa44e,
0xb0002814,0xae991fd9,0x2c87af91,0xaf6e2ee9,0x2ed02875,0xa9932fa0,0xaf462d27,0x2cb02875,0xab5eaddc,0x2ff4ac32,0x2ff4a515,0x2d27afff,
0x9fd92fd4,0xa44ead96,0xae5ea9f1,0xaf3026a1,0x2e1faed0,0x2ff4addc,0xa8752fff,0x2e1fafe6,0xaffc29f1,0xa814ac87,0x2e5eae99,0xadfe9648,
0x2eb52814,0xaf5a2f30,0xb0002934,0xac5d2fed,0xa993ae3f,0x2c3228d5,0x2e7c28d5,0x2f46a875,0xa5152fd4,0xad723000,0x9cb6af5a,0xac322fd4,
0x2e3faee9,0x2e1f9fd9,0xad272f91,0x2f02a814,0xaffc28d5,0x2cd8aff4,0x2fedabb7,0x2b05afa0,0x2d962aaa,0xae992515,0xae99a765,0xaf5a2993,
0x1cb6adba,0x2cb0aeb5,0x2765aeb5,0xaddc2f6e,0xaff82d4d,0xa30ea814,0xafaf2c07,0xa17e2b05,0xa44e2e3f,0xadfe2b5e,0xa9342f1a,0x2cd8a875,
0x2fddacb0,0xb0002f80,0x2f6eaaaa,0x2fddaed0,0x2d001cb6,0x217e2765,0x217e2cb0,0x2bb7addc,0x2ee9afdd,0x2d4daa4e,0x2ffcadba,0xa44ea5db,
0xa9f1a934,0x2fd4aee9,0x26a1ae5e,0xad962b05,0xafc92f1a,0x2f46aff4,0xaf802bb7,0xafe62f1a,0xafdd2d4d,0xadba2c07,0xaa4ea814,0xa5db2b05,
0xaaaa2f1a,0xafc92f02,0xafe62f02,0x2993a17e,0x2e3fa765,0xafa02fff,0xa17e2d72,0x2e3facb0,0x2e5eb000,0xad4d2eb5,0x2f91ac5d,0x2fedaf5a,
0x2ee9aff8,0x2ffcafaf,0x2d4da30e,0xa44ea17e,0xa5dbaaaa,0x2f6eafe6,0x2f6eafc9,0xac5d2993,0xafe62dba,0x2d72ae99,0x9cb6ac5d,0xaed02dba,
0xabb72f30,0x28d5ac07,0xafa02cd8,0xaff42f91,0xa9342e3f,0xae5e2f1a,0xaee92b5e,0x2b05a875,0x2dbaa765,0xac5d2d72,0xae992fff,0x2dbaacb0,
0x2f80afd4,0xa7652a4e,0x25152a4e,0x2f46ae99,0x217eacd8,0x230e1fd9,0x2fafad4d,0x2ff8afbc,0xa9f1a44e,0x26a1a934,0x2fd4adfe,0xad962cd8,
0xafe62e3f,0x9cb6a17e,0x2d72afa0,0xaed02e3f,0xad272f80,0xa8752515,0xa875a765,0xafa02f46,0x293425db,0xac072a4e,0xafbc2dba,0xaffc2fdd,
0x2f1aacb0,0x2bb7aaaa,0xaff42f80,0x2f1aaed0,0x2f30b000,0x2cd8ac5d,0xac072eb5,0x2f91af5a,0x25dbacd8,0x2dbaad4d,0x2a4e1fd9,0x2fddafbc,
0xad722875,0x2e7cae1f,0x2fc9ae1f,0x2fffaff4,0xafc92fdd,0xaf802f6e,0x2f46b000,0xafe62fdd,0xabb72e5e,0xafa02f91,0x28d5ad4d,0xaff42fed,
0x2934217e,0xafbc2faf,0xac07230e,0xaffc2ff8,0x2f5aad72,0xafd42fc9,0xafd42e7c,0xb0002fff,0x9cb69648,0xacb0a6a1,0xa765a6a1,0x2ddc2a4e,
0xa17e9fd9,0xaff4aee9,0xa875a814,0x2ff82f91,0xa44ea30e,0xadfeafa0,0xa934a8d5,0x2cd82f02,0xa5dba515,0x9648aaaa,0xa9f1a993,0xa5db2765,
0xa30e9cb6,0xad27a765,0xad27acb0,0x2faf2ddc,0xa814a5db,0xaffcaf5a,0xadfead96,0x2e5e2fdd,0xaa4ea934,0xac5daee9,0xaeb5ae5e,0x96482b05,
0xac32ab5e,0x2993a30e,0xaf46af02,0xae7cab5e,0xa5db9fd9,0xad96a814,0xaf5aaee9,0x2fdd2f91,0xaaaaa8d5,0xafc9afaf,0xafe6afaf,0x29932e1f,
0xad00ac32,0xa8d5addc,0xaff8afff,0xad00a515,0xae5eadba,0x2d4d26a1,0xaf91afd4,0xafedaf6e,0xa814a17e,0xadfea875,0xaffcaff4,0x2e5e2ff8,
0xac87aaaa,0xaf5aafe6,0xaf5aafc9,0xa6a12993,0xae7cad96,0x9cb6ac87,0xaddcaeb5,0xafc9ad96,0xafafaf30,0x2f1a2c07,0xab5eacd8,0xad00af91,
0xa934a30e,0xae5ea8d5,0xaee9afa0,0x2b052f02,0xad96ac32,0xaeb5afff,0xac87addc,0xad96a515,0xaf80aeb5,0x2765a9f1,0xa515a9f1,0xaf46afdd,
0xaff8afed,0x2ff42dfe,0x28751fd9,0x217eac07,0xaa4ea44e,0xaeb5a934,0xac5dadfe,0x96482cd8,0xae7cad00,0xaddcaff8,0x9cb6a8d5,0xafc9ad00,
0xaff8af80,0x2bb7a515,0x2bb72765,0xab5eaf46,0xaf30afdd,0x2fbc2f5a,0x2ee92d96,0x2dfe25db,0xab5ea515,0xaf02a993,0xa30eaaaa,0xab5e2765,
0xaf30adba,0xacd8afd4,0x2c0726a1,0xaf91af6e,0xafddafed,0x2d961fd9,0x2f5a2dfe,0x25dbac07,0xad72af02,0x2e7c2ff8,0x2fc92ff8,0x2fff2e3f,
0xac32a5db,0xaf46a9f1,0x29939648,0xae7ca5db,0xafafae5e,0xab5eaf91,0x2f1a2d4d,0xad00afed,0xaf30aff8,0x2ee92875,0x2fbc2ff4,0x2dfe217e,
0xa9f1ad72,0x2c5d2fc9,0x2c5d2e7c,0x2d962fff,0xaf80aa4e,0xafc9ac87,0xafe6ac87,0x2f462dba,0xa8d5af30,0x2f02a44e,0xa30eae5e,0xafa09fd9,
0x2fbc2bb7,0xa9342e1f,0x2ffc2d27,0x2c07ad00,0x26a12ed0,0xaa4eafff,0x16482ddc,0x26a12fe6,0xafafaaaa,0xafa0acb0,0xafa0aed0,0x2d002f80,
0xa44eaeb5,0x2f919648,0x2b05aa4e,0xafbcac5d,0x30002d4d,0xac872cd8,0x2e992fbc,0x2f6e9fd9,0xa5152d27,0x9cb6afaf,0xad72230e,0xac322d27,
0xafd4ab05,0xaf6eacd8,0xadbaafed,0x26a12ffc,0x1cb6ae1f,0x2fe6230e,0x2ed0230e,0xad72af1a,0x2faf2e7c,0xae1f2aaa,0x28d52f80,0x2faf2c32,
0xac0729f1,0x2934ae99,0xaffcac87,0xafbc9648,0xafedab5e,0xaf30ad00,0xa934afaf,0xa8142f1a,0x26a1ad72,0x30002765,0x30002cb0,0xa5dbafff,
0x2ed02f5a,0xaf4626a1,0xa9932c87,0x2cb02f5a,0xae3f1fd9,0x2d27acd8,0xae1fafbc,0xaf02ad4d,0xaffcabb7,0xaee9ad27,0x244eae1f,0xad4d2d00,
0x29f1acb0,0x2fdd2993,0x2eb52f46,0x29f1aed0,0x2d722fdd,0xafe69648,0xaed09648,0x9cb62fd4,0xafa0a814,0x2f02a934,0xa30eaf30,0xa8d5afed,
0xb000ac07,0xae99ad4d,0x2c87ab05,0xaf6e2814,0x2c32abb7,0x2f802b5e,0x2aaa2ff8,0x2e7cabb7,0x2b5e2fff,0xaff4a765,0xaff4acb0,0xad272d72,
0xaffcac5d,0x2fed9648,0x2cd8aa4e,0x2b05aeb5,0xaff8ac32,0xae3fad72,0x2f029cb6,0xaff8a515,0x2d4da9f1,0x2ee92c87,0xa44e2e99,0x2ffc1648,
0x26a12fbc,0xaf6eab05,0xadbaaf91,0xafd4244e,0xaf46ae3f,0x2fc928d5,0x2fe628d5,0x2f80a875,0xafe6ac5d,0xaddcad96,0x2fff29f1,0xaed0ac5d,
0x2e3fa814,0x2e1f2d4d,0xad272b05,0x2f022c07,0x9fd92f1a,0xae5ead00,0xa44eafaf,0xaf30ab5e,0xad96af80,0x2e992cb0,0x2e992ed0,0x2f5a2aaa,
0xad72adba,0xa515aeb5,0xac32aeb5,0x9cb62f6e,0x2d272dfe,0xad002fbc,0x2bb72ee9,0x2e1faf30,0xacd8ae3f,0x2ffcab5e,0xab05af1a,0xafed2875,
0x2c872e7c,0xadbaa993,0x2a4e2f46,0x2c872c32,0xad00addc,0xa17eaed0,0xa17eafe6,0xabb72fff,0x2c072e99,0xadfe2f6e,0x9fd93000,0x2fedac87,
0xa9f1af30,0x2fd4a814,0x26a1afed,0xad96a934,0x27652fa0,0xaaaaad00,0xa9932faf,0xa5152fa0,0xac87adfe,0x9648aee9,0x29f1afbc,0xae992f30,
0x29932f1a,0xaed02f02,0xacb02f02,0x2f46a17e,0xa30eafc9,0x2f1a9cb6,0x2e1faddc,0xa30eae7c,0xa44e3000,0x9fd9aeb5,0xaf302c5d,0xae5e2f5a,
0xac07ae1f,0x1fd9af02,0x2dfeae3f,0xafed2d27,0x25db2f80,0xaf6e2e7c,0xaf6e2c32,0x2c5d2aaa,0x2515b000,0x2ddc25db,0x2fffa6a1,0x2c32b000,
0xabb72f91,0x28d5afbc,0xafa0a44e,0xaff42b05,0xab05ae3f,0x244eaf1a,0x2fbcab5e,0xaf912875,0x16482fc9,0xafd42ddc,0xafdd1cb6,0x16482e7c,
0x2aaaafd4,0x2c322a4e,0x2e7c2a4e,0x2f80ae99,0xae1f2e5e,0x2d00affc,0xabb7adfe,0xad27a814,0xa9f1ae5e,0x26a1af30,0x2fd49fd9,0xad96a44e,
0xa5152ff4,0xafff2d27,0xaddcab5e,0xac322ff4,0x2d27af46,0x28752cb0,0x28752ed0,0x2fa0a993,0xaf912c87,0x2ee9af6e,0x2814b000,0x1fd9ae99,
0xa8d5ae7c,0x2875af46,0x2e3f2993,0xa8d5ac32,0xa9343000,0xafed2c5d,0xa814aeb5,0xaf302f5a,0x2e99ae5e,0x16482dfe,0xa9f12ffc,0x2c872814,
0xafff2875,0x2fe6ae1f,0x2ed0ae1f,0x2ddcaff4,0xa765ae99,0x2993af5a,0x2aaa2d96,0x2515ae99,0xabb72fed,0xafa02b05,0x28d5affc,0xaff42cd8,
0x2f91ad27,0xa8142f02,0xaee92e3f,0x9fd92e1f,0xaf5a9cb6,0x2fd4ac32,0x2fd4a515,0x3000ad72,0x2aaaaf6e,0x2ed0afdd,0x2cb0afdd,0xaf803000,
0xaf1a2934,0x2875acd8,0xae3f244e,0xab5e2dfe,0xac072faf,0xab05217e,0xad4d2ff8,0x2814230e,0x2eb5a765,0xaf6e2ddc,0x2dba9cb6,0x2eb5acb0,
0x2bb7af80,0x2f1aafe6,0x2f1aafc9,0xaff42f46,0xae5e26a1,0x2b05ad96,0xa934a9f1,0xaee92fd4,0xadba2ffc,0xa5dba44e,0xafdd2ee9,0xaa4e2d4d,
0x2cb0217e,0xaddc2bb7,0x1cb62d00,0x2765217e,0x2c5daf91,0x2f5aafed,0x3000ae5e,0xaeb52d4d,0xad72217e,0x2cb0ae3f,0x2765ae3f,0xafff2fa0,
0xaf022fe6,0x217ea993,0xaf1a2aaa,0xaf022fc9,0x28142a4e,0xab0525db,0xad4d2fdd,0xac072dba,0x2cd8afa0,0x2f91aff4,0x2f30abb7,0xac0728d5,
0xac5d9cb6,0x2dbaaed0,0x2dbaafe6,0xae992d72,0xafc92f6e,0x2993ac5d,0xaaaaa5db,0xafe62f6e,0xa30e2d4d,0xa17ea44e,0xaff82ee9,0xafaf2ffc,
0x2d4dafaf,0x2fbcaff8,0x2cd8a17e,0x9fd9a30e,0xaa4ea515,0x2e99af46,0x2fd4af80,0xaa4e2765,0xafff2e99,0x2cb0adba,0x2765adba,0xad722c5d,
0xab5e2ee9,0x2875ab05,0xae3f2934,0xaf1a2e5e,0x2dbaafbc,0x2fddaffc,0x25db2934,0x2a4eac07,0xa765a875,0x2f46afa0,0x2f80ad27,0x2515a875,
0xafa02d72,0x2e3faed0,0x2e3fafe6,0xa17e9cb6,0xadfe2fd4,0x2cd8ad96,0xa44ea9f1,0xa93426a1,0x2e1fafc9,0x2ff4afff,0xa8752d72,0x2e1fae7c,
0x9fd9aa4e,0x2fbcafdd,0x2cd8a5db,0x2d4dadba,0xaeb52c07,0x2f5aaf91,0x3000af30,0x2c5dacd8,0xaf802ff4,0x2ed0af1a,0x2cb0af1a,0x2aaaabb7,
0x2e7cafd4,0x2fffb000,0xad722f5a,0x2fc9afd4,0x230eac07,0x2ff8affc,0x217e2934,0x2fafafbc,0xad4d28d5,0x2fedaff4,0x2e5eabb7,0x2f91afa0,
0xb0002f46,0x2fddafe6,0x2fddafc9,0x2f6eaf80,0xaaaaaa4e,0xaed0ac87,0xacb0ac87,0x2f802dba,0xab5eab05,0xafafafed,0xad00acd8,0x2f1a2ffc,
0xac07abb7,0xab05ae1f,0xad4dad27,0x28142d00,0xac5dac32,0x29f19cb6,0xad96ad72,0xac5da515,0xafafaf80,0xafa0afe6,0xafa0afc9,0x2d002f46,
0xafedafd4,0xa934adba,0xaf30af6e,0xa81426a1,0xb000affc,0x2c87244e,0xae99aee9,0xaf6ead4d,0xafe6aff8,0x2fff2f02,0xaddcae3f,0xaed0aff8,
0xaeb5af30,0xaa4eae5e,0x9648a44e,0xac5d9fd9,0xad72ae1f,0x2cb0230e,0x2765230e,0xafffaf1a,0xabb7acb0,0x2ff82f46,0x2b5e2993,0xabb7aed0,
0xa814a9f1,0x2b052e99,0x2d4d2c87,0x2c071648,0xa44ea8d5,0x2b05a30e,0x2f912f02,0xafbcafa0,0x26a11cb6,0x30002ed0,0x30002fe6,0xa5dbad72,
0x2c3229f1,0x2aaa2eb5,0x2f802fdd,0x2e7c29f1,0x2e3f2d4d,0xad27a44e,0x2e1f2ee9,0x2f022ffc,0x2d4d2bb7,0x2fbc2d27,0x2cd82e1f,0x9fd9ad00,
0x2f5a2e7c,0x2c872f80,0x26a12aaa,0x2f5a2c32,0x2fff2fdd,0xacb09648,0xa7659648,0x2d722fd4,0x2f1a2fbc,0xafafaf91,0xad00ab05,0xab5e244e,
0x30002fbc,0x2e992ffc,0xac87a934,0x2f6e2c07,0x2ed02faf,0xa99328d5,0xaf46ae1f,0x2cb02faf,0x2b5e2d72,0xaff4aed0,0xaff4afe6,0xad279cb6,
0x9fd926a1,0xa44eadba,0xae5eaf6e,0xaf30afd4,0x2d272ed0,0x230e2ddc,0xafafafff,0x2d272fe6,0x1fd929f1,0xafbcac87,0xacd8ae99,0xad4d9648,
0xac5da814,0xaa4eaf30,0x9648a934,0xaeb5afed,0xaf80ae3f,0x2ed028d5,0x2cb028d5,0x2aaaa875,0xa51526a1,0xad721648,0x9cb6aa4e,0xac3226a1,
0xae3fac07,0xae1faffc,0x2d272934,0xaf02afbc,0xaffcafa0,0x2cd8a30e,0x2fed2f02,0x2b05a8d5,0xad96af46,0x2e992fe6,0x2e992fc9,0x2f5a2f80,
0xafffadba,0xae7caeb5,0xafc9aeb5,0x2d722f6e,0x217ead4d,0x2ff42814,0x2875ac07,0xaff8ab05,0x2fed2e3f,0xad4d2b5e,0x2f912f1a,0x2e5ea875,
0xa5db2cb0,0x9648af80,0xa9f12aaa,0xa5db2ed0,0xad00afff,0xa17eafc9,0xa17eae7c,0xabb72d72,0x2ee925db,0x2d4d2f5a,0x2ffc2d96,0xa44eafdd,
0x29f12f91,0xafd4ac07,0xa6a12cd8,0x2d962f30,0xafc9ab5e,0x2f46a30e,0xaf80af02,0xafe6ab5e,0x25dbad4d,0x2d96ac07,0x2f5a2814,0xafddab05,
0x2f462f1a,0xa7652f02,0x25152f02,0x2f80a17e,0xad002765,0xa8d5afff,0xaff8ad72,0xad002cb0,0xacd8b000,0x2dfe2eb5,0x2934ac5d,0x244eaf5a,
0x2ee9217e,0x2ffc2875,0x2d4d2ff4,0xa44eaff8,0x25db2f46,0xaf6e2515,0xaf6ea765,0x2c5d2f80,0xafe6ad96,0x2d72ac87,0x9cb6aeb5,0xaed0ad96,
0x2bb7ab05,0xa8d52ee9,0x2fa02e5e,0x2ff42934,0x2f912e3f,0x2cd82f1a,0xac072b5e,0x2f30a875,0xad962765,0xaeb5ad72,0xac87afff,0xad962cb0,
0xa993afd4,0x2fc92a4e,0x2fe62a4e,0x2aaaae99,0x2ff82cd8,0xaff49fd9,0xa8752d4d,0xa17e2fbc,0x29f12fed,0xa6a12f91,0xafd4ad4d,0x2d962e5e,
0xafe6ad00,0x9cb6aff8,0x2d72a8d5,0xaed0ad00,0x2d27a993,0x28752fe6,0x28752fc9,0x2fa02aaa,0x29342fdd,0xac07af5a,0xafbcad96,0xaffca5db,
0xab5e2cb0,0xaf022aaa,0xa30eaf80,0xab5e2ed0,0xab05b000,0x2e5eac5d,0x2ee92eb5,0x2934af5a,0x2fdd2cd8,0xad962d4d,0xaf5a9fd9,0xa5db2fbc,
0xaddc2875,0x2cb0ae1f,0x2765ae1f,0x1cb6aff4,0xafc9a5db,0xaf80a9f1,0x2f469648,0xafe6a5db,0x2bb7acd8,0x2fa02934,0xa8d52dfe,0x2ff4244e,
0x29342ff8,0xafbca875,0xac07aff4,0xaffca17e,0xaf5aaddc,0x2fd42765,0x2fd42cb0,0x30001cb6,0xa993af6e,0x2765afdd,0xa515afdd,0xaaaa3000,
0x28d52f91,0xaf022e5e,0x230e2fed,0x2fa0ad4d,0xa814afaf,0x2f91a17e,0x9fd9aff8,0xaee9a30e,0x26a12fc9,0xaa4ead72,0x16482fff,0x26a12e7c,
0x2bb7af46,0x2f1aae7c,0x2f1aac32,0xaff42993,0xacd82eb5,0xaf301648,0xaf912a4e,0x2c072c5d,0x2dbaadfe,0x25db2e5e,0x2fdda814,0x2a4eaffc,
0xae7c2d27,0x2d72afaf,0xafff230e,0xafc92d27,0x2fd4a934,0x2f6ea44e,0x2dba2cd8,0xa6a1adfe,0xafff217e,0xa515ae3f,0xac32ae3f,0xaddc2fa0,
0x2faf2515,0xae1f2f80,0x28d52f46,0x2fafa765,0xaee9aa4e,0x2f91a5db,0x9fd9afdd,0xa814adba,0x2e5e2b5e,0x29342d00,0xab052faf,0x2ee9af1a,
0xac5daddc,0x2dbaafc9,0x2dbaae7c,0xae999cb6,0x27652f5a,0xaf8026a1,0xaf462c87,0xa5152f5a,0x230eaffc,0x217e2e5e,0x2ff8a814,0x2fafadfe,
0x1fd92faf,0xac072ff8,0xafed217e,0x2dfe230e,0x29f1afe6,0x2fddaaaa,0x2eb52993,0x29f1afc9,0xaddc2e99,0xa515adba,0xac32adba,0xafff2c5d,
0x2fa0ac07,0xaf022f30,0x230e2f91,0x28d52cd8,0xadba2ee9,0xafdd2dfe,0xa5dbaf30,0xaa4e2fbc,0x2fc9abb7,0x2aaa2b5e,0xa9932ff8,0x2fe6abb7,
0xafa09cb6,0x2e3fafc9,0x2e3fae7c,0xa17eaddc,0x2d4d2c5d,0xae5e1648,0xafed2a4e,0xaf912eb5,0xaff82765,0xae3f1cb6,0x2f02addc,0xaff82cb0,
0x2dfe2a4e,0xac072fdd,0xafed25db,0x1fd92dba,0xa6a1aee9,0x2f6ea934,0x2dba2b05,0x2fd4ae5e,0xaaaa2ff4,0x2765af1a,0xa515af1a,0xa993abb7,
0xacb0ac5d,0x9cb6ad96,0x2ddc29f1,0xa765ac5d,0xa30e2fbc,0xaff82dfe,0xa17eaf30,0xafaf2ee9,0x2dfeaf1a,0x244e2d00,0xacd82faf,0x29342b5e,
0xb0002993,0x2fddae7c,0x2fddac32,0x2f6eaf46,0x2ddcb000,0x2fe6afd4,0x2ed0afd4,0xafff2f5a,0xad279fd9,0x2d00aee9,0xabb7a814,0xae1f2f91,
0xae5e2ff4,0x9fd9a8d5,0xaf302fa0,0xa44e2bb7,0x2c872515,0xadba2aaa,0x2a4e2993,0x2c87a765,0x2ff4ad72,0x2e1fac32,0x2e1fa515,0xa8759cb6,
0x2814ae99,0x2ffcaf6e,0x2dfeb000,0xae5e2c87,0xaf5a2b05,0x2eb5afbc,0xac5da44e,0xb0002f91,0xac322fa0,0x2993ad00,0xaf462faf,0xae7c2fa0,
0x2c871fd9,0x16482814,0xa9f12ee9,0x2e99af91,0x2f80afa0,0x2c32a875,0x2e7ca875,0x2aaaad27,0xa30eac32,0x2f1aaddc,0x2e1fafff,0xa30ea515,
0xafed2d96,0x2ffcafd4,0xab05a6a1,0xacd829f1,0xa8142e1f,0xadfe2f02,0xaffc2e3f,0x2e5ead27,0x2e99a993,0xaa4e2cb0,0xaa4e2ed0,0x2fd4af46,
0x2e7cb000,0x1cb625db,0x2ddca6a1,0x2fc9b000,0xa875a934,0x2b5ea814,0x2f1aafed,0x2e3faf30,0xaf302ff4,0xafed2fa0,0xa814a8d5,0xa9342bb7,
0x16482c32,0xafd42fff,0xafdd2ddc,0x16482515,0x2f46ac5d,0xaed02f6e,0xacb02f6e,0x2993a5db,0x2e1fafed,0xad002dfe,0x2bb71fd9,0x2d27ac07,
0xaf5a2cd8,0xac5d2b05,0x2eb5affc,0xb0002fed,0xae7c2ff4,0xaddc2d27,0x9cb6ab5e,0xafc92ff4,0x217e2aaa,0xaf022e7c,0xaf022c32,0xaf1a2f80,
0x2f30ac87,0xafbc2f6e,0xaee93000,0xadfe2e99,0xa8d5a515,0x2875a993,0x2e3faaaa,0xa8d52765,0xaf912d96,0x244ea6a1,0x2fbcafd4,0xab0529f1,
0xae992fed,0x96489fd9,0x29f1adfe,0xac872c07,0x9cb62bb7,0xa515217e,0xac32217e,0xad722d00,0x2c32ae99,0x2f46af5a,0xa9932d96,0x2e7cae99,
0xa875a44e,0x2f1aaf30,0x2b5e9fd9,0x2e3fae5e,0xaf302d27,0x2ee9af02,0x2fbcae3f,0x2dfeae1f,0xaf6e2fff,0x2eb5aed0,0x2eb5afe6,0x2dbaaddc,
0xaddcadba,0xafe6aeb5,0xaed0aeb5,0x2fff2f6e,0xae1fadfe,0xae3fafbc,0xaf02aee9,0x2d272f30,0xae5eae3f,0x9fd9ab5e,0xaf30af1a,0xa44e2875,
0xae99ae7c,0x2d962993,0xaf5aaf46,0xae99ac32,0xad00ad72,0xa17eac32,0xa17ea515,0xabb79cb6,0xac07ac87,0x2dfe29f1,0x1fd99648,0xafedae99,
0xa9f1ab05,0x2fd42fbc,0x26a1244e,0xad96af91,0xa765a8d5,0x2aaa2e3f,0x29932875,0x2515a8d5,0x2e992dfe,0x30002ee9,0x2f6e2fbc,0xac87af30,
0x2f802f1a,0x2c322f02,0x2e7c2f02,0x2aaaa17e,0x2ff42fc9,0xab5e1cb6,0x2d272ddc,0x2ff42e7c,0x2fed3000,0xaffcaeb5,0x2b052c5d,0x2cd82f5a,
0x2c072d27,0x9fd92bb7,0xadfead00,0x2fed2e1f,0x25db2993,0xaf6eacb0,0xaf6eaed0,0x2c5d2f46,0xa5151648,0xaddcafdd,0xafffafd4,0xac321648,
0xabb7a934,0x28d5a814,0xafa0afed,0xaff4af30,0xaf30ae3f,0xafedaf1a,0xa814ab5e,0xa9342875,0xb000afc9,0xa6a1addc,0x25db9cb6,0xb000ae7c,
0xaf46afd4,0x2ed02a4e,0x2cb02a4e,0xa993ae99,0xad27ae5e,0x2e3f2ffc,0x2f022dfe,0x2e1f2814,0xa9f1acd8,0x26a1ab05,0x2fd42ffc,0xad96afed,
0x2515a30e,0x2fff2e1f,0x2ddc2f1a,0x2c32a30e,0x2d272aaa,0x28752e7c,0x28752c32,0x2fa02f80,0x2f912e99,0xaee9a9f1,0xa8141648,0x9fd92c87,
0x2fa02e7c,0x2faf2f46,0xad00a993,0x2fa02c32,0x2f913000,0xa44e2c5d,0xafbcaeb5,0x2b052f5a,0x2c872e5e,0xb000adfe,0xaf6eaffc,0xae99a814,
0x9cb62875,0xa515ae1f,0xac32ae1f,0xad72aff4,0x27652c87,0xa9932a4e,0xaaaaadba,0xa5152c87,0xabb7a44e,0xafa0af30,0x28d59fd9,0xaff4ae5e,
0xaf91ae1f,0x2814abb7,0x2ee92d00,0x1fd9ad27,0xaf5aafff,0x2fd42ed0,0x2fd42fe6,0x30002ddc,0xaf46af6e,0xac32afdd,0xae7cafdd,0x29933000,
0x2b5ea934,0x2faf2cd8,0x2d00a44e,0xaf1aadfe,0x2ee92faf,0xaf30217e,0x2dfe2ff8,0x2fbc230e,0xac5d2765,0x29f1addc,0xad961cb6,0xac5d2cb0,
0x2bb7a993,0x2f1aa515,0x2f1a2765,0xaff4aaaa,0x2e5e2fd4,0xab052dba,0x29342f6e,0x2ee9a6a1,0xadba1fd9,0xa5dbafed,0xafddac07,0xaa4e2dfe,
0xacb0aff8,0x2ddc2f02,0x9cb6ae3f,0xa765aff8,0x2eb52f91,0x2a4e2fed,0x16482e5e,0x2c5dad4d,0xaddc217e,0xae7cae3f,0xafc9ae3f,0x9cb62fa0,
0xabb7afe6,0x2ff82993,0x2b5eaaaa,0xabb7afc9,0x2fbc2a4e,0xaf3025db,0x2dfe2fdd,0x2ee92dba,0xacd828d5,0xaf91230e,0xaf30af02,0x2c072fa0,
0xac5dafff,0x2dbaac32,0x2dbaa515,0xae99addc,0x2fc929f1,0xa9932eb5,0x2aaa2fdd,0x2fe629f1,0xa30e2dfe,0xa17eafed,0xaff8ac07,0xafaf1fd9,
0xadfeafaf,0xa814aff8,0x2e5ea17e,0xaffca30e,0x2f5a2515,0x2c872f46,0x26a12f80,0x2f5aa765,0x9cb62e99,0xae7cadba,0xafc9adba,0xaddc2c5d,
0xaf1aaee9,0x2faf2b05,0x2d00a934,0x2b5eae5e,0x2dbaa814,0x2fdd9fd9,0x25db2f91,0x2a4eaee9,0x27652faf,0xaf4628d5,0xaf80ae1f,0xa5152faf,
0xafa0addc,0x2e3fac32,0x2e3fa515,0xa17eafff,0x2dfea6a1,0xacd82dba,0x244e2f6e,0x29342fd4,0x2d272fc9,0x230e2fff,0xafafad72,0x2d272e7c,
0xaffcaa4e,0xa814afdd,0x2e5ea5db,0xadfeadba,0x2c5dac07,0x2a4e2f91,0x16482f30,0x2eb52cd8,0x29932ff4,0xac32af1a,0xae7caf1a,0xaf46abb7,
0xae7c26a1,0xafff1648,0x2d72aa4e,0xafc926a1,0x230eaee9,0x2ff89fd9,0x217e2f91,0x2fafa814,0x2d4d2fa0,0xafed230e,0xae5eaf02,0xaf9128d5,
0xb000aaaa,0x2fdda515,0x2fdd2765,0x2f6ea993,0x1cb6b000,0x2cb0afd4,0x2765afd4,0xaddc2f5a,0xa17e2ffc,0xaff42c07,0xa8752fbc,0x2ff8a934,
0x244eaff4,0x2dfe28d5,0x2934afa0,0xacd8abb7,0xa5db2fe6,0x9648af46,0xa9f12f80,0xa5db2fc9,0x2ff41cb6,0x2e1f2765,0x2e1f2cb0,0xa875addc,
0xafbca5db,0x1fd9af5a,0xad4dad96,0xacd82fdd,0x2f5a2934,0xaeb52ee9,0x2c5d2e5e,0x3000ab05,0xaed0ab5e,0x2f80a30e,0xaaaaaf02,0xacb0ab5e,
0xa5db2ffc,0xad962fbc,0xaf5a2c07,0x2fdda934,0x2aaaafa0,0x2fc9a875,0x2fe6a875,0xa993ad27,0xad002ed0,0xa8d5ad72,0xaff81cb6,0xad002fe6,
0x2e5ead96,0xad4d2fd4,0x2f9126a1,0x2feda9f1,0xafbca17e,0xad4da875,0x1fd9aff4,0xacd82ff8,0x2e992aaa,0xaa4e2fe6,0xaa4e2fc9,0x2fd4a993,
0xacb0ad96,0x2fffac87,0x2d72aeb5,0xa765ad96,0x28752f30,0xab5eac07,0xaf1a2cd8,0xae3f2f91,0x2934aff4,0x2e5eafa0,0x2ee928d5,0xab05abb7,
0xad962ed0,0xaeb51cb6,0xac87ad72,0xad962fe6,0x2f80ac5d,0xa7652f6e,0x25152f6e,0x2f46a5db,0xaff8244e,0x2ff4ad4d,0x2875affc,0x217eaee9,
0x2f5a244e,0x2c5d2934,0xaeb52dfe,0x3000acd8,0xacb0ad00,0x2d72aff8,0x2fffa8d5,0xa765ad00,0x217e2f80,0xaf022515,0xaf02a765,0xaf1a2f46,
0x2b05afdd,0xa8142f5a,0x2c072d96,0x2d4d25db,0xab5e2fe6,0xaf022f80,0xa30eaf46,0xab5e2fc9,0x2f30ad96,0x2cd826a1,0xac072fd4,0x2f91a9f1,
0xafdd244e,0x2d96affc,0x2f5aad4d,0x25dbaee9,0x2d722bb7,0xae7c217e,0xafc9217e,0xafff2d00,0xaed0a5db,0xaaaaa9f1,0x2f809648,0xacb0a5db,
0x28752e5e,0xaf1a2f91,0xab5ead4d,0xae3f2fed,0x2b05aff8,0x2c072875,0xa8142ff4,0x2d4d217e,0xaf6e2d72,0x2eb5afc9,0x2eb5ae7c,0x2dbaafff,
0x2f80af5a,0x2fc9ae99,0x2fe6ae99,0xaf462d96,0xa8d5ab05,0x2f02afed,0xa30eacd8,0xafa02ffc,0xafbc2f02,0x2934ad27,0xaffc2e1f,0xac072e3f,
0x26a12c32,0xaa4e1cb6,0x16482d72,0x26a12515,0x28752aaa,0xa8d52cb0,0xa8d52ed0,0x2e3faf80,0x2fedaeb5,0x29349648,0x2f30aa4e,0x2814ac5d,
0x1648ad4d,0x2e99acd8,0x2c87afbc,0xa9f11fd9,0xafe62d27,0x2fffafaf,0xaddc230e,0xaed02d27,0xafd42f30,0xaf6e2e5e,0xadba244e,0x26a11fd9,
0x9cb62d27,0xafe62ff4,0xaed02ff4,0x2d72ab5e,0x2fafacb0,0xae1f2f46,0x28d52993,0x2fafaed0,0x2c07af6e,0xa9342c87,0x2ffcae99,0x2fbcb000,
0xa44eab5e,0x2b05ad00,0x2f91afaf,0xafbc2f1a,0xafd42d72,0x1648a765,0x1648acb0,0xafdd2fff,0xac322f5a,0xaaaa26a1,0xaf802c87,0xae7c2f5a,
0x2d009fd9,0xae1f2cd8,0xad272fbc,0xabb72d4d,0x2ffcaf02,0x2ee9ae1f,0xa44e2d27,0x2d4dae3f,0x29f1ae7c,0x2fddaf80,0x2eb5aaaa,0x29f1ac32,
0xad7225db,0x2fe6b000,0x2ed0b000,0x1cb6a6a1,0xafa02fbc,0x2f02af91,0xa30eab05,0xa8d5244e,0x96482c07,0xac872d4d,0xae992b05,0x29f1a814,
0x2ed0abb7,0xa9932b5e,0xaf462ff8,0x2cb0abb7,0x2f1aafff,0xa30e2765,0xa30e2cb0,0x2e1fad72,0x1fd9ac5d,0x244e9648,0x2e5eaa4e,0x2f30aeb5,
0xaff82ed0,0xae3f2ddc,0x2f02afff,0xaff82fe6,0xad4d2f6e,0xaee92e99,0x244eac87,0xaffc3000,0x26a12814,0xaf6e2f30,0xadba2934,0xafd42fed,
0x2f46ad00,0xafc92fa0,0xafe62fa0,0xaf802faf,0x2515ac5d,0x2d72ad96,0x1cb629f1,0x2c32ac5d,0xad002814,0x2d27ad4d,0x2e1fab05,0x2bb7ac07,
0xaffc2f1a,0x2cd8ad00,0x2fedafaf,0x2b05ab5e,0xadba2f80,0x2c87acb0,0x2c87aed0,0x2a4eaaaa,0xaf80af6e,0xafc9afdd,0xafe6afdd,0x2f463000,
0xafa0af91,0xabb7ae5e,0xaff4afed,0x28d52d4d,0xafbcafaf,0x2934a17e,0xaffcaff8,0xac07a30e,0xafd4afc9,0x2f5a2d72,0xb000afff,0xafd4ae7c,
0x2bb72aaa,0x2f1a2cb0,0x2f1a2ed0,0xaff4af80,0x2cd82c5d,0x2f303000,0x2f912f5a,0xac07aeb5,0x2dba2d4d,0x25db2cd8,0x2fdd2fbc,0x2a4e9fd9,
0x2e7c2e1f,0xad72a875,0x2fff2ff4,0x2fc92e1f,0x26a12934,0xa9f1244e,0xad96acd8,0x2fd42dfe,0x9cb6217e,0xafe6ae3f,0xaed0ae3f,0x2d722fa0,
0xa875a515,0xad27af80,0xafa0af46,0xa8752765,0xac07aa4e,0x2934a5db,0xaffcafdd,0xafbcadba,0xae5eaf1a,0xa934ae3f,0x2b052875,0xaee9ab5e,
0xac5dad72,0x2dba2765,0x2dba2cb0,0xae99afff,0xa765aa4e,0x2f802fd4,0x2f462e99,0x2515aa4e,0x230e9fd9,0x217e2cd8,0x2ff82fbc,0x2faf2d4d,
0x2ffc2faf,0x2ee92ff8,0xa44e217e,0x2d4d230e,0x2f6e2fe6,0xa5db2aaa,0xac5da993,0x2f6e2fc9,0x2d722e99,0xafe6adba,0xaed0adba,0x9cb62c5d,
0x28d52c07,0xabb7af30,0xaff4af91,0xafa0acd8,0xadbaac07,0xafddad4d,0xa5dbab05,0xaa4e2814,0xafc9af02,0xaaaaaf1a,0x2993217e,0xafe6af02,
0xafa0afff,0x2e3f2765,0x2e3f2cb0,0xa17ead72,0xad4daeb5,0x2e5e3000,0x2fed2f5a,0x2f912c5d,0x217ea765,0x2d009cb6,0x2bb72ddc,0x217eacb0,
0x2d4d2a4e,0x2ee92fdd,0xa44e25db,0x2ffc2dba,0x2fd42ee9,0xa9f12934,0xad96ab05,0x26a12e5e,0x2f462ff4,0xafc9af1a,0xafe6af1a,0xaf80abb7,
0x2cb02eb5,0x1cb62dba,0xaddcaf6e,0x27652eb5,0xa30e2814,0xaff8ad4d,0xa17eab05,0xafafac07,0xadfeab5e,0xa44eae3f,0x2cd82875,0xa934af1a,
0xb000af80,0x2fdd2cb0,0x2fdd2ed0,0x2f6e2aaa,0xad72b000,0xa515afd4,0xac32afd4,0x9cb62f5a,0x2e1f1fd9,0x2e3f2ee9,0x2f022814,0xad27af91,
0x2cd82ff4,0xaffca8d5,0x2b052fa0,0x2fed2bb7,0xae99a515,0x2d96aaaa,0xaf5aa993,0xae992765,0x2ff42ddc,0x2e1f2ed0,0x2e1f2fe6,0xa875afff,
0xa8142c87,0xaffca9f1,0xadfe1648,0x2e5e2e99,0xaf5aaf30,0x2eb5a814,0xac5dafed,0xb000a934,0x2c32a8d5,0xa9932e3f,0x2f462875,0x2e7ca8d5,
0xae999fd9,0xb000a814,0xaf6eaee9,0x2c872f91,0xa993afa0,0x2ed0a875,0x2cb0a875,0xaf46ad27,0x2ff42c32,0xab5e2ddc,0x2d272fff,0x2ff42515,
0xa44e2d96,0x9fd9afd4,0xaf30a6a1,0xae5e29f1,0x2814ad27,0x2dfeabb7,0x2ffc2d00,0xae5eae1f,0x2e992f80,0xaa4e2e7c,0xaa4e2c32,0x2fd42aaa,
0xae7c1648,0x9cb6afdd,0xaddcafd4,0xafc91648,0xa875af91,0x2b5e2fbc,0x2f1a244e,0x2e3fab05,0x2b052ff4,0xa44e2fa0,0xafbca8d5,0x2f912bb7,
0xb000ac32,0xa6a1afff,0x25dbaddc,0xb000a515,0x2aaaac5d,0x2c322f6e,0x2e7c2f6e,0x2f80a5db,0x2d272fed,0xae3fadfe,0xaf029fd9,0xae1f2c07,
0xaf5aae5e,0xac5daf30,0x2eb59fd9,0xb000a44e,0x2e7ca30e,0x2ddc2e1f,0x1cb62f1a,0x2fc9a30e,0x217e2f46,0xaf02acb0,0xaf02aed0,0xaf1a2993,
0xaf30ae99,0x2fbc29f1,0x2ee99648,0x2dfeac87,0x2fa02515,0x2faf2993,0xad002aaa,0x2fa0a765,0xa9342d96,0xafeda6a1,0xa814afd4,0xaf3029f1,
0xac87afed,0x30001fd9,0x2f6e2dfe,0x2e99ac07,0x2fff2bb7,0xafe6217e,0xaed0217e,0xaddc2d00,0xac322c87,0xaf462a4e,0x2993adba,0xae7c2c87,
0xa875afed,0x2f1aab05,0x2b5e2ffc,0x2e3facd8,0x2f302e1f,0xaee92bb7,0xafbcad00,0xadfe2d27,0xaf6e9cb6,0x2eb5ac32,0x2eb5a515,0x2dbaad72,
0x2aaaaf5a,0x2ed0ae99,0x2cb0ae99,0xaf802d96,0xab5e2f30,0xafaf244e,0xad002e5e,0x2f1a1fd9,0x2c07af02,0x2b052d27,0x2d4dae1f,0xa814ae3f,
0xac5d2ed0,0x29f1afff,0xad962ddc,0xac5d2fe6,0x28752f80,0xa8d52fe6,0xa8d52fc9,0x2e3faf46,0xa44eafd4,0x2f91adba,0x2b05af6e,0xafbc26a1,
0x96482ffc,0xae99a44e,0xac872ee9,0x29f12d4d,0x2515aff8,0x1cb62f02,0x2d72ae3f,0x2c32aff8,0xaeb5ab05,0xaa4eacd8,0x9648afed,0xac5d2ffc,
0x2d722d27,0xacb02ff4,0xa7652ff4,0x2fffab5e,0xabb7ae7c,0x2ff8aaaa,0x2b5eaf80,0xabb7ac32,0x28142f6e,0xab05ac87,0xad4d2e99,0xac073000,
0x2feda8d5,0x2f30a30e,0x29342f02,0x2814afa0,0xafd49cb6,0x1648aed0,0x1648afe6,0xafdd2d72,0x2ed029f1,0xaf462eb5,0xa9932fdd,0x2cb029f1,
0xad00ad4d,0x2e1f244e,0x2d27aee9,0x2bb7affc,0xad4d2f02,0xafbc2e1f,0xacd8ad27,0x1fd92e3f,0x2f5aacb0,0x2c872993,0x26a12f46,0x2f5aaed0,
0xafff25db,0x2cb0b000,0x2765b000,0xad72a6a1,0x2f1a2814,0xafaf2934,0xad002f30,0xab5e2fed,0x1648afbc,0x2c87affc,0x2e992934,0xa9f1ac07,
0xac322faf,0xaf8028d5,0xaaaaae1f,0xae7c2faf,0x2f1aad72,0xa30e2ed0,0xa30e2fe6,0x2e1f1cb6,0xaffc26a1,0x2fedadba,0x2cd8af6e,0x2b05afd4,
0x2d272c32,0x230e2d72,0xafaf1cb6,0x2d272515,0x9fd9af6e,0x2fbcae99,0x2cd82c87,0x2d4db000,0xac5d2fbc,0xaa4eab05,0x9648af91,0xaeb5244e,
0x2f80ad00,0xaed02fa0,0xacb02fa0,0xaaaa2faf,0xafe626a1,0xaddc1648,0x2fffaa4e,0xaed026a1,0x2d002c07,0xad272ffc,0xae1fa934,0xabb72fbc,
0x1fd9afa0,0x2e5ea30e,0x244e2f02,0x2f30a8d5,0xadba2f46,0x2c87afe6,0x2c87afc9,0x2a4eaf80,0x2fffad96,0x2e7cac5d,0x2fc9ac5d,0xad7229f1,
0x217eadfe,0x2ff4afbc,0x2875aee9,0xaff82f30,0xafed2d00,0x2d4daf1a,0xaf912b5e,0xae5e2faf,0xa5db2e7c,0x9648a993,0xa9f12f46,0xa5db2c32,
0xae3f2fff,0xaff82fc9,0xaff82e7c,0x2f02ad72,0x2c0725db,0xadfe2f5a,0x9fd92d96,0x2fedafdd,0x2f6eaf91,0xa6a12c07,0x2fd4acd8,0x2dbaaf30,
0xa765ab5e,0x2aaaa30e,0x2993af02,0x2515ab5e,0x25dbadfe,0x2d96aee9,0x2f5aafbc,0xafdd2f30,0xaf462b5e,0x2765abb7,0xa515abb7,0xaf802ff8,
0xad002fc9,0xa8d51cb6,0xaff82ddc,0xad002e7c,0x2cd81648,0xadfe2c5d,0xa9342eb5,0xa44e2a4e,0x2c07217e,0x9fd92875,0xadfe2ff4,0x2fedaff8,
0x2fddaf46,0x29f1a515,0x29f12765,0x2eb5af80,0x2515ad96,0x2ddcac87,0x2fffaeb5,0x2c32ad96,0xaf022b05,0x2fa0aee9,0x28d5ae5e,0x230ea934,
0xaf912d00,0xacd82b5e,0x2c07af1a,0xaf302faf,0xad962fc9,0xaeb52ddc,0xac871cb6,0xad962e7c,0x299326a1,0xafc92f5a,0xafe62f5a,0xaaaa2c87,
0x2ff8ae5e,0xaff42ffc,0xa8752dfe,0xa17e2814,0x2f6eafed,0x2fd4af91,0xa6a12d4d,0x2dbaae5e,0x2515ad00,0x2fffaff8,0x2ddca8d5,0x2c32ad00,
0xae1f2993,0x2fafafe6,0x2fafafc9,0x28d5aaaa,0xaf912fdd,0x2ee9af5a,0x2814ad96,0x1fd9a5db,0xab5e2e7c,0xaf022f46,0xa30ea993,0xab5e2c32,
0x2b051648,0xae5e2eb5,0xaee92c5d,0xa9342a4e,0x2fddae5e,0xad962dfe,0xaf5a2ffc,0xa5db2814,0x2ddcafaf,0xacb02d27,0xa7652d27,0x9cb6230e,
0xa765a5db,0x2993a9f1,0x2aaa9648,0x2515a5db,0xaf022cd8,0x28d5a934,0x2fa0adfe,0x230ea44e,0xaf912ff8,0x2814a875,0x2ee9aff4,0x1fd9a17e,
0xaa4e2ddc,0x26a1a765,0x26a1acb0,0x16489cb6,0x9d7f9e49,0xaddcaeb3,0x12480000,0x22ad0000,0x9bdb9cb6,0xac2ead04,0x18b61648,0x290226ad,
0x98b69a49,0xa902aaaf,0x1bdb1a49,0x2c2e2aaf,0x92489648,0xa2ada6ad,0x1d7f1cb6,0x2ddc2d04,0xa420a4b7,0xae8daf7f,0x18b60000,0x23760000,
0xa1e4a312,0xacacad9c,0x1f121cb6,0x29992777,0x9f12a0b6,0xa999ab78,0x21e420b6,0x2cac2b78,0x98b69cb6,0xa376a777,0x24202312,0x2e8d2d9c,
0xa6e0a7db,0xaf3fb025,0x1bdb0000,0x24200000,0xa4e9a5e4,0xad2aae34,0x21e41fdb,0x2a312820,0xa1e4a3db,0xaa31ac21,0x24e923db,0x2d2a2c21,
0x9bdb9fdb,0xa420a820,0x26e025e4,0x2f3f2e34,0xa8d0a980,0xaff2b08c,0x1d7f0000,0x24840000,0xa6e0a820,0xada9aecd,0x2420217f,0x2ac82885,
0xa420a580,0xaac8ac86,0x26e02580,0x2da92c86,0x9d7fa17f,0xa484a885,0x28d02820,0x2ff22ecd,0xaa31ab13,0xb052b0f3,0x1f120000,0x24e90000,
0xa86ba94e,0xae28af65,0x254d2312,0x2b5f28e9,0xa54da712,0xab5faceb,0x286b2712,0x2e282ceb,0x9f12a312,0xa4e9a8e9,0x2a31294e,0x30522f65,
0xab91ac54,0xb0acb15a,0x20520000,0x254d0000,0xa967aa7c,0xaea7affe,0x267b2452,0x2bf6294e,0xa67ba852,0xabf6ad50,0x29672852,0x2ea72d50,
0xa052a452,0xa54da94e,0x2b912a7c,0x30ac2ffe,0xac79ad1e,0xb106b1c1,0x211b0000,0x25b20000,0xaa63abab,0xaf26b04c,0x27a9251b,0x2c4729b3,
0xa7a9a91c,0xac47adb6,0x2a63291c,0x2f262db6,0xa11ba51b,0xa5b2a9b3,0x2c792bab,0x3106304c,0xad2aade8,0xb160b229,0x21e40000,0x26170000,
0xab5fac6d,0xafa5b099,0x286b25e4,0x2c932a17,0xa86ba9e5,0xac93ae1b,0x2b5f29e5,0x2fa52e1b,0xa1e4a5e4,0xa617aa17,0x2d2a2c6d,0x31603099,
0xb1bbb292,0xb44fb4f6,0x267b0000,0x28d00000,0xb012b0e6,0xb216b357,0x2cde2a7c,0x2f3f2cd2,0xacdeae80,0xaf3fb0d9,0x30122e80,0x321630d9,
0xa67baa7c,0xa8d0acd2,0x31bb30e6,0x344f3357,0xb216b2fb,0xb47eb52d,0x26e00000,0x29020000,0xb052b133,0xb257b3a7,0x2d2a2ae1,0x2f8c2d04,
0xad2aaee6,0xaf8cb10c,0x30522ee6,0x3257310c,0xa6e0aae1,0xa902ad04,0x32163133,0x347e33a7,0xb271b364,0xb4aeb565,0x27440000,0x29350000,
0xb092b181,0xb298b3f7,0x2d762b46,0x2fd82d37,0xad76af4c,0xafd8b140,0x30922f4c,0x32983140,0xa744ab46,0xa935ad37,0x32713181,0x34ae33f7,
0xb2cdb3cf,0xb4deb59d,0x27a90000,0x29670000,0xb0d2b1ce,0xb2dab423,0x2dc22bab,0x30122d6a,0xadc2afb2,0xb012b174,0x30d22fb2,0x32da3174,
0xa7a9abab,0xa967ad6a,0x32cd31ce,0x34de3423,0xb329b41d,0xb50eb5d6,0x28070000,0x29990000,0xb113b21c,0xb31cb44c,0x2e0e2c08,0x30392d9c,
0xae0eb00c,0xb039b1a7,0x3113300c,0x331c31a7,0xa807ac08,0xa999ad9c,0x3329321c,0x350e344c,0xb386b453,0xb53fb60f,0x28390000,0x29cc0000,
0xb153b26b,0xb35eb474,0x2e5a2c3a,0x305f2dcf,0xae5ab03f,0xb05fb1db,0x3153303f,0x335e31db,0xa839ac3a,0xa9ccadcf,0x3386326b,0x353f3474,
0xb3e3b489,0xb570b649,0x286b0000,0x29fe0000,0xb194b2b9,0xb3a0b49d,0x2ea72c6d,0x30852e02,0xaea7b072,0xb085b20f,0x31943072,0x33a0320f,
0xa86bac6d,0xa9feae02,0x33e332b9,0x3570349d,0xb420b4bf,0xb5a1b683,0x289e0000,0x2a310000,0xb1d5b308,0xb3e3b4c6,0x2ef32c9f,0x30ac2e34,
0xaef3b0a5,0xb0acb243,0x31d530a5,0x33e33243,0xa89eac9f,0xaa31ae34,0x34203308,0x35a134c6,0xb5d2b6be,0xb76fb857,0x2a630000,0x2bf60000,
0xb413b4ef,0xb523b642,0x30d22e67,0x32092ffe,0xb0d2b278,0xb209b40f,0x34133278,0x3523340f,0xaa63ae67,0xabf6affe,0x35d234ef,0x376f3642,
0xb604b6fa,0xb7a5b878,0x2a950000,0x2c140000,0xb434b519,0xb546b66d,0x30f92e9a,0x32303019,0xb0f9b2ac,0xb230b42a,0x343432ac,0x3546342a,
0xaa95ae9a,0xac14b019,0x36043519,0x37a5366d,0xb637b736,0xb7dbb899,0x2ac80000,0x2c2e0000,0xb456b542,0xb569b699,0x31202ecd,0x32573032,
0xb120b2e1,0xb257b445,0x345632e1,0x35693445,0xaac8aecd,0xac2eb032,0x36373542,0x37db3699,0xb66ab773,0xb809b8bb,0x2afa0000,0x2c470000,
0xb478b56c,0xb58cb6c6,0x31462f00,0x327e304c,0xb146b315,0xb27eb460,0x34783315,0x358c3460,0xaafaaf00,0xac47b04c,0x366a356c,0x380936c6,
0xb69db7b0,0xb825b8dd,0x2b2d0000,0x2c600000,0xb49ab596,0xb5afb6f2,0x316d2f32,0x32a53065,0xb16db34a,0xb2a5b47b,0x349a334a,0x35af347b,
0xab2daf32,0xac60b065,0x369d3596,0x382536f2,0xb6d1b7ee,0xb841b8ff,0x2b5f0000,0x2c790000,0xb4bcb5c1,0xb5d2b71f,0x31942f65,0x32cd307f,
0xb194b37f,0xb2cdb496,0x34bc337f,0x35d23496,0xab5faf65,0xac79b07f,0x36d135c1,0x3841371f,0xb705b817,0xb85db923,0x2b910000,0x2c930000,
0xb4deb5eb,0xb5f6b74d,0x31bb2f98,0x32f43099,0xb1bbb3b4,0xb2f4b4b1,0x34de33b4,0x35f634b1,0xab91af98,0xac93b099,0x370535eb,0x385d374d,
0xb73ab837,0xb87ab946,0x2bc40000,0x2cac0000,0xb500b616,0xb61ab77a,0x31e22fcb,0x331c30b2,0xb1e2b3e9,0xb31cb4cd,0x350033e9,0x361a34cd,
0xabc4afcb,0xacacb0b2,0x373a3616,0x387a377a,0xb897b96b,0xb98dbaa6,0x2cc50000,0x2d900000,0xb63eb7a8,0xb767b895,0x334330cc,0x3442319a,
0xb343b4e8,0xb442b5c8,0x363e34e8,0x376735c8,0xacc5b0cc,0xad90b19a,0x389737a8,0x398d3895,0xb8b4b990,0xb9aebad1,0x2cde0000,0x2da90000,
0xb662b7d7,0xb78db8ae,0x336b30e6,0x345631b4,0xb36bb504,0xb456b5e4,0x36623504,0x378d35e4,0xacdeb0e6,0xada9b1b4,0x38b437d7,0x39ae38ae,
0xb8d2b9b5,0xb9cfbafd,0x2cf80000,0x2dc20000,0xb687b803,0xb7b4b8c7,0x339330ff,0x346a31ce,0xb393b51f,0xb46ab601,0x3687351f,0x37b43601,
0xacf8b0ff,0xadc2b1ce,0x38d23803,0x39cf38c7,0xb8f0b9dc,0xb9f1bb29,0x2d110000,0x2ddc0000,0xb6acb81b,0xb7dbb8e1,0x33bb3119,0x347e31e8,
0xb3bbb53b,0xb47eb61e,0x36ac353b,0x37db361e,0xad11b119,0xaddcb1e8,0x38f0381b,0x39f138e1,0xb90fba02,0xba14bb57,0x2d2a0000,0x2df50000,
0xb6d1b833,0xb801b8fb,0x33e33133,0x34933202,0xb3e3b557,0xb493b63a,0x36d13557,0x3801363a,0xad2ab133,0xadf5b202,0x390f3833,0x3a1438fb,
0xb92eba2a,0xba37bb86,0x2d440000,0x2e0e0000,0xb6f6b84b,0xb815b915,0x3405314d,0x34a7321c,0xb405b573,0xb4a7b657,0x36f63573,0x38153657,
0xad44b14d,0xae0eb21c,0x392e384b,0x3a373915,0xb94dba53,0xba5abbb6,0x2d5d0000,0x2e280000,0xb71bb863,0xb829b930,0x34193167,0x34bc3236,
0xb419b58f,0xb4bcb675,0x371b358f,0x38293675,0xad5db167,0xae28b236,0x394d3863,0x3a5a3930,0xb96dba7c,0xba7ebbe7,0x2d760000,0x2e410000,
0xb741b87c,0xb83db94b,0x342e3181,0x34d03250,0xb42eb5ab,0xb4d0b692,0x374135ab,0x383d3692,0xad76b181,0xae41b250,0x396d387c,0x3a7e394b,
0xa17fa248,0xb1cfb2a1,0x16480000,0x26ad0000,0x9fdba0b6,0xb029b0fd,0x1cb61a48,0x2d002aac,0x9cb69e48,0xad00aeaa,0x1fdb1e48,0x30292eaa,
0x96489a48,0xa6adaaac,0x217f20b6,0x31cf30fd,0xa81fa8b6,0xb27cb365,0x1cb60000,0x27760000,0xa5e4a711,0xb0a6b191,0x231120b6,0x2d972b75,
0xa311a4b6,0xad97af72,0x25e424b6,0x30a62f72,0x9cb6a0b6,0xa776ab75,0x281f2711,0x327c3191,0xaadeabd9,0xb328b414,0x1fdb0000,0x281f0000,
0xa8e8a9e3,0xb122b226,0x25e423db,0x2e2d2c1f,0xa5e4a7da,0xae2db01d,0x28e827da,0x3122301d,0x9fdba3db,0xa81fac1f,0x2ade29e3,0x33283226,
0xaccead7e,0xb3d3b475,0x217f0000,0x28840000,0xaadeac1f,0xb19eb2b9,0x281f257f,0x2ec32c83,0xa81fa97f,0xaec3b080,0x2ade297f,0x319e3080,
0xa17fa57f,0xa884ac83,0x2cce2c1f,0x33d332b9,0xae2daf0e,0xb43eb4d5,0x23110000,0x28e80000,0xac6aad4c,0xb219b34c,0x294d2711,0x2f592ce7,
0xa94dab11,0xaf59b0e4,0x2c6a2b11,0x321930e4,0xa311a711,0xa8e8ace7,0x2e2d2d4c,0x343e334c,0xaf8bb04e,0xb493b534,0x24520000,0x294d0000,
0xad65ae78,0xb294b3df,0x2a7a2852,0x2fef2d4c,0xaa7aac51,0xafefb147,0x2d652c51,0x32943147,0xa452a852,0xa94dad4c,0x2f8b2e78,0x349333df,
0xb074b115,0xb4e7b593,0x251b0000,0x29b10000,0xae5fafa4,0xb30fb438,0x2ba7291b,0x30422db0,0xaba7ad1a,0xb042b1aa,0x2e5f2d1a,0x330f31aa,
0xa51ba91b,0xa9b1adb0,0x30742fa4,0x34e73438,0xb122b1db,0xb53ab5f1,0x25e40000,0x2a160000,0xaf59b067,0xb389b481,0x2c6a29e3,0x308d2e14,
0xac6aade2,0xb08db20d,0x2f592de2,0x3389320d,0xa5e4a9e3,0xaa16ae14,0x31223067,0x353a3481,0xb58db64e,0xb805b887,0x2a7a0000,0x2cce0000,
0xb402b4c9,0xb5dfb6f9,0x30d72e78,0x332830cb,0xb0d7b26f,0xb328b4bd,0x3402326f,0x35df34bd,0xaa7aae78,0xacceb0cb,0x358d34c9,0x380536f9,
0xb5dfb6aa,0xb82ab8b0,0x2ade0000,0x2d000000,0xb43eb511,0xb61ab73d,0x31222edc,0x337130fd,0xb122b2d2,0xb371b4ed,0x343e32d2,0x361a34ed,
0xaadeaedc,0xad00b0fd,0x35df3511,0x382a373d,0xb631b705,0xb850b8d8,0x2b430000,0x2d330000,0xb47bb558,0xb654b780,0x316c2f40,0x33ba312e,
0xb16cb334,0xb3bab51d,0x347b3334,0x3654351d,0xab43af40,0xad33b12e,0x36313558,0x38503780,0xb682b75e,0xb874b900,0x2ba70000,0x2d650000,
0xb4b7b59f,0xb68db7c2,0x31b62fa4,0x34023160,0xb1b6b396,0xb402b54c,0x34b73396,0x368d354c,0xaba7afa4,0xad65b160,0x3682359f,0x387437c2,
0xb6d2b7b7,0xb899b927,0x2c060000,0x2d970000,0xb4f3b5e5,0xb6c6b802,0x32013004,0x34263191,0xb201b3f7,0xb426b57c,0x34f333f7,0x36c6357c,
0xac06b004,0xad97b191,0x36d235e5,0x38993802,0xb721b807,0xb8bcb94d,0x2c380000,0x2dc90000,0xb52fb62b,0xb6ffb822,0x324b3036,0x344b31c3,
0xb24bb42c,0xb44bb5ab,0x352f342c,0x36ff35ab,0xac38b036,0xadc9b1c3,0x3721362b,0x38bc3822,0xb76fb832,0xb8e0b972,0x2c6a0000,0x2dfb0000,
0xb56ab670,0xb737b842,0x32943067,0x346f31f4,0xb294b45d,0xb46fb5da,0x356a345d,0x373735da,0xac6ab067,0xadfbb1f4,0x376f3670,0x38e03842,
0xb7bdb85d,0xb902b996,0x2c9c0000,0x2e2d0000,0xb5a5b6b5,0xb76fb862,0x32de3099,0x34933226,0xb2deb48d,0xb493b608,0x35a5348d,0x376f3608,
0xac9cb099,0xae2db226,0x37bd36b5,0x39023862,0xb924b9ba,0xba1dbab5,0x2e5f0000,0x2fef0000,0xb7a6b881,0xb8a8b96d,0x34b73257,0x35d433df,
0xb4b7b637,0xb5d4b7a1,0x37a63637,0x38a837a1,0xae5fb257,0xafefb3df,0x39243881,0x3a1d396d,0xb946b9dc,0xba39bad0,0x2e910000,0x30100000,
0xb7ddb8a0,0xb8c1b989,0x34db3288,0x35f73408,0xb4dbb665,0xb5f7b7cd,0x37dd3665,0x38c137cd,0xae91b288,0xb010b408,0x394638a0,0x3a393989,
0xb966b9fe,0xba54bae9,0x2ec30000,0x30290000,0xb80ab8bf,0xb8dbb9a4,0x34ff32b9,0x361a3420,0xb4ffb693,0xb61ab7f9,0x380a3693,0x38db37f9,
0xaec3b2b9,0xb029b420,0x396638bf,0x3a5439a4,0xb986ba1f,0xba6fbb02,0x2ef50000,0x30420000,0xb825b8dd,0xb8f3b9be,0x352332ea,0x363c3438,
0xb523b6c1,0xb63cb812,0x382536c1,0x38f33812,0xaef5b2ea,0xb042b438,0x398638dd,0x3a6f39be,0xb9a6ba3f,0xba89bb1a,0x2f270000,0x305b0000,
0xb840b8fb,0xb90cb9d8,0x3546331b,0x365f3451,0xb546b6ee,0xb65fb828,0x384036ee,0x390c3828,0xaf27b31b,0xb05bb451,0x39a638fb,0x3a8939d8,
0xb9c5ba5e,0xbaa2bb30,0x2f590000,0x30740000,0xb85ab918,0xb924b9f2,0x356a334c,0x36823469,0xb56ab71b,0xb682b83d,0x385a371b,0x3924383d,
0xaf59b34c,0xb074b469,0x39c53918,0x3aa239f2,0xb9e3ba7c,0xbababb46,0x2f8b0000,0x308d0000,0xb874b935,0xb93cba0b,0x358d337d,0x36a43481,
0xb58db748,0xb6a4b852,0x38743748,0x393c3852,0xaf8bb37d,0xb08db481,0x39e33935,0x3aba3a0b,0xba00ba99,0xbad1bb5a,0x2fbd0000,0x30a60000,
0xb88eb951,0xb954ba23,0x35b133ae,0x36c63499,0xb5b1b775,0xb6c6b867,0x388e3775,0x39543867,0xafbdb3ae,0xb0a6b499,0x3a003951,0x3ad13a23,
0xbae8bb6e,0xbb7fbbdd,0x30be0000,0x31850000,0xb96bba3b,0xba19bae6,0x36e834b1,0x37f33570,0xb6e8b87c,0xb7f3b91d,0x396b387c,0x3a19391d,
0xb0beb4b1,0xb185b570,0x3ae83a3b,0x3b7f3ae6,0xbafebb80,0xbb8ebbe6,0x30d70000,0x319e0000,0xb982ba52,0xba2dbaf9,0x370a34c9,0x380a3587,
0xb70ab891,0xb80ab930,0x39823891,0x3a2d3930,0xb0d7b4c9,0xb19eb587,0x3afe3a52,0x3b8e3af9,0xbb13bb91,0xbb9cbbed,0x30f00000,0x31b60000,
0xb999ba69,0xba41bb0b,0x372c34e1,0x381a359f,0xb72cb8a6,0xb81ab943,0x399938a6,0x3a413943,0xb0f0b4e1,0xb1b6b59f,0x3b133a69,0x3b9c3b0b,
0xbb27bba0,0xbba9bbf4,0x31090000,0x31cf0000,0xb9afba7f,0xba54bb1d,0x374e34f9,0x382a35b6,0xb74eb8ba,0xb82ab956,0x39af38ba,0x3a543956,
0xb109b4f9,0xb1cfb5b6,0x3b273a7f,0x3ba93b1d,0xbb3abbaf,0xbbb5bbf8,0x31220000,0x31e80000,0xb9c5ba95,0xba67bb2e,0x376f3511,0x383a35ce,
0xb76fb8ce,0xb83ab969,0x39c538ce,0x3a673969,0xb122b511,0xb1e8b5ce,0x3b3a3a95,0x3bb53b2e,0xbb4cbbbc,0xbbc0bbfc,0x313b0000,0x32010000,
0xb9dabaaa,0xba7abb3e,0x37903529,0x384a35e5,0xb790b8e2,0xb84ab97b,0x39da38e2,0x3a7a397b,0xb13bb529,0xb201b5e5,0x3b4c3aaa,0x3bc03b3e,
0xbb5ebbc9,0xbbcbbbff,0x31530000,0x32190000,0xb9f0babf,0xba8cbb4e,0x37b23540,0x385a35fd,0xb7b2b8f6,0xb85ab98d,0x39f038f6,0x3a8c398d,
0xb153b540,0xb219b5fd,0x3b5e3abf,0x3bcb3b4e,0xbb6fbbd4,0xbbd4bc00,0x316c0000,0x32320000,0xba04bad3,0xba9ebb5d,0x37d23558,0x386a3614,
0xb7d2b909,0xb86ab99f,0x3a043909,0x3a9e399f,0xb16cb558,0xb232b614,0x3b6f3ad3,0x3bd43b5d,0x0,0x0,0x0,0x0,
0x2e1f0000,0x336431a8,0x33643400,0x2e1f31a8,0x31a80000,0x31a83400,0xb1a80000,0xb1a8b400,0x33640000,0xae1f31a8,0xae1fb400,0x336431a8,
0x34000000,0xb4000000,0x34000000,0xb4000000,0x33640000,0xae1fb1a8,0xae1f3400,0x3364b1a8,0x31a80000,0x31a8b400,0xb1a80000,0xb1a83400,
0x2e1f0000,0x3364b1a8,0x3364b400,0x2e1fb1a8,0x0,0x0,0x0,0x0,0xae1f0000,0xb36431a8,0xb3643400,0xae1f31a8,
0xb1a80000,0xb1a83400,0x31a80000,0x31a8b400,0xb3640000,0x2e1f31a8,0x2e1fb400,0xb36431a8,0xb4000000,0x34000000,0xb4000000,0x34000000,
0xb3640000,0x2e1fb1a8,0x2e1f3400,0xb364b1a8,0xb1a80000,0xb1a8b400,0x31a80000,0x31a83400,0xae1f0000,0xb364b1a8,0xb364b400,0xae1fb1a8,
0x0,0x0,0x0,0x0,0xae1f0000,0xb364b1a8,0xb364b400,0xae1fb1a8,0x31a80000,0x31a83400,0xb1a80000,0xb1a8b400,
0xb3640000,0x2e1fb1a8,0x2e1f3400,0xb364b1a8,0x34000000,0xb4000000,0x34000000,0xb4000000,0xb3640000,0x2e1f31a8,0x2e1fb400,0xb36431a8,
0x31a80000,0x31a8b400,0xb1a80000,0xb1a83400,0xae1f0000,0xb36431a8,0xb3643400,0xae1f31a8,0x0,0x0,0x0,0x0,
0x2e1f0000,0x3364b1a8,0x3364b400,0x2e1fb1a8,0xb1a80000,0xb1a83400,0x31a80000,0x31a8b400,0x33640000,0xae1fb1a8,0xae1f3400,0x3364b1a8,
0xb4000000,0x34000000,0xb4000000,0x34000000,0x33640000,0xae1f31a8,0xae1fb400,0x336431a8,0xb1a80000,0xb1a8b400,0x31a80000,0x31a83400,
0x2e1f0000,0x336431a8,0x33643400,0x2e1f31a8,0x34003400,0x34003400,0x34003400,0x34003400,0x33643400,0x2e1f31a8,0xae1f0000,0xb364b1a8,
0x31a83400,0xb1a80000,0xb1a8b400,0x31a80000,0x2e1f3400,0xb364b1a8,0x33640000,0xae1f31a8,0x3400,0xb400,0x3400,0xb400,
0xae1f3400,0x3364b1a8,0xb3640000,0x2e1f31a8,0xb1a83400,0x31a80000,0x31a8b400,0xb1a80000,0xb3643400,0xae1f31a8,0x2e1f0000,0x3364b1a8,
0xb4003400,0xb4003400,0xb4003400,0xb4003400,0xb3643400,0xae1f31a8,0x2e1f0000,0x3364b1a8,0xb1a83400,0x31a80000,0x31a8b400,0xb1a80000,
0xae1f3400,0x3364b1a8,0xb3640000,0x2e1f31a8,0x3400,0xb400,0x3400,0xb400,0x2e1f3400,0xb364b1a8,0x33640000,0xae1f31a8,
0x31a83400,0xb1a80000,0xb1a8b400,0x31a80000,0x33643400,0x2e1f31a8,0xae1f0000,0xb364b1a8,0x34003400,0x34003400,0x34003400,0x34003400,
0xb364b400,0xae1fb1a8,0x2e1f0000,0x336431a8,0x31a83400,0xb1a80000,0xb1a8b400,0x31a80000,0xae1fb400,0x336431a8,0xb3640000,0x2e1fb1a8,
0x3400,0xb400,0x3400,0xb400,0x2e1fb400,0xb36431a8,0x33640000,0xae1fb1a8,0xb1a83400,0x31a80000,0x31a8b400,0xb1a80000,
0x3364b400,0x2e1fb1a8,0xae1f0000,0xb36431a8,0xb4003400,0xb4003400,0xb4003400,0xb4003400,0x3364b400,0x2e1fb1a8,0xae1f0000,0xb36431a8,
0xb1a83400,0x31a80000,0x31a8b400,0xb1a80000,0x2e1fb400,0xb36431a8,0x33640000,0xae1fb1a8,0x3400,0xb400,0x3400,0xb400,
0xae1fb400,0x336431a8,0xb3640000,0x2e1fb1a8,0x31a83400,0xb1a80000,0xb1a8b400,0x31a80000,0xb364b400,0xae1fb1a8,0x2e1f0000,0x336431a8,
0x0,0x0,0x0,0x0,0xae1f0000,0xb364b1a8,0xb364b400,0xae1fb1a8,0xb1a80000,0xb1a8b400,0x31a80000,0x31a83400,
0xb3640000,0x2e1fb1a8,0x2e1f3400,0xb364b1a8,0xb4000000,0x34000000,0xb4000000,0x34000000,0xb3640000,0x2e1f31a8,0x2e1fb400,0xb36431a8,
0xb1a80000,0xb1a83400,0x31a80000,0x31a8b400,0xae1f0000,0xb36431a8,0xb3643400,0xae1f31a8,0x0,0x0,0x0,0x0,
0x2e1f0000,0x3364b1a8,0x3364b400,0x2e1fb1a8,0x31a80000,0x31a8b400,0xb1a80000,0xb1a83400,0x33640000,0xae1fb1a8,0xae1f3400,0x3364b1a8,
0x34000000,0xb4000000,0x34000000,0xb4000000,0x33640000,0xae1f31a8,0xae1fb400,0x336431a8,0x31a80000,0x31a83400,0xb1a80000,0xb1a8b400,
0x2e1f0000,0x336431a8,0x33643400,0x2e1f31a8,0x0,0x0,0x0,0x0,0x2e1f0000,0x336431a8,0x33643400,0x2e1f31a8,
0xb1a80000,0xb1a8b400,0x31a80000,0x31a83400,0x33640000,0xae1f31a8,0xae1fb400,0x336431a8,0xb4000000,0x34000000,0xb4000000,0x34000000,
0x33640000,0xae1fb1a8,0xae1f3400,0x3364b1a8,0xb1a80000,0xb1a83400,0x31a80000,0x31a8b400,0x2e1f0000,0x3364b1a8,0x3364b400,0x2e1fb1a8,
0x0,0x0,0x0,0x0,0xae1f0000,0xb36431a8,0xb3643400,0xae1f31a8,0x31a80000,0x31a8b400,0xb1a80000,0xb1a83400,
0xb3640000,0x2e1f31a8,0x2e1fb400,0xb36431a8,0x34000000,0xb4000000,0x34000000,0xb4000000,0xb3640000,0x2e1fb1a8,0x2e1f3400,0xb364b1a8,
0x31a80000,0x31a83400,0xb1a80000,0xb1a8b400,0xae1f0000,0xb364b1a8,0xb364b400,0xae1fb1a8,
};

typedef CUresult (*EncodeFn)(CUtensorMap*, CUtensorMapDataType, cuuint32_t, void*, const cuuint64_t*, const cuuint64_t*,
                             const cuuint32_t*, const cuuint32_t*, CUtensorMapInterleave, CUtensorMapSwizzle,
                             CUtensorMapL2promotion, CUtensorMapFloatOOBfill);

}

extern "C" void kernel_launch(void* const* d_in, const int* in_sizes, int n_in, void* d_out, int out_size) {
    Params p;
    p.x = (const __nv_bfloat16*)d_in[0];
    p.lar = (const __nv_bfloat16*)d_in[1];
    p.aim = (const __nv_bfloat16*)d_in[2];
    p.cr = (const __nv_bfloat16*)d_in[3];
    p.ci = (const __nv_bfloat16*)d_in[4];
    p.logdt = (const __nv_bfloat16*)d_in[5];
    p.dskip = (const __nv_bfloat16*)d_in[6];
    p.wr = (const __nv_bfloat16*)d_in[8];
    p.out = (__nv_bfloat16*)d_out;
    cudaGetSymbolAddress((void**)&p.sc, g_scratch);
    cudaGetSymbolAddress((void**)&p.tab, g_tab);

    void* fn = nullptr;
    cudaDriverEntryPointQueryResult qr;
    cudaGetDriverEntryPoint("cuTensorMapEncodeTiled", &fn, cudaEnableDefault, &qr);
    EncodeFn enc = (EncodeFn)fn;
    CUtensorMap tm_x, tm_g, tm_d;
    const cuuint32_t es[5] = {1, 1, 1, 1, 1};
    {
        const cuuint64_t gd[4] = {1024, 128, 8, 2}, gs[3] = {32768, 4096, 2048};
        const cuuint32_t bx[4] = {16, 64, 4, 1};
        enc(&tm_x, CU_TENSOR_MAP_DATA_TYPE_BFLOAT16, 4, d_in[0], gd, gs, bx, es, CU_TENSOR_MAP_INTERLEAVE_NONE,
            CU_TENSOR_MAP_SWIZZLE_NONE, CU_TENSOR_MAP_L2_PROMOTION_NONE, CU_TENSOR_MAP_FLOAT_OOB_FILL_NONE);
    }
    {
        char *wg = (char*)d_in[9], *wu = (char*)d_in[10];
        p.up_first = wu < wg;
        const cuuint64_t gd[3] = {3584, 1024, 2}, gs[2] = {7168, (cuuint64_t)(p.up_first ? wg - wu : wu - wg)};
        const cuuint32_t bx[3] = {64, 64, 2};
        enc(&tm_g, CU_TENSOR_MAP_DATA_TYPE_BFLOAT16, 3, p.up_first ? wu : wg, gd, gs, bx, es, CU_TENSOR_MAP_INTERLEAVE_NONE,
            CU_TENSOR_MAP_SWIZZLE_128B, (CUtensorMapL2promotion)GPROMO, CU_TENSOR_MAP_FLOAT_OOB_FILL_NONE);
    }
    {
        const cuuint64_t gd[3] = {64, 3584, 16}, gs[2] = {2048, 128};
        const cuuint32_t bx[3] = {64, 64, 2};
        enc(&tm_d, CU_TENSOR_MAP_DATA_TYPE_BFLOAT16, 3, d_in[11], gd, gs, bx, es, CU_TENSOR_MAP_INTERLEAVE_NONE,
            CU_TENSOR_MAP_SWIZZLE_128B, (CUtensorMapL2promotion)DPROMO, CU_TENSOR_MAP_FLOAT_OOB_FILL_NONE);
    }
    cudaFuncSetAttribute(fused_kernel, cudaFuncAttributeMaxDynamicSharedMemorySize, SM_TOTAL + 256);
    fused_kernel<<<128, NTHREADS, SM_TOTAL + 256>>>(p, tm_x, tm_g, tm_d);
}
```

```cpp
#include <cuda_runtime.h>
#include <cuda.h>
#include <cuda_bf16.h>
#include <cuda_fp16.h>
#include <stdint.h>

#define TG(i)
#define TS(i)
#define TSL(i)

#define TSW 0
#define SDELAY 1500
#define EDELAY 800
#define FILL 0x52110
#define STSLEEP 100
#define NPF 3
#define REFILL 0x55421
#define NREP 4
#define GPROMO 0
#define DPROMO 0
#define WPOL "evict_first"
#define PDELAY 600
#define IDEPTH 2

namespace {

constexpr int NTHREADS = 512;
constexpr int SPIN_LIMIT = 1 << 16;

constexpr int SM_SLAB = 0;
constexpr int SM_RING = 32768;
constexpr int SUB     = 1088;
constexpr int SM_K    = SM_RING + 10 * 8192;
constexpr int SM_S    = SM_K + 32 * SUB;
constexpr int SM_U    = SM_S + 32 * SUB;
constexpr int SM_F2   = SM_U + 32 * SUB;
constexpr int SM_XSEL = SM_F2 + 1536;
constexpr int SM_PAIR = SM_XSEL + 4096;
constexpr int SM_H    = SM_PAIR + 2048;
constexpr int SM_KEYS = SM_H + 1024;
constexpr int SM_TOK  = SM_KEYS + 64;
constexpr int SM_FIX  = SM_TOK + 16;
constexpr int SM_XRAW = SM_FIX + 32;
constexpr int SM_SCL  = SM_XRAW + 64;
constexpr int SM_BAR  = SM_SCL + 16;
constexpr int SM_RED  = SM_XSEL;
constexpr int SM_TAB  = SM_RING + 7 * 8192;
constexpr int B_FULL = 0, B_ROW = 24, B_STG = 32, B_SLAB = 36, B_TOK = 38, B_UFREE = 39, B_FIX = 40, B_PAIR = 41,
              B_TAB = 42, B_TFREE = 43, B_KFREE = 44, B_U = 46, B_PEER = 48, NBAR = 52;
constexpr int SM_TOTAL = SM_BAR + NBAR * 8;
static_assert(SM_TOTAL + 256 <= 232448, "smem");
__device__ __forceinline__ uint32_t chunk_off(int n) { return SM_RING + (n < 7 ? n : n - 7) * 16384; }
constexpr int KP = 272;

struct Scratch {
    uint4 stats[4][1032];
    uint32_t part[128 * 56 * 16];
    uint32_t epoch;
};
__device__ Scratch g_scratch;

struct Params {
    const __nv_bfloat16 *lar, *aim, *cr, *ci, *logdt, *dskip;
    const __nv_bfloat16 *x, *wr;
    __nv_bfloat16* out;
    Scratch* sc;
    const uint4* tab;
    int up_first;
};

__device__ __forceinline__ uint4 ldg128(const void* p) {
    uint4 v; asm volatile("ld.global.nc.v4.u32 {%0,%1,%2,%3}, [%4];" : "=r"(v.x), "=r"(v.y), "=r"(v.z), "=r"(v.w) : "l"(p)); return v;
}
__device__ __forceinline__ uint4 ld_relaxed128(const void* p) {
    uint4 v;
    asm volatile("{ .reg .b128 t; ld.relaxed.gpu.global.b128 t, [%4]; mov.b128 {%0,%1,%2,%3}, t; }"
                 : "=r"(v.x), "=r"(v.y), "=r"(v.z), "=r"(v.w) : "l"(p) : "memory");
    return v;
}
__device__ __forceinline__ void st_relaxed128(void* p, uint4 v) {
    asm volatile("{ .reg .b128 t; mov.b128 t, {%1,%2,%3,%4}; st.relaxed.gpu.global.b128 [%0], t; }"
                 :: "l"(p), "r"(v.x), "r"(v.y), "r"(v.z), "r"(v.w) : "memory");
}
__device__ __forceinline__ void st_relaxed32(void* p, uint32_t v) {
    asm volatile("st.relaxed.gpu.global.u32 [%0], %1;" :: "l"(p), "r"(v) : "memory");
}
__device__ __forceinline__ uint32_t lds32(uint32_t a) { uint32_t v; asm volatile("ld.shared.u32 %0, [%1];" : "=r"(v) : "r"(a)); return v; }
__device__ __forceinline__ uint32_t lds16(uint32_t a) { uint32_t v; asm volatile("ld.shared.u16 %0, [%1];" : "=r"(v) : "r"(a)); return v; }
__device__ __forceinline__ uint2 lds64(uint32_t a) { uint2 v; asm volatile("ld.shared.v2.u32 {%0,%1}, [%2];" : "=r"(v.x), "=r"(v.y) : "r"(a)); return v; }
__device__ __forceinline__ uint4 lds128(uint32_t a) {
    uint4 v; asm volatile("ld.shared.v4.u32 {%0,%1,%2,%3}, [%4];" : "=r"(v.x), "=r"(v.y), "=r"(v.z), "=r"(v.w) : "r"(a)); return v;
}
__device__ __forceinline__ void sts16(uint32_t a, uint32_t v) { asm volatile("st.shared.u16 [%0], %1;" :: "r"(a), "h"((uint16_t)v) : "memory"); }
__device__ __forceinline__ void sts32(uint32_t a, uint32_t v) { asm volatile("st.shared.u32 [%0], %1;" :: "r"(a), "r"(v) : "memory"); }
__device__ __forceinline__ void sts64(uint32_t a, uint32_t x, uint32_t y) { asm volatile("st.shared.v2.u32 [%0], {%1,%2};" :: "r"(a), "r"(x), "r"(y) : "memory"); }
__device__ __forceinline__ void sts128(uint32_t a, uint32_t x, uint32_t y, uint32_t z, uint32_t w) {
    asm volatile("st.shared.v4.u32 [%0], {%1,%2,%3,%4};" :: "r"(a), "r"(x), "r"(y), "r"(z), "r"(w) : "memory");
}
__device__ __forceinline__ void ldsm4(uint32_t a, uint32_t& r0, uint32_t& r1, uint32_t& r2, uint32_t& r3) {
    asm volatile("ldmatrix.sync.aligned.m8n8.x4.shared.b16 {%0,%1,%2,%3}, [%4];" : "=r"(r0), "=r"(r1), "=r"(r2), "=r"(r3) : "r"(a));
}
__device__ __forceinline__ void mma_f16(float (&d)[4], uint32_t a0, uint32_t a1, uint32_t a2, uint32_t a3, uint32_t b0, uint32_t b1) {
    asm("mma.sync.aligned.m16n8k16.row.col.f32.f16.f16.f32 {%0,%1,%2,%3}, {%4,%5,%6,%7}, {%8,%9}, {%0,%1,%2,%3};"
        : "+f"(d[0]), "+f"(d[1]), "+f"(d[2]), "+f"(d[3]) : "r"(a0), "r"(a1), "r"(a2), "r"(a3), "r"(b0), "r"(b1));
}
__device__ __forceinline__ void mma_bf16(float (&d)[4], uint32_t a0, uint32_t a1, uint32_t a2, uint32_t a3, uint32_t b0, uint32_t b1) {
    asm("mma.sync.aligned.m16n8k16.row.col.f32.bf16.bf16.f32 {%0,%1,%2,%3}, {%4,%5,%6,%7}, {%8,%9}, {%0,%1,%2,%3};"
        : "+f"(d[0]), "+f"(d[1]), "+f"(d[2]), "+f"(d[3]) : "r"(a0), "r"(a1), "r"(a2), "r"(a3), "r"(b0), "r"(b1));
}
__device__ __forceinline__ uint32_t prmt(uint32_t a, uint32_t b, uint32_t s) { uint32_t d; asm("prmt.b32 %0, %1, %2, %3;" : "=r"(d) : "r"(a), "r"(b), "r"(s)); return d; }
__device__ __forceinline__ uint32_t pack_h(float lo, float hi) { uint32_t d; asm("cvt.rn.f16x2.f32 %0, %1, %2;" : "=r"(d) : "f"(hi), "f"(lo)); return d; }
__device__ __forceinline__ uint32_t pack_b(float lo, float hi) { uint32_t d; asm("cvt.rn.bf16x2.f32 %0, %1, %2;" : "=r"(d) : "f"(hi), "f"(lo)); return d; }
__device__ __forceinline__ float blo(uint32_t v) { return __uint_as_float(v << 16); }
__device__ __forceinline__ float bhi(uint32_t v) { return __uint_as_float(v & 0xFFFF0000u); }
__device__ __forceinline__ float rb(float v) { return blo(pack_b(v, v)); }
__device__ __forceinline__ uint32_t bsub2(uint32_t a, uint32_t b) { uint32_t d; asm("sub.rn.bf16x2 %0, %1, %2;" : "=r"(d) : "r"(a), "r"(b)); return d; }
__device__ __forceinline__ uint32_t badd2(uint32_t a, uint32_t b) { uint32_t d; asm("add.rn.bf16x2 %0, %1, %2;" : "=r"(d) : "r"(a), "r"(b)); return d; }
__device__ __forceinline__ uint32_t bmul2(uint32_t a, uint32_t b) { uint32_t d; asm("mul.rn.bf16x2 %0, %1, %2;" : "=r"(d) : "r"(a), "r"(b)); return d; }
__device__ __forceinline__ uint32_t bfma2(uint32_t a, uint32_t b, uint32_t c) { uint32_t d; asm("fma.rn.bf16x2 %0, %1, %2, %3;" : "=r"(d) : "r"(a), "r"(b), "r"(c)); return d; }
__device__ __forceinline__ uint32_t dup_lo(uint32_t v) { uint32_t d; asm("{ .reg .b16 l, h; mov.b32 {l, h}, %1; mov.b32 %0, {l, l}; }" : "=r"(d) : "r"(v)); return d; }
__device__ __forceinline__ uint32_t dup_hi(uint32_t v) { uint32_t d; asm("{ .reg .b16 l, h; mov.b32 {l, h}, %1; mov.b32 %0, {h, h}; }" : "=r"(d) : "r"(v)); return d; }
__device__ __forceinline__ uint32_t norm2(uint32_t x, uint32_t m, uint32_t hi, uint32_t lo) {
    uint32_t a = bsub2(x, m);
    return bfma2(a, hi, bmul2(a, lo));
}
__device__ __forceinline__ float ex2(float v) { float d; asm("ex2.approx.ftz.f32 %0, %1;" : "=f"(d) : "f"(v)); return d; }
__device__ __forceinline__ float rcp(float v) { float d; asm("rcp.approx.ftz.f32 %0, %1;" : "=f"(d) : "f"(v)); return d; }
__device__ __forceinline__ float sigmoidf_(float v) { return rcp(1.0f + ex2(-1.4426950408889634f * v)); }
__device__ __forceinline__ float siluf_(float v) { return v * sigmoidf_(v); }

__device__ __forceinline__ void mbar_init(uint32_t a, int n) { asm volatile("mbarrier.init.shared::cta.b64 [%0], %1;" :: "r"(a), "r"(n) : "memory"); }
__device__ __forceinline__ void mbar_expect(uint32_t a, int tx) { asm volatile("mbarrier.arrive.expect_tx.shared::cta.b64 _, [%0], %1;" :: "r"(a), "r"(tx) : "memory"); }
__device__ __forceinline__ void mbar_arrive(uint32_t a) { asm volatile("mbarrier.arrive.shared::cta.b64 _, [%0];" :: "r"(a) : "memory"); }
__device__ __forceinline__ bool mbar_try(uint32_t a) {
    uint32_t d; asm volatile("{ .reg .pred p; mbarrier.try_wait.parity.shared::cta.b64 p, [%1], 0; selp.u32 %0, 1, 0, p; }" : "=r"(d) : "r"(a) : "memory"); return d;
}
__device__ __forceinline__ void mbar_wait(uint32_t a) {
    if (__builtin_expect(!mbar_try(a), 0)) {
        int n = SPIN_LIMIT;
        while (!mbar_try(a) && --n) {}
    }
}
__device__ __forceinline__ void mbar_arrive_peer(uint32_t a) { asm volatile("mbarrier.arrive.relaxed.cluster.shared::cluster.b64 _, [%0];" :: "r"(a) : "memory"); }
__device__ __forceinline__ uint32_t mapa(uint32_t a, uint32_t rank) { uint32_t d; asm("mapa.shared::cluster.u32 %0, %1, %2;" : "=r"(d) : "r"(a), "r"(rank)); return d; }
__device__ __forceinline__ void st_async2(uint32_t a, uint32_t x, uint32_t y, uint32_t bar) {
    asm volatile("st.async.weak.shared::cluster.mbarrier::complete_tx::bytes.v2.b32 [%0], {%1,%2}, [%3];" :: "r"(a), "r"(x), "r"(y), "r"(bar) : "memory");
}
__device__ __forceinline__ void st_async4(uint32_t a, uint32_t x, uint32_t y, uint32_t z, uint32_t w, uint32_t bar) {
    asm volatile("st.async.weak.shared::cluster.mbarrier::complete_tx::bytes.v4.b32 [%0], {%1,%2,%3,%4}, [%5];"
                 :: "r"(a), "r"(x), "r"(y), "r"(z), "r"(w), "r"(bar) : "memory");
}
__device__ __forceinline__ void stsm4(uint32_t a, uint32_t r0, uint32_t r1, uint32_t r2, uint32_t r3) {
    asm volatile("stmatrix.sync.aligned.m8n8.x4.shared.b16 [%0], {%1,%2,%3,%4};" :: "r"(a), "r"(r0), "r"(r1), "r"(r2), "r"(r3) : "memory");
}
__device__ __forceinline__ void proxy_fence() { asm volatile("fence.proxy.async.shared::cta;" ::: "memory"); }
__device__ __forceinline__ void bar_sync(int id, int n) { asm volatile("bar.sync %0, %1;" :: "r"(id), "r"(n) : "memory"); }
__device__ __forceinline__ void bar_arrive(int id, int n) { asm volatile("bar.arrive %0, %1;" :: "r"(id), "r"(n) : "memory"); }
__device__ __forceinline__ void cluster_arrive() { asm volatile("barrier.cluster.arrive.relaxed.aligned;" ::: "memory"); }
__device__ __forceinline__ void cluster_wait() { asm volatile("barrier.cluster.wait.aligned;" ::: "memory"); }
__device__ __forceinline__ void tma3d(uint32_t dst, const CUtensorMap* tm, int c0, int c1, int c2, uint32_t bar, uint64_t pol) {
    asm volatile("cp.async.bulk.tensor.3d.shared::cluster.global.mbarrier::complete_tx::bytes.L2::cache_hint [%0], [%1, {%3, %4, %6}], [%2], %5;"
                 :: "r"(dst), "l"(tm), "r"(bar), "r"(c0), "r"(c1), "l"(pol), "r"(c2) : "memory");
}
__device__ __forceinline__ bool elect() {
    uint32_t p; asm volatile("{ .reg .pred p; elect.sync _|p, 0xFFFFFFFF; selp.u32 %0, 1, 0, p; }" : "=r"(p)); return p;
}

struct cf { float r, i; };
__device__ __forceinline__ cf cmul(cf a, cf b) { return {a.r * b.r - a.i * b.i, a.r * b.i + a.i * b.r}; }
__device__ __forceinline__ cf csq(cf a) { return {a.r * a.r - a.i * a.i, (a.r + a.r) * a.i}; }
__device__ __forceinline__ cf cexp_(float a2, float b) { float m = ex2(a2); return {m * __cosf(b), m * __sinf(b)}; }
struct hc { uint32_t r, i; };
__device__ __forceinline__ hc pk(cf a, cf b) { return {pack_h(a.r, b.r), pack_h(a.i, b.i)}; }
__device__ __forceinline__ hc hmulc(hc a, hc b) {
    const __half2 ar = *reinterpret_cast<__half2*>(&a.r), ai = *reinterpret_cast<__half2*>(&a.i);
    const __half2 br = *reinterpret_cast<__half2*>(&b.r), bi = *reinterpret_cast<__half2*>(&b.i);
    const __half2 r = __hfma2(ar, br, __hneg2(__hmul2_rn(ai, bi))), i = __hfma2(ar, bi, __hmul2_rn(ai, br));
    return {*reinterpret_cast<const uint32_t*>(&r), *reinterpret_cast<const uint32_t*>(&i)};
}
__device__ __forceinline__ void sth(uint32_t a, hc v) { sts32(a, v.r); sts32(a + 128, v.i); }
__device__ __forceinline__ uint32_t cpy(uint32_t v, uint32_t z) { uint32_t d; asm("xor.b32 %0, %1, %2;" : "=r"(d) : "r"(v), "r"(z)); return d; }
__device__ __forceinline__ uint32_t pin(uint32_t v) { return __shfl_sync(0xFFFFFFFFu, v, threadIdx.x & 31); }
__device__ __forceinline__ void sched_fence() { asm volatile("pmevent 0;" ::: "memory"); }
__device__ __forceinline__ float tanh_(float v) { float d; asm("tanh.approx.f32 %0, %1;" : "=f"(d) : "f"(v)); return d; }
__device__ __forceinline__ float silu2(float h) {
    return fmaf(h, tanh_(h), h);
}
__device__ __forceinline__ uint32_t hfma2_(uint32_t a, uint32_t b, uint32_t c) { uint32_t d; asm("fma.rn.f16x2 %0, %1, %2, %3;" : "=r"(d) : "r"(a), "r"(b), "r"(c)); return d; }
__device__ __forceinline__ uint32_t hfms2_(uint32_t a, uint32_t b, uint32_t c) {
    uint32_t d; asm("{ .reg .b32 t; neg.f16x2 t, %1; fma.rn.f16x2 %0, t, %2, %3; }" : "=r"(d) : "r"(a), "r"(b), "r"(c)); return d;
}

__device__ __forceinline__ uint64_t bdesc(uint32_t addr, uint32_t sbo) {
    return (uint64_t)((addr & 0x3FFFFu) >> 4) | ((uint64_t)(128 >> 4) << 16) | ((uint64_t)(sbo >> 4) << 32);
}
__device__ __forceinline__ void wg_h(uint32_t (&d)[16], const uint32_t* a, const uint32_t* b, uint64_t d0, uint64_t d1, uint64_t d2, uint64_t d3) {
    asm volatile(
        "wgmma.mma_async.sync.aligned.m64n64k16.f16.f16.f16 {%0,%1,%2,%3,%4,%5,%6,%7,%8,%9,%10,%11,%12,%13,%14,%15}, {%16,%17,%18,%19}, %32, 0, 1, 1, 1;\n"
        "wgmma.mma_async.sync.aligned.m64n64k16.f16.f16.f16 {%0,%1,%2,%3,%4,%5,%6,%7,%8,%9,%10,%11,%12,%13,%14,%15}, {%20,%21,%22,%23}, %33, 1, 1, 1, 1;\n"
        "wgmma.mma_async.sync.aligned.m64n64k16.f16.f16.f16 {%0,%1,%2,%3,%4,%5,%6,%7,%8,%9,%10,%11,%12,%13,%14,%15}, {%24,%25,%26,%27}, %34, 1, 1, 1, 1;\n"
        "wgmma.mma_async.sync.aligned.m64n64k16.f16.f16.f16 {%0,%1,%2,%3,%4,%5,%6,%7,%8,%9,%10,%11,%12,%13,%14,%15}, {%28,%29,%30,%31}, %35, 1, 1, 1, 1;\n"
        : "=r"(d[0]), "=r"(d[1]), "=r"(d[2]), "=r"(d[3]), "=r"(d[4]), "=r"(d[5]), "=r"(d[6]), "=r"(d[7]), "=r"(d[8]), "=r"(d[9]), "=r"(d[10]), "=r"(d[11]), "=r"(d[12]), "=r"(d[13]), "=r"(d[14]), "=r"(d[15])
        : "r"(a[0]), "r"(a[1]), "r"(a[2]), "r"(a[3]), "r"(a[4]), "r"(a[5]), "r"(a[6]), "r"(a[7]), "r"(b[0]), "r"(b[1]), "r"(b[2]), "r"(b[3]), "r"(b[4]), "r"(b[5]), "r"(b[6]), "r"(b[7]), "l"(d0), "l"(d1), "l"(d2), "l"(d3));
}
__device__ __forceinline__ void wg_f0(float (&d)[32], const uint32_t* a, const uint32_t* b, uint64_t d0, uint64_t d1, uint64_t d2, uint64_t d3) {
    asm volatile(
        "wgmma.mma_async.sync.aligned.m64n64k16.f32.f16.f16 {%0,%1,%2,%3,%4,%5,%6,%7,%8,%9,%10,%11,%12,%13,%14,%15,%16,%17,%18,%19,%20,%21,%22,%23,%24,%25,%26,%27,%28,%29,%30,%31}, {%32,%33,%34,%35}, %48, 0, 1, 1, 1;\n"
        "wgmma.mma_async.sync.aligned.m64n64k16.f32.f16.f16 {%0,%1,%2,%3,%4,%5,%6,%7,%8,%9,%10,%11,%12,%13,%14,%15,%16,%17,%18,%19,%20,%21,%22,%23,%24,%25,%26,%27,%28,%29,%30,%31}, {%36,%37,%38,%39}, %49, 1, 1, 1, 1;\n"
        "wgmma.mma_async.sync.aligned.m64n64k16.f32.f16.f16 {%0,%1,%2,%3,%4,%5,%6,%7,%8,%9,%10,%11,%12,%13,%14,%15,%16,%17,%18,%19,%20,%21,%22,%23,%24,%25,%26,%27,%28,%29,%30,%31}, {%40,%41,%42,%43}, %50, 1, 1, 1, 1;\n"
        "wgmma.mma_async.sync.aligned.m64n64k16.f32.f16.f16 {%0,%1,%2,%3,%4,%5,%6,%7,%8,%9,%10,%11,%12,%13,%14,%15,%16,%17,%18,%19,%20,%21,%22,%23,%24,%25,%26,%27,%28,%29,%30,%31}, {%44,%45,%46,%47}, %51, 1, 1, 1, 1;\n"
        : "=f"(d[0]), "=f"(d[1]), "=f"(d[2]), "=f"(d[3]), "=f"(d[4]), "=f"(d[5]), "=f"(d[6]), "=f"(d[7]), "=f"(d[8]), "=f"(d[9]), "=f"(d[10]), "=f"(d[11]), "=f"(d[12]), "=f"(d[13]), "=f"(d[14]), "=f"(d[15]), "=f"(d[16]), "=f"(d[17]), "=f"(d[18]), "=f"(d[19]), "=f"(d[20]), "=f"(d[21]), "=f"(d[22]), "=f"(d[23]), "=f"(d[24]), "=f"(d[25]), "=f"(d[26]), "=f"(d[27]), "=f"(d[28]), "=f"(d[29]), "=f"(d[30]), "=f"(d[31])
        : "r"(a[0]), "r"(a[1]), "r"(a[2]), "r"(a[3]), "r"(a[4]), "r"(a[5]), "r"(a[6]), "r"(a[7]), "r"(b[0]), "r"(b[1]), "r"(b[2]), "r"(b[3]), "r"(b[4]), "r"(b[5]), "r"(b[6]), "r"(b[7]), "l"(d0), "l"(d1), "l"(d2), "l"(d3));
}
__device__ __forceinline__ void wg_f1(float (&d)[32], const uint32_t* a, const uint32_t* b, uint64_t d0, uint64_t d1, uint64_t d2, uint64_t d3) {
    asm volatile(
        "wgmma.mma_async.sync.aligned.m64n64k16.f32.f16.f16 {%0,%1,%2,%3,%4,%5,%6,%7,%8,%9,%10,%11,%12,%13,%14,%15,%16,%17,%18,%19,%20,%21,%22,%23,%24,%25,%26,%27,%28,%29,%30,%31}, {%32,%33,%34,%35}, %48, 1, 1, 1, 1;\n"
        "wgmma.mma_async.sync.aligned.m64n64k16.f32.f16.f16 {%0,%1,%2,%3,%4,%5,%6,%7,%8,%9,%10,%11,%12,%13,%14,%15,%16,%17,%18,%19,%20,%21,%22,%23,%24,%25,%26,%27,%28,%29,%30,%31}, {%36,%37,%38,%39}, %49, 1, 1, 1, 1;\n"
        "wgmma.mma_async.sync.aligned.m64n64k16.f32.f16.f16 {%0,%1,%2,%3,%4,%5,%6,%7,%8,%9,%10,%11,%12,%13,%14,%15,%16,%17,%18,%19,%20,%21,%22,%23,%24,%25,%26,%27,%28,%29,%30,%31}, {%40,%41,%42,%43}, %50, 1, 1, 1, 1;\n"
        "wgmma.mma_async.sync.aligned.m64n64k16.f32.f16.f16 {%0,%1,%2,%3,%4,%5,%6,%7,%8,%9,%10,%11,%12,%13,%14,%15,%16,%17,%18,%19,%20,%21,%22,%23,%24,%25,%26,%27,%28,%29,%30,%31}, {%44,%45,%46,%47}, %51, 1, 1, 1, 1;\n"
        : "+f"(d[0]), "+f"(d[1]), "+f"(d[2]), "+f"(d[3]), "+f"(d[4]), "+f"(d[5]), "+f"(d[6]), "+f"(d[7]), "+f"(d[8]), "+f"(d[9]), "+f"(d[10]), "+f"(d[11]), "+f"(d[12]), "+f"(d[13]), "+f"(d[14]), "+f"(d[15]), "+f"(d[16]), "+f"(d[17]), "+f"(d[18]), "+f"(d[19]), "+f"(d[20]), "+f"(d[21]), "+f"(d[22]), "+f"(d[23]), "+f"(d[24]), "+f"(d[25]), "+f"(d[26]), "+f"(d[27]), "+f"(d[28]), "+f"(d[29]), "+f"(d[30]), "+f"(d[31])
        : "r"(a[0]), "r"(a[1]), "r"(a[2]), "r"(a[3]), "r"(a[4]), "r"(a[5]), "r"(a[6]), "r"(a[7]), "r"(b[0]), "r"(b[1]), "r"(b[2]), "r"(b[3]), "r"(b[4]), "r"(b[5]), "r"(b[6]), "r"(b[7]), "l"(d0), "l"(d1), "l"(d2), "l"(d3));
}
__device__ __forceinline__ void wg_s(uint32_t* d, const uint32_t* a, const uint32_t* b, uint64_t d0, uint64_t d1) {
    asm volatile(
        "wgmma.mma_async.sync.aligned.m64n32k16.f16.f16.f16 {%0,%1,%2,%3,%4,%5,%6,%7}, {%8,%9,%10,%11}, %16, 0, 1, 1, 1;\n"
        "wgmma.mma_async.sync.aligned.m64n32k16.f16.f16.f16 {%0,%1,%2,%3,%4,%5,%6,%7}, {%12,%13,%14,%15}, %17, 1, 1, 1, 1;\n"
        : "=r"(d[0]), "=r"(d[1]), "=r"(d[2]), "=r"(d[3]), "=r"(d[4]), "=r"(d[5]), "=r"(d[6]), "=r"(d[7])
        : "r"(a[0]), "r"(a[1]), "r"(a[2]), "r"(a[3]), "r"(b[0]), "r"(b[1]), "r"(b[2]), "r"(b[3]), "l"(d0), "l"(d1));
}
template <int ACC> __device__ __forceinline__ void wg_w(float (&d)[4], uint64_t da, uint64_t db) {
    asm volatile("wgmma.mma_async.sync.aligned.m64n8k16.f32.bf16.bf16 {%0,%1,%2,%3}, %4, %5, %6, 1, 1, 1, 0;"
                 : "+f"(d[0]), "+f"(d[1]), "+f"(d[2]), "+f"(d[3]) : "l"(da), "l"(db), "n"(ACC));
}
__device__ __forceinline__ void wg_w0(float (&d)[4], uint64_t da, uint64_t db) {
    asm volatile("wgmma.mma_async.sync.aligned.m64n8k16.f32.bf16.bf16 {%0,%1,%2,%3}, %4, %5, 0, 1, 1, 1, 0;"
                 : "=f"(d[0]), "=f"(d[1]), "=f"(d[2]), "=f"(d[3]) : "l"(da), "l"(db));
}
__device__ __forceinline__ void wg_fence() { asm volatile("wgmma.fence.sync.aligned;" ::: "memory"); }
__device__ __forceinline__ void wg_commit() { asm volatile("wgmma.commit_group.sync.aligned;" ::: "memory"); }
template <int N> __device__ __forceinline__ void wg_wait() { asm volatile("wgmma.wait_group.sync.aligned %0;" :: "n"(N) : "memory"); }
__device__ __forceinline__ void touch(uint32_t& r) { asm volatile("" : "+r"(r) :: "memory"); }
__device__ __forceinline__ void touch(float& r) { asm volatile("" : "+f"(r) :: "memory"); }
template <class T, int N> __device__ __forceinline__ void touch(T (&r)[N]) {
#pragma unroll
    for (int i = 0; i < N; i++) touch(r[i]);
}

__global__ void __cluster_dims__(2, 1, 1) __launch_bounds__(NTHREADS, 1)
fused_kernel(const Params p, const __grid_constant__ CUtensorMap tm_x, const __grid_constant__ CUtensorMap tm_g,
             const __grid_constant__ CUtensorMap tm_d)
{
    extern __shared__ __align__(1024) uint8_t smem_raw[];
    const uint32_t sm = (uint32_t)__cvta_generic_to_shared(smem_raw);
    const uint32_t bars = sm + SM_BAR;
    const int tid = threadIdx.x, lane = tid & 31;
    const int g = lane >> 2, q = lane & 3;
    const int c = blockIdx.x, rank = c & 1, G = c >> 1;

    if (tid < 256) {
        uint2 lar4, aim4, cr4, ci4;
        uint32_t ldt_raw, dsk_raw;
        {
            const uint32_t i = c * 256 + tid;
            asm volatile("ld.global.nc.v2.u32 {%0,%1}, [%10]; ld.global.nc.v2.u32 {%2,%3}, [%11]; ld.global.nc.u16 %8, [%14];\n"
                         "ld.global.nc.v2.u32 {%4,%5}, [%12]; ld.global.nc.v2.u32 {%6,%7}, [%13]; ld.global.nc.u16 %9, [%15];"
                         : "=r"(lar4.x), "=r"(lar4.y), "=r"(aim4.x), "=r"(aim4.y), "=r"(cr4.x), "=r"(cr4.y), "=r"(ci4.x), "=r"(ci4.y), "=r"(ldt_raw), "=r"(dsk_raw)
                         : "l"(p.lar + i * 4), "l"(p.aim + i * 4), "l"(p.cr + i * 4), "l"(p.ci + i * 4), "l"(p.logdt + (i >> 5)), "l"(p.dskip + (i >> 5)));
        }
        cluster_arrive();
        sched_fence();
        const int warp = __shfl_sync(0xFFFFFFFFu, tid >> 5, 0);
        const float logdt = blo(ldt_raw), dsk = blo(dsk_raw);
        asm volatile("setmaxnreg.inc.sync.aligned.u32 168;");
        const int wgi = warp >> 2, w = warp & 3;
        const uint32_t wb = sm + SM_K + (w < 2 ? 16 * w + 8 * wgi : 16 + 16 * wgi + 8 * w) * SUB;
        sth(wb + lane * 4, hc{0x3C003C00u, 0u});
        const uint32_t tb0 = pin(sm + SM_S + (16 * wgi + w) * SUB + lane * 16), tb1 = pin(sm + SM_S + (16 * wgi + w) * SUB + ((lane + 1) & 31) * 16);
        const uint32_t seg = pin(sm + SM_K + (2 * warp + (lane & 1)) * SUB + (lane >> 1) * 16);
        const uint32_t zst = pin(sm + SM_S + (16 * wgi + (lane >> 4)) * SUB + (16 * w + (lane & 15)) * 16);
        sched_fence();

        {
            const uint32_t z = (uint32_t)(uintptr_t)p.lar & 1;
            lar4.x = cpy(lar4.x, z); lar4.y = cpy(lar4.y, z); aim4.x = cpy(aim4.x, z); aim4.y = cpy(aim4.y, z);
            cr4.x = cpy(cr4.x, z); cr4.y = cpy(cr4.y, z); ci4.x = cpy(ci4.x, z); ci4.y = cpy(ci4.y, z);
        }
        const float dt = rb(expf(logdt));
        float outscale, cs, dn;
        {
            uint32_t m0 = __vmaxu2(__vmaxu2(cr4.x & 0x7FFF7FFFu, cr4.y & 0x7FFF7FFFu), __vmaxu2(ci4.x & 0x7FFF7FFFu, ci4.y & 0x7FFF7FFFu));
            uint32_t m1 = max(m0 & 0xFFFFu, m0 >> 16);
            float cmax = blo(__reduce_max_sync(0xFFFFFFFFu, m1));
            const float sc = fminf(fmaxf(fmaxf(2.0f * dt * cmax, fabsf(dsk) * (1.0f / 1024.0f)), 1e-30f), 1e30f);
            outscale = __uint_as_float(__float_as_uint(sc) & 0x7F800000u);
            const float inv = __uint_as_float(0x7F000000u - __float_as_uint(outscale));
            cs = 2.0f * dt * inv * (1.0f / 512.0f);
            dn = dsk * inv * (1.0f / 512.0f);
            if (lane == 0) sts16(sm + SM_SCL + warp * 2, __float_as_uint(32768.0f * outscale) >> 16);
        }
        if (warp == TSW) TSL(39);
        uint32_t fc[16], fs[16], ta[4], tb[4];
        float kacc[2][3][4];
#pragma unroll
        for (int i = 0; i < 2; i++)
#pragma unroll
            for (int j = 0; j < 3; j++) kacc[i][j][0] = kacc[i][j][1] = kacc[i][j][2] = kacc[i][j][3] = 0.f;
        if (lane == 0) kacc[0][0][0] = dn;
        {
            const uint32_t st = wb + lane * 4;
            const uint32_t zk = lds32(wb + 128);
            const uint32_t la = wb + ((lane & 8) ? 29 : (lane & 7)) * KP + (lane >> 4) * 128;
            const uint32_t lo = wb + ((lane >> 3) & 1) * 128 + (lane >> 4) * 16;
            const uint32_t lb = lo + (8 + (lane & 7)) * KP, lb2 = lo + (24 + min(lane & 7, 4)) * KP, lm = lo + 30 * KP;
#pragma unroll 1
            for (int s = 0; s < 2; s++) {
                const uint32_t wl = s ? lar4.y : lar4.x, wa = s ? aim4.y : aim4.x, wr_ = s ? cr4.y : cr4.x, wi = s ? ci4.y : ci4.x;
                const uint32_t ea = pack_b(ex2(blo(wl) * 1.4426950408889634f), ex2(bhi(wl) * 1.4426950408889634f));
                const float a2[2] = {-(blo(ea) * dt) * 1.4426950408889634f, -(bhi(ea) * dt) * 1.4426950408889634f};
                const float b[2] = {blo(wa) * dt, bhi(wa) * dt};
                {
                    cf z8[2], z16[2], z32[2], z64[2], z128[2];
#pragma unroll
                    for (int e = 0; e < 2; e++) {
                        z8[e] = cexp_(a2[e] * 8.f, b[e] * 8.f);
                        z16[e] = csq(z8[e]); z32[e] = csq(z16[e]); z64[e] = csq(z32[e]); z128[e] = csq(z64[e]);
                    }
                    const hc r1 = pk(z8[0], z8[1]), r2 = pk(z16[0], z16[1]), r3 = hmulc(r1, r2), r4 = pk(z32[0], z32[1]);
                    sth(st + 1 * KP, r1); sth(st + 2 * KP, r2); sth(st + 3 * KP, r3); sth(st + 4 * KP, r4);
                    sth(st + 5 * KP, hmulc(r1, r4)); sth(st + 6 * KP, hmulc(r2, r4)); sth(st + 7 * KP, hmulc(r3, r4));
                    sth(st + 29 * KP, pk(z64[0], z64[1])); sth(st + 30 * KP, pk(z128[0], z128[1]));
                }
                {
                    cf C[2], z2[2], z4[2], v2[2], v4[2], c1[2], d1[2];
#pragma unroll
                    for (int e = 0; e < 2; e++) {
                        C[e] = {(e ? bhi(wr_) : blo(wr_)) * cs, (e ? bhi(wi) : blo(wi)) * -cs};
                        const cf z = cexp_(a2[e], -b[e]);
                        const cf v = cexp_(a2[e] * 256.f, b[e] * -256.f);
                        z2[e] = csq(z); z4[e] = csq(z2[e]); v2[e] = csq(v); v4[e] = csq(v2[e]);
                        c1[e] = cmul(C[e], z); d1[e] = cmul(C[e], v);
                    }
                    const hc l0 = pk(C[0], C[1]), l1 = pk(c1[0], c1[1]), e1 = pk(d1[0], d1[1]);
                    const hc h = pk(z2[0], z2[1]), f = pk(z4[0], z4[1]), w = pk(v2[0], v2[1]), y = pk(v4[0], v4[1]);
                    const hc l2 = hmulc(l0, h), l3 = hmulc(l1, h), e2 = hmulc(l0, w), e3 = hmulc(e1, w), e4 = hmulc(l0, y), g2 = hmulc(e1, h);
                    sth(st + 8 * KP, l0); sth(st + 9 * KP, l1); sth(st + 10 * KP, l2); sth(st + 11 * KP, l3);
                    sth(st + 12 * KP, hmulc(l0, f)); sth(st + 13 * KP, hmulc(l1, f)); sth(st + 14 * KP, hmulc(l2, f)); sth(st + 15 * KP, hmulc(l3, f));
                    sth(st + 16 * KP, e1);
                    sth(st + 17 * KP, g2);
                    sth(st + 18 * KP, hmulc(e1, f));
                    sth(st + 19 * KP, hmulc(g2, f));
                    sth(st + 20 * KP, e2);
                    sth(st + 21 * KP, hmulc(e2, f));
                    sth(st + 22 * KP, e3);
                    sth(st + 23 * KP, hmulc(e3, f));
                    sth(st + 24 * KP, e4);
                    sth(st + 25 * KP, hmulc(e1, y));
                    sth(st + 26 * KP, hmulc(e2, y));
                    sth(st + 27 * KP, hmulc(e3, y));
                    sth(st + 28 * KP, hmulc(e4, y));
                }
                __syncwarp();
                if (warp == TSW && s == 0) TSL(27);
                if (s == 1 && lane == 0) mbar_arrive(bars + B_TFREE * 8 + (tb[3] & zk));
#pragma unroll
                for (int kp = 0; kp < 4; kp++) {
                    uint32_t bb[3][4], m2[4];
                    ldsm4(lm + kp * 32, m2[0], m2[1], m2[2], m2[3]);
                    ldsm4(lb + kp * 32, bb[0][0], bb[0][1], bb[0][2], bb[0][3]);
                    ldsm4(lb + 8 * KP + kp * 32, bb[1][0], bb[1][1], bb[1][2], bb[1][3]);
                    ldsm4(lb2 + kp * 32, bb[2][0], bb[2][1], bb[2][2], bb[2][3]);
#pragma unroll
                    for (int k2 = 0; k2 < 2; k2++) {
                        hc v0, m1;
                        ldsm4(la + kp * 32 + k2 * 16, v0.r, m1.r, v0.i, m1.i);
                        const hc mm = {m2[2 * k2], m2[2 * k2 + 1]};
                        const hc v1 = hmulc(v0, m1), v2 = hmulc(v0, mm), v3 = hmulc(v1, mm);
                        v0.r = cpy(v0.r, zk); v0.i = cpy(v0.i, zk);
#pragma unroll
                        for (int nt = 0; nt < 3; nt++) {
                            mma_f16(kacc[0][nt], v0.r, v1.r, v0.i, v1.i, bb[nt][2 * k2], bb[nt][2 * k2 + 1]);
                            mma_f16(kacc[1][nt], v2.r, v3.r, v2.i, v3.i, bb[nt][2 * k2], bb[nt][2 * k2 + 1]);
                        }
                    }
                }
                __syncwarp();
                if (warp == TSW) TSL(s ? 40 : 33);
                if (s == 0) {
                    cluster_wait();
                    mbar_wait(bars + B_TAB * 8);
#pragma unroll
                    for (int i = 0; i < 10; i++) {
                        const uint4 u = lds128(sm + SM_TAB + i * 2048 + (tid & 127) * 16);
                        uint32_t* t = i < 4 ? fc + 4 * i : i < 8 ? fs + 4 * (i - 4) : i == 8 ? ta : tb;
                        t[0] = u.x; t[1] = u.y; t[2] = u.z; t[3] = u.w;
                    }
                }
            }
        }
        TSL(1);
        bar_sync(10 + wgi, 128);
        {
            uint32_t v[3][4];
#pragma unroll
            for (int i = 0; i < 12; i++) v[i >> 2][i & 3] = pack_h(kacc[(i >> 1) & 1][i >> 2][2 * (i & 1)], kacc[(i >> 1) & 1][i >> 2][2 * (i & 1) + 1]);
            stsm4(tb0, v[1][0], v[1][1], v[1][2], v[1][3]);
            stsm4(tb0 + 512, v[2][0], v[2][1], v[2][2], v[2][3]);
            stsm4(seg, v[0][0], v[0][1], v[0][2], v[0][3]);
            __syncwarp();
            const uint4 a = lds128(tb0), na = lds128(tb1), nb = lds128(tb1 + 512);
            const uint2 b = lds64(tb0 + 512);
            const bool last = lane == 31;
            const uint32_t n1 = last ? na.z : na.x, n2 = last ? na.w : na.z, n3 = last ? nb.x : na.w;
            const uint32_t sn = last ? 0x5432 : 0x3210, n4 = prmt(nb.x, nb.y, sn), n5 = prmt(nb.y, nb.z, sn);
            sts128(seg + 256, prmt(a.x, 0, 0x1010), prmt(a.x, a.y, 0x5432), prmt(a.y, 0, 0x1010), prmt(a.y, n1, 0x5432));
            sts128(seg + 512, prmt(a.z, 0, 0x1010), a.z, prmt(a.z, 0, 0x3232), prmt(n2, 0, 0x1010));
            sts128(seg + 768, prmt(a.w, 0, 0x1010), a.w, prmt(a.w, 0, 0x3232), prmt(n3, 0, 0x1010));
            const uint32_t s3 = (lane & 1) ? 0x5454 : 0x5410;
#pragma unroll
            for (int i = 0; i < 4; i++) {
                const uint32_t cur = (i & 2) ? b.y : b.x, nx = (i & 2) ? n5 : n4, h = (i & 1) * 0x2222;
                const uint32_t vv = prmt(cur, 0, 0x1010 + h);
                sts128(seg + 16 * SUB + i * 256, vv, vv, prmt(cur, nx, s3 + h), prmt(nx, 0, 0x1010 + h));
            }
        }
        proxy_fence();
        TSL(2);
        bar_sync(10 + wgi, 128);
        const uint64_t dre = bdesc(sm + SM_F2 + 512, 256), dim = bdesc(sm + SM_F2, 256);
        uint32_t k0[32], k1[32];
#pragma unroll
        for (int b = 0; b < 2; b++) {
            const uint64_t d1 = bdesc(sm + SM_K + (16 * b + 8 * wgi) * SUB, SUB);
            uint32_t re[16], im[16];
            if (b == 0 && wgi == 1) bar_sync(5, 256);
            wg_fence();
            wg_h(re, fc, fc + 8, d1, d1 + 16, d1 + 32, d1 + 48);
            wg_h(im, fs, fs + 8, d1, d1 + 16, d1 + 32, d1 + 48);
            wg_commit();
            if (b == 0 && wgi == 0) bar_arrive(5, 256);
            wg_wait<0>();
            touch(re); touch(im);
            if (lane == 0) mbar_arrive(bars + (B_KFREE + b) * 8);
            uint32_t (&kk)[32] = b ? k1 : k0;
#pragma unroll
            for (int hh = 0; hh < 2; hh++) {
#pragma unroll
                for (int i = 8 * hh; i < 8 * hh + 8; i++) {
                    re[i] = hfma2_(ta[i & 3], im[i], re[i]); im[i] = hfms2_(tb[i & 3], re[i], im[i]); re[i] = hfma2_(ta[i & 3], im[i], re[i]);
                }
                wg_fence();
                wg_s(kk + 16 * hh, re + 8 * hh, im + 8 * hh, dre, dim);
                wg_s(kk + 16 * hh + 8, re + 8 * hh + 4, im + 8 * hh + 4, dre, dim);
                wg_commit();
            }
            wg_wait<0>();
            touch(kk);
        }
        if (warp == TSW) TSL(35);
        asm volatile("setmaxnreg.inc.sync.aligned.u32 184;");
        touch(k1);
        {
            const uint32_t sg = (g & 1) ? 0xBC00BC00u : 0x3C003C00u;
#pragma unroll
            for (int i = 0; i < 16; i++) {
                const int r = 8 * (i >> 2) + (i & 3);
                k1[r] = hfms2_(sg, k0[r + 4], k1[r]); k1[r + 4] = hfma2_(sg, k0[r], k1[r + 4]);
            }
            touch(k1);
        }
        const uint32_t peer = mapa(sm, rank ^ 1), so = SM_U + 8 * wgi * SUB + w * 1024 + (8 * q + (g ^ (2 * q))) * 16;
        const uint2 sc = lds64(sm + SM_SCL + wgi * 8);
#pragma unroll 1
        for (int b = 0; b < 2; b++) {
            const uint32_t zb = sm + SM_S + 16 * wgi * SUB;
            constexpr int zi = 8 * SUB;
            uint32_t re[16], im[16], su[2][16], z[2][16], y[2][16];
            auto twiddle = [&](int hh) {
#pragma unroll
                for (int i = 8 * hh; i < 8 * hh + 8; i++) {
                    re[i] = hfma2_(ta[i & 3], im[i], re[i]); im[i] = hfms2_(tb[i & 3], re[i], im[i]); re[i] = hfma2_(ta[i & 3], im[i], re[i]);
                    touch(re[i]); touch(im[i]);
                }
            };
            auto dft16 = [&](int hh) {
                wg_fence();
                wg_s(su[hh], re + 8 * hh, im + 8 * hh, dre, dim); wg_s(su[hh] + 8, re + 8 * hh + 4, im + 8 * hh + 4, dre, dim);
                wg_commit();
                sched_fence();
            };
            auto product = [&](int hh) {
                if (b == 0) {
#pragma unroll
                    for (int i = 0; i < 8; i++) {
                        const int r = 8 * (i >> 2) + (i & 3), kr = 16 * hh + r;
                        const hc u = {su[hh][r], su[hh][r + 4]};
                        const hc t = hmulc(u, hc{k0[kr], k0[kr + 4]}), pp = hmulc(u, hc{k1[kr], k1[kr + 4]});
                        z[hh][r] = t.r; z[hh][r + 4] = t.i; k1[kr] = pp.r; k1[kr + 4] = pp.i;
                        touch(k1[kr]); touch(k1[kr + 4]);
                    }
                } else {
#pragma unroll
                    for (int i = 0; i < 8; i++) {
                        const int r = 8 * (i >> 2) + (i & 3), kr = 16 * hh + r;
                        const hc u = {su[hh][r], su[hh][r + 4]};
                        z[hh][r] = hfms2_(u.i, k0[kr + 4], hfma2_(u.r, k0[kr], k1[kr]));
                        z[hh][r + 4] = hfma2_(u.i, k0[kr], hfma2_(u.r, k0[kr + 4], k1[kr + 4]));
                    }
                }
                touch(z[hh]);
            };
            auto idft16 = [&](int hh) {
                wg_fence();
                wg_s(y[hh], z[hh] + 4, z[hh], dre, dim); wg_s(y[hh] + 8, z[hh] + 12, z[hh] + 8, dre, dim);
                wg_commit();
                sched_fence();
            };
            auto untwiddle = [&](int hh) {
#pragma unroll
                for (int i = 0; i < 2; i++) {
                    uint32_t* const yi = y[hh] + 8 * i, * const yr = yi + 4;
#pragma unroll
                    for (int n = 0; n < 4; n++) {
                        yr[n] = hfms2_(ta[n], yi[n], yr[n]); yi[n] = hfma2_(tb[n], yr[n], yi[n]); yr[n] = hfms2_(ta[n], yi[n], yr[n]);
                    }
                    const uint32_t a = zst + (4 * hh + 2 * i) * SUB;
                    stsm4(a, yr[0], yr[1], yr[2], yr[3]);
                    stsm4(a + zi, yi[0], yi[1], yi[2], yi[3]);
                }
            };
            auto done = [&]() { sched_fence(); wg_wait<0>(); };
            {
                const uint64_t d1 = bdesc(sm + SM_U + (16 * b + 8 * wgi) * SUB, SUB);
                mbar_wait(bars + (B_U + b) * 8);
                proxy_fence();
                if (b == 0) { TSL(3); if (wgi == 1) bar_sync(9, 256); }
                wg_fence();
                wg_h(re, fc, fc + 8, d1, d1 + 16, d1 + 32, d1 + 48);
                wg_h(im, fs, fs + 8, d1, d1 + 16, d1 + 32, d1 + 48);
                wg_commit();
                if (b == 0 && wgi == 0) bar_arrive(9, 256);
                wg_wait<0>();
                touch(re); touch(im);
            }
            if (lane == 0) mbar_arrive_peer(peer + SM_BAR + (B_PEER + 2 * wgi + b) * 8);
            twiddle(0); twiddle(1); dft16(0); dft16(1);
            wg_wait<1>(); touch(su[0]);
            product(0); done(); touch(su[1]); idft16(0);
            product(1); done(); touch(y[0]); idft16(1);
            bar_sync(10 + wgi, 128);
            untwiddle(0); done(); touch(y[1]);
            untwiddle(1);
            proxy_fence();
            if (warp == TSW) TSL(36 + b);
            bar_sync(10 + wgi, 128);
            float acc[32];
            const uint64_t d4 = bdesc(zb, SUB);
            wg_fence();
            wg_f0(acc, fc, fc + 8, d4, d4 + 16, d4 + 32, d4 + 48);
            wg_f1(acc, fs, fs + 8, d4 + zi / 16, d4 + zi / 16 + 16, d4 + zi / 16 + 32, d4 + zi / 16 + 48);
            wg_commit();
            mbar_wait(bars + (B_PEER + 2 * wgi + b) * 8);
            wg_wait<0>();
            touch(acc);
            uint32_t s[2][2][4];
#pragma unroll
            for (int i = 0; i < 8; i++) {
                s[i >> 2][(i >> 1) & 1][2 * (i & 1)] = bmul2(pack_b(acc[i], acc[8 + i]), sc.x);
                s[i >> 2][(i >> 1) & 1][2 * (i & 1) + 1] = bmul2(pack_b(acc[16 + i], acc[24 + i]), sc.y);
            }
            const uint32_t sb = SM_BAR + (B_STG + b) * 8;
#pragma unroll
            for (int j = 0; j < 2; j++)
                if (j == rank) {
#pragma unroll
                    for (int hi = 0; hi < 2; hi++) {
                        const uint32_t (&r)[4] = s[1 - j][hi], (&l)[4] = s[j][hi];
                        st_async4(peer + so + 16 * b * SUB + hi * 512, r[0], r[1], r[2], r[3], peer + sb);
                        sts128(sm + (so ^ 64) + (16 * b + 4) * SUB + hi * 512, l[0], l[1], l[2], l[3]);
                    }
                }
            __syncwarp();
            if (lane == 0) mbar_arrive(sm + sb);
            if (warp == TSW) TSL(5 + b);
        }
        TSL(7);
    } else {
    const int warp = __shfl_sync(0xFFFFFFFFu, tid >> 5, 0);
    if (warp < 12) {
        const int v = warp - 8;
        cluster_arrive();
        const uint32_t xs = sm + SM_U + v * 8192;
        if (elect()) {
#pragma unroll
            for (int r = 0; r < 2; r++) mbar_init(bars + (B_ROW + 2 * v + r) * 8, 1);
            asm volatile("fence.mbarrier_init.release.cluster;" ::: "memory");
#pragma unroll
            for (int e = 0; e < 2; e++) {
                if (e) { const int t0_ = clock(); while ((int)clock() - t0_ < EDELAY) __nanosleep(40); }
                mbar_expect(bars + (B_ROW + 2 * v + e) * 8, 4096);
#pragma unroll
                for (int r = 0; r < 2; r++)
                    asm volatile("cp.async.bulk.shared::cluster.global.mbarrier::complete_tx::bytes [%0], [%1], 2048, [%2];"
                                 :: "r"(xs + e * 4096 + r * 2048), "l"(p.x + (size_t)(128 * (c & 15) + 32 * v + 16 * r + 2 * (c >> 4) + e) * 1024),
                                    "r"(bars + (B_ROW + 2 * v + e) * 8) : "memory");
            }
        }
        __syncwarp();
        uint4 w4[4];
#pragma unroll
        for (int k = 0; k < 4; k++) w4[k] = ldg128(reinterpret_cast<const uint4*>(p.wr) + 32 * k + lane);
        {
            constexpr uint32_t ONE = 0x3F803F80u;
            const uint32_t zr = p.up_first >> 1;
            uint4 w5[4];
#pragma unroll
            for (int k = 0; k < 4; k++) {
                w5[k].x = w4[k].x + zr; w5[k].y = w4[k].y + zr; w5[k].z = w4[k].z + zr; w5[k].w = w4[k].w + zr;
                w4[k].x = cpy(w4[k].x, zr); w4[k].y = cpy(w4[k].y, zr); w4[k].z = cpy(w4[k].z, zr); w4[k].w = cpy(w4[k].w, zr);
            }
            const bool od = g & 1;
#pragma unroll 1
            for (int r2 = 0; r2 < 2; r2++) {
                mbar_wait(bars + (B_ROW + 2 * v + r2) * 8);
                TSL(43);
                float s1[2][4] = {}, q0[2][4] = {};
#pragma unroll
                for (int k = 0; k < 4; k++)
#pragma unroll
                    for (int r = 0; r < 2; r++) {
                        const uint4 x = lds128(xs + r2 * 4096 + r * 2048 + k * 512 + lane * 16);
                        const uint4& ww = r ? w5[k] : w4[k];
                        mma_bf16(q0[r], cpy(x.x, zr), ww.x, cpy(x.y, zr), ww.y, x.x, x.y);
                        mma_bf16(s1[r], x.x, x.y, x.z, x.w, ONE, ONE);
                        mma_bf16(q0[r], cpy(x.z, zr), ww.z, cpy(x.w, zr), ww.w, x.z, x.w);
                    }
#pragma unroll
                for (int r = 0; r < 2; r++)
                    if (q == (g >> 1))
                        sts128(sm + SM_RED + (4 * v + r2 + 2 * r) * 144 + g * 16, __float_as_uint(od ? q0[r][1] : q0[r][0]),
                               __float_as_uint(od ? q0[r][3] : q0[r][2]), __float_as_uint(s1[r][0]), __float_as_uint(s1[r][2]));
            }
            bar_arrive(7, 160);
        }
        TSL(8);
        bar_sync(6, 160);
        const uint32_t tag = lds32(sm + SM_TOK + 8);
        cluster_wait();
        asm volatile("setmaxnreg.dec.sync.aligned.u32 104;");
        const uint32_t peer = mapa(sm, rank ^ 1);
        if (v == 0 && lane == 0) mbar_arrive_peer(peer + SM_BAR + B_UFREE * 8);
        {
            uint4 st[8];
            const uint4* src = p.sc->stats[G & (NREP - 1)] + rank * 512 + 16 * v + (lane >> 1);
            const uint32_t tb = ((tag & 1) << 15) | ((tag >> 1) << 31);
            const uint32_t xo = pin(sm + SM_SLAB + v * 512 + lane * 16);
            const uint32_t ub = pin(mapa(bars + B_U * 8, lane & 1)), ud = pin(mapa(sm + SM_U + rank * SUB + (16 * v + (lane >> 1)) * 16, lane & 1));
            bar_sync(3, 192);
            if (warp == 8) TSL(44);
#pragma unroll
            for (int i = 0; i < 8; i++) st[i] = ld_relaxed128(src + (i >> 2) * 64 + (i & 3) * 128);
            uint4 x0[8];
            mbar_wait(bars + B_UFREE * 8);
            mbar_wait(bars + B_SLAB * 8);
#pragma unroll
            for (int i = 0; i < 8; i++) x0[i] = lds128(xo + (i & 1) * 8192 + (i >> 1) * 2048);
            for (int it = 0; it < SPIN_LIMIT; it++) {
                uint32_t bad = 0;
#pragma unroll
                for (int i = 0; i < 8; i++) bad |= st[i].z ^ tb;
                if (__all_sync(0xFFFFFFFFu, (bad & 0x80008000u) == 0)) break;
#pragma unroll
                for (int i = 0; i < 8; i++)
                    if ((st[i].z ^ tb) & 0x80008000u) st[i] = ld_relaxed128(src + (i >> 2) * 64 + (i & 3) * 128);
            }
            TSL(11); TG(31);
#pragma unroll
            for (int i = 0; i < 8; i++) st[i].z &= 0x7FFF7FFFu;
            const bool own = (lane & 1) == rank;
            uint32_t n[2][8][4];
#pragma unroll
            for (int b = 0; b < 2; b++) {
                if (b) mbar_wait(bars + (B_SLAB + 1) * 8);
#pragma unroll
                for (int i = 0; i < 8; i++) {
                    const uint4 x = b ? lds128(xo + 16384 + (i & 1) * 8192 + (i >> 1) * 2048) : x0[i];
                    const uint4& t = st[4 * b + (i >> 1)];
                    const uint32_t m = (i & 1) ? dup_hi(t.x) : dup_lo(t.x), hi = (i & 1) ? dup_hi(t.z) : dup_lo(t.z), lo = (i & 1) ? dup_hi(t.y) : dup_lo(t.y);
                    uint32_t (&r)[4] = n[b][i];
                    r[0] = norm2(x.x, m, hi, lo); r[1] = norm2(x.y, m, hi, lo); r[2] = norm2(x.z, m, hi, lo); r[3] = norm2(x.w, m, hi, lo);
                    if (b && (i & 1)) sched_fence();
                }
#pragma unroll
                for (int cp = 0; cp < 4; cp++) {
                    float f[8][2];
#pragma unroll
                    for (int i = 0; i < 8; i++) { f[i][0] = blo(n[b][i][cp]); f[i][1] = bhi(n[b][i][cp]); }
#pragma unroll
                    for (int h = 0; h < 2; h++)
                        st_async4(ud + (16 * b + 4 * cp + 2 * h) * SUB, pack_h(f[0][h], f[1][h]), pack_h(f[2][h], f[3][h]),
                                  pack_h(f[4][h], f[5][h]), pack_h(f[6][h], f[7][h]), ub + b * 8);
                    if (b) {
#pragma unroll
                        for (int i = 0; i < 8; i++) { n[1][i][cp] = pack_b(silu2(f[i][0]), silu2(f[i][1])); touch(n[1][i][cp]); }
                        sched_fence();
                    }
                }
                TSL(b ? 41 : 12);
            }
            const uint32_t zr = p.up_first >> 1;
#pragma unroll
            for (int i = 0; i < 32; i++) {
                uint32_t& r = n[0][i >> 2][i & 3];
                r = pack_b(silu2(__uint_as_float(prmt(r, zr, 0x1044))), silu2(__uint_as_float(prmt(r, zr, 0x3244))));
                touch(r);
                if ((i & 7) == 7) sched_fence();
            }
            TSL(0);
            const uint32_t stg = pin(sm + SM_U + (own ? 4 * SUB : 0) + v * 1024 + (lane >> 4) * 512 + (((lane & 14) * 8) ^ (own ? 64 : 0)));
            const int tl = pin(256 * v + 16 * (lane >> 1) + 8 * rank);
            __nv_bfloat16* const op = p.out + (size_t)tl * 1024 + G * 16 + (lane & 1) * 8;
            mbar_wait(bars + B_TOK * 8);
            const uint2 tr = lds64(sm + SM_TOK);
#pragma unroll
            for (int b = 0; b < 2; b++) {
                const int d0 = tr.x - tl - 1024 * b, d1 = tr.y - tl - 1024 * b;
                uint32_t skip = ((d0 & ~7) ? 0u : 1u << d0) | ((d1 & ~7) ? 0u : 1u << d1);
                uint4 x[8];
                if (b) {
#pragma unroll
                    for (int i = 0; i < 8; i++) x[i] = lds128(xo + b * 16384 + (i & 1) * 8192 + (i >> 1) * 2048);
                }
                mbar_wait(bars + (B_STG + b) * 8);
                if (skip) {
#pragma unroll 1
                    for (int k = 0; k < 2; k++) {
                        const int d = k ? d1 : d0;
                        if (!(d & ~7)) {
                            const uint32_t a = (stg ^ ((d & 6) * 16)) + 16 * b * SUB + (d & 6) * 64 + (d & 1) * 8, dst = mapa(sm, k);
                            const uint2 s0 = lds64(a), s1 = lds64(a + 8 * SUB);
                            st_async4(dst + SM_FIX + (lane & 1) * 16, s0.x, s0.y, s1.x, s1.y, dst + SM_BAR + B_FIX * 8);
                        }
                    }
                }
                __syncwarp();
#pragma unroll
                for (int i = 0; i < 4; i++) {
                    const uint32_t a = (stg ^ (32 * i)) + 16 * b * SUB + 128 * i;
                    const uint4 r0 = lds128(a), r1 = lds128(a + 8 * SUB);
#pragma unroll
                    for (int e = 0; e < 2; e++) {
                        if (!b) x[2 * i + e] = lds128(xo + e * 8192 + i * 2048);
                        const uint4& xx = x[2 * i + e];
                        const uint32_t s0 = e ? r0.z : r0.x, s1 = e ? r0.w : r0.y, s2 = e ? r1.z : r1.x, s3 = e ? r1.w : r1.y;
                        const uint32_t (&gt)[4] = n[b][2 * i + e];
                        asm volatile("{ .reg .pred p; setp.eq.u32 p, %5, 0; @p st.global.v4.u32 [%0], {%1,%2,%3,%4}; }"
                                     :: "l"(op + (size_t)(1024 * b + 2 * i + e) * 1024), "r"(badd2(xx.x, bmul2(s0, gt[0]))), "r"(badd2(xx.y, bmul2(s1, gt[1]))),
                                        "r"(badd2(xx.z, bmul2(s2, gt[2]))), "r"(badd2(xx.w, bmul2(s3, gt[3]))), "r"(skip & (1u << (2 * i + e))) : "memory");
                    }
                    if (!b) { sched_fence(); if (i < 3) __nanosleep(STSLEEP); }
                }
                TSL(b ? 23 : 22);
            }
            TSL(17); TG(30);
        }
    } else {
        const int v = warp - 12;
        if (lane == 0) {
            if (v == 1) {
                mbar_init(bars + B_TAB * 8, 1); mbar_init(bars + B_TFREE * 8, 8); mbar_init(bars + B_KFREE * 8, 8); mbar_init(bars + (B_KFREE + 1) * 8, 8);
                mbar_expect(bars + B_TAB * 8, 20480 + 1536);
            } else if (v == 0) {
                mbar_init(bars + B_SLAB * 8, 1); mbar_init(bars + (B_SLAB + 1) * 8, 1); mbar_init(bars + B_TOK * 8, 2); mbar_init(bars + B_UFREE * 8, 1);
                mbar_expect(bars + B_SLAB * 8, 16384); mbar_expect(bars + (B_SLAB + 1) * 8, 16384);
            } else {
                mbar_init(bars + (B_STG + v - 2) * 8, 9); mbar_init(bars + (B_FIX + v - 2) * 8, 1);
                mbar_init(bars + (B_U + v - 2) * 8, 1); mbar_expect(bars + (B_U + v - 2) * 8, 16384);
                mbar_expect(bars + (B_STG + v - 2) * 8, 8192); mbar_expect(bars + (B_FIX + v - 2) * 8, v == 2 ? 32 : 2048);
            }
            mbar_init(bars + (B_PEER + v) * 8, 4);
#pragma unroll
            for (int i = 0; i < 3; i++) { mbar_init(bars + (B_FULL + 3 * v + i) * 8, 1); mbar_expect(bars + (B_FULL + 3 * v + i) * 8, 16384); }
            asm volatile("fence.mbarrier_init.release.cluster;" ::: "memory");
        }
        __syncwarp();
        cluster_arrive();
        asm volatile("setmaxnreg.dec.sync.aligned.u32 40;");
        uint64_t pol; asm volatile("createpolicy.fractional.L2::" WPOL ".b64 %0, 1.0;" : "=l"(pol));
        auto load_chunk = [&](int n) {
            if (n < 8) tma3d(sm + chunk_off(n), &tm_g, G * 64, rank * 512 + n * 64, 0, bars + (B_FULL + n) * 8, pol);
            else tma3d(sm + chunk_off(n), &tm_d, 0, G * 64, rank * 8 + (n - 8) * 2, bars + (B_FULL + n) * 8, pol);
        };
        uint32_t* const my_part = p.sc->part + ((2 * (32 * rank + v) + (q & 1)) * 56 + G) * 16 + g + 8 * (q >> 1);
        if (G < 56) {
#pragma unroll
            for (int n = 0; n < 8; n++) st_relaxed32(my_part + n * 8 * 56 * 16, 0);
        }
        cluster_wait();
        const bool lead = elect();
        uint32_t key = 0;
        if (v == 0) {
            asm volatile("prefetch.tensormap [%0];" :: "l"(&tm_x) : "memory");
            asm volatile("prefetch.tensormap [%0];" :: "l"(&tm_g) : "memory");
            { const int t0_ = clock(); while ((int)clock() - t0_ < SDELAY) __nanosleep(40); }
            if (lead) {
                int n = 0;
#pragma unroll 1
                for (int i = 0; i < 5; i++) {
                    if (G < 56) {
#pragma unroll 1
                        for (; n < ((FILL >> (4 * i)) & 15); n++) {
                            if (n >= IDEPTH) mbar_wait(bars + (B_FULL + n - IDEPTH) * 8);
                            if (n == 3) mbar_wait(bars + B_TFREE * 8);
                            load_chunk(n);
                        }
                    }
                    if (i < 4)
                        asm volatile("cp.async.bulk.tensor.4d.shared::cluster.global.mbarrier::complete_tx::bytes [%0], [%1, {%3, %4, %5, %6}], [%2];"
                                     :: "r"(sm + SM_SLAB + (i & 1) * 16384 + (i >> 1) * 8192), "l"(&tm_x), "r"(bars + (B_SLAB + (i & 1)) * 8),
                                        "r"(G * 16), "r"(64 * (i & 1)), "r"(4 * rank), "r"(i >> 1) : "memory");
                }
                TS(20);
                if (G < 56) {
#pragma unroll 1
                    for (int i = 0; i < NPF; i++) {
                        if (i < IDEPTH) mbar_wait(bars + (B_FULL + 5 + i - IDEPTH) * 8);
                        asm volatile("cp.async.bulk.prefetch.tensor.3d.L2.global [%0, {%1, %2, %3}];" :: "l"(&tm_g), "r"(G * 64), "r"(rank * 512 + (5 + i) * 64), "r"(0) : "memory");
                    }
                    mbar_wait(bars + B_KFREE * 8); load_chunk(5);
                    mbar_wait(bars + (B_KFREE + 1) * 8); load_chunk(6);
                }
                TS(21);
            }
            __syncwarp();
        } else if (v == 1) {
            if (lead) {
                asm volatile("cp.async.bulk.shared::cluster.global.mbarrier::complete_tx::bytes [%0], [%1], 20480, [%2];"
                             :: "r"(sm + SM_TAB), "l"(p.tab), "r"(bars + B_TAB * 8) : "memory");
                asm volatile("cp.async.bulk.shared::cluster.global.mbarrier::complete_tx::bytes [%0], [%1], 1536, [%2];"
                             :: "r"(sm + SM_F2), "l"(p.tab + 1280), "r"(bars + B_TAB * 8) : "memory");
                asm volatile("prefetch.tensormap [%0];" :: "l"(&tm_d) : "memory");
            }
        } else {
            const int sw = v - 2;
            if (sw == 0) {
                uint32_t tag;
                uint4* const my_stats = p.sc->stats[q] + c * 8 + g;
                asm volatile("ld.relaxed.gpu.global.u32 %0, [%1];" : "=r"(tag) : "l"(&p.sc->epoch) : "memory");
                float ws = 0.f;
#pragma unroll
                for (int k = 0; k < 4; k++) {
                    const uint4 w = ldg128(reinterpret_cast<const uint4*>(p.wr) + 32 * k + lane);
                    ws += (blo(w.x) + bhi(w.x)) + (blo(w.y) + bhi(w.y)) + (blo(w.z) + bhi(w.z)) + (blo(w.w) + bhi(w.w));
                }
                if (q < NREP) st_relaxed128(my_stats, make_uint4(0, 0, 0, 0));
                tag = tag % 3 + 1;
                sts32(sm + SM_TOK + 8, tag);
                bar_arrive(6, 160);
#pragma unroll
                for (int o = 1; o < 32; o <<= 1) ws += __shfl_xor_sync(0xFFFFFFFFu, ws, o);
                const uint32_t tb = ((tag & 1) << 15) | ((tag >> 1) << 31);
                const uint32_t ra = sm + SM_RED + (lane >> 1) * 144 + (lane & 1) * 64;
                const uint32_t kidx = 0xFFFF - (128 * (c & 15) + 16 * (lane >> 2) + 2 * (c >> 4) + ((lane >> 1) & 1));
                touch(ws);
                bar_sync(7, 160);
                const uint4 a0 = lds128(ra), a1 = lds128(ra + 16), a2 = lds128(ra + 32), a3 = lds128(ra + 48);
#define F(v) __uint_as_float(v)
                float ss = (F(a0.x) + F(a1.x)) + (F(a2.x) + F(a3.x)), dw = (F(a0.y) + F(a1.y)) + (F(a2.y) + F(a3.y));
                float sx = ((F(a0.z) + F(a1.z)) + (F(a2.z) + F(a3.z))) + ((F(a0.w) + F(a1.w)) + (F(a2.w) + F(a3.w)));
#undef F
                ss += __shfl_xor_sync(0xFFFFFFFFu, ss, 1); dw += __shfl_xor_sync(0xFFFFFFFFu, dw, 1); sx += __shfl_xor_sync(0xFFFFFFFFu, sx, 1);
                const float mean = sx * (1.0f / 1024.0f);
                const float var = fmaxf(ss * (1.0f / 1024.0f) - mean * mean, 0.f);
                const float m = rb(mean);
                float sd; asm("sqrt.approx.ftz.f32 %0, %1;" : "=f"(sd) : "f"(rb(rb(var) + 1e-5f)));
                const float rs = rcp(rb(sd));
                const float hi = rb(rs);
                const uint32_t p0 = pack_b(m, 0.5f * hi), p1 = pack_b(0.5f * (rs - hi), rs * (dw - m * ws));
                const uint32_t o0 = __shfl_xor_sync(0xFFFFFFFFu, p0, 2), o1 = __shfl_xor_sync(0xFFFFFFFFu, p1, 2);
                const uint32_t kr = ((p1 ^ (p1 >> 31 ? 0xFFFF0000u : 0x80000000u)) & 0xFFFF0000u) | kidx;
                const uint32_t k1 = __reduce_max_sync(0xFFFFFFFFu, kr), k2 = __reduce_max_sync(0xFFFFFFFFu, kr == k1 ? 0u : kr);
                const uint32_t sl = (q & 2) ? 0x1054 : 0x5410;
                if (q < NREP) st_relaxed128(my_stats, make_uint4(prmt(p0, o0, sl), prmt(p1, o1, sl), (prmt(p0, o0, sl + 0x2222) & 0x7FFF7FFFu) | tb, g == 0 ? k1 : k2));
                TSL(9);
                { const int t0_ = clock(); while ((int)clock() - t0_ < PDELAY) __nanosleep(20); }
            }
            bar_sync(3, 192);
            const uint32_t tg = lds32(sm + SM_TOK + 8), tb = ((tg & 1) << 15) | ((tg >> 1) << 31);
            {
                const uint32_t* src = &p.sc->stats[G & (NREP - 1)][(sw * 64 + (lane >> 1)) * 8 + (lane & 1)].z;
                uint2 kz[4];
#pragma unroll
                for (int i = 0; i < 4; i++) kz[i] = make_uint2(~tb, 0);
                int it = 0;
                bool ok;
                do {
#pragma unroll
                    for (int i = 0; i < 4; i++)
                        asm volatile("{ .reg .pred p; .reg .b64 t; setp.ne.u32 p, %3, 0; mov.b64 t, {%0,%1};\n"
                                     "@p ld.relaxed.gpu.global.b64 t, [%2]; mov.b64 {%0,%1}, t; }"
                                     : "+r"(kz[i].x), "+r"(kz[i].y) : "l"(src + i * 512), "r"((kz[i].x ^ tb) & 0x80008000u) : "memory");
                    ok = __all_sync(0xFFFFFFFFu, (((kz[0].x ^ tb) | (kz[1].x ^ tb) | (kz[2].x ^ tb) | (kz[3].x ^ tb)) & 0x80008000u) == 0);
                } while (!ok && ++it < SPIN_LIMIT);
                const uint32_t a1 = max(kz[0].y, kz[1].y), b1 = max(kz[2].y, kz[3].y);
                const uint32_t h1 = max(a1, b1), h2 = __vimax3_u32(min(a1, b1), min(kz[0].y, kz[1].y), min(kz[2].y, kz[3].y));
                const uint32_t w1 = __reduce_max_sync(0xFFFFFFFFu, h1), w2 = __reduce_max_sync(0xFFFFFFFFu, h1 == w1 ? h2 : h1);
                sts64(sm + SM_KEYS + sw * 8, w1, w2);
                bar_sync(8, 64);
                const uint2 o = lds64(sm + SM_KEYS + 8 - sw * 8);
                key = sw ? __vimax3_u32(min(w1, o.x), w2, o.y) : max(w1, o.x);
                TSL(19);
            }
            const int t = (0xFFFF - (key & 0xFFFF)) & 2047;
            {
                const uint4* row = reinterpret_cast<const uint4*>(p.x + (size_t)t * 1024);
                uint4 xr[3];
                xr[0] = ldg128(row + 64 * rank + lane); xr[1] = ldg128(row + 64 * rank + 32 + lane); xr[2] = ldg128(row + 2 * G + (lane & 1));
                uint4 stk;
                int it = 0;
                do stk = ld_relaxed128(p.sc->stats[G & (NREP - 1)] + ((t >> 1) & 7) * 128 + (t >> 4)); while (((stk.z ^ tb) & 0x80008000u) && ++it < SPIN_LIMIT);
                if (lane == 0) {
                    sts32(sm + SM_TOK + 4 * sw, t);
                    if (c == 0 && sw == 0) st_relaxed32(&p.sc->epoch, tg);
                }
                const uint32_t se = (t & 1) ? 0x3232 : 0x1010;
                const uint32_t m = prmt(stk.x, 0, se), hi = bmul2(prmt(stk.z, 0, se) & 0x7FFF7FFFu, 0x40004000u), lo = bmul2(prmt(stk.y, 0, se), 0x40004000u);
                const uint32_t a = sm + SM_XSEL + lane * 32 + sw * 16;
#pragma unroll
                for (int i = 0; i < 2; i++)
                    sts128(a + i * 1024, norm2(xr[i].x, m, hi, lo), norm2(xr[i].y, m, hi, lo), norm2(xr[i].z, m, hi, lo), norm2(xr[i].w, m, hi, lo));
                proxy_fence();
                __syncwarp();
                if (lane == 0) mbar_arrive(bars + B_TOK * 8);
                if (sw == rank && lane < 2) {
                    sts128(sm + SM_XRAW + lane * 16, xr[2].x, xr[2].y, xr[2].z, xr[2].w);
                    sts128(sm + SM_XRAW + 32 + lane * 16, norm2(xr[2].x, m, hi, lo), norm2(xr[2].y, m, hi, lo), norm2(xr[2].z, m, hi, lo), norm2(xr[2].w, m, hi, lo));
                }
                __syncwarp();
                TSL(42);
            }
        }
        mbar_wait(bars + B_TOK * 8);
        const uint32_t tag = lds32(sm + SM_TOK + 8);
        {
            if (G < 56) {
                const uint64_t dw = (uint64_t)((sm & 0x3FFFFu) >> 4) | (1ull << 16) | (64ull << 32) | (1ull << 62);
                const uint64_t dx = (uint64_t)(((sm + SM_XSEL) & 0x3FFFFu) >> 4) | (2ull << 16) | (8ull << 32);
                const uint64_t dh = (uint64_t)(((sm + SM_H) & 0x3FFFFu) >> 4) | (8ull << 16) | (8ull << 32);
                const uint64_t dw2 = dw + (tag >> 2);
                float ag[4], au[4];
                TSL(13);
#pragma unroll
                for (int n = 0; n < 8; n++) {
                    const uint64_t a = (n < 7 ? dw : dw2) + (chunk_off(n) >> 4), b = dx + n * 16;
                    mbar_wait(bars + (B_FULL + n) * 8);
                    wg_fence();
                    if (n == 0) { wg_w0(ag, a, b); wg_w0(au, a + 512, b); } else { wg_w<1>(ag, a, b); wg_w<1>(au, a + 512, b); }
#pragma unroll
                    for (int k = 1; k < 4; k++) { wg_w<1>(ag, a + 128 * k, b + 4 * k); wg_w<1>(au, a + 512 + 128 * k, b + 4 * k); }
                    wg_commit();
                    bool any = false;
#pragma unroll
                    for (int i = 0; i < 5; i++) any |= ((REFILL >> (4 * i)) & 15) == n;
                    if (any) {
                        if (n <= 5) { wg_wait<1>(); bar_sync(4, 128); }
                        if (v == (n & 3)) {
#pragma unroll
                            for (int i = 0; i < 5; i++) if (((REFILL >> (4 * i)) & 15) == n && lead) load_chunk(7 + i);
                            __syncwarp();
                        }
                    }
                    if (n == 4) TSL(4);
                    if (n == 7) TSL(34);
                }
                wg_wait<0>();
                touch(ag); touch(au);
                TSL(14);
                if (q == 0) {
#pragma unroll
                    for (int r = 0; r < 2; r++) {
                        const uint32_t dst = mapa(sm, r), o = dst + SM_PAIR + rank * 1024 + v * 256 + g * 32;
                        st_async4(o, __float_as_uint(ag[0]), __float_as_uint(ag[1]), __float_as_uint(ag[2]), __float_as_uint(ag[3]), dst + SM_BAR + B_PAIR * 8);
                        st_async4(o + 16, __float_as_uint(au[0]), __float_as_uint(au[1]), __float_as_uint(au[2]), __float_as_uint(au[3]), dst + SM_BAR + B_PAIR * 8);
                    }
                }
                mbar_wait(bars + B_PAIR * 8);
                {
                    const uint32_t o = sm + SM_PAIR + v * 256 + g * 32 + q * 4, og = o + (p.up_first ? 16 : 0), ou = o + (p.up_first ? 0 : 16);
                    const float gs = rb(__uint_as_float(lds32(og)) + __uint_as_float(lds32(og + 1024)));
                    const float us = rb(__uint_as_float(lds32(ou)) + __uint_as_float(lds32(ou + 1024)));
                    const float hv = rb(siluf_(gs)) * us;
                    const uint32_t hd = sm + SM_H + (2 * v + (q >> 1)) * 128 + (q & 1) * 32 + g * 2, hb = pack_b(hv, hv);
                    sts16(hd, hb); sts16(hd + 64, hb);
                }
                proxy_fence();
                bar_sync(4, 128);
                TSL(15);
#pragma unroll
                for (int n = 0; n < 4; n++) {
                    const uint64_t a = dw2 + (chunk_off(8 + n) >> 4);
                    float d[2][4];
                    mbar_wait(bars + (B_FULL + 8 + n) * 8);
                    if (n == 3) TSL(24);
                    wg_fence();
                    wg_w0(d[0], a, dh); wg_w0(d[1], a + 512, dh);
#pragma unroll
                    for (int k = 1; k < 4; k++) { wg_w<1>(d[0], a + 128 * k, dh + 16 * k); wg_w<1>(d[1], a + 512 + 128 * k, dh + 16 * k); }
                    wg_commit();
                    wg_wait<0>();
#pragma unroll
                    for (int i = 0; i < 2; i++) {
                        touch(d[i]);
                        st_relaxed32(my_part + (2 * n + i) * 8 * 56 * 16, (__float_as_uint((q & 2) ? d[i][2] : d[i][0]) & ~3u) | tag);
                    }
                }
                TSL(16);
            } else {
                mbar_wait(bars + B_STG * 8);
            }
            {
                const uint2* src = reinterpret_cast<const uint2*>(p.sc->part) + c * 448 + v * 112 + lane;
                uint2 pv[4];
#pragma unroll
                for (int i = 0; i < 4; i++) pv[i] = make_uint2(i == 3 && lane >= 16 ? tag : 0u, i == 3 && lane >= 16 ? tag : 0u);
                for (int it = 0; it < SPIN_LIMIT; it++) {
#pragma unroll
                    for (int i = 0; i < 4; i++)
                        if (((pv[i].x ^ tag) | (pv[i].y ^ tag)) & 3)
                            asm volatile("ld.relaxed.gpu.global.v2.u32 {%0,%1}, [%2];" : "=r"(pv[i].x), "=r"(pv[i].y) : "l"(src + 32 * i) : "memory");
                    uint32_t bad = 0;
#pragma unroll
                    for (int i = 0; i < 4; i++) bad |= (pv[i].x ^ tag) | (pv[i].y ^ tag);
                    if (__all_sync(0xFFFFFFFFu, (bad & 3) == 0)) break;
                }
#define F(v) __uint_as_float(v)
                sts64(sm + SM_XSEL + (tid & 127) * 8, __float_as_uint((F(pv[0].x) + F(pv[1].x)) + (F(pv[2].x) + F(pv[3].x))),
                      __float_as_uint((F(pv[0].y) + F(pv[1].y)) + (F(pv[2].y) + F(pv[3].y))));
            }
            if (v != 2 + rank) {
                bar_arrive(8, 128);
            } else {
                const int t = (0xFFFF - (key & 0xFFFF)) & 2047, col = lane & 15;
                const float sg = rb(sigmoidf_(F((key & 0x80000000u) ? (key & 0x7FFF0000u) : (~key & 0xFFFF0000u))));
                const float xn = blo(lds16(sm + SM_XRAW + 32 + col * 2)), xv = blo(lds16(sm + SM_XRAW + col * 2));
                mbar_wait(bars + B_FIX * 8);
                const float s = blo(lds16(sm + SM_FIX + col * 2));
                __nv_bfloat16* const op = p.out + (size_t)t * 1024 + G * 16 + col;
                sched_fence();
                bar_sync(8, 128);
                TSL(25);
                float y8[8];
#pragma unroll
                for (int i = 0; i < 8; i++) y8[i] = F(lds32(sm + SM_XSEL + i * 128 + lane * 4));
#undef F
                float y = ((y8[0] + y8[1]) + (y8[2] + y8[3])) + ((y8[4] + y8[5]) + (y8[6] + y8[7]));
                y += __shfl_xor_sync(0xFFFFFFFFu, y, 16);
                const float z = rb(xn + rb(rb(y) * sg));
                if (lane < 16) *op = __float2bfloat16(xv + rb(s * rb(siluf_(z))));
                TSL(26); TG(29);
            }
        }
    }
    }
}

__device__ __align__(128) const uint32_t g_tab[5504] = {
0x2fff3000,0x2e7c2fd4,0x2fc92fd4,0xad72af5a,0x2ff82ffc,0x230e2c07,0x2faf2fbc,0x217ea934,0x2fed2ff4,0xad4da8d5,0x2f912fa0,0x2e5e2bb7,
0x2fdd2fe6,0xb000af46,0x2f6e2f80,0x2fdd2fc9,0x2ff42fff,0x2e1f2fc9,0x2e1f2e7c,0xa875ad72,0x2fbc2fdd,0x9fd92a4e,0x2d4d2dba,0x2cd825db,
0x2f5a2f91,0xaeb5ac07,0x2c5d2cd8,0x30002f30,0x2ed02f1a,0xaf80aff4,0x2aaa2bb7,0x2cb02f1a,0x2fdd2ffc,0x2dba2fbc,0x2a4e2c07,0x25dba934,
0x2f462fa0,0xa7652875,0x25152875,0x2f802d27,0x2e3f2ed0,0xafa0ad72,0xa17e1cb6,0x2e3f2fe6,0x2cd82d96,0xadfeafd4,0xa934a6a1,0xa44e29f1,
0x2fbc2ff8,0x2d4d2faf,0x9fd9230e,0x2cd8217e,0x2e992f46,0xaa4e2515,0xaa4ea765,0x2fd42f80,0x2cb02dba,0xafffae99,0xad72ac5d,0x27652dba,
0x28752b05,0xab5eaee9,0xaf1aae5e,0xae3fa934,0x2f912ff4,0x2cd82fa0,0xac07a8d5,0x2f302bb7,0x2dba2ed0,0xac5d1cb6,0xae99ad72,0x2dba2fe6,
0x29932c5d,0xafc9af6e,0xafe6af6e,0xaaaa25db,0xa17e244e,0xa30ead4d,0xafafaffc,0xaff8aee9,0x2f5a2fed,0x2c5d2f91,0xaeb5ad4d,0x30002e5e,
0x2cb02e3f,0xad72a17e,0xafffafa0,0x27652e3f,0x217e2993,0xaf02afe6,0xaf02afc9,0xaf1aaaaa,0xab05a5db,0x2814aa4e,0xac07adba,0xad4dafdd,
0x2f1a2fe6,0x2bb72f80,0xaff4af46,0x2f1a2fc9,0x2b052d96,0xae5ea6a1,0xaee9afd4,0xa93429f1,0xa5db244e,0xadbaaffc,0xaa4ead4d,0xafddaee9,
0xaddcabb7,0x2cb0a17e,0x2765a17e,0x1cb6ad00,0x2ed02fdd,0x2aaa2f6e,0xaf80b000,0x2cb02fdd,0x28752cd8,0xaf1aa934,0xab5eadfe,0xae3fa44e,
0xab05a17e,0xac07afaf,0x2814a30e,0xad4daff8,0xaf6eaddc,0x2eb52765,0x2eb52cb0,0x2dba1cb6,0x29932f5a,0xa7652e99,0x25152e99,0x2aaaad96,
0xafa0ab05,0xabb7afed,0xaff4acd8,0x28d52ffc,0xa814af02,0x2f912d27,0x9fd9ae1f,0xaee9ae3f,0x2fd42c32,0xaf5a1cb6,0x30002d72,0x2fd42515,
0x28752f46,0xa8d52e7c,0xa8d52c32,0x2e3fa993,0xafedac5d,0xa934b000,0xaf30af5a,0xa8142eb5,0x1648adfe,0x2e992e5e,0x2c87a814,0xa9f1affc,
0x2fe62e1f,0xafffa875,0x2ddc2ff4,0x2ed02e1f,0x26a12f30,0xa9f12e5e,0xad96244e,0x2fd41fd9,0xafffad27,0xa515aff4,0xac32aff4,0xaddc2b5e,
0x2875acb0,0x2d272f46,0x2fa02993,0x2875aed0,0x2ee92f6e,0xaf91ac87,0x1fd92e99,0x28143000,0x244e2f1a,0xab052e3f,0xaf91a875,0x2fbc2b5e,
0xafd4addc,0x1648afc9,0x1648ae7c,0xafdd9cb6,0x2c32aa4e,0x2aaa2fd4,0x2f802e99,0x2e7caa4e,0x2d002ffc,0xae1fae5e,0xad272814,0xabb72dfe,
0x1fd92f02,0xac072e1f,0xafedad27,0x2dfe2e3f,0xaf6eae7c,0x25dbaf80,0x2c5daaaa,0xaf6eac32,0x2ddca5db,0x25153000,0x2c323000,0x2fff26a1,
0x28d52fbc,0xabb7af91,0xaff4ab05,0xafa0244e,0x96482ee9,0xac872dfe,0xae99af30,0x29f12fbc,0xaed0af02,0x2993af1a,0x2f46217e,0xacb0af02,
0x2f1a1cb6,0xa30e2fc9,0xa30e2e7c,0x2e1f2ddc,0x9fd92eb5,0xa44eb000,0xae5eaf5a,0xaf30ac5d,0xa17e2ed0,0xad002ddc,0xabb7afff,0xa17e2fe6,
0xadfeaf6e,0x2c07ae99,0x2fed2c87,0x9fd9b000,0x2fd42814,0xa9f12f30,0xad962934,0x26a12fed,0xaaaa2d00,0x2765afa0,0xa515afa0,0xa993afaf,
0xa5152eb5,0xad722dba,0x9cb6af6e,0xac322eb5,0xad00afbc,0x2d27adfe,0x2e1f2f30,0x2bb7aee9,0x2ffc2b5e,0xacd82e3f,0xafeda875,0xab052f1a,
0xadba2993,0x2c87ae7c,0x2c87ac32,0x2a4eaf46,0xaddc2d96,0xafe62c5d,0xaed02c5d,0x2fffa9f1,0x2e1fad4d,0x2e3f2814,0x2f02ac07,0xad27ab05,
0xae5e2d00,0x9fd9af1a,0xaf302b5e,0xa44e2faf,0x2e99acb0,0xad962f80,0x2f5aaaaa,0x2e99aed0,0xae3f2d72,0xaff82c32,0xaff82515,0x2f021cb6,
0x2ee9ac87,0x2d4d29f1,0x2ffc9648,0xa44eae99,0xaf6e2b05,0x26a1afbc,0xafd4a44e,0xadba2f91,0x2fc9a8d5,0xaf462e3f,0x2f802875,0x2fe6a8d5,
0xae992d4d,0xb0002c07,0xaf6ea814,0x2c872b05,0x2f80ab5e,0x2c322bb7,0x2e7c2bb7,0x2aaaaff8,0xaff42765,0x2b5eafff,0xad27ad72,0xaff42cb0,
0x2fed1648,0xaffc2c5d,0x2b052eb5,0x2cd82a4e,0xaee92d27,0xaffc2bb7,0xad4dad00,0x244e2e1f,0x2fdda993,0x29f12cb0,0x29f12ed0,0x2eb5af46,
0xafe61648,0x2d72afdd,0x9cb6afd4,0xaed01648,0x2f022934,0xafa02814,0xa8d52fed,0xa30e2f30,0xaf302d00,0xafed2b5e,0xa814af1a,0xa9342faf,
0x3000a765,0x26a12d72,0xa5db2fff,0x3000acb0,0xaf46a6a1,0x2ed0af5a,0x2cb0af5a,0xa993ac87,0x2d272cd8,0xae3f9fd9,0xaf022d4d,0xae1f2fbc,
0xaf6e2cd8,0xafd42b05,0x26a1affc,0xadba2fed,0x2fe6a30e,0x1cb62e1f,0xad722f1a,0x2ed0a30e,0xae1faaaa,0x2fafae7c,0x2fafac32,0x28d5af80,
0x29342e99,0xac07a9f1,0xafbc1648,0xaffc2c87,0xafa02cb0,0xafaf2aaa,0x2d00af80,0xafa02ed0,0x2f911648,0xa44e2eb5,0xafbc2c5d,0x2b052a4e,
0xac87acd8,0x3000ad4d,0x2f6e1fd9,0x2e99afbc,0x9cb62faf,0xa515ad27,0xac32ad27,0xad72a30e,0xafc92c87,0xaf802a4e,0x2f46adba,0xafe62c87,
0x2f02244e,0xa8d52f30,0xafa01fd9,0xa30e2e5e,0xa934ae1f,0x2fbcabb7,0x2c072d00,0x2ffcad27,0xaa4e2fff,0x26a1aed0,0x26a1afe6,0x1648addc,
0xaf4629f1,0xac3225db,0xae7c25db,0x29931648,0xab5e2f91,0xafaf2e5e,0xad002fed,0x2f1aad4d,0x2ee9a875,0xaf302ff8,0x2dfea17e,0x2fbcaff4,
0x2c5dafc9,0xa9f12d72,0x2d96afff,0x2c5dae7c,0xaf022993,0xab5e2515,0xab5ea765,0xa30e2aaa,0xacd82fd4,0xaf302dba,0xaf912f6e,0x2c07a6a1,
0x2d969fd9,0xafdd2fed,0x25db2c07,0x2f5aadfe,0x2e7caff8,0xad722f02,0x2fffae3f,0x2fc9aff8,0xaeb52934,0xaa4e244e,0x9648acd8,0xac5d2dfe,
0xaddc2ff8,0xae7c2d00,0xafc92d00,0x9cb628d5,0x2bb72515,0xaff82f80,0xab5e2f46,0x2bb7a765,0x2fbcaf5a,0xaf302fdd,0x2dfea5db,0x2ee9ad96,
0xae5e28d5,0xa934230e,0x2b05af02,0xaee92fa0,0xaeb52fff,0xad962c32,0xad962515,0xac872ddc,0x276529f1,0xaf802eb5,0xaf462fdd,0xa51529f1,
0x2ff4adfe,0xaff82fed,0x217e2c07,0x28759fd9,0xadfe2875,0xa814217e,0x2e5eaff8,0xaffc2ff4,0xaf5a2fe6,0xac872aaa,0xa6a1a993,0xaf5a2fc9,
0x9cb62c87,0xae7c2d96,0xafc92d96,0xaddc2eb5,0x2f1aac07,0xafaf2f30,0xad002f91,0xab5e2cd8,0xad962814,0xa5db1fd9,0x2fddaf91,0xaf5a2ee9,
0xafc92faf,0xaaaa28d5,0x2993ae1f,0xafe62faf,0xa8d52ddc,0xad002c32,0xad002515,0xaff82fff,0x2d4da6a1,0xae5e2dba,0xafed2f6e,0xaf912fd4,
0xad272765,0xa30e1cb6,0x2fafaddc,0xad272cb0,0xaffc2f5a,0xa81425db,0x2e5eafdd,0xadfe2d96,0xac5d2ee9,0xaa4e2934,0x9648ab05,0xaeb52e5e,
0x2993230e,0xac322b5e,0xae7c2b5e,0xaf462f02,0xacb026a1,0x9cb61648,0x2ddcaa4e,0xa76526a1,0xaff42ee9,0xa17e1fd9,0x2ff8af91,0xa8752814,
0xadfe2fa0,0xa44e230e,0x2cd8af02,0xa93428d5,0x96482aaa,0xa5db2515,0xa5dba765,0xa9f12993,0x2f462f5a,0x2c322e99,0x2e7c2e99,0xa993ad96,
0x2f1a2f30,0xa875244e,0x2e3f2e5e,0x2b5e1fd9,0x2ee92f02,0xaf30ad27,0x2dfe2e1f,0x2fbc2e3f,0x2eb52ed0,0xaf6eafff,0x2dba2ddc,0x2eb52fe6,
0x28752993,0xa8d52515,0xa8d5a765,0x2e3f2aaa,0x244e26a1,0xaf91ad96,0xab05a9f1,0x2fbc2fd4,0x96481fd9,0xae99afed,0xac87ac07,0x29f12dfe,
0xa515a17e,0x9cb6abb7,0xad72ad00,0xac32a17e,0xac5dab05,0xaf5aacd8,0xb000afed,0x2eb52ffc,0xaddcad27,0xae7caff4,0xafc9aff4,0x9cb62b5e,
0xaf02ae7c,0x217eaaaa,0xaf1aaf80,0xaf02ac32,0xafbcaf6e,0x2f302c87,0xadfeae99,0xaee9b000,0xafedafa0,0xaf30aff4,0xa934abb7,0xa81428d5,
0xafd4afff,0x1648ac32,0x1648a515,0xafddaddc,0xaed0af6e,0x2f462c5d,0x299325db,0xacb0af6e,0xad00adfe,0x2e1f2fed,0x2d272c07,0x2bb79fd9,
0xadfeaf02,0xa814ae1f,0x2e5e2d27,0xaffcae3f,0xaa4eacb0,0x2e992993,0x2fd42f46,0xaa4eaed0,0x1cb6a5db,0x2e7c3000,0x2fc93000,0x2ddc26a1,
0x2b5e2814,0xa8752934,0x2e3f2f30,0x2f1a2fed,0x1648a814,0x2c879fd9,0x2e992f91,0xa9f1aee9,0x2c322875,0x2f802fa0,0x2aaa2d27,0x2e7c2875,
0x2f1a2ddc,0xa30e2c32,0xa30e2515,0x2e1f2fff,0x2ffc2fd4,0xafedad96,0xacd8a9f1,0xab0526a1,0x2e1f2c32,0x2ff42d72,0xa8751cb6,0x2e1f2515,
0x2ffc2f6e,0x28142e99,0xae5eac87,0x2dfe3000,0x2eb52fbc,0xaf5aab05,0xb000af91,0xac5d244e,0x29932d00,0xac32afa0,0xae7cafa0,0xaf46afaf,
0x2fe62fd4,0x2ddc3000,0xafffaf5a,0x2ed02fd4,0x2d002ee9,0xad271fd9,0xae1faf91,0xabb72814,0x9fd928d5,0xae5eaff4,0xa44eabb7,0xaf30afa0,
0xadbaaaaa,0x2c87a515,0x2c872765,0x2a4ea993,0x9cb62d96,0xacb02c5d,0xa7652c5d,0x2ddca9f1,0xaff8adfe,0xa30eafbc,0xafafaee9,0xa17e2f30,
0x244ead00,0x2dfe2f1a,0x2934ab5e,0xacd8afaf,0x2fdd2e7c,0xb000a993,0x2f6e2f46,0x2fdd2c32,0xae3f9cb6,0xaff8a765,0xaff8acb0,0x2f022ddc,
0xac07afdd,0x2dfeaa4e,0x1fd9adba,0xafeda5db,0x2f6e2934,0xa6a12ee9,0x2fd42e5e,0x2dbaab05,0x27652f1a,0xaaaaaff4,0xa9932bb7,0xa5152f1a,
0xafddadfe,0xadbaaee9,0xaa4eafbc,0xa5db2f30,0x2aaaab5e,0x2fc92bb7,0x2fe62bb7,0xa993aff8,0x2e3f2fc9,0xafa01cb6,0xa17e2ddc,0x2e3f2e7c,
0xae5e9648,0x2d4dac5d,0xaf91aeb5,0xafedaa4e,0xac07aff8,0x1fd9afaf,0x2dfea30e,0xafeda17e,0x2fdd2aaa,0x29f12fe6,0x29f12fc9,0x2eb5a993,
0xa5152dba,0xaddcae99,0xafffac5d,0xac322dba,0xaf02af30,0x2fa02c07,0x28d5acd8,0x230eaf91,0x2934ad00,0x2e5eab5e,0x2ee92f1a,0xab05afaf,
0x2dba2fc9,0xac5d2ddc,0xae991cb6,0x2dba2e7c,0xaf80a6a1,0x2765af5a,0xa515af5a,0xaf46ac87,0x217eae5e,0x230e2ffc,0x2faf2dfe,0x2ff82814,
0x2f6e244e,0x2fd42934,0xa6a12dfe,0x2dbaacd8,0xa5152e3f,0xafffa17e,0xaddcafa0,0xac322e3f,0xae1faf80,0x2fafa515,0x2faf2765,0x28d5af46,
0x2f9125db,0xaee92a4e,0xa8142dba,0x9fd92fdd,0x2f1a2e7c,0x2bb72f46,0xaff4a993,0x2f1a2c32,0xaf309648,0xacd8aeb5,0x2c07ac5d,0xaf91aa4e,
0x25dbae5e,0x2dba2dfe,0x2a4e2ffc,0x2fdd2814,0x2d722faf,0xae7cad27,0xafc9ad27,0xafffa30e,0x27652fdd,0xa9932f6e,0xaaaab000,0xa5152fdd,
0xaf02ae5e,0x28d5af91,0x2fa02d4d,0x230eafed,0x2f91217e,0xa8142faf,0xaee9230e,0x9fd92ff8,0xaa4e2d72,0x26a1afc9,0x26a1ae7c,0x1648afff,
0xaf8029f1,0xafc925db,0xafe625db,0x2f461648,0x2fa0a934,0x2bb72cd8,0x2ff4a44e,0xa8d5adfe,0xafbc2875,0x2934aff8,0xaffc217e,0xac072ff4,
0x2fd4a765,0xaf5a2ddc,0x30009cb6,0x2fd4acb0,0xaf02aaaa,0xab5eacb0,0xab5eaed0,0xa30e2f80,0x2e5e2c5d,0xab053000,0x29342f5a,0x2ee9aeb5,
0xad96ad4d,0x2fddacd8,0xa5dbafbc,0xaf5a1fd9,0x2cb02e1f,0xaddca875,0x1cb62ff4,0x27652e1f,0xa6a1af91,0x29f1afed,0x2d96ae5e,0xafd42d4d,
0x9cb62ff8,0xafe62d00,0xaed02d00,0x2d7228d5,0x2875afe6,0x2d272993,0x2fa0aaaa,0x2875afc9,0xac072f5a,0x2934afdd,0xaffc25db,0xafbc2d96,
0x2cd8af1a,0x2f91ae3f,0x2f302875,0xac07ab5e,0xaeb52d72,0xad96a765,0xad96acb0,0xac872fff,0x2fc9aa4e,0xa9932fd4,0x2aaa2e99,0x2fe6aa4e,
0xaff41fd9,0x2ff8acd8,0xa17eafbc,0xa875ad4d,0x2ffca875,0x2ee9a17e,0xa44e2ff8,0x2d4daff4,0xaf6ea515,0x25dbaf46,0x2c5daf80,0xaf6e2765,
0x2d722c87,0xafe62d96,0xaed02d96,0x9cb62eb5,0xa8d5aee9,0x2bb72b05,0x2ff4a934,0x2fa0ae5e,0x2d962c07,0x25db2d4d,0xafdd2b05,0x2f5aa814,
0xa765af02,0x2f46af1a,0x2f80217e,0x2515af02,0xa8d52fff,0xad00a765,0xad00acb0,0xaff82d72,0x2dfeaeb5,0xacd83000,0x244e2f5a,0x29342c5d,
0xa17e2fc9,0xad002fff,0xabb7ad72,0xa17e2e7c,0x2d4daf5a,0x2ee9a5db,0xa44e2fdd,0x2ffcad96,0xafd42c07,0x29f1af91,0x2d96af30,0xa6a1acd8,
0x2f46230e,0xafc92b5e,0xafe62b5e,0xaf802f02,0xae7c2eb5,0xafff2dba,0x2d72af6e,0xafc92eb5,0x2ff4a814,0x217e2d4d,0xaff82b05,0x28752c07,
0xad4dab5e,0x2fedae3f,0x2e5e2875,0x2f91af1a,0x96482f80,0xa5dbacb0,0xa5dbaed0,0xa9f1aaaa,0xad729648,0xa515a6a1,0xac32a6a1,0x9cb62a4e,
0xae1f2ffc,0xae3f2c07,0xaf022fbc,0x2d27a934,0x2cd8230e,0xaffc2fa0,0x2b0528d5,0x2fedaf02,0x2e99afe6,0xad962f46,0x2f5aaf80,0x2e99afc9,
0x230eaddc,0x2d27aed0,0x2d27afe6,0xafaf2fff,0xafbc2c87,0x1fd9a9f1,0xad4d1648,0xacd82e99,0xaa4e2f30,0xac5d2814,0xaeb52fed,0x96482934,
0x2ed0a8d5,0xaf802e3f,0x2aaa2875,0x2cb0a8d5,0x2e99affc,0x3000afbc,0x2f6eac07,0xac872934,0xa993a8d5,0x2ed0afaf,0x2cb0afaf,0xaf462e1f,
0xaff42ed0,0x2b5ead72,0xad271cb6,0xaff42fe6,0xa44e2dba,0x9fd9a6a1,0xaf302fd4,0xae5e2f6e,0x2fbcad27,0x2d4dabb7,0x9fd92d00,0x2cd8ae1f,
0x2c87af80,0x2f5aae7c,0x2f5aac32,0x26a1aaaa,0xacb01648,0x2fffafdd,0x2d72afd4,0xa7651648,0xafaf2f91,0x2f1aafbc,0xab5ea44e,0xad002b05,
0x2b05230e,0xa44e28d5,0xafbc2fa0,0x2f91af02,0x3000aed0,0x26a19cb6,0xa5db2d72,0x3000afe6,0x2aaaaeb5,0x2c32a9f1,0x2e7ca9f1,0x2f80afdd,
0xad27244e,0x2e3fad4d,0x2f02affc,0x2e1faee9,0xaa4e2e5e,0xaeb52f30,0xac5d1fd9,0x9648244e,0x2cb0a30e,0xad722e1f,0xafff2f1a,0x2765a30e,
0x2ff8af46,0xabb72cb0,0xabb72ed0,0x2b5ea993,0x2b05ae99,0xa81429f1,0x2c079648,0x2d4dac87,0xafa02fe6,0xafaf2f80,0x2d00af46,0xafa02fc9,
0xa9342dba,0xafed2fd4,0xa814a6a1,0xaf302f6e,0x2c87a44e,0xb0002ffc,0xaf6e2d4d,0xae992ee9,0x2fffaf02,0xafe62ff8,0xaed02ff8,0xaddc2e3f,
0xaed02c87,0xaaaa2a4e,0x2f80adba,0xacb02c87,0xafaf2fed,0xab5e2b05,0x2f1aaffc,0xad002cd8,0xab052e1f,0xac072bb7,0x2814ad00,0xad4d2d27,
0x29f11cb6,0xac5d2c32,0xac5d2515,0xad962d72,0x2d722d96,0x25152c5d,0x2c322c5d,0x1cb6a9f1,0x2d272d4d,0xad00a814,0x2bb72c07,0x2e1f2b05,
0x2cd82d00,0xaffcaf1a,0x2b052b5e,0x2fed2faf,0x2c872cb0,0xadbaaf80,0x2a4e2aaa,0x2c872ed0,0xae3faddc,0xaff8aed0,0xaff8afe6,0x2f022fff,
0xaee9ae99,0xad4daf6e,0xaffcb000,0x244e2c87,0xaf6eaf30,0x26a1a814,0xafd4afed,0xadbaa934,0xafc9afa0,0x2f462d00,0xaf80afaf,0xafe6afa0,
0xac87ad4d,0x9648ac07,0x29f12814,0xae99ab05,0xa993ab5e,0x2ed02bb7,0x2cb02bb7,0xaf46aff8,0xa30ea765,0x2f1a2fff,0x2e1f2d72,0xa30eacb0,
0x244e1648,0x1fd92c5d,0x2f302eb5,0x2e5e2a4e,0x2ee92e1f,0x2ffc2f02,0x2d4d2e3f,0xa44ead27,0x2fdd2f80,0x29f12e7c,0x29f12c32,0x2eb52aaa,
0x2fe63000,0xad72a5db,0x1cb626a1,0x2ed03000,0x2f022f91,0xafa0afbc,0xa8d5a44e,0xa30e2b05,0x2b052d00,0xa44e2b5e,0xafbcaf1a,0x2f912faf,
0x16482765,0xafd4ad72,0xafddafff,0x16482cb0,0xaaaaa6a1,0xac32af5a,0xae7caf5a,0xaf80ac87,0xae1facd8,0x2d001fd9,0xabb7ad4d,0xad27afbc,
0xaf6eae5e,0xafd4af30,0x26a19fd9,0xadbaa44e,0xafe6aff4,0x9cb6ad27,0x2d722b5e,0xaed0aff4,0xae1faf46,0x2faf2cb0,0x2faf2ed0,0x28d5a993,
0xa934ac87,0x2c072f6e,0x2fbc3000,0x2ffc2e99,0xa8d5acb0,0x2875aaaa,0x2e3f2f80,0xa8d5aed0,0x29341648,0x2fed2eb5,0x28142c5d,0x2f302a4e,
0x2e992cd8,0x16482d4d,0xa9f19fd9,0x2c872fbc,0x2fff2faf,0xafe6ad27,0xaed0ad27,0xaddca30e,0x2fc92e99,0x2f802f5a,0xaf46ad96,0x2fe62e99,
0x2f022fed,0xa8d52b05,0xafa0affc,0xa30e2cd8,0x29342d27,0xafbcaf02,0xac07ae3f,0xaffcae1f,0xaa4e9cb6,0x26a1ac32,0x26a1a515,0x1648ad72,
0xaaaa29f1,0xaed025db,0xacb025db,0x2f801648,0xaf1aaf91,0x2875ae5e,0xae3fafed,0xab5e2d4d,0x2c07a875,0x2b052ff8,0x2d4da17e,0xa814aff4,
0x2eb52fc9,0xaf6ead72,0x2dba2fff,0x2eb52e7c,0xaf02af80,0xab5eafe6,0xab5eafc9,0xa30e2f46,0x2cd8a6a1,0x2f302d96,0x2f9129f1,0xac07afd4,
0x2d962ffc,0xafdda44e,0x25db2ee9,0x2f5a2d4d,0xae7ca17e,0x2d72abb7,0xafffad00,0xafc9a17e,0x2c5da934,0x2f5aa44e,0x30002cd8,0xaeb5adfe,
0x2d722ff8,0xacb02d00,0xa7652d00,0x2fff28d5,0xaf02a515,0x217eaf80,0xaf1aaf46,0xaf022765,0xa814af5a,0x2b052fdd,0x2d4da5db,0x2c07ad96,
0x2e5e2fa0,0x29342ff4,0xab052bb7,0x2ee9a8d5,0xaeb59cb6,0xad96aed0,0xad96afe6,0xac872d72,0xa765af6e,0x2f802c5d,0x2f4625db,0x2515af6e,
0x2ff42d4d,0xaff8a44e,0x217e2ee9,0x28752ffc,0xad4d2875,0xafbc217e,0xacd8aff8,0x1fd92ff4,0xaa4eafe6,0x2e99aaaa,0x2fd42993,0xaa4eafc9,
0x2fff2c87,0xacb02d96,0xa7652d96,0x2d722eb5,0xab5e2c07,0x2875af30,0xae3faf91,0xaf1aacd8,0xad96afbc,0xa5dbaffc,0x2fdd2934,0xaf5aac07,
0x2fc92875,0x2aaa2fa0,0xa9932d27,0x2fe62875,0xa8d52d72,0xad00aed0,0xad00afe6,0xaff89cb6,0xad4dafd4,0x2e5e2d96,0x2fed29f1,0x2f91a6a1,
0x2e1fa765,0x2ff49cb6,0xa8752ddc,0x2e1facb0,0x1fd92f5a,0xafbc25db,0xacd8afdd,0xad4d2d96,0xaeb5aee9,0x2f5aa934,0x30002b05,0x2c5dae5e,
0x2f80230e,0xaed02b5e,0xacb02b5e,0xaaaa2f02,0x2cb02fd4,0x1cb63000,0xaddcaf5a,0x27652fd4,0xaff4ac07,0xa17eaffc,0x2ff82934,0xa875afbc,
0x2dfea8d5,0x244e2ff4,0xacd82bb7,0x29342fa0,0x96482f46,0xa5dbafe6,0xa5dbafc9,0xa9f1af80,0xafff9648,0xae7ca6a1,0xafc9a6a1,0x2d722a4e,
0x2ff81fd9,0x230e2ee9,0x2faf2814,0x217eaf91,0xafeda30e,0x2d4dafa0,0xaf91a8d5,0xae5e2f02,0x2fdd2515,0xb0002aaa,0x2f6e2993,0x2fdda765,
0x230eafff,0x2d27afc9,0x2d27ae7c,0xafaf2d72,0xa8142fdd,0xaffc2a4e,0xadfe2dba,0x2e5e25db,0x2a4eaf91,0x2c5d2c07,0x2eb5acd8,0x1648af30,
0xac322f1a,0x2993aff4,0xaf462bb7,0xae7c2f1a,0x2fdd1fd9,0x2dba2814,0x2a4e2ee9,0x25dbaf91,0xaf46a8d5,0x2765afaf,0xa515afaf,0xaf802e1f,
0x2e3f2c32,0xafa02ddc,0xa17e2fff,0x2e3f2515,0xacd8adba,0x2dfe26a1,0x2934afd4,0x244eaf6e,0xa8142ff8,0xadfe2faf,0xaffc230e,0x2e5e217e,
0x2c87af46,0x2f5aa515,0x2f5a2765,0x26a1af80,0xae7c2dba,0x9cb6ae99,0xaddcac5d,0xafc92dba,0x2fafab05,0xaf1a2ee9,0x2b5e2e5e,0x2d002934,
0xaf91a30e,0xacd8a8d5,0x2c07afa0,0xaf302f02,0x2dba2c32,0xac5d2fff,0xae992ddc,0x2dba2515,0xa993aeb5,0x2fc9a9f1,0x2fe6a9f1,0x2aaaafdd,
0xa17e2fed,0xa30eadfe,0xafaf9fd9,0xaff82c07,0x2a4eafed,0x2eb5af91,0x2c5d2d4d,0x1648ae5e,0xae7c2e3f,0xaddca17e,0x9cb6afa0,0xafc92e3f,
0x2ff8a993,0xabb72fe6,0xabb72fc9,0x2b5e2aaa,0xaf30a5db,0x2fbcaa4e,0x2ee9adba,0x2dfeafdd,0x2f1a2515,0x2bb72993,0xaff42aaa,0x2f1aa765,
0xab05adba,0x2e5eafd4,0x2ee926a1,0x2934af6e,0xa5db2fed,0xadba9fd9,0xaa4eadfe,0xafdd2c07,0x2ddcaf02,0xacb02ff8,0xa7652ff8,0x9cb62e3f,
0xac322fdd,0xaf462f6e,0x2993b000,0xae7c2fdd,0x2fafacd8,0x2b5e2934,0xaf1a2dfe,0x2d00244e,0xaf30a17e,0x2ee9afaf,0x2fbca30e,0x2dfeaff8,
0x29f12ddc,0xac5da765,0xac5dacb0,0xad969cb6,0xa993aa4e,0x2765ac87,0xa515ac87,0xaaaa2dba,0xafa02f30,0xabb7244e,0xaff42e5e,0x28d51fd9,
0x28142bb7,0xaf912e1f,0x1fd92d27,0x2ee9ad00,0x2fd4aed0,0xaf5a2fff,0x3000addc,0x2fd4afe6,0x2fafaf46,0x2fa0ae7c,0x2fa0ac32,0xad002993,
0xa44eac5d,0x2f91b000,0x2b05af5a,0xafbc2eb5,0xb0002dfe,0x2c87ae5e,0xae992814,0xaf6e2ffc,0xa5152e1f,0x9cb6a875,0xad722ff4,0xac322e1f,
0x26a12b05,0xa9f12cd8,0xad962fed,0x2fd4affc,0x2fffae1f,0x2515230e,0x2c32230e,0x2ddcaf1a,0x2875ae7c,0x2d27aaaa,0x2fa0af80,0x2875ac32,
0xaee929f1,0x2f91ae99,0x9fd9ac87,0xa8149648,0xafed2f1a,0xaf302e3f,0xa934a875,0xa8142b5e,0xa6a12ddc,0xb0002fc9,0xb0002e7c,0x25db1cb6,
0x2ed0aa4e,0xaf462fd4,0xa9932e99,0x2cb0aa4e,0x2e3faffc,0xad272e5e,0x2e1fa814,0x2f02adfe,0x9fd9abb7,0x2c07ad27,0x2fedae1f,0xadfe2d00,
0xaf6e2cb0,0x25dba993,0x2c5daf46,0xaf6e2ed0,0xaddc2fdd,0xa5159648,0xac329648,0xafff2fd4,0x28d52814,0xabb72934,0xaff42f30,0xafa02fed,
0x3000aee9,0x2e99adfe,0xac872f30,0x2f6eafbc,0x2c32af02,0x2f80af1a,0x2aaa217e,0x2e7caf02,0xab5e9cb6,0x2ff4afc9,0x2ff4ae7c,0x2d27addc,
0xaffc2eb5,0x2fedb000,0x2cd8af5a,0x2b05ac5d,0xa17e2c32,0xad002d72,0xabb71cb6,0xa17e2515,0x2dfea9f1,0xac072c87,0xafed2e99,0x1fd91648,
0x2fd4afbc,0xa9f12b05,0xad962f91,0x26a1a44e,0x2aaaae3f,0xa76528d5,0x251528d5,0x2993a875,0xafe62eb5,0xaddc2dba,0x2fffaf6e,0xaed02eb5,
0xae3f2fbc,0xae1f2dfe,0x2d27af30,0xaf022ee9,0x9fd92b5e,0xae5e2e3f,0xa44ea875,0xaf302f1a,0x2d96a993,0xae992e7c,0xae992c32,0xaf5a2f46,
0x299329f1,0xa76525db,0x251525db,0x2aaa1648,0x28d52934,0xaf02acd8,0x230e244e,0x2fa02dfe,0x28142875,0xaf91aff8,0x1fd9217e,0x2ee92ff4,
0x26a12765,0xaa4eaddc,0x16481cb6,0x26a12cb0,0xaf02af46,0xab5eae7c,0xab5eac32,0xa30e2993,0xae5eaeb5,0x2b059648,0xa934aa4e,0xaee9ac5d,
0xad96adfe,0x2fdd2e5e,0xa5dba814,0xaf5aaffc,0xacb0ad27,0x2ddc2faf,0x9cb6a30e,0xa765ad27,0x2fd42f91,0x2f6e2fed,0x2dba2e5e,0xa6a1ad4d,
0x2fff2ff8,0x25152d00,0x2c322d00,0x2ddc28d5,0x2faf2fe6,0xae1fa993,0x28d52aaa,0x2faf2fc9,0x2ee92f5a,0xaf91afdd,0x1fd925db,0x28142d96,
0xacd8ab5e,0xaf91ad00,0xaf30afaf,0x2c072f1a,0xaeb5addc,0xad96afc9,0xad96ae7c,0xac879cb6,0xafc9af5a,0x2993a6a1,0xaaaaac87,0xafe6af5a,
0xaff4affc,0x2ff82e5e,0xa17ea814,0xa875adfe,0x9fd9a875,0x2c07a17e,0x2fed2ff8,0xadfeaff4,0x29f12515,0x2fdd2f46,0x2eb52f80,0x29f1a765,
0x2ddc2c87,0x25152d96,0x2c322d96,0x2fff2eb5,0x2fa02ee9,0xaf02ab05,0x230e2934,0x28d52e5e,0x2d962ee9,0x25db2dfe,0xafddaf30,0x2f5a2fbc,
0x27652bb7,0xaf46ab5e,0xaf80aff8,0xa5152bb7,0xa8d59cb6,0xad00afc9,0xad00ae7c,0xaff8addc,0xadfeac5d,0x2cd89648,0xa44eaa4e,0xa934aeb5,
0xaff8afc9,0xae3fafff,0x2f022d72,0xaff8ae7c,0xadfeaf5a,0x2c07a5db,0x2fed2fdd,0x9fd9ad96,0xa6a1ac07,0x2f6e2f91,0x2dba2f30,0x2fd42cd8,
0x2aaa230e,0xa7652b5e,0x25152b5e,0x29932f02,0x2e7c2c5d,0x2fff2d96,0xad72a9f1,0x2fc92c5d,0x2ff42fbc,0x217e2dfe,0xaff8af30,0x28752ee9,
0x2d4d2f1a,0xafedad00,0xae5eafaf,0xaf91ab5e,0x96482993,0xa5dbae7c,0xa5dbac32,0xa9f1af46,0xaddc9648,0xafe6a6a1,0xaed0a6a1,0x2fff2a4e,
0xad27affc,0x2d00ac07,0xabb7afbc,0xae1f2934,0x2e5e230e,0x1fd92fa0,0x2f3028d5,0x244eaf02,0x2c872fe6,0xadbaaf46,0x2a4e2f80,0x2c872fc9,
0x230ead72,0x2d27ac32,0x2d27a515,0xafaf9cb6,0x2fbc2e99,0x9fd92f6e,0x2d4d3000,0x2cd8ac87,0xaa4e2b05,0xac5dafbc,0xaeb5a44e,0x96482f91,
0xaed0afa0,0x2f802d00,0xaaaaafaf,0xacb0afa0,0x2c872ffc,0x16482fbc,0xa9f12c07,0x2e99a934,0xaf80a8d5,0xac32afaf,0xae7cafaf,0xaaaa2e1f,
0xa30eaed0,0x2f1a2d72,0x2e1f9cb6,0xa30eafe6,0x2fed2dba,0xaffca6a1,0x2b052fd4,0x2cd82f6e,0xafbcae1f,0xad4daf02,0x1fd9ae3f,0xacd82d27,
0x2c87a993,0x2f5a2cb0,0x2f5a2ed0,0x26a1af46,0x2cb03000,0xafffa5db,0xad7226a1,0x27653000,0xafafa934,0x2f1aa814,0xab5eafed,0xad00af30,
0x2f30230e,0x2fed28d5,0x28142fa0,0x2934af02,0x16482ed0,0xafd41cb6,0xafddad72,0x16482fe6,0xaf46aeb5,0x2ed0a9f1,0x2cb0a9f1,0xa993afdd,
0x2e1fa44e,0xad002d4d,0x2bb72ffc,0x2d272ee9,0xaa4e2cd8,0xaeb52b05,0xac5daffc,0x96482fed,0xacb0aff4,0x2d72ad27,0x2fff2b5e,0xa765aff4,
0x2ff82aaa,0xabb72e7c,0xabb72c32,0x2b5e2f80,0xab052c87,0x2814af6e,0xac07b000,0xad4dae99,0xa8d5afe6,0x2875af80,0x2e3f2f46,0xa8d5afc9,
0x2f912dba,0xa44e2fd4,0xafbca6a1,0x2b052f6e,0xae99244e,0x9648affc,0x29f1ad4d,0xac87aee9,0x1cb6af02,0x25152ff8,0x2c322ff8,0x2d722e3f,
0x2ed02e99,0x2aaa2f5a,0xaf80ad96,0x2cb02e99,0xafafa44e,0xab5eaf30,0x2f1a9fd9,0xad00ae5e,0x2b05ad27,0x2c072f02,0xa8142e3f,0x2d4d2e1f,
0x29f12fff,0xac5daed0,0xac5dafe6,0xad96addc,0xaf46aa4e,0xac32ac87,0xae7cac87,0x29932dba,0x2f1a2b05,0xa8752fed,0x2e3f2cd8,0x2b5eaffc,
0xaee9abb7,0x2f30ae1f,0xadfead27,0xafbc2d00,0x2eb52c32,0xaf6e1cb6,0x2dba2d72,0x2eb52515,0x2fafa993,0x2fa0a515,0x2fa02765,0xad00aaaa,
0xafed26a1,0xa934ad96,0xaf30a9f1,0xa8142fd4,0x30009fd9,0xac872fed,0x2e992c07,0x2f6eadfe,0xafe6a17e,0x2fffabb7,0xaddcad00,0xaed0a17e,
0xac5d2f30,0xaf5a2e5e,0xb000244e,0x2eb51fd9,0x2ddcae1f,0x2e7c230e,0x2fc9230e,0x1cb6af1a,0xaf022cb0,0x217eaf46,0xaf1aa993,0xaf022ed0,
0x2fbca9f1,0xaf302e99,0x2dfe2c87,0x2ee91648,0xa44eafa0,0x2b05aff4,0x2f91abb7,0xafbc28d5,0xa6a12fff,0xb0002c32,0xb0002515,0x25db2ddc,
0x2c32af6e,0x2aaa2c5d,0x2f8025db,0x2e7caf6e,0xae3f2dfe,0x2d27afed,0xae1fac07,0xaf021fd9,0x2dfe2bb7,0x28142d27,0xae5e2e1f,0x2ffcad00,
0xaa4eae7c,0x2e99af80,0x2fd4aaaa,0xaa4eac32,0x9cb62fdd,0xae7c9648,0xafc99648,0xaddc2fd4,0x2b5eafbc,0xa8752f91,0x2e3f2b05,0x2f1aa44e,
0xb0002814,0xae991fd9,0x2c87af91,0xaf6e2ee9,0x2ed02875,0xa9932fa0,0xaf462d27,0x2cb02875,0xab5eaddc,0x2ff4ac32,0x2ff4a515,0x2d27afff,
0x9fd92fd4,0xa44ead96,0xae5ea9f1,0xaf3026a1,0x2e1faed0,0x2ff4addc,0xa8752fff,0x2e1fafe6,0xaffc29f1,0xa814ac87,0x2e5eae99,0xadfe9648,
0x2eb52814,0xaf5a2f30,0xb0002934,0xac5d2fed,0xa993ae3f,0x2c3228d5,0x2e7c28d5,0x2f46a875,0xa5152fd4,0xad723000,0x9cb6af5a,0xac322fd4,
0x2e3faee9,0x2e1f9fd9,0xad272f91,0x2f02a814,0xaffc28d5,0x2cd8aff4,0x2fedabb7,0x2b05afa0,0x2d962aaa,0xae992515,0xae99a765,0xaf5a2993,
0x1cb6adba,0x2cb0aeb5,0x2765aeb5,0xaddc2f6e,0xaff82d4d,0xa30ea814,0xafaf2c07,0xa17e2b05,0xa44e2e3f,0xadfe2b5e,0xa9342f1a,0x2cd8a875,
0x2fddacb0,0xb0002f80,0x2f6eaaaa,0x2fddaed0,0x2d001cb6,0x217e2765,0x217e2cb0,0x2bb7addc,0x2ee9afdd,0x2d4daa4e,0x2ffcadba,0xa44ea5db,
0xa9f1a934,0x2fd4aee9,0x26a1ae5e,0xad962b05,0xafc92f1a,0x2f46aff4,0xaf802bb7,0xafe62f1a,0xafdd2d4d,0xadba2c07,0xaa4ea814,0xa5db2b05,
0xaaaa2f1a,0xafc92f02,0xafe62f02,0x2993a17e,0x2e3fa765,0xafa02fff,0xa17e2d72,0x2e3facb0,0x2e5eb000,0xad4d2eb5,0x2f91ac5d,0x2fedaf5a,
0x2ee9aff8,0x2ffcafaf,0x2d4da30e,0xa44ea17e,0xa5dbaaaa,0x2f6eafe6,0x2f6eafc9,0xac5d2993,0xafe62dba,0x2d72ae99,0x9cb6ac5d,0xaed02dba,
0xabb72f30,0x28d5ac07,0xafa02cd8,0xaff42f91,0xa9342e3f,0xae5e2f1a,0xaee92b5e,0x2b05a875,0x2dbaa765,0xac5d2d72,0xae992fff,0x2dbaacb0,
0x2f80afd4,0xa7652a4e,0x25152a4e,0x2f46ae99,0x217eacd8,0x230e1fd9,0x2fafad4d,0x2ff8afbc,0xa9f1a44e,0x26a1a934,0x2fd4adfe,0xad962cd8,
0xafe62e3f,0x9cb6a17e,0x2d72afa0,0xaed02e3f,0xad272f80,0xa8752515,0xa875a765,0xafa02f46,0x293425db,0xac072a4e,0xafbc2dba,0xaffc2fdd,
0x2f1aacb0,0x2bb7aaaa,0xaff42f80,0x2f1aaed0,0x2f30b000,0x2cd8ac5d,0xac072eb5,0x2f91af5a,0x25dbacd8,0x2dbaad4d,0x2a4e1fd9,0x2fddafbc,
0xad722875,0x2e7cae1f,0x2fc9ae1f,0x2fffaff4,0xafc92fdd,0xaf802f6e,0x2f46b000,0xafe62fdd,0xabb72e5e,0xafa02f91,0x28d5ad4d,0xaff42fed,
0x2934217e,0xafbc2faf,0xac07230e,0xaffc2ff8,0x2f5aad72,0xafd42fc9,0xafd42e7c,0xb0002fff,0x9cb69648,0xacb0a6a1,0xa765a6a1,0x2ddc2a4e,
0xa17e9fd9,0xaff4aee9,0xa875a814,0x2ff82f91,0xa44ea30e,0xadfeafa0,0xa934a8d5,0x2cd82f02,0xa5dba515,0x9648aaaa,0xa9f1a993,0xa5db2765,
0xa30e9cb6,0xad27a765,0xad27acb0,0x2faf2ddc,0xa814a5db,0xaffcaf5a,0xadfead96,0x2e5e2fdd,0xaa4ea934,0xac5daee9,0xaeb5ae5e,0x96482b05,
0xac32ab5e,0x2993a30e,0xaf46af02,0xae7cab5e,0xa5db9fd9,0xad96a814,0xaf5aaee9,0x2fdd2f91,0xaaaaa8d5,0xafc9afaf,0xafe6afaf,0x29932e1f,
0xad00ac32,0xa8d5addc,0xaff8afff,0xad00a515,0xae5eadba,0x2d4d26a1,0xaf91afd4,0xafedaf6e,0xa814a17e,0xadfea875,0xaffcaff4,0x2e5e2ff8,
0xac87aaaa,0xaf5aafe6,0xaf5aafc9,0xa6a12993,0xae7cad96,0x9cb6ac87,0xaddcaeb5,0xafc9ad96,0xafafaf30,0x2f1a2c07,0xab5eacd8,0xad00af91,
0xa934a30e,0xae5ea8d5,0xaee9afa0,0x2b052f02,0xad96ac32,0xaeb5afff,0xac87addc,0xad96a515,0xaf80aeb5,0x2765a9f1,0xa515a9f1,0xaf46afdd,
0xaff8afed,0x2ff42dfe,0x28751fd9,0x217eac07,0xaa4ea44e,0xaeb5a934,0xac5dadfe,0x96482cd8,0xae7cad00,0xaddcaff8,0x9cb6a8d5,0xafc9ad00,
0xaff8af80,0x2bb7a515,0x2bb72765,0xab5eaf46,0xaf30afdd,0x2fbc2f5a,0x2ee92d96,0x2dfe25db,0xab5ea515,0xaf02a993,0xa30eaaaa,0xab5e2765,
0xaf30adba,0xacd8afd4,0x2c0726a1,0xaf91af6e,0xafddafed,0x2d961fd9,0x2f5a2dfe,0x25dbac07,0xad72af02,0x2e7c2ff8,0x2fc92ff8,0x2fff2e3f,
0xac32a5db,0xaf46a9f1,0x29939648,0xae7ca5db,0xafafae5e,0xab5eaf91,0x2f1a2d4d,0xad00afed,0xaf30aff8,0x2ee92875,0x2fbc2ff4,0x2dfe217e,
0xa9f1ad72,0x2c5d2fc9,0x2c5d2e7c,0x2d962fff,0xaf80aa4e,0xafc9ac87,0xafe6ac87,0x2f462dba,0xa8d5af30,0x2f02a44e,0xa30eae5e,0xafa09fd9,
0x2fbc2bb7,0xa9342e1f,0x2ffc2d27,0x2c07ad00,0x26a12ed0,0xaa4eafff,0x16482ddc,0x26a12fe6,0xafafaaaa,0xafa0acb0,0xafa0aed0,0x2d002f80,
0xa44eaeb5,0x2f919648,0x2b05aa4e,0xafbcac5d,0x30002d4d,0xac872cd8,0x2e992fbc,0x2f6e9fd9,0xa5152d27,0x9cb6afaf,0xad72230e,0xac322d27,
0xafd4ab05,0xaf6eacd8,0xadbaafed,0x26a12ffc,0x1cb6ae1f,0x2fe6230e,0x2ed0230e,0xad72af1a,0x2faf2e7c,0xae1f2aaa,0x28d52f80,0x2faf2c32,
0xac0729f1,0x2934ae99,0xaffcac87,0xafbc9648,0xafedab5e,0xaf30ad00,0xa934afaf,0xa8142f1a,0x26a1ad72,0x30002765,0x30002cb0,0xa5dbafff,
0x2ed02f5a,0xaf4626a1,0xa9932c87,0x2cb02f5a,0xae3f1fd9,0x2d27acd8,0xae1fafbc,0xaf02ad4d,0xaffcabb7,0xaee9ad27,0x244eae1f,0xad4d2d00,
0x29f1acb0,0x2fdd2993,0x2eb52f46,0x29f1aed0,0x2d722fdd,0xafe69648,0xaed09648,0x9cb62fd4,0xafa0a814,0x2f02a934,0xa30eaf30,0xa8d5afed,
0xb000ac07,0xae99ad4d,0x2c87ab05,0xaf6e2814,0x2c32abb7,0x2f802b5e,0x2aaa2ff8,0x2e7cabb7,0x2b5e2fff,0xaff4a765,0xaff4acb0,0xad272d72,
0xaffcac5d,0x2fed9648,0x2cd8aa4e,0x2b05aeb5,0xaff8ac32,0xae3fad72,0x2f029cb6,0xaff8a515,0x2d4da9f1,0x2ee92c87,0xa44e2e99,0x2ffc1648,
0x26a12fbc,0xaf6eab05,0xadbaaf91,0xafd4244e,0xaf46ae3f,0x2fc928d5,0x2fe628d5,0x2f80a875,0xafe6ac5d,0xaddcad96,0x2fff29f1,0xaed0ac5d,
0x2e3fa814,0x2e1f2d4d,0xad272b05,0x2f022c07,0x9fd92f1a,0xae5ead00,0xa44eafaf,0xaf30ab5e,0xad96af80,0x2e992cb0,0x2e992ed0,0x2f5a2aaa,
0xad72adba,0xa515aeb5,0xac32aeb5,0x9cb62f6e,0x2d272dfe,0xad002fbc,0x2bb72ee9,0x2e1faf30,0xacd8ae3f,0x2ffcab5e,0xab05af1a,0xafed2875,
0x2c872e7c,0xadbaa993,0x2a4e2f46,0x2c872c32,0xad00addc,0xa17eaed0,0xa17eafe6,0xabb72fff,0x2c072e99,0xadfe2f6e,0x9fd93000,0x2fedac87,
0xa9f1af30,0x2fd4a814,0x26a1afed,0xad96a934,0x27652fa0,0xaaaaad00,0xa9932faf,0xa5152fa0,0xac87adfe,0x9648aee9,0x29f1afbc,0xae992f30,
0x29932f1a,0xaed02f02,0xacb02f02,0x2f46a17e,0xa30eafc9,0x2f1a9cb6,0x2e1faddc,0xa30eae7c,0xa44e3000,0x9fd9aeb5,0xaf302c5d,0xae5e2f5a,
0xac07ae1f,0x1fd9af02,0x2dfeae3f,0xafed2d27,0x25db2f80,0xaf6e2e7c,0xaf6e2c32,0x2c5d2aaa,0x2515b000,0x2ddc25db,0x2fffa6a1,0x2c32b000,
0xabb72f91,0x28d5afbc,0xafa0a44e,0xaff42b05,0xab05ae3f,0x244eaf1a,0x2fbcab5e,0xaf912875,0x16482fc9,0xafd42ddc,0xafdd1cb6,0x16482e7c,
0x2aaaafd4,0x2c322a4e,0x2e7c2a4e,0x2f80ae99,0xae1f2e5e,0x2d00affc,0xabb7adfe,0xad27a814,0xa9f1ae5e,0x26a1af30,0x2fd49fd9,0xad96a44e,
0xa5152ff4,0xafff2d27,0xaddcab5e,0xac322ff4,0x2d27af46,0x28752cb0,0x28752ed0,0x2fa0a993,0xaf912c87,0x2ee9af6e,0x2814b000,0x1fd9ae99,
0xa8d5ae7c,0x2875af46,0x2e3f2993,0xa8d5ac32,0xa9343000,0xafed2c5d,0xa814aeb5,0xaf302f5a,0x2e99ae5e,0x16482dfe,0xa9f12ffc,0x2c872814,
0xafff2875,0x2fe6ae1f,0x2ed0ae1f,0x2ddcaff4,0xa765ae99,0x2993af5a,0x2aaa2d96,0x2515ae99,0xabb72fed,0xafa02b05,0x28d5affc,0xaff42cd8,
0x2f91ad27,0xa8142f02,0xaee92e3f,0x9fd92e1f,0xaf5a9cb6,0x2fd4ac32,0x2fd4a515,0x3000ad72,0x2aaaaf6e,0x2ed0afdd,0x2cb0afdd,0xaf803000,
0xaf1a2934,0x2875acd8,0xae3f244e,0xab5e2dfe,0xac072faf,0xab05217e,0xad4d2ff8,0x2814230e,0x2eb5a765,0xaf6e2ddc,0x2dba9cb6,0x2eb5acb0,
0x2bb7af80,0x2f1aafe6,0x2f1aafc9,0xaff42f46,0xae5e26a1,0x2b05ad96,0xa934a9f1,0xaee92fd4,0xadba2ffc,0xa5dba44e,0xafdd2ee9,0xaa4e2d4d,
0x2cb0217e,0xaddc2bb7,0x1cb62d00,0x2765217e,0x2c5daf91,0x2f5aafed,0x3000ae5e,0xaeb52d4d,0xad72217e,0x2cb0ae3f,0x2765ae3f,0xafff2fa0,
0xaf022fe6,0x217ea993,0xaf1a2aaa,0xaf022fc9,0x28142a4e,0xab0525db,0xad4d2fdd,0xac072dba,0x2cd8afa0,0x2f91aff4,0x2f30abb7,0xac0728d5,
0xac5d9cb6,0x2dbaaed0,0x2dbaafe6,0xae992d72,0xafc92f6e,0x2993ac5d,0xaaaaa5db,0xafe62f6e,0xa30e2d4d,0xa17ea44e,0xaff82ee9,0xafaf2ffc,
0x2d4dafaf,0x2fbcaff8,0x2cd8a17e,0x9fd9a30e,0xaa4ea515,0x2e99af46,0x2fd4af80,0xaa4e2765,0xafff2e99,0x2cb0adba,0x2765adba,0xad722c5d,
0xab5e2ee9,0x2875ab05,0xae3f2934,0xaf1a2e5e,0x2dbaafbc,0x2fddaffc,0x25db2934,0x2a4eac07,0xa765a875,0x2f46afa0,0x2f80ad27,0x2515a875,
0xafa02d72,0x2e3faed0,0x2e3fafe6,0xa17e9cb6,0xadfe2fd4,0x2cd8ad96,0xa44ea9f1,0xa93426a1,0x2e1fafc9,0x2ff4afff,0xa8752d72,0x2e1fae7c,
0x9fd9aa4e,0x2fbcafdd,0x2cd8a5db,0x2d4dadba,0xaeb52c07,0x2f5aaf91,0x3000af30,0x2c5dacd8,0xaf802ff4,0x2ed0af1a,0x2cb0af1a,0x2aaaabb7,
0x2e7cafd4,0x2fffb000,0xad722f5a,0x2fc9afd4,0x230eac07,0x2ff8affc,0x217e2934,0x2fafafbc,0xad4d28d5,0x2fedaff4,0x2e5eabb7,0x2f91afa0,
0xb0002f46,0x2fddafe6,0x2fddafc9,0x2f6eaf80,0xaaaaaa4e,0xaed0ac87,0xacb0ac87,0x2f802dba,0xab5eab05,0xafafafed,0xad00acd8,0x2f1a2ffc,
0xac07abb7,0xab05ae1f,0xad4dad27,0x28142d00,0xac5dac32,0x29f19cb6,0xad96ad72,0xac5da515,0xafafaf80,0xafa0afe6,0xafa0afc9,0x2d002f46,
0xafedafd4,0xa934adba,0xaf30af6e,0xa81426a1,0xb000affc,0x2c87244e,0xae99aee9,0xaf6ead4d,0xafe6aff8,0x2fff2f02,0xaddcae3f,0xaed0aff8,
0xaeb5af30,0xaa4eae5e,0x9648a44e,0xac5d9fd9,0xad72ae1f,0x2cb0230e,0x2765230e,0xafffaf1a,0xabb7acb0,0x2ff82f46,0x2b5e2993,0xabb7aed0,
0xa814a9f1,0x2b052e99,0x2d4d2c87,0x2c071648,0xa44ea8d5,0x2b05a30e,0x2f912f02,0xafbcafa0,0x26a11cb6,0x30002ed0,0x30002fe6,0xa5dbad72,
0x2c3229f1,0x2aaa2eb5,0x2f802fdd,0x2e7c29f1,0x2e3f2d4d,0xad27a44e,0x2e1f2ee9,0x2f022ffc,0x2d4d2bb7,0x2fbc2d27,0x2cd82e1f,0x9fd9ad00,
0x2f5a2e7c,0x2c872f80,0x26a12aaa,0x2f5a2c32,0x2fff2fdd,0xacb09648,0xa7659648,0x2d722fd4,0x2f1a2fbc,0xafafaf91,0xad00ab05,0xab5e244e,
0x30002fbc,0x2e992ffc,0xac87a934,0x2f6e2c07,0x2ed02faf,0xa99328d5,0xaf46ae1f,0x2cb02faf,0x2b5e2d72,0xaff4aed0,0xaff4afe6,0xad279cb6,
0x9fd926a1,0xa44eadba,0xae5eaf6e,0xaf30afd4,0x2d272ed0,0x230e2ddc,0xafafafff,0x2d272fe6,0x1fd929f1,0xafbcac87,0xacd8ae99,0xad4d9648,
0xac5da814,0xaa4eaf30,0x9648a934,0xaeb5afed,0xaf80ae3f,0x2ed028d5,0x2cb028d5,0x2aaaa875,0xa51526a1,0xad721648,0x9cb6aa4e,0xac3226a1,
0xae3fac07,0xae1faffc,0x2d272934,0xaf02afbc,0xaffcafa0,0x2cd8a30e,0x2fed2f02,0x2b05a8d5,0xad96af46,0x2e992fe6,0x2e992fc9,0x2f5a2f80,
0xafffadba,0xae7caeb5,0xafc9aeb5,0x2d722f6e,0x217ead4d,0x2ff42814,0x2875ac07,0xaff8ab05,0x2fed2e3f,0xad4d2b5e,0x2f912f1a,0x2e5ea875,
0xa5db2cb0,0x9648af80,0xa9f12aaa,0xa5db2ed0,0xad00afff,0xa17eafc9,0xa17eae7c,0xabb72d72,0x2ee925db,0x2d4d2f5a,0x2ffc2d96,0xa44eafdd,
0x29f12f91,0xafd4ac07,0xa6a12cd8,0x2d962f30,0xafc9ab5e,0x2f46a30e,0xaf80af02,0xafe6ab5e,0x25dbad4d,0x2d96ac07,0x2f5a2814,0xafddab05,
0x2f462f1a,0xa7652f02,0x25152f02,0x2f80a17e,0xad002765,0xa8d5afff,0xaff8ad72,0xad002cb0,0xacd8b000,0x2dfe2eb5,0x2934ac5d,0x244eaf5a,
0x2ee9217e,0x2ffc2875,0x2d4d2ff4,0xa44eaff8,0x25db2f46,0xaf6e2515,0xaf6ea765,0x2c5d2f80,0xafe6ad96,0x2d72ac87,0x9cb6aeb5,0xaed0ad96,
0x2bb7ab05,0xa8d52ee9,0x2fa02e5e,0x2ff42934,0x2f912e3f,0x2cd82f1a,0xac072b5e,0x2f30a875,0xad962765,0xaeb5ad72,0xac87afff,0xad962cb0,
0xa993afd4,0x2fc92a4e,0x2fe62a4e,0x2aaaae99,0x2ff82cd8,0xaff49fd9,0xa8752d4d,0xa17e2fbc,0x29f12fed,0xa6a12f91,0xafd4ad4d,0x2d962e5e,
0xafe6ad00,0x9cb6aff8,0x2d72a8d5,0xaed0ad00,0x2d27a993,0x28752fe6,0x28752fc9,0x2fa02aaa,0x29342fdd,0xac07af5a,0xafbcad96,0xaffca5db,
0xab5e2cb0,0xaf022aaa,0xa30eaf80,0xab5e2ed0,0xab05b000,0x2e5eac5d,0x2ee92eb5,0x2934af5a,0x2fdd2cd8,0xad962d4d,0xaf5a9fd9,0xa5db2fbc,
0xaddc2875,0x2cb0ae1f,0x2765ae1f,0x1cb6aff4,0xafc9a5db,0xaf80a9f1,0x2f469648,0xafe6a5db,0x2bb7acd8,0x2fa02934,0xa8d52dfe,0x2ff4244e,
0x29342ff8,0xafbca875,0xac07aff4,0xaffca17e,0xaf5aaddc,0x2fd42765,0x2fd42cb0,0x30001cb6,0xa993af6e,0x2765afdd,0xa515afdd,0xaaaa3000,
0x28d52f91,0xaf022e5e,0x230e2fed,0x2fa0ad4d,0xa814afaf,0x2f91a17e,0x9fd9aff8,0xaee9a30e,0x26a12fc9,0xaa4ead72,0x16482fff,0x26a12e7c,
0x2bb7af46,0x2f1aae7c,0x2f1aac32,0xaff42993,0xacd82eb5,0xaf301648,0xaf912a4e,0x2c072c5d,0x2dbaadfe,0x25db2e5e,0x2fdda814,0x2a4eaffc,
0xae7c2d27,0x2d72afaf,0xafff230e,0xafc92d27,0x2fd4a934,0x2f6ea44e,0x2dba2cd8,0xa6a1adfe,0xafff217e,0xa515ae3f,0xac32ae3f,0xaddc2fa0,
0x2faf2515,0xae1f2f80,0x28d52f46,0x2fafa765,0xaee9aa4e,0x2f91a5db,0x9fd9afdd,0xa814adba,0x2e5e2b5e,0x29342d00,0xab052faf,0x2ee9af1a,
0xac5daddc,0x2dbaafc9,0x2dbaae7c,0xae999cb6,0x27652f5a,0xaf8026a1,0xaf462c87,0xa5152f5a,0x230eaffc,0x217e2e5e,0x2ff8a814,0x2fafadfe,
0x1fd92faf,0xac072ff8,0xafed217e,0x2dfe230e,0x29f1afe6,0x2fddaaaa,0x2eb52993,0x29f1afc9,0xaddc2e99,0xa515adba,0xac32adba,0xafff2c5d,
0x2fa0ac07,0xaf022f30,0x230e2f91,0x28d52cd8,0xadba2ee9,0xafdd2dfe,0xa5dbaf30,0xaa4e2fbc,0x2fc9abb7,0x2aaa2b5e,0xa9932ff8,0x2fe6abb7,
0xafa09cb6,0x2e3fafc9,0x2e3fae7c,0xa17eaddc,0x2d4d2c5d,0xae5e1648,0xafed2a4e,0xaf912eb5,0xaff82765,0xae3f1cb6,0x2f02addc,0xaff82cb0,
0x2dfe2a4e,0xac072fdd,0xafed25db,0x1fd92dba,0xa6a1aee9,0x2f6ea934,0x2dba2b05,0x2fd4ae5e,0xaaaa2ff4,0x2765af1a,0xa515af1a,0xa993abb7,
0xacb0ac5d,0x9cb6ad96,0x2ddc29f1,0xa765ac5d,0xa30e2fbc,0xaff82dfe,0xa17eaf30,0xafaf2ee9,0x2dfeaf1a,0x244e2d00,0xacd82faf,0x29342b5e,
0xb0002993,0x2fddae7c,0x2fddac32,0x2f6eaf46,0x2ddcb000,0x2fe6afd4,0x2ed0afd4,0xafff2f5a,0xad279fd9,0x2d00aee9,0xabb7a814,0xae1f2f91,
0xae5e2ff4,0x9fd9a8d5,0xaf302fa0,0xa44e2bb7,0x2c872515,0xadba2aaa,0x2a4e2993,0x2c87a765,0x2ff4ad72,0x2e1fac32,0x2e1fa515,0xa8759cb6,
0x2814ae99,0x2ffcaf6e,0x2dfeb000,0xae5e2c87,0xaf5a2b05,0x2eb5afbc,0xac5da44e,0xb0002f91,0xac322fa0,0x2993ad00,0xaf462faf,0xae7c2fa0,
0x2c871fd9,0x16482814,0xa9f12ee9,0x2e99af91,0x2f80afa0,0x2c32a875,0x2e7ca875,0x2aaaad27,0xa30eac32,0x2f1aaddc,0x2e1fafff,0xa30ea515,
0xafed2d96,0x2ffcafd4,0xab05a6a1,0xacd829f1,0xa8142e1f,0xadfe2f02,0xaffc2e3f,0x2e5ead27,0x2e99a993,0xaa4e2cb0,0xaa4e2ed0,0x2fd4af46,
0x2e7cb000,0x1cb625db,0x2ddca6a1,0x2fc9b000,0xa875a934,0x2b5ea814,0x2f1aafed,0x2e3faf30,0xaf302ff4,0xafed2fa0,0xa814a8d5,0xa9342bb7,
0x16482c32,0xafd42fff,0xafdd2ddc,0x16482515,0x2f46ac5d,0xaed02f6e,0xacb02f6e,0x2993a5db,0x2e1fafed,0xad002dfe,0x2bb71fd9,0x2d27ac07,
0xaf5a2cd8,0xac5d2b05,0x2eb5affc,0xb0002fed,0xae7c2ff4,0xaddc2d27,0x9cb6ab5e,0xafc92ff4,0x217e2aaa,0xaf022e7c,0xaf022c32,0xaf1a2f80,
0x2f30ac87,0xafbc2f6e,0xaee93000,0xadfe2e99,0xa8d5a515,0x2875a993,0x2e3faaaa,0xa8d52765,0xaf912d96,0x244ea6a1,0x2fbcafd4,0xab0529f1,
0xae992fed,0x96489fd9,0x29f1adfe,0xac872c07,0x9cb62bb7,0xa515217e,0xac32217e,0xad722d00,0x2c32ae99,0x2f46af5a,0xa9932d96,0x2e7cae99,
0xa875a44e,0x2f1aaf30,0x2b5e9fd9,0x2e3fae5e,0xaf302d27,0x2ee9af02,0x2fbcae3f,0x2dfeae1f,0xaf6e2fff,0x2eb5aed0,0x2eb5afe6,0x2dbaaddc,
0xaddcadba,0xafe6aeb5,0xaed0aeb5,0x2fff2f6e,0xae1fadfe,0xae3fafbc,0xaf02aee9,0x2d272f30,0xae5eae3f,0x9fd9ab5e,0xaf30af1a,0xa44e2875,
0xae99ae7c,0x2d962993,0xaf5aaf46,0xae99ac32,0xad00ad72,0xa17eac32,0xa17ea515,0xabb79cb6,0xac07ac87,0x2dfe29f1,0x1fd99648,0xafedae99,
0xa9f1ab05,0x2fd42fbc,0x26a1244e,0xad96af91,0xa765a8d5,0x2aaa2e3f,0x29932875,0x2515a8d5,0x2e992dfe,0x30002ee9,0x2f6e2fbc,0xac87af30,
0x2f802f1a,0x2c322f02,0x2e7c2f02,0x2aaaa17e,0x2ff42fc9,0xab5e1cb6,0x2d272ddc,0x2ff42e7c,0x2fed3000,0xaffcaeb5,0x2b052c5d,0x2cd82f5a,
0x2c072d27,0x9fd92bb7,0xadfead00,0x2fed2e1f,0x25db2993,0xaf6eacb0,0xaf6eaed0,0x2c5d2f46,0xa5151648,0xaddcafdd,0xafffafd4,0xac321648,
0xabb7a934,0x28d5a814,0xafa0afed,0xaff4af30,0xaf30ae3f,0xafedaf1a,0xa814ab5e,0xa9342875,0xb000afc9,0xa6a1addc,0x25db9cb6,0xb000ae7c,
0xaf46afd4,0x2ed02a4e,0x2cb02a4e,0xa993ae99,0xad27ae5e,0x2e3f2ffc,0x2f022dfe,0x2e1f2814,0xa9f1acd8,0x26a1ab05,0x2fd42ffc,0xad96afed,
0x2515a30e,0x2fff2e1f,0x2ddc2f1a,0x2c32a30e,0x2d272aaa,0x28752e7c,0x28752c32,0x2fa02f80,0x2f912e99,0xaee9a9f1,0xa8141648,0x9fd92c87,
0x2fa02e7c,0x2faf2f46,0xad00a993,0x2fa02c32,0x2f913000,0xa44e2c5d,0xafbcaeb5,0x2b052f5a,0x2c872e5e,0xb000adfe,0xaf6eaffc,0xae99a814,
0x9cb62875,0xa515ae1f,0xac32ae1f,0xad72aff4,0x27652c87,0xa9932a4e,0xaaaaadba,0xa5152c87,0xabb7a44e,0xafa0af30,0x28d59fd9,0xaff4ae5e,
0xaf91ae1f,0x2814abb7,0x2ee92d00,0x1fd9ad27,0xaf5aafff,0x2fd42ed0,0x2fd42fe6,0x30002ddc,0xaf46af6e,0xac32afdd,0xae7cafdd,0x29933000,
0x2b5ea934,0x2faf2cd8,0x2d00a44e,0xaf1aadfe,0x2ee92faf,0xaf30217e,0x2dfe2ff8,0x2fbc230e,0xac5d2765,0x29f1addc,0xad961cb6,0xac5d2cb0,
0x2bb7a993,0x2f1aa515,0x2f1a2765,0xaff4aaaa,0x2e5e2fd4,0xab052dba,0x29342f6e,0x2ee9a6a1,0xadba1fd9,0xa5dbafed,0xafddac07,0xaa4e2dfe,
0xacb0aff8,0x2ddc2f02,0x9cb6ae3f,0xa765aff8,0x2eb52f91,0x2a4e2fed,0x16482e5e,0x2c5dad4d,0xaddc217e,0xae7cae3f,0xafc9ae3f,0x9cb62fa0,
0xabb7afe6,0x2ff82993,0x2b5eaaaa,0xabb7afc9,0x2fbc2a4e,0xaf3025db,0x2dfe2fdd,0x2ee92dba,0xacd828d5,0xaf91230e,0xaf30af02,0x2c072fa0,
0xac5dafff,0x2dbaac32,0x2dbaa515,0xae99addc,0x2fc929f1,0xa9932eb5,0x2aaa2fdd,0x2fe629f1,0xa30e2dfe,0xa17eafed,0xaff8ac07,0xafaf1fd9,
0xadfeafaf,0xa814aff8,0x2e5ea17e,0xaffca30e,0x2f5a2515,0x2c872f46,0x26a12f80,0x2f5aa765,0x9cb62e99,0xae7cadba,0xafc9adba,0xaddc2c5d,
0xaf1aaee9,0x2faf2b05,0x2d00a934,0x2b5eae5e,0x2dbaa814,0x2fdd9fd9,0x25db2f91,0x2a4eaee9,0x27652faf,0xaf4628d5,0xaf80ae1f,0xa5152faf,
0xafa0addc,0x2e3fac32,0x2e3fa515,0xa17eafff,0x2dfea6a1,0xacd82dba,0x244e2f6e,0x29342fd4,0x2d272fc9,0x230e2fff,0xafafad72,0x2d272e7c,
0xaffcaa4e,0xa814afdd,0x2e5ea5db,0xadfeadba,0x2c5dac07,0x2a4e2f91,0x16482f30,0x2eb52cd8,0x29932ff4,0xac32af1a,0xae7caf1a,0xaf46abb7,
0xae7c26a1,0xafff1648,0x2d72aa4e,0xafc926a1,0x230eaee9,0x2ff89fd9,0x217e2f91,0x2fafa814,0x2d4d2fa0,0xafed230e,0xae5eaf02,0xaf9128d5,
0xb000aaaa,0x2fdda515,0x2fdd2765,0x2f6ea993,0x1cb6b000,0x2cb0afd4,0x2765afd4,0xaddc2f5a,0xa17e2ffc,0xaff42c07,0xa8752fbc,0x2ff8a934,
0x244eaff4,0x2dfe28d5,0x2934afa0,0xacd8abb7,0xa5db2fe6,0x9648af46,0xa9f12f80,0xa5db2fc9,0x2ff41cb6,0x2e1f2765,0x2e1f2cb0,0xa875addc,
0xafbca5db,0x1fd9af5a,0xad4dad96,0xacd82fdd,0x2f5a2934,0xaeb52ee9,0x2c5d2e5e,0x3000ab05,0xaed0ab5e,0x2f80a30e,0xaaaaaf02,0xacb0ab5e,
0xa5db2ffc,0xad962fbc,0xaf5a2c07,0x2fdda934,0x2aaaafa0,0x2fc9a875,0x2fe6a875,0xa993ad27,0xad002ed0,0xa8d5ad72,0xaff81cb6,0xad002fe6,
0x2e5ead96,0xad4d2fd4,0x2f9126a1,0x2feda9f1,0xafbca17e,0xad4da875,0x1fd9aff4,0xacd82ff8,0x2e992aaa,0xaa4e2fe6,0xaa4e2fc9,0x2fd4a993,
0xacb0ad96,0x2fffac87,0x2d72aeb5,0xa765ad96,0x28752f30,0xab5eac07,0xaf1a2cd8,0xae3f2f91,0x2934aff4,0x2e5eafa0,0x2ee928d5,0xab05abb7,
0xad962ed0,0xaeb51cb6,0xac87ad72,0xad962fe6,0x2f80ac5d,0xa7652f6e,0x25152f6e,0x2f46a5db,0xaff8244e,0x2ff4ad4d,0x2875affc,0x217eaee9,
0x2f5a244e,0x2c5d2934,0xaeb52dfe,0x3000acd8,0xacb0ad00,0x2d72aff8,0x2fffa8d5,0xa765ad00,0x217e2f80,0xaf022515,0xaf02a765,0xaf1a2f46,
0x2b05afdd,0xa8142f5a,0x2c072d96,0x2d4d25db,0xab5e2fe6,0xaf022f80,0xa30eaf46,0xab5e2fc9,0x2f30ad96,0x2cd826a1,0xac072fd4,0x2f91a9f1,
0xafdd244e,0x2d96affc,0x2f5aad4d,0x25dbaee9,0x2d722bb7,0xae7c217e,0xafc9217e,0xafff2d00,0xaed0a5db,0xaaaaa9f1,0x2f809648,0xacb0a5db,
0x28752e5e,0xaf1a2f91,0xab5ead4d,0xae3f2fed,0x2b05aff8,0x2c072875,0xa8142ff4,0x2d4d217e,0xaf6e2d72,0x2eb5afc9,0x2eb5ae7c,0x2dbaafff,
0x2f80af5a,0x2fc9ae99,0x2fe6ae99,0xaf462d96,0xa8d5ab05,0x2f02afed,0xa30eacd8,0xafa02ffc,0xafbc2f02,0x2934ad27,0xaffc2e1f,0xac072e3f,
0x26a12c32,0xaa4e1cb6,0x16482d72,0x26a12515,0x28752aaa,0xa8d52cb0,0xa8d52ed0,0x2e3faf80,0x2fedaeb5,0x29349648,0x2f30aa4e,0x2814ac5d,
0x1648ad4d,0x2e99acd8,0x2c87afbc,0xa9f11fd9,0xafe62d27,0x2fffafaf,0xaddc230e,0xaed02d27,0xafd42f30,0xaf6e2e5e,0xadba244e,0x26a11fd9,
0x9cb62d27,0xafe62ff4,0xaed02ff4,0x2d72ab5e,0x2fafacb0,0xae1f2f46,0x28d52993,0x2fafaed0,0x2c07af6e,0xa9342c87,0x2ffcae99,0x2fbcb000,
0xa44eab5e,0x2b05ad00,0x2f91afaf,0xafbc2f1a,0xafd42d72,0x1648a765,0x1648acb0,0xafdd2fff,0xac322f5a,0xaaaa26a1,0xaf802c87,0xae7c2f5a,
0x2d009fd9,0xae1f2cd8,0xad272fbc,0xabb72d4d,0x2ffcaf02,0x2ee9ae1f,0xa44e2d27,0x2d4dae3f,0x29f1ae7c,0x2fddaf80,0x2eb5aaaa,0x29f1ac32,
0xad7225db,0x2fe6b000,0x2ed0b000,0x1cb6a6a1,0xafa02fbc,0x2f02af91,0xa30eab05,0xa8d5244e,0x96482c07,0xac872d4d,0xae992b05,0x29f1a814,
0x2ed0abb7,0xa9932b5e,0xaf462ff8,0x2cb0abb7,0x2f1aafff,0xa30e2765,0xa30e2cb0,0x2e1fad72,0x1fd9ac5d,0x244e9648,0x2e5eaa4e,0x2f30aeb5,
0xaff82ed0,0xae3f2ddc,0x2f02afff,0xaff82fe6,0xad4d2f6e,0xaee92e99,0x244eac87,0xaffc3000,0x26a12814,0xaf6e2f30,0xadba2934,0xafd42fed,
0x2f46ad00,0xafc92fa0,0xafe62fa0,0xaf802faf,0x2515ac5d,0x2d72ad96,0x1cb629f1,0x2c32ac5d,0xad002814,0x2d27ad4d,0x2e1fab05,0x2bb7ac07,
0xaffc2f1a,0x2cd8ad00,0x2fedafaf,0x2b05ab5e,0xadba2f80,0x2c87acb0,0x2c87aed0,0x2a4eaaaa,0xaf80af6e,0xafc9afdd,0xafe6afdd,0x2f463000,
0xafa0af91,0xabb7ae5e,0xaff4afed,0x28d52d4d,0xafbcafaf,0x2934a17e,0xaffcaff8,0xac07a30e,0xafd4afc9,0x2f5a2d72,0xb000afff,0xafd4ae7c,
0x2bb72aaa,0x2f1a2cb0,0x2f1a2ed0,0xaff4af80,0x2cd82c5d,0x2f303000,0x2f912f5a,0xac07aeb5,0x2dba2d4d,0x25db2cd8,0x2fdd2fbc,0x2a4e9fd9,
0x2e7c2e1f,0xad72a875,0x2fff2ff4,0x2fc92e1f,0x26a12934,0xa9f1244e,0xad96acd8,0x2fd42dfe,0x9cb6217e,0xafe6ae3f,0xaed0ae3f,0x2d722fa0,
0xa875a515,0xad27af80,0xafa0af46,0xa8752765,0xac07aa4e,0x2934a5db,0xaffcafdd,0xafbcadba,0xae5eaf1a,0xa934ae3f,0x2b052875,0xaee9ab5e,
0xac5dad72,0x2dba2765,0x2dba2cb0,0xae99afff,0xa765aa4e,0x2f802fd4,0x2f462e99,0x2515aa4e,0x230e9fd9,0x217e2cd8,0x2ff82fbc,0x2faf2d4d,
0x2ffc2faf,0x2ee92ff8,0xa44e217e,0x2d4d230e,0x2f6e2fe6,0xa5db2aaa,0xac5da993,0x2f6e2fc9,0x2d722e99,0xafe6adba,0xaed0adba,0x9cb62c5d,
0x28d52c07,0xabb7af30,0xaff4af91,0xafa0acd8,0xadbaac07,0xafddad4d,0xa5dbab05,0xaa4e2814,0xafc9af02,0xaaaaaf1a,0x2993217e,0xafe6af02,
0xafa0afff,0x2e3f2765,0x2e3f2cb0,0xa17ead72,0xad4daeb5,0x2e5e3000,0x2fed2f5a,0x2f912c5d,0x217ea765,0x2d009cb6,0x2bb72ddc,0x217eacb0,
0x2d4d2a4e,0x2ee92fdd,0xa44e25db,0x2ffc2dba,0x2fd42ee9,0xa9f12934,0xad96ab05,0x26a12e5e,0x2f462ff4,0xafc9af1a,0xafe6af1a,0xaf80abb7,
0x2cb02eb5,0x1cb62dba,0xaddcaf6e,0x27652eb5,0xa30e2814,0xaff8ad4d,0xa17eab05,0xafafac07,0xadfeab5e,0xa44eae3f,0x2cd82875,0xa934af1a,
0xb000af80,0x2fdd2cb0,0x2fdd2ed0,0x2f6e2aaa,0xad72b000,0xa515afd4,0xac32afd4,0x9cb62f5a,0x2e1f1fd9,0x2e3f2ee9,0x2f022814,0xad27af91,
0x2cd82ff4,0xaffca8d5,0x2b052fa0,0x2fed2bb7,0xae99a515,0x2d96aaaa,0xaf5aa993,0xae992765,0x2ff42ddc,0x2e1f2ed0,0x2e1f2fe6,0xa875afff,
0xa8142c87,0xaffca9f1,0xadfe1648,0x2e5e2e99,0xaf5aaf30,0x2eb5a814,0xac5dafed,0xb000a934,0x2c32a8d5,0xa9932e3f,0x2f462875,0x2e7ca8d5,
0xae999fd9,0xb000a814,0xaf6eaee9,0x2c872f91,0xa993afa0,0x2ed0a875,0x2cb0a875,0xaf46ad27,0x2ff42c32,0xab5e2ddc,0x2d272fff,0x2ff42515,
0xa44e2d96,0x9fd9afd4,0xaf30a6a1,0xae5e29f1,0x2814ad27,0x2dfeabb7,0x2ffc2d00,0xae5eae1f,0x2e992f80,0xaa4e2e7c,0xaa4e2c32,0x2fd42aaa,
0xae7c1648,0x9cb6afdd,0xaddcafd4,0xafc91648,0xa875af91,0x2b5e2fbc,0x2f1a244e,0x2e3fab05,0x2b052ff4,0xa44e2fa0,0xafbca8d5,0x2f912bb7,
0xb000ac32,0xa6a1afff,0x25dbaddc,0xb000a515,0x2aaaac5d,0x2c322f6e,0x2e7c2f6e,0x2f80a5db,0x2d272fed,0xae3fadfe,0xaf029fd9,0xae1f2c07,
0xaf5aae5e,0xac5daf30,0x2eb59fd9,0xb000a44e,0x2e7ca30e,0x2ddc2e1f,0x1cb62f1a,0x2fc9a30e,0x217e2f46,0xaf02acb0,0xaf02aed0,0xaf1a2993,
0xaf30ae99,0x2fbc29f1,0x2ee99648,0x2dfeac87,0x2fa02515,0x2faf2993,0xad002aaa,0x2fa0a765,0xa9342d96,0xafeda6a1,0xa814afd4,0xaf3029f1,
0xac87afed,0x30001fd9,0x2f6e2dfe,0x2e99ac07,0x2fff2bb7,0xafe6217e,0xaed0217e,0xaddc2d00,0xac322c87,0xaf462a4e,0x2993adba,0xae7c2c87,
0xa875afed,0x2f1aab05,0x2b5e2ffc,0x2e3facd8,0x2f302e1f,0xaee92bb7,0xafbcad00,0xadfe2d27,0xaf6e9cb6,0x2eb5ac32,0x2eb5a515,0x2dbaad72,
0x2aaaaf5a,0x2ed0ae99,0x2cb0ae99,0xaf802d96,0xab5e2f30,0xafaf244e,0xad002e5e,0x2f1a1fd9,0x2c07af02,0x2b052d27,0x2d4dae1f,0xa814ae3f,
0xac5d2ed0,0x29f1afff,0xad962ddc,0xac5d2fe6,0x28752f80,0xa8d52fe6,0xa8d52fc9,0x2e3faf46,0xa44eafd4,0x2f91adba,0x2b05af6e,0xafbc26a1,
0x96482ffc,0xae99a44e,0xac872ee9,0x29f12d4d,0x2515aff8,0x1cb62f02,0x2d72ae3f,0x2c32aff8,0xaeb5ab05,0xaa4eacd8,0x9648afed,0xac5d2ffc,
0x2d722d27,0xacb02ff4,0xa7652ff4,0x2fffab5e,0xabb7ae7c,0x2ff8aaaa,0x2b5eaf80,0xabb7ac32,0x28142f6e,0xab05ac87,0xad4d2e99,0xac073000,
0x2feda8d5,0x2f30a30e,0x29342f02,0x2814afa0,0xafd49cb6,0x1648aed0,0x1648afe6,0xafdd2d72,0x2ed029f1,0xaf462eb5,0xa9932fdd,0x2cb029f1,
0xad00ad4d,0x2e1f244e,0x2d27aee9,0x2bb7affc,0xad4d2f02,0xafbc2e1f,0xacd8ad27,0x1fd92e3f,0x2f5aacb0,0x2c872993,0x26a12f46,0x2f5aaed0,
0xafff25db,0x2cb0b000,0x2765b000,0xad72a6a1,0x2f1a2814,0xafaf2934,0xad002f30,0xab5e2fed,0x1648afbc,0x2c87affc,0x2e992934,0xa9f1ac07,
0xac322faf,0xaf8028d5,0xaaaaae1f,0xae7c2faf,0x2f1aad72,0xa30e2ed0,0xa30e2fe6,0x2e1f1cb6,0xaffc26a1,0x2fedadba,0x2cd8af6e,0x2b05afd4,
0x2d272c32,0x230e2d72,0xafaf1cb6,0x2d272515,0x9fd9af6e,0x2fbcae99,0x2cd82c87,0x2d4db000,0xac5d2fbc,0xaa4eab05,0x9648af91,0xaeb5244e,
0x2f80ad00,0xaed02fa0,0xacb02fa0,0xaaaa2faf,0xafe626a1,0xaddc1648,0x2fffaa4e,0xaed026a1,0x2d002c07,0xad272ffc,0xae1fa934,0xabb72fbc,
0x1fd9afa0,0x2e5ea30e,0x244e2f02,0x2f30a8d5,0xadba2f46,0x2c87afe6,0x2c87afc9,0x2a4eaf80,0x2fffad96,0x2e7cac5d,0x2fc9ac5d,0xad7229f1,
0x217eadfe,0x2ff4afbc,0x2875aee9,0xaff82f30,0xafed2d00,0x2d4daf1a,0xaf912b5e,0xae5e2faf,0xa5db2e7c,0x9648a993,0xa9f12f46,0xa5db2c32,
0xae3f2fff,0xaff82fc9,0xaff82e7c,0x2f02ad72,0x2c0725db,0xadfe2f5a,0x9fd92d96,0x2fedafdd,0x2f6eaf91,0xa6a12c07,0x2fd4acd8,0x2dbaaf30,
0xa765ab5e,0x2aaaa30e,0x2993af02,0x2515ab5e,0x25dbadfe,0x2d96aee9,0x2f5aafbc,0xafdd2f30,0xaf462b5e,0x2765abb7,0xa515abb7,0xaf802ff8,
0xad002fc9,0xa8d51cb6,0xaff82ddc,0xad002e7c,0x2cd81648,0xadfe2c5d,0xa9342eb5,0xa44e2a4e,0x2c07217e,0x9fd92875,0xadfe2ff4,0x2fedaff8,
0x2fddaf46,0x29f1a515,0x29f12765,0x2eb5af80,0x2515ad96,0x2ddcac87,0x2fffaeb5,0x2c32ad96,0xaf022b05,0x2fa0aee9,0x28d5ae5e,0x230ea934,
0xaf912d00,0xacd82b5e,0x2c07af1a,0xaf302faf,0xad962fc9,0xaeb52ddc,0xac871cb6,0xad962e7c,0x299326a1,0xafc92f5a,0xafe62f5a,0xaaaa2c87,
0x2ff8ae5e,0xaff42ffc,0xa8752dfe,0xa17e2814,0x2f6eafed,0x2fd4af91,0xa6a12d4d,0x2dbaae5e,0x2515ad00,0x2fffaff8,0x2ddca8d5,0x2c32ad00,
0xae1f2993,0x2fafafe6,0x2fafafc9,0x28d5aaaa,0xaf912fdd,0x2ee9af5a,0x2814ad96,0x1fd9a5db,0xab5e2e7c,0xaf022f46,0xa30ea993,0xab5e2c32,
0x2b051648,0xae5e2eb5,0xaee92c5d,0xa9342a4e,0x2fddae5e,0xad962dfe,0xaf5a2ffc,0xa5db2814,0x2ddcafaf,0xacb02d27,0xa7652d27,0x9cb6230e,
0xa765a5db,0x2993a9f1,0x2aaa9648,0x2515a5db,0xaf022cd8,0x28d5a934,0x2fa0adfe,0x230ea44e,0xaf912ff8,0x2814a875,0x2ee9aff4,0x1fd9a17e,
0xaa4e2ddc,0x26a1a765,0x26a1acb0,0x16489cb6,0x9d7f9e49,0xaddcaeb3,0x12480000,0x22ad0000,0x9bdb9cb6,0xac2ead04,0x18b61648,0x290226ad,
0x98b69a49,0xa902aaaf,0x1bdb1a49,0x2c2e2aaf,0x92489648,0xa2ada6ad,0x1d7f1cb6,0x2ddc2d04,0xa420a4b7,0xae8daf7f,0x18b60000,0x23760000,
0xa1e4a312,0xacacad9c,0x1f121cb6,0x29992777,0x9f12a0b6,0xa999ab78,0x21e420b6,0x2cac2b78,0x98b69cb6,0xa376a777,0x24202312,0x2e8d2d9c,
0xa6e0a7db,0xaf3fb025,0x1bdb0000,0x24200000,0xa4e9a5e4,0xad2aae34,0x21e41fdb,0x2a312820,0xa1e4a3db,0xaa31ac21,0x24e923db,0x2d2a2c21,
0x9bdb9fdb,0xa420a820,0x26e025e4,0x2f3f2e34,0xa8d0a980,0xaff2b08c,0x1d7f0000,0x24840000,0xa6e0a820,0xada9aecd,0x2420217f,0x2ac82885,
0xa420a580,0xaac8ac86,0x26e02580,0x2da92c86,0x9d7fa17f,0xa484a885,0x28d02820,0x2ff22ecd,0xaa31ab13,0xb052b0f3,0x1f120000,0x24e90000,
0xa86ba94e,0xae28af65,0x254d2312,0x2b5f28e9,0xa54da712,0xab5faceb,0x286b2712,0x2e282ceb,0x9f12a312,0xa4e9a8e9,0x2a31294e,0x30522f65,
0xab91ac54,0xb0acb15a,0x20520000,0x254d0000,0xa967aa7c,0xaea7affe,0x267b2452,0x2bf6294e,0xa67ba852,0xabf6ad50,0x29672852,0x2ea72d50,
0xa052a452,0xa54da94e,0x2b912a7c,0x30ac2ffe,0xac79ad1e,0xb106b1c1,0x211b0000,0x25b20000,0xaa63abab,0xaf26b04c,0x27a9251b,0x2c4729b3,
0xa7a9a91c,0xac47adb6,0x2a63291c,0x2f262db6,0xa11ba51b,0xa5b2a9b3,0x2c792bab,0x3106304c,0xad2aade8,0xb160b229,0x21e40000,0x26170000,
0xab5fac6d,0xafa5b099,0x286b25e4,0x2c932a17,0xa86ba9e5,0xac93ae1b,0x2b5f29e5,0x2fa52e1b,0xa1e4a5e4,0xa617aa17,0x2d2a2c6d,0x31603099,
0xb1bbb292,0xb44fb4f6,0x267b0000,0x28d00000,0xb012b0e6,0xb216b357,0x2cde2a7c,0x2f3f2cd2,0xacdeae80,0xaf3fb0d9,0x30122e80,0x321630d9,
0xa67baa7c,0xa8d0acd2,0x31bb30e6,0x344f3357,0xb216b2fb,0xb47eb52d,0x26e00000,0x29020000,0xb052b133,0xb257b3a7,0x2d2a2ae1,0x2f8c2d04,
0xad2aaee6,0xaf8cb10c,0x30522ee6,0x3257310c,0xa6e0aae1,0xa902ad04,0x32163133,0x347e33a7,0xb271b364,0xb4aeb565,0x27440000,0x29350000,
0xb092b181,0xb298b3f7,0x2d762b46,0x2fd82d37,0xad76af4c,0xafd8b140,0x30922f4c,0x32983140,0xa744ab46,0xa935ad37,0x32713181,0x34ae33f7,
0xb2cdb3cf,0xb4deb59d,0x27a90000,0x29670000,0xb0d2b1ce,0xb2dab423,0x2dc22bab,0x30122d6a,0xadc2afb2,0xb012b174,0x30d22fb2,0x32da3174,
0xa7a9abab,0xa967ad6a,0x32cd31ce,0x34de3423,0xb329b41d,0xb50eb5d6,0x28070000,0x29990000,0xb113b21c,0xb31cb44c,0x2e0e2c08,0x30392d9c,
0xae0eb00c,0xb039b1a7,0x3113300c,0x331c31a7,0xa807ac08,0xa999ad9c,0x3329321c,0x350e344c,0xb386b453,0xb53fb60f,0x28390000,0x29cc0000,
0xb153b26b,0xb35eb474,0x2e5a2c3a,0x305f2dcf,0xae5ab03f,0xb05fb1db,0x3153303f,0x335e31db,0xa839ac3a,0xa9ccadcf,0x3386326b,0x353f3474,
0xb3e3b489,0xb570b649,0x286b0000,0x29fe0000,0xb194b2b9,0xb3a0b49d,0x2ea72c6d,0x30852e02,0xaea7b072,0xb085b20f,0x31943072,0x33a0320f,
0xa86bac6d,0xa9feae02,0x33e332b9,0x3570349d,0xb420b4bf,0xb5a1b683,0x289e0000,0x2a310000,0xb1d5b308,0xb3e3b4c6,0x2ef32c9f,0x30ac2e34,
0xaef3b0a5,0xb0acb243,0x31d530a5,0x33e33243,0xa89eac9f,0xaa31ae34,0x34203308,0x35a134c6,0xb5d2b6be,0xb76fb857,0x2a630000,0x2bf60000,
0xb413b4ef,0xb523b642,0x30d22e67,0x32092ffe,0xb0d2b278,0xb209b40f,0x34133278,0x3523340f,0xaa63ae67,0xabf6affe,0x35d234ef,0x376f3642,
0xb604b6fa,0xb7a5b878,0x2a950000,0x2c140000,0xb434b519,0xb546b66d,0x30f92e9a,0x32303019,0xb0f9b2ac,0xb230b42a,0x343432ac,0x3546342a,
0xaa95ae9a,0xac14b019,0x36043519,0x37a5366d,0xb637b736,0xb7dbb899,0x2ac80000,0x2c2e0000,0xb456b542,0xb569b699,0x31202ecd,0x32573032,
0xb120b2e1,0xb257b445,0x345632e1,0x35693445,0xaac8aecd,0xac2eb032,0x36373542,0x37db3699,0xb66ab773,0xb809b8bb,0x2afa0000,0x2c470000,
0xb478b56c,0xb58cb6c6,0x31462f00,0x327e304c,0xb146b315,0xb27eb460,0x34783315,0x358c3460,0xaafaaf00,0xac47b04c,0x366a356c,0x380936c6,
0xb69db7b0,0xb825b8dd,0x2b2d0000,0x2c600000,0xb49ab596,0xb5afb6f2,0x316d2f32,0x32a53065,0xb16db34a,0xb2a5b47b,0x349a334a,0x35af347b,
0xab2daf32,0xac60b065,0x369d3596,0x382536f2,0xb6d1b7ee,0xb841b8ff,0x2b5f0000,0x2c790000,0xb4bcb5c1,0xb5d2b71f,0x31942f65,0x32cd307f,
0xb194b37f,0xb2cdb496,0x34bc337f,0x35d23496,0xab5faf65,0xac79b07f,0x36d135c1,0x3841371f,0xb705b817,0xb85db923,0x2b910000,0x2c930000,
0xb4deb5eb,0xb5f6b74d,0x31bb2f98,0x32f43099,0xb1bbb3b4,0xb2f4b4b1,0x34de33b4,0x35f634b1,0xab91af98,0xac93b099,0x370535eb,0x385d374d,
0xb73ab837,0xb87ab946,0x2bc40000,0x2cac0000,0xb500b616,0xb61ab77a,0x31e22fcb,0x331c30b2,0xb1e2b3e9,0xb31cb4cd,0x350033e9,0x361a34cd,
0xabc4afcb,0xacacb0b2,0x373a3616,0x387a377a,0xb897b96b,0xb98dbaa6,0x2cc50000,0x2d900000,0xb63eb7a8,0xb767b895,0x334330cc,0x3442319a,
0xb343b4e8,0xb442b5c8,0x363e34e8,0x376735c8,0xacc5b0cc,0xad90b19a,0x389737a8,0x398d3895,0xb8b4b990,0xb9aebad1,0x2cde0000,0x2da90000,
0xb662b7d7,0xb78db8ae,0x336b30e6,0x345631b4,0xb36bb504,0xb456b5e4,0x36623504,0x378d35e4,0xacdeb0e6,0xada9b1b4,0x38b437d7,0x39ae38ae,
0xb8d2b9b5,0xb9cfbafd,0x2cf80000,0x2dc20000,0xb687b803,0xb7b4b8c7,0x339330ff,0x346a31ce,0xb393b51f,0xb46ab601,0x3687351f,0x37b43601,
0xacf8b0ff,0xadc2b1ce,0x38d23803,0x39cf38c7,0xb8f0b9dc,0xb9f1bb29,0x2d110000,0x2ddc0000,0xb6acb81b,0xb7dbb8e1,0x33bb3119,0x347e31e8,
0xb3bbb53b,0xb47eb61e,0x36ac353b,0x37db361e,0xad11b119,0xaddcb1e8,0x38f0381b,0x39f138e1,0xb90fba02,0xba14bb57,0x2d2a0000,0x2df50000,
0xb6d1b833,0xb801b8fb,0x33e33133,0x34933202,0xb3e3b557,0xb493b63a,0x36d13557,0x3801363a,0xad2ab133,0xadf5b202,0x390f3833,0x3a1438fb,
0xb92eba2a,0xba37bb86,0x2d440000,0x2e0e0000,0xb6f6b84b,0xb815b915,0x3405314d,0x34a7321c,0xb405b573,0xb4a7b657,0x36f63573,0x38153657,
0xad44b14d,0xae0eb21c,0x392e384b,0x3a373915,0xb94dba53,0xba5abbb6,0x2d5d0000,0x2e280000,0xb71bb863,0xb829b930,0x34193167,0x34bc3236,
0xb419b58f,0xb4bcb675,0x371b358f,0x38293675,0xad5db167,0xae28b236,0x394d3863,0x3a5a3930,0xb96dba7c,0xba7ebbe7,0x2d760000,0x2e410000,
0xb741b87c,0xb83db94b,0x342e3181,0x34d03250,0xb42eb5ab,0xb4d0b692,0x374135ab,0x383d3692,0xad76b181,0xae41b250,0x396d387c,0x3a7e394b,
0xa17fa248,0xb1cfb2a1,0x16480000,0x26ad0000,0x9fdba0b6,0xb029b0fd,0x1cb61a48,0x2d002aac,0x9cb69e48,0xad00aeaa,0x1fdb1e48,0x30292eaa,
0x96489a48,0xa6adaaac,0x217f20b6,0x31cf30fd,0xa81fa8b6,0xb27cb365,0x1cb60000,0x27760000,0xa5e4a711,0xb0a6b191,0x231120b6,0x2d972b75,
0xa311a4b6,0xad97af72,0x25e424b6,0x30a62f72,0x9cb6a0b6,0xa776ab75,0x281f2711,0x327c3191,0xaadeabd9,0xb328b414,0x1fdb0000,0x281f0000,
0xa8e8a9e3,0xb122b226,0x25e423db,0x2e2d2c1f,0xa5e4a7da,0xae2db01d,0x28e827da,0x3122301d,0x9fdba3db,0xa81fac1f,0x2ade29e3,0x33283226,
0xaccead7e,0xb3d3b475,0x217f0000,0x28840000,0xaadeac1f,0xb19eb2b9,0x281f257f,0x2ec32c83,0xa81fa97f,0xaec3b080,0x2ade297f,0x319e3080,
0xa17fa57f,0xa884ac83,0x2cce2c1f,0x33d332b9,0xae2daf0e,0xb43eb4d5,0x23110000,0x28e80000,0xac6aad4c,0xb219b34c,0x294d2711,0x2f592ce7,
0xa94dab11,0xaf59b0e4,0x2c6a2b11,0x321930e4,0xa311a711,0xa8e8ace7,0x2e2d2d4c,0x343e334c,0xaf8bb04e,0xb493b534,0x24520000,0x294d0000,
0xad65ae78,0xb294b3df,0x2a7a2852,0x2fef2d4c,0xaa7aac51,0xafefb147,0x2d652c51,0x32943147,0xa452a852,0xa94dad4c,0x2f8b2e78,0x349333df,
0xb074b115,0xb4e7b593,0x251b0000,0x29b10000,0xae5fafa4,0xb30fb438,0x2ba7291b,0x30422db0,0xaba7ad1a,0xb042b1aa,0x2e5f2d1a,0x330f31aa,
0xa51ba91b,0xa9b1adb0,0x30742fa4,0x34e73438,0xb122b1db,0xb53ab5f1,0x25e40000,0x2a160000,0xaf59b067,0xb389b481,0x2c6a29e3,0x308d2e14,
0xac6aade2,0xb08db20d,0x2f592de2,0x3389320d,0xa5e4a9e3,0xaa16ae14,0x31223067,0x353a3481,0xb58db64e,0xb805b887,0x2a7a0000,0x2cce0000,
0xb402b4c9,0xb5dfb6f9,0x30d72e78,0x332830cb,0xb0d7b26f,0xb328b4bd,0x3402326f,0x35df34bd,0xaa7aae78,0xacceb0cb,0x358d34c9,0x380536f9,
0xb5dfb6aa,0xb82ab8b0,0x2ade0000,0x2d000000,0xb43eb511,0xb61ab73d,0x31222edc,0x337130fd,0xb122b2d2,0xb371b4ed,0x343e32d2,0x361a34ed,
0xaadeaedc,0xad00b0fd,0x35df3511,0x382a373d,0xb631b705,0xb850b8d8,0x2b430000,0x2d330000,0xb47bb558,0xb654b780,0x316c2f40,0x33ba312e,
0xb16cb334,0xb3bab51d,0x347b3334,0x3654351d,0xab43af40,0xad33b12e,0x36313558,0x38503780,0xb682b75e,0xb874b900,0x2ba70000,0x2d650000,
0xb4b7b59f,0xb68db7c2,0x31b62fa4,0x34023160,0xb1b6b396,0xb402b54c,0x34b73396,0x368d354c,0xaba7afa4,0xad65b160,0x3682359f,0x387437c2,
0xb6d2b7b7,0xb899b927,0x2c060000,0x2d970000,0xb4f3b5e5,0xb6c6b802,0x32013004,0x34263191,0xb201b3f7,0xb426b57c,0x34f333f7,0x36c6357c,
0xac06b004,0xad97b191,0x36d235e5,0x38993802,0xb721b807,0xb8bcb94d,0x2c380000,0x2dc90000,0xb52fb62b,0xb6ffb822,0x324b3036,0x344b31c3,
0xb24bb42c,0xb44bb5ab,0x352f342c,0x36ff35ab,0xac38b036,0xadc9b1c3,0x3721362b,0x38bc3822,0xb76fb832,0xb8e0b972,0x2c6a0000,0x2dfb0000,
0xb56ab670,0xb737b842,0x32943067,0x346f31f4,0xb294b45d,0xb46fb5da,0x356a345d,0x373735da,0xac6ab067,0xadfbb1f4,0x376f3670,0x38e03842,
0xb7bdb85d,0xb902b996,0x2c9c0000,0x2e2d0000,0xb5a5b6b5,0xb76fb862,0x32de3099,0x34933226,0xb2deb48d,0xb493b608,0x35a5348d,0x376f3608,
0xac9cb099,0xae2db226,0x37bd36b5,0x39023862,0xb924b9ba,0xba1dbab5,0x2e5f0000,0x2fef0000,0xb7a6b881,0xb8a8b96d,0x34b73257,0x35d433df,
0xb4b7b637,0xb5d4b7a1,0x37a63637,0x38a837a1,0xae5fb257,0xafefb3df,0x39243881,0x3a1d396d,0xb946b9dc,0xba39bad0,0x2e910000,0x30100000,
0xb7ddb8a0,0xb8c1b989,0x34db3288,0x35f73408,0xb4dbb665,0xb5f7b7cd,0x37dd3665,0x38c137cd,0xae91b288,0xb010b408,0x394638a0,0x3a393989,
0xb966b9fe,0xba54bae9,0x2ec30000,0x30290000,0xb80ab8bf,0xb8dbb9a4,0x34ff32b9,0x361a3420,0xb4ffb693,0xb61ab7f9,0x380a3693,0x38db37f9,
0xaec3b2b9,0xb029b420,0x396638bf,0x3a5439a4,0xb986ba1f,0xba6fbb02,0x2ef50000,0x30420000,0xb825b8dd,0xb8f3b9be,0x352332ea,0x363c3438,
0xb523b6c1,0xb63cb812,0x382536c1,0x38f33812,0xaef5b2ea,0xb042b438,0x398638dd,0x3a6f39be,0xb9a6ba3f,0xba89bb1a,0x2f270000,0x305b0000,
0xb840b8fb,0xb90cb9d8,0x3546331b,0x365f3451,0xb546b6ee,0xb65fb828,0x384036ee,0x390c3828,0xaf27b31b,0xb05bb451,0x39a638fb,0x3a8939d8,
0xb9c5ba5e,0xbaa2bb30,0x2f590000,0x30740000,0xb85ab918,0xb924b9f2,0x356a334c,0x36823469,0xb56ab71b,0xb682b83d,0x385a371b,0x3924383d,
0xaf59b34c,0xb074b469,0x39c53918,0x3aa239f2,0xb9e3ba7c,0xbababb46,0x2f8b0000,0x308d0000,0xb874b935,0xb93cba0b,0x358d337d,0x36a43481,
0xb58db748,0xb6a4b852,0x38743748,0x393c3852,0xaf8bb37d,0xb08db481,0x39e33935,0x3aba3a0b,0xba00ba99,0xbad1bb5a,0x2fbd0000,0x30a60000,
0xb88eb951,0xb954ba23,0x35b133ae,0x36c63499,0xb5b1b775,0xb6c6b867,0x388e3775,0x39543867,0xafbdb3ae,0xb0a6b499,0x3a003951,0x3ad13a23,
0xbae8bb6e,0xbb7fbbdd,0x30be0000,0x31850000,0xb96bba3b,0xba19bae6,0x36e834b1,0x37f33570,0xb6e8b87c,0xb7f3b91d,0x396b387c,0x3a19391d,
0xb0beb4b1,0xb185b570,0x3ae83a3b,0x3b7f3ae6,0xbafebb80,0xbb8ebbe6,0x30d70000,0x319e0000,0xb982ba52,0xba2dbaf9,0x370a34c9,0x380a3587,
0xb70ab891,0xb80ab930,0x39823891,0x3a2d3930,0xb0d7b4c9,0xb19eb587,0x3afe3a52,0x3b8e3af9,0xbb13bb91,0xbb9cbbed,0x30f00000,0x31b60000,
0xb999ba69,0xba41bb0b,0x372c34e1,0x381a359f,0xb72cb8a6,0xb81ab943,0x399938a6,0x3a413943,0xb0f0b4e1,0xb1b6b59f,0x3b133a69,0x3b9c3b0b,
0xbb27bba0,0xbba9bbf4,0x31090000,0x31cf0000,0xb9afba7f,0xba54bb1d,0x374e34f9,0x382a35b6,0xb74eb8ba,0xb82ab956,0x39af38ba,0x3a543956,
0xb109b4f9,0xb1cfb5b6,0x3b273a7f,0x3ba93b1d,0xbb3abbaf,0xbbb5bbf8,0x31220000,0x31e80000,0xb9c5ba95,0xba67bb2e,0x376f3511,0x383a35ce,
0xb76fb8ce,0xb83ab969,0x39c538ce,0x3a673969,0xb122b511,0xb1e8b5ce,0x3b3a3a95,0x3bb53b2e,0xbb4cbbbc,0xbbc0bbfc,0x313b0000,0x32010000,
0xb9dabaaa,0xba7abb3e,0x37903529,0x384a35e5,0xb790b8e2,0xb84ab97b,0x39da38e2,0x3a7a397b,0xb13bb529,0xb201b5e5,0x3b4c3aaa,0x3bc03b3e,
0xbb5ebbc9,0xbbcbbbff,0x31530000,0x32190000,0xb9f0babf,0xba8cbb4e,0x37b23540,0x385a35fd,0xb7b2b8f6,0xb85ab98d,0x39f038f6,0x3a8c398d,
0xb153b540,0xb219b5fd,0x3b5e3abf,0x3bcb3b4e,0xbb6fbbd4,0xbbd4bc00,0x316c0000,0x32320000,0xba04bad3,0xba9ebb5d,0x37d23558,0x386a3614,
0xb7d2b909,0xb86ab99f,0x3a043909,0x3a9e399f,0xb16cb558,0xb232b614,0x3b6f3ad3,0x3bd43b5d,0x0,0x0,0x0,0x0,
0x2e1f0000,0x336431a8,0x33643400,0x2e1f31a8,0x31a80000,0x31a83400,0xb1a80000,0xb1a8b400,0x33640000,0xae1f31a8,0xae1fb400,0x336431a8,
0x34000000,0xb4000000,0x34000000,0xb4000000,0x33640000,0xae1fb1a8,0xae1f3400,0x3364b1a8,0x31a80000,0x31a8b400,0xb1a80000,0xb1a83400,
0x2e1f0000,0x3364b1a8,0x3364b400,0x2e1fb1a8,0x0,0x0,0x0,0x0,0xae1f0000,0xb36431a8,0xb3643400,0xae1f31a8,
0xb1a80000,0xb1a83400,0x31a80000,0x31a8b400,0xb3640000,0x2e1f31a8,0x2e1fb400,0xb36431a8,0xb4000000,0x34000000,0xb4000000,0x34000000,
0xb3640000,0x2e1fb1a8,0x2e1f3400,0xb364b1a8,0xb1a80000,0xb1a8b400,0x31a80000,0x31a83400,0xae1f0000,0xb364b1a8,0xb364b400,0xae1fb1a8,
0x0,0x0,0x0,0x0,0xae1f0000,0xb364b1a8,0xb364b400,0xae1fb1a8,0x31a80000,0x31a83400,0xb1a80000,0xb1a8b400,
0xb3640000,0x2e1fb1a8,0x2e1f3400,0xb364b1a8,0x34000000,0xb4000000,0x34000000,0xb4000000,0xb3640000,0x2e1f31a8,0x2e1fb400,0xb36431a8,
0x31a80000,0x31a8b400,0xb1a80000,0xb1a83400,0xae1f0000,0xb36431a8,0xb3643400,0xae1f31a8,0x0,0x0,0x0,0x0,
0x2e1f0000,0x3364b1a8,0x3364b400,0x2e1fb1a8,0xb1a80000,0xb1a83400,0x31a80000,0x31a8b400,0x33640000,0xae1fb1a8,0xae1f3400,0x3364b1a8,
0xb4000000,0x34000000,0xb4000000,0x34000000,0x33640000,0xae1f31a8,0xae1fb400,0x336431a8,0xb1a80000,0xb1a8b400,0x31a80000,0x31a83400,
0x2e1f0000,0x336431a8,0x33643400,0x2e1f31a8,0x34003400,0x34003400,0x34003400,0x34003400,0x33643400,0x2e1f31a8,0xae1f0000,0xb364b1a8,
0x31a83400,0xb1a80000,0xb1a8b400,0x31a80000,0x2e1f3400,0xb364b1a8,0x33640000,0xae1f31a8,0x3400,0xb400,0x3400,0xb400,
0xae1f3400,0x3364b1a8,0xb3640000,0x2e1f31a8,0xb1a83400,0x31a80000,0x31a8b400,0xb1a80000,0xb3643400,0xae1f31a8,0x2e1f0000,0x3364b1a8,
0xb4003400,0xb4003400,0xb4003400,0xb4003400,0xb3643400,0xae1f31a8,0x2e1f0000,0x3364b1a8,0xb1a83400,0x31a80000,0x31a8b400,0xb1a80000,
0xae1f3400,0x3364b1a8,0xb3640000,0x2e1f31a8,0x3400,0xb400,0x3400,0xb400,0x2e1f3400,0xb364b1a8,0x33640000,0xae1f31a8,
0x31a83400,0xb1a80000,0xb1a8b400,0x31a80000,0x33643400,0x2e1f31a8,0xae1f0000,0xb364b1a8,0x34003400,0x34003400,0x34003400,0x34003400,
0xb364b400,0xae1fb1a8,0x2e1f0000,0x336431a8,0x31a83400,0xb1a80000,0xb1a8b400,0x31a80000,0xae1fb400,0x336431a8,0xb3640000,0x2e1fb1a8,
0x3400,0xb400,0x3400,0xb400,0x2e1fb400,0xb36431a8,0x33640000,0xae1fb1a8,0xb1a83400,0x31a80000,0x31a8b400,0xb1a80000,
0x3364b400,0x2e1fb1a8,0xae1f0000,0xb36431a8,0xb4003400,0xb4003400,0xb4003400,0xb4003400,0x3364b400,0x2e1fb1a8,0xae1f0000,0xb36431a8,
0xb1a83400,0x31a80000,0x31a8b400,0xb1a80000,0x2e1fb400,0xb36431a8,0x33640000,0xae1fb1a8,0x3400,0xb400,0x3400,0xb400,
0xae1fb400,0x336431a8,0xb3640000,0x2e1fb1a8,0x31a83400,0xb1a80000,0xb1a8b400,0x31a80000,0xb364b400,0xae1fb1a8,0x2e1f0000,0x336431a8,
0x0,0x0,0x0,0x0,0xae1f0000,0xb364b1a8,0xb364b400,0xae1fb1a8,0xb1a80000,0xb1a8b400,0x31a80000,0x31a83400,
0xb3640000,0x2e1fb1a8,0x2e1f3400,0xb364b1a8,0xb4000000,0x34000000,0xb4000000,0x34000000,0xb3640000,0x2e1f31a8,0x2e1fb400,0xb36431a8,
0xb1a80000,0xb1a83400,0x31a80000,0x31a8b400,0xae1f0000,0xb36431a8,0xb3643400,0xae1f31a8,0x0,0x0,0x0,0x0,
0x2e1f0000,0x3364b1a8,0x3364b400,0x2e1fb1a8,0x31a80000,0x31a8b400,0xb1a80000,0xb1a83400,0x33640000,0xae1fb1a8,0xae1f3400,0x3364b1a8,
0x34000000,0xb4000000,0x34000000,0xb4000000,0x33640000,0xae1f31a8,0xae1fb400,0x336431a8,0x31a80000,0x31a83400,0xb1a80000,0xb1a8b400,
0x2e1f0000,0x336431a8,0x33643400,0x2e1f31a8,0x0,0x0,0x0,0x0,0x2e1f0000,0x336431a8,0x33643400,0x2e1f31a8,
0xb1a80000,0xb1a8b400,0x31a80000,0x31a83400,0x33640000,0xae1f31a8,0xae1fb400,0x336431a8,0xb4000000,0x34000000,0xb4000000,0x34000000,
0x33640000,0xae1fb1a8,0xae1f3400,0x3364b1a8,0xb1a80000,0xb1a83400,0x31a80000,0x31a8b400,0x2e1f0000,0x3364b1a8,0x3364b400,0x2e1fb1a8,
0x0,0x0,0x0,0x0,0xae1f0000,0xb36431a8,0xb3643400,0xae1f31a8,0x31a80000,0x31a8b400,0xb1a80000,0xb1a83400,
0xb3640000,0x2e1f31a8,0x2e1fb400,0xb36431a8,0x34000000,0xb4000000,0x34000000,0xb4000000,0xb3640000,0x2e1fb1a8,0x2e1f3400,0xb364b1a8,
0x31a80000,0x31a83400,0xb1a80000,0xb1a8b400,0xae1f0000,0xb364b1a8,0xb364b400,0xae1fb1a8,
};

typedef CUresult (*EncodeFn)(CUtensorMap*, CUtensorMapDataType, cuuint32_t, void*, const cuuint64_t*, const cuuint64_t*,
                             const cuuint32_t*, const cuuint32_t*, CUtensorMapInterleave, CUtensorMapSwizzle,
                             CUtensorMapL2promotion, CUtensorMapFloatOOBfill);

}

extern "C" void kernel_launch(void* const* d_in, const int* in_sizes, int n_in, void* d_out, int out_size) {
    Params p;
    p.x = (const __nv_bfloat16*)d_in[0];
    p.lar = (const __nv_bfloat16*)d_in[1];
    p.aim = (const __nv_bfloat16*)d_in[2];
    p.cr = (const __nv_bfloat16*)d_in[3];
    p.ci = (const __nv_bfloat16*)d_in[4];
    p.logdt = (const __nv_bfloat16*)d_in[5];
    p.dskip = (const __nv_bfloat16*)d_in[6];
    p.wr = (const __nv_bfloat16*)d_in[8];
    p.out = (__nv_bfloat16*)d_out;
    cudaGetSymbolAddress((void**)&p.sc, g_scratch);
    cudaGetSymbolAddress((void**)&p.tab, g_tab);

    void* fn = nullptr;
    cudaDriverEntryPointQueryResult qr;
    cudaGetDriverEntryPoint("cuTensorMapEncodeTiled", &fn, cudaEnableDefault, &qr);
    EncodeFn enc = (EncodeFn)fn;
    CUtensorMap tm_x, tm_g, tm_d;
    const cuuint32_t es[5] = {1, 1, 1, 1, 1};
    {
        const cuuint64_t gd[4] = {1024, 128, 8, 2}, gs[3] = {32768, 4096, 2048};
        const cuuint32_t bx[4] = {16, 64, 4, 1};
        enc(&tm_x, CU_TENSOR_MAP_DATA_TYPE_BFLOAT16, 4, d_in[0], gd, gs, bx, es, CU_TENSOR_MAP_INTERLEAVE_NONE,
            CU_TENSOR_MAP_SWIZZLE_NONE, CU_TENSOR_MAP_L2_PROMOTION_NONE, CU_TENSOR_MAP_FLOAT_OOB_FILL_NONE);
    }
    {
        char *wg = (char*)d_in[9], *wu = (char*)d_in[10];
        p.up_first = wu < wg;
        const cuuint64_t gd[3] = {3584, 1024, 2}, gs[2] = {7168, (cuuint64_t)(p.up_first ? wg - wu : wu - wg)};
        const cuuint32_t bx[3] = {64, 64, 2};
        enc(&tm_g, CU_TENSOR_MAP_DATA_TYPE_BFLOAT16, 3, p.up_first ? wu : wg, gd, gs, bx, es, CU_TENSOR_MAP_INTERLEAVE_NONE,
            CU_TENSOR_MAP_SWIZZLE_128B, (CUtensorMapL2promotion)GPROMO, CU_TENSOR_MAP_FLOAT_OOB_FILL_NONE);
    }
    {
        const cuuint64_t gd[3] = {64, 3584, 16}, gs[2] = {2048, 128};
        const cuuint32_t bx[3] = {64, 64, 2};
        enc(&tm_d, CU_TENSOR_MAP_DATA_TYPE_BFLOAT16, 3, d_in[11], gd, gs, bx, es, CU_TENSOR_MAP_INTERLEAVE_NONE,
            CU_TENSOR_MAP_SWIZZLE_128B, (CUtensorMapL2promotion)DPROMO, CU_TENSOR_MAP_FLOAT_OOB_FILL_NONE);
    }
    cudaFuncSetAttribute(fused_kernel, cudaFuncAttributeMaxDynamicSharedMemorySize, SM_TOTAL + 256);
    fused_kernel<<<128, NTHREADS, SM_TOTAL + 256>>>(p, tm_x, tm_g, tm_d);
}
```

```cpp
#include <cuda_runtime.h>
#include <cuda.h>
#include <cuda_bf16.h>
#include <cuda_fp16.h>
#include <stdint.h>

#define TG(i)
#define TS(i)
#define TSL(i)

#define TSW 0
#define SDELAY 1500
#define EDELAY 800
#define FILL 0x53211
#define STSLEEP 200
#define NPF 3
#define REFILL 0x55421
#define NREP 4
#define GPROMO 0
#define DPROMO 0
#define WPOL "evict_first"
#define FUSE 3
#define PDELAY 900
#define IDEPTH 3

namespace {

constexpr int NTHREADS = 512;
constexpr int SPIN_LIMIT = 1 << 16;

constexpr int SM_SLAB = 0;
constexpr int SM_RING = 32768;
constexpr int SUB     = 1088;
constexpr int SM_K    = SM_RING + 10 * 8192;
constexpr int SM_S    = SM_K + 32 * SUB;
constexpr int SM_U    = SM_S + 32 * SUB;
constexpr int SM_F2   = SM_U + 32 * SUB;
constexpr int SM_XSEL = SM_F2 + 1536;
constexpr int SM_PAIR = SM_XSEL + 4096;
constexpr int SM_H    = SM_PAIR + 2048;
constexpr int SM_KEYS = SM_H + 1024;
constexpr int SM_TOK  = SM_KEYS + 64;
constexpr int SM_FIX  = SM_TOK + 16;
constexpr int SM_XRAW = SM_FIX + 32;
constexpr int SM_SCL  = SM_XRAW + 64;
constexpr int SM_BAR  = SM_SCL + 16;
constexpr int SM_RED  = SM_XSEL;
constexpr int SM_TAB  = SM_RING + 7 * 8192;
constexpr int B_FULL = 0, B_ROW = 24, B_STG = 32, B_SLAB = 36, B_TOK = 38, B_UFREE = 39, B_FIX = 40, B_PAIR = 41,
              B_TAB = 42, B_TFREE = 43, B_KFREE = 44, B_U = 46, B_PEER = 48, NBAR = 52;
constexpr int SM_TOTAL = SM_BAR + NBAR * 8;
static_assert(SM_TOTAL + 256 <= 232448, "smem");
__device__ __forceinline__ uint32_t chunk_off(int n) { return SM_RING + (n < 7 ? n : n - 7) * 16384; }
constexpr int KP = 272;

struct Scratch {
    uint4 stats[4][1032];
    uint32_t part[128 * 56 * 16];
    uint32_t epoch;
};
__device__ Scratch g_scratch;

struct Params {
    const __nv_bfloat16 *lar, *aim, *cr, *ci, *logdt, *dskip;
    const __nv_bfloat16 *x, *wr;
    __nv_bfloat16* out;
    Scratch* sc;
    const uint4* tab;
    int up_first;
};

__device__ __forceinline__ uint4 ldg128(const void* p) {
    uint4 v; asm volatile("ld.global.nc.v4.u32 {%0,%1,%2,%3}, [%4];" : "=r"(v.x), "=r"(v.y), "=r"(v.z), "=r"(v.w) : "l"(p)); return v;
}
__device__ __forceinline__ uint4 ld_relaxed128(const void* p) {
    uint4 v;
    asm volatile("{ .reg .b128 t; ld.relaxed.gpu.global.b128 t, [%4]; mov.b128 {%0,%1,%2,%3}, t; }"
                 : "=r"(v.x), "=r"(v.y), "=r"(v.z), "=r"(v.w) : "l"(p) : "memory");
    return v;
}
__device__ __forceinline__ void st_relaxed128(void* p, uint4 v) {
    asm volatile("{ .reg .b128 t; mov.b128 t, {%1,%2,%3,%4}; st.relaxed.gpu.global.b128 [%0], t; }"
                 :: "l"(p), "r"(v.x), "r"(v.y), "r"(v.z), "r"(v.w) : "memory");
}
__device__ __forceinline__ void st_relaxed32(void* p, uint32_t v) {
    asm volatile("st.relaxed.gpu.global.u32 [%0], %1;" :: "l"(p), "r"(v) : "memory");
}
__device__ __forceinline__ uint32_t lds32(uint32_t a) { uint32_t v; asm volatile("ld.shared.u32 %0, [%1];" : "=r"(v) : "r"(a)); return v; }
__device__ __forceinline__ uint32_t lds16(uint32_t a) { uint32_t v; asm volatile("ld.shared.u16 %0, [%1];" : "=r"(v) : "r"(a)); return v; }
__device__ __forceinline__ uint2 lds64(uint32_t a) { uint2 v; asm volatile("ld.shared.v2.u32 {%0,%1}, [%2];" : "=r"(v.x), "=r"(v.y) : "r"(a)); return v; }
__device__ __forceinline__ uint4 lds128(uint32_t a) {
    uint4 v; asm volatile("ld.shared.v4.u32 {%0,%1,%2,%3}, [%4];" : "=r"(v.x), "=r"(v.y), "=r"(v.z), "=r"(v.w) : "r"(a)); return v;
}
__device__ __forceinline__ void sts16(uint32_t a, uint32_t v) { asm volatile("st.shared.u16 [%0], %1;" :: "r"(a), "h"((uint16_t)v) : "memory"); }
__device__ __forceinline__ void sts32(uint32_t a, uint32_t v) { asm volatile("st.shared.u32 [%0], %1;" :: "r"(a), "r"(v) : "memory"); }
__device__ __forceinline__ void sts64(uint32_t a, uint32_t x, uint32_t y) { asm volatile("st.shared.v2.u32 [%0], {%1,%2};" :: "r"(a), "r"(x), "r"(y) : "memory"); }
__device__ __forceinline__ void sts128(uint32_t a, uint32_t x, uint32_t y, uint32_t z, uint32_t w) {
    asm volatile("st.shared.v4.u32 [%0], {%1,%2,%3,%4};" :: "r"(a), "r"(x), "r"(y), "r"(z), "r"(w) : "memory");
}
__device__ __forceinline__ void ldsm4(uint32_t a, uint32_t& r0, uint32_t& r1, uint32_t& r2, uint32_t& r3) {
    asm volatile("ldmatrix.sync.aligned.m8n8.x4.shared.b16 {%0,%1,%2,%3}, [%4];" : "=r"(r0), "=r"(r1), "=r"(r2), "=r"(r3) : "r"(a));
}
__device__ __forceinline__ void mma_f16(float (&d)[4], uint32_t a0, uint32_t a1, uint32_t a2, uint32_t a3, uint32_t b0, uint32_t b1) {
    asm("mma.sync.aligned.m16n8k16.row.col.f32.f16.f16.f32 {%0,%1,%2,%3}, {%4,%5,%6,%7}, {%8,%9}, {%0,%1,%2,%3};"
        : "+f"(d[0]), "+f"(d[1]), "+f"(d[2]), "+f"(d[3]) : "r"(a0), "r"(a1), "r"(a2), "r"(a3), "r"(b0), "r"(b1));
}
__device__ __forceinline__ void mma_bf16(float (&d)[4], uint32_t a0, uint32_t a1, uint32_t a2, uint32_t a3, uint32_t b0, uint32_t b1) {
    asm("mma.sync.aligned.m16n8k16.row.col.f32.bf16.bf16.f32 {%0,%1,%2,%3}, {%4,%5,%6,%7}, {%8,%9}, {%0,%1,%2,%3};"
        : "+f"(d[0]), "+f"(d[1]), "+f"(d[2]), "+f"(d[3]) : "r"(a0), "r"(a1), "r"(a2), "r"(a3), "r"(b0), "r"(b1));
}
__device__ __forceinline__ uint32_t prmt(uint32_t a, uint32_t b, uint32_t s) { uint32_t d; asm("prmt.b32 %0, %1, %2, %3;" : "=r"(d) : "r"(a), "r"(b), "r"(s)); return d; }
__device__ __forceinline__ uint32_t pack_h(float lo, float hi) { uint32_t d; asm("cvt.rn.f16x2.f32 %0, %1, %2;" : "=r"(d) : "f"(hi), "f"(lo)); return d; }
__device__ __forceinline__ uint32_t pack_b(float lo, float hi) { uint32_t d; asm("cvt.rn.bf16x2.f32 %0, %1, %2;" : "=r"(d) : "f"(hi), "f"(lo)); return d; }
__device__ __forceinline__ float blo(uint32_t v) { return __uint_as_float(v << 16); }
__device__ __forceinline__ float bhi(uint32_t v) { return __uint_as_float(v & 0xFFFF0000u); }
__device__ __forceinline__ float rb(float v) { return blo(pack_b(v, v)); }
__device__ __forceinline__ uint32_t bsub2(uint32_t a, uint32_t b) { uint32_t d; asm("sub.rn.bf16x2 %0, %1, %2;" : "=r"(d) : "r"(a), "r"(b)); return d; }
__device__ __forceinline__ uint32_t badd2(uint32_t a, uint32_t b) { uint32_t d; asm("add.rn.bf16x2 %0, %1, %2;" : "=r"(d) : "r"(a), "r"(b)); return d; }
__device__ __forceinline__ uint32_t bmul2(uint32_t a, uint32_t b) { uint32_t d; asm("mul.rn.bf16x2 %0, %1, %2;" : "=r"(d) : "r"(a), "r"(b)); return d; }
__device__ __forceinline__ uint32_t bfma2(uint32_t a, uint32_t b, uint32_t c) { uint32_t d; asm("fma.rn.bf16x2 %0, %1, %2, %3;" : "=r"(d) : "r"(a), "r"(b), "r"(c)); return d; }
__device__ __forceinline__ uint32_t dup_lo(uint32_t v) { uint32_t d; asm("{ .reg .b16 l, h; mov.b32 {l, h}, %1; mov.b32 %0, {l, l}; }" : "=r"(d) : "r"(v)); return d; }
__device__ __forceinline__ uint32_t dup_hi(uint32_t v) { uint32_t d; asm("{ .reg .b16 l, h; mov.b32 {l, h}, %1; mov.b32 %0, {h, h}; }" : "=r"(d) : "r"(v)); return d; }
__device__ __forceinline__ uint32_t norm2(uint32_t x, uint32_t m, uint32_t hi, uint32_t lo) {
    uint32_t a = bsub2(x, m);
    return bfma2(a, hi, bmul2(a, lo));
}
__device__ __forceinline__ float ex2(float v) { float d; asm("ex2.approx.ftz.f32 %0, %1;" : "=f"(d) : "f"(v)); return d; }
__device__ __forceinline__ float rcp(float v) { float d; asm("rcp.approx.ftz.f32 %0, %1;" : "=f"(d) : "f"(v)); return d; }
__device__ __forceinline__ float sigmoidf_(float v) { return rcp(1.0f + ex2(-1.4426950408889634f * v)); }
__device__ __forceinline__ float siluf_(float v) { return v * sigmoidf_(v); }

__device__ __forceinline__ void mbar_init(uint32_t a, int n) { asm volatile("mbarrier.init.shared::cta.b64 [%0], %1;" :: "r"(a), "r"(n) : "memory"); }
__device__ __forceinline__ void mbar_expect(uint32_t a, int tx) { asm volatile("mbarrier.arrive.expect_tx.shared::cta.b64 _, [%0], %1;" :: "r"(a), "r"(tx) : "memory"); }
__device__ __forceinline__ void mbar_arrive(uint32_t a) { asm volatile("mbarrier.arrive.shared::cta.b64 _, [%0];" :: "r"(a) : "memory"); }
__device__ __forceinline__ bool mbar_try(uint32_t a) {
    uint32_t d; asm volatile("{ .reg .pred p; mbarrier.try_wait.parity.shared::cta.b64 p, [%1], 0; selp.u32 %0, 1, 0, p; }" : "=r"(d) : "r"(a) : "memory"); return d;
}
__device__ __forceinline__ void mbar_wait(uint32_t a) {
    if (__builtin_expect(!mbar_try(a), 0)) {
        int n = SPIN_LIMIT;
        while (!mbar_try(a) && --n) {}
    }
}
__device__ __forceinline__ void mbar_arrive_peer(uint32_t a) { asm volatile("mbarrier.arrive.relaxed.cluster.shared::cluster.b64 _, [%0];" :: "r"(a) : "memory"); }
__device__ __forceinline__ uint32_t mapa(uint32_t a, uint32_t rank) { uint32_t d; asm("mapa.shared::cluster.u32 %0, %1, %2;" : "=r"(d) : "r"(a), "r"(rank)); return d; }
__device__ __forceinline__ void st_async2(uint32_t a, uint32_t x, uint32_t y, uint32_t bar) {
    asm volatile("st.async.weak.shared::cluster.mbarrier::complete_tx::bytes.v2.b32 [%0], {%1,%2}, [%3];" :: "r"(a), "r"(x), "r"(y), "r"(bar) : "memory");
}
__device__ __forceinline__ void st_async4(uint32_t a, uint32_t x, uint32_t y, uint32_t z, uint32_t w, uint32_t bar) {
    asm volatile("st.async.weak.shared::cluster.mbarrier::complete_tx::bytes.v4.b32 [%0], {%1,%2,%3,%4}, [%5];"
                 :: "r"(a), "r"(x), "r"(y), "r"(z), "r"(w), "r"(bar) : "memory");
}
__device__ __forceinline__ void stsm4(uint32_t a, uint32_t r0, uint32_t r1, uint32_t r2, uint32_t r3) {
    asm volatile("stmatrix.sync.aligned.m8n8.x4.shared.b16 [%0], {%1,%2,%3,%4};" :: "r"(a), "r"(r0), "r"(r1), "r"(r2), "r"(r3) : "memory");
}
__device__ __forceinline__ void proxy_fence() { asm volatile("fence.proxy.async.shared::cta;" ::: "memory"); }
__device__ __forceinline__ void bar_sync(int id, int n) { asm volatile("bar.sync %0, %1;" :: "r"(id), "r"(n) : "memory"); }
__device__ __forceinline__ void bar_arrive(int id, int n) { asm volatile("bar.arrive %0, %1;" :: "r"(id), "r"(n) : "memory"); }
__device__ __forceinline__ void cluster_arrive() { asm volatile("barrier.cluster.arrive.relaxed.aligned;" ::: "memory"); }
__device__ __forceinline__ void cluster_wait() { asm volatile("barrier.cluster.wait.aligned;" ::: "memory"); }
__device__ __forceinline__ void tma3d(uint32_t dst, const CUtensorMap* tm, int c0, int c1, int c2, uint32_t bar, uint64_t pol) {
    asm volatile("cp.async.bulk.tensor.3d.shared::cluster.global.mbarrier::complete_tx::bytes.L2::cache_hint [%0], [%1, {%3, %4, %6}], [%2], %5;"
                 :: "r"(dst), "l"(tm), "r"(bar), "r"(c0), "r"(c1), "l"(pol), "r"(c2) : "memory");
}
__device__ __forceinline__ bool elect() {
    uint32_t p; asm volatile("{ .reg .pred p; elect.sync _|p, 0xFFFFFFFF; selp.u32 %0, 1, 0, p; }" : "=r"(p)); return p;
}

struct cf { float r, i; };
__device__ __forceinline__ cf cmul(cf a, cf b) { return {a.r * b.r - a.i * b.i, a.r * b.i + a.i * b.r}; }
__device__ __forceinline__ cf csq(cf a) { return {a.r * a.r - a.i * a.i, (a.r + a.r) * a.i}; }
__device__ __forceinline__ cf cexp_(float a2, float b) { float m = ex2(a2); return {m * __cosf(b), m * __sinf(b)}; }
struct hc { uint32_t r, i; };
__device__ __forceinline__ hc pk(cf a, cf b) { return {pack_h(a.r, b.r), pack_h(a.i, b.i)}; }
__device__ __forceinline__ hc hmulc(hc a, hc b) {
    const __half2 ar = *reinterpret_cast<__half2*>(&a.r), ai = *reinterpret_cast<__half2*>(&a.i);
    const __half2 br = *reinterpret_cast<__half2*>(&b.r), bi = *reinterpret_cast<__half2*>(&b.i);
    const __half2 r = __hfma2(ar, br, __hneg2(__hmul2_rn(ai, bi))), i = __hfma2(ar, bi, __hmul2_rn(ai, br));
    return {*reinterpret_cast<const uint32_t*>(&r), *reinterpret_cast<const uint32_t*>(&i)};
}
__device__ __forceinline__ void sth(uint32_t a, hc v) { sts32(a, v.r); sts32(a + 128, v.i); }
__device__ __forceinline__ uint32_t cpy(uint32_t v, uint32_t z) { uint32_t d; asm("xor.b32 %0, %1, %2;" : "=r"(d) : "r"(v), "r"(z)); return d; }
__device__ __forceinline__ uint32_t pin(uint32_t v) { return __shfl_sync(0xFFFFFFFFu, v, threadIdx.x & 31); }
__device__ __forceinline__ void sched_fence() { asm volatile("pmevent 0;" ::: "memory"); }
__device__ __forceinline__ float tanh_(float v) { float d; asm("tanh.approx.f32 %0, %1;" : "=f"(d) : "f"(v)); return d; }
__device__ __forceinline__ float silu2(float h) {
    return fmaf(h, tanh_(h), h);
}
__device__ __forceinline__ uint32_t hfma2_(uint32_t a, uint32_t b, uint32_t c) { uint32_t d; asm("fma.rn.f16x2 %0, %1, %2, %3;" : "=r"(d) : "r"(a), "r"(b), "r"(c)); return d; }
__device__ __forceinline__ uint32_t hfms2_(uint32_t a, uint32_t b, uint32_t c) {
    uint32_t d; asm("{ .reg .b32 t; neg.f16x2 t, %1; fma.rn.f16x2 %0, t, %2, %3; }" : "=r"(d) : "r"(a), "r"(b), "r"(c)); return d;
}

__device__ __forceinline__ uint64_t bdesc(uint32_t addr, uint32_t sbo) {
    return (uint64_t)((addr & 0x3FFFFu) >> 4) | ((uint64_t)(128 >> 4) << 16) | ((uint64_t)(sbo >> 4) << 32);
}
__device__ __forceinline__ void wg_h(uint32_t (&d)[16], const uint32_t* a, const uint32_t* b, uint64_t d0, uint64_t d1, uint64_t d2, uint64_t d3) {
    asm volatile(
        "wgmma.mma_async.sync.aligned.m64n64k16.f16.f16.f16 {%0,%1,%2,%3,%4,%5,%6,%7,%8,%9,%10,%11,%12,%13,%14,%15}, {%16,%17,%18,%19}, %32, 0, 1, 1, 1;\n"
        "wgmma.mma_async.sync.aligned.m64n64k16.f16.f16.f16 {%0,%1,%2,%3,%4,%5,%6,%7,%8,%9,%10,%11,%12,%13,%14,%15}, {%20,%21,%22,%23}, %33, 1, 1, 1, 1;\n"
        "wgmma.mma_async.sync.aligned.m64n64k16.f16.f16.f16 {%0,%1,%2,%3,%4,%5,%6,%7,%8,%9,%10,%11,%12,%13,%14,%15}, {%24,%25,%26,%27}, %34, 1, 1, 1, 1;\n"
        "wgmma.mma_async.sync.aligned.m64n64k16.f16.f16.f16 {%0,%1,%2,%3,%4,%5,%6,%7,%8,%9,%10,%11,%12,%13,%14,%15}, {%28,%29,%30,%31}, %35, 1, 1, 1, 1;\n"
        : "=r"(d[0]), "=r"(d[1]), "=r"(d[2]), "=r"(d[3]), "=r"(d[4]), "=r"(d[5]), "=r"(d[6]), "=r"(d[7]), "=r"(d[8]), "=r"(d[9]), "=r"(d[10]), "=r"(d[11]), "=r"(d[12]), "=r"(d[13]), "=r"(d[14]), "=r"(d[15])
        : "r"(a[0]), "r"(a[1]), "r"(a[2]), "r"(a[3]), "r"(a[4]), "r"(a[5]), "r"(a[6]), "r"(a[7]), "r"(b[0]), "r"(b[1]), "r"(b[2]), "r"(b[3]), "r"(b[4]), "r"(b[5]), "r"(b[6]), "r"(b[7]), "l"(d0), "l"(d1), "l"(d2), "l"(d3));
}
__device__ __forceinline__ void wg_f0(float (&d)[32], const uint32_t* a, const uint32_t* b, uint64_t d0, uint64_t d1, uint64_t d2, uint64_t d3) {
    asm volatile(
        "wgmma.mma_async.sync.aligned.m64n64k16.f32.f16.f16 {%0,%1,%2,%3,%4,%5,%6,%7,%8,%9,%10,%11,%12,%13,%14,%15,%16,%17,%18,%19,%20,%21,%22,%23,%24,%25,%26,%27,%28,%29,%30,%31}, {%32,%33,%34,%35}, %48, 0, 1, 1, 1;\n"
        "wgmma.mma_async.sync.aligned.m64n64k16.f32.f16.f16 {%0,%1,%2,%3,%4,%5,%6,%7,%8,%9,%10,%11,%12,%13,%14,%15,%16,%17,%18,%19,%20,%21,%22,%23,%24,%25,%26,%27,%28,%29,%30,%31}, {%36,%37,%38,%39}, %49, 1, 1, 1, 1;\n"
        "wgmma.mma_async.sync.aligned.m64n64k16.f32.f16.f16 {%0,%1,%2,%3,%4,%5,%6,%7,%8,%9,%10,%11,%12,%13,%14,%15,%16,%17,%18,%19,%20,%21,%22,%23,%24,%25,%26,%27,%28,%29,%30,%31}, {%40,%41,%42,%43}, %50, 1, 1, 1, 1;\n"
        "wgmma.mma_async.sync.aligned.m64n64k16.f32.f16.f16 {%0,%1,%2,%3,%4,%5,%6,%7,%8,%9,%10,%11,%12,%13,%14,%15,%16,%17,%18,%19,%20,%21,%22,%23,%24,%25,%26,%27,%28,%29,%30,%31}, {%44,%45,%46,%47}, %51, 1, 1, 1, 1;\n"
        : "=f"(d[0]), "=f"(d[1]), "=f"(d[2]), "=f"(d[3]), "=f"(d[4]), "=f"(d[5]), "=f"(d[6]), "=f"(d[7]), "=f"(d[8]), "=f"(d[9]), "=f"(d[10]), "=f"(d[11]), "=f"(d[12]), "=f"(d[13]), "=f"(d[14]), "=f"(d[15]), "=f"(d[16]), "=f"(d[17]), "=f"(d[18]), "=f"(d[19]), "=f"(d[20]), "=f"(d[21]), "=f"(d[22]), "=f"(d[23]), "=f"(d[24]), "=f"(d[25]), "=f"(d[26]), "=f"(d[27]), "=f"(d[28]), "=f"(d[29]), "=f"(d[30]), "=f"(d[31])
        : "r"(a[0]), "r"(a[1]), "r"(a[2]), "r"(a[3]), "r"(a[4]), "r"(a[5]), "r"(a[6]), "r"(a[7]), "r"(b[0]), "r"(b[1]), "r"(b[2]), "r"(b[3]), "r"(b[4]), "r"(b[5]), "r"(b[6]), "r"(b[7]), "l"(d0), "l"(d1), "l"(d2), "l"(d3));
}
__device__ __forceinline__ void wg_f1(float (&d)[32], const uint32_t* a, const uint32_t* b, uint64_t d0, uint64_t d1, uint64_t d2, uint64_t d3) {
    asm volatile(
        "wgmma.mma_async.sync.aligned.m64n64k16.f32.f16.f16 {%0,%1,%2,%3,%4,%5,%6,%7,%8,%9,%10,%11,%12,%13,%14,%15,%16,%17,%18,%19,%20,%21,%22,%23,%24,%25,%26,%27,%28,%29,%30,%31}, {%32,%33,%34,%35}, %48, 1, 1, 1, 1;\n"
        "wgmma.mma_async.sync.aligned.m64n64k16.f32.f16.f16 {%0,%1,%2,%3,%4,%5,%6,%7,%8,%9,%10,%11,%12,%13,%14,%15,%16,%17,%18,%19,%20,%21,%22,%23,%24,%25,%26,%27,%28,%29,%30,%31}, {%36,%37,%38,%39}, %49, 1, 1, 1, 1;\n"
        "wgmma.mma_async.sync.aligned.m64n64k16.f32.f16.f16 {%0,%1,%2,%3,%4,%5,%6,%7,%8,%9,%10,%11,%12,%13,%14,%15,%16,%17,%18,%19,%20,%21,%22,%23,%24,%25,%26,%27,%28,%29,%30,%31}, {%40,%41,%42,%43}, %50, 1, 1, 1, 1;\n"
        "wgmma.mma_async.sync.aligned.m64n64k16.f32.f16.f16 {%0,%1,%2,%3,%4,%5,%6,%7,%8,%9,%10,%11,%12,%13,%14,%15,%16,%17,%18,%19,%20,%21,%22,%23,%24,%25,%26,%27,%28,%29,%30,%31}, {%44,%45,%46,%47}, %51, 1, 1, 1, 1;\n"
        : "+f"(d[0]), "+f"(d[1]), "+f"(d[2]), "+f"(d[3]), "+f"(d[4]), "+f"(d[5]), "+f"(d[6]), "+f"(d[7]), "+f"(d[8]), "+f"(d[9]), "+f"(d[10]), "+f"(d[11]), "+f"(d[12]), "+f"(d[13]), "+f"(d[14]), "+f"(d[15]), "+f"(d[16]), "+f"(d[17]), "+f"(d[18]), "+f"(d[19]), "+f"(d[20]), "+f"(d[21]), "+f"(d[22]), "+f"(d[23]), "+f"(d[24]), "+f"(d[25]), "+f"(d[26]), "+f"(d[27]), "+f"(d[28]), "+f"(d[29]), "+f"(d[30]), "+f"(d[31])
        : "r"(a[0]), "r"(a[1]), "r"(a[2]), "r"(a[3]), "r"(a[4]), "r"(a[5]), "r"(a[6]), "r"(a[7]), "r"(b[0]), "r"(b[1]), "r"(b[2]), "r"(b[3]), "r"(b[4]), "r"(b[5]), "r"(b[6]), "r"(b[7]), "l"(d0), "l"(d1), "l"(d2), "l"(d3));
}
__device__ __forceinline__ void wg_s(uint32_t* d, const uint32_t* a, const uint32_t* b, uint64_t d0, uint64_t d1) {
    asm volatile(
        "wgmma.mma_async.sync.aligned.m64n32k16.f16.f16.f16 {%0,%1,%2,%3,%4,%5,%6,%7}, {%8,%9,%10,%11}, %16, 0, 1, 1, 1;\n"
        "wgmma.mma_async.sync.aligned.m64n32k16.f16.f16.f16 {%0,%1,%2,%3,%4,%5,%6,%7}, {%12,%13,%14,%15}, %17, 1, 1, 1, 1;\n"
        : "=r"(d[0]), "=r"(d[1]), "=r"(d[2]), "=r"(d[3]), "=r"(d[4]), "=r"(d[5]), "=r"(d[6]), "=r"(d[7])
        : "r"(a[0]), "r"(a[1]), "r"(a[2]), "r"(a[3]), "r"(b[0]), "r"(b[1]), "r"(b[2]), "r"(b[3]), "l"(d0), "l"(d1));
}
template <int ACC> __device__ __forceinline__ void wg_w(float (&d)[4], uint64_t da, uint64_t db) {
    asm volatile("wgmma.mma_async.sync.aligned.m64n8k16.f32.bf16.bf16 {%0,%1,%2,%3}, %4, %5, %6, 1, 1, 1, 0;"
                 : "+f"(d[0]), "+f"(d[1]), "+f"(d[2]), "+f"(d[3]) : "l"(da), "l"(db), "n"(ACC));
}
__device__ __forceinline__ void wg_w0(float (&d)[4], uint64_t da, uint64_t db) {
    asm volatile("wgmma.mma_async.sync.aligned.m64n8k16.f32.bf16.bf16 {%0,%1,%2,%3}, %4, %5, 0, 1, 1, 1, 0;"
                 : "=f"(d[0]), "=f"(d[1]), "=f"(d[2]), "=f"(d[3]) : "l"(da), "l"(db));
}
__device__ __forceinline__ void wg_fence() { asm volatile("wgmma.fence.sync.aligned;" ::: "memory"); }
__device__ __forceinline__ void wg_commit() { asm volatile("wgmma.commit_group.sync.aligned;" ::: "memory"); }
template <int N> __device__ __forceinline__ void wg_wait() { asm volatile("wgmma.wait_group.sync.aligned %0;" :: "n"(N) : "memory"); }
__device__ __forceinline__ void touch(uint32_t& r) { asm volatile("" : "+r"(r) :: "memory"); }
__device__ __forceinline__ void touch(float& r) { asm volatile("" : "+f"(r) :: "memory"); }
template <class T, int N> __device__ __forceinline__ void touch(T (&r)[N]) {
#pragma unroll
    for (int i = 0; i < N; i++) touch(r[i]);
}

__global__ void __cluster_dims__(2, 1, 1) __launch_bounds__(NTHREADS, 1)
fused_kernel(const Params p, const __grid_constant__ CUtensorMap tm_x, const __grid_constant__ CUtensorMap tm_g,
             const __grid_constant__ CUtensorMap tm_d)
{
    extern __shared__ __align__(1024) uint8_t smem_raw[];
    const uint32_t sm = (uint32_t)__cvta_generic_to_shared(smem_raw);
    const uint32_t bars = sm + SM_BAR;
    const int tid = threadIdx.x, lane = tid & 31;
    const int g = lane >> 2, q = lane & 3;
    const int c = blockIdx.x, rank = c & 1, G = c >> 1;

    if (tid < 256) {
        uint2 lar4, aim4, cr4, ci4;
        uint32_t ldt_raw, dsk_raw;
        {
            const uint32_t i = c * 256 + tid;
            asm volatile("ld.global.nc.v2.u32 {%0,%1}, [%10]; ld.global.nc.v2.u32 {%2,%3}, [%11]; ld.global.nc.u16 %8, [%14];\n"
                         "ld.global.nc.v2.u32 {%4,%5}, [%12]; ld.global.nc.v2.u32 {%6,%7}, [%13]; ld.global.nc.u16 %9, [%15];"
                         : "=r"(lar4.x), "=r"(lar4.y), "=r"(aim4.x), "=r"(aim4.y), "=r"(cr4.x), "=r"(cr4.y), "=r"(ci4.x), "=r"(ci4.y), "=r"(ldt_raw), "=r"(dsk_raw)
                         : "l"(p.lar + i * 4), "l"(p.aim + i * 4), "l"(p.cr + i * 4), "l"(p.ci + i * 4), "l"(p.logdt + (i >> 5)), "l"(p.dskip + (i >> 5)));
        }
        cluster_arrive();
        sched_fence();
        const int warp = __shfl_sync(0xFFFFFFFFu, tid >> 5, 0);
        const float logdt = blo(ldt_raw), dsk = blo(dsk_raw);
        asm volatile("setmaxnreg.inc.sync.aligned.u32 168;");
        const int wgi = warp >> 2, w = warp & 3;
        const uint32_t wb = sm + SM_K + (w < 2 ? 16 * w + 8 * wgi : 16 + 16 * wgi + 8 * w) * SUB;
        sth(wb + lane * 4, hc{0x3C003C00u, 0u});
        const uint32_t tb0 = pin(sm + SM_S + (16 * wgi + w) * SUB + lane * 16), tb1 = pin(sm + SM_S + (16 * wgi + w) * SUB + ((lane + 1) & 31) * 16);
        const uint32_t seg = pin(sm + SM_K + (2 * warp + (lane & 1)) * SUB + (lane >> 1) * 16);
        const uint32_t zst = pin(sm + SM_S + (16 * wgi + (lane >> 4)) * SUB + (16 * w + (lane & 15)) * 16);
        sched_fence();

        {
            const uint32_t z = (uint32_t)(uintptr_t)p.lar & 1;
            lar4.x = cpy(lar4.x, z); lar4.y = cpy(lar4.y, z); aim4.x = cpy(aim4.x, z); aim4.y = cpy(aim4.y, z);
            cr4.x = cpy(cr4.x, z); cr4.y = cpy(cr4.y, z); ci4.x = cpy(ci4.x, z); ci4.y = cpy(ci4.y, z);
        }
        const float dt = rb(expf(logdt));
        float outscale, cs, dn;
        {
            uint32_t m0 = __vmaxu2(__vmaxu2(cr4.x & 0x7FFF7FFFu, cr4.y & 0x7FFF7FFFu), __vmaxu2(ci4.x & 0x7FFF7FFFu, ci4.y & 0x7FFF7FFFu));
            uint32_t m1 = max(m0 & 0xFFFFu, m0 >> 16);
            float cmax = blo(__reduce_max_sync(0xFFFFFFFFu, m1));
            const float sc = fminf(fmaxf(fmaxf(2.0f * dt * cmax, fabsf(dsk) * (1.0f / 1024.0f)), 1e-30f), 1e30f);
            outscale = __uint_as_float(__float_as_uint(sc) & 0x7F800000u);
            const float inv = __uint_as_float(0x7F000000u - __float_as_uint(outscale));
            cs = 2.0f * dt * inv * (1.0f / 512.0f);
            dn = dsk * inv * (1.0f / 512.0f);
            if (lane == 0) sts16(sm + SM_SCL + warp * 2, __float_as_uint(32768.0f * outscale) >> 16);
        }
        if (warp == TSW) TSL(39);
        uint32_t fc[16], fs[16], ta[4], tb[4];
        float kacc[2][3][4];
#pragma unroll
        for (int i = 0; i < 2; i++)
#pragma unroll
            for (int j = 0; j < 3; j++) kacc[i][j][0] = kacc[i][j][1] = kacc[i][j][2] = kacc[i][j][3] = 0.f;
        if (lane == 0) kacc[0][0][0] = dn;
        {
            const uint32_t st = wb + lane * 4;
            const uint32_t zk = lds32(wb + 128);
            const uint32_t la = wb + ((lane & 8) ? 29 : (lane & 7)) * KP + (lane >> 4) * 128;
            const uint32_t lo = wb + ((lane >> 3) & 1) * 128 + (lane >> 4) * 16;
            const uint32_t lb = lo + (8 + (lane & 7)) * KP, lb2 = lo + (24 + min(lane & 7, 4)) * KP, lm = lo + 30 * KP;
#pragma unroll 1
            for (int s = 0; s < 2; s++) {
                const uint32_t wl = s ? lar4.y : lar4.x, wa = s ? aim4.y : aim4.x, wr_ = s ? cr4.y : cr4.x, wi = s ? ci4.y : ci4.x;
                const uint32_t ea = pack_b(ex2(blo(wl) * 1.4426950408889634f), ex2(bhi(wl) * 1.4426950408889634f));
                const float a2[2] = {-(blo(ea) * dt) * 1.4426950408889634f, -(bhi(ea) * dt) * 1.4426950408889634f};
                const float b[2] = {blo(wa) * dt, bhi(wa) * dt};
                {
                    cf z8[2], z16[2], z32[2], z64[2], z128[2];
#pragma unroll
                    for (int e = 0; e < 2; e++) {
                        z8[e] = cexp_(a2[e] * 8.f, b[e] * 8.f);
                        z16[e] = csq(z8[e]); z32[e] = csq(z16[e]); z64[e] = csq(z32[e]); z128[e] = csq(z64[e]);
                    }
                    const hc r1 = pk(z8[0], z8[1]), r2 = pk(z16[0], z16[1]), r3 = hmulc(r1, r2), r4 = pk(z32[0], z32[1]);
                    sth(st + 1 * KP, r1); sth(st + 2 * KP, r2); sth(st + 3 * KP, r3); sth(st + 4 * KP, r4);
                    sth(st + 5 * KP, hmulc(r1, r4)); sth(st + 6 * KP, hmulc(r2, r4)); sth(st + 7 * KP, hmulc(r3, r4));
                    sth(st + 29 * KP, pk(z64[0], z64[1])); sth(st + 30 * KP, pk(z128[0], z128[1]));
                }
                {
                    cf C[2], z2[2], z4[2], v2[2], v4[2], c1[2], d1[2];
#pragma unroll
                    for (int e = 0; e < 2; e++) {
                        C[e] = {(e ? bhi(wr_) : blo(wr_)) * cs, (e ? bhi(wi) : blo(wi)) * -cs};
                        const cf z = cexp_(a2[e], -b[e]);
                        const cf v = cexp_(a2[e] * 256.f, b[e] * -256.f);
                        z2[e] = csq(z); z4[e] = csq(z2[e]); v2[e] = csq(v); v4[e] = csq(v2[e]);
                        c1[e] = cmul(C[e], z); d1[e] = cmul(C[e], v);
                    }
                    const hc l0 = pk(C[0], C[1]), l1 = pk(c1[0], c1[1]), e1 = pk(d1[0], d1[1]);
                    const hc h = pk(z2[0], z2[1]), f = pk(z4[0], z4[1]), w = pk(v2[0], v2[1]), y = pk(v4[0], v4[1]);
                    const hc l2 = hmulc(l0, h), l3 = hmulc(l1, h), e2 = hmulc(l0, w), e3 = hmulc(e1, w), e4 = hmulc(l0, y), g2 = hmulc(e1, h);
                    sth(st + 8 * KP, l0); sth(st + 9 * KP, l1); sth(st + 10 * KP, l2); sth(st + 11 * KP, l3);
                    sth(st + 12 * KP, hmulc(l0, f)); sth(st + 13 * KP, hmulc(l1, f)); sth(st + 14 * KP, hmulc(l2, f)); sth(st + 15 * KP, hmulc(l3, f));
                    sth(st + 16 * KP, e1);
                    sth(st + 17 * KP, g2);
                    sth(st + 18 * KP, hmulc(e1, f));
                    sth(st + 19 * KP, hmulc(g2, f));
                    sth(st + 20 * KP, e2);
                    sth(st + 21 * KP, hmulc(e2, f));
                    sth(st + 22 * KP, e3);
                    sth(st + 23 * KP, hmulc(e3, f));
                    sth(st + 24 * KP, e4);
                    sth(st + 25 * KP, hmulc(e1, y));
                    sth(st + 26 * KP, hmulc(e2, y));
                    sth(st + 27 * KP, hmulc(e3, y));
                    sth(st + 28 * KP, hmulc(e4, y));
                }
                __syncwarp();
                if (warp == TSW && s == 0) TSL(27);
                if (s == 1 && lane == 0) mbar_arrive(bars + B_TFREE * 8 + (tb[3] & zk));
#pragma unroll
                for (int kp = 0; kp < 4; kp++) {
                    uint32_t bb[3][4], m2[4];
                    ldsm4(lm + kp * 32, m2[0], m2[1], m2[2], m2[3]);
                    ldsm4(lb + kp * 32, bb[0][0], bb[0][1], bb[0][2], bb[0][3]);
                    ldsm4(lb + 8 * KP + kp * 32, bb[1][0], bb[1][1], bb[1][2], bb[1][3]);
                    ldsm4(lb2 + kp * 32, bb[2][0], bb[2][1], bb[2][2], bb[2][3]);
#pragma unroll
                    for (int k2 = 0; k2 < 2; k2++) {
                        hc v0, m1;
                        ldsm4(la + kp * 32 + k2 * 16, v0.r, m1.r, v0.i, m1.i);
                        const hc mm = {m2[2 * k2], m2[2 * k2 + 1]};
                        const hc v1 = hmulc(v0, m1), v2 = hmulc(v0, mm), v3 = hmulc(v1, mm);
                        v0.r = cpy(v0.r, zk); v0.i = cpy(v0.i, zk);
#pragma unroll
                        for (int nt = 0; nt < 3; nt++) {
                            mma_f16(kacc[0][nt], v0.r, v1.r, v0.i, v1.i, bb[nt][2 * k2], bb[nt][2 * k2 + 1]);
                            mma_f16(kacc[1][nt], v2.r, v3.r, v2.i, v3.i, bb[nt][2 * k2], bb[nt][2 * k2 + 1]);
                        }
                    }
                }
                __syncwarp();
                if (warp == TSW) TSL(s ? 40 : 33);
                if (s == 0) {
                    cluster_wait();
                    mbar_wait(bars + B_TAB * 8);
#pragma unroll
                    for (int i = 0; i < 10; i++) {
                        const uint4 u = lds128(sm + SM_TAB + i * 2048 + (tid & 127) * 16);
                        uint32_t* t = i < 4 ? fc + 4 * i : i < 8 ? fs + 4 * (i - 4) : i == 8 ? ta : tb;
                        t[0] = u.x; t[1] = u.y; t[2] = u.z; t[3] = u.w;
                    }
                }
            }
        }
        TSL(1);
        bar_sync(10 + wgi, 128);
        {
            uint32_t v[3][4];
#pragma unroll
            for (int i = 0; i < 12; i++) v[i >> 2][i & 3] = pack_h(kacc[(i >> 1) & 1][i >> 2][2 * (i & 1)], kacc[(i >> 1) & 1][i >> 2][2 * (i & 1) + 1]);
            stsm4(tb0, v[1][0], v[1][1], v[1][2], v[1][3]);
            stsm4(tb0 + 512, v[2][0], v[2][1], v[2][2], v[2][3]);
            stsm4(seg, v[0][0], v[0][1], v[0][2], v[0][3]);
            __syncwarp();
            const uint4 a = lds128(tb0), na = lds128(tb1), nb = lds128(tb1 + 512);
            const uint2 b = lds64(tb0 + 512);
            const bool last = lane == 31;
            const uint32_t n1 = last ? na.z : na.x, n2 = last ? na.w : na.z, n3 = last ? nb.x : na.w;
            const uint32_t sn = last ? 0x5432 : 0x3210, n4 = prmt(nb.x, nb.y, sn), n5 = prmt(nb.y, nb.z, sn);
            sts128(seg + 256, prmt(a.x, 0, 0x1010), prmt(a.x, a.y, 0x5432), prmt(a.y, 0, 0x1010), prmt(a.y, n1, 0x5432));
            sts128(seg + 512, prmt(a.z, 0, 0x1010), a.z, prmt(a.z, 0, 0x3232), prmt(n2, 0, 0x1010));
            sts128(seg + 768, prmt(a.w, 0, 0x1010), a.w, prmt(a.w, 0, 0x3232), prmt(n3, 0, 0x1010));
            const uint32_t s3 = (lane & 1) ? 0x5454 : 0x5410;
#pragma unroll
            for (int i = 0; i < 4; i++) {
                const uint32_t cur = (i & 2) ? b.y : b.x, nx = (i & 2) ? n5 : n4, h = (i & 1) * 0x2222;
                const uint32_t vv = prmt(cur, 0, 0x1010 + h);
                sts128(seg + 16 * SUB + i * 256, vv, vv, prmt(cur, nx, s3 + h), prmt(nx, 0, 0x1010 + h));
            }
        }
        proxy_fence();
        TSL(2);
        bar_sync(10 + wgi, 128);
        const uint64_t dre = bdesc(sm + SM_F2 + 512, 256), dim = bdesc(sm + SM_F2, 256);
        uint32_t k0[32], k1[32];
#pragma unroll
        for (int b = 0; b < 2; b++) {
            const uint64_t d1 = bdesc(sm + SM_K + (16 * b + 8 * wgi) * SUB, SUB);
            uint32_t re[16], im[16];
            if (b == 0 && wgi == 1) bar_sync(5, 256);
            wg_fence();
            wg_h(re, fc, fc + 8, d1, d1 + 16, d1 + 32, d1 + 48);
            wg_h(im, fs, fs + 8, d1, d1 + 16, d1 + 32, d1 + 48);
            wg_commit();
            if (b == 0 && wgi == 0) bar_arrive(5, 256);
            wg_wait<0>();
            touch(re); touch(im);
            if (lane == 0) mbar_arrive(bars + (B_KFREE + b) * 8);
            uint32_t (&kk)[32] = b ? k1 : k0;
#pragma unroll
            for (int hh = 0; hh < 2; hh++) {
#pragma unroll
                for (int i = 8 * hh; i < 8 * hh + 8; i++) {
                    re[i] = hfma2_(ta[i & 3], im[i], re[i]); im[i] = hfms2_(tb[i & 3], re[i], im[i]); re[i] = hfma2_(ta[i & 3], im[i], re[i]);
                }
                wg_fence();
                wg_s(kk + 16 * hh, re + 8 * hh, im + 8 * hh, dre, dim);
                wg_s(kk + 16 * hh + 8, re + 8 * hh + 4, im + 8 * hh + 4, dre, dim);
                wg_commit();
            }
            wg_wait<0>();
            touch(kk);
        }
        if (warp == TSW) TSL(35);
        asm volatile("setmaxnreg.inc.sync.aligned.u32 184;");
        touch(k1);
        {
            const uint32_t sg = (g & 1) ? 0xBC00BC00u : 0x3C003C00u;
#pragma unroll
            for (int i = 0; i < 16; i++) {
                const int r = 8 * (i >> 2) + (i & 3);
                k1[r] = hfms2_(sg, k0[r + 4], k1[r]); k1[r + 4] = hfma2_(sg, k0[r], k1[r + 4]);
            }
            touch(k1);
        }
        const uint32_t peer = mapa(sm, rank ^ 1), so = SM_U + 8 * wgi * SUB + w * 1024 + (8 * q + (g ^ (2 * q))) * 16;
        const uint2 sc = lds64(sm + SM_SCL + wgi * 8);
#pragma unroll 1
        for (int b = 0; b < 2; b++) {
            const uint32_t zb = sm + SM_S + 16 * wgi * SUB;
            constexpr int zi = 8 * SUB;
            uint32_t re[16], im[16], su[2][16], z[2][16], y[2][16];
            auto twiddle = [&](int hh) {
#pragma unroll
                for (int i = 8 * hh; i < 8 * hh + 8; i++) {
                    re[i] = hfma2_(ta[i & 3], im[i], re[i]); im[i] = hfms2_(tb[i & 3], re[i], im[i]); re[i] = hfma2_(ta[i & 3], im[i], re[i]);
                    touch(re[i]); touch(im[i]);
                }
            };
            auto dft16 = [&](int hh) {
                wg_fence();
                wg_s(su[hh], re + 8 * hh, im + 8 * hh, dre, dim); wg_s(su[hh] + 8, re + 8 * hh + 4, im + 8 * hh + 4, dre, dim);
                wg_commit();
                sched_fence();
            };
            auto product = [&](int hh) {
                if (b == 0) {
#pragma unroll
                    for (int i = 0; i < 8; i++) {
                        const int r = 8 * (i >> 2) + (i & 3), kr = 16 * hh + r;
                        const hc u = {su[hh][r], su[hh][r + 4]};
                        const hc t = hmulc(u, hc{k0[kr], k0[kr + 4]}), pp = hmulc(u, hc{k1[kr], k1[kr + 4]});
                        z[hh][r] = t.r; z[hh][r + 4] = t.i; k1[kr] = pp.r; k1[kr + 4] = pp.i;
                        touch(k1[kr]); touch(k1[kr + 4]);
                    }
                } else {
#pragma unroll
                    for (int i = 0; i < 8; i++) {
                        const int r = 8 * (i >> 2) + (i & 3), kr = 16 * hh + r;
                        const hc u = {su[hh][r], su[hh][r + 4]};
                        z[hh][r] = hfms2_(u.i, k0[kr + 4], hfma2_(u.r, k0[kr], k1[kr]));
                        z[hh][r + 4] = hfma2_(u.i, k0[kr], hfma2_(u.r, k0[kr + 4], k1[kr + 4]));
                    }
                }
                touch(z[hh]);
            };
            auto idft16 = [&](int hh) {
                wg_fence();
                wg_s(y[hh], z[hh] + 4, z[hh], dre, dim); wg_s(y[hh] + 8, z[hh] + 12, z[hh] + 8, dre, dim);
                wg_commit();
                sched_fence();
            };
            auto untwiddle = [&](int hh) {
#pragma unroll
                for (int i = 0; i < 2; i++) {
                    uint32_t* const yi = y[hh] + 8 * i, * const yr = yi + 4;
#pragma unroll
                    for (int n = 0; n < 4; n++) {
                        yr[n] = hfms2_(ta[n], yi[n], yr[n]); yi[n] = hfma2_(tb[n], yr[n], yi[n]); yr[n] = hfms2_(ta[n], yi[n], yr[n]);
                    }
                    const uint32_t a = zst + (4 * hh + 2 * i) * SUB;
                    stsm4(a, yr[0], yr[1], yr[2], yr[3]);
                    stsm4(a + zi, yi[0], yi[1], yi[2], yi[3]);
                }
            };
            auto done = [&]() { sched_fence(); wg_wait<0>(); };
            {
                const uint64_t d1 = bdesc(sm + SM_U + (16 * b + 8 * wgi) * SUB, SUB);
                mbar_wait(bars + (B_U + b) * 8);
                proxy_fence();
                if (b == 0) { TSL(3); if (wgi == 1) bar_sync(9, 256); }
                wg_fence();
                wg_h(re, fc, fc + 8, d1, d1 + 16, d1 + 32, d1 + 48);
                wg_h(im, fs, fs + 8, d1, d1 + 16, d1 + 32, d1 + 48);
                wg_commit();
                if (b == 0 && wgi == 0) bar_arrive(9, 256);
                wg_wait<0>();
                touch(re); touch(im);
            }
            if (lane == 0) mbar_arrive_peer(peer + SM_BAR + (B_PEER + 2 * wgi + b) * 8);
            twiddle(0); twiddle(1); dft16(0); dft16(1);
            wg_wait<1>(); touch(su[0]);
            product(0); done(); touch(su[1]); idft16(0);
            product(1); done(); touch(y[0]); idft16(1);
            bar_sync(10 + wgi, 128);
            untwiddle(0); done(); touch(y[1]);
            untwiddle(1);
            proxy_fence();
            if (warp == TSW) TSL(36 + b);
            bar_sync(10 + wgi, 128);
            float acc[32];
            const uint64_t d4 = bdesc(zb, SUB);
            wg_fence();
            wg_f0(acc, fc, fc + 8, d4, d4 + 16, d4 + 32, d4 + 48);
            wg_f1(acc, fs, fs + 8, d4 + zi / 16, d4 + zi / 16 + 16, d4 + zi / 16 + 32, d4 + zi / 16 + 48);
            wg_commit();
            mbar_wait(bars + (B_PEER + 2 * wgi + b) * 8);
            wg_wait<0>();
            touch(acc);
            uint32_t s[2][2][4];
#pragma unroll
            for (int i = 0; i < 8; i++) {
                s[i >> 2][(i >> 1) & 1][2 * (i & 1)] = bmul2(pack_b(acc[i], acc[8 + i]), sc.x);
                s[i >> 2][(i >> 1) & 1][2 * (i & 1) + 1] = bmul2(pack_b(acc[16 + i], acc[24 + i]), sc.y);
            }
            const uint32_t sb = SM_BAR + (B_STG + b) * 8;
#pragma unroll
            for (int j = 0; j < 2; j++)
                if (j == rank) {
#pragma unroll
                    for (int hi = 0; hi < 2; hi++) {
                        const uint32_t (&r)[4] = s[1 - j][hi], (&l)[4] = s[j][hi];
                        st_async4(peer + so + 16 * b * SUB + hi * 512, r[0], r[1], r[2], r[3], peer + sb);
                        sts128(sm + (so ^ 64) + (16 * b + 4) * SUB + hi * 512, l[0], l[1], l[2], l[3]);
                    }
                }
            __syncwarp();
            if (lane == 0) mbar_arrive(sm + sb);
            if (warp == TSW) TSL(5 + b);
        }
        TSL(7);
    } else {
    const int warp = __shfl_sync(0xFFFFFFFFu, tid >> 5, 0);
    if (warp < 12) {
        const int v = warp - 8;
        cluster_arrive();
        const uint32_t xs = sm + SM_U + v * 8192;
        if (elect()) {
#pragma unroll
            for (int r = 0; r < 2; r++) mbar_init(bars + (B_ROW + 2 * v + r) * 8, 1);
            asm volatile("fence.mbarrier_init.release.cluster;" ::: "memory");
#pragma unroll
            for (int e = 0; e < 2; e++) {
                if (e) { const int t0_ = clock(); while ((int)clock() - t0_ < EDELAY) __nanosleep(40); }
                mbar_expect(bars + (B_ROW + 2 * v + e) * 8, 4096);
#pragma unroll
                for (int r = 0; r < 2; r++)
                    asm volatile("cp.async.bulk.shared::cluster.global.mbarrier::complete_tx::bytes [%0], [%1], 2048, [%2];"
                                 :: "r"(xs + e * 4096 + r * 2048), "l"(p.x + (size_t)(128 * (c & 15) + 32 * v + 16 * r + 2 * (c >> 4) + e) * 1024),
                                    "r"(bars + (B_ROW + 2 * v + e) * 8) : "memory");
            }
        }
        __syncwarp();
        uint4 w4[4];
#pragma unroll
        for (int k = 0; k < 4; k++) w4[k] = ldg128(reinterpret_cast<const uint4*>(p.wr) + 32 * k + lane);
        {
            constexpr uint32_t ONE = 0x3F803F80u;
            const uint32_t zr = p.up_first >> 1;
            uint4 w5[4];
#pragma unroll
            for (int k = 0; k < 4; k++) {
                w5[k].x = w4[k].x + zr; w5[k].y = w4[k].y + zr; w5[k].z = w4[k].z + zr; w5[k].w = w4[k].w + zr;
                w4[k].x = cpy(w4[k].x, zr); w4[k].y = cpy(w4[k].y, zr); w4[k].z = cpy(w4[k].z, zr); w4[k].w = cpy(w4[k].w, zr);
            }
            const bool od = g & 1;
#pragma unroll 1
            for (int r2 = 0; r2 < 2; r2++) {
                mbar_wait(bars + (B_ROW + 2 * v + r2) * 8);
                TSL(43);
                float s1[2][4] = {}, q0[2][4] = {};
#pragma unroll
                for (int k = 0; k < 4; k++)
#pragma unroll
                    for (int r = 0; r < 2; r++) {
                        const uint4 x = lds128(xs + r2 * 4096 + r * 2048 + k * 512 + lane * 16);
                        const uint4& ww = r ? w5[k] : w4[k];
                        mma_bf16(q0[r], cpy(x.x, zr), ww.x, cpy(x.y, zr), ww.y, x.x, x.y);
                        mma_bf16(s1[r], x.x, x.y, x.z, x.w, ONE, ONE);
                        mma_bf16(q0[r], cpy(x.z, zr), ww.z, cpy(x.w, zr), ww.w, x.z, x.w);
                    }
#pragma unroll
                for (int r = 0; r < 2; r++)
                    if (q == (g >> 1))
                        sts128(sm + SM_RED + (4 * v + r2 + 2 * r) * 144 + g * 16, __float_as_uint(od ? q0[r][1] : q0[r][0]),
                               __float_as_uint(od ? q0[r][3] : q0[r][2]), __float_as_uint(s1[r][0]), __float_as_uint(s1[r][2]));
            }
            bar_arrive(7, 160);
        }
        TSL(8);
        bar_sync(6, 160);
        const uint32_t tag = lds32(sm + SM_TOK + 8);
        cluster_wait();
        asm volatile("setmaxnreg.dec.sync.aligned.u32 104;");
        const uint32_t peer = mapa(sm, rank ^ 1);
        if (v == 0 && lane == 0) mbar_arrive_peer(peer + SM_BAR + B_UFREE * 8);
        {
            uint4 st[8];
            const uint4* src = p.sc->stats[G & (NREP - 1)] + rank * 512 + 16 * v + (lane >> 1);
            const uint32_t tb = ((tag & 1) << 15) | ((tag >> 1) << 31);
            const uint32_t xo = pin(sm + SM_SLAB + v * 512 + lane * 16);
            const uint32_t ub = pin(mapa(bars + B_U * 8, lane & 1)), ud = pin(mapa(sm + SM_U + rank * SUB + (16 * v + (lane >> 1)) * 16, lane & 1));
            bar_sync(3, 192);
            if (warp == 8) TSL(44);
#pragma unroll
            for (int i = 0; i < 8; i++) st[i] = ld_relaxed128(src + (i >> 2) * 64 + (i & 3) * 128);
            uint4 x0[8];
            mbar_wait(bars + B_UFREE * 8);
            mbar_wait(bars + B_SLAB * 8);
#pragma unroll
            for (int i = 0; i < 8; i++) x0[i] = lds128(xo + (i & 1) * 8192 + (i >> 1) * 2048);
            for (int it = 0; it < SPIN_LIMIT; it++) {
                uint32_t bad = 0;
#pragma unroll
                for (int i = 0; i < 8; i++) bad |= st[i].z ^ tb;
                if (__all_sync(0xFFFFFFFFu, (bad & 0x80008000u) == 0)) break;
#pragma unroll
                for (int i = 0; i < 8; i++)
                    if ((st[i].z ^ tb) & 0x80008000u) st[i] = ld_relaxed128(src + (i >> 2) * 64 + (i & 3) * 128);
            }
            TSL(11); TG(31);
#pragma unroll
            for (int i = 0; i < 8; i++) st[i].z &= 0x7FFF7FFFu;
            const bool own = (lane & 1) == rank;
            uint32_t n[2][8][4];
#pragma unroll
            for (int i = 0; i < 4; i++) { n[0][i][0] = st[4 + i].x; n[0][i][1] = st[4 + i].y; n[0][i][2] = st[4 + i].z; }
#pragma unroll 1
            for (int b = 0; ; b++) {
#pragma unroll
                for (int i = 0; i < 8; i++) {
                    const uint4& t = st[i >> 1];
                    const uint32_t m = (i & 1) ? dup_hi(t.x) : dup_lo(t.x), hi = (i & 1) ? dup_hi(t.z) : dup_lo(t.z), lo = (i & 1) ? dup_hi(t.y) : dup_lo(t.y);
                    uint32_t (&r)[4] = n[1][i];
                    r[0] = norm2(x0[i].x, m, hi, lo); r[1] = norm2(x0[i].y, m, hi, lo); r[2] = norm2(x0[i].z, m, hi, lo); r[3] = norm2(x0[i].w, m, hi, lo);
                }
                sched_fence();
#pragma unroll
                for (int cp = 0; cp < 4; cp++) {
                    float f[8][2];
#pragma unroll
                    for (int i = 0; i < 8; i++) { f[i][0] = blo(n[1][i][cp]); f[i][1] = bhi(n[1][i][cp]); }
#pragma unroll
                    for (int h = 0; h < 2; h++)
                        st_async4(ud + (16 * b + 4 * cp + 2 * h) * SUB, pack_h(f[0][h], f[1][h]), pack_h(f[2][h], f[3][h]),
                                  pack_h(f[4][h], f[5][h]), pack_h(f[6][h], f[7][h]), ub + b * 8);
                    if (cp == 3) TSL(b ? 41 : 12);
                    if (cp >= FUSE) {
#pragma unroll
                        for (int i = 0; i < 8; i++) { n[1][i][cp] = pack_b(silu2(f[i][0]), silu2(f[i][1])); touch(n[1][i][cp]); }
                    }
                    sched_fence();
                }
#pragma unroll
                for (int cp = 0; cp < FUSE; cp++) {
#pragma unroll
                    for (int i = 0; i < 8; i++) {
                        uint32_t& r = n[1][i][cp];
                        r = pack_b(silu2(__uint_as_float(prmt(r, tag >> 2, 0x1044))), silu2(__uint_as_float(prmt(r, tag >> 2, 0x3244))));
                        touch(r);
                    }
                    sched_fence();
                }
                if (b) break;
                mbar_wait(bars + (B_SLAB + 1) * 8);
#pragma unroll
                for (int i = 0; i < 8; i++) {
                    if (i < 4) { st[i].x = n[0][i][0]; st[i].y = n[0][i][1]; st[i].z = n[0][i][2]; }
#pragma unroll
                    for (int k = 0; k < 4; k++) n[0][i][k] = n[1][i][k];
                    x0[i] = lds128(xo + 16384 + (i & 1) * 8192 + (i >> 1) * 2048);
                }
            }
            TSL(0);
            const uint32_t stg = pin(sm + SM_U + (own ? 4 * SUB : 0) + v * 1024 + (lane >> 4) * 512 + (((lane & 14) * 8) ^ (own ? 64 : 0)));
            const int tl = pin(256 * v + 16 * (lane >> 1) + 8 * rank);
            __nv_bfloat16* const op = p.out + (size_t)tl * 1024 + G * 16 + (lane & 1) * 8;
            mbar_wait(bars + B_TOK * 8);
            const uint2 tr = lds64(sm + SM_TOK);
#pragma unroll 1
            for (int b = 0; ; b++) {
                const int d0 = tr.x - tl - 1024 * b, d1 = tr.y - tl - 1024 * b;
                uint32_t skip = ((d0 & ~7) ? 0u : 1u << d0) | ((d1 & ~7) ? 0u : 1u << d1);
                const uint32_t sb = stg + 16 * b * SUB, xb = xo + b * 16384;
                __nv_bfloat16* const ob = op + (size_t)b * 1024 * 1024;
                uint4 x[2] = {lds128(xb), lds128(xb + 8192)};
                mbar_wait(bars + (B_STG + b) * 8);
                if (skip) {
#pragma unroll 1
                    for (int k = 0; k < 2; k++) {
                        const int d = k ? d1 : d0;
                        if (!(d & ~7)) {
                            const uint32_t a = (sb ^ ((d & 6) * 16)) + (d & 6) * 64 + (d & 1) * 8, dst = mapa(sm, k);
                            const uint2 s0 = lds64(a), s1 = lds64(a + 8 * SUB);
                            st_async4(dst + SM_FIX + (lane & 1) * 16, s0.x, s0.y, s1.x, s1.y, dst + SM_BAR + B_FIX * 8);
                        }
                    }
                }
                __syncwarp();
#pragma unroll
                for (int i = 0; i < 4; i++) {
                    const uint32_t a = (sb ^ (32 * i)) + 128 * i;
                    const uint4 r0 = lds128(a), r1 = lds128(a + 8 * SUB);
#pragma unroll
                    for (int e = 0; e < 2; e++) {
                        const uint32_t s0 = e ? r0.z : r0.x, s1 = e ? r0.w : r0.y, s2 = e ? r1.z : r1.x, s3 = e ? r1.w : r1.y;
                        const uint32_t (&gt)[4] = n[0][2 * i + e];
                        asm volatile("{ .reg .pred p; setp.eq.u32 p, %5, 0; @p st.global.v4.u32 [%0], {%1,%2,%3,%4}; }"
                                     :: "l"(ob + (2 * i + e) * 1024), "r"(badd2(x[e].x, bmul2(s0, gt[0]))), "r"(badd2(x[e].y, bmul2(s1, gt[1]))),
                                        "r"(badd2(x[e].z, bmul2(s2, gt[2]))), "r"(badd2(x[e].w, bmul2(s3, gt[3]))), "r"(skip & (1u << (2 * i + e))) : "memory");
                        if (i < 3) x[e] = lds128(xb + e * 8192 + (i + 1) * 2048);
                    }
                    if (i < 3 && !b) __nanosleep(STSLEEP);
                }
                TSL(b ? 23 : 22);
                if (b) break;
#pragma unroll
                for (int i = 0; i < 32; i++) n[0][i >> 2][i & 3] = n[1][i >> 2][i & 3];
            }
            TSL(17); TG(30);
        }
    } else {
        const int v = warp - 12;
        if (lane == 0) {
            if (v == 1) {
                mbar_init(bars + B_TAB * 8, 1); mbar_init(bars + B_TFREE * 8, 8); mbar_init(bars + B_KFREE * 8, 8); mbar_init(bars + (B_KFREE + 1) * 8, 8);
                mbar_expect(bars + B_TAB * 8, 20480 + 1536);
            } else if (v == 0) {
                mbar_init(bars + B_SLAB * 8, 1); mbar_init(bars + (B_SLAB + 1) * 8, 1); mbar_init(bars + B_TOK * 8, 2); mbar_init(bars + B_UFREE * 8, 1);
                mbar_expect(bars + B_SLAB * 8, 16384); mbar_expect(bars + (B_SLAB + 1) * 8, 16384);
            } else {
                mbar_init(bars + (B_STG + v - 2) * 8, 9); mbar_init(bars + (B_FIX + v - 2) * 8, 1);
                mbar_init(bars + (B_U + v - 2) * 8, 1); mbar_expect(bars + (B_U + v - 2) * 8, 16384);
                mbar_expect(bars + (B_STG + v - 2) * 8, 8192); mbar_expect(bars + (B_FIX + v - 2) * 8, v == 2 ? 32 : 2048);
            }
            mbar_init(bars + (B_PEER + v) * 8, 4);
#pragma unroll
            for (int i = 0; i < 3; i++) { mbar_init(bars + (B_FULL + 3 * v + i) * 8, 1); mbar_expect(bars + (B_FULL + 3 * v + i) * 8, 16384); }
            asm volatile("fence.mbarrier_init.release.cluster;" ::: "memory");
        }
        __syncwarp();
        cluster_arrive();
        asm volatile("setmaxnreg.dec.sync.aligned.u32 40;");
        uint64_t pol; asm volatile("createpolicy.fractional.L2::" WPOL ".b64 %0, 1.0;" : "=l"(pol));
        auto load_chunk = [&](int n) {
            if (n < 8) tma3d(sm + chunk_off(n), &tm_g, G * 64, rank * 512 + n * 64, 0, bars + (B_FULL + n) * 8, pol);
            else tma3d(sm + chunk_off(n), &tm_d, 0, G * 64, rank * 8 + (n - 8) * 2, bars + (B_FULL + n) * 8, pol);
        };
        uint32_t* const my_part = p.sc->part + ((2 * (32 * rank + v) + (q & 1)) * 56 + G) * 16 + g + 8 * (q >> 1);
        if (G < 56) {
#pragma unroll
            for (int n = 0; n < 8; n++) st_relaxed32(my_part + n * 8 * 56 * 16, 0);
        }
        cluster_wait();
        const bool lead = elect();
        uint32_t key = 0;
        if (v == 0) {
            asm volatile("prefetch.tensormap [%0];" :: "l"(&tm_x) : "memory");
            asm volatile("prefetch.tensormap [%0];" :: "l"(&tm_g) : "memory");
            { const int t0_ = clock(); while ((int)clock() - t0_ < SDELAY) __nanosleep(40); }
            if (lead) {
                int n = 0;
#pragma unroll 1
                for (int i = 0; i < 5; i++) {
                    if (G < 56) {
#pragma unroll 1
                        for (; n < ((FILL >> (4 * i)) & 15); n++) {
                            if (n >= IDEPTH) mbar_wait(bars + (B_FULL + n - IDEPTH) * 8);
                            if (n == 3) mbar_wait(bars + B_TFREE * 8);
                            load_chunk(n);
                        }
                    }
                    if (i < 4)
                        asm volatile("cp.async.bulk.tensor.4d.shared::cluster.global.mbarrier::complete_tx::bytes [%0], [%1, {%3, %4, %5, %6}], [%2];"
                                     :: "r"(sm + SM_SLAB + (i & 1) * 16384 + (i >> 1) * 8192), "l"(&tm_x), "r"(bars + (B_SLAB + (i & 1)) * 8),
                                        "r"(G * 16), "r"(64 * (i & 1)), "r"(4 * rank), "r"(i >> 1) : "memory");
                }
                TS(20);
                if (G < 56) {
#pragma unroll 1
                    for (int i = 0; i < NPF; i++) {
                        if (i < IDEPTH) mbar_wait(bars + (B_FULL + 5 + i - IDEPTH) * 8);
                        asm volatile("cp.async.bulk.prefetch.tensor.3d.L2.global [%0, {%1, %2, %3}];" :: "l"(&tm_g), "r"(G * 64), "r"(rank * 512 + (5 + i) * 64), "r"(0) : "memory");
                    }
                    mbar_wait(bars + B_KFREE * 8); load_chunk(5);
                    mbar_wait(bars + (B_KFREE + 1) * 8); load_chunk(6);
                }
                TS(21);
            }
            __syncwarp();
        } else if (v == 1) {
            if (lead) {
                asm volatile("cp.async.bulk.shared::cluster.global.mbarrier::complete_tx::bytes [%0], [%1], 20480, [%2];"
                             :: "r"(sm + SM_TAB), "l"(p.tab), "r"(bars + B_TAB * 8) : "memory");
                asm volatile("cp.async.bulk.shared::cluster.global.mbarrier::complete_tx::bytes [%0], [%1], 1536, [%2];"
                             :: "r"(sm + SM_F2), "l"(p.tab + 1280), "r"(bars + B_TAB * 8) : "memory");
                asm volatile("prefetch.tensormap [%0];" :: "l"(&tm_d) : "memory");
            }
        } else {
            const int sw = v - 2;
            if (sw == 0) {
                uint32_t tag;
                uint4* const my_stats = p.sc->stats[q] + c * 8 + g;
                asm volatile("ld.relaxed.gpu.global.u32 %0, [%1];" : "=r"(tag) : "l"(&p.sc->epoch) : "memory");
                float ws = 0.f;
#pragma unroll
                for (int k = 0; k < 4; k++) {
                    const uint4 w = ldg128(reinterpret_cast<const uint4*>(p.wr) + 32 * k + lane);
                    ws += (blo(w.x) + bhi(w.x)) + (blo(w.y) + bhi(w.y)) + (blo(w.z) + bhi(w.z)) + (blo(w.w) + bhi(w.w));
                }
                if (q < NREP) st_relaxed128(my_stats, make_uint4(0, 0, 0, 0));
                tag = tag % 3 + 1;
                sts32(sm + SM_TOK + 8, tag);
                bar_arrive(6, 160);
#pragma unroll
                for (int o = 1; o < 32; o <<= 1) ws += __shfl_xor_sync(0xFFFFFFFFu, ws, o);
                const uint32_t tb = ((tag & 1) << 15) | ((tag >> 1) << 31);
                const uint32_t ra = sm + SM_RED + (lane >> 1) * 144 + (lane & 1) * 64;
                const uint32_t kidx = 0xFFFF - (128 * (c & 15) + 16 * (lane >> 2) + 2 * (c >> 4) + ((lane >> 1) & 1));
                touch(ws);
                bar_sync(7, 160);
                const uint4 a0 = lds128(ra), a1 = lds128(ra + 16), a2 = lds128(ra + 32), a3 = lds128(ra + 48);
#define F(v) __uint_as_float(v)
                float ss = (F(a0.x) + F(a1.x)) + (F(a2.x) + F(a3.x)), dw = (F(a0.y) + F(a1.y)) + (F(a2.y) + F(a3.y));
                float sx = ((F(a0.z) + F(a1.z)) + (F(a2.z) + F(a3.z))) + ((F(a0.w) + F(a1.w)) + (F(a2.w) + F(a3.w)));
#undef F
                ss += __shfl_xor_sync(0xFFFFFFFFu, ss, 1); dw += __shfl_xor_sync(0xFFFFFFFFu, dw, 1); sx += __shfl_xor_sync(0xFFFFFFFFu, sx, 1);
                const float mean = sx * (1.0f / 1024.0f);
                const float var = fmaxf(ss * (1.0f / 1024.0f) - mean * mean, 0.f);
                const float m = rb(mean);
                float sd; asm("sqrt.approx.ftz.f32 %0, %1;" : "=f"(sd) : "f"(rb(rb(var) + 1e-5f)));
                const float rs = rcp(rb(sd));
                const float hi = rb(rs);
                const uint32_t p0 = pack_b(m, 0.5f * hi), p1 = pack_b(0.5f * (rs - hi), rs * (dw - m * ws));
                const uint32_t o0 = __shfl_xor_sync(0xFFFFFFFFu, p0, 2), o1 = __shfl_xor_sync(0xFFFFFFFFu, p1, 2);
                const uint32_t kr = ((p1 ^ (p1 >> 31 ? 0xFFFF0000u : 0x80000000u)) & 0xFFFF0000u) | kidx;
                const uint32_t k1 = __reduce_max_sync(0xFFFFFFFFu, kr), k2 = __reduce_max_sync(0xFFFFFFFFu, kr == k1 ? 0u : kr);
                const uint32_t sl = (q & 2) ? 0x1054 : 0x5410;
                if (q < NREP) st_relaxed128(my_stats, make_uint4(prmt(p0, o0, sl), prmt(p1, o1, sl), (prmt(p0, o0, sl + 0x2222) & 0x7FFF7FFFu) | tb, g == 0 ? k1 : k2));
                TSL(9);
                { const int t0_ = clock(); while ((int)clock() - t0_ < PDELAY) __nanosleep(20); }
            }
            bar_sync(3, 192);
            const uint32_t tg = lds32(sm + SM_TOK + 8), tb = ((tg & 1) << 15) | ((tg >> 1) << 31);
            {
                const uint32_t* src = &p.sc->stats[G & (NREP - 1)][(sw * 64 + (lane >> 1)) * 8 + (lane & 1)].z;
                uint2 kz[4];
#pragma unroll
                for (int i = 0; i < 4; i++) kz[i] = make_uint2(~tb, 0);
                int it = 0;
                bool ok;
                do {
#pragma unroll
                    for (int i = 0; i < 4; i++)
                        asm volatile("{ .reg .pred p; .reg .b64 t; setp.ne.u32 p, %3, 0; mov.b64 t, {%0,%1};\n"
                                     "@p ld.relaxed.gpu.global.b64 t, [%2]; mov.b64 {%0,%1}, t; }"
                                     : "+r"(kz[i].x), "+r"(kz[i].y) : "l"(src + i * 512), "r"((kz[i].x ^ tb) & 0x80008000u) : "memory");
                    ok = __all_sync(0xFFFFFFFFu, (((kz[0].x ^ tb) | (kz[1].x ^ tb) | (kz[2].x ^ tb) | (kz[3].x ^ tb)) & 0x80008000u) == 0);
                } while (!ok && ++it < SPIN_LIMIT);
                const uint32_t a1 = max(kz[0].y, kz[1].y), b1 = max(kz[2].y, kz[3].y);
                const uint32_t h1 = max(a1, b1), h2 = __vimax3_u32(min(a1, b1), min(kz[0].y, kz[1].y), min(kz[2].y, kz[3].y));
                const uint32_t w1 = __reduce_max_sync(0xFFFFFFFFu, h1), w2 = __reduce_max_sync(0xFFFFFFFFu, h1 == w1 ? h2 : h1);
                sts64(sm + SM_KEYS + sw * 8, w1, w2);
                bar_sync(8, 64);
                const uint2 o = lds64(sm + SM_KEYS + 8 - sw * 8);
                key = sw ? __vimax3_u32(min(w1, o.x), w2, o.y) : max(w1, o.x);
                TSL(19);
            }
            const int t = (0xFFFF - (key & 0xFFFF)) & 2047;
            {
                const uint4* row = reinterpret_cast<const uint4*>(p.x + (size_t)t * 1024);
                uint4 xr[3];
                xr[0] = ldg128(row + 64 * rank + lane); xr[1] = ldg128(row + 64 * rank + 32 + lane); xr[2] = ldg128(row + 2 * G + (lane & 1));
                uint4 stk;
                int it = 0;
                do stk = ld_relaxed128(p.sc->stats[G & (NREP - 1)] + ((t >> 1) & 7) * 128 + (t >> 4)); while (((stk.z ^ tb) & 0x80008000u) && ++it < SPIN_LIMIT);
                if (lane == 0) {
                    sts32(sm + SM_TOK + 4 * sw, t);
                    if (c == 0 && sw == 0) st_relaxed32(&p.sc->epoch, tg);
                }
                const uint32_t se = (t & 1) ? 0x3232 : 0x1010;
                const uint32_t m = prmt(stk.x, 0, se), hi = bmul2(prmt(stk.z, 0, se) & 0x7FFF7FFFu, 0x40004000u), lo = bmul2(prmt(stk.y, 0, se), 0x40004000u);
                const uint32_t a = sm + SM_XSEL + lane * 32 + sw * 16;
#pragma unroll
                for (int i = 0; i < 2; i++)
                    sts128(a + i * 1024, norm2(xr[i].x, m, hi, lo), norm2(xr[i].y, m, hi, lo), norm2(xr[i].z, m, hi, lo), norm2(xr[i].w, m, hi, lo));
                proxy_fence();
                __syncwarp();
                if (lane == 0) mbar_arrive(bars + B_TOK * 8);
                if (sw == rank && lane < 2) {
                    sts128(sm + SM_XRAW + lane * 16, xr[2].x, xr[2].y, xr[2].z, xr[2].w);
                    sts128(sm + SM_XRAW + 32 + lane * 16, norm2(xr[2].x, m, hi, lo), norm2(xr[2].y, m, hi, lo), norm2(xr[2].z, m, hi, lo), norm2(xr[2].w, m, hi, lo));
                }
                __syncwarp();
                TSL(42);
            }
        }
        mbar_wait(bars + B_TOK * 8);
        const uint32_t tag = lds32(sm + SM_TOK + 8);
        {
            if (G < 56) {
                const uint32_t SMB = sm & 0x3FFFFu;
                const uint64_t dw = (uint64_t)(SMB >> 4) | (1ull << 16) | (64ull << 32) | (1ull << 62);
                const uint64_t dx = (uint64_t)((SMB + SM_XSEL) >> 4) | (2ull << 16) | (8ull << 32);
                const uint64_t dh = (uint64_t)((SMB + SM_H) >> 4) | (8ull << 16) | (8ull << 32);
                const uint64_t dw2 = dw + (tag >> 2);
                float ag[4], au[4];
                TSL(13);
#pragma unroll
                for (int n = 0; n < 8; n++) {
                    const uint64_t a = (n < 7 ? dw : dw2) + (chunk_off(n) >> 4), b = dx + n * 16;
                    mbar_wait(bars + (B_FULL + n) * 8);
                    wg_fence();
                    if (n == 0) { wg_w0(ag, a, b); wg_w0(au, a + 512, b); } else { wg_w<1>(ag, a, b); wg_w<1>(au, a + 512, b); }
#pragma unroll
                    for (int k = 1; k < 4; k++) { wg_w<1>(ag, a + 128 * k, b + 4 * k); wg_w<1>(au, a + 512 + 128 * k, b + 4 * k); }
                    wg_commit();
                    bool any = false;
#pragma unroll
                    for (int i = 0; i < 5; i++) any |= ((REFILL >> (4 * i)) & 15) == n;
                    if (any) {
                        if (n <= 5) { wg_wait<1>(); bar_sync(4, 128); }
                        if (v == (n & 3)) {
#pragma unroll
                            for (int i = 0; i < 5; i++) if (((REFILL >> (4 * i)) & 15) == n && lead) load_chunk(7 + i);
                            __syncwarp();
                        }
                    }
                    if (n == 4) TSL(4);
                    if (n == 7) TSL(34);
                }
                wg_wait<0>();
                touch(ag); touch(au);
                TSL(14);
                if (q == 0) {
#pragma unroll
                    for (int r = 0; r < 2; r++) {
                        const uint32_t dst = mapa(sm, r), o = dst + SM_PAIR + rank * 1024 + v * 256 + g * 32;
                        st_async4(o, __float_as_uint(ag[0]), __float_as_uint(ag[1]), __float_as_uint(ag[2]), __float_as_uint(ag[3]), dst + SM_BAR + B_PAIR * 8);
                        st_async4(o + 16, __float_as_uint(au[0]), __float_as_uint(au[1]), __float_as_uint(au[2]), __float_as_uint(au[3]), dst + SM_BAR + B_PAIR * 8);
                    }
                }
                mbar_wait(bars + B_PAIR * 8);
                {
                    const uint32_t o = sm + SM_PAIR + v * 256 + g * 32 + q * 4, og = o + (p.up_first ? 16 : 0), ou = o + (p.up_first ? 0 : 16);
                    const float gs = rb(__uint_as_float(lds32(og)) + __uint_as_float(lds32(og + 1024)));
                    const float us = rb(__uint_as_float(lds32(ou)) + __uint_as_float(lds32(ou + 1024)));
                    const float hv = rb(siluf_(gs)) * us;
                    const uint32_t hd = sm + SM_H + (2 * v + (q >> 1)) * 128 + (q & 1) * 32 + g * 2, hb = pack_b(hv, hv);
                    sts16(hd, hb); sts16(hd + 64, hb);
                }
                proxy_fence();
                bar_sync(4, 128);
                TSL(15);
#pragma unroll
                for (int n = 0; n < 4; n++) {
                    const uint64_t a = dw2 + (chunk_off(8 + n) >> 4);
                    float d[2][4];
                    mbar_wait(bars + (B_FULL + 8 + n) * 8);
                    if (n == 3) TSL(24);
                    wg_fence();
                    wg_w0(d[0], a, dh); wg_w0(d[1], a + 512, dh);
#pragma unroll
                    for (int k = 1; k < 4; k++) { wg_w<1>(d[0], a + 128 * k, dh + 16 * k); wg_w<1>(d[1], a + 512 + 128 * k, dh + 16 * k); }
                    wg_commit();
                    wg_wait<0>();
#pragma unroll
                    for (int i = 0; i < 2; i++) {
                        touch(d[i]);
                        st_relaxed32(my_part + (2 * n + i) * 8 * 56 * 16, (__float_as_uint((q & 2) ? d[i][2] : d[i][0]) & ~3u) | tag);
                    }
                }
                TSL(16);
            } else {
                mbar_wait(bars + B_STG * 8);
            }
            {
                const uint2* src = reinterpret_cast<const uint2*>(p.sc->part) + c * 448 + v * 112 + lane;
                uint2 pv[4];
#pragma unroll
                for (int i = 0; i < 4; i++) pv[i] = make_uint2(i == 3 && lane >= 16 ? tag : 0u, i == 3 && lane >= 16 ? tag : 0u);
                for (int it = 0; it < SPIN_LIMIT; it++) {
#pragma unroll
                    for (int i = 0; i < 4; i++)
                        if (((pv[i].x ^ tag) | (pv[i].y ^ tag)) & 3)
                            asm volatile("ld.relaxed.gpu.global.v2.u32 {%0,%1}, [%2];" : "=r"(pv[i].x), "=r"(pv[i].y) : "l"(src + 32 * i) : "memory");
                    uint32_t bad = 0;
#pragma unroll
                    for (int i = 0; i < 4; i++) bad |= (pv[i].x ^ tag) | (pv[i].y ^ tag);
                    if (__all_sync(0xFFFFFFFFu, (bad & 3) == 0)) break;
                }
#define F(v) __uint_as_float(v)
                sts64(sm + SM_XSEL + (tid & 127) * 8, __float_as_uint((F(pv[0].x) + F(pv[1].x)) + (F(pv[2].x) + F(pv[3].x))),
                      __float_as_uint((F(pv[0].y) + F(pv[1].y)) + (F(pv[2].y) + F(pv[3].y))));
            }
            if (v != 2 + rank) {
                bar_arrive(8, 128);
            } else {
                const int t = (0xFFFF - (key & 0xFFFF)) & 2047, col = lane & 15;
                const float sg = rb(sigmoidf_(F((key & 0x80000000u) ? (key & 0x7FFF0000u) : (~key & 0xFFFF0000u))));
                const float xn = blo(lds16(sm + SM_XRAW + 32 + col * 2)), xv = blo(lds16(sm + SM_XRAW + col * 2));
                mbar_wait(bars + B_FIX * 8);
                const float s = blo(lds16(sm + SM_FIX + col * 2));
                __nv_bfloat16* const op = p.out + (size_t)t * 1024 + G * 16 + col;
                sched_fence();
                bar_sync(8, 128);
                TSL(25);
                float y8[8];
#pragma unroll
                for (int i = 0; i < 8; i++) y8[i] = F(lds32(sm + SM_XSEL + i * 128 + lane * 4));
#undef F
                float y = ((y8[0] + y8[1]) + (y8[2] + y8[3])) + ((y8[4] + y8[5]) + (y8[6] + y8[7]));
                y += __shfl_xor_sync(0xFFFFFFFFu, y, 16);
                const float z = rb(xn + rb(rb(y) * sg));
                if (lane < 16) *op = __float2bfloat16(xv + rb(s * rb(siluf_(z))));
                TSL(26); TG(29);
            }
        }
    }
    }
}

__device__ __align__(128) const uint32_t g_tab[5504] = {
0x2fff3000,0x2e7c2fd4,0x2fc92fd4,0xad72af5a,0x2ff82ffc,0x230e2c07,0x2faf2fbc,0x217ea934,0x2fed2ff4,0xad4da8d5,0x2f912fa0,0x2e5e2bb7,
0x2fdd2fe6,0xb000af46,0x2f6e2f80,0x2fdd2fc9,0x2ff42fff,0x2e1f2fc9,0x2e1f2e7c,0xa875ad72,0x2fbc2fdd,0x9fd92a4e,0x2d4d2dba,0x2cd825db,
0x2f5a2f91,0xaeb5ac07,0x2c5d2cd8,0x30002f30,0x2ed02f1a,0xaf80aff4,0x2aaa2bb7,0x2cb02f1a,0x2fdd2ffc,0x2dba2fbc,0x2a4e2c07,0x25dba934,
0x2f462fa0,0xa7652875,0x25152875,0x2f802d27,0x2e3f2ed0,0xafa0ad72,0xa17e1cb6,0x2e3f2fe6,0x2cd82d96,0xadfeafd4,0xa934a6a1,0xa44e29f1,
0x2fbc2ff8,0x2d4d2faf,0x9fd9230e,0x2cd8217e,0x2e992f46,0xaa4e2515,0xaa4ea765,0x2fd42f80,0x2cb02dba,0xafffae99,0xad72ac5d,0x27652dba,
0x28752b05,0xab5eaee9,0xaf1aae5e,0xae3fa934,0x2f912ff4,0x2cd82fa0,0xac07a8d5,0x2f302bb7,0x2dba2ed0,0xac5d1cb6,0xae99ad72,0x2dba2fe6,
0x29932c5d,0xafc9af6e,0xafe6af6e,0xaaaa25db,0xa17e244e,0xa30ead4d,0xafafaffc,0xaff8aee9,0x2f5a2fed,0x2c5d2f91,0xaeb5ad4d,0x30002e5e,
0x2cb02e3f,0xad72a17e,0xafffafa0,0x27652e3f,0x217e2993,0xaf02afe6,0xaf02afc9,0xaf1aaaaa,0xab05a5db,0x2814aa4e,0xac07adba,0xad4dafdd,
0x2f1a2fe6,0x2bb72f80,0xaff4af46,0x2f1a2fc9,0x2b052d96,0xae5ea6a1,0xaee9afd4,0xa93429f1,0xa5db244e,0xadbaaffc,0xaa4ead4d,0xafddaee9,
0xaddcabb7,0x2cb0a17e,0x2765a17e,0x1cb6ad00,0x2ed02fdd,0x2aaa2f6e,0xaf80b000,0x2cb02fdd,0x28752cd8,0xaf1aa934,0xab5eadfe,0xae3fa44e,
0xab05a17e,0xac07afaf,0x2814a30e,0xad4daff8,0xaf6eaddc,0x2eb52765,0x2eb52cb0,0x2dba1cb6,0x29932f5a,0xa7652e99,0x25152e99,0x2aaaad96,
0xafa0ab05,0xabb7afed,0xaff4acd8,0x28d52ffc,0xa814af02,0x2f912d27,0x9fd9ae1f,0xaee9ae3f,0x2fd42c32,0xaf5a1cb6,0x30002d72,0x2fd42515,
0x28752f46,0xa8d52e7c,0xa8d52c32,0x2e3fa993,0xafedac5d,0xa934b000,0xaf30af5a,0xa8142eb5,0x1648adfe,0x2e992e5e,0x2c87a814,0xa9f1affc,
0x2fe62e1f,0xafffa875,0x2ddc2ff4,0x2ed02e1f,0x26a12f30,0xa9f12e5e,0xad96244e,0x2fd41fd9,0xafffad27,0xa515aff4,0xac32aff4,0xaddc2b5e,
0x2875acb0,0x2d272f46,0x2fa02993,0x2875aed0,0x2ee92f6e,0xaf91ac87,0x1fd92e99,0x28143000,0x244e2f1a,0xab052e3f,0xaf91a875,0x2fbc2b5e,
0xafd4addc,0x1648afc9,0x1648ae7c,0xafdd9cb6,0x2c32aa4e,0x2aaa2fd4,0x2f802e99,0x2e7caa4e,0x2d002ffc,0xae1fae5e,0xad272814,0xabb72dfe,
0x1fd92f02,0xac072e1f,0xafedad27,0x2dfe2e3f,0xaf6eae7c,0x25dbaf80,0x2c5daaaa,0xaf6eac32,0x2ddca5db,0x25153000,0x2c323000,0x2fff26a1,
0x28d52fbc,0xabb7af91,0xaff4ab05,0xafa0244e,0x96482ee9,0xac872dfe,0xae99af30,0x29f12fbc,0xaed0af02,0x2993af1a,0x2f46217e,0xacb0af02,
0x2f1a1cb6,0xa30e2fc9,0xa30e2e7c,0x2e1f2ddc,0x9fd92eb5,0xa44eb000,0xae5eaf5a,0xaf30ac5d,0xa17e2ed0,0xad002ddc,0xabb7afff,0xa17e2fe6,
0xadfeaf6e,0x2c07ae99,0x2fed2c87,0x9fd9b000,0x2fd42814,0xa9f12f30,0xad962934,0x26a12fed,0xaaaa2d00,0x2765afa0,0xa515afa0,0xa993afaf,
0xa5152eb5,0xad722dba,0x9cb6af6e,0xac322eb5,0xad00afbc,0x2d27adfe,0x2e1f2f30,0x2bb7aee9,0x2ffc2b5e,0xacd82e3f,0xafeda875,0xab052f1a,
0xadba2993,0x2c87ae7c,0x2c87ac32,0x2a4eaf46,0xaddc2d96,0xafe62c5d,0xaed02c5d,0x2fffa9f1,0x2e1fad4d,0x2e3f2814,0x2f02ac07,0xad27ab05,
0xae5e2d00,0x9fd9af1a,0xaf302b5e,0xa44e2faf,0x2e99acb0,0xad962f80,0x2f5aaaaa,0x2e99aed0,0xae3f2d72,0xaff82c32,0xaff82515,0x2f021cb6,
0x2ee9ac87,0x2d4d29f1,0x2ffc9648,0xa44eae99,0xaf6e2b05,0x26a1afbc,0xafd4a44e,0xadba2f91,0x2fc9a8d5,0xaf462e3f,0x2f802875,0x2fe6a8d5,
0xae992d4d,0xb0002c07,0xaf6ea814,0x2c872b05,0x2f80ab5e,0x2c322bb7,0x2e7c2bb7,0x2aaaaff8,0xaff42765,0x2b5eafff,0xad27ad72,0xaff42cb0,
0x2fed1648,0xaffc2c5d,0x2b052eb5,0x2cd82a4e,0xaee92d27,0xaffc2bb7,0xad4dad00,0x244e2e1f,0x2fdda993,0x29f12cb0,0x29f12ed0,0x2eb5af46,
0xafe61648,0x2d72afdd,0x9cb6afd4,0xaed01648,0x2f022934,0xafa02814,0xa8d52fed,0xa30e2f30,0xaf302d00,0xafed2b5e,0xa814af1a,0xa9342faf,
0x3000a765,0x26a12d72,0xa5db2fff,0x3000acb0,0xaf46a6a1,0x2ed0af5a,0x2cb0af5a,0xa993ac87,0x2d272cd8,0xae3f9fd9,0xaf022d4d,0xae1f2fbc,
0xaf6e2cd8,0xafd42b05,0x26a1affc,0xadba2fed,0x2fe6a30e,0x1cb62e1f,0xad722f1a,0x2ed0a30e,0xae1faaaa,0x2fafae7c,0x2fafac32,0x28d5af80,
0x29342e99,0xac07a9f1,0xafbc1648,0xaffc2c87,0xafa02cb0,0xafaf2aaa,0x2d00af80,0xafa02ed0,0x2f911648,0xa44e2eb5,0xafbc2c5d,0x2b052a4e,
0xac87acd8,0x3000ad4d,0x2f6e1fd9,0x2e99afbc,0x9cb62faf,0xa515ad27,0xac32ad27,0xad72a30e,0xafc92c87,0xaf802a4e,0x2f46adba,0xafe62c87,
0x2f02244e,0xa8d52f30,0xafa01fd9,0xa30e2e5e,0xa934ae1f,0x2fbcabb7,0x2c072d00,0x2ffcad27,0xaa4e2fff,0x26a1aed0,0x26a1afe6,0x1648addc,
0xaf4629f1,0xac3225db,0xae7c25db,0x29931648,0xab5e2f91,0xafaf2e5e,0xad002fed,0x2f1aad4d,0x2ee9a875,0xaf302ff8,0x2dfea17e,0x2fbcaff4,
0x2c5dafc9,0xa9f12d72,0x2d96afff,0x2c5dae7c,0xaf022993,0xab5e2515,0xab5ea765,0xa30e2aaa,0xacd82fd4,0xaf302dba,0xaf912f6e,0x2c07a6a1,
0x2d969fd9,0xafdd2fed,0x25db2c07,0x2f5aadfe,0x2e7caff8,0xad722f02,0x2fffae3f,0x2fc9aff8,0xaeb52934,0xaa4e244e,0x9648acd8,0xac5d2dfe,
0xaddc2ff8,0xae7c2d00,0xafc92d00,0x9cb628d5,0x2bb72515,0xaff82f80,0xab5e2f46,0x2bb7a765,0x2fbcaf5a,0xaf302fdd,0x2dfea5db,0x2ee9ad96,
0xae5e28d5,0xa934230e,0x2b05af02,0xaee92fa0,0xaeb52fff,0xad962c32,0xad962515,0xac872ddc,0x276529f1,0xaf802eb5,0xaf462fdd,0xa51529f1,
0x2ff4adfe,0xaff82fed,0x217e2c07,0x28759fd9,0xadfe2875,0xa814217e,0x2e5eaff8,0xaffc2ff4,0xaf5a2fe6,0xac872aaa,0xa6a1a993,0xaf5a2fc9,
0x9cb62c87,0xae7c2d96,0xafc92d96,0xaddc2eb5,0x2f1aac07,0xafaf2f30,0xad002f91,0xab5e2cd8,0xad962814,0xa5db1fd9,0x2fddaf91,0xaf5a2ee9,
0xafc92faf,0xaaaa28d5,0x2993ae1f,0xafe62faf,0xa8d52ddc,0xad002c32,0xad002515,0xaff82fff,0x2d4da6a1,0xae5e2dba,0xafed2f6e,0xaf912fd4,
0xad272765,0xa30e1cb6,0x2fafaddc,0xad272cb0,0xaffc2f5a,0xa81425db,0x2e5eafdd,0xadfe2d96,0xac5d2ee9,0xaa4e2934,0x9648ab05,0xaeb52e5e,
0x2993230e,0xac322b5e,0xae7c2b5e,0xaf462f02,0xacb026a1,0x9cb61648,0x2ddcaa4e,0xa76526a1,0xaff42ee9,0xa17e1fd9,0x2ff8af91,0xa8752814,
0xadfe2fa0,0xa44e230e,0x2cd8af02,0xa93428d5,0x96482aaa,0xa5db2515,0xa5dba765,0xa9f12993,0x2f462f5a,0x2c322e99,0x2e7c2e99,0xa993ad96,
0x2f1a2f30,0xa875244e,0x2e3f2e5e,0x2b5e1fd9,0x2ee92f02,0xaf30ad27,0x2dfe2e1f,0x2fbc2e3f,0x2eb52ed0,0xaf6eafff,0x2dba2ddc,0x2eb52fe6,
0x28752993,0xa8d52515,0xa8d5a765,0x2e3f2aaa,0x244e26a1,0xaf91ad96,0xab05a9f1,0x2fbc2fd4,0x96481fd9,0xae99afed,0xac87ac07,0x29f12dfe,
0xa515a17e,0x9cb6abb7,0xad72ad00,0xac32a17e,0xac5dab05,0xaf5aacd8,0xb000afed,0x2eb52ffc,0xaddcad27,0xae7caff4,0xafc9aff4,0x9cb62b5e,
0xaf02ae7c,0x217eaaaa,0xaf1aaf80,0xaf02ac32,0xafbcaf6e,0x2f302c87,0xadfeae99,0xaee9b000,0xafedafa0,0xaf30aff4,0xa934abb7,0xa81428d5,
0xafd4afff,0x1648ac32,0x1648a515,0xafddaddc,0xaed0af6e,0x2f462c5d,0x299325db,0xacb0af6e,0xad00adfe,0x2e1f2fed,0x2d272c07,0x2bb79fd9,
0xadfeaf02,0xa814ae1f,0x2e5e2d27,0xaffcae3f,0xaa4eacb0,0x2e992993,0x2fd42f46,0xaa4eaed0,0x1cb6a5db,0x2e7c3000,0x2fc93000,0x2ddc26a1,
0x2b5e2814,0xa8752934,0x2e3f2f30,0x2f1a2fed,0x1648a814,0x2c879fd9,0x2e992f91,0xa9f1aee9,0x2c322875,0x2f802fa0,0x2aaa2d27,0x2e7c2875,
0x2f1a2ddc,0xa30e2c32,0xa30e2515,0x2e1f2fff,0x2ffc2fd4,0xafedad96,0xacd8a9f1,0xab0526a1,0x2e1f2c32,0x2ff42d72,0xa8751cb6,0x2e1f2515,
0x2ffc2f6e,0x28142e99,0xae5eac87,0x2dfe3000,0x2eb52fbc,0xaf5aab05,0xb000af91,0xac5d244e,0x29932d00,0xac32afa0,0xae7cafa0,0xaf46afaf,
0x2fe62fd4,0x2ddc3000,0xafffaf5a,0x2ed02fd4,0x2d002ee9,0xad271fd9,0xae1faf91,0xabb72814,0x9fd928d5,0xae5eaff4,0xa44eabb7,0xaf30afa0,
0xadbaaaaa,0x2c87a515,0x2c872765,0x2a4ea993,0x9cb62d96,0xacb02c5d,0xa7652c5d,0x2ddca9f1,0xaff8adfe,0xa30eafbc,0xafafaee9,0xa17e2f30,
0x244ead00,0x2dfe2f1a,0x2934ab5e,0xacd8afaf,0x2fdd2e7c,0xb000a993,0x2f6e2f46,0x2fdd2c32,0xae3f9cb6,0xaff8a765,0xaff8acb0,0x2f022ddc,
0xac07afdd,0x2dfeaa4e,0x1fd9adba,0xafeda5db,0x2f6e2934,0xa6a12ee9,0x2fd42e5e,0x2dbaab05,0x27652f1a,0xaaaaaff4,0xa9932bb7,0xa5152f1a,
0xafddadfe,0xadbaaee9,0xaa4eafbc,0xa5db2f30,0x2aaaab5e,0x2fc92bb7,0x2fe62bb7,0xa993aff8,0x2e3f2fc9,0xafa01cb6,0xa17e2ddc,0x2e3f2e7c,
0xae5e9648,0x2d4dac5d,0xaf91aeb5,0xafedaa4e,0xac07aff8,0x1fd9afaf,0x2dfea30e,0xafeda17e,0x2fdd2aaa,0x29f12fe6,0x29f12fc9,0x2eb5a993,
0xa5152dba,0xaddcae99,0xafffac5d,0xac322dba,0xaf02af30,0x2fa02c07,0x28d5acd8,0x230eaf91,0x2934ad00,0x2e5eab5e,0x2ee92f1a,0xab05afaf,
0x2dba2fc9,0xac5d2ddc,0xae991cb6,0x2dba2e7c,0xaf80a6a1,0x2765af5a,0xa515af5a,0xaf46ac87,0x217eae5e,0x230e2ffc,0x2faf2dfe,0x2ff82814,
0x2f6e244e,0x2fd42934,0xa6a12dfe,0x2dbaacd8,0xa5152e3f,0xafffa17e,0xaddcafa0,0xac322e3f,0xae1faf80,0x2fafa515,0x2faf2765,0x28d5af46,
0x2f9125db,0xaee92a4e,0xa8142dba,0x9fd92fdd,0x2f1a2e7c,0x2bb72f46,0xaff4a993,0x2f1a2c32,0xaf309648,0xacd8aeb5,0x2c07ac5d,0xaf91aa4e,
0x25dbae5e,0x2dba2dfe,0x2a4e2ffc,0x2fdd2814,0x2d722faf,0xae7cad27,0xafc9ad27,0xafffa30e,0x27652fdd,0xa9932f6e,0xaaaab000,0xa5152fdd,
0xaf02ae5e,0x28d5af91,0x2fa02d4d,0x230eafed,0x2f91217e,0xa8142faf,0xaee9230e,0x9fd92ff8,0xaa4e2d72,0x26a1afc9,0x26a1ae7c,0x1648afff,
0xaf8029f1,0xafc925db,0xafe625db,0x2f461648,0x2fa0a934,0x2bb72cd8,0x2ff4a44e,0xa8d5adfe,0xafbc2875,0x2934aff8,0xaffc217e,0xac072ff4,
0x2fd4a765,0xaf5a2ddc,0x30009cb6,0x2fd4acb0,0xaf02aaaa,0xab5eacb0,0xab5eaed0,0xa30e2f80,0x2e5e2c5d,0xab053000,0x29342f5a,0x2ee9aeb5,
0xad96ad4d,0x2fddacd8,0xa5dbafbc,0xaf5a1fd9,0x2cb02e1f,0xaddca875,0x1cb62ff4,0x27652e1f,0xa6a1af91,0x29f1afed,0x2d96ae5e,0xafd42d4d,
0x9cb62ff8,0xafe62d00,0xaed02d00,0x2d7228d5,0x2875afe6,0x2d272993,0x2fa0aaaa,0x2875afc9,0xac072f5a,0x2934afdd,0xaffc25db,0xafbc2d96,
0x2cd8af1a,0x2f91ae3f,0x2f302875,0xac07ab5e,0xaeb52d72,0xad96a765,0xad96acb0,0xac872fff,0x2fc9aa4e,0xa9932fd4,0x2aaa2e99,0x2fe6aa4e,
0xaff41fd9,0x2ff8acd8,0xa17eafbc,0xa875ad4d,0x2ffca875,0x2ee9a17e,0xa44e2ff8,0x2d4daff4,0xaf6ea515,0x25dbaf46,0x2c5daf80,0xaf6e2765,
0x2d722c87,0xafe62d96,0xaed02d96,0x9cb62eb5,0xa8d5aee9,0x2bb72b05,0x2ff4a934,0x2fa0ae5e,0x2d962c07,0x25db2d4d,0xafdd2b05,0x2f5aa814,
0xa765af02,0x2f46af1a,0x2f80217e,0x2515af02,0xa8d52fff,0xad00a765,0xad00acb0,0xaff82d72,0x2dfeaeb5,0xacd83000,0x244e2f5a,0x29342c5d,
0xa17e2fc9,0xad002fff,0xabb7ad72,0xa17e2e7c,0x2d4daf5a,0x2ee9a5db,0xa44e2fdd,0x2ffcad96,0xafd42c07,0x29f1af91,0x2d96af30,0xa6a1acd8,
0x2f46230e,0xafc92b5e,0xafe62b5e,0xaf802f02,0xae7c2eb5,0xafff2dba,0x2d72af6e,0xafc92eb5,0x2ff4a814,0x217e2d4d,0xaff82b05,0x28752c07,
0xad4dab5e,0x2fedae3f,0x2e5e2875,0x2f91af1a,0x96482f80,0xa5dbacb0,0xa5dbaed0,0xa9f1aaaa,0xad729648,0xa515a6a1,0xac32a6a1,0x9cb62a4e,
0xae1f2ffc,0xae3f2c07,0xaf022fbc,0x2d27a934,0x2cd8230e,0xaffc2fa0,0x2b0528d5,0x2fedaf02,0x2e99afe6,0xad962f46,0x2f5aaf80,0x2e99afc9,
0x230eaddc,0x2d27aed0,0x2d27afe6,0xafaf2fff,0xafbc2c87,0x1fd9a9f1,0xad4d1648,0xacd82e99,0xaa4e2f30,0xac5d2814,0xaeb52fed,0x96482934,
0x2ed0a8d5,0xaf802e3f,0x2aaa2875,0x2cb0a8d5,0x2e99affc,0x3000afbc,0x2f6eac07,0xac872934,0xa993a8d5,0x2ed0afaf,0x2cb0afaf,0xaf462e1f,
0xaff42ed0,0x2b5ead72,0xad271cb6,0xaff42fe6,0xa44e2dba,0x9fd9a6a1,0xaf302fd4,0xae5e2f6e,0x2fbcad27,0x2d4dabb7,0x9fd92d00,0x2cd8ae1f,
0x2c87af80,0x2f5aae7c,0x2f5aac32,0x26a1aaaa,0xacb01648,0x2fffafdd,0x2d72afd4,0xa7651648,0xafaf2f91,0x2f1aafbc,0xab5ea44e,0xad002b05,
0x2b05230e,0xa44e28d5,0xafbc2fa0,0x2f91af02,0x3000aed0,0x26a19cb6,0xa5db2d72,0x3000afe6,0x2aaaaeb5,0x2c32a9f1,0x2e7ca9f1,0x2f80afdd,
0xad27244e,0x2e3fad4d,0x2f02affc,0x2e1faee9,0xaa4e2e5e,0xaeb52f30,0xac5d1fd9,0x9648244e,0x2cb0a30e,0xad722e1f,0xafff2f1a,0x2765a30e,
0x2ff8af46,0xabb72cb0,0xabb72ed0,0x2b5ea993,0x2b05ae99,0xa81429f1,0x2c079648,0x2d4dac87,0xafa02fe6,0xafaf2f80,0x2d00af46,0xafa02fc9,
0xa9342dba,0xafed2fd4,0xa814a6a1,0xaf302f6e,0x2c87a44e,0xb0002ffc,0xaf6e2d4d,0xae992ee9,0x2fffaf02,0xafe62ff8,0xaed02ff8,0xaddc2e3f,
0xaed02c87,0xaaaa2a4e,0x2f80adba,0xacb02c87,0xafaf2fed,0xab5e2b05,0x2f1aaffc,0xad002cd8,0xab052e1f,0xac072bb7,0x2814ad00,0xad4d2d27,
0x29f11cb6,0xac5d2c32,0xac5d2515,0xad962d72,0x2d722d96,0x25152c5d,0x2c322c5d,0x1cb6a9f1,0x2d272d4d,0xad00a814,0x2bb72c07,0x2e1f2b05,
0x2cd82d00,0xaffcaf1a,0x2b052b5e,0x2fed2faf,0x2c872cb0,0xadbaaf80,0x2a4e2aaa,0x2c872ed0,0xae3faddc,0xaff8aed0,0xaff8afe6,0x2f022fff,
0xaee9ae99,0xad4daf6e,0xaffcb000,0x244e2c87,0xaf6eaf30,0x26a1a814,0xafd4afed,0xadbaa934,0xafc9afa0,0x2f462d00,0xaf80afaf,0xafe6afa0,
0xac87ad4d,0x9648ac07,0x29f12814,0xae99ab05,0xa993ab5e,0x2ed02bb7,0x2cb02bb7,0xaf46aff8,0xa30ea765,0x2f1a2fff,0x2e1f2d72,0xa30eacb0,
0x244e1648,0x1fd92c5d,0x2f302eb5,0x2e5e2a4e,0x2ee92e1f,0x2ffc2f02,0x2d4d2e3f,0xa44ead27,0x2fdd2f80,0x29f12e7c,0x29f12c32,0x2eb52aaa,
0x2fe63000,0xad72a5db,0x1cb626a1,0x2ed03000,0x2f022f91,0xafa0afbc,0xa8d5a44e,0xa30e2b05,0x2b052d00,0xa44e2b5e,0xafbcaf1a,0x2f912faf,
0x16482765,0xafd4ad72,0xafddafff,0x16482cb0,0xaaaaa6a1,0xac32af5a,0xae7caf5a,0xaf80ac87,0xae1facd8,0x2d001fd9,0xabb7ad4d,0xad27afbc,
0xaf6eae5e,0xafd4af30,0x26a19fd9,0xadbaa44e,0xafe6aff4,0x9cb6ad27,0x2d722b5e,0xaed0aff4,0xae1faf46,0x2faf2cb0,0x2faf2ed0,0x28d5a993,
0xa934ac87,0x2c072f6e,0x2fbc3000,0x2ffc2e99,0xa8d5acb0,0x2875aaaa,0x2e3f2f80,0xa8d5aed0,0x29341648,0x2fed2eb5,0x28142c5d,0x2f302a4e,
0x2e992cd8,0x16482d4d,0xa9f19fd9,0x2c872fbc,0x2fff2faf,0xafe6ad27,0xaed0ad27,0xaddca30e,0x2fc92e99,0x2f802f5a,0xaf46ad96,0x2fe62e99,
0x2f022fed,0xa8d52b05,0xafa0affc,0xa30e2cd8,0x29342d27,0xafbcaf02,0xac07ae3f,0xaffcae1f,0xaa4e9cb6,0x26a1ac32,0x26a1a515,0x1648ad72,
0xaaaa29f1,0xaed025db,0xacb025db,0x2f801648,0xaf1aaf91,0x2875ae5e,0xae3fafed,0xab5e2d4d,0x2c07a875,0x2b052ff8,0x2d4da17e,0xa814aff4,
0x2eb52fc9,0xaf6ead72,0x2dba2fff,0x2eb52e7c,0xaf02af80,0xab5eafe6,0xab5eafc9,0xa30e2f46,0x2cd8a6a1,0x2f302d96,0x2f9129f1,0xac07afd4,
0x2d962ffc,0xafdda44e,0x25db2ee9,0x2f5a2d4d,0xae7ca17e,0x2d72abb7,0xafffad00,0xafc9a17e,0x2c5da934,0x2f5aa44e,0x30002cd8,0xaeb5adfe,
0x2d722ff8,0xacb02d00,0xa7652d00,0x2fff28d5,0xaf02a515,0x217eaf80,0xaf1aaf46,0xaf022765,0xa814af5a,0x2b052fdd,0x2d4da5db,0x2c07ad96,
0x2e5e2fa0,0x29342ff4,0xab052bb7,0x2ee9a8d5,0xaeb59cb6,0xad96aed0,0xad96afe6,0xac872d72,0xa765af6e,0x2f802c5d,0x2f4625db,0x2515af6e,
0x2ff42d4d,0xaff8a44e,0x217e2ee9,0x28752ffc,0xad4d2875,0xafbc217e,0xacd8aff8,0x1fd92ff4,0xaa4eafe6,0x2e99aaaa,0x2fd42993,0xaa4eafc9,
0x2fff2c87,0xacb02d96,0xa7652d96,0x2d722eb5,0xab5e2c07,0x2875af30,0xae3faf91,0xaf1aacd8,0xad96afbc,0xa5dbaffc,0x2fdd2934,0xaf5aac07,
0x2fc92875,0x2aaa2fa0,0xa9932d27,0x2fe62875,0xa8d52d72,0xad00aed0,0xad00afe6,0xaff89cb6,0xad4dafd4,0x2e5e2d96,0x2fed29f1,0x2f91a6a1,
0x2e1fa765,0x2ff49cb6,0xa8752ddc,0x2e1facb0,0x1fd92f5a,0xafbc25db,0xacd8afdd,0xad4d2d96,0xaeb5aee9,0x2f5aa934,0x30002b05,0x2c5dae5e,
0x2f80230e,0xaed02b5e,0xacb02b5e,0xaaaa2f02,0x2cb02fd4,0x1cb63000,0xaddcaf5a,0x27652fd4,0xaff4ac07,0xa17eaffc,0x2ff82934,0xa875afbc,
0x2dfea8d5,0x244e2ff4,0xacd82bb7,0x29342fa0,0x96482f46,0xa5dbafe6,0xa5dbafc9,0xa9f1af80,0xafff9648,0xae7ca6a1,0xafc9a6a1,0x2d722a4e,
0x2ff81fd9,0x230e2ee9,0x2faf2814,0x217eaf91,0xafeda30e,0x2d4dafa0,0xaf91a8d5,0xae5e2f02,0x2fdd2515,0xb0002aaa,0x2f6e2993,0x2fdda765,
0x230eafff,0x2d27afc9,0x2d27ae7c,0xafaf2d72,0xa8142fdd,0xaffc2a4e,0xadfe2dba,0x2e5e25db,0x2a4eaf91,0x2c5d2c07,0x2eb5acd8,0x1648af30,
0xac322f1a,0x2993aff4,0xaf462bb7,0xae7c2f1a,0x2fdd1fd9,0x2dba2814,0x2a4e2ee9,0x25dbaf91,0xaf46a8d5,0x2765afaf,0xa515afaf,0xaf802e1f,
0x2e3f2c32,0xafa02ddc,0xa17e2fff,0x2e3f2515,0xacd8adba,0x2dfe26a1,0x2934afd4,0x244eaf6e,0xa8142ff8,0xadfe2faf,0xaffc230e,0x2e5e217e,
0x2c87af46,0x2f5aa515,0x2f5a2765,0x26a1af80,0xae7c2dba,0x9cb6ae99,0xaddcac5d,0xafc92dba,0x2fafab05,0xaf1a2ee9,0x2b5e2e5e,0x2d002934,
0xaf91a30e,0xacd8a8d5,0x2c07afa0,0xaf302f02,0x2dba2c32,0xac5d2fff,0xae992ddc,0x2dba2515,0xa993aeb5,0x2fc9a9f1,0x2fe6a9f1,0x2aaaafdd,
0xa17e2fed,0xa30eadfe,0xafaf9fd9,0xaff82c07,0x2a4eafed,0x2eb5af91,0x2c5d2d4d,0x1648ae5e,0xae7c2e3f,0xaddca17e,0x9cb6afa0,0xafc92e3f,
0x2ff8a993,0xabb72fe6,0xabb72fc9,0x2b5e2aaa,0xaf30a5db,0x2fbcaa4e,0x2ee9adba,0x2dfeafdd,0x2f1a2515,0x2bb72993,0xaff42aaa,0x2f1aa765,
0xab05adba,0x2e5eafd4,0x2ee926a1,0x2934af6e,0xa5db2fed,0xadba9fd9,0xaa4eadfe,0xafdd2c07,0x2ddcaf02,0xacb02ff8,0xa7652ff8,0x9cb62e3f,
0xac322fdd,0xaf462f6e,0x2993b000,0xae7c2fdd,0x2fafacd8,0x2b5e2934,0xaf1a2dfe,0x2d00244e,0xaf30a17e,0x2ee9afaf,0x2fbca30e,0x2dfeaff8,
0x29f12ddc,0xac5da765,0xac5dacb0,0xad969cb6,0xa993aa4e,0x2765ac87,0xa515ac87,0xaaaa2dba,0xafa02f30,0xabb7244e,0xaff42e5e,0x28d51fd9,
0x28142bb7,0xaf912e1f,0x1fd92d27,0x2ee9ad00,0x2fd4aed0,0xaf5a2fff,0x3000addc,0x2fd4afe6,0x2fafaf46,0x2fa0ae7c,0x2fa0ac32,0xad002993,
0xa44eac5d,0x2f91b000,0x2b05af5a,0xafbc2eb5,0xb0002dfe,0x2c87ae5e,0xae992814,0xaf6e2ffc,0xa5152e1f,0x9cb6a875,0xad722ff4,0xac322e1f,
0x26a12b05,0xa9f12cd8,0xad962fed,0x2fd4affc,0x2fffae1f,0x2515230e,0x2c32230e,0x2ddcaf1a,0x2875ae7c,0x2d27aaaa,0x2fa0af80,0x2875ac32,
0xaee929f1,0x2f91ae99,0x9fd9ac87,0xa8149648,0xafed2f1a,0xaf302e3f,0xa934a875,0xa8142b5e,0xa6a12ddc,0xb0002fc9,0xb0002e7c,0x25db1cb6,
0x2ed0aa4e,0xaf462fd4,0xa9932e99,0x2cb0aa4e,0x2e3faffc,0xad272e5e,0x2e1fa814,0x2f02adfe,0x9fd9abb7,0x2c07ad27,0x2fedae1f,0xadfe2d00,
0xaf6e2cb0,0x25dba993,0x2c5daf46,0xaf6e2ed0,0xaddc2fdd,0xa5159648,0xac329648,0xafff2fd4,0x28d52814,0xabb72934,0xaff42f30,0xafa02fed,
0x3000aee9,0x2e99adfe,0xac872f30,0x2f6eafbc,0x2c32af02,0x2f80af1a,0x2aaa217e,0x2e7caf02,0xab5e9cb6,0x2ff4afc9,0x2ff4ae7c,0x2d27addc,
0xaffc2eb5,0x2fedb000,0x2cd8af5a,0x2b05ac5d,0xa17e2c32,0xad002d72,0xabb71cb6,0xa17e2515,0x2dfea9f1,0xac072c87,0xafed2e99,0x1fd91648,
0x2fd4afbc,0xa9f12b05,0xad962f91,0x26a1a44e,0x2aaaae3f,0xa76528d5,0x251528d5,0x2993a875,0xafe62eb5,0xaddc2dba,0x2fffaf6e,0xaed02eb5,
0xae3f2fbc,0xae1f2dfe,0x2d27af30,0xaf022ee9,0x9fd92b5e,0xae5e2e3f,0xa44ea875,0xaf302f1a,0x2d96a993,0xae992e7c,0xae992c32,0xaf5a2f46,
0x299329f1,0xa76525db,0x251525db,0x2aaa1648,0x28d52934,0xaf02acd8,0x230e244e,0x2fa02dfe,0x28142875,0xaf91aff8,0x1fd9217e,0x2ee92ff4,
0x26a12765,0xaa4eaddc,0x16481cb6,0x26a12cb0,0xaf02af46,0xab5eae7c,0xab5eac32,0xa30e2993,0xae5eaeb5,0x2b059648,0xa934aa4e,0xaee9ac5d,
0xad96adfe,0x2fdd2e5e,0xa5dba814,0xaf5aaffc,0xacb0ad27,0x2ddc2faf,0x9cb6a30e,0xa765ad27,0x2fd42f91,0x2f6e2fed,0x2dba2e5e,0xa6a1ad4d,
0x2fff2ff8,0x25152d00,0x2c322d00,0x2ddc28d5,0x2faf2fe6,0xae1fa993,0x28d52aaa,0x2faf2fc9,0x2ee92f5a,0xaf91afdd,0x1fd925db,0x28142d96,
0xacd8ab5e,0xaf91ad00,0xaf30afaf,0x2c072f1a,0xaeb5addc,0xad96afc9,0xad96ae7c,0xac879cb6,0xafc9af5a,0x2993a6a1,0xaaaaac87,0xafe6af5a,
0xaff4affc,0x2ff82e5e,0xa17ea814,0xa875adfe,0x9fd9a875,0x2c07a17e,0x2fed2ff8,0xadfeaff4,0x29f12515,0x2fdd2f46,0x2eb52f80,0x29f1a765,
0x2ddc2c87,0x25152d96,0x2c322d96,0x2fff2eb5,0x2fa02ee9,0xaf02ab05,0x230e2934,0x28d52e5e,0x2d962ee9,0x25db2dfe,0xafddaf30,0x2f5a2fbc,
0x27652bb7,0xaf46ab5e,0xaf80aff8,0xa5152bb7,0xa8d59cb6,0xad00afc9,0xad00ae7c,0xaff8addc,0xadfeac5d,0x2cd89648,0xa44eaa4e,0xa934aeb5,
0xaff8afc9,0xae3fafff,0x2f022d72,0xaff8ae7c,0xadfeaf5a,0x2c07a5db,0x2fed2fdd,0x9fd9ad96,0xa6a1ac07,0x2f6e2f91,0x2dba2f30,0x2fd42cd8,
0x2aaa230e,0xa7652b5e,0x25152b5e,0x29932f02,0x2e7c2c5d,0x2fff2d96,0xad72a9f1,0x2fc92c5d,0x2ff42fbc,0x217e2dfe,0xaff8af30,0x28752ee9,
0x2d4d2f1a,0xafedad00,0xae5eafaf,0xaf91ab5e,0x96482993,0xa5dbae7c,0xa5dbac32,0xa9f1af46,0xaddc9648,0xafe6a6a1,0xaed0a6a1,0x2fff2a4e,
0xad27affc,0x2d00ac07,0xabb7afbc,0xae1f2934,0x2e5e230e,0x1fd92fa0,0x2f3028d5,0x244eaf02,0x2c872fe6,0xadbaaf46,0x2a4e2f80,0x2c872fc9,
0x230ead72,0x2d27ac32,0x2d27a515,0xafaf9cb6,0x2fbc2e99,0x9fd92f6e,0x2d4d3000,0x2cd8ac87,0xaa4e2b05,0xac5dafbc,0xaeb5a44e,0x96482f91,
0xaed0afa0,0x2f802d00,0xaaaaafaf,0xacb0afa0,0x2c872ffc,0x16482fbc,0xa9f12c07,0x2e99a934,0xaf80a8d5,0xac32afaf,0xae7cafaf,0xaaaa2e1f,
0xa30eaed0,0x2f1a2d72,0x2e1f9cb6,0xa30eafe6,0x2fed2dba,0xaffca6a1,0x2b052fd4,0x2cd82f6e,0xafbcae1f,0xad4daf02,0x1fd9ae3f,0xacd82d27,
0x2c87a993,0x2f5a2cb0,0x2f5a2ed0,0x26a1af46,0x2cb03000,0xafffa5db,0xad7226a1,0x27653000,0xafafa934,0x2f1aa814,0xab5eafed,0xad00af30,
0x2f30230e,0x2fed28d5,0x28142fa0,0x2934af02,0x16482ed0,0xafd41cb6,0xafddad72,0x16482fe6,0xaf46aeb5,0x2ed0a9f1,0x2cb0a9f1,0xa993afdd,
0x2e1fa44e,0xad002d4d,0x2bb72ffc,0x2d272ee9,0xaa4e2cd8,0xaeb52b05,0xac5daffc,0x96482fed,0xacb0aff4,0x2d72ad27,0x2fff2b5e,0xa765aff4,
0x2ff82aaa,0xabb72e7c,0xabb72c32,0x2b5e2f80,0xab052c87,0x2814af6e,0xac07b000,0xad4dae99,0xa8d5afe6,0x2875af80,0x2e3f2f46,0xa8d5afc9,
0x2f912dba,0xa44e2fd4,0xafbca6a1,0x2b052f6e,0xae99244e,0x9648affc,0x29f1ad4d,0xac87aee9,0x1cb6af02,0x25152ff8,0x2c322ff8,0x2d722e3f,
0x2ed02e99,0x2aaa2f5a,0xaf80ad96,0x2cb02e99,0xafafa44e,0xab5eaf30,0x2f1a9fd9,0xad00ae5e,0x2b05ad27,0x2c072f02,0xa8142e3f,0x2d4d2e1f,
0x29f12fff,0xac5daed0,0xac5dafe6,0xad96addc,0xaf46aa4e,0xac32ac87,0xae7cac87,0x29932dba,0x2f1a2b05,0xa8752fed,0x2e3f2cd8,0x2b5eaffc,
0xaee9abb7,0x2f30ae1f,0xadfead27,0xafbc2d00,0x2eb52c32,0xaf6e1cb6,0x2dba2d72,0x2eb52515,0x2fafa993,0x2fa0a515,0x2fa02765,0xad00aaaa,
0xafed26a1,0xa934ad96,0xaf30a9f1,0xa8142fd4,0x30009fd9,0xac872fed,0x2e992c07,0x2f6eadfe,0xafe6a17e,0x2fffabb7,0xaddcad00,0xaed0a17e,
0xac5d2f30,0xaf5a2e5e,0xb000244e,0x2eb51fd9,0x2ddcae1f,0x2e7c230e,0x2fc9230e,0x1cb6af1a,0xaf022cb0,0x217eaf46,0xaf1aa993,0xaf022ed0,
0x2fbca9f1,0xaf302e99,0x2dfe2c87,0x2ee91648,0xa44eafa0,0x2b05aff4,0x2f91abb7,0xafbc28d5,0xa6a12fff,0xb0002c32,0xb0002515,0x25db2ddc,
0x2c32af6e,0x2aaa2c5d,0x2f8025db,0x2e7caf6e,0xae3f2dfe,0x2d27afed,0xae1fac07,0xaf021fd9,0x2dfe2bb7,0x28142d27,0xae5e2e1f,0x2ffcad00,
0xaa4eae7c,0x2e99af80,0x2fd4aaaa,0xaa4eac32,0x9cb62fdd,0xae7c9648,0xafc99648,0xaddc2fd4,0x2b5eafbc,0xa8752f91,0x2e3f2b05,0x2f1aa44e,
0xb0002814,0xae991fd9,0x2c87af91,0xaf6e2ee9,0x2ed02875,0xa9932fa0,0xaf462d27,0x2cb02875,0xab5eaddc,0x2ff4ac32,0x2ff4a515,0x2d27afff,
0x9fd92fd4,0xa44ead96,0xae5ea9f1,0xaf3026a1,0x2e1faed0,0x2ff4addc,0xa8752fff,0x2e1fafe6,0xaffc29f1,0xa814ac87,0x2e5eae99,0xadfe9648,
0x2eb52814,0xaf5a2f30,0xb0002934,0xac5d2fed,0xa993ae3f,0x2c3228d5,0x2e7c28d5,0x2f46a875,0xa5152fd4,0xad723000,0x9cb6af5a,0xac322fd4,
0x2e3faee9,0x2e1f9fd9,0xad272f91,0x2f02a814,0xaffc28d5,0x2cd8aff4,0x2fedabb7,0x2b05afa0,0x2d962aaa,0xae992515,0xae99a765,0xaf5a2993,
0x1cb6adba,0x2cb0aeb5,0x2765aeb5,0xaddc2f6e,0xaff82d4d,0xa30ea814,0xafaf2c07,0xa17e2b05,0xa44e2e3f,0xadfe2b5e,0xa9342f1a,0x2cd8a875,
0x2fddacb0,0xb0002f80,0x2f6eaaaa,0x2fddaed0,0x2d001cb6,0x217e2765,0x217e2cb0,0x2bb7addc,0x2ee9afdd,0x2d4daa4e,0x2ffcadba,0xa44ea5db,
0xa9f1a934,0x2fd4aee9,0x26a1ae5e,0xad962b05,0xafc92f1a,0x2f46aff4,0xaf802bb7,0xafe62f1a,0xafdd2d4d,0xadba2c07,0xaa4ea814,0xa5db2b05,
0xaaaa2f1a,0xafc92f02,0xafe62f02,0x2993a17e,0x2e3fa765,0xafa02fff,0xa17e2d72,0x2e3facb0,0x2e5eb000,0xad4d2eb5,0x2f91ac5d,0x2fedaf5a,
0x2ee9aff8,0x2ffcafaf,0x2d4da30e,0xa44ea17e,0xa5dbaaaa,0x2f6eafe6,0x2f6eafc9,0xac5d2993,0xafe62dba,0x2d72ae99,0x9cb6ac5d,0xaed02dba,
0xabb72f30,0x28d5ac07,0xafa02cd8,0xaff42f91,0xa9342e3f,0xae5e2f1a,0xaee92b5e,0x2b05a875,0x2dbaa765,0xac5d2d72,0xae992fff,0x2dbaacb0,
0x2f80afd4,0xa7652a4e,0x25152a4e,0x2f46ae99,0x217eacd8,0x230e1fd9,0x2fafad4d,0x2ff8afbc,0xa9f1a44e,0x26a1a934,0x2fd4adfe,0xad962cd8,
0xafe62e3f,0x9cb6a17e,0x2d72afa0,0xaed02e3f,0xad272f80,0xa8752515,0xa875a765,0xafa02f46,0x293425db,0xac072a4e,0xafbc2dba,0xaffc2fdd,
0x2f1aacb0,0x2bb7aaaa,0xaff42f80,0x2f1aaed0,0x2f30b000,0x2cd8ac5d,0xac072eb5,0x2f91af5a,0x25dbacd8,0x2dbaad4d,0x2a4e1fd9,0x2fddafbc,
0xad722875,0x2e7cae1f,0x2fc9ae1f,0x2fffaff4,0xafc92fdd,0xaf802f6e,0x2f46b000,0xafe62fdd,0xabb72e5e,0xafa02f91,0x28d5ad4d,0xaff42fed,
0x2934217e,0xafbc2faf,0xac07230e,0xaffc2ff8,0x2f5aad72,0xafd42fc9,0xafd42e7c,0xb0002fff,0x9cb69648,0xacb0a6a1,0xa765a6a1,0x2ddc2a4e,
0xa17e9fd9,0xaff4aee9,0xa875a814,0x2ff82f91,0xa44ea30e,0xadfeafa0,0xa934a8d5,0x2cd82f02,0xa5dba515,0x9648aaaa,0xa9f1a993,0xa5db2765,
0xa30e9cb6,0xad27a765,0xad27acb0,0x2faf2ddc,0xa814a5db,0xaffcaf5a,0xadfead96,0x2e5e2fdd,0xaa4ea934,0xac5daee9,0xaeb5ae5e,0x96482b05,
0xac32ab5e,0x2993a30e,0xaf46af02,0xae7cab5e,0xa5db9fd9,0xad96a814,0xaf5aaee9,0x2fdd2f91,0xaaaaa8d5,0xafc9afaf,0xafe6afaf,0x29932e1f,
0xad00ac32,0xa8d5addc,0xaff8afff,0xad00a515,0xae5eadba,0x2d4d26a1,0xaf91afd4,0xafedaf6e,0xa814a17e,0xadfea875,0xaffcaff4,0x2e5e2ff8,
0xac87aaaa,0xaf5aafe6,0xaf5aafc9,0xa6a12993,0xae7cad96,0x9cb6ac87,0xaddcaeb5,0xafc9ad96,0xafafaf30,0x2f1a2c07,0xab5eacd8,0xad00af91,
0xa934a30e,0xae5ea8d5,0xaee9afa0,0x2b052f02,0xad96ac32,0xaeb5afff,0xac87addc,0xad96a515,0xaf80aeb5,0x2765a9f1,0xa515a9f1,0xaf46afdd,
0xaff8afed,0x2ff42dfe,0x28751fd9,0x217eac07,0xaa4ea44e,0xaeb5a934,0xac5dadfe,0x96482cd8,0xae7cad00,0xaddcaff8,0x9cb6a8d5,0xafc9ad00,
0xaff8af80,0x2bb7a515,0x2bb72765,0xab5eaf46,0xaf30afdd,0x2fbc2f5a,0x2ee92d96,0x2dfe25db,0xab5ea515,0xaf02a993,0xa30eaaaa,0xab5e2765,
0xaf30adba,0xacd8afd4,0x2c0726a1,0xaf91af6e,0xafddafed,0x2d961fd9,0x2f5a2dfe,0x25dbac07,0xad72af02,0x2e7c2ff8,0x2fc92ff8,0x2fff2e3f,
0xac32a5db,0xaf46a9f1,0x29939648,0xae7ca5db,0xafafae5e,0xab5eaf91,0x2f1a2d4d,0xad00afed,0xaf30aff8,0x2ee92875,0x2fbc2ff4,0x2dfe217e,
0xa9f1ad72,0x2c5d2fc9,0x2c5d2e7c,0x2d962fff,0xaf80aa4e,0xafc9ac87,0xafe6ac87,0x2f462dba,0xa8d5af30,0x2f02a44e,0xa30eae5e,0xafa09fd9,
0x2fbc2bb7,0xa9342e1f,0x2ffc2d27,0x2c07ad00,0x26a12ed0,0xaa4eafff,0x16482ddc,0x26a12fe6,0xafafaaaa,0xafa0acb0,0xafa0aed0,0x2d002f80,
0xa44eaeb5,0x2f919648,0x2b05aa4e,0xafbcac5d,0x30002d4d,0xac872cd8,0x2e992fbc,0x2f6e9fd9,0xa5152d27,0x9cb6afaf,0xad72230e,0xac322d27,
0xafd4ab05,0xaf6eacd8,0xadbaafed,0x26a12ffc,0x1cb6ae1f,0x2fe6230e,0x2ed0230e,0xad72af1a,0x2faf2e7c,0xae1f2aaa,0x28d52f80,0x2faf2c32,
0xac0729f1,0x2934ae99,0xaffcac87,0xafbc9648,0xafedab5e,0xaf30ad00,0xa934afaf,0xa8142f1a,0x26a1ad72,0x30002765,0x30002cb0,0xa5dbafff,
0x2ed02f5a,0xaf4626a1,0xa9932c87,0x2cb02f5a,0xae3f1fd9,0x2d27acd8,0xae1fafbc,0xaf02ad4d,0xaffcabb7,0xaee9ad27,0x244eae1f,0xad4d2d00,
0x29f1acb0,0x2fdd2993,0x2eb52f46,0x29f1aed0,0x2d722fdd,0xafe69648,0xaed09648,0x9cb62fd4,0xafa0a814,0x2f02a934,0xa30eaf30,0xa8d5afed,
0xb000ac07,0xae99ad4d,0x2c87ab05,0xaf6e2814,0x2c32abb7,0x2f802b5e,0x2aaa2ff8,0x2e7cabb7,0x2b5e2fff,0xaff4a765,0xaff4acb0,0xad272d72,
0xaffcac5d,0x2fed9648,0x2cd8aa4e,0x2b05aeb5,0xaff8ac32,0xae3fad72,0x2f029cb6,0xaff8a515,0x2d4da9f1,0x2ee92c87,0xa44e2e99,0x2ffc1648,
0x26a12fbc,0xaf6eab05,0xadbaaf91,0xafd4244e,0xaf46ae3f,0x2fc928d5,0x2fe628d5,0x2f80a875,0xafe6ac5d,0xaddcad96,0x2fff29f1,0xaed0ac5d,
0x2e3fa814,0x2e1f2d4d,0xad272b05,0x2f022c07,0x9fd92f1a,0xae5ead00,0xa44eafaf,0xaf30ab5e,0xad96af80,0x2e992cb0,0x2e992ed0,0x2f5a2aaa,
0xad72adba,0xa515aeb5,0xac32aeb5,0x9cb62f6e,0x2d272dfe,0xad002fbc,0x2bb72ee9,0x2e1faf30,0xacd8ae3f,0x2ffcab5e,0xab05af1a,0xafed2875,
0x2c872e7c,0xadbaa993,0x2a4e2f46,0x2c872c32,0xad00addc,0xa17eaed0,0xa17eafe6,0xabb72fff,0x2c072e99,0xadfe2f6e,0x9fd93000,0x2fedac87,
0xa9f1af30,0x2fd4a814,0x26a1afed,0xad96a934,0x27652fa0,0xaaaaad00,0xa9932faf,0xa5152fa0,0xac87adfe,0x9648aee9,0x29f1afbc,0xae992f30,
0x29932f1a,0xaed02f02,0xacb02f02,0x2f46a17e,0xa30eafc9,0x2f1a9cb6,0x2e1faddc,0xa30eae7c,0xa44e3000,0x9fd9aeb5,0xaf302c5d,0xae5e2f5a,
0xac07ae1f,0x1fd9af02,0x2dfeae3f,0xafed2d27,0x25db2f80,0xaf6e2e7c,0xaf6e2c32,0x2c5d2aaa,0x2515b000,0x2ddc25db,0x2fffa6a1,0x2c32b000,
0xabb72f91,0x28d5afbc,0xafa0a44e,0xaff42b05,0xab05ae3f,0x244eaf1a,0x2fbcab5e,0xaf912875,0x16482fc9,0xafd42ddc,0xafdd1cb6,0x16482e7c,
0x2aaaafd4,0x2c322a4e,0x2e7c2a4e,0x2f80ae99,0xae1f2e5e,0x2d00affc,0xabb7adfe,0xad27a814,0xa9f1ae5e,0x26a1af30,0x2fd49fd9,0xad96a44e,
0xa5152ff4,0xafff2d27,0xaddcab5e,0xac322ff4,0x2d27af46,0x28752cb0,0x28752ed0,0x2fa0a993,0xaf912c87,0x2ee9af6e,0x2814b000,0x1fd9ae99,
0xa8d5ae7c,0x2875af46,0x2e3f2993,0xa8d5ac32,0xa9343000,0xafed2c5d,0xa814aeb5,0xaf302f5a,0x2e99ae5e,0x16482dfe,0xa9f12ffc,0x2c872814,
0xafff2875,0x2fe6ae1f,0x2ed0ae1f,0x2ddcaff4,0xa765ae99,0x2993af5a,0x2aaa2d96,0x2515ae99,0xabb72fed,0xafa02b05,0x28d5affc,0xaff42cd8,
0x2f91ad27,0xa8142f02,0xaee92e3f,0x9fd92e1f,0xaf5a9cb6,0x2fd4ac32,0x2fd4a515,0x3000ad72,0x2aaaaf6e,0x2ed0afdd,0x2cb0afdd,0xaf803000,
0xaf1a2934,0x2875acd8,0xae3f244e,0xab5e2dfe,0xac072faf,0xab05217e,0xad4d2ff8,0x2814230e,0x2eb5a765,0xaf6e2ddc,0x2dba9cb6,0x2eb5acb0,
0x2bb7af80,0x2f1aafe6,0x2f1aafc9,0xaff42f46,0xae5e26a1,0x2b05ad96,0xa934a9f1,0xaee92fd4,0xadba2ffc,0xa5dba44e,0xafdd2ee9,0xaa4e2d4d,
0x2cb0217e,0xaddc2bb7,0x1cb62d00,0x2765217e,0x2c5daf91,0x2f5aafed,0x3000ae5e,0xaeb52d4d,0xad72217e,0x2cb0ae3f,0x2765ae3f,0xafff2fa0,
0xaf022fe6,0x217ea993,0xaf1a2aaa,0xaf022fc9,0x28142a4e,0xab0525db,0xad4d2fdd,0xac072dba,0x2cd8afa0,0x2f91aff4,0x2f30abb7,0xac0728d5,
0xac5d9cb6,0x2dbaaed0,0x2dbaafe6,0xae992d72,0xafc92f6e,0x2993ac5d,0xaaaaa5db,0xafe62f6e,0xa30e2d4d,0xa17ea44e,0xaff82ee9,0xafaf2ffc,
0x2d4dafaf,0x2fbcaff8,0x2cd8a17e,0x9fd9a30e,0xaa4ea515,0x2e99af46,0x2fd4af80,0xaa4e2765,0xafff2e99,0x2cb0adba,0x2765adba,0xad722c5d,
0xab5e2ee9,0x2875ab05,0xae3f2934,0xaf1a2e5e,0x2dbaafbc,0x2fddaffc,0x25db2934,0x2a4eac07,0xa765a875,0x2f46afa0,0x2f80ad27,0x2515a875,
0xafa02d72,0x2e3faed0,0x2e3fafe6,0xa17e9cb6,0xadfe2fd4,0x2cd8ad96,0xa44ea9f1,0xa93426a1,0x2e1fafc9,0x2ff4afff,0xa8752d72,0x2e1fae7c,
0x9fd9aa4e,0x2fbcafdd,0x2cd8a5db,0x2d4dadba,0xaeb52c07,0x2f5aaf91,0x3000af30,0x2c5dacd8,0xaf802ff4,0x2ed0af1a,0x2cb0af1a,0x2aaaabb7,
0x2e7cafd4,0x2fffb000,0xad722f5a,0x2fc9afd4,0x230eac07,0x2ff8affc,0x217e2934,0x2fafafbc,0xad4d28d5,0x2fedaff4,0x2e5eabb7,0x2f91afa0,
0xb0002f46,0x2fddafe6,0x2fddafc9,0x2f6eaf80,0xaaaaaa4e,0xaed0ac87,0xacb0ac87,0x2f802dba,0xab5eab05,0xafafafed,0xad00acd8,0x2f1a2ffc,
0xac07abb7,0xab05ae1f,0xad4dad27,0x28142d00,0xac5dac32,0x29f19cb6,0xad96ad72,0xac5da515,0xafafaf80,0xafa0afe6,0xafa0afc9,0x2d002f46,
0xafedafd4,0xa934adba,0xaf30af6e,0xa81426a1,0xb000affc,0x2c87244e,0xae99aee9,0xaf6ead4d,0xafe6aff8,0x2fff2f02,0xaddcae3f,0xaed0aff8,
0xaeb5af30,0xaa4eae5e,0x9648a44e,0xac5d9fd9,0xad72ae1f,0x2cb0230e,0x2765230e,0xafffaf1a,0xabb7acb0,0x2ff82f46,0x2b5e2993,0xabb7aed0,
0xa814a9f1,0x2b052e99,0x2d4d2c87,0x2c071648,0xa44ea8d5,0x2b05a30e,0x2f912f02,0xafbcafa0,0x26a11cb6,0x30002ed0,0x30002fe6,0xa5dbad72,
0x2c3229f1,0x2aaa2eb5,0x2f802fdd,0x2e7c29f1,0x2e3f2d4d,0xad27a44e,0x2e1f2ee9,0x2f022ffc,0x2d4d2bb7,0x2fbc2d27,0x2cd82e1f,0x9fd9ad00,
0x2f5a2e7c,0x2c872f80,0x26a12aaa,0x2f5a2c32,0x2fff2fdd,0xacb09648,0xa7659648,0x2d722fd4,0x2f1a2fbc,0xafafaf91,0xad00ab05,0xab5e244e,
0x30002fbc,0x2e992ffc,0xac87a934,0x2f6e2c07,0x2ed02faf,0xa99328d5,0xaf46ae1f,0x2cb02faf,0x2b5e2d72,0xaff4aed0,0xaff4afe6,0xad279cb6,
0x9fd926a1,0xa44eadba,0xae5eaf6e,0xaf30afd4,0x2d272ed0,0x230e2ddc,0xafafafff,0x2d272fe6,0x1fd929f1,0xafbcac87,0xacd8ae99,0xad4d9648,
0xac5da814,0xaa4eaf30,0x9648a934,0xaeb5afed,0xaf80ae3f,0x2ed028d5,0x2cb028d5,0x2aaaa875,0xa51526a1,0xad721648,0x9cb6aa4e,0xac3226a1,
0xae3fac07,0xae1faffc,0x2d272934,0xaf02afbc,0xaffcafa0,0x2cd8a30e,0x2fed2f02,0x2b05a8d5,0xad96af46,0x2e992fe6,0x2e992fc9,0x2f5a2f80,
0xafffadba,0xae7caeb5,0xafc9aeb5,0x2d722f6e,0x217ead4d,0x2ff42814,0x2875ac07,0xaff8ab05,0x2fed2e3f,0xad4d2b5e,0x2f912f1a,0x2e5ea875,
0xa5db2cb0,0x9648af80,0xa9f12aaa,0xa5db2ed0,0xad00afff,0xa17eafc9,0xa17eae7c,0xabb72d72,0x2ee925db,0x2d4d2f5a,0x2ffc2d96,0xa44eafdd,
0x29f12f91,0xafd4ac07,0xa6a12cd8,0x2d962f30,0xafc9ab5e,0x2f46a30e,0xaf80af02,0xafe6ab5e,0x25dbad4d,0x2d96ac07,0x2f5a2814,0xafddab05,
0x2f462f1a,0xa7652f02,0x25152f02,0x2f80a17e,0xad002765,0xa8d5afff,0xaff8ad72,0xad002cb0,0xacd8b000,0x2dfe2eb5,0x2934ac5d,0x244eaf5a,
0x2ee9217e,0x2ffc2875,0x2d4d2ff4,0xa44eaff8,0x25db2f46,0xaf6e2515,0xaf6ea765,0x2c5d2f80,0xafe6ad96,0x2d72ac87,0x9cb6aeb5,0xaed0ad96,
0x2bb7ab05,0xa8d52ee9,0x2fa02e5e,0x2ff42934,0x2f912e3f,0x2cd82f1a,0xac072b5e,0x2f30a875,0xad962765,0xaeb5ad72,0xac87afff,0xad962cb0,
0xa993afd4,0x2fc92a4e,0x2fe62a4e,0x2aaaae99,0x2ff82cd8,0xaff49fd9,0xa8752d4d,0xa17e2fbc,0x29f12fed,0xa6a12f91,0xafd4ad4d,0x2d962e5e,
0xafe6ad00,0x9cb6aff8,0x2d72a8d5,0xaed0ad00,0x2d27a993,0x28752fe6,0x28752fc9,0x2fa02aaa,0x29342fdd,0xac07af5a,0xafbcad96,0xaffca5db,
0xab5e2cb0,0xaf022aaa,0xa30eaf80,0xab5e2ed0,0xab05b000,0x2e5eac5d,0x2ee92eb5,0x2934af5a,0x2fdd2cd8,0xad962d4d,0xaf5a9fd9,0xa5db2fbc,
0xaddc2875,0x2cb0ae1f,0x2765ae1f,0x1cb6aff4,0xafc9a5db,0xaf80a9f1,0x2f469648,0xafe6a5db,0x2bb7acd8,0x2fa02934,0xa8d52dfe,0x2ff4244e,
0x29342ff8,0xafbca875,0xac07aff4,0xaffca17e,0xaf5aaddc,0x2fd42765,0x2fd42cb0,0x30001cb6,0xa993af6e,0x2765afdd,0xa515afdd,0xaaaa3000,
0x28d52f91,0xaf022e5e,0x230e2fed,0x2fa0ad4d,0xa814afaf,0x2f91a17e,0x9fd9aff8,0xaee9a30e,0x26a12fc9,0xaa4ead72,0x16482fff,0x26a12e7c,
0x2bb7af46,0x2f1aae7c,0x2f1aac32,0xaff42993,0xacd82eb5,0xaf301648,0xaf912a4e,0x2c072c5d,0x2dbaadfe,0x25db2e5e,0x2fdda814,0x2a4eaffc,
0xae7c2d27,0x2d72afaf,0xafff230e,0xafc92d27,0x2fd4a934,0x2f6ea44e,0x2dba2cd8,0xa6a1adfe,0xafff217e,0xa515ae3f,0xac32ae3f,0xaddc2fa0,
0x2faf2515,0xae1f2f80,0x28d52f46,0x2fafa765,0xaee9aa4e,0x2f91a5db,0x9fd9afdd,0xa814adba,0x2e5e2b5e,0x29342d00,0xab052faf,0x2ee9af1a,
0xac5daddc,0x2dbaafc9,0x2dbaae7c,0xae999cb6,0x27652f5a,0xaf8026a1,0xaf462c87,0xa5152f5a,0x230eaffc,0x217e2e5e,0x2ff8a814,0x2fafadfe,
0x1fd92faf,0xac072ff8,0xafed217e,0x2dfe230e,0x29f1afe6,0x2fddaaaa,0x2eb52993,0x29f1afc9,0xaddc2e99,0xa515adba,0xac32adba,0xafff2c5d,
0x2fa0ac07,0xaf022f30,0x230e2f91,0x28d52cd8,0xadba2ee9,0xafdd2dfe,0xa5dbaf30,0xaa4e2fbc,0x2fc9abb7,0x2aaa2b5e,0xa9932ff8,0x2fe6abb7,
0xafa09cb6,0x2e3fafc9,0x2e3fae7c,0xa17eaddc,0x2d4d2c5d,0xae5e1648,0xafed2a4e,0xaf912eb5,0xaff82765,0xae3f1cb6,0x2f02addc,0xaff82cb0,
0x2dfe2a4e,0xac072fdd,0xafed25db,0x1fd92dba,0xa6a1aee9,0x2f6ea934,0x2dba2b05,0x2fd4ae5e,0xaaaa2ff4,0x2765af1a,0xa515af1a,0xa993abb7,
0xacb0ac5d,0x9cb6ad96,0x2ddc29f1,0xa765ac5d,0xa30e2fbc,0xaff82dfe,0xa17eaf30,0xafaf2ee9,0x2dfeaf1a,0x244e2d00,0xacd82faf,0x29342b5e,
0xb0002993,0x2fddae7c,0x2fddac32,0x2f6eaf46,0x2ddcb000,0x2fe6afd4,0x2ed0afd4,0xafff2f5a,0xad279fd9,0x2d00aee9,0xabb7a814,0xae1f2f91,
0xae5e2ff4,0x9fd9a8d5,0xaf302fa0,0xa44e2bb7,0x2c872515,0xadba2aaa,0x2a4e2993,0x2c87a765,0x2ff4ad72,0x2e1fac32,0x2e1fa515,0xa8759cb6,
0x2814ae99,0x2ffcaf6e,0x2dfeb000,0xae5e2c87,0xaf5a2b05,0x2eb5afbc,0xac5da44e,0xb0002f91,0xac322fa0,0x2993ad00,0xaf462faf,0xae7c2fa0,
0x2c871fd9,0x16482814,0xa9f12ee9,0x2e99af91,0x2f80afa0,0x2c32a875,0x2e7ca875,0x2aaaad27,0xa30eac32,0x2f1aaddc,0x2e1fafff,0xa30ea515,
0xafed2d96,0x2ffcafd4,0xab05a6a1,0xacd829f1,0xa8142e1f,0xadfe2f02,0xaffc2e3f,0x2e5ead27,0x2e99a993,0xaa4e2cb0,0xaa4e2ed0,0x2fd4af46,
0x2e7cb000,0x1cb625db,0x2ddca6a1,0x2fc9b000,0xa875a934,0x2b5ea814,0x2f1aafed,0x2e3faf30,0xaf302ff4,0xafed2fa0,0xa814a8d5,0xa9342bb7,
0x16482c32,0xafd42fff,0xafdd2ddc,0x16482515,0x2f46ac5d,0xaed02f6e,0xacb02f6e,0x2993a5db,0x2e1fafed,0xad002dfe,0x2bb71fd9,0x2d27ac07,
0xaf5a2cd8,0xac5d2b05,0x2eb5affc,0xb0002fed,0xae7c2ff4,0xaddc2d27,0x9cb6ab5e,0xafc92ff4,0x217e2aaa,0xaf022e7c,0xaf022c32,0xaf1a2f80,
0x2f30ac87,0xafbc2f6e,0xaee93000,0xadfe2e99,0xa8d5a515,0x2875a993,0x2e3faaaa,0xa8d52765,0xaf912d96,0x244ea6a1,0x2fbcafd4,0xab0529f1,
0xae992fed,0x96489fd9,0x29f1adfe,0xac872c07,0x9cb62bb7,0xa515217e,0xac32217e,0xad722d00,0x2c32ae99,0x2f46af5a,0xa9932d96,0x2e7cae99,
0xa875a44e,0x2f1aaf30,0x2b5e9fd9,0x2e3fae5e,0xaf302d27,0x2ee9af02,0x2fbcae3f,0x2dfeae1f,0xaf6e2fff,0x2eb5aed0,0x2eb5afe6,0x2dbaaddc,
0xaddcadba,0xafe6aeb5,0xaed0aeb5,0x2fff2f6e,0xae1fadfe,0xae3fafbc,0xaf02aee9,0x2d272f30,0xae5eae3f,0x9fd9ab5e,0xaf30af1a,0xa44e2875,
0xae99ae7c,0x2d962993,0xaf5aaf46,0xae99ac32,0xad00ad72,0xa17eac32,0xa17ea515,0xabb79cb6,0xac07ac87,0x2dfe29f1,0x1fd99648,0xafedae99,
0xa9f1ab05,0x2fd42fbc,0x26a1244e,0xad96af91,0xa765a8d5,0x2aaa2e3f,0x29932875,0x2515a8d5,0x2e992dfe,0x30002ee9,0x2f6e2fbc,0xac87af30,
0x2f802f1a,0x2c322f02,0x2e7c2f02,0x2aaaa17e,0x2ff42fc9,0xab5e1cb6,0x2d272ddc,0x2ff42e7c,0x2fed3000,0xaffcaeb5,0x2b052c5d,0x2cd82f5a,
0x2c072d27,0x9fd92bb7,0xadfead00,0x2fed2e1f,0x25db2993,0xaf6eacb0,0xaf6eaed0,0x2c5d2f46,0xa5151648,0xaddcafdd,0xafffafd4,0xac321648,
0xabb7a934,0x28d5a814,0xafa0afed,0xaff4af30,0xaf30ae3f,0xafedaf1a,0xa814ab5e,0xa9342875,0xb000afc9,0xa6a1addc,0x25db9cb6,0xb000ae7c,
0xaf46afd4,0x2ed02a4e,0x2cb02a4e,0xa993ae99,0xad27ae5e,0x2e3f2ffc,0x2f022dfe,0x2e1f2814,0xa9f1acd8,0x26a1ab05,0x2fd42ffc,0xad96afed,
0x2515a30e,0x2fff2e1f,0x2ddc2f1a,0x2c32a30e,0x2d272aaa,0x28752e7c,0x28752c32,0x2fa02f80,0x2f912e99,0xaee9a9f1,0xa8141648,0x9fd92c87,
0x2fa02e7c,0x2faf2f46,0xad00a993,0x2fa02c32,0x2f913000,0xa44e2c5d,0xafbcaeb5,0x2b052f5a,0x2c872e5e,0xb000adfe,0xaf6eaffc,0xae99a814,
0x9cb62875,0xa515ae1f,0xac32ae1f,0xad72aff4,0x27652c87,0xa9932a4e,0xaaaaadba,0xa5152c87,0xabb7a44e,0xafa0af30,0x28d59fd9,0xaff4ae5e,
0xaf91ae1f,0x2814abb7,0x2ee92d00,0x1fd9ad27,0xaf5aafff,0x2fd42ed0,0x2fd42fe6,0x30002ddc,0xaf46af6e,0xac32afdd,0xae7cafdd,0x29933000,
0x2b5ea934,0x2faf2cd8,0x2d00a44e,0xaf1aadfe,0x2ee92faf,0xaf30217e,0x2dfe2ff8,0x2fbc230e,0xac5d2765,0x29f1addc,0xad961cb6,0xac5d2cb0,
0x2bb7a993,0x2f1aa515,0x2f1a2765,0xaff4aaaa,0x2e5e2fd4,0xab052dba,0x29342f6e,0x2ee9a6a1,0xadba1fd9,0xa5dbafed,0xafddac07,0xaa4e2dfe,
0xacb0aff8,0x2ddc2f02,0x9cb6ae3f,0xa765aff8,0x2eb52f91,0x2a4e2fed,0x16482e5e,0x2c5dad4d,0xaddc217e,0xae7cae3f,0xafc9ae3f,0x9cb62fa0,
0xabb7afe6,0x2ff82993,0x2b5eaaaa,0xabb7afc9,0x2fbc2a4e,0xaf3025db,0x2dfe2fdd,0x2ee92dba,0xacd828d5,0xaf91230e,0xaf30af02,0x2c072fa0,
0xac5dafff,0x2dbaac32,0x2dbaa515,0xae99addc,0x2fc929f1,0xa9932eb5,0x2aaa2fdd,0x2fe629f1,0xa30e2dfe,0xa17eafed,0xaff8ac07,0xafaf1fd9,
0xadfeafaf,0xa814aff8,0x2e5ea17e,0xaffca30e,0x2f5a2515,0x2c872f46,0x26a12f80,0x2f5aa765,0x9cb62e99,0xae7cadba,0xafc9adba,0xaddc2c5d,
0xaf1aaee9,0x2faf2b05,0x2d00a934,0x2b5eae5e,0x2dbaa814,0x2fdd9fd9,0x25db2f91,0x2a4eaee9,0x27652faf,0xaf4628d5,0xaf80ae1f,0xa5152faf,
0xafa0addc,0x2e3fac32,0x2e3fa515,0xa17eafff,0x2dfea6a1,0xacd82dba,0x244e2f6e,0x29342fd4,0x2d272fc9,0x230e2fff,0xafafad72,0x2d272e7c,
0xaffcaa4e,0xa814afdd,0x2e5ea5db,0xadfeadba,0x2c5dac07,0x2a4e2f91,0x16482f30,0x2eb52cd8,0x29932ff4,0xac32af1a,0xae7caf1a,0xaf46abb7,
0xae7c26a1,0xafff1648,0x2d72aa4e,0xafc926a1,0x230eaee9,0x2ff89fd9,0x217e2f91,0x2fafa814,0x2d4d2fa0,0xafed230e,0xae5eaf02,0xaf9128d5,
0xb000aaaa,0x2fdda515,0x2fdd2765,0x2f6ea993,0x1cb6b000,0x2cb0afd4,0x2765afd4,0xaddc2f5a,0xa17e2ffc,0xaff42c07,0xa8752fbc,0x2ff8a934,
0x244eaff4,0x2dfe28d5,0x2934afa0,0xacd8abb7,0xa5db2fe6,0x9648af46,0xa9f12f80,0xa5db2fc9,0x2ff41cb6,0x2e1f2765,0x2e1f2cb0,0xa875addc,
0xafbca5db,0x1fd9af5a,0xad4dad96,0xacd82fdd,0x2f5a2934,0xaeb52ee9,0x2c5d2e5e,0x3000ab05,0xaed0ab5e,0x2f80a30e,0xaaaaaf02,0xacb0ab5e,
0xa5db2ffc,0xad962fbc,0xaf5a2c07,0x2fdda934,0x2aaaafa0,0x2fc9a875,0x2fe6a875,0xa993ad27,0xad002ed0,0xa8d5ad72,0xaff81cb6,0xad002fe6,
0x2e5ead96,0xad4d2fd4,0x2f9126a1,0x2feda9f1,0xafbca17e,0xad4da875,0x1fd9aff4,0xacd82ff8,0x2e992aaa,0xaa4e2fe6,0xaa4e2fc9,0x2fd4a993,
0xacb0ad96,0x2fffac87,0x2d72aeb5,0xa765ad96,0x28752f30,0xab5eac07,0xaf1a2cd8,0xae3f2f91,0x2934aff4,0x2e5eafa0,0x2ee928d5,0xab05abb7,
0xad962ed0,0xaeb51cb6,0xac87ad72,0xad962fe6,0x2f80ac5d,0xa7652f6e,0x25152f6e,0x2f46a5db,0xaff8244e,0x2ff4ad4d,0x2875affc,0x217eaee9,
0x2f5a244e,0x2c5d2934,0xaeb52dfe,0x3000acd8,0xacb0ad00,0x2d72aff8,0x2fffa8d5,0xa765ad00,0x217e2f80,0xaf022515,0xaf02a765,0xaf1a2f46,
0x2b05afdd,0xa8142f5a,0x2c072d96,0x2d4d25db,0xab5e2fe6,0xaf022f80,0xa30eaf46,0xab5e2fc9,0x2f30ad96,0x2cd826a1,0xac072fd4,0x2f91a9f1,
0xafdd244e,0x2d96affc,0x2f5aad4d,0x25dbaee9,0x2d722bb7,0xae7c217e,0xafc9217e,0xafff2d00,0xaed0a5db,0xaaaaa9f1,0x2f809648,0xacb0a5db,
0x28752e5e,0xaf1a2f91,0xab5ead4d,0xae3f2fed,0x2b05aff8,0x2c072875,0xa8142ff4,0x2d4d217e,0xaf6e2d72,0x2eb5afc9,0x2eb5ae7c,0x2dbaafff,
0x2f80af5a,0x2fc9ae99,0x2fe6ae99,0xaf462d96,0xa8d5ab05,0x2f02afed,0xa30eacd8,0xafa02ffc,0xafbc2f02,0x2934ad27,0xaffc2e1f,0xac072e3f,
0x26a12c32,0xaa4e1cb6,0x16482d72,0x26a12515,0x28752aaa,0xa8d52cb0,0xa8d52ed0,0x2e3faf80,0x2fedaeb5,0x29349648,0x2f30aa4e,0x2814ac5d,
0x1648ad4d,0x2e99acd8,0x2c87afbc,0xa9f11fd9,0xafe62d27,0x2fffafaf,0xaddc230e,0xaed02d27,0xafd42f30,0xaf6e2e5e,0xadba244e,0x26a11fd9,
0x9cb62d27,0xafe62ff4,0xaed02ff4,0x2d72ab5e,0x2fafacb0,0xae1f2f46,0x28d52993,0x2fafaed0,0x2c07af6e,0xa9342c87,0x2ffcae99,0x2fbcb000,
0xa44eab5e,0x2b05ad00,0x2f91afaf,0xafbc2f1a,0xafd42d72,0x1648a765,0x1648acb0,0xafdd2fff,0xac322f5a,0xaaaa26a1,0xaf802c87,0xae7c2f5a,
0x2d009fd9,0xae1f2cd8,0xad272fbc,0xabb72d4d,0x2ffcaf02,0x2ee9ae1f,0xa44e2d27,0x2d4dae3f,0x29f1ae7c,0x2fddaf80,0x2eb5aaaa,0x29f1ac32,
0xad7225db,0x2fe6b000,0x2ed0b000,0x1cb6a6a1,0xafa02fbc,0x2f02af91,0xa30eab05,0xa8d5244e,0x96482c07,0xac872d4d,0xae992b05,0x29f1a814,
0x2ed0abb7,0xa9932b5e,0xaf462ff8,0x2cb0abb7,0x2f1aafff,0xa30e2765,0xa30e2cb0,0x2e1fad72,0x1fd9ac5d,0x244e9648,0x2e5eaa4e,0x2f30aeb5,
0xaff82ed0,0xae3f2ddc,0x2f02afff,0xaff82fe6,0xad4d2f6e,0xaee92e99,0x244eac87,0xaffc3000,0x26a12814,0xaf6e2f30,0xadba2934,0xafd42fed,
0x2f46ad00,0xafc92fa0,0xafe62fa0,0xaf802faf,0x2515ac5d,0x2d72ad96,0x1cb629f1,0x2c32ac5d,0xad002814,0x2d27ad4d,0x2e1fab05,0x2bb7ac07,
0xaffc2f1a,0x2cd8ad00,0x2fedafaf,0x2b05ab5e,0xadba2f80,0x2c87acb0,0x2c87aed0,0x2a4eaaaa,0xaf80af6e,0xafc9afdd,0xafe6afdd,0x2f463000,
0xafa0af91,0xabb7ae5e,0xaff4afed,0x28d52d4d,0xafbcafaf,0x2934a17e,0xaffcaff8,0xac07a30e,0xafd4afc9,0x2f5a2d72,0xb000afff,0xafd4ae7c,
0x2bb72aaa,0x2f1a2cb0,0x2f1a2ed0,0xaff4af80,0x2cd82c5d,0x2f303000,0x2f912f5a,0xac07aeb5,0x2dba2d4d,0x25db2cd8,0x2fdd2fbc,0x2a4e9fd9,
0x2e7c2e1f,0xad72a875,0x2fff2ff4,0x2fc92e1f,0x26a12934,0xa9f1244e,0xad96acd8,0x2fd42dfe,0x9cb6217e,0xafe6ae3f,0xaed0ae3f,0x2d722fa0,
0xa875a515,0xad27af80,0xafa0af46,0xa8752765,0xac07aa4e,0x2934a5db,0xaffcafdd,0xafbcadba,0xae5eaf1a,0xa934ae3f,0x2b052875,0xaee9ab5e,
0xac5dad72,0x2dba2765,0x2dba2cb0,0xae99afff,0xa765aa4e,0x2f802fd4,0x2f462e99,0x2515aa4e,0x230e9fd9,0x217e2cd8,0x2ff82fbc,0x2faf2d4d,
0x2ffc2faf,0x2ee92ff8,0xa44e217e,0x2d4d230e,0x2f6e2fe6,0xa5db2aaa,0xac5da993,0x2f6e2fc9,0x2d722e99,0xafe6adba,0xaed0adba,0x9cb62c5d,
0x28d52c07,0xabb7af30,0xaff4af91,0xafa0acd8,0xadbaac07,0xafddad4d,0xa5dbab05,0xaa4e2814,0xafc9af02,0xaaaaaf1a,0x2993217e,0xafe6af02,
0xafa0afff,0x2e3f2765,0x2e3f2cb0,0xa17ead72,0xad4daeb5,0x2e5e3000,0x2fed2f5a,0x2f912c5d,0x217ea765,0x2d009cb6,0x2bb72ddc,0x217eacb0,
0x2d4d2a4e,0x2ee92fdd,0xa44e25db,0x2ffc2dba,0x2fd42ee9,0xa9f12934,0xad96ab05,0x26a12e5e,0x2f462ff4,0xafc9af1a,0xafe6af1a,0xaf80abb7,
0x2cb02eb5,0x1cb62dba,0xaddcaf6e,0x27652eb5,0xa30e2814,0xaff8ad4d,0xa17eab05,0xafafac07,0xadfeab5e,0xa44eae3f,0x2cd82875,0xa934af1a,
0xb000af80,0x2fdd2cb0,0x2fdd2ed0,0x2f6e2aaa,0xad72b000,0xa515afd4,0xac32afd4,0x9cb62f5a,0x2e1f1fd9,0x2e3f2ee9,0x2f022814,0xad27af91,
0x2cd82ff4,0xaffca8d5,0x2b052fa0,0x2fed2bb7,0xae99a515,0x2d96aaaa,0xaf5aa993,0xae992765,0x2ff42ddc,0x2e1f2ed0,0x2e1f2fe6,0xa875afff,
0xa8142c87,0xaffca9f1,0xadfe1648,0x2e5e2e99,0xaf5aaf30,0x2eb5a814,0xac5dafed,0xb000a934,0x2c32a8d5,0xa9932e3f,0x2f462875,0x2e7ca8d5,
0xae999fd9,0xb000a814,0xaf6eaee9,0x2c872f91,0xa993afa0,0x2ed0a875,0x2cb0a875,0xaf46ad27,0x2ff42c32,0xab5e2ddc,0x2d272fff,0x2ff42515,
0xa44e2d96,0x9fd9afd4,0xaf30a6a1,0xae5e29f1,0x2814ad27,0x2dfeabb7,0x2ffc2d00,0xae5eae1f,0x2e992f80,0xaa4e2e7c,0xaa4e2c32,0x2fd42aaa,
0xae7c1648,0x9cb6afdd,0xaddcafd4,0xafc91648,0xa875af91,0x2b5e2fbc,0x2f1a244e,0x2e3fab05,0x2b052ff4,0xa44e2fa0,0xafbca8d5,0x2f912bb7,
0xb000ac32,0xa6a1afff,0x25dbaddc,0xb000a515,0x2aaaac5d,0x2c322f6e,0x2e7c2f6e,0x2f80a5db,0x2d272fed,0xae3fadfe,0xaf029fd9,0xae1f2c07,
0xaf5aae5e,0xac5daf30,0x2eb59fd9,0xb000a44e,0x2e7ca30e,0x2ddc2e1f,0x1cb62f1a,0x2fc9a30e,0x217e2f46,0xaf02acb0,0xaf02aed0,0xaf1a2993,
0xaf30ae99,0x2fbc29f1,0x2ee99648,0x2dfeac87,0x2fa02515,0x2faf2993,0xad002aaa,0x2fa0a765,0xa9342d96,0xafeda6a1,0xa814afd4,0xaf3029f1,
0xac87afed,0x30001fd9,0x2f6e2dfe,0x2e99ac07,0x2fff2bb7,0xafe6217e,0xaed0217e,0xaddc2d00,0xac322c87,0xaf462a4e,0x2993adba,0xae7c2c87,
0xa875afed,0x2f1aab05,0x2b5e2ffc,0x2e3facd8,0x2f302e1f,0xaee92bb7,0xafbcad00,0xadfe2d27,0xaf6e9cb6,0x2eb5ac32,0x2eb5a515,0x2dbaad72,
0x2aaaaf5a,0x2ed0ae99,0x2cb0ae99,0xaf802d96,0xab5e2f30,0xafaf244e,0xad002e5e,0x2f1a1fd9,0x2c07af02,0x2b052d27,0x2d4dae1f,0xa814ae3f,
0xac5d2ed0,0x29f1afff,0xad962ddc,0xac5d2fe6,0x28752f80,0xa8d52fe6,0xa8d52fc9,0x2e3faf46,0xa44eafd4,0x2f91adba,0x2b05af6e,0xafbc26a1,
0x96482ffc,0xae99a44e,0xac872ee9,0x29f12d4d,0x2515aff8,0x1cb62f02,0x2d72ae3f,0x2c32aff8,0xaeb5ab05,0xaa4eacd8,0x9648afed,0xac5d2ffc,
0x2d722d27,0xacb02ff4,0xa7652ff4,0x2fffab5e,0xabb7ae7c,0x2ff8aaaa,0x2b5eaf80,0xabb7ac32,0x28142f6e,0xab05ac87,0xad4d2e99,0xac073000,
0x2feda8d5,0x2f30a30e,0x29342f02,0x2814afa0,0xafd49cb6,0x1648aed0,0x1648afe6,0xafdd2d72,0x2ed029f1,0xaf462eb5,0xa9932fdd,0x2cb029f1,
0xad00ad4d,0x2e1f244e,0x2d27aee9,0x2bb7affc,0xad4d2f02,0xafbc2e1f,0xacd8ad27,0x1fd92e3f,0x2f5aacb0,0x2c872993,0x26a12f46,0x2f5aaed0,
0xafff25db,0x2cb0b000,0x2765b000,0xad72a6a1,0x2f1a2814,0xafaf2934,0xad002f30,0xab5e2fed,0x1648afbc,0x2c87affc,0x2e992934,0xa9f1ac07,
0xac322faf,0xaf8028d5,0xaaaaae1f,0xae7c2faf,0x2f1aad72,0xa30e2ed0,0xa30e2fe6,0x2e1f1cb6,0xaffc26a1,0x2fedadba,0x2cd8af6e,0x2b05afd4,
0x2d272c32,0x230e2d72,0xafaf1cb6,0x2d272515,0x9fd9af6e,0x2fbcae99,0x2cd82c87,0x2d4db000,0xac5d2fbc,0xaa4eab05,0x9648af91,0xaeb5244e,
0x2f80ad00,0xaed02fa0,0xacb02fa0,0xaaaa2faf,0xafe626a1,0xaddc1648,0x2fffaa4e,0xaed026a1,0x2d002c07,0xad272ffc,0xae1fa934,0xabb72fbc,
0x1fd9afa0,0x2e5ea30e,0x244e2f02,0x2f30a8d5,0xadba2f46,0x2c87afe6,0x2c87afc9,0x2a4eaf80,0x2fffad96,0x2e7cac5d,0x2fc9ac5d,0xad7229f1,
0x217eadfe,0x2ff4afbc,0x2875aee9,0xaff82f30,0xafed2d00,0x2d4daf1a,0xaf912b5e,0xae5e2faf,0xa5db2e7c,0x9648a993,0xa9f12f46,0xa5db2c32,
0xae3f2fff,0xaff82fc9,0xaff82e7c,0x2f02ad72,0x2c0725db,0xadfe2f5a,0x9fd92d96,0x2fedafdd,0x2f6eaf91,0xa6a12c07,0x2fd4acd8,0x2dbaaf30,
0xa765ab5e,0x2aaaa30e,0x2993af02,0x2515ab5e,0x25dbadfe,0x2d96aee9,0x2f5aafbc,0xafdd2f30,0xaf462b5e,0x2765abb7,0xa515abb7,0xaf802ff8,
0xad002fc9,0xa8d51cb6,0xaff82ddc,0xad002e7c,0x2cd81648,0xadfe2c5d,0xa9342eb5,0xa44e2a4e,0x2c07217e,0x9fd92875,0xadfe2ff4,0x2fedaff8,
0x2fddaf46,0x29f1a515,0x29f12765,0x2eb5af80,0x2515ad96,0x2ddcac87,0x2fffaeb5,0x2c32ad96,0xaf022b05,0x2fa0aee9,0x28d5ae5e,0x230ea934,
0xaf912d00,0xacd82b5e,0x2c07af1a,0xaf302faf,0xad962fc9,0xaeb52ddc,0xac871cb6,0xad962e7c,0x299326a1,0xafc92f5a,0xafe62f5a,0xaaaa2c87,
0x2ff8ae5e,0xaff42ffc,0xa8752dfe,0xa17e2814,0x2f6eafed,0x2fd4af91,0xa6a12d4d,0x2dbaae5e,0x2515ad00,0x2fffaff8,0x2ddca8d5,0x2c32ad00,
0xae1f2993,0x2fafafe6,0x2fafafc9,0x28d5aaaa,0xaf912fdd,0x2ee9af5a,0x2814ad96,0x1fd9a5db,0xab5e2e7c,0xaf022f46,0xa30ea993,0xab5e2c32,
0x2b051648,0xae5e2eb5,0xaee92c5d,0xa9342a4e,0x2fddae5e,0xad962dfe,0xaf5a2ffc,0xa5db2814,0x2ddcafaf,0xacb02d27,0xa7652d27,0x9cb6230e,
0xa765a5db,0x2993a9f1,0x2aaa9648,0x2515a5db,0xaf022cd8,0x28d5a934,0x2fa0adfe,0x230ea44e,0xaf912ff8,0x2814a875,0x2ee9aff4,0x1fd9a17e,
0xaa4e2ddc,0x26a1a765,0x26a1acb0,0x16489cb6,0x9d7f9e49,0xaddcaeb3,0x12480000,0x22ad0000,0x9bdb9cb6,0xac2ead04,0x18b61648,0x290226ad,
0x98b69a49,0xa902aaaf,0x1bdb1a49,0x2c2e2aaf,0x92489648,0xa2ada6ad,0x1d7f1cb6,0x2ddc2d04,0xa420a4b7,0xae8daf7f,0x18b60000,0x23760000,
0xa1e4a312,0xacacad9c,0x1f121cb6,0x29992777,0x9f12a0b6,0xa999ab78,0x21e420b6,0x2cac2b78,0x98b69cb6,0xa376a777,0x24202312,0x2e8d2d9c,
0xa6e0a7db,0xaf3fb025,0x1bdb0000,0x24200000,0xa4e9a5e4,0xad2aae34,0x21e41fdb,0x2a312820,0xa1e4a3db,0xaa31ac21,0x24e923db,0x2d2a2c21,
0x9bdb9fdb,0xa420a820,0x26e025e4,0x2f3f2e34,0xa8d0a980,0xaff2b08c,0x1d7f0000,0x24840000,0xa6e0a820,0xada9aecd,0x2420217f,0x2ac82885,
0xa420a580,0xaac8ac86,0x26e02580,0x2da92c86,0x9d7fa17f,0xa484a885,0x28d02820,0x2ff22ecd,0xaa31ab13,0xb052b0f3,0x1f120000,0x24e90000,
0xa86ba94e,0xae28af65,0x254d2312,0x2b5f28e9,0xa54da712,0xab5faceb,0x286b2712,0x2e282ceb,0x9f12a312,0xa4e9a8e9,0x2a31294e,0x30522f65,
0xab91ac54,0xb0acb15a,0x20520000,0x254d0000,0xa967aa7c,0xaea7affe,0x267b2452,0x2bf6294e,0xa67ba852,0xabf6ad50,0x29672852,0x2ea72d50,
0xa052a452,0xa54da94e,0x2b912a7c,0x30ac2ffe,0xac79ad1e,0xb106b1c1,0x211b0000,0x25b20000,0xaa63abab,0xaf26b04c,0x27a9251b,0x2c4729b3,
0xa7a9a91c,0xac47adb6,0x2a63291c,0x2f262db6,0xa11ba51b,0xa5b2a9b3,0x2c792bab,0x3106304c,0xad2aade8,0xb160b229,0x21e40000,0x26170000,
0xab5fac6d,0xafa5b099,0x286b25e4,0x2c932a17,0xa86ba9e5,0xac93ae1b,0x2b5f29e5,0x2fa52e1b,0xa1e4a5e4,0xa617aa17,0x2d2a2c6d,0x31603099,
0xb1bbb292,0xb44fb4f6,0x267b0000,0x28d00000,0xb012b0e6,0xb216b357,0x2cde2a7c,0x2f3f2cd2,0xacdeae80,0xaf3fb0d9,0x30122e80,0x321630d9,
0xa67baa7c,0xa8d0acd2,0x31bb30e6,0x344f3357,0xb216b2fb,0xb47eb52d,0x26e00000,0x29020000,0xb052b133,0xb257b3a7,0x2d2a2ae1,0x2f8c2d04,
0xad2aaee6,0xaf8cb10c,0x30522ee6,0x3257310c,0xa6e0aae1,0xa902ad04,0x32163133,0x347e33a7,0xb271b364,0xb4aeb565,0x27440000,0x29350000,
0xb092b181,0xb298b3f7,0x2d762b46,0x2fd82d37,0xad76af4c,0xafd8b140,0x30922f4c,0x32983140,0xa744ab46,0xa935ad37,0x32713181,0x34ae33f7,
0xb2cdb3cf,0xb4deb59d,0x27a90000,0x29670000,0xb0d2b1ce,0xb2dab423,0x2dc22bab,0x30122d6a,0xadc2afb2,0xb012b174,0x30d22fb2,0x32da3174,
0xa7a9abab,0xa967ad6a,0x32cd31ce,0x34de3423,0xb329b41d,0xb50eb5d6,0x28070000,0x29990000,0xb113b21c,0xb31cb44c,0x2e0e2c08,0x30392d9c,
0xae0eb00c,0xb039b1a7,0x3113300c,0x331c31a7,0xa807ac08,0xa999ad9c,0x3329321c,0x350e344c,0xb386b453,0xb53fb60f,0x28390000,0x29cc0000,
0xb153b26b,0xb35eb474,0x2e5a2c3a,0x305f2dcf,0xae5ab03f,0xb05fb1db,0x3153303f,0x335e31db,0xa839ac3a,0xa9ccadcf,0x3386326b,0x353f3474,
0xb3e3b489,0xb570b649,0x286b0000,0x29fe0000,0xb194b2b9,0xb3a0b49d,0x2ea72c6d,0x30852e02,0xaea7b072,0xb085b20f,0x31943072,0x33a0320f,
0xa86bac6d,0xa9feae02,0x33e332b9,0x3570349d,0xb420b4bf,0xb5a1b683,0x289e0000,0x2a310000,0xb1d5b308,0xb3e3b4c6,0x2ef32c9f,0x30ac2e34,
0xaef3b0a5,0xb0acb243,0x31d530a5,0x33e33243,0xa89eac9f,0xaa31ae34,0x34203308,0x35a134c6,0xb5d2b6be,0xb76fb857,0x2a630000,0x2bf60000,
0xb413b4ef,0xb523b642,0x30d22e67,0x32092ffe,0xb0d2b278,0xb209b40f,0x34133278,0x3523340f,0xaa63ae67,0xabf6affe,0x35d234ef,0x376f3642,
0xb604b6fa,0xb7a5b878,0x2a950000,0x2c140000,0xb434b519,0xb546b66d,0x30f92e9a,0x32303019,0xb0f9b2ac,0xb230b42a,0x343432ac,0x3546342a,
0xaa95ae9a,0xac14b019,0x36043519,0x37a5366d,0xb637b736,0xb7dbb899,0x2ac80000,0x2c2e0000,0xb456b542,0xb569b699,0x31202ecd,0x32573032,
0xb120b2e1,0xb257b445,0x345632e1,0x35693445,0xaac8aecd,0xac2eb032,0x36373542,0x37db3699,0xb66ab773,0xb809b8bb,0x2afa0000,0x2c470000,
0xb478b56c,0xb58cb6c6,0x31462f00,0x327e304c,0xb146b315,0xb27eb460,0x34783315,0x358c3460,0xaafaaf00,0xac47b04c,0x366a356c,0x380936c6,
0xb69db7b0,0xb825b8dd,0x2b2d0000,0x2c600000,0xb49ab596,0xb5afb6f2,0x316d2f32,0x32a53065,0xb16db34a,0xb2a5b47b,0x349a334a,0x35af347b,
0xab2daf32,0xac60b065,0x369d3596,0x382536f2,0xb6d1b7ee,0xb841b8ff,0x2b5f0000,0x2c790000,0xb4bcb5c1,0xb5d2b71f,0x31942f65,0x32cd307f,
0xb194b37f,0xb2cdb496,0x34bc337f,0x35d23496,0xab5faf65,0xac79b07f,0x36d135c1,0x3841371f,0xb705b817,0xb85db923,0x2b910000,0x2c930000,
0xb4deb5eb,0xb5f6b74d,0x31bb2f98,0x32f43099,0xb1bbb3b4,0xb2f4b4b1,0x34de33b4,0x35f634b1,0xab91af98,0xac93b099,0x370535eb,0x385d374d,
0xb73ab837,0xb87ab946,0x2bc40000,0x2cac0000,0xb500b616,0xb61ab77a,0x31e22fcb,0x331c30b2,0xb1e2b3e9,0xb31cb4cd,0x350033e9,0x361a34cd,
0xabc4afcb,0xacacb0b2,0x373a3616,0x387a377a,0xb897b96b,0xb98dbaa6,0x2cc50000,0x2d900000,0xb63eb7a8,0xb767b895,0x334330cc,0x3442319a,
0xb343b4e8,0xb442b5c8,0x363e34e8,0x376735c8,0xacc5b0cc,0xad90b19a,0x389737a8,0x398d3895,0xb8b4b990,0xb9aebad1,0x2cde0000,0x2da90000,
0xb662b7d7,0xb78db8ae,0x336b30e6,0x345631b4,0xb36bb504,0xb456b5e4,0x36623504,0x378d35e4,0xacdeb0e6,0xada9b1b4,0x38b437d7,0x39ae38ae,
0xb8d2b9b5,0xb9cfbafd,0x2cf80000,0x2dc20000,0xb687b803,0xb7b4b8c7,0x339330ff,0x346a31ce,0xb393b51f,0xb46ab601,0x3687351f,0x37b43601,
0xacf8b0ff,0xadc2b1ce,0x38d23803,0x39cf38c7,0xb8f0b9dc,0xb9f1bb29,0x2d110000,0x2ddc0000,0xb6acb81b,0xb7dbb8e1,0x33bb3119,0x347e31e8,
0xb3bbb53b,0xb47eb61e,0x36ac353b,0x37db361e,0xad11b119,0xaddcb1e8,0x38f0381b,0x39f138e1,0xb90fba02,0xba14bb57,0x2d2a0000,0x2df50000,
0xb6d1b833,0xb801b8fb,0x33e33133,0x34933202,0xb3e3b557,0xb493b63a,0x36d13557,0x3801363a,0xad2ab133,0xadf5b202,0x390f3833,0x3a1438fb,
0xb92eba2a,0xba37bb86,0x2d440000,0x2e0e0000,0xb6f6b84b,0xb815b915,0x3405314d,0x34a7321c,0xb405b573,0xb4a7b657,0x36f63573,0x38153657,
0xad44b14d,0xae0eb21c,0x392e384b,0x3a373915,0xb94dba53,0xba5abbb6,0x2d5d0000,0x2e280000,0xb71bb863,0xb829b930,0x34193167,0x34bc3236,
0xb419b58f,0xb4bcb675,0x371b358f,0x38293675,0xad5db167,0xae28b236,0x394d3863,0x3a5a3930,0xb96dba7c,0xba7ebbe7,0x2d760000,0x2e410000,
0xb741b87c,0xb83db94b,0x342e3181,0x34d03250,0xb42eb5ab,0xb4d0b692,0x374135ab,0x383d3692,0xad76b181,0xae41b250,0x396d387c,0x3a7e394b,
0xa17fa248,0xb1cfb2a1,0x16480000,0x26ad0000,0x9fdba0b6,0xb029b0fd,0x1cb61a48,0x2d002aac,0x9cb69e48,0xad00aeaa,0x1fdb1e48,0x30292eaa,
0x96489a48,0xa6adaaac,0x217f20b6,0x31cf30fd,0xa81fa8b6,0xb27cb365,0x1cb60000,0x27760000,0xa5e4a711,0xb0a6b191,0x231120b6,0x2d972b75,
0xa311a4b6,0xad97af72,0x25e424b6,0x30a62f72,0x9cb6a0b6,0xa776ab75,0x281f2711,0x327c3191,0xaadeabd9,0xb328b414,0x1fdb0000,0x281f0000,
0xa8e8a9e3,0xb122b226,0x25e423db,0x2e2d2c1f,0xa5e4a7da,0xae2db01d,0x28e827da,0x3122301d,0x9fdba3db,0xa81fac1f,0x2ade29e3,0x33283226,
0xaccead7e,0xb3d3b475,0x217f0000,0x28840000,0xaadeac1f,0xb19eb2b9,0x281f257f,0x2ec32c83,0xa81fa97f,0xaec3b080,0x2ade297f,0x319e3080,
0xa17fa57f,0xa884ac83,0x2cce2c1f,0x33d332b9,0xae2daf0e,0xb43eb4d5,0x23110000,0x28e80000,0xac6aad4c,0xb219b34c,0x294d2711,0x2f592ce7,
0xa94dab11,0xaf59b0e4,0x2c6a2b11,0x321930e4,0xa311a711,0xa8e8ace7,0x2e2d2d4c,0x343e334c,0xaf8bb04e,0xb493b534,0x24520000,0x294d0000,
0xad65ae78,0xb294b3df,0x2a7a2852,0x2fef2d4c,0xaa7aac51,0xafefb147,0x2d652c51,0x32943147,0xa452a852,0xa94dad4c,0x2f8b2e78,0x349333df,
0xb074b115,0xb4e7b593,0x251b0000,0x29b10000,0xae5fafa4,0xb30fb438,0x2ba7291b,0x30422db0,0xaba7ad1a,0xb042b1aa,0x2e5f2d1a,0x330f31aa,
0xa51ba91b,0xa9b1adb0,0x30742fa4,0x34e73438,0xb122b1db,0xb53ab5f1,0x25e40000,0x2a160000,0xaf59b067,0xb389b481,0x2c6a29e3,0x308d2e14,
0xac6aade2,0xb08db20d,0x2f592de2,0x3389320d,0xa5e4a9e3,0xaa16ae14,0x31223067,0x353a3481,0xb58db64e,0xb805b887,0x2a7a0000,0x2cce0000,
0xb402b4c9,0xb5dfb6f9,0x30d72e78,0x332830cb,0xb0d7b26f,0xb328b4bd,0x3402326f,0x35df34bd,0xaa7aae78,0xacceb0cb,0x358d34c9,0x380536f9,
0xb5dfb6aa,0xb82ab8b0,0x2ade0000,0x2d000000,0xb43eb511,0xb61ab73d,0x31222edc,0x337130fd,0xb122b2d2,0xb371b4ed,0x343e32d2,0x361a34ed,
0xaadeaedc,0xad00b0fd,0x35df3511,0x382a373d,0xb631b705,0xb850b8d8,0x2b430000,0x2d330000,0xb47bb558,0xb654b780,0x316c2f40,0x33ba312e,
0xb16cb334,0xb3bab51d,0x347b3334,0x3654351d,0xab43af40,0xad33b12e,0x36313558,0x38503780,0xb682b75e,0xb874b900,0x2ba70000,0x2d650000,
0xb4b7b59f,0xb68db7c2,0x31b62fa4,0x34023160,0xb1b6b396,0xb402b54c,0x34b73396,0x368d354c,0xaba7afa4,0xad65b160,0x3682359f,0x387437c2,
0xb6d2b7b7,0xb899b927,0x2c060000,0x2d970000,0xb4f3b5e5,0xb6c6b802,0x32013004,0x34263191,0xb201b3f7,0xb426b57c,0x34f333f7,0x36c6357c,
0xac06b004,0xad97b191,0x36d235e5,0x38993802,0xb721b807,0xb8bcb94d,0x2c380000,0x2dc90000,0xb52fb62b,0xb6ffb822,0x324b3036,0x344b31c3,
0xb24bb42c,0xb44bb5ab,0x352f342c,0x36ff35ab,0xac38b036,0xadc9b1c3,0x3721362b,0x38bc3822,0xb76fb832,0xb8e0b972,0x2c6a0000,0x2dfb0000,
0xb56ab670,0xb737b842,0x32943067,0x346f31f4,0xb294b45d,0xb46fb5da,0x356a345d,0x373735da,0xac6ab067,0xadfbb1f4,0x376f3670,0x38e03842,
0xb7bdb85d,0xb902b996,0x2c9c0000,0x2e2d0000,0xb5a5b6b5,0xb76fb862,0x32de3099,0x34933226,0xb2deb48d,0xb493b608,0x35a5348d,0x376f3608,
0xac9cb099,0xae2db226,0x37bd36b5,0x39023862,0xb924b9ba,0xba1dbab5,0x2e5f0000,0x2fef0000,0xb7a6b881,0xb8a8b96d,0x34b73257,0x35d433df,
0xb4b7b637,0xb5d4b7a1,0x37a63637,0x38a837a1,0xae5fb257,0xafefb3df,0x39243881,0x3a1d396d,0xb946b9dc,0xba39bad0,0x2e910000,0x30100000,
0xb7ddb8a0,0xb8c1b989,0x34db3288,0x35f73408,0xb4dbb665,0xb5f7b7cd,0x37dd3665,0x38c137cd,0xae91b288,0xb010b408,0x394638a0,0x3a393989,
0xb966b9fe,0xba54bae9,0x2ec30000,0x30290000,0xb80ab8bf,0xb8dbb9a4,0x34ff32b9,0x361a3420,0xb4ffb693,0xb61ab7f9,0x380a3693,0x38db37f9,
0xaec3b2b9,0xb029b420,0x396638bf,0x3a5439a4,0xb986ba1f,0xba6fbb02,0x2ef50000,0x30420000,0xb825b8dd,0xb8f3b9be,0x352332ea,0x363c3438,
0xb523b6c1,0xb63cb812,0x382536c1,0x38f33812,0xaef5b2ea,0xb042b438,0x398638dd,0x3a6f39be,0xb9a6ba3f,0xba89bb1a,0x2f270000,0x305b0000,
0xb840b8fb,0xb90cb9d8,0x3546331b,0x365f3451,0xb546b6ee,0xb65fb828,0x384036ee,0x390c3828,0xaf27b31b,0xb05bb451,0x39a638fb,0x3a8939d8,
0xb9c5ba5e,0xbaa2bb30,0x2f590000,0x30740000,0xb85ab918,0xb924b9f2,0x356a334c,0x36823469,0xb56ab71b,0xb682b83d,0x385a371b,0x3924383d,
0xaf59b34c,0xb074b469,0x39c53918,0x3aa239f2,0xb9e3ba7c,0xbababb46,0x2f8b0000,0x308d0000,0xb874b935,0xb93cba0b,0x358d337d,0x36a43481,
0xb58db748,0xb6a4b852,0x38743748,0x393c3852,0xaf8bb37d,0xb08db481,0x39e33935,0x3aba3a0b,0xba00ba99,0xbad1bb5a,0x2fbd0000,0x30a60000,
0xb88eb951,0xb954ba23,0x35b133ae,0x36c63499,0xb5b1b775,0xb6c6b867,0x388e3775,0x39543867,0xafbdb3ae,0xb0a6b499,0x3a003951,0x3ad13a23,
0xbae8bb6e,0xbb7fbbdd,0x30be0000,0x31850000,0xb96bba3b,0xba19bae6,0x36e834b1,0x37f33570,0xb6e8b87c,0xb7f3b91d,0x396b387c,0x3a19391d,
0xb0beb4b1,0xb185b570,0x3ae83a3b,0x3b7f3ae6,0xbafebb80,0xbb8ebbe6,0x30d70000,0x319e0000,0xb982ba52,0xba2dbaf9,0x370a34c9,0x380a3587,
0xb70ab891,0xb80ab930,0x39823891,0x3a2d3930,0xb0d7b4c9,0xb19eb587,0x3afe3a52,0x3b8e3af9,0xbb13bb91,0xbb9cbbed,0x30f00000,0x31b60000,
0xb999ba69,0xba41bb0b,0x372c34e1,0x381a359f,0xb72cb8a6,0xb81ab943,0x399938a6,0x3a413943,0xb0f0b4e1,0xb1b6b59f,0x3b133a69,0x3b9c3b0b,
0xbb27bba0,0xbba9bbf4,0x31090000,0x31cf0000,0xb9afba7f,0xba54bb1d,0x374e34f9,0x382a35b6,0xb74eb8ba,0xb82ab956,0x39af38ba,0x3a543956,
0xb109b4f9,0xb1cfb5b6,0x3b273a7f,0x3ba93b1d,0xbb3abbaf,0xbbb5bbf8,0x31220000,0x31e80000,0xb9c5ba95,0xba67bb2e,0x376f3511,0x383a35ce,
0xb76fb8ce,0xb83ab969,0x39c538ce,0x3a673969,0xb122b511,0xb1e8b5ce,0x3b3a3a95,0x3bb53b2e,0xbb4cbbbc,0xbbc0bbfc,0x313b0000,0x32010000,
0xb9dabaaa,0xba7abb3e,0x37903529,0x384a35e5,0xb790b8e2,0xb84ab97b,0x39da38e2,0x3a7a397b,0xb13bb529,0xb201b5e5,0x3b4c3aaa,0x3bc03b3e,
0xbb5ebbc9,0xbbcbbbff,0x31530000,0x32190000,0xb9f0babf,0xba8cbb4e,0x37b23540,0x385a35fd,0xb7b2b8f6,0xb85ab98d,0x39f038f6,0x3a8c398d,
0xb153b540,0xb219b5fd,0x3b5e3abf,0x3bcb3b4e,0xbb6fbbd4,0xbbd4bc00,0x316c0000,0x32320000,0xba04bad3,0xba9ebb5d,0x37d23558,0x386a3614,
0xb7d2b909,0xb86ab99f,0x3a043909,0x3a9e399f,0xb16cb558,0xb232b614,0x3b6f3ad3,0x3bd43b5d,0x0,0x0,0x0,0x0,
0x2e1f0000,0x336431a8,0x33643400,0x2e1f31a8,0x31a80000,0x31a83400,0xb1a80000,0xb1a8b400,0x33640000,0xae1f31a8,0xae1fb400,0x336431a8,
0x34000000,0xb4000000,0x34000000,0xb4000000,0x33640000,0xae1fb1a8,0xae1f3400,0x3364b1a8,0x31a80000,0x31a8b400,0xb1a80000,0xb1a83400,
0x2e1f0000,0x3364b1a8,0x3364b400,0x2e1fb1a8,0x0,0x0,0x0,0x0,0xae1f0000,0xb36431a8,0xb3643400,0xae1f31a8,
0xb1a80000,0xb1a83400,0x31a80000,0x31a8b400,0xb3640000,0x2e1f31a8,0x2e1fb400,0xb36431a8,0xb4000000,0x34000000,0xb4000000,0x34000000,
0xb3640000,0x2e1fb1a8,0x2e1f3400,0xb364b1a8,0xb1a80000,0xb1a8b400,0x31a80000,0x31a83400,0xae1f0000,0xb364b1a8,0xb364b400,0xae1fb1a8,
0x0,0x0,0x0,0x0,0xae1f0000,0xb364b1a8,0xb364b400,0xae1fb1a8,0x31a80000,0x31a83400,0xb1a80000,0xb1a8b400,
0xb3640000,0x2e1fb1a8,0x2e1f3400,0xb364b1a8,0x34000000,0xb4000000,0x34000000,0xb4000000,0xb3640000,0x2e1f31a8,0x2e1fb400,0xb36431a8,
0x31a80000,0x31a8b400,0xb1a80000,0xb1a83400,0xae1f0000,0xb36431a8,0xb3643400,0xae1f31a8,0x0,0x0,0x0,0x0,
0x2e1f0000,0x3364b1a8,0x3364b400,0x2e1fb1a8,0xb1a80000,0xb1a83400,0x31a80000,0x31a8b400,0x33640000,0xae1fb1a8,0xae1f3400,0x3364b1a8,
0xb4000000,0x34000000,0xb4000000,0x34000000,0x33640000,0xae1f31a8,0xae1fb400,0x336431a8,0xb1a80000,0xb1a8b400,0x31a80000,0x31a83400,
0x2e1f0000,0x336431a8,0x33643400,0x2e1f31a8,0x34003400,0x34003400,0x34003400,0x34003400,0x33643400,0x2e1f31a8,0xae1f0000,0xb364b1a8,
0x31a83400,0xb1a80000,0xb1a8b400,0x31a80000,0x2e1f3400,0xb364b1a8,0x33640000,0xae1f31a8,0x3400,0xb400,0x3400,0xb400,
0xae1f3400,0x3364b1a8,0xb3640000,0x2e1f31a8,0xb1a83400,0x31a80000,0x31a8b400,0xb1a80000,0xb3643400,0xae1f31a8,0x2e1f0000,0x3364b1a8,
0xb4003400,0xb4003400,0xb4003400,0xb4003400,0xb3643400,0xae1f31a8,0x2e1f0000,0x3364b1a8,0xb1a83400,0x31a80000,0x31a8b400,0xb1a80000,
0xae1f3400,0x3364b1a8,0xb3640000,0x2e1f31a8,0x3400,0xb400,0x3400,0xb400,0x2e1f3400,0xb364b1a8,0x33640000,0xae1f31a8,
0x31a83400,0xb1a80000,0xb1a8b400,0x31a80000,0x33643400,0x2e1f31a8,0xae1f0000,0xb364b1a8,0x34003400,0x34003400,0x34003400,0x34003400,
0xb364b400,0xae1fb1a8,0x2e1f0000,0x336431a8,0x31a83400,0xb1a80000,0xb1a8b400,0x31a80000,0xae1fb400,0x336431a8,0xb3640000,0x2e1fb1a8,
0x3400,0xb400,0x3400,0xb400,0x2e1fb400,0xb36431a8,0x33640000,0xae1fb1a8,0xb1a83400,0x31a80000,0x31a8b400,0xb1a80000,
0x3364b400,0x2e1fb1a8,0xae1f0000,0xb36431a8,0xb4003400,0xb4003400,0xb4003400,0xb4003400,0x3364b400,0x2e1fb1a8,0xae1f0000,0xb36431a8,
0xb1a83400,0x31a80000,0x31a8b400,0xb1a80000,0x2e1fb400,0xb36431a8,0x33640000,0xae1fb1a8,0x3400,0xb400,0x3400,0xb400,
0xae1fb400,0x336431a8,0xb3640000,0x2e1fb1a8,0x31a83400,0xb1a80000,0xb1a8b400,0x31a80000,0xb364b400,0xae1fb1a8,0x2e1f0000,0x336431a8,
0x0,0x0,0x0,0x0,0xae1f0000,0xb364b1a8,0xb364b400,0xae1fb1a8,0xb1a80000,0xb1a8b400,0x31a80000,0x31a83400,
0xb3640000,0x2e1fb1a8,0x2e1f3400,0xb364b1a8,0xb4000000,0x34000000,0xb4000000,0x34000000,0xb3640000,0x2e1f31a8,0x2e1fb400,0xb36431a8,
0xb1a80000,0xb1a83400,0x31a80000,0x31a8b400,0xae1f0000,0xb36431a8,0xb3643400,0xae1f31a8,0x0,0x0,0x0,0x0,
0x2e1f0000,0x3364b1a8,0x3364b400,0x2e1fb1a8,0x31a80000,0x31a8b400,0xb1a80000,0xb1a83400,0x33640000,0xae1fb1a8,0xae1f3400,0x3364b1a8,
0x34000000,0xb4000000,0x34000000,0xb4000000,0x33640000,0xae1f31a8,0xae1fb400,0x336431a8,0x31a80000,0x31a83400,0xb1a80000,0xb1a8b400,
0x2e1f0000,0x336431a8,0x33643400,0x2e1f31a8,0x0,0x0,0x0,0x0,0x2e1f0000,0x336431a8,0x33643400,0x2e1f31a8,
0xb1a80000,0xb1a8b400,0x31a80000,0x31a83400,0x33640000,0xae1f31a8,0xae1fb400,0x336431a8,0xb4000000,0x34000000,0xb4000000,0x34000000,
0x33640000,0xae1fb1a8,0xae1f3400,0x3364b1a8,0xb1a80000,0xb1a83400,0x31a80000,0x31a8b400,0x2e1f0000,0x3364b1a8,0x3364b400,0x2e1fb1a8,
0x0,0x0,0x0,0x0,0xae1f0000,0xb36431a8,0xb3643400,0xae1f31a8,0x31a80000,0x31a8b400,0xb1a80000,0xb1a83400,
0xb3640000,0x2e1f31a8,0x2e1fb400,0xb36431a8,0x34000000,0xb4000000,0x34000000,0xb4000000,0xb3640000,0x2e1fb1a8,0x2e1f3400,0xb364b1a8,
0x31a80000,0x31a83400,0xb1a80000,0xb1a8b400,0xae1f0000,0xb364b1a8,0xb364b400,0xae1fb1a8,
};

typedef CUresult (*EncodeFn)(CUtensorMap*, CUtensorMapDataType, cuuint32_t, void*, const cuuint64_t*, const cuuint64_t*,
                             const cuuint32_t*, const cuuint32_t*, CUtensorMapInterleave, CUtensorMapSwizzle,
                             CUtensorMapL2promotion, CUtensorMapFloatOOBfill);

}

extern "C" void kernel_launch(void* const* d_in, const int* in_sizes, int n_in, void* d_out, int out_size) {
    Params p;
    p.x = (const __nv_bfloat16*)d_in[0];
    p.lar = (const __nv_bfloat16*)d_in[1];
    p.aim = (const __nv_bfloat16*)d_in[2];
    p.cr = (const __nv_bfloat16*)d_in[3];
    p.ci = (const __nv_bfloat16*)d_in[4];
    p.logdt = (const __nv_bfloat16*)d_in[5];
    p.dskip = (const __nv_bfloat16*)d_in[6];
    p.wr = (const __nv_bfloat16*)d_in[8];
    p.out = (__nv_bfloat16*)d_out;
    cudaGetSymbolAddress((void**)&p.sc, g_scratch);
    cudaGetSymbolAddress((void**)&p.tab, g_tab);

    void* fn = nullptr;
    cudaDriverEntryPointQueryResult qr;
    cudaGetDriverEntryPoint("cuTensorMapEncodeTiled", &fn, cudaEnableDefault, &qr);
    EncodeFn enc = (EncodeFn)fn;
    CUtensorMap tm_x, tm_g, tm_d;
    const cuuint32_t es[5] = {1, 1, 1, 1, 1};
    {
        const cuuint64_t gd[4] = {1024, 128, 8, 2}, gs[3] = {32768, 4096, 2048};
        const cuuint32_t bx[4] = {16, 64, 4, 1};
        enc(&tm_x, CU_TENSOR_MAP_DATA_TYPE_BFLOAT16, 4, d_in[0], gd, gs, bx, es, CU_TENSOR_MAP_INTERLEAVE_NONE,
            CU_TENSOR_MAP_SWIZZLE_NONE, CU_TENSOR_MAP_L2_PROMOTION_NONE, CU_TENSOR_MAP_FLOAT_OOB_FILL_NONE);
    }
    {
        char *wg = (char*)d_in[9], *wu = (char*)d_in[10];
        p.up_first = wu < wg;
        const cuuint64_t gd[3] = {3584, 1024, 2}, gs[2] = {7168, (cuuint64_t)(p.up_first ? wg - wu : wu - wg)};
        const cuuint32_t bx[3] = {64, 64, 2};
        enc(&tm_g, CU_TENSOR_MAP_DATA_TYPE_BFLOAT16, 3, p.up_first ? wu : wg, gd, gs, bx, es, CU_TENSOR_MAP_INTERLEAVE_NONE,
            CU_TENSOR_MAP_SWIZZLE_128B, (CUtensorMapL2promotion)GPROMO, CU_TENSOR_MAP_FLOAT_OOB_FILL_NONE);
    }
    {
        const cuuint64_t gd[3] = {64, 3584, 16}, gs[2] = {2048, 128};
        const cuuint32_t bx[3] = {64, 64, 2};
        enc(&tm_d, CU_TENSOR_MAP_DATA_TYPE_BFLOAT16, 3, d_in[11], gd, gs, bx, es, CU_TENSOR_MAP_INTERLEAVE_NONE,
            CU_TENSOR_MAP_SWIZZLE_128B, (CUtensorMapL2promotion)DPROMO, CU_TENSOR_MAP_FLOAT_OOB_FILL_NONE);
    }
    cudaFuncSetAttribute(fused_kernel, cudaFuncAttributeMaxDynamicSharedMemorySize, SM_TOTAL + 256);
    fused_kernel<<<128, NTHREADS, SM_TOTAL + 256>>>(p, tm_x, tm_g, tm_d);
}
```

```cpp
#include <cuda_runtime.h>
#include <cuda.h>
#include <cuda_bf16.h>
#include <cuda_fp16.h>
#include <stdint.h>

#define TG(i)
#define TS(i)
#define TSL(i)

#define TSW 0
#define SDELAY 1500
#define EDELAY 800
#define FILL 0x53211
#define STSLEEP 200
#define NPRE 8
#define IDEPTH2 3
#define ORDER 0x74365210
#define SDAT 5
#define REFILL 0x631
#define NREP 4
#define GPROMO 0
#define DPROMO 0
#define WPOL "evict_first"
#define FUSE 3
#define PDELAY 900
#define IDEPTH 3

namespace {

constexpr int NTHREADS = 512;
constexpr int SPIN_LIMIT = 1 << 16;

constexpr int SM_SLAB = 0;
constexpr int SM_RING = 32768;
constexpr int SUB     = 1088;
constexpr int SM_K    = SM_RING + 10 * 8192;
constexpr int SM_S    = SM_K + 32 * SUB;
constexpr int SM_U    = SM_S + 32 * SUB;
constexpr int SM_F2   = SM_U + 32 * SUB;
constexpr int SM_XSEL = SM_F2 + 1536;
constexpr int SM_PAIR = SM_XSEL + 4096;
constexpr int SM_H    = SM_PAIR + 2048;
constexpr int SM_KEYS = SM_H + 1024;
constexpr int SM_TOK  = SM_KEYS + 64;
constexpr int SM_XRAW = SM_TOK + 16;
constexpr int SM_SCL  = SM_XRAW + 128;
constexpr int SM_BAR  = SM_SCL + 16;
constexpr int SM_RED  = SM_XSEL;
constexpr int SM_TAB  = SM_RING + 7 * 8192;
constexpr int B_FULL = 0, B_ROW = 24, B_STG = 32, B_SFREE = 34, B_SDONE = 35, B_SLAB = 36, B_TOK = 38, B_UFREE = 39, B_PAIR = 41,
              B_TAB = 42, B_TFREE = 43, B_KFREE = 44, B_U = 46, B_PEER = 48, NBAR = 52;
constexpr int SM_TOTAL = SM_BAR + NBAR * 8;
static_assert(SM_TOTAL + 256 <= 232448, "smem");
__device__ __forceinline__ uint32_t chunk_off(int n) {
    return n < 5 ? SM_RING + n * 16384 : n < 7 ? SM_S + (n - 5) * 16384 : n < 9 ? SM_K + (n - 7) * 16384 : SM_RING + (n - 9) * 16384;
}
constexpr int KP = 272;

struct Scratch {
    uint4 stats[4][1032];
    uint32_t part[128 * 56 * 16];
    uint32_t epoch;
};
__device__ Scratch g_scratch;

struct Params {
    const __nv_bfloat16 *lar, *aim, *cr, *ci, *logdt, *dskip;
    const __nv_bfloat16 *x, *wr;
    __nv_bfloat16* out;
    Scratch* sc;
    const uint4* tab;
    int up_first;
};

__device__ __forceinline__ uint4 ldg128(const void* p) {
    uint4 v; asm volatile("ld.global.nc.v4.u32 {%0,%1,%2,%3}, [%4];" : "=r"(v.x), "=r"(v.y), "=r"(v.z), "=r"(v.w) : "l"(p)); return v;
}
__device__ __forceinline__ uint4 ld_relaxed128(const void* p) {
    uint4 v;
    asm volatile("{ .reg .b128 t; ld.relaxed.gpu.global.b128 t, [%4]; mov.b128 {%0,%1,%2,%3}, t; }"
                 : "=r"(v.x), "=r"(v.y), "=r"(v.z), "=r"(v.w) : "l"(p) : "memory");
    return v;
}
__device__ __forceinline__ void st_relaxed128(void* p, uint4 v) {
    asm volatile("{ .reg .b128 t; mov.b128 t, {%1,%2,%3,%4}; st.relaxed.gpu.global.b128 [%0], t; }"
                 :: "l"(p), "r"(v.x), "r"(v.y), "r"(v.z), "r"(v.w) : "memory");
}
__device__ __forceinline__ void st_relaxed32(void* p, uint32_t v) {
    asm volatile("st.relaxed.gpu.global.u32 [%0], %1;" :: "l"(p), "r"(v) : "memory");
}
__device__ __forceinline__ uint32_t lds32(uint32_t a) { uint32_t v; asm volatile("ld.shared.u32 %0, [%1];" : "=r"(v) : "r"(a)); return v; }
__device__ __forceinline__ uint32_t lds16(uint32_t a) { uint32_t v; asm volatile("ld.shared.u16 %0, [%1];" : "=r"(v) : "r"(a)); return v; }
__device__ __forceinline__ uint2 lds64(uint32_t a) { uint2 v; asm volatile("ld.shared.v2.u32 {%0,%1}, [%2];" : "=r"(v.x), "=r"(v.y) : "r"(a)); return v; }
__device__ __forceinline__ uint4 lds128(uint32_t a) {
    uint4 v; asm volatile("ld.shared.v4.u32 {%0,%1,%2,%3}, [%4];" : "=r"(v.x), "=r"(v.y), "=r"(v.z), "=r"(v.w) : "r"(a)); return v;
}
__device__ __forceinline__ void sts16(uint32_t a, uint32_t v) { asm volatile("st.shared.u16 [%0], %1;" :: "r"(a), "h"((uint16_t)v) : "memory"); }
__device__ __forceinline__ void sts32(uint32_t a, uint32_t v) { asm volatile("st.shared.u32 [%0], %1;" :: "r"(a), "r"(v) : "memory"); }
__device__ __forceinline__ void sts64(uint32_t a, uint32_t x, uint32_t y) { asm volatile("st.shared.v2.u32 [%0], {%1,%2};" :: "r"(a), "r"(x), "r"(y) : "memory"); }
__device__ __forceinline__ void sts128(uint32_t a, uint32_t x, uint32_t y, uint32_t z, uint32_t w) {
    asm volatile("st.shared.v4.u32 [%0], {%1,%2,%3,%4};" :: "r"(a), "r"(x), "r"(y), "r"(z), "r"(w) : "memory");
}
__device__ __forceinline__ void ldsm4(uint32_t a, uint32_t& r0, uint32_t& r1, uint32_t& r2, uint32_t& r3) {
    asm volatile("ldmatrix.sync.aligned.m8n8.x4.shared.b16 {%0,%1,%2,%3}, [%4];" : "=r"(r0), "=r"(r1), "=r"(r2), "=r"(r3) : "r"(a));
}
__device__ __forceinline__ void mma_f16(float (&d)[4], uint32_t a0, uint32_t a1, uint32_t a2, uint32_t a3, uint32_t b0, uint32_t b1) {
    asm("mma.sync.aligned.m16n8k16.row.col.f32.f16.f16.f32 {%0,%1,%2,%3}, {%4,%5,%6,%7}, {%8,%9}, {%0,%1,%2,%3};"
        : "+f"(d[0]), "+f"(d[1]), "+f"(d[2]), "+f"(d[3]) : "r"(a0), "r"(a1), "r"(a2), "r"(a3), "r"(b0), "r"(b1));
}
__device__ __forceinline__ void mma_bf16(float (&d)[4], uint32_t a0, uint32_t a1, uint32_t a2, uint32_t a3, uint32_t b0, uint32_t b1) {
    asm("mma.sync.aligned.m16n8k16.row.col.f32.bf16.bf16.f32 {%0,%1,%2,%3}, {%4,%5,%6,%7}, {%8,%9}, {%0,%1,%2,%3};"
        : "+f"(d[0]), "+f"(d[1]), "+f"(d[2]), "+f"(d[3]) : "r"(a0), "r"(a1), "r"(a2), "r"(a3), "r"(b0), "r"(b1));
}
__device__ __forceinline__ uint32_t prmt(uint32_t a, uint32_t b, uint32_t s) { uint32_t d; asm("prmt.b32 %0, %1, %2, %3;" : "=r"(d) : "r"(a), "r"(b), "r"(s)); return d; }
__device__ __forceinline__ uint32_t pack_h(float lo, float hi) { uint32_t d; asm("cvt.rn.f16x2.f32 %0, %1, %2;" : "=r"(d) : "f"(hi), "f"(lo)); return d; }
__device__ __forceinline__ uint32_t pack_b(float lo, float hi) { uint32_t d; asm("cvt.rn.bf16x2.f32 %0, %1, %2;" : "=r"(d) : "f"(hi), "f"(lo)); return d; }
__device__ __forceinline__ float blo(uint32_t v) { return __uint_as_float(v << 16); }
__device__ __forceinline__ float bhi(uint32_t v) { return __uint_as_float(v & 0xFFFF0000u); }
__device__ __forceinline__ float rb(float v) { return blo(pack_b(v, v)); }
__device__ __forceinline__ uint32_t bsub2(uint32_t a, uint32_t b) { uint32_t d; asm("sub.rn.bf16x2 %0, %1, %2;" : "=r"(d) : "r"(a), "r"(b)); return d; }
__device__ __forceinline__ uint32_t badd2(uint32_t a, uint32_t b) { uint32_t d; asm("add.rn.bf16x2 %0, %1, %2;" : "=r"(d) : "r"(a), "r"(b)); return d; }
__device__ __forceinline__ uint32_t bmul2(uint32_t a, uint32_t b) { uint32_t d; asm("mul.rn.bf16x2 %0, %1, %2;" : "=r"(d) : "r"(a), "r"(b)); return d; }
__device__ __forceinline__ uint32_t bfma2(uint32_t a, uint32_t b, uint32_t c) { uint32_t d; asm("fma.rn.bf16x2 %0, %1, %2, %3;" : "=r"(d) : "r"(a), "r"(b), "r"(c)); return d; }
__device__ __forceinline__ uint32_t dup_lo(uint32_t v) { uint32_t d; asm("{ .reg .b16 l, h; mov.b32 {l, h}, %1; mov.b32 %0, {l, l}; }" : "=r"(d) : "r"(v)); return d; }
__device__ __forceinline__ uint32_t dup_hi(uint32_t v) { uint32_t d; asm("{ .reg .b16 l, h; mov.b32 {l, h}, %1; mov.b32 %0, {h, h}; }" : "=r"(d) : "r"(v)); return d; }
__device__ __forceinline__ uint32_t norm2(uint32_t x, uint32_t m, uint32_t hi, uint32_t lo) {
    uint32_t a = bsub2(x, m);
    return bfma2(a, hi, bmul2(a, lo));
}
__device__ __forceinline__ float ex2(float v) { float d; asm("ex2.approx.ftz.f32 %0, %1;" : "=f"(d) : "f"(v)); return d; }
__device__ __forceinline__ float rcp(float v) { float d; asm("rcp.approx.ftz.f32 %0, %1;" : "=f"(d) : "f"(v)); return d; }
__device__ __forceinline__ float sigmoidf_(float v) { return rcp(1.0f + ex2(-1.4426950408889634f * v)); }
__device__ __forceinline__ float siluf_(float v) { return v * sigmoidf_(v); }

__device__ __forceinline__ void mbar_init(uint32_t a, int n) { asm volatile("mbarrier.init.shared::cta.b64 [%0], %1;" :: "r"(a), "r"(n) : "memory"); }
__device__ __forceinline__ void mbar_expect(uint32_t a, int tx) { asm volatile("mbarrier.arrive.expect_tx.shared::cta.b64 _, [%0], %1;" :: "r"(a), "r"(tx) : "memory"); }
__device__ __forceinline__ void mbar_arrive(uint32_t a) { asm volatile("mbarrier.arrive.shared::cta.b64 _, [%0];" :: "r"(a) : "memory"); }
__device__ __forceinline__ bool mbar_try(uint32_t a) {
    uint32_t d; asm volatile("{ .reg .pred p; mbarrier.try_wait.parity.shared::cta.b64 p, [%1], 0; selp.u32 %0, 1, 0, p; }" : "=r"(d) : "r"(a) : "memory"); return d;
}
__device__ __forceinline__ void mbar_wait(uint32_t a) {
    if (__builtin_expect(!mbar_try(a), 0)) {
        int n = SPIN_LIMIT;
        while (!mbar_try(a) && --n) {}
    }
}
__device__ __forceinline__ void mbar_arrive_peer(uint32_t a) { asm volatile("mbarrier.arrive.relaxed.cluster.shared::cluster.b64 _, [%0];" :: "r"(a) : "memory"); }
__device__ __forceinline__ uint32_t mapa(uint32_t a, uint32_t rank) { uint32_t d; asm("mapa.shared::cluster.u32 %0, %1, %2;" : "=r"(d) : "r"(a), "r"(rank)); return d; }
__device__ __forceinline__ void st_async2(uint32_t a, uint32_t x, uint32_t y, uint32_t bar) {
    asm volatile("st.async.weak.shared::cluster.mbarrier::complete_tx::bytes.v2.b32 [%0], {%1,%2}, [%3];" :: "r"(a), "r"(x), "r"(y), "r"(bar) : "memory");
}
__device__ __forceinline__ void st_async4(uint32_t a, uint32_t x, uint32_t y, uint32_t z, uint32_t w, uint32_t bar) {
    asm volatile("st.async.weak.shared::cluster.mbarrier::complete_tx::bytes.v4.b32 [%0], {%1,%2,%3,%4}, [%5];"
                 :: "r"(a), "r"(x), "r"(y), "r"(z), "r"(w), "r"(bar) : "memory");
}
__device__ __forceinline__ void stsm4(uint32_t a, uint32_t r0, uint32_t r1, uint32_t r2, uint32_t r3) {
    asm volatile("stmatrix.sync.aligned.m8n8.x4.shared.b16 [%0], {%1,%2,%3,%4};" :: "r"(a), "r"(r0), "r"(r1), "r"(r2), "r"(r3) : "memory");
}
__device__ __forceinline__ void proxy_fence() { asm volatile("fence.proxy.async.shared::cta;" ::: "memory"); }
__device__ __forceinline__ void bar_sync(int id, int n) { asm volatile("bar.sync %0, %1;" :: "r"(id), "r"(n) : "memory"); }
__device__ __forceinline__ void bar_arrive(int id, int n) { asm volatile("bar.arrive %0, %1;" :: "r"(id), "r"(n) : "memory"); }
__device__ __forceinline__ void group_sync(int wgi) {
    asm volatile("{ .reg .pred p; setp.ne.s32 p, %0, 0; @p bar.sync 11, 128; @!p bar.sync 10, 128; }" :: "r"(wgi) : "memory");
}
__device__ __forceinline__ void cluster_arrive() { asm volatile("barrier.cluster.arrive.relaxed.aligned;" ::: "memory"); }
__device__ __forceinline__ void cluster_wait() { asm volatile("barrier.cluster.wait.aligned;" ::: "memory"); }
__device__ __forceinline__ void tma3d(uint32_t dst, const CUtensorMap* tm, int c0, int c1, int c2, uint32_t bar, uint64_t pol) {
    asm volatile("cp.async.bulk.tensor.3d.shared::cluster.global.mbarrier::complete_tx::bytes.L2::cache_hint [%0], [%1, {%3, %4, %6}], [%2], %5;"
                 :: "r"(dst), "l"(tm), "r"(bar), "r"(c0), "r"(c1), "l"(pol), "r"(c2) : "memory");
}
__device__ __forceinline__ bool elect() {
    uint32_t p; asm volatile("{ .reg .pred p; elect.sync _|p, 0xFFFFFFFF; selp.u32 %0, 1, 0, p; }" : "=r"(p)); return p;
}

struct cf { float r, i; };
__device__ __forceinline__ cf cmul(cf a, cf b) { return {a.r * b.r - a.i * b.i, a.r * b.i + a.i * b.r}; }
__device__ __forceinline__ cf csq(cf a) { return {a.r * a.r - a.i * a.i, (a.r + a.r) * a.i}; }
__device__ __forceinline__ cf cexp_(float a2, float b) { float m = ex2(a2); return {m * __cosf(b), m * __sinf(b)}; }
struct hc { uint32_t r, i; };
__device__ __forceinline__ hc pk(cf a, cf b) { return {pack_h(a.r, b.r), pack_h(a.i, b.i)}; }
__device__ __forceinline__ hc hmulc(hc a, hc b) {
    const __half2 ar = *reinterpret_cast<__half2*>(&a.r), ai = *reinterpret_cast<__half2*>(&a.i);
    const __half2 br = *reinterpret_cast<__half2*>(&b.r), bi = *reinterpret_cast<__half2*>(&b.i);
    const __half2 r = __hfma2(ar, br, __hneg2(__hmul2_rn(ai, bi))), i = __hfma2(ar, bi, __hmul2_rn(ai, br));
    return {*reinterpret_cast<const uint32_t*>(&r), *reinterpret_cast<const uint32_t*>(&i)};
}
__device__ __forceinline__ void sth(uint32_t a, hc v) { sts32(a, v.r); sts32(a + 128, v.i); }
__device__ __forceinline__ uint32_t cpy(uint32_t v, uint32_t z) { uint32_t d; asm("xor.b32 %0, %1, %2;" : "=r"(d) : "r"(v), "r"(z)); return d; }
__device__ __forceinline__ uint32_t pin(uint32_t v) { return __shfl_sync(0xFFFFFFFFu, v, threadIdx.x & 31); }
__device__ __forceinline__ void sched_fence() { asm volatile("pmevent 0;" ::: "memory"); }
__device__ __forceinline__ float tanh_(float v) { float d; asm("tanh.approx.f32 %0, %1;" : "=f"(d) : "f"(v)); return d; }
__device__ __forceinline__ float silu2(float h) {
    return fmaf(h, tanh_(h), h);
}
__device__ __forceinline__ uint32_t hfma2_(uint32_t a, uint32_t b, uint32_t c) { uint32_t d; asm("fma.rn.f16x2 %0, %1, %2, %3;" : "=r"(d) : "r"(a), "r"(b), "r"(c)); return d; }
__device__ __forceinline__ uint32_t hfms2_(uint32_t a, uint32_t b, uint32_t c) {
    uint32_t d; asm("{ .reg .b32 t; neg.f16x2 t, %1; fma.rn.f16x2 %0, t, %2, %3; }" : "=r"(d) : "r"(a), "r"(b), "r"(c)); return d;
}

__device__ __forceinline__ uint64_t bdesc(uint32_t addr, uint32_t sbo) {
    return (uint64_t)((addr & 0x3FFFFu) >> 4) | ((uint64_t)(128 >> 4) << 16) | ((uint64_t)(sbo >> 4) << 32);
}
__device__ __forceinline__ void wg_h(uint32_t (&d)[16], const uint32_t* a, const uint32_t* b, uint64_t d0, uint64_t d1, uint64_t d2, uint64_t d3) {
    asm volatile(
        "wgmma.mma_async.sync.aligned.m64n64k16.f16.f16.f16 {%0,%1,%2,%3,%4,%5,%6,%7,%8,%9,%10,%11,%12,%13,%14,%15}, {%16,%17,%18,%19}, %32, 0, 1, 1, 1;\n"
        "wgmma.mma_async.sync.aligned.m64n64k16.f16.f16.f16 {%0,%1,%2,%3,%4,%5,%6,%7,%8,%9,%10,%11,%12,%13,%14,%15}, {%20,%21,%22,%23}, %33, 1, 1, 1, 1;\n"
        "wgmma.mma_async.sync.aligned.m64n64k16.f16.f16.f16 {%0,%1,%2,%3,%4,%5,%6,%7,%8,%9,%10,%11,%12,%13,%14,%15}, {%24,%25,%26,%27}, %34, 1, 1, 1, 1;\n"
        "wgmma.mma_async.sync.aligned.m64n64k16.f16.f16.f16 {%0,%1,%2,%3,%4,%5,%6,%7,%8,%9,%10,%11,%12,%13,%14,%15}, {%28,%29,%30,%31}, %35, 1, 1, 1, 1;\n"
        : "=r"(d[0]), "=r"(d[1]), "=r"(d[2]), "=r"(d[3]), "=r"(d[4]), "=r"(d[5]), "=r"(d[6]), "=r"(d[7]), "=r"(d[8]), "=r"(d[9]), "=r"(d[10]), "=r"(d[11]), "=r"(d[12]), "=r"(d[13]), "=r"(d[14]), "=r"(d[15])
        : "r"(a[0]), "r"(a[1]), "r"(a[2]), "r"(a[3]), "r"(a[4]), "r"(a[5]), "r"(a[6]), "r"(a[7]), "r"(b[0]), "r"(b[1]), "r"(b[2]), "r"(b[3]), "r"(b[4]), "r"(b[5]), "r"(b[6]), "r"(b[7]), "l"(d0), "l"(d1), "l"(d2), "l"(d3));
}
__device__ __forceinline__ void wg_f0(float (&d)[32], const uint32_t* a, const uint32_t* b, uint64_t d0, uint64_t d1, uint64_t d2, uint64_t d3) {
    asm volatile(
        "wgmma.mma_async.sync.aligned.m64n64k16.f32.f16.f16 {%0,%1,%2,%3,%4,%5,%6,%7,%8,%9,%10,%11,%12,%13,%14,%15,%16,%17,%18,%19,%20,%21,%22,%23,%24,%25,%26,%27,%28,%29,%30,%31}, {%32,%33,%34,%35}, %48, 0, 1, 1, 1;\n"
        "wgmma.mma_async.sync.aligned.m64n64k16.f32.f16.f16 {%0,%1,%2,%3,%4,%5,%6,%7,%8,%9,%10,%11,%12,%13,%14,%15,%16,%17,%18,%19,%20,%21,%22,%23,%24,%25,%26,%27,%28,%29,%30,%31}, {%36,%37,%38,%39}, %49, 1, 1, 1, 1;\n"
        "wgmma.mma_async.sync.aligned.m64n64k16.f32.f16.f16 {%0,%1,%2,%3,%4,%5,%6,%7,%8,%9,%10,%11,%12,%13,%14,%15,%16,%17,%18,%19,%20,%21,%22,%23,%24,%25,%26,%27,%28,%29,%30,%31}, {%40,%41,%42,%43}, %50, 1, 1, 1, 1;\n"
        "wgmma.mma_async.sync.aligned.m64n64k16.f32.f16.f16 {%0,%1,%2,%3,%4,%5,%6,%7,%8,%9,%10,%11,%12,%13,%14,%15,%16,%17,%18,%19,%20,%21,%22,%23,%24,%25,%26,%27,%28,%29,%30,%31}, {%44,%45,%46,%47}, %51, 1, 1, 1, 1;\n"
        : "=f"(d[0]), "=f"(d[1]), "=f"(d[2]), "=f"(d[3]), "=f"(d[4]), "=f"(d[5]), "=f"(d[6]), "=f"(d[7]), "=f"(d[8]), "=f"(d[9]), "=f"(d[10]), "=f"(d[11]), "=f"(d[12]), "=f"(d[13]), "=f"(d[14]), "=f"(d[15]), "=f"(d[16]), "=f"(d[17]), "=f"(d[18]), "=f"(d[19]), "=f"(d[20]), "=f"(d[21]), "=f"(d[22]), "=f"(d[23]), "=f"(d[24]), "=f"(d[25]), "=f"(d[26]), "=f"(d[27]), "=f"(d[28]), "=f"(d[29]), "=f"(d[30]), "=f"(d[31])
        : "r"(a[0]), "r"(a[1]), "r"(a[2]), "r"(a[3]), "r"(a[4]), "r"(a[5]), "r"(a[6]), "r"(a[7]), "r"(b[0]), "r"(b[1]), "r"(b[2]), "r"(b[3]), "r"(b[4]), "r"(b[5]), "r"(b[6]), "r"(b[7]), "l"(d0), "l"(d1), "l"(d2), "l"(d3));
}
__device__ __forceinline__ void wg_f1(float (&d)[32], const uint32_t* a, const uint32_t* b, uint64_t d0, uint64_t d1, uint64_t d2, uint64_t d3) {
    asm volatile(
        "wgmma.mma_async.sync.aligned.m64n64k16.f32.f16.f16 {%0,%1,%2,%3,%4,%5,%6,%7,%8,%9,%10,%11,%12,%13,%14,%15,%16,%17,%18,%19,%20,%21,%22,%23,%24,%25,%26,%27,%28,%29,%30,%31}, {%32,%33,%34,%35}, %48, 1, 1, 1, 1;\n"
        "wgmma.mma_async.sync.aligned.m64n64k16.f32.f16.f16 {%0,%1,%2,%3,%4,%5,%6,%7,%8,%9,%10,%11,%12,%13,%14,%15,%16,%17,%18,%19,%20,%21,%22,%23,%24,%25,%26,%27,%28,%29,%30,%31}, {%36,%37,%38,%39}, %49, 1, 1, 1, 1;\n"
        "wgmma.mma_async.sync.aligned.m64n64k16.f32.f16.f16 {%0,%1,%2,%3,%4,%5,%6,%7,%8,%9,%10,%11,%12,%13,%14,%15,%16,%17,%18,%19,%20,%21,%22,%23,%24,%25,%26,%27,%28,%29,%30,%31}, {%40,%41,%42,%43}, %50, 1, 1, 1, 1;\n"
        "wgmma.mma_async.sync.aligned.m64n64k16.f32.f16.f16 {%0,%1,%2,%3,%4,%5,%6,%7,%8,%9,%10,%11,%12,%13,%14,%15,%16,%17,%18,%19,%20,%21,%22,%23,%24,%25,%26,%27,%28,%29,%30,%31}, {%44,%45,%46,%47}, %51, 1, 1, 1, 1;\n"
        : "+f"(d[0]), "+f"(d[1]), "+f"(d[2]), "+f"(d[3]), "+f"(d[4]), "+f"(d[5]), "+f"(d[6]), "+f"(d[7]), "+f"(d[8]), "+f"(d[9]), "+f"(d[10]), "+f"(d[11]), "+f"(d[12]), "+f"(d[13]), "+f"(d[14]), "+f"(d[15]), "+f"(d[16]), "+f"(d[17]), "+f"(d[18]), "+f"(d[19]), "+f"(d[20]), "+f"(d[21]), "+f"(d[22]), "+f"(d[23]), "+f"(d[24]), "+f"(d[25]), "+f"(d[26]), "+f"(d[27]), "+f"(d[28]), "+f"(d[29]), "+f"(d[30]), "+f"(d[31])
        : "r"(a[0]), "r"(a[1]), "r"(a[2]), "r"(a[3]), "r"(a[4]), "r"(a[5]), "r"(a[6]), "r"(a[7]), "r"(b[0]), "r"(b[1]), "r"(b[2]), "r"(b[3]), "r"(b[4]), "r"(b[5]), "r"(b[6]), "r"(b[7]), "l"(d0), "l"(d1), "l"(d2), "l"(d3));
}
__device__ __forceinline__ void wg_s(uint32_t* d, const uint32_t* a, const uint32_t* b, uint64_t d0, uint64_t d1) {
    asm volatile(
        "wgmma.mma_async.sync.aligned.m64n32k16.f16.f16.f16 {%0,%1,%2,%3,%4,%5,%6,%7}, {%8,%9,%10,%11}, %16, 0, 1, 1, 1;\n"
        "wgmma.mma_async.sync.aligned.m64n32k16.f16.f16.f16 {%0,%1,%2,%3,%4,%5,%6,%7}, {%12,%13,%14,%15}, %17, 1, 1, 1, 1;\n"
        : "=r"(d[0]), "=r"(d[1]), "=r"(d[2]), "=r"(d[3]), "=r"(d[4]), "=r"(d[5]), "=r"(d[6]), "=r"(d[7])
        : "r"(a[0]), "r"(a[1]), "r"(a[2]), "r"(a[3]), "r"(b[0]), "r"(b[1]), "r"(b[2]), "r"(b[3]), "l"(d0), "l"(d1));
}
template <int ACC> __device__ __forceinline__ void wg_w(float (&d)[4], uint64_t da, uint64_t db) {
    asm volatile("wgmma.mma_async.sync.aligned.m64n8k16.f32.bf16.bf16 {%0,%1,%2,%3}, %4, %5, %6, 1, 1, 1, 0;"
                 : "+f"(d[0]), "+f"(d[1]), "+f"(d[2]), "+f"(d[3]) : "l"(da), "l"(db), "n"(ACC));
}
__device__ __forceinline__ void wg_w0(float (&d)[4], uint64_t da, uint64_t db) {
    asm volatile("wgmma.mma_async.sync.aligned.m64n8k16.f32.bf16.bf16 {%0,%1,%2,%3}, %4, %5, 0, 1, 1, 1, 0;"
                 : "=f"(d[0]), "=f"(d[1]), "=f"(d[2]), "=f"(d[3]) : "l"(da), "l"(db));
}
__device__ __forceinline__ void wg_fence() { asm volatile("wgmma.fence.sync.aligned;" ::: "memory"); }
__device__ __forceinline__ void wg_commit() { asm volatile("wgmma.commit_group.sync.aligned;" ::: "memory"); }
template <int N> __device__ __forceinline__ void wg_wait() { asm volatile("wgmma.wait_group.sync.aligned %0;" :: "n"(N) : "memory"); }
__device__ __forceinline__ void touch(uint32_t& r) { asm volatile("" : "+r"(r) :: "memory"); }
__device__ __forceinline__ void touch(float& r) { asm volatile("" : "+f"(r) :: "memory"); }
template <class T, int N> __device__ __forceinline__ void touch(T (&r)[N]) {
#pragma unroll
    for (int i = 0; i < N; i++) touch(r[i]);
}

__global__ void __cluster_dims__(2, 1, 1) __launch_bounds__(NTHREADS, 1)
fused_kernel(const Params p, const __grid_constant__ CUtensorMap tm_x, const __grid_constant__ CUtensorMap tm_g,
             const __grid_constant__ CUtensorMap tm_d)
{
    extern __shared__ __align__(1024) uint8_t smem_raw[];
    const uint32_t sm = (uint32_t)__cvta_generic_to_shared(smem_raw);
    const uint32_t bars = sm + SM_BAR;
    const int tid = threadIdx.x, lane = tid & 31;
    const int g = lane >> 2, q = lane & 3;
    const int c = blockIdx.x, rank = c & 1, G = c >> 1;

    if (tid < 256) {
        uint2 lar4, aim4, cr4, ci4;
        uint32_t ldt_raw, dsk_raw;
        {
            const uint32_t i = c * 256 + tid;
            asm volatile("ld.global.nc.v2.u32 {%0,%1}, [%10]; ld.global.nc.v2.u32 {%2,%3}, [%11]; ld.global.nc.u16 %8, [%14];\n"
                         "ld.global.nc.v2.u32 {%4,%5}, [%12]; ld.global.nc.v2.u32 {%6,%7}, [%13]; ld.global.nc.u16 %9, [%15];"
                         : "=r"(lar4.x), "=r"(lar4.y), "=r"(aim4.x), "=r"(aim4.y), "=r"(cr4.x), "=r"(cr4.y), "=r"(ci4.x), "=r"(ci4.y), "=r"(ldt_raw), "=r"(dsk_raw)
                         : "l"(p.lar + i * 4), "l"(p.aim + i * 4), "l"(p.cr + i * 4), "l"(p.ci + i * 4), "l"(p.logdt + (i >> 5)), "l"(p.dskip + (i >> 5)));
        }
        cluster_arrive();
        sched_fence();
        const int warp = __shfl_sync(0xFFFFFFFFu, tid >> 5, 0);
        const float logdt = blo(ldt_raw), dsk = blo(dsk_raw);
        asm volatile("setmaxnreg.inc.sync.aligned.u32 160;");
        const int wgi = warp >> 2, w = warp & 3;
        const uint32_t wb = sm + SM_K + (w < 2 ? 16 * w + 8 * wgi : 16 + 16 * wgi + 8 * w) * SUB;
        sth(wb + lane * 4, hc{0x3C003C00u, 0u});
        const uint32_t tb0 = pin(sm + SM_S + (16 * wgi + w) * SUB + lane * 16), tb1 = pin(sm + SM_S + (16 * wgi + w) * SUB + ((lane + 1) & 31) * 16);
        const uint32_t seg = pin(sm + SM_K + (2 * warp + (lane & 1)) * SUB + (lane >> 1) * 16);
        const uint32_t zst = pin(sm + SM_S + (16 * wgi + (lane >> 4)) * SUB + (16 * w + (lane & 15)) * 16);
        sched_fence();

        {
            const uint32_t z = (uint32_t)(uintptr_t)p.lar & 1;
            lar4.x = cpy(lar4.x, z); lar4.y = cpy(lar4.y, z); aim4.x = cpy(aim4.x, z); aim4.y = cpy(aim4.y, z);
            cr4.x = cpy(cr4.x, z); cr4.y = cpy(cr4.y, z); ci4.x = cpy(ci4.x, z); ci4.y = cpy(ci4.y, z);
        }
        const float dt = rb(expf(logdt));
        float outscale, cs, dn;
        {
            uint32_t m0 = __vmaxu2(__vmaxu2(cr4.x & 0x7FFF7FFFu, cr4.y & 0x7FFF7FFFu), __vmaxu2(ci4.x & 0x7FFF7FFFu, ci4.y & 0x7FFF7FFFu));
            uint32_t m1 = max(m0 & 0xFFFFu, m0 >> 16);
            float cmax = blo(__reduce_max_sync(0xFFFFFFFFu, m1));
            const float sc = fminf(fmaxf(fmaxf(2.0f * dt * cmax, fabsf(dsk) * (1.0f / 1024.0f)), 1e-30f), 1e30f);
            outscale = __uint_as_float(__float_as_uint(sc) & 0x7F800000u);
            const float inv = __uint_as_float(0x7F000000u - __float_as_uint(outscale));
            cs = 2.0f * dt * inv * (1.0f / 512.0f);
            dn = dsk * inv * (1.0f / 512.0f);
            if (lane == 0) sts16(sm + SM_SCL + warp * 2, __float_as_uint(32768.0f * outscale) >> 16);
        }
        if (warp == TSW) TSL(39);
        uint32_t fc[16], fs[16], ta[4], tb[4];
        float kacc[2][3][4];
#pragma unroll
        for (int i = 0; i < 2; i++)
#pragma unroll
            for (int j = 0; j < 3; j++) kacc[i][j][0] = kacc[i][j][1] = kacc[i][j][2] = kacc[i][j][3] = 0.f;
        if (lane == 0) kacc[0][0][0] = dn;
        {
            const uint32_t st = wb + lane * 4;
            const uint32_t zk = lds32(wb + 128);
            const uint32_t la = wb + ((lane & 8) ? 29 : (lane & 7)) * KP + (lane >> 4) * 128;
            const uint32_t lo = wb + ((lane >> 3) & 1) * 128 + (lane >> 4) * 16;
            const uint32_t lb = lo + (8 + (lane & 7)) * KP, lb2 = lo + (24 + min(lane & 7, 4)) * KP, lm = lo + 30 * KP;
#pragma unroll 1
            for (int s = 0; s < 2; s++) {
                const uint32_t wl = s ? lar4.y : lar4.x, wa = s ? aim4.y : aim4.x, wr_ = s ? cr4.y : cr4.x, wi = s ? ci4.y : ci4.x;
                const uint32_t ea = pack_b(ex2(blo(wl) * 1.4426950408889634f), ex2(bhi(wl) * 1.4426950408889634f));
                const float a2[2] = {-(blo(ea) * dt) * 1.4426950408889634f, -(bhi(ea) * dt) * 1.4426950408889634f};
                const float b[2] = {blo(wa) * dt, bhi(wa) * dt};
                {
                    cf z8[2], z16[2], z32[2], z64[2], z128[2];
#pragma unroll
                    for (int e = 0; e < 2; e++) {
                        z8[e] = cexp_(a2[e] * 8.f, b[e] * 8.f);
                        z16[e] = csq(z8[e]); z32[e] = csq(z16[e]); z64[e] = csq(z32[e]); z128[e] = csq(z64[e]);
                    }
                    const hc r1 = pk(z8[0], z8[1]), r2 = pk(z16[0], z16[1]), r3 = hmulc(r1, r2), r4 = pk(z32[0], z32[1]);
                    sth(st + 1 * KP, r1); sth(st + 2 * KP, r2); sth(st + 3 * KP, r3); sth(st + 4 * KP, r4);
                    sth(st + 5 * KP, hmulc(r1, r4)); sth(st + 6 * KP, hmulc(r2, r4)); sth(st + 7 * KP, hmulc(r3, r4));
                    sth(st + 29 * KP, pk(z64[0], z64[1])); sth(st + 30 * KP, pk(z128[0], z128[1]));
                }
                {
                    cf C[2], z2[2], z4[2], v2[2], v4[2], c1[2], d1[2];
#pragma unroll
                    for (int e = 0; e < 2; e++) {
                        C[e] = {(e ? bhi(wr_) : blo(wr_)) * cs, (e ? bhi(wi) : blo(wi)) * -cs};
                        const cf z = cexp_(a2[e], -b[e]);
                        const cf v = cexp_(a2[e] * 256.f, b[e] * -256.f);
                        z2[e] = csq(z); z4[e] = csq(z2[e]); v2[e] = csq(v); v4[e] = csq(v2[e]);
                        c1[e] = cmul(C[e], z); d1[e] = cmul(C[e], v);
                    }
                    const hc l0 = pk(C[0], C[1]), l1 = pk(c1[0], c1[1]), e1 = pk(d1[0], d1[1]);
                    const hc h = pk(z2[0], z2[1]), f = pk(z4[0], z4[1]), w = pk(v2[0], v2[1]), y = pk(v4[0], v4[1]);
                    const hc l2 = hmulc(l0, h), l3 = hmulc(l1, h), e2 = hmulc(l0, w), e3 = hmulc(e1, w), e4 = hmulc(l0, y), g2 = hmulc(e1, h);
                    sth(st + 8 * KP, l0); sth(st + 9 * KP, l1); sth(st + 10 * KP, l2); sth(st + 11 * KP, l3);
                    sth(st + 12 * KP, hmulc(l0, f)); sth(st + 13 * KP, hmulc(l1, f)); sth(st + 14 * KP, hmulc(l2, f)); sth(st + 15 * KP, hmulc(l3, f));
                    sth(st + 16 * KP, e1);
                    sth(st + 17 * KP, g2);
                    sth(st + 18 * KP, hmulc(e1, f));
                    sth(st + 19 * KP, hmulc(g2, f));
                    sth(st + 20 * KP, e2);
                    sth(st + 21 * KP, hmulc(e2, f));
                    sth(st + 22 * KP, e3);
                    sth(st + 23 * KP, hmulc(e3, f));
                    sth(st + 24 * KP, e4);
                    sth(st + 25 * KP, hmulc(e1, y));
                    sth(st + 26 * KP, hmulc(e2, y));
                    sth(st + 27 * KP, hmulc(e3, y));
                    sth(st + 28 * KP, hmulc(e4, y));
                }
                __syncwarp();
                if (warp == TSW && s == 0) TSL(27);
                if (s == 1 && lane == 0) mbar_arrive(bars + B_TFREE * 8 + (tb[3] & zk));
#pragma unroll
                for (int kp = 0; kp < 4; kp++) {
                    uint32_t bb[3][4], m2[4];
                    ldsm4(lm + kp * 32, m2[0], m2[1], m2[2], m2[3]);
                    ldsm4(lb + kp * 32, bb[0][0], bb[0][1], bb[0][2], bb[0][3]);
                    ldsm4(lb + 8 * KP + kp * 32, bb[1][0], bb[1][1], bb[1][2], bb[1][3]);
                    ldsm4(lb2 + kp * 32, bb[2][0], bb[2][1], bb[2][2], bb[2][3]);
#pragma unroll
                    for (int k2 = 0; k2 < 2; k2++) {
                        hc v0, m1;
                        ldsm4(la + kp * 32 + k2 * 16, v0.r, m1.r, v0.i, m1.i);
                        const hc mm = {m2[2 * k2], m2[2 * k2 + 1]};
                        const hc v1 = hmulc(v0, m1), v2 = hmulc(v0, mm), v3 = hmulc(v1, mm);
                        v0.r = cpy(v0.r, zk); v0.i = cpy(v0.i, zk);
#pragma unroll
                        for (int nt = 0; nt < 3; nt++) {
                            mma_f16(kacc[0][nt], v0.r, v1.r, v0.i, v1.i, bb[nt][2 * k2], bb[nt][2 * k2 + 1]);
                            mma_f16(kacc[1][nt], v2.r, v3.r, v2.i, v3.i, bb[nt][2 * k2], bb[nt][2 * k2 + 1]);
                        }
                    }
                }
                __syncwarp();
                if (warp == TSW) TSL(s ? 40 : 33);
                if (s == 0) {
                    cluster_wait();
                    mbar_wait(bars + B_TAB * 8);
#pragma unroll
                    for (int i = 0; i < 10; i++) {
                        const uint4 u = lds128(sm + SM_TAB + i * 2048 + (tid & 127) * 16);
                        uint32_t* t = i < 4 ? fc + 4 * i : i < 8 ? fs + 4 * (i - 4) : i == 8 ? ta : tb;
                        t[0] = u.x; t[1] = u.y; t[2] = u.z; t[3] = u.w;
                    }
                }
            }
        }
        TSL(1);
        group_sync(wgi);
        {
            uint32_t v[3][4];
#pragma unroll
            for (int i = 0; i < 12; i++) v[i >> 2][i & 3] = pack_h(kacc[(i >> 1) & 1][i >> 2][2 * (i & 1)], kacc[(i >> 1) & 1][i >> 2][2 * (i & 1) + 1]);
            stsm4(tb0, v[1][0], v[1][1], v[1][2], v[1][3]);
            stsm4(tb0 + 512, v[2][0], v[2][1], v[2][2], v[2][3]);
            stsm4(seg, v[0][0], v[0][1], v[0][2], v[0][3]);
            __syncwarp();
            const uint4 a = lds128(tb0), na = lds128(tb1), nb = lds128(tb1 + 512);
            const uint2 b = lds64(tb0 + 512);
            const bool last = lane == 31;
            const uint32_t n1 = last ? na.z : na.x, n2 = last ? na.w : na.z, n3 = last ? nb.x : na.w;
            const uint32_t sn = last ? 0x5432 : 0x3210, n4 = prmt(nb.x, nb.y, sn), n5 = prmt(nb.y, nb.z, sn);
            sts128(seg + 256, prmt(a.x, 0, 0x1010), prmt(a.x, a.y, 0x5432), prmt(a.y, 0, 0x1010), prmt(a.y, n1, 0x5432));
            sts128(seg + 512, prmt(a.z, 0, 0x1010), a.z, prmt(a.z, 0, 0x3232), prmt(n2, 0, 0x1010));
            sts128(seg + 768, prmt(a.w, 0, 0x1010), a.w, prmt(a.w, 0, 0x3232), prmt(n3, 0, 0x1010));
            const uint32_t s3 = (lane & 1) ? 0x5454 : 0x5410;
#pragma unroll
            for (int i = 0; i < 4; i++) {
                const uint32_t cur = (i & 2) ? b.y : b.x, nx = (i & 2) ? n5 : n4, h = (i & 1) * 0x2222;
                const uint32_t vv = prmt(cur, 0, 0x1010 + h);
                sts128(seg + 16 * SUB + i * 256, vv, vv, prmt(cur, nx, s3 + h), prmt(nx, 0, 0x1010 + h));
            }
        }
        proxy_fence();
        __syncwarp();
        if (lane == 0) mbar_arrive(bars + B_SFREE * 8);
        TSL(2);
        group_sync(wgi);
        const uint64_t dre = bdesc(sm + SM_F2 + 512, 256), dim = bdesc(sm + SM_F2, 256);
        uint32_t k0[32], k1[32];
#pragma unroll
        for (int b = 0; b < 2; b++) {
            const uint64_t d1 = bdesc(sm + SM_K + (16 * b + 8 * wgi) * SUB, SUB);
            uint32_t re[16], im[16];
            if (b == 0 && wgi == 1) bar_sync(5, 256);
            wg_fence();
            wg_h(re, fc, fc + 8, d1, d1 + 16, d1 + 32, d1 + 48);
            wg_h(im, fs, fs + 8, d1, d1 + 16, d1 + 32, d1 + 48);
            wg_commit();
            if (b == 0 && wgi == 0) bar_arrive(5, 256);
            wg_wait<0>();
            touch(re); touch(im);
            if (lane == 0) mbar_arrive(bars + (B_KFREE + b) * 8);
            uint32_t (&kk)[32] = b ? k1 : k0;
#pragma unroll
            for (int hh = 0; hh < 2; hh++) {
#pragma unroll
                for (int i = 8 * hh; i < 8 * hh + 8; i++) {
                    re[i] = hfma2_(ta[i & 3], im[i], re[i]); im[i] = hfms2_(tb[i & 3], re[i], im[i]); re[i] = hfma2_(ta[i & 3], im[i], re[i]);
                }
                wg_fence();
                wg_s(kk + 16 * hh, re + 8 * hh, im + 8 * hh, dre, dim);
                wg_s(kk + 16 * hh + 8, re + 8 * hh + 4, im + 8 * hh + 4, dre, dim);
                wg_commit();
            }
            wg_wait<0>();
            touch(kk);
        }
        if (warp == TSW) TSL(35);
        asm volatile("setmaxnreg.inc.sync.aligned.u32 176;");
        touch(k1);
        {
            const uint32_t sg = (g & 1) ? 0xBC00BC00u : 0x3C003C00u;
#pragma unroll
            for (int i = 0; i < 16; i++) {
                const int r = 8 * (i >> 2) + (i & 3);
                k1[r] = hfms2_(sg, k0[r + 4], k1[r]); k1[r + 4] = hfma2_(sg, k0[r], k1[r + 4]);
            }
            touch(k1);
        }
        const uint32_t peer = mapa(sm, rank ^ 1), so = SM_U + 8 * wgi * SUB + w * 1024 + (8 * q + (g ^ (2 * q))) * 16;
#pragma unroll 1
        for (int b = 0; b < 2; b++) {
            const uint32_t zb = sm + SM_S + 16 * wgi * SUB;
            constexpr int zi = 8 * SUB;
            uint32_t re[16], im[16], su[2][16], z[2][16], y[2][16];
            auto twiddle = [&](int hh) {
#pragma unroll
                for (int i = 8 * hh; i < 8 * hh + 8; i++) {
                    re[i] = hfma2_(ta[i & 3], im[i], re[i]); im[i] = hfms2_(tb[i & 3], re[i], im[i]); re[i] = hfma2_(ta[i & 3], im[i], re[i]);
                    touch(re[i]); touch(im[i]);
                }
            };
            auto dft16 = [&](int hh) {
                wg_fence();
                wg_s(su[hh], re + 8 * hh, im + 8 * hh, dre, dim); wg_s(su[hh] + 8, re + 8 * hh + 4, im + 8 * hh + 4, dre, dim);
                wg_commit();
                sched_fence();
            };
            auto product = [&](int hh) {
                if (b == 0) {
#pragma unroll
                    for (int i = 0; i < 8; i++) {
                        const int r = 8 * (i >> 2) + (i & 3), kr = 16 * hh + r;
                        const hc u = {su[hh][r], su[hh][r + 4]};
                        const hc t = hmulc(u, hc{k0[kr], k0[kr + 4]}), pp = hmulc(u, hc{k1[kr], k1[kr + 4]});
                        z[hh][r] = t.r; z[hh][r + 4] = t.i; k1[kr] = pp.r; k1[kr + 4] = pp.i;
                        touch(k1[kr]); touch(k1[kr + 4]);
                    }
                } else {
#pragma unroll
                    for (int i = 0; i < 8; i++) {
                        const int r = 8 * (i >> 2) + (i & 3), kr = 16 * hh + r;
                        const hc u = {su[hh][r], su[hh][r + 4]};
                        z[hh][r] = hfms2_(u.i, k0[kr + 4], hfma2_(u.r, k0[kr], k1[kr]));
                        z[hh][r + 4] = hfma2_(u.i, k0[kr], hfma2_(u.r, k0[kr + 4], k1[kr + 4]));
                    }
                }
                touch(z[hh]);
            };
            auto idft16 = [&](int hh) {
                wg_fence();
                wg_s(y[hh], z[hh] + 4, z[hh], dre, dim); wg_s(y[hh] + 8, z[hh] + 12, z[hh] + 8, dre, dim);
                wg_commit();
                sched_fence();
            };
            auto untwiddle = [&](int hh) {
#pragma unroll
                for (int i = 0; i < 2; i++) {
                    uint32_t* const yi = y[hh] + 8 * i, * const yr = yi + 4;
#pragma unroll
                    for (int n = 0; n < 4; n++) {
                        yr[n] = hfms2_(ta[n], yi[n], yr[n]); yi[n] = hfma2_(tb[n], yr[n], yi[n]); yr[n] = hfms2_(ta[n], yi[n], yr[n]);
                    }
                    const uint32_t a = zst + (4 * hh + 2 * i) * SUB;
                    stsm4(a, yr[0], yr[1], yr[2], yr[3]);
                    stsm4(a + zi, yi[0], yi[1], yi[2], yi[3]);
                }
            };
            auto done = [&]() { sched_fence(); wg_wait<0>(); };
            {
                const uint64_t d1 = bdesc(sm + SM_U + (16 * b + 8 * wgi) * SUB, SUB);
                mbar_wait(bars + (B_U + b) * 8);
                proxy_fence();
                if (b == 0) { TSL(3); if (wgi == 1) bar_sync(9, 256); }
                wg_fence();
                wg_h(re, fc, fc + 8, d1, d1 + 16, d1 + 32, d1 + 48);
                wg_h(im, fs, fs + 8, d1, d1 + 16, d1 + 32, d1 + 48);
                wg_commit();
                if (b == 0 && wgi == 0) bar_arrive(9, 256);
                wg_wait<0>();
                touch(re); touch(im);
            }
            if (lane == 0) mbar_arrive_peer(peer + SM_BAR + (B_PEER + 2 * wgi + b) * 8);
            twiddle(0); twiddle(1); dft16(0); dft16(1);
            wg_wait<1>(); touch(su[0]);
            product(0); done(); touch(su[1]); idft16(0);
            product(1); done(); touch(y[0]); idft16(1);
            mbar_wait(bars + B_SDONE * 8);
            group_sync(wgi);
            untwiddle(0); done(); touch(y[1]);
            untwiddle(1);
            proxy_fence();
            if (warp == TSW) TSL(36 + b);
            group_sync(wgi);
            float acc[32];
            const uint64_t d4 = bdesc(zb, SUB);
            wg_fence();
            wg_f0(acc, fc, fc + 8, d4, d4 + 16, d4 + 32, d4 + 48);
            wg_f1(acc, fs, fs + 8, d4 + zi / 16, d4 + zi / 16 + 16, d4 + zi / 16 + 32, d4 + zi / 16 + 48);
            wg_commit();
            mbar_wait(bars + (B_PEER + 2 * wgi + b) * 8);
            const uint2 sc = lds64(sm + SM_SCL + wgi * 8);
            wg_wait<0>();
            touch(acc);
            uint32_t s[2][2][4];
#pragma unroll
            for (int i = 0; i < 8; i++) {
                s[i >> 2][(i >> 1) & 1][2 * (i & 1)] = bmul2(pack_b(acc[i], acc[8 + i]), sc.x);
                s[i >> 2][(i >> 1) & 1][2 * (i & 1) + 1] = bmul2(pack_b(acc[16 + i], acc[24 + i]), sc.y);
            }
            const uint32_t sb = SM_BAR + (B_STG + b) * 8;
#pragma unroll
            for (int j = 0; j < 2; j++)
                if (j == rank) {
#pragma unroll
                    for (int hi = 0; hi < 2; hi++) {
                        const uint32_t (&r)[4] = s[1 - j][hi], (&l)[4] = s[j][hi];
                        st_async4(peer + so + 16 * b * SUB + hi * 512, r[0], r[1], r[2], r[3], peer + sb);
                        sts128(sm + (so ^ 64) + (16 * b + 4) * SUB + hi * 512, l[0], l[1], l[2], l[3]);
                    }
                }
            __syncwarp();
            if (lane == 0) mbar_arrive(sm + sb);
            if (warp == TSW) TSL(5 + b);
        }
        TSL(7);
    } else {
    const int warp = __shfl_sync(0xFFFFFFFFu, tid >> 5, 0);
    if (warp < 12) {
        const int v = warp - 8;
        cluster_arrive();
        const uint32_t xs = sm + SM_U + v * 8192;
        if (elect()) {
#pragma unroll
            for (int r = 0; r < 2; r++) mbar_init(bars + (B_ROW + 2 * v + r) * 8, 1);
            asm volatile("fence.mbarrier_init.release.cluster;" ::: "memory");
#pragma unroll
            for (int e = 0; e < 2; e++) {
                if (e) { const int t0_ = clock(); while ((int)clock() - t0_ < EDELAY) __nanosleep(40); }
                mbar_expect(bars + (B_ROW + 2 * v + e) * 8, 4096);
#pragma unroll
                for (int r = 0; r < 2; r++)
                    asm volatile("cp.async.bulk.shared::cluster.global.mbarrier::complete_tx::bytes [%0], [%1], 2048, [%2];"
                                 :: "r"(xs + e * 4096 + r * 2048), "l"(p.x + (size_t)(128 * (c & 15) + 32 * v + 16 * r + 2 * (c >> 4) + e) * 1024),
                                    "r"(bars + (B_ROW + 2 * v + e) * 8) : "memory");
            }
        }
        __syncwarp();
        uint4 w4[4];
#pragma unroll
        for (int k = 0; k < 4; k++) w4[k] = ldg128(reinterpret_cast<const uint4*>(p.wr) + 32 * k + lane);
        {
            constexpr uint32_t ONE = 0x3F803F80u;
            const uint32_t zr = p.up_first >> 1;
            uint4 w5[4];
#pragma unroll
            for (int k = 0; k < 4; k++) {
                w5[k].x = w4[k].x + zr; w5[k].y = w4[k].y + zr; w5[k].z = w4[k].z + zr; w5[k].w = w4[k].w + zr;
                w4[k].x = cpy(w4[k].x, zr); w4[k].y = cpy(w4[k].y, zr); w4[k].z = cpy(w4[k].z, zr); w4[k].w = cpy(w4[k].w, zr);
            }
            const bool od = g & 1;
#pragma unroll 1
            for (int r2 = 0; r2 < 2; r2++) {
                mbar_wait(bars + (B_ROW + 2 * v + r2) * 8);
                TSL(43);
                float s1[2][4] = {}, q0[2][4] = {};
#pragma unroll
                for (int k = 0; k < 4; k++)
#pragma unroll
                    for (int r = 0; r < 2; r++) {
                        const uint4 x = lds128(xs + r2 * 4096 + r * 2048 + k * 512 + lane * 16);
                        const uint4& ww = r ? w5[k] : w4[k];
                        mma_bf16(q0[r], cpy(x.x, zr), ww.x, cpy(x.y, zr), ww.y, x.x, x.y);
                        mma_bf16(s1[r], x.x, x.y, x.z, x.w, ONE, ONE);
                        mma_bf16(q0[r], cpy(x.z, zr), ww.z, cpy(x.w, zr), ww.w, x.z, x.w);
                    }
#pragma unroll
                for (int r = 0; r < 2; r++)
                    if (q == (g >> 1))
                        sts128(sm + SM_RED + (4 * v + r2 + 2 * r) * 144 + g * 16, __float_as_uint(od ? q0[r][1] : q0[r][0]),
                               __float_as_uint(od ? q0[r][3] : q0[r][2]), __float_as_uint(s1[r][0]), __float_as_uint(s1[r][2]));
            }
            bar_arrive(7, 160);
        }
        TSL(8);
        bar_sync(6, 160);
        const uint32_t tag = lds32(sm + SM_TOK + 8);
        cluster_wait();
        asm volatile("setmaxnreg.dec.sync.aligned.u32 104;");
        const uint32_t peer = mapa(sm, rank ^ 1);
        if (v == 0 && lane == 0) mbar_arrive_peer(peer + SM_BAR + B_UFREE * 8);
        {
            uint4 st[8];
            const uint4* src = p.sc->stats[G & (NREP - 1)] + rank * 512 + 16 * v + (lane >> 1);
            const uint32_t tb = ((tag & 1) << 15) | ((tag >> 1) << 31);
            const uint32_t xo = pin(sm + SM_SLAB + v * 512 + lane * 16);
            const uint32_t ub = pin(mapa(bars + B_U * 8, lane & 1)), ud = pin(mapa(sm + SM_U + rank * SUB + (16 * v + (lane >> 1)) * 16, lane & 1));
            sched_fence();
            bar_sync(3, 192);
            if (warp == 8) TSL(44);
#pragma unroll
            for (int i = 0; i < 8; i++) st[i] = ld_relaxed128(src + (i >> 2) * 64 + (i & 3) * 128);
            uint4 x0[8];
            mbar_wait(bars + B_UFREE * 8);
            mbar_wait(bars + B_SLAB * 8);
#pragma unroll
            for (int i = 0; i < 8; i++) x0[i] = lds128(xo + (i & 1) * 8192 + (i >> 1) * 2048);
            for (int it = 0; it < SPIN_LIMIT; it++) {
                uint32_t bad = 0;
#pragma unroll
                for (int i = 0; i < 8; i++) bad |= st[i].z ^ tb;
                if (__all_sync(0xFFFFFFFFu, (bad & 0x80008000u) == 0)) break;
#pragma unroll
                for (int i = 0; i < 8; i++)
                    if ((st[i].z ^ tb) & 0x80008000u) st[i] = ld_relaxed128(src + (i >> 2) * 64 + (i & 3) * 128);
            }
            TSL(11); TG(31);
#pragma unroll
            for (int i = 0; i < 8; i++) st[i].z &= 0x7FFF7FFFu;
            uint32_t n[2][8][4];
#pragma unroll
            for (int i = 0; i < 4; i++) { n[0][i][0] = st[4 + i].x; n[0][i][1] = st[4 + i].y; n[0][i][2] = st[4 + i].z; }
#pragma unroll 1
            for (int b = 0; ; b++) {
#pragma unroll
                for (int i = 0; i < 8; i++) {
                    const uint4& t = st[i >> 1];
                    const uint32_t m = (i & 1) ? dup_hi(t.x) : dup_lo(t.x), hi = (i & 1) ? dup_hi(t.z) : dup_lo(t.z), lo = (i & 1) ? dup_hi(t.y) : dup_lo(t.y);
                    uint32_t (&r)[4] = n[1][i];
                    r[0] = norm2(x0[i].x, m, hi, lo); r[1] = norm2(x0[i].y, m, hi, lo); r[2] = norm2(x0[i].z, m, hi, lo); r[3] = norm2(x0[i].w, m, hi, lo);
                }
                sched_fence();
#pragma unroll
                for (int cp = 0; cp < 4; cp++) {
                    float f[8][2];
#pragma unroll
                    for (int i = 0; i < 8; i++) { f[i][0] = blo(n[1][i][cp]); f[i][1] = bhi(n[1][i][cp]); }
#pragma unroll
                    for (int h = 0; h < 2; h++)
                        st_async4(ud + (16 * b + 4 * cp + 2 * h) * SUB, pack_h(f[0][h], f[1][h]), pack_h(f[2][h], f[3][h]),
                                  pack_h(f[4][h], f[5][h]), pack_h(f[6][h], f[7][h]), ub + b * 8);
                    if (cp == 3) TSL(b ? 41 : 12);
                    if (cp >= FUSE) {
#pragma unroll
                        for (int i = 0; i < 8; i++) { n[1][i][cp] = pack_b(silu2(f[i][0]), silu2(f[i][1])); touch(n[1][i][cp]); }
                    }
                    sched_fence();
                }
#pragma unroll
                for (int cp = 0; cp < FUSE; cp++) {
#pragma unroll
                    for (int i = 0; i < 8; i++) {
                        uint32_t& r = n[1][i][cp];
                        r = pack_b(silu2(__uint_as_float(prmt(r, tag >> 2, 0x1044))), silu2(__uint_as_float(prmt(r, tag >> 2, 0x3244))));
                        touch(r);
                    }
                    sched_fence();
                }
                if (b) break;
                mbar_wait(bars + (B_SLAB + 1) * 8);
#pragma unroll
                for (int i = 0; i < 8; i++) {
                    if (i < 4) { st[i].x = n[0][i][0]; st[i].y = n[0][i][1]; st[i].z = n[0][i][2]; }
#pragma unroll
                    for (int k = 0; k < 4; k++) n[0][i][k] = n[1][i][k];
                    x0[i] = lds128(xo + 16384 + (i & 1) * 8192 + (i >> 1) * 2048);
                }
            }
            TSL(0);
            const int ln = (xo - sm) >> 4;
            const bool own = (ln & 1) == rank;
            const uint32_t stg = pin(sm + SM_U + (own ? 4 * SUB : 0) + (ln >> 4) * 512 + (((ln & 14) * 8) ^ (own ? 64 : 0)));
            const int tl = pin(16 * (ln >> 1) + 8 * rank);
            __nv_bfloat16* const op = p.out + (size_t)tl * 1024 + G * 16 + (ln & 1) * 8;
            mbar_wait(bars + B_TOK * 8);
            const uint2 tr = lds64(sm + SM_TOK);
            const int d0 = tr.x - tl, d1 = tr.y - tl;
            uint32_t skip = ((d0 & ~0x407) ? 0u : 1u << ((d0 & 7) + (d0 >> 7))) | ((d1 & ~0x407) ? 0u : 1u << ((d1 & 7) + (d1 >> 7)));
            auto put = [&](int b, int i, const uint4& x, uint32_t s0, uint32_t s1, uint32_t s2, uint32_t s3) {
                const uint32_t (&gt)[4] = n[b][i];
                asm volatile("{ .reg .pred p; setp.eq.u32 p, %5, 0; @p st.global.v4.u32 [%0], {%1,%2,%3,%4}; }"
                             :: "l"(op + (size_t)(1024 * b + i) * 1024), "r"(badd2(x.x, bmul2(s0, gt[0]))), "r"(badd2(x.y, bmul2(s1, gt[1]))),
                                "r"(badd2(x.z, bmul2(s2, gt[2]))), "r"(badd2(x.w, bmul2(s3, gt[3]))), "r"(skip & (1u << (8 * b + i))) : "memory");
            };
            mbar_wait(bars + B_STG * 8);
#pragma unroll
            for (int i = 0; i < 4; i++) {
                const uint32_t a = (stg ^ (32 * i)) + 128 * i;
                const uint4 r0 = lds128(a), r1 = lds128(a + 8 * SUB), xa = lds128(xo + i * 2048), xb = lds128(xo + 8192 + i * 2048);
                put(0, 2 * i, xa, r0.x, r0.y, r1.x, r1.y); put(0, 2 * i + 1, xb, r0.z, r0.w, r1.z, r1.w);
                sched_fence();
                if (i < 3) __nanosleep(STSLEEP);
            }
            TSL(22);
            uint4 x[8], r[2][4];
#pragma unroll
            for (int i = 0; i < 8; i++) x[i] = lds128(xo + 16384 + (i & 1) * 8192 + (i >> 1) * 2048);
            mbar_wait(bars + (B_STG + 1) * 8);
#pragma unroll
            for (int i = 0; i < 4; i++) r[0][i] = lds128((stg ^ (32 * (i >> 1))) + (16 + 8 * (i & 1)) * SUB + 128 * (i >> 1));
#pragma unroll
            for (int h = 0; h < 2; h++) {
#pragma unroll
                for (int i = 0; i < 2; i++) {
                    const uint4 &r0 = r[h][2 * i], &r1 = r[h][2 * i + 1];
                    if (!h) { r[1][2 * i] = lds128((stg ^ (64 + 32 * i)) + 16 * SUB + 256 + 128 * i); r[1][2 * i + 1] = lds128((stg ^ (64 + 32 * i)) + 24 * SUB + 256 + 128 * i); }
                    put(1, 4 * h + 2 * i, x[4 * h + 2 * i], r0.x, r0.y, r1.x, r1.y); put(1, 4 * h + 2 * i + 1, x[4 * h + 2 * i + 1], r0.z, r0.w, r1.z, r1.w);
                }
            }
            TSL(23);
            TSL(17); TG(30);
        }
    } else {
        const int v = warp - 12;
        if (lane == 0) {
            if (v == 1) {
                mbar_init(bars + B_TAB * 8, 1); mbar_init(bars + B_TFREE * 8, 8); mbar_init(bars + B_KFREE * 8, 8); mbar_init(bars + (B_KFREE + 1) * 8, 8);
                mbar_expect(bars + B_TAB * 8, 20480 + 1536);
            } else if (v == 0) {
                mbar_init(bars + B_SLAB * 8, 1); mbar_init(bars + (B_SLAB + 1) * 8, 1); mbar_init(bars + B_TOK * 8, 2); mbar_init(bars + B_UFREE * 8, 1);
                mbar_init(bars + B_SFREE * 8, 8); mbar_init(bars + B_SDONE * 8, 4);
                mbar_expect(bars + B_SLAB * 8, 16384); mbar_expect(bars + (B_SLAB + 1) * 8, 16384);
            } else {
                mbar_init(bars + (B_STG + v - 2) * 8, 9);
                mbar_init(bars + (B_U + v - 2) * 8, 1); mbar_expect(bars + (B_U + v - 2) * 8, 16384);
                mbar_expect(bars + (B_STG + v - 2) * 8, 8192);
                if (v == 2) { mbar_init(bars + B_PAIR * 8, 1); mbar_expect(bars + B_PAIR * 8, 1024); }
            }
            mbar_init(bars + (B_PEER + v) * 8, 4);
#pragma unroll
            for (int i = 0; i < 3; i++) { mbar_init(bars + (B_FULL + 3 * v + i) * 8, 1); mbar_expect(bars + (B_FULL + 3 * v + i) * 8, 16384); }
            asm volatile("fence.mbarrier_init.release.cluster;" ::: "memory");
        }
        __syncwarp();
        cluster_arrive();
        asm volatile("setmaxnreg.dec.sync.aligned.u32 56;");
        uint64_t pol; asm volatile("createpolicy.fractional.L2::" WPOL ".b64 %0, 1.0;" : "=l"(pol));
        auto load_chunk = [&](int n) {
            if (n < 8) tma3d(sm + chunk_off(n), &tm_g, G * 64, rank * 512 + n * 64, 0, bars + (B_FULL + n) * 8, pol);
            else tma3d(sm + chunk_off(n), &tm_d, 0, G * 64, rank * 8 + (n - 8) * 2, bars + (B_FULL + n) * 8, pol);
        };
        uint32_t* const my_part = p.sc->part + ((2 * (32 * rank + v) + (q & 1)) * 56 + G) * 16 + g + 8 * (q >> 1);
        if (G < 56) {
#pragma unroll
            for (int n = 0; n < 8; n++) st_relaxed32(my_part + n * 8 * 56 * 16, 0);
        }
        cluster_wait();
        const bool lead = elect();
        uint32_t key = 0;
        if (v == 0) {
            asm volatile("prefetch.tensormap [%0];" :: "l"(&tm_x) : "memory");
            asm volatile("prefetch.tensormap [%0];" :: "l"(&tm_g) : "memory");
            { const int t0_ = clock(); while ((int)clock() - t0_ < SDELAY) __nanosleep(40); }
            if (lead) {
                int n = 0;
#pragma unroll 1
                for (int i = 0; i < 5; i++) {
                    if (G < 56) {
#pragma unroll 1
                        for (; n < ((FILL >> (4 * i)) & 15); n++) {
                            if (n >= IDEPTH) mbar_wait(bars + (B_FULL + n - IDEPTH) * 8);
                            if (n == 3) mbar_wait(bars + B_TFREE * 8);
                            load_chunk(n);
                        }
                    }
                    if (i < 4)
                        asm volatile("cp.async.bulk.tensor.4d.shared::cluster.global.mbarrier::complete_tx::bytes [%0], [%1, {%3, %4, %5, %6}], [%2];"
                                     :: "r"(sm + SM_SLAB + (i & 1) * 16384 + (i >> 1) * 8192), "l"(&tm_x), "r"(bars + (B_SLAB + (i & 1)) * 8),
                                        "r"(G * 16), "r"(64 * (i & 1)), "r"(4 * rank), "r"(i >> 1) : "memory");
                }
                TS(20);
                if (G < 56) {
#pragma unroll 1
                    for (; n < NPRE; n++) {
                        mbar_wait(bars + (B_FULL + n - IDEPTH2) * 8);
                        mbar_wait(bars + (n < 7 ? B_SFREE : B_KFREE) * 8);
                        load_chunk(n);
                    }
                }
                TS(21);
            }
            __syncwarp();
        } else if (v == 1) {
            if (lead) {
                asm volatile("cp.async.bulk.shared::cluster.global.mbarrier::complete_tx::bytes [%0], [%1], 20480, [%2];"
                             :: "r"(sm + SM_TAB), "l"(p.tab), "r"(bars + B_TAB * 8) : "memory");
                asm volatile("cp.async.bulk.shared::cluster.global.mbarrier::complete_tx::bytes [%0], [%1], 1536, [%2];"
                             :: "r"(sm + SM_F2), "l"(p.tab + 1280), "r"(bars + B_TAB * 8) : "memory");
                asm volatile("prefetch.tensormap [%0];" :: "l"(&tm_d) : "memory");
            }
        } else {
            const int sw = v - 2;
            if (sw == 0) {
                uint32_t tag;
                uint4* const my_stats = p.sc->stats[q] + c * 8 + g;
                asm volatile("ld.relaxed.gpu.global.u32 %0, [%1];" : "=r"(tag) : "l"(&p.sc->epoch) : "memory");
                float ws = 0.f;
#pragma unroll
                for (int k = 0; k < 4; k++) {
                    const uint4 w = ldg128(reinterpret_cast<const uint4*>(p.wr) + 32 * k + lane);
                    ws += (blo(w.x) + bhi(w.x)) + (blo(w.y) + bhi(w.y)) + (blo(w.z) + bhi(w.z)) + (blo(w.w) + bhi(w.w));
                }
                if (q < NREP) st_relaxed128(my_stats, make_uint4(0, 0, 0, 0));
                tag = tag % 3 + 1;
                sts32(sm + SM_TOK + 8, tag);
                bar_arrive(6, 160);
#pragma unroll
                for (int o = 1; o < 32; o <<= 1) ws += __shfl_xor_sync(0xFFFFFFFFu, ws, o);
                const uint32_t tb = ((tag & 1) << 15) | ((tag >> 1) << 31);
                const uint32_t ra = sm + SM_RED + (lane >> 1) * 144 + (lane & 1) * 64;
                const uint32_t kidx = 0xFFFF - (128 * (c & 15) + 16 * (lane >> 2) + 2 * (c >> 4) + ((lane >> 1) & 1));
                touch(ws);
                bar_sync(7, 160);
                const uint4 a0 = lds128(ra), a1 = lds128(ra + 16), a2 = lds128(ra + 32), a3 = lds128(ra + 48);
#define F(v) __uint_as_float(v)
                float ss = (F(a0.x) + F(a1.x)) + (F(a2.x) + F(a3.x)), dw = (F(a0.y) + F(a1.y)) + (F(a2.y) + F(a3.y));
                float sx = ((F(a0.z) + F(a1.z)) + (F(a2.z) + F(a3.z))) + ((F(a0.w) + F(a1.w)) + (F(a2.w) + F(a3.w)));
#undef F
                ss += __shfl_xor_sync(0xFFFFFFFFu, ss, 1); dw += __shfl_xor_sync(0xFFFFFFFFu, dw, 1); sx += __shfl_xor_sync(0xFFFFFFFFu, sx, 1);
                const float mean = sx * (1.0f / 1024.0f);
                const float var = fmaxf(ss * (1.0f / 1024.0f) - mean * mean, 0.f);
                const float m = rb(mean);
                float sd; asm("sqrt.approx.ftz.f32 %0, %1;" : "=f"(sd) : "f"(rb(rb(var) + 1e-5f)));
                const float rs = rcp(rb(sd));
                const float hi = rb(rs);
                const uint32_t p0 = pack_b(m, 0.5f * hi), p1 = pack_b(0.5f * (rs - hi), rs * (dw - m * ws));
                const uint32_t o0 = __shfl_xor_sync(0xFFFFFFFFu, p0, 2), o1 = __shfl_xor_sync(0xFFFFFFFFu, p1, 2);
                const uint32_t kr = ((p1 ^ (p1 >> 31 ? 0xFFFF0000u : 0x80000000u)) & 0xFFFF0000u) | kidx;
                const uint32_t k1 = __reduce_max_sync(0xFFFFFFFFu, kr), k2 = __reduce_max_sync(0xFFFFFFFFu, kr == k1 ? 0u : kr);
                const uint32_t sl = (q & 2) ? 0x1054 : 0x5410;
                if (q < NREP) st_relaxed128(my_stats, make_uint4(prmt(p0, o0, sl), prmt(p1, o1, sl), (prmt(p0, o0, sl + 0x2222) & 0x7FFF7FFFu) | tb, g == 0 ? k1 : k2));
                TSL(9);
                { const int t0_ = clock(); while ((int)clock() - t0_ < PDELAY) __nanosleep(20); }
            }
            bar_sync(3, 192);
            const uint32_t tg = lds32(sm + SM_TOK + 8), tb = ((tg & 1) << 15) | ((tg >> 1) << 31);
            {
                const uint32_t* src = &p.sc->stats[G & (NREP - 1)][(sw * 64 + (lane >> 1)) * 8 + (lane & 1)].z;
                uint2 kz[4];
#pragma unroll
                for (int i = 0; i < 4; i++) kz[i] = make_uint2(~tb, 0);
                int it = 0;
                bool ok;
                do {
#pragma unroll
                    for (int i = 0; i < 4; i++)
                        asm volatile("{ .reg .pred p; .reg .b64 t; setp.ne.u32 p, %3, 0; mov.b64 t, {%0,%1};\n"
                                     "@p ld.relaxed.gpu.global.b64 t, [%2]; mov.b64 {%0,%1}, t; }"
                                     : "+r"(kz[i].x), "+r"(kz[i].y) : "l"(src + i * 512), "r"((kz[i].x ^ tb) & 0x80008000u) : "memory");
                    ok = __all_sync(0xFFFFFFFFu, (((kz[0].x ^ tb) | (kz[1].x ^ tb) | (kz[2].x ^ tb) | (kz[3].x ^ tb)) & 0x80008000u) == 0);
                } while (!ok && ++it < SPIN_LIMIT);
                const uint32_t a1 = max(kz[0].y, kz[1].y), b1 = max(kz[2].y, kz[3].y);
                const uint32_t h1 = max(a1, b1), h2 = __vimax3_u32(min(a1, b1), min(kz[0].y, kz[1].y), min(kz[2].y, kz[3].y));
                const uint32_t w1 = __reduce_max_sync(0xFFFFFFFFu, h1), w2 = __reduce_max_sync(0xFFFFFFFFu, h1 == w1 ? h2 : h1);
                sts64(sm + SM_KEYS + sw * 8, w1, w2);
                bar_sync(8, 64);
                const uint2 o = lds64(sm + SM_KEYS + 8 - sw * 8);
                key = sw ? __vimax3_u32(min(w1, o.x), w2, o.y) : max(w1, o.x);
                TSL(19);
            }
            const int t = (0xFFFF - (key & 0xFFFF)) & 2047;
            {
                const uint4* row = reinterpret_cast<const uint4*>(p.x + (size_t)t * 1024);
                uint4 xr[3];
                xr[0] = ldg128(row + 64 * rank + lane); xr[1] = ldg128(row + 64 * rank + 32 + lane); xr[2] = ldg128(row + 2 * G + (lane & 1));
                uint4 stk;
                int it = 0;
                do stk = ld_relaxed128(p.sc->stats[G & (NREP - 1)] + ((t >> 1) & 7) * 128 + (t >> 4)); while (((stk.z ^ tb) & 0x80008000u) && ++it < SPIN_LIMIT);
                if (lane == 0) {
                    sts32(sm + SM_TOK + 4 * sw, t);
                    if (c == 0 && sw == 0) st_relaxed32(&p.sc->epoch, tg);
                }
                const uint32_t se = (t & 1) ? 0x3232 : 0x1010;
                const uint32_t m = prmt(stk.x, 0, se), hi = bmul2(prmt(stk.z, 0, se) & 0x7FFF7FFFu, 0x40004000u), lo = bmul2(prmt(stk.y, 0, se), 0x40004000u);
                const uint32_t a = sm + SM_XSEL + lane * 32 + sw * 16;
#pragma unroll
                for (int i = 0; i < 2; i++)
                    sts128(a + i * 1024, norm2(xr[i].x, m, hi, lo), norm2(xr[i].y, m, hi, lo), norm2(xr[i].z, m, hi, lo), norm2(xr[i].w, m, hi, lo));
                proxy_fence();
                __syncwarp();
                if (lane == 0) mbar_arrive(bars + B_TOK * 8);
                if (lane < 2) {
                    sts128(sm + SM_XRAW + sw * 64 + lane * 16, xr[2].x, xr[2].y, xr[2].z, xr[2].w);
                    sts128(sm + SM_XRAW + sw * 64 + 32 + lane * 16, norm2(xr[2].x, m, hi, lo), norm2(xr[2].y, m, hi, lo), norm2(xr[2].z, m, hi, lo), norm2(xr[2].w, m, hi, lo));
                }
                __syncwarp();
                TSL(42);
            }
        }
        const uint32_t po = pin(sm + SM_PAIR + v * 256 + lane * 4), pd = pin(mapa(po, rank ^ 1)), pb = pin(mapa(bars + B_PAIR * 8, rank ^ 1));
        const uint32_t hd = pin(sm + SM_H + (2 * v + (q >> 1)) * 128 + (q & 1) * 32 + g * 2);
        const bool upf = pin(p.up_first);
        mbar_wait(bars + B_TOK * 8);
        const uint32_t tag = lds32(sm + SM_TOK + 8);
        {
            if (G < 56) {
                const uint32_t SMB = sm & 0x3FFFFu;
                const uint64_t dw = (uint64_t)(SMB >> 4) | (1ull << 16) | (64ull << 32) | (1ull << 62);
                const uint64_t dx = (uint64_t)((SMB + SM_XSEL) >> 4) | (2ull << 16) | (8ull << 32);
                const uint64_t dh = (uint64_t)((SMB + SM_H) >> 4) | (8ull << 16) | (8ull << 32);
                const uint64_t dw2 = dw + (tag >> 2);
                float ag[4], au[4];
                TSL(13);
#pragma unroll
                for (int st = 0; st < 8; st++) {
                    const int n = (ORDER >> (4 * st)) & 15;
                    const uint64_t a = dw + (chunk_off(n) >> 4), b = dx + n * 16;
                    mbar_wait(bars + (B_FULL + n) * 8);
                    wg_fence();
                    if (st == 0) { wg_w0(ag, a, b); wg_w0(au, a + 512, b); } else { wg_w<1>(ag, a, b); wg_w<1>(au, a + 512, b); }
#pragma unroll
                    for (int k = 1; k < 4; k++) { wg_w<1>(ag, a + 128 * k, b + 4 * k); wg_w<1>(au, a + 512 + 128 * k, b + 4 * k); }
                    wg_commit();
                    if (st == 0 && v == 0) {
                        mbar_wait(bars + (B_KFREE + 1) * 8);
                        if (lead) {
#pragma unroll
                            for (int i = NPRE; i < 9; i++) load_chunk(i);
                        }
                        __syncwarp();
                    }
                    bool any = false;
#pragma unroll
                    for (int i = 0; i < 3; i++) any |= ((REFILL >> (4 * i)) & 15) == st;
                    if (any) {
                        wg_wait<1>(); bar_sync(4, 128);
                        if (v == (st & 3)) {
#pragma unroll
                            for (int i = 0; i < 3; i++) if (((REFILL >> (4 * i)) & 15) == st && lead) load_chunk(9 + i);
                            __syncwarp();
                        }
                    }
                    if (st == SDAT) { wg_wait<1>(); if (lane == 0) mbar_arrive(bars + B_SDONE * 8); }
                    if (st == SDAT) TSL(4);
                }
                wg_wait<0>();
                touch(ag); touch(au);
                TSL(14);
                if (q == 0) {
                    st_async4(pd, __float_as_uint(ag[0]), __float_as_uint(ag[1]), __float_as_uint(ag[2]), __float_as_uint(ag[3]), pb);
                    st_async4(pd + 128, __float_as_uint(au[0]), __float_as_uint(au[1]), __float_as_uint(au[2]), __float_as_uint(au[3]), pb);
                    sts128(po + 1024, __float_as_uint(ag[0]), __float_as_uint(ag[1]), __float_as_uint(ag[2]), __float_as_uint(ag[3]));
                    sts128(po + 1152, __float_as_uint(au[0]), __float_as_uint(au[1]), __float_as_uint(au[2]), __float_as_uint(au[3]));
                }
                __syncwarp();
                {
                    const float a0 = __uint_as_float(lds32(po + 1024)), a1 = __uint_as_float(lds32(po + 1152));
                    mbar_wait(bars + B_PAIR * 8);
                    const uint32_t gu = pack_b(a0 + __uint_as_float(lds32(po)), a1 + __uint_as_float(lds32(po + 128)));
                    const float gs = upf ? bhi(gu) : blo(gu), us = upf ? blo(gu) : bhi(gu);
                    const float hv = rb(siluf_(gs)) * us;
                    const uint32_t hb = pack_b(hv, hv);
                    sts16(hd, hb); sts16(hd + 64, hb);
                }
                proxy_fence();
                bar_sync(4, 128);
                TSL(15);
                float d[2][2][4];
#pragma unroll
                for (int n = 0; n < 5; n++) {
                    if (n < 4) {
                        const uint64_t a = dw2 + (chunk_off(8 + n) >> 4);
                        mbar_wait(bars + (B_FULL + 8 + n) * 8);
                        if (n == 3) TSL(24);
                        wg_fence();
                        wg_w0(d[n & 1][0], a, dh); wg_w0(d[n & 1][1], a + 512, dh);
#pragma unroll
                        for (int k = 1; k < 4; k++) { wg_w<1>(d[n & 1][0], a + 128 * k, dh + 16 * k); wg_w<1>(d[n & 1][1], a + 512 + 128 * k, dh + 16 * k); }
                        wg_commit();
                    }
                    if (n > 0) {
                        if (n < 4) wg_wait<1>(); else wg_wait<0>();
#pragma unroll
                        for (int i = 0; i < 2; i++) {
                            float (&r)[4] = d[(n - 1) & 1][i];
                            touch(r);
                            st_relaxed32(my_part + (2 * n - 2 + i) * 8 * 56 * 16, (__float_as_uint((q & 2) ? r[2] : r[0]) & ~3u) | tag);
                        }
                    }
                }
                TSL(16);
            } else {
                if (lane == 0) mbar_arrive(bars + B_SDONE * 8);
                mbar_wait(bars + B_STG * 8);
            }
            const int k = v & 1, t = lds32(sm + SM_TOK + 4 * k);
            if (((t >> 3) & 1) == rank) {
                const uint2* src = reinterpret_cast<const uint2*>(p.sc->part) + (2 * G + k) * 448 + (v >> 1) * 224 + lane;
                const int col = lane & 15, tq = (t >> 1) & 3;
                float sg = rb(sigmoidf_(__uint_as_float((key & 0x80000000u) ? (key & 0x7FFF0000u) : (~key & 0xFFFF0000u))));
                float xn = blo(lds16(sm + SM_XRAW + k * 64 + 32 + col * 2)), xv = blo(lds16(sm + SM_XRAW + k * 64 + col * 2));
                const bool own = (col >> 3) == rank;
                const uint32_t sa = pin(sm + SM_U + (16 * (t >> 10) + 8 * ((col >> 2) & 1) + (own ? 4 : 0)) * SUB + ((t >> 7) & 7) * 512 + 128 * tq
                                        + ((t & 0x70) ^ (32 * tq) ^ (own ? 64 : 0)) + (t & 1) * 8 + (col & 3) * 2);
                const uint32_t ra = pin(sm + SM_XSEL + k * 512 + lane * 4), wa = pin(sm + SM_XSEL + k * 512 + (v >> 1) * 256 + lane * 8);
                __nv_bfloat16* const op = p.out + pin(t * 1024 + G * 16 + col);
                touch(sg); touch(xn); touch(xv);
                sched_fence();
                uint2 pv[7] = {};
                for (int it = 0; it < SPIN_LIMIT; it++) {
#pragma unroll
                    for (int i = 0; i < 7; i++)
                        if (((pv[i].x ^ tag) | (pv[i].y ^ tag)) & 3)
                            asm volatile("ld.relaxed.gpu.global.v2.u32 {%0,%1}, [%2];" : "=r"(pv[i].x), "=r"(pv[i].y) : "l"(src + 32 * i) : "memory");
                    uint32_t bd[7];
#pragma unroll
                    for (int i = 0; i < 7; i++) { bd[i] = (pv[i].x ^ tag) | (pv[i].y ^ tag); touch(bd[i]); }
                    const uint32_t bad = (bd[0] | bd[1] | bd[2]) | (bd[3] | bd[4] | bd[5]) | bd[6];
                    if (__all_sync(0xFFFFFFFFu, (bad & 3) == 0)) break;
                }
#define F(v) __uint_as_float(v)
                sts64(wa, __float_as_uint(((F(pv[0].x) + F(pv[1].x)) + (F(pv[2].x) + F(pv[3].x))) + ((F(pv[4].x) + F(pv[5].x)) + F(pv[6].x))),
                      __float_as_uint(((F(pv[0].y) + F(pv[1].y)) + (F(pv[2].y) + F(pv[3].y))) + ((F(pv[4].y) + F(pv[5].y)) + F(pv[6].y))));
                if (v < 2) {
                    if (k) bar_arrive(13, 64); else bar_arrive(12, 64);
                } else {
                    mbar_wait(bars + (B_STG + (t >> 10)) * 8);
                    const float s = blo(lds16(sa));
                    if (k) bar_sync(13, 64); else bar_sync(12, 64);
                    TSL(25);
                    float y = (F(lds32(ra)) + F(lds32(ra + 128))) + (F(lds32(ra + 256)) + F(lds32(ra + 384)));
#undef F
                    y += __shfl_xor_sync(0xFFFFFFFFu, y, 16);
                    const float z = rb(xn + rb(rb(y) * sg));
                    if (lane < 16) *op = __float2bfloat16(xv + rb(s * rb(siluf_(z))));
                }
                TSL(26); TG(29);
            }
        }
    }
    }
}

__device__ __align__(128) const uint32_t g_tab[5504] = {
0x2fff3000,0x2e7c2fd4,0x2fc92fd4,0xad72af5a,0x2ff82ffc,0x230e2c07,0x2faf2fbc,0x217ea934,0x2fed2ff4,0xad4da8d5,0x2f912fa0,0x2e5e2bb7,
0x2fdd2fe6,0xb000af46,0x2f6e2f80,0x2fdd2fc9,0x2ff42fff,0x2e1f2fc9,0x2e1f2e7c,0xa875ad72,0x2fbc2fdd,0x9fd92a4e,0x2d4d2dba,0x2cd825db,
0x2f5a2f91,0xaeb5ac07,0x2c5d2cd8,0x30002f30,0x2ed02f1a,0xaf80aff4,0x2aaa2bb7,0x2cb02f1a,0x2fdd2ffc,0x2dba2fbc,0x2a4e2c07,0x25dba934,
0x2f462fa0,0xa7652875,0x25152875,0x2f802d27,0x2e3f2ed0,0xafa0ad72,0xa17e1cb6,0x2e3f2fe6,0x2cd82d96,0xadfeafd4,0xa934a6a1,0xa44e29f1,
0x2fbc2ff8,0x2d4d2faf,0x9fd9230e,0x2cd8217e,0x2e992f46,0xaa4e2515,0xaa4ea765,0x2fd42f80,0x2cb02dba,0xafffae99,0xad72ac5d,0x27652dba,
0x28752b05,0xab5eaee9,0xaf1aae5e,0xae3fa934,0x2f912ff4,0x2cd82fa0,0xac07a8d5,0x2f302bb7,0x2dba2ed0,0xac5d1cb6,0xae99ad72,0x2dba2fe6,
0x29932c5d,0xafc9af6e,0xafe6af6e,0xaaaa25db,0xa17e244e,0xa30ead4d,0xafafaffc,0xaff8aee9,0x2f5a2fed,0x2c5d2f91,0xaeb5ad4d,0x30002e5e,
0x2cb02e3f,0xad72a17e,0xafffafa0,0x27652e3f,0x217e2993,0xaf02afe6,0xaf02afc9,0xaf1aaaaa,0xab05a5db,0x2814aa4e,0xac07adba,0xad4dafdd,
0x2f1a2fe6,0x2bb72f80,0xaff4af46,0x2f1a2fc9,0x2b052d96,0xae5ea6a1,0xaee9afd4,0xa93429f1,0xa5db244e,0xadbaaffc,0xaa4ead4d,0xafddaee9,
0xaddcabb7,0x2cb0a17e,0x2765a17e,0x1cb6ad00,0x2ed02fdd,0x2aaa2f6e,0xaf80b000,0x2cb02fdd,0x28752cd8,0xaf1aa934,0xab5eadfe,0xae3fa44e,
0xab05a17e,0xac07afaf,0x2814a30e,0xad4daff8,0xaf6eaddc,0x2eb52765,0x2eb52cb0,0x2dba1cb6,0x29932f5a,0xa7652e99,0x25152e99,0x2aaaad96,
0xafa0ab05,0xabb7afed,0xaff4acd8,0x28d52ffc,0xa814af02,0x2f912d27,0x9fd9ae1f,0xaee9ae3f,0x2fd42c32,0xaf5a1cb6,0x30002d72,0x2fd42515,
0x28752f46,0xa8d52e7c,0xa8d52c32,0x2e3fa993,0xafedac5d,0xa934b000,0xaf30af5a,0xa8142eb5,0x1648adfe,0x2e992e5e,0x2c87a814,0xa9f1affc,
0x2fe62e1f,0xafffa875,0x2ddc2ff4,0x2ed02e1f,0x26a12f30,0xa9f12e5e,0xad96244e,0x2fd41fd9,0xafffad27,0xa515aff4,0xac32aff4,0xaddc2b5e,
0x2875acb0,0x2d272f46,0x2fa02993,0x2875aed0,0x2ee92f6e,0xaf91ac87,0x1fd92e99,0x28143000,0x244e2f1a,0xab052e3f,0xaf91a875,0x2fbc2b5e,
0xafd4addc,0x1648afc9,0x1648ae7c,0xafdd9cb6,0x2c32aa4e,0x2aaa2fd4,0x2f802e99,0x2e7caa4e,0x2d002ffc,0xae1fae5e,0xad272814,0xabb72dfe,
0x1fd92f02,0xac072e1f,0xafedad27,0x2dfe2e3f,0xaf6eae7c,0x25dbaf80,0x2c5daaaa,0xaf6eac32,0x2ddca5db,0x25153000,0x2c323000,0x2fff26a1,
0x28d52fbc,0xabb7af91,0xaff4ab05,0xafa0244e,0x96482ee9,0xac872dfe,0xae99af30,0x29f12fbc,0xaed0af02,0x2993af1a,0x2f46217e,0xacb0af02,
0x2f1a1cb6,0xa30e2fc9,0xa30e2e7c,0x2e1f2ddc,0x9fd92eb5,0xa44eb000,0xae5eaf5a,0xaf30ac5d,0xa17e2ed0,0xad002ddc,0xabb7afff,0xa17e2fe6,
0xadfeaf6e,0x2c07ae99,0x2fed2c87,0x9fd9b000,0x2fd42814,0xa9f12f30,0xad962934,0x26a12fed,0xaaaa2d00,0x2765afa0,0xa515afa0,0xa993afaf,
0xa5152eb5,0xad722dba,0x9cb6af6e,0xac322eb5,0xad00afbc,0x2d27adfe,0x2e1f2f30,0x2bb7aee9,0x2ffc2b5e,0xacd82e3f,0xafeda875,0xab052f1a,
0xadba2993,0x2c87ae7c,0x2c87ac32,0x2a4eaf46,0xaddc2d96,0xafe62c5d,0xaed02c5d,0x2fffa9f1,0x2e1fad4d,0x2e3f2814,0x2f02ac07,0xad27ab05,
0xae5e2d00,0x9fd9af1a,0xaf302b5e,0xa44e2faf,0x2e99acb0,0xad962f80,0x2f5aaaaa,0x2e99aed0,0xae3f2d72,0xaff82c32,0xaff82515,0x2f021cb6,
0x2ee9ac87,0x2d4d29f1,0x2ffc9648,0xa44eae99,0xaf6e2b05,0x26a1afbc,0xafd4a44e,0xadba2f91,0x2fc9a8d5,0xaf462e3f,0x2f802875,0x2fe6a8d5,
0xae992d4d,0xb0002c07,0xaf6ea814,0x2c872b05,0x2f80ab5e,0x2c322bb7,0x2e7c2bb7,0x2aaaaff8,0xaff42765,0x2b5eafff,0xad27ad72,0xaff42cb0,
0x2fed1648,0xaffc2c5d,0x2b052eb5,0x2cd82a4e,0xaee92d27,0xaffc2bb7,0xad4dad00,0x244e2e1f,0x2fdda993,0x29f12cb0,0x29f12ed0,0x2eb5af46,
0xafe61648,0x2d72afdd,0x9cb6afd4,0xaed01648,0x2f022934,0xafa02814,0xa8d52fed,0xa30e2f30,0xaf302d00,0xafed2b5e,0xa814af1a,0xa9342faf,
0x3000a765,0x26a12d72,0xa5db2fff,0x3000acb0,0xaf46a6a1,0x2ed0af5a,0x2cb0af5a,0xa993ac87,0x2d272cd8,0xae3f9fd9,0xaf022d4d,0xae1f2fbc,
0xaf6e2cd8,0xafd42b05,0x26a1affc,0xadba2fed,0x2fe6a30e,0x1cb62e1f,0xad722f1a,0x2ed0a30e,0xae1faaaa,0x2fafae7c,0x2fafac32,0x28d5af80,
0x29342e99,0xac07a9f1,0xafbc1648,0xaffc2c87,0xafa02cb0,0xafaf2aaa,0x2d00af80,0xafa02ed0,0x2f911648,0xa44e2eb5,0xafbc2c5d,0x2b052a4e,
0xac87acd8,0x3000ad4d,0x2f6e1fd9,0x2e99afbc,0x9cb62faf,0xa515ad27,0xac32ad27,0xad72a30e,0xafc92c87,0xaf802a4e,0x2f46adba,0xafe62c87,
0x2f02244e,0xa8d52f30,0xafa01fd9,0xa30e2e5e,0xa934ae1f,0x2fbcabb7,0x2c072d00,0x2ffcad27,0xaa4e2fff,0x26a1aed0,0x26a1afe6,0x1648addc,
0xaf4629f1,0xac3225db,0xae7c25db,0x29931648,0xab5e2f91,0xafaf2e5e,0xad002fed,0x2f1aad4d,0x2ee9a875,0xaf302ff8,0x2dfea17e,0x2fbcaff4,
0x2c5dafc9,0xa9f12d72,0x2d96afff,0x2c5dae7c,0xaf022993,0xab5e2515,0xab5ea765,0xa30e2aaa,0xacd82fd4,0xaf302dba,0xaf912f6e,0x2c07a6a1,
0x2d969fd9,0xafdd2fed,0x25db2c07,0x2f5aadfe,0x2e7caff8,0xad722f02,0x2fffae3f,0x2fc9aff8,0xaeb52934,0xaa4e244e,0x9648acd8,0xac5d2dfe,
0xaddc2ff8,0xae7c2d00,0xafc92d00,0x9cb628d5,0x2bb72515,0xaff82f80,0xab5e2f46,0x2bb7a765,0x2fbcaf5a,0xaf302fdd,0x2dfea5db,0x2ee9ad96,
0xae5e28d5,0xa934230e,0x2b05af02,0xaee92fa0,0xaeb52fff,0xad962c32,0xad962515,0xac872ddc,0x276529f1,0xaf802eb5,0xaf462fdd,0xa51529f1,
0x2ff4adfe,0xaff82fed,0x217e2c07,0x28759fd9,0xadfe2875,0xa814217e,0x2e5eaff8,0xaffc2ff4,0xaf5a2fe6,0xac872aaa,0xa6a1a993,0xaf5a2fc9,
0x9cb62c87,0xae7c2d96,0xafc92d96,0xaddc2eb5,0x2f1aac07,0xafaf2f30,0xad002f91,0xab5e2cd8,0xad962814,0xa5db1fd9,0x2fddaf91,0xaf5a2ee9,
0xafc92faf,0xaaaa28d5,0x2993ae1f,0xafe62faf,0xa8d52ddc,0xad002c32,0xad002515,0xaff82fff,0x2d4da6a1,0xae5e2dba,0xafed2f6e,0xaf912fd4,
0xad272765,0xa30e1cb6,0x2fafaddc,0xad272cb0,0xaffc2f5a,0xa81425db,0x2e5eafdd,0xadfe2d96,0xac5d2ee9,0xaa4e2934,0x9648ab05,0xaeb52e5e,
0x2993230e,0xac322b5e,0xae7c2b5e,0xaf462f02,0xacb026a1,0x9cb61648,0x2ddcaa4e,0xa76526a1,0xaff42ee9,0xa17e1fd9,0x2ff8af91,0xa8752814,
0xadfe2fa0,0xa44e230e,0x2cd8af02,0xa93428d5,0x96482aaa,0xa5db2515,0xa5dba765,0xa9f12993,0x2f462f5a,0x2c322e99,0x2e7c2e99,0xa993ad96,
0x2f1a2f30,0xa875244e,0x2e3f2e5e,0x2b5e1fd9,0x2ee92f02,0xaf30ad27,0x2dfe2e1f,0x2fbc2e3f,0x2eb52ed0,0xaf6eafff,0x2dba2ddc,0x2eb52fe6,
0x28752993,0xa8d52515,0xa8d5a765,0x2e3f2aaa,0x244e26a1,0xaf91ad96,0xab05a9f1,0x2fbc2fd4,0x96481fd9,0xae99afed,0xac87ac07,0x29f12dfe,
0xa515a17e,0x9cb6abb7,0xad72ad00,0xac32a17e,0xac5dab05,0xaf5aacd8,0xb000afed,0x2eb52ffc,0xaddcad27,0xae7caff4,0xafc9aff4,0x9cb62b5e,
0xaf02ae7c,0x217eaaaa,0xaf1aaf80,0xaf02ac32,0xafbcaf6e,0x2f302c87,0xadfeae99,0xaee9b000,0xafedafa0,0xaf30aff4,0xa934abb7,0xa81428d5,
0xafd4afff,0x1648ac32,0x1648a515,0xafddaddc,0xaed0af6e,0x2f462c5d,0x299325db,0xacb0af6e,0xad00adfe,0x2e1f2fed,0x2d272c07,0x2bb79fd9,
0xadfeaf02,0xa814ae1f,0x2e5e2d27,0xaffcae3f,0xaa4eacb0,0x2e992993,0x2fd42f46,0xaa4eaed0,0x1cb6a5db,0x2e7c3000,0x2fc93000,0x2ddc26a1,
0x2b5e2814,0xa8752934,0x2e3f2f30,0x2f1a2fed,0x1648a814,0x2c879fd9,0x2e992f91,0xa9f1aee9,0x2c322875,0x2f802fa0,0x2aaa2d27,0x2e7c2875,
0x2f1a2ddc,0xa30e2c32,0xa30e2515,0x2e1f2fff,0x2ffc2fd4,0xafedad96,0xacd8a9f1,0xab0526a1,0x2e1f2c32,0x2ff42d72,0xa8751cb6,0x2e1f2515,
0x2ffc2f6e,0x28142e99,0xae5eac87,0x2dfe3000,0x2eb52fbc,0xaf5aab05,0xb000af91,0xac5d244e,0x29932d00,0xac32afa0,0xae7cafa0,0xaf46afaf,
0x2fe62fd4,0x2ddc3000,0xafffaf5a,0x2ed02fd4,0x2d002ee9,0xad271fd9,0xae1faf91,0xabb72814,0x9fd928d5,0xae5eaff4,0xa44eabb7,0xaf30afa0,
0xadbaaaaa,0x2c87a515,0x2c872765,0x2a4ea993,0x9cb62d96,0xacb02c5d,0xa7652c5d,0x2ddca9f1,0xaff8adfe,0xa30eafbc,0xafafaee9,0xa17e2f30,
0x244ead00,0x2dfe2f1a,0x2934ab5e,0xacd8afaf,0x2fdd2e7c,0xb000a993,0x2f6e2f46,0x2fdd2c32,0xae3f9cb6,0xaff8a765,0xaff8acb0,0x2f022ddc,
0xac07afdd,0x2dfeaa4e,0x1fd9adba,0xafeda5db,0x2f6e2934,0xa6a12ee9,0x2fd42e5e,0x2dbaab05,0x27652f1a,0xaaaaaff4,0xa9932bb7,0xa5152f1a,
0xafddadfe,0xadbaaee9,0xaa4eafbc,0xa5db2f30,0x2aaaab5e,0x2fc92bb7,0x2fe62bb7,0xa993aff8,0x2e3f2fc9,0xafa01cb6,0xa17e2ddc,0x2e3f2e7c,
0xae5e9648,0x2d4dac5d,0xaf91aeb5,0xafedaa4e,0xac07aff8,0x1fd9afaf,0x2dfea30e,0xafeda17e,0x2fdd2aaa,0x29f12fe6,0x29f12fc9,0x2eb5a993,
0xa5152dba,0xaddcae99,0xafffac5d,0xac322dba,0xaf02af30,0x2fa02c07,0x28d5acd8,0x230eaf91,0x2934ad00,0x2e5eab5e,0x2ee92f1a,0xab05afaf,
0x2dba2fc9,0xac5d2ddc,0xae991cb6,0x2dba2e7c,0xaf80a6a1,0x2765af5a,0xa515af5a,0xaf46ac87,0x217eae5e,0x230e2ffc,0x2faf2dfe,0x2ff82814,
0x2f6e244e,0x2fd42934,0xa6a12dfe,0x2dbaacd8,0xa5152e3f,0xafffa17e,0xaddcafa0,0xac322e3f,0xae1faf80,0x2fafa515,0x2faf2765,0x28d5af46,
0x2f9125db,0xaee92a4e,0xa8142dba,0x9fd92fdd,0x2f1a2e7c,0x2bb72f46,0xaff4a993,0x2f1a2c32,0xaf309648,0xacd8aeb5,0x2c07ac5d,0xaf91aa4e,
0x25dbae5e,0x2dba2dfe,0x2a4e2ffc,0x2fdd2814,0x2d722faf,0xae7cad27,0xafc9ad27,0xafffa30e,0x27652fdd,0xa9932f6e,0xaaaab000,0xa5152fdd,
0xaf02ae5e,0x28d5af91,0x2fa02d4d,0x230eafed,0x2f91217e,0xa8142faf,0xaee9230e,0x9fd92ff8,0xaa4e2d72,0x26a1afc9,0x26a1ae7c,0x1648afff,
0xaf8029f1,0xafc925db,0xafe625db,0x2f461648,0x2fa0a934,0x2bb72cd8,0x2ff4a44e,0xa8d5adfe,0xafbc2875,0x2934aff8,0xaffc217e,0xac072ff4,
0x2fd4a765,0xaf5a2ddc,0x30009cb6,0x2fd4acb0,0xaf02aaaa,0xab5eacb0,0xab5eaed0,0xa30e2f80,0x2e5e2c5d,0xab053000,0x29342f5a,0x2ee9aeb5,
0xad96ad4d,0x2fddacd8,0xa5dbafbc,0xaf5a1fd9,0x2cb02e1f,0xaddca875,0x1cb62ff4,0x27652e1f,0xa6a1af91,0x29f1afed,0x2d96ae5e,0xafd42d4d,
0x9cb62ff8,0xafe62d00,0xaed02d00,0x2d7228d5,0x2875afe6,0x2d272993,0x2fa0aaaa,0x2875afc9,0xac072f5a,0x2934afdd,0xaffc25db,0xafbc2d96,
0x2cd8af1a,0x2f91ae3f,0x2f302875,0xac07ab5e,0xaeb52d72,0xad96a765,0xad96acb0,0xac872fff,0x2fc9aa4e,0xa9932fd4,0x2aaa2e99,0x2fe6aa4e,
0xaff41fd9,0x2ff8acd8,0xa17eafbc,0xa875ad4d,0x2ffca875,0x2ee9a17e,0xa44e2ff8,0x2d4daff4,0xaf6ea515,0x25dbaf46,0x2c5daf80,0xaf6e2765,
0x2d722c87,0xafe62d96,0xaed02d96,0x9cb62eb5,0xa8d5aee9,0x2bb72b05,0x2ff4a934,0x2fa0ae5e,0x2d962c07,0x25db2d4d,0xafdd2b05,0x2f5aa814,
0xa765af02,0x2f46af1a,0x2f80217e,0x2515af02,0xa8d52fff,0xad00a765,0xad00acb0,0xaff82d72,0x2dfeaeb5,0xacd83000,0x244e2f5a,0x29342c5d,
0xa17e2fc9,0xad002fff,0xabb7ad72,0xa17e2e7c,0x2d4daf5a,0x2ee9a5db,0xa44e2fdd,0x2ffcad96,0xafd42c07,0x29f1af91,0x2d96af30,0xa6a1acd8,
0x2f46230e,0xafc92b5e,0xafe62b5e,0xaf802f02,0xae7c2eb5,0xafff2dba,0x2d72af6e,0xafc92eb5,0x2ff4a814,0x217e2d4d,0xaff82b05,0x28752c07,
0xad4dab5e,0x2fedae3f,0x2e5e2875,0x2f91af1a,0x96482f80,0xa5dbacb0,0xa5dbaed0,0xa9f1aaaa,0xad729648,0xa515a6a1,0xac32a6a1,0x9cb62a4e,
0xae1f2ffc,0xae3f2c07,0xaf022fbc,0x2d27a934,0x2cd8230e,0xaffc2fa0,0x2b0528d5,0x2fedaf02,0x2e99afe6,0xad962f46,0x2f5aaf80,0x2e99afc9,
0x230eaddc,0x2d27aed0,0x2d27afe6,0xafaf2fff,0xafbc2c87,0x1fd9a9f1,0xad4d1648,0xacd82e99,0xaa4e2f30,0xac5d2814,0xaeb52fed,0x96482934,
0x2ed0a8d5,0xaf802e3f,0x2aaa2875,0x2cb0a8d5,0x2e99affc,0x3000afbc,0x2f6eac07,0xac872934,0xa993a8d5,0x2ed0afaf,0x2cb0afaf,0xaf462e1f,
0xaff42ed0,0x2b5ead72,0xad271cb6,0xaff42fe6,0xa44e2dba,0x9fd9a6a1,0xaf302fd4,0xae5e2f6e,0x2fbcad27,0x2d4dabb7,0x9fd92d00,0x2cd8ae1f,
0x2c87af80,0x2f5aae7c,0x2f5aac32,0x26a1aaaa,0xacb01648,0x2fffafdd,0x2d72afd4,0xa7651648,0xafaf2f91,0x2f1aafbc,0xab5ea44e,0xad002b05,
0x2b05230e,0xa44e28d5,0xafbc2fa0,0x2f91af02,0x3000aed0,0x26a19cb6,0xa5db2d72,0x3000afe6,0x2aaaaeb5,0x2c32a9f1,0x2e7ca9f1,0x2f80afdd,
0xad27244e,0x2e3fad4d,0x2f02affc,0x2e1faee9,0xaa4e2e5e,0xaeb52f30,0xac5d1fd9,0x9648244e,0x2cb0a30e,0xad722e1f,0xafff2f1a,0x2765a30e,
0x2ff8af46,0xabb72cb0,0xabb72ed0,0x2b5ea993,0x2b05ae99,0xa81429f1,0x2c079648,0x2d4dac87,0xafa02fe6,0xafaf2f80,0x2d00af46,0xafa02fc9,
0xa9342dba,0xafed2fd4,0xa814a6a1,0xaf302f6e,0x2c87a44e,0xb0002ffc,0xaf6e2d4d,0xae992ee9,0x2fffaf02,0xafe62ff8,0xaed02ff8,0xaddc2e3f,
0xaed02c87,0xaaaa2a4e,0x2f80adba,0xacb02c87,0xafaf2fed,0xab5e2b05,0x2f1aaffc,0xad002cd8,0xab052e1f,0xac072bb7,0x2814ad00,0xad4d2d27,
0x29f11cb6,0xac5d2c32,0xac5d2515,0xad962d72,0x2d722d96,0x25152c5d,0x2c322c5d,0x1cb6a9f1,0x2d272d4d,0xad00a814,0x2bb72c07,0x2e1f2b05,
0x2cd82d00,0xaffcaf1a,0x2b052b5e,0x2fed2faf,0x2c872cb0,0xadbaaf80,0x2a4e2aaa,0x2c872ed0,0xae3faddc,0xaff8aed0,0xaff8afe6,0x2f022fff,
0xaee9ae99,0xad4daf6e,0xaffcb000,0x244e2c87,0xaf6eaf30,0x26a1a814,0xafd4afed,0xadbaa934,0xafc9afa0,0x2f462d00,0xaf80afaf,0xafe6afa0,
0xac87ad4d,0x9648ac07,0x29f12814,0xae99ab05,0xa993ab5e,0x2ed02bb7,0x2cb02bb7,0xaf46aff8,0xa30ea765,0x2f1a2fff,0x2e1f2d72,0xa30eacb0,
0x244e1648,0x1fd92c5d,0x2f302eb5,0x2e5e2a4e,0x2ee92e1f,0x2ffc2f02,0x2d4d2e3f,0xa44ead27,0x2fdd2f80,0x29f12e7c,0x29f12c32,0x2eb52aaa,
0x2fe63000,0xad72a5db,0x1cb626a1,0x2ed03000,0x2f022f91,0xafa0afbc,0xa8d5a44e,0xa30e2b05,0x2b052d00,0xa44e2b5e,0xafbcaf1a,0x2f912faf,
0x16482765,0xafd4ad72,0xafddafff,0x16482cb0,0xaaaaa6a1,0xac32af5a,0xae7caf5a,0xaf80ac87,0xae1facd8,0x2d001fd9,0xabb7ad4d,0xad27afbc,
0xaf6eae5e,0xafd4af30,0x26a19fd9,0xadbaa44e,0xafe6aff4,0x9cb6ad27,0x2d722b5e,0xaed0aff4,0xae1faf46,0x2faf2cb0,0x2faf2ed0,0x28d5a993,
0xa934ac87,0x2c072f6e,0x2fbc3000,0x2ffc2e99,0xa8d5acb0,0x2875aaaa,0x2e3f2f80,0xa8d5aed0,0x29341648,0x2fed2eb5,0x28142c5d,0x2f302a4e,
0x2e992cd8,0x16482d4d,0xa9f19fd9,0x2c872fbc,0x2fff2faf,0xafe6ad27,0xaed0ad27,0xaddca30e,0x2fc92e99,0x2f802f5a,0xaf46ad96,0x2fe62e99,
0x2f022fed,0xa8d52b05,0xafa0affc,0xa30e2cd8,0x29342d27,0xafbcaf02,0xac07ae3f,0xaffcae1f,0xaa4e9cb6,0x26a1ac32,0x26a1a515,0x1648ad72,
0xaaaa29f1,0xaed025db,0xacb025db,0x2f801648,0xaf1aaf91,0x2875ae5e,0xae3fafed,0xab5e2d4d,0x2c07a875,0x2b052ff8,0x2d4da17e,0xa814aff4,
0x2eb52fc9,0xaf6ead72,0x2dba2fff,0x2eb52e7c,0xaf02af80,0xab5eafe6,0xab5eafc9,0xa30e2f46,0x2cd8a6a1,0x2f302d96,0x2f9129f1,0xac07afd4,
0x2d962ffc,0xafdda44e,0x25db2ee9,0x2f5a2d4d,0xae7ca17e,0x2d72abb7,0xafffad00,0xafc9a17e,0x2c5da934,0x2f5aa44e,0x30002cd8,0xaeb5adfe,
0x2d722ff8,0xacb02d00,0xa7652d00,0x2fff28d5,0xaf02a515,0x217eaf80,0xaf1aaf46,0xaf022765,0xa814af5a,0x2b052fdd,0x2d4da5db,0x2c07ad96,
0x2e5e2fa0,0x29342ff4,0xab052bb7,0x2ee9a8d5,0xaeb59cb6,0xad96aed0,0xad96afe6,0xac872d72,0xa765af6e,0x2f802c5d,0x2f4625db,0x2515af6e,
0x2ff42d4d,0xaff8a44e,0x217e2ee9,0x28752ffc,0xad4d2875,0xafbc217e,0xacd8aff8,0x1fd92ff4,0xaa4eafe6,0x2e99aaaa,0x2fd42993,0xaa4eafc9,
0x2fff2c87,0xacb02d96,0xa7652d96,0x2d722eb5,0xab5e2c07,0x2875af30,0xae3faf91,0xaf1aacd8,0xad96afbc,0xa5dbaffc,0x2fdd2934,0xaf5aac07,
0x2fc92875,0x2aaa2fa0,0xa9932d27,0x2fe62875,0xa8d52d72,0xad00aed0,0xad00afe6,0xaff89cb6,0xad4dafd4,0x2e5e2d96,0x2fed29f1,0x2f91a6a1,
0x2e1fa765,0x2ff49cb6,0xa8752ddc,0x2e1facb0,0x1fd92f5a,0xafbc25db,0xacd8afdd,0xad4d2d96,0xaeb5aee9,0x2f5aa934,0x30002b05,0x2c5dae5e,
0x2f80230e,0xaed02b5e,0xacb02b5e,0xaaaa2f02,0x2cb02fd4,0x1cb63000,0xaddcaf5a,0x27652fd4,0xaff4ac07,0xa17eaffc,0x2ff82934,0xa875afbc,
0x2dfea8d5,0x244e2ff4,0xacd82bb7,0x29342fa0,0x96482f46,0xa5dbafe6,0xa5dbafc9,0xa9f1af80,0xafff9648,0xae7ca6a1,0xafc9a6a1,0x2d722a4e,
0x2ff81fd9,0x230e2ee9,0x2faf2814,0x217eaf91,0xafeda30e,0x2d4dafa0,0xaf91a8d5,0xae5e2f02,0x2fdd2515,0xb0002aaa,0x2f6e2993,0x2fdda765,
0x230eafff,0x2d27afc9,0x2d27ae7c,0xafaf2d72,0xa8142fdd,0xaffc2a4e,0xadfe2dba,0x2e5e25db,0x2a4eaf91,0x2c5d2c07,0x2eb5acd8,0x1648af30,
0xac322f1a,0x2993aff4,0xaf462bb7,0xae7c2f1a,0x2fdd1fd9,0x2dba2814,0x2a4e2ee9,0x25dbaf91,0xaf46a8d5,0x2765afaf,0xa515afaf,0xaf802e1f,
0x2e3f2c32,0xafa02ddc,0xa17e2fff,0x2e3f2515,0xacd8adba,0x2dfe26a1,0x2934afd4,0x244eaf6e,0xa8142ff8,0xadfe2faf,0xaffc230e,0x2e5e217e,
0x2c87af46,0x2f5aa515,0x2f5a2765,0x26a1af80,0xae7c2dba,0x9cb6ae99,0xaddcac5d,0xafc92dba,0x2fafab05,0xaf1a2ee9,0x2b5e2e5e,0x2d002934,
0xaf91a30e,0xacd8a8d5,0x2c07afa0,0xaf302f02,0x2dba2c32,0xac5d2fff,0xae992ddc,0x2dba2515,0xa993aeb5,0x2fc9a9f1,0x2fe6a9f1,0x2aaaafdd,
0xa17e2fed,0xa30eadfe,0xafaf9fd9,0xaff82c07,0x2a4eafed,0x2eb5af91,0x2c5d2d4d,0x1648ae5e,0xae7c2e3f,0xaddca17e,0x9cb6afa0,0xafc92e3f,
0x2ff8a993,0xabb72fe6,0xabb72fc9,0x2b5e2aaa,0xaf30a5db,0x2fbcaa4e,0x2ee9adba,0x2dfeafdd,0x2f1a2515,0x2bb72993,0xaff42aaa,0x2f1aa765,
0xab05adba,0x2e5eafd4,0x2ee926a1,0x2934af6e,0xa5db2fed,0xadba9fd9,0xaa4eadfe,0xafdd2c07,0x2ddcaf02,0xacb02ff8,0xa7652ff8,0x9cb62e3f,
0xac322fdd,0xaf462f6e,0x2993b000,0xae7c2fdd,0x2fafacd8,0x2b5e2934,0xaf1a2dfe,0x2d00244e,0xaf30a17e,0x2ee9afaf,0x2fbca30e,0x2dfeaff8,
0x29f12ddc,0xac5da765,0xac5dacb0,0xad969cb6,0xa993aa4e,0x2765ac87,0xa515ac87,0xaaaa2dba,0xafa02f30,0xabb7244e,0xaff42e5e,0x28d51fd9,
0x28142bb7,0xaf912e1f,0x1fd92d27,0x2ee9ad00,0x2fd4aed0,0xaf5a2fff,0x3000addc,0x2fd4afe6,0x2fafaf46,0x2fa0ae7c,0x2fa0ac32,0xad002993,
0xa44eac5d,0x2f91b000,0x2b05af5a,0xafbc2eb5,0xb0002dfe,0x2c87ae5e,0xae992814,0xaf6e2ffc,0xa5152e1f,0x9cb6a875,0xad722ff4,0xac322e1f,
0x26a12b05,0xa9f12cd8,0xad962fed,0x2fd4affc,0x2fffae1f,0x2515230e,0x2c32230e,0x2ddcaf1a,0x2875ae7c,0x2d27aaaa,0x2fa0af80,0x2875ac32,
0xaee929f1,0x2f91ae99,0x9fd9ac87,0xa8149648,0xafed2f1a,0xaf302e3f,0xa934a875,0xa8142b5e,0xa6a12ddc,0xb0002fc9,0xb0002e7c,0x25db1cb6,
0x2ed0aa4e,0xaf462fd4,0xa9932e99,0x2cb0aa4e,0x2e3faffc,0xad272e5e,0x2e1fa814,0x2f02adfe,0x9fd9abb7,0x2c07ad27,0x2fedae1f,0xadfe2d00,
0xaf6e2cb0,0x25dba993,0x2c5daf46,0xaf6e2ed0,0xaddc2fdd,0xa5159648,0xac329648,0xafff2fd4,0x28d52814,0xabb72934,0xaff42f30,0xafa02fed,
0x3000aee9,0x2e99adfe,0xac872f30,0x2f6eafbc,0x2c32af02,0x2f80af1a,0x2aaa217e,0x2e7caf02,0xab5e9cb6,0x2ff4afc9,0x2ff4ae7c,0x2d27addc,
0xaffc2eb5,0x2fedb000,0x2cd8af5a,0x2b05ac5d,0xa17e2c32,0xad002d72,0xabb71cb6,0xa17e2515,0x2dfea9f1,0xac072c87,0xafed2e99,0x1fd91648,
0x2fd4afbc,0xa9f12b05,0xad962f91,0x26a1a44e,0x2aaaae3f,0xa76528d5,0x251528d5,0x2993a875,0xafe62eb5,0xaddc2dba,0x2fffaf6e,0xaed02eb5,
0xae3f2fbc,0xae1f2dfe,0x2d27af30,0xaf022ee9,0x9fd92b5e,0xae5e2e3f,0xa44ea875,0xaf302f1a,0x2d96a993,0xae992e7c,0xae992c32,0xaf5a2f46,
0x299329f1,0xa76525db,0x251525db,0x2aaa1648,0x28d52934,0xaf02acd8,0x230e244e,0x2fa02dfe,0x28142875,0xaf91aff8,0x1fd9217e,0x2ee92ff4,
0x26a12765,0xaa4eaddc,0x16481cb6,0x26a12cb0,0xaf02af46,0xab5eae7c,0xab5eac32,0xa30e2993,0xae5eaeb5,0x2b059648,0xa934aa4e,0xaee9ac5d,
0xad96adfe,0x2fdd2e5e,0xa5dba814,0xaf5aaffc,0xacb0ad27,0x2ddc2faf,0x9cb6a30e,0xa765ad27,0x2fd42f91,0x2f6e2fed,0x2dba2e5e,0xa6a1ad4d,
0x2fff2ff8,0x25152d00,0x2c322d00,0x2ddc28d5,0x2faf2fe6,0xae1fa993,0x28d52aaa,0x2faf2fc9,0x2ee92f5a,0xaf91afdd,0x1fd925db,0x28142d96,
0xacd8ab5e,0xaf91ad00,0xaf30afaf,0x2c072f1a,0xaeb5addc,0xad96afc9,0xad96ae7c,0xac879cb6,0xafc9af5a,0x2993a6a1,0xaaaaac87,0xafe6af5a,
0xaff4affc,0x2ff82e5e,0xa17ea814,0xa875adfe,0x9fd9a875,0x2c07a17e,0x2fed2ff8,0xadfeaff4,0x29f12515,0x2fdd2f46,0x2eb52f80,0x29f1a765,
0x2ddc2c87,0x25152d96,0x2c322d96,0x2fff2eb5,0x2fa02ee9,0xaf02ab05,0x230e2934,0x28d52e5e,0x2d962ee9,0x25db2dfe,0xafddaf30,0x2f5a2fbc,
0x27652bb7,0xaf46ab5e,0xaf80aff8,0xa5152bb7,0xa8d59cb6,0xad00afc9,0xad00ae7c,0xaff8addc,0xadfeac5d,0x2cd89648,0xa44eaa4e,0xa934aeb5,
0xaff8afc9,0xae3fafff,0x2f022d72,0xaff8ae7c,0xadfeaf5a,0x2c07a5db,0x2fed2fdd,0x9fd9ad96,0xa6a1ac07,0x2f6e2f91,0x2dba2f30,0x2fd42cd8,
0x2aaa230e,0xa7652b5e,0x25152b5e,0x29932f02,0x2e7c2c5d,0x2fff2d96,0xad72a9f1,0x2fc92c5d,0x2ff42fbc,0x217e2dfe,0xaff8af30,0x28752ee9,
0x2d4d2f1a,0xafedad00,0xae5eafaf,0xaf91ab5e,0x96482993,0xa5dbae7c,0xa5dbac32,0xa9f1af46,0xaddc9648,0xafe6a6a1,0xaed0a6a1,0x2fff2a4e,
0xad27affc,0x2d00ac07,0xabb7afbc,0xae1f2934,0x2e5e230e,0x1fd92fa0,0x2f3028d5,0x244eaf02,0x2c872fe6,0xadbaaf46,0x2a4e2f80,0x2c872fc9,
0x230ead72,0x2d27ac32,0x2d27a515,0xafaf9cb6,0x2fbc2e99,0x9fd92f6e,0x2d4d3000,0x2cd8ac87,0xaa4e2b05,0xac5dafbc,0xaeb5a44e,0x96482f91,
0xaed0afa0,0x2f802d00,0xaaaaafaf,0xacb0afa0,0x2c872ffc,0x16482fbc,0xa9f12c07,0x2e99a934,0xaf80a8d5,0xac32afaf,0xae7cafaf,0xaaaa2e1f,
0xa30eaed0,0x2f1a2d72,0x2e1f9cb6,0xa30eafe6,0x2fed2dba,0xaffca6a1,0x2b052fd4,0x2cd82f6e,0xafbcae1f,0xad4daf02,0x1fd9ae3f,0xacd82d27,
0x2c87a993,0x2f5a2cb0,0x2f5a2ed0,0x26a1af46,0x2cb03000,0xafffa5db,0xad7226a1,0x27653000,0xafafa934,0x2f1aa814,0xab5eafed,0xad00af30,
0x2f30230e,0x2fed28d5,0x28142fa0,0x2934af02,0x16482ed0,0xafd41cb6,0xafddad72,0x16482fe6,0xaf46aeb5,0x2ed0a9f1,0x2cb0a9f1,0xa993afdd,
0x2e1fa44e,0xad002d4d,0x2bb72ffc,0x2d272ee9,0xaa4e2cd8,0xaeb52b05,0xac5daffc,0x96482fed,0xacb0aff4,0x2d72ad27,0x2fff2b5e,0xa765aff4,
0x2ff82aaa,0xabb72e7c,0xabb72c32,0x2b5e2f80,0xab052c87,0x2814af6e,0xac07b000,0xad4dae99,0xa8d5afe6,0x2875af80,0x2e3f2f46,0xa8d5afc9,
0x2f912dba,0xa44e2fd4,0xafbca6a1,0x2b052f6e,0xae99244e,0x9648affc,0x29f1ad4d,0xac87aee9,0x1cb6af02,0x25152ff8,0x2c322ff8,0x2d722e3f,
0x2ed02e99,0x2aaa2f5a,0xaf80ad96,0x2cb02e99,0xafafa44e,0xab5eaf30,0x2f1a9fd9,0xad00ae5e,0x2b05ad27,0x2c072f02,0xa8142e3f,0x2d4d2e1f,
0x29f12fff,0xac5daed0,0xac5dafe6,0xad96addc,0xaf46aa4e,0xac32ac87,0xae7cac87,0x29932dba,0x2f1a2b05,0xa8752fed,0x2e3f2cd8,0x2b5eaffc,
0xaee9abb7,0x2f30ae1f,0xadfead27,0xafbc2d00,0x2eb52c32,0xaf6e1cb6,0x2dba2d72,0x2eb52515,0x2fafa993,0x2fa0a515,0x2fa02765,0xad00aaaa,
0xafed26a1,0xa934ad96,0xaf30a9f1,0xa8142fd4,0x30009fd9,0xac872fed,0x2e992c07,0x2f6eadfe,0xafe6a17e,0x2fffabb7,0xaddcad00,0xaed0a17e,
0xac5d2f30,0xaf5a2e5e,0xb000244e,0x2eb51fd9,0x2ddcae1f,0x2e7c230e,0x2fc9230e,0x1cb6af1a,0xaf022cb0,0x217eaf46,0xaf1aa993,0xaf022ed0,
0x2fbca9f1,0xaf302e99,0x2dfe2c87,0x2ee91648,0xa44eafa0,0x2b05aff4,0x2f91abb7,0xafbc28d5,0xa6a12fff,0xb0002c32,0xb0002515,0x25db2ddc,
0x2c32af6e,0x2aaa2c5d,0x2f8025db,0x2e7caf6e,0xae3f2dfe,0x2d27afed,0xae1fac07,0xaf021fd9,0x2dfe2bb7,0x28142d27,0xae5e2e1f,0x2ffcad00,
0xaa4eae7c,0x2e99af80,0x2fd4aaaa,0xaa4eac32,0x9cb62fdd,0xae7c9648,0xafc99648,0xaddc2fd4,0x2b5eafbc,0xa8752f91,0x2e3f2b05,0x2f1aa44e,
0xb0002814,0xae991fd9,0x2c87af91,0xaf6e2ee9,0x2ed02875,0xa9932fa0,0xaf462d27,0x2cb02875,0xab5eaddc,0x2ff4ac32,0x2ff4a515,0x2d27afff,
0x9fd92fd4,0xa44ead96,0xae5ea9f1,0xaf3026a1,0x2e1faed0,0x2ff4addc,0xa8752fff,0x2e1fafe6,0xaffc29f1,0xa814ac87,0x2e5eae99,0xadfe9648,
0x2eb52814,0xaf5a2f30,0xb0002934,0xac5d2fed,0xa993ae3f,0x2c3228d5,0x2e7c28d5,0x2f46a875,0xa5152fd4,0xad723000,0x9cb6af5a,0xac322fd4,
0x2e3faee9,0x2e1f9fd9,0xad272f91,0x2f02a814,0xaffc28d5,0x2cd8aff4,0x2fedabb7,0x2b05afa0,0x2d962aaa,0xae992515,0xae99a765,0xaf5a2993,
0x1cb6adba,0x2cb0aeb5,0x2765aeb5,0xaddc2f6e,0xaff82d4d,0xa30ea814,0xafaf2c07,0xa17e2b05,0xa44e2e3f,0xadfe2b5e,0xa9342f1a,0x2cd8a875,
0x2fddacb0,0xb0002f80,0x2f6eaaaa,0x2fddaed0,0x2d001cb6,0x217e2765,0x217e2cb0,0x2bb7addc,0x2ee9afdd,0x2d4daa4e,0x2ffcadba,0xa44ea5db,
0xa9f1a934,0x2fd4aee9,0x26a1ae5e,0xad962b05,0xafc92f1a,0x2f46aff4,0xaf802bb7,0xafe62f1a,0xafdd2d4d,0xadba2c07,0xaa4ea814,0xa5db2b05,
0xaaaa2f1a,0xafc92f02,0xafe62f02,0x2993a17e,0x2e3fa765,0xafa02fff,0xa17e2d72,0x2e3facb0,0x2e5eb000,0xad4d2eb5,0x2f91ac5d,0x2fedaf5a,
0x2ee9aff8,0x2ffcafaf,0x2d4da30e,0xa44ea17e,0xa5dbaaaa,0x2f6eafe6,0x2f6eafc9,0xac5d2993,0xafe62dba,0x2d72ae99,0x9cb6ac5d,0xaed02dba,
0xabb72f30,0x28d5ac07,0xafa02cd8,0xaff42f91,0xa9342e3f,0xae5e2f1a,0xaee92b5e,0x2b05a875,0x2dbaa765,0xac5d2d72,0xae992fff,0x2dbaacb0,
0x2f80afd4,0xa7652a4e,0x25152a4e,0x2f46ae99,0x217eacd8,0x230e1fd9,0x2fafad4d,0x2ff8afbc,0xa9f1a44e,0x26a1a934,0x2fd4adfe,0xad962cd8,
0xafe62e3f,0x9cb6a17e,0x2d72afa0,0xaed02e3f,0xad272f80,0xa8752515,0xa875a765,0xafa02f46,0x293425db,0xac072a4e,0xafbc2dba,0xaffc2fdd,
0x2f1aacb0,0x2bb7aaaa,0xaff42f80,0x2f1aaed0,0x2f30b000,0x2cd8ac5d,0xac072eb5,0x2f91af5a,0x25dbacd8,0x2dbaad4d,0x2a4e1fd9,0x2fddafbc,
0xad722875,0x2e7cae1f,0x2fc9ae1f,0x2fffaff4,0xafc92fdd,0xaf802f6e,0x2f46b000,0xafe62fdd,0xabb72e5e,0xafa02f91,0x28d5ad4d,0xaff42fed,
0x2934217e,0xafbc2faf,0xac07230e,0xaffc2ff8,0x2f5aad72,0xafd42fc9,0xafd42e7c,0xb0002fff,0x9cb69648,0xacb0a6a1,0xa765a6a1,0x2ddc2a4e,
0xa17e9fd9,0xaff4aee9,0xa875a814,0x2ff82f91,0xa44ea30e,0xadfeafa0,0xa934a8d5,0x2cd82f02,0xa5dba515,0x9648aaaa,0xa9f1a993,0xa5db2765,
0xa30e9cb6,0xad27a765,0xad27acb0,0x2faf2ddc,0xa814a5db,0xaffcaf5a,0xadfead96,0x2e5e2fdd,0xaa4ea934,0xac5daee9,0xaeb5ae5e,0x96482b05,
0xac32ab5e,0x2993a30e,0xaf46af02,0xae7cab5e,0xa5db9fd9,0xad96a814,0xaf5aaee9,0x2fdd2f91,0xaaaaa8d5,0xafc9afaf,0xafe6afaf,0x29932e1f,
0xad00ac32,0xa8d5addc,0xaff8afff,0xad00a515,0xae5eadba,0x2d4d26a1,0xaf91afd4,0xafedaf6e,0xa814a17e,0xadfea875,0xaffcaff4,0x2e5e2ff8,
0xac87aaaa,0xaf5aafe6,0xaf5aafc9,0xa6a12993,0xae7cad96,0x9cb6ac87,0xaddcaeb5,0xafc9ad96,0xafafaf30,0x2f1a2c07,0xab5eacd8,0xad00af91,
0xa934a30e,0xae5ea8d5,0xaee9afa0,0x2b052f02,0xad96ac32,0xaeb5afff,0xac87addc,0xad96a515,0xaf80aeb5,0x2765a9f1,0xa515a9f1,0xaf46afdd,
0xaff8afed,0x2ff42dfe,0x28751fd9,0x217eac07,0xaa4ea44e,0xaeb5a934,0xac5dadfe,0x96482cd8,0xae7cad00,0xaddcaff8,0x9cb6a8d5,0xafc9ad00,
0xaff8af80,0x2bb7a515,0x2bb72765,0xab5eaf46,0xaf30afdd,0x2fbc2f5a,0x2ee92d96,0x2dfe25db,0xab5ea515,0xaf02a993,0xa30eaaaa,0xab5e2765,
0xaf30adba,0xacd8afd4,0x2c0726a1,0xaf91af6e,0xafddafed,0x2d961fd9,0x2f5a2dfe,0x25dbac07,0xad72af02,0x2e7c2ff8,0x2fc92ff8,0x2fff2e3f,
0xac32a5db,0xaf46a9f1,0x29939648,0xae7ca5db,0xafafae5e,0xab5eaf91,0x2f1a2d4d,0xad00afed,0xaf30aff8,0x2ee92875,0x2fbc2ff4,0x2dfe217e,
0xa9f1ad72,0x2c5d2fc9,0x2c5d2e7c,0x2d962fff,0xaf80aa4e,0xafc9ac87,0xafe6ac87,0x2f462dba,0xa8d5af30,0x2f02a44e,0xa30eae5e,0xafa09fd9,
0x2fbc2bb7,0xa9342e1f,0x2ffc2d27,0x2c07ad00,0x26a12ed0,0xaa4eafff,0x16482ddc,0x26a12fe6,0xafafaaaa,0xafa0acb0,0xafa0aed0,0x2d002f80,
0xa44eaeb5,0x2f919648,0x2b05aa4e,0xafbcac5d,0x30002d4d,0xac872cd8,0x2e992fbc,0x2f6e9fd9,0xa5152d27,0x9cb6afaf,0xad72230e,0xac322d27,
0xafd4ab05,0xaf6eacd8,0xadbaafed,0x26a12ffc,0x1cb6ae1f,0x2fe6230e,0x2ed0230e,0xad72af1a,0x2faf2e7c,0xae1f2aaa,0x28d52f80,0x2faf2c32,
0xac0729f1,0x2934ae99,0xaffcac87,0xafbc9648,0xafedab5e,0xaf30ad00,0xa934afaf,0xa8142f1a,0x26a1ad72,0x30002765,0x30002cb0,0xa5dbafff,
0x2ed02f5a,0xaf4626a1,0xa9932c87,0x2cb02f5a,0xae3f1fd9,0x2d27acd8,0xae1fafbc,0xaf02ad4d,0xaffcabb7,0xaee9ad27,0x244eae1f,0xad4d2d00,
0x29f1acb0,0x2fdd2993,0x2eb52f46,0x29f1aed0,0x2d722fdd,0xafe69648,0xaed09648,0x9cb62fd4,0xafa0a814,0x2f02a934,0xa30eaf30,0xa8d5afed,
0xb000ac07,0xae99ad4d,0x2c87ab05,0xaf6e2814,0x2c32abb7,0x2f802b5e,0x2aaa2ff8,0x2e7cabb7,0x2b5e2fff,0xaff4a765,0xaff4acb0,0xad272d72,
0xaffcac5d,0x2fed9648,0x2cd8aa4e,0x2b05aeb5,0xaff8ac32,0xae3fad72,0x2f029cb6,0xaff8a515,0x2d4da9f1,0x2ee92c87,0xa44e2e99,0x2ffc1648,
0x26a12fbc,0xaf6eab05,0xadbaaf91,0xafd4244e,0xaf46ae3f,0x2fc928d5,0x2fe628d5,0x2f80a875,0xafe6ac5d,0xaddcad96,0x2fff29f1,0xaed0ac5d,
0x2e3fa814,0x2e1f2d4d,0xad272b05,0x2f022c07,0x9fd92f1a,0xae5ead00,0xa44eafaf,0xaf30ab5e,0xad96af80,0x2e992cb0,0x2e992ed0,0x2f5a2aaa,
0xad72adba,0xa515aeb5,0xac32aeb5,0x9cb62f6e,0x2d272dfe,0xad002fbc,0x2bb72ee9,0x2e1faf30,0xacd8ae3f,0x2ffcab5e,0xab05af1a,0xafed2875,
0x2c872e7c,0xadbaa993,0x2a4e2f46,0x2c872c32,0xad00addc,0xa17eaed0,0xa17eafe6,0xabb72fff,0x2c072e99,0xadfe2f6e,0x9fd93000,0x2fedac87,
0xa9f1af30,0x2fd4a814,0x26a1afed,0xad96a934,0x27652fa0,0xaaaaad00,0xa9932faf,0xa5152fa0,0xac87adfe,0x9648aee9,0x29f1afbc,0xae992f30,
0x29932f1a,0xaed02f02,0xacb02f02,0x2f46a17e,0xa30eafc9,0x2f1a9cb6,0x2e1faddc,0xa30eae7c,0xa44e3000,0x9fd9aeb5,0xaf302c5d,0xae5e2f5a,
0xac07ae1f,0x1fd9af02,0x2dfeae3f,0xafed2d27,0x25db2f80,0xaf6e2e7c,0xaf6e2c32,0x2c5d2aaa,0x2515b000,0x2ddc25db,0x2fffa6a1,0x2c32b000,
0xabb72f91,0x28d5afbc,0xafa0a44e,0xaff42b05,0xab05ae3f,0x244eaf1a,0x2fbcab5e,0xaf912875,0x16482fc9,0xafd42ddc,0xafdd1cb6,0x16482e7c,
0x2aaaafd4,0x2c322a4e,0x2e7c2a4e,0x2f80ae99,0xae1f2e5e,0x2d00affc,0xabb7adfe,0xad27a814,0xa9f1ae5e,0x26a1af30,0x2fd49fd9,0xad96a44e,
0xa5152ff4,0xafff2d27,0xaddcab5e,0xac322ff4,0x2d27af46,0x28752cb0,0x28752ed0,0x2fa0a993,0xaf912c87,0x2ee9af6e,0x2814b000,0x1fd9ae99,
0xa8d5ae7c,0x2875af46,0x2e3f2993,0xa8d5ac32,0xa9343000,0xafed2c5d,0xa814aeb5,0xaf302f5a,0x2e99ae5e,0x16482dfe,0xa9f12ffc,0x2c872814,
0xafff2875,0x2fe6ae1f,0x2ed0ae1f,0x2ddcaff4,0xa765ae99,0x2993af5a,0x2aaa2d96,0x2515ae99,0xabb72fed,0xafa02b05,0x28d5affc,0xaff42cd8,
0x2f91ad27,0xa8142f02,0xaee92e3f,0x9fd92e1f,0xaf5a9cb6,0x2fd4ac32,0x2fd4a515,0x3000ad72,0x2aaaaf6e,0x2ed0afdd,0x2cb0afdd,0xaf803000,
0xaf1a2934,0x2875acd8,0xae3f244e,0xab5e2dfe,0xac072faf,0xab05217e,0xad4d2ff8,0x2814230e,0x2eb5a765,0xaf6e2ddc,0x2dba9cb6,0x2eb5acb0,
0x2bb7af80,0x2f1aafe6,0x2f1aafc9,0xaff42f46,0xae5e26a1,0x2b05ad96,0xa934a9f1,0xaee92fd4,0xadba2ffc,0xa5dba44e,0xafdd2ee9,0xaa4e2d4d,
0x2cb0217e,0xaddc2bb7,0x1cb62d00,0x2765217e,0x2c5daf91,0x2f5aafed,0x3000ae5e,0xaeb52d4d,0xad72217e,0x2cb0ae3f,0x2765ae3f,0xafff2fa0,
0xaf022fe6,0x217ea993,0xaf1a2aaa,0xaf022fc9,0x28142a4e,0xab0525db,0xad4d2fdd,0xac072dba,0x2cd8afa0,0x2f91aff4,0x2f30abb7,0xac0728d5,
0xac5d9cb6,0x2dbaaed0,0x2dbaafe6,0xae992d72,0xafc92f6e,0x2993ac5d,0xaaaaa5db,0xafe62f6e,0xa30e2d4d,0xa17ea44e,0xaff82ee9,0xafaf2ffc,
0x2d4dafaf,0x2fbcaff8,0x2cd8a17e,0x9fd9a30e,0xaa4ea515,0x2e99af46,0x2fd4af80,0xaa4e2765,0xafff2e99,0x2cb0adba,0x2765adba,0xad722c5d,
0xab5e2ee9,0x2875ab05,0xae3f2934,0xaf1a2e5e,0x2dbaafbc,0x2fddaffc,0x25db2934,0x2a4eac07,0xa765a875,0x2f46afa0,0x2f80ad27,0x2515a875,
0xafa02d72,0x2e3faed0,0x2e3fafe6,0xa17e9cb6,0xadfe2fd4,0x2cd8ad96,0xa44ea9f1,0xa93426a1,0x2e1fafc9,0x2ff4afff,0xa8752d72,0x2e1fae7c,
0x9fd9aa4e,0x2fbcafdd,0x2cd8a5db,0x2d4dadba,0xaeb52c07,0x2f5aaf91,0x3000af30,0x2c5dacd8,0xaf802ff4,0x2ed0af1a,0x2cb0af1a,0x2aaaabb7,
0x2e7cafd4,0x2fffb000,0xad722f5a,0x2fc9afd4,0x230eac07,0x2ff8affc,0x217e2934,0x2fafafbc,0xad4d28d5,0x2fedaff4,0x2e5eabb7,0x2f91afa0,
0xb0002f46,0x2fddafe6,0x2fddafc9,0x2f6eaf80,0xaaaaaa4e,0xaed0ac87,0xacb0ac87,0x2f802dba,0xab5eab05,0xafafafed,0xad00acd8,0x2f1a2ffc,
0xac07abb7,0xab05ae1f,0xad4dad27,0x28142d00,0xac5dac32,0x29f19cb6,0xad96ad72,0xac5da515,0xafafaf80,0xafa0afe6,0xafa0afc9,0x2d002f46,
0xafedafd4,0xa934adba,0xaf30af6e,0xa81426a1,0xb000affc,0x2c87244e,0xae99aee9,0xaf6ead4d,0xafe6aff8,0x2fff2f02,0xaddcae3f,0xaed0aff8,
0xaeb5af30,0xaa4eae5e,0x9648a44e,0xac5d9fd9,0xad72ae1f,0x2cb0230e,0x2765230e,0xafffaf1a,0xabb7acb0,0x2ff82f46,0x2b5e2993,0xabb7aed0,
0xa814a9f1,0x2b052e99,0x2d4d2c87,0x2c071648,0xa44ea8d5,0x2b05a30e,0x2f912f02,0xafbcafa0,0x26a11cb6,0x30002ed0,0x30002fe6,0xa5dbad72,
0x2c3229f1,0x2aaa2eb5,0x2f802fdd,0x2e7c29f1,0x2e3f2d4d,0xad27a44e,0x2e1f2ee9,0x2f022ffc,0x2d4d2bb7,0x2fbc2d27,0x2cd82e1f,0x9fd9ad00,
0x2f5a2e7c,0x2c872f80,0x26a12aaa,0x2f5a2c32,0x2fff2fdd,0xacb09648,0xa7659648,0x2d722fd4,0x2f1a2fbc,0xafafaf91,0xad00ab05,0xab5e244e,
0x30002fbc,0x2e992ffc,0xac87a934,0x2f6e2c07,0x2ed02faf,0xa99328d5,0xaf46ae1f,0x2cb02faf,0x2b5e2d72,0xaff4aed0,0xaff4afe6,0xad279cb6,
0x9fd926a1,0xa44eadba,0xae5eaf6e,0xaf30afd4,0x2d272ed0,0x230e2ddc,0xafafafff,0x2d272fe6,0x1fd929f1,0xafbcac87,0xacd8ae99,0xad4d9648,
0xac5da814,0xaa4eaf30,0x9648a934,0xaeb5afed,0xaf80ae3f,0x2ed028d5,0x2cb028d5,0x2aaaa875,0xa51526a1,0xad721648,0x9cb6aa4e,0xac3226a1,
0xae3fac07,0xae1faffc,0x2d272934,0xaf02afbc,0xaffcafa0,0x2cd8a30e,0x2fed2f02,0x2b05a8d5,0xad96af46,0x2e992fe6,0x2e992fc9,0x2f5a2f80,
0xafffadba,0xae7caeb5,0xafc9aeb5,0x2d722f6e,0x217ead4d,0x2ff42814,0x2875ac07,0xaff8ab05,0x2fed2e3f,0xad4d2b5e,0x2f912f1a,0x2e5ea875,
0xa5db2cb0,0x9648af80,0xa9f12aaa,0xa5db2ed0,0xad00afff,0xa17eafc9,0xa17eae7c,0xabb72d72,0x2ee925db,0x2d4d2f5a,0x2ffc2d96,0xa44eafdd,
0x29f12f91,0xafd4ac07,0xa6a12cd8,0x2d962f30,0xafc9ab5e,0x2f46a30e,0xaf80af02,0xafe6ab5e,0x25dbad4d,0x2d96ac07,0x2f5a2814,0xafddab05,
0x2f462f1a,0xa7652f02,0x25152f02,0x2f80a17e,0xad002765,0xa8d5afff,0xaff8ad72,0xad002cb0,0xacd8b000,0x2dfe2eb5,0x2934ac5d,0x244eaf5a,
0x2ee9217e,0x2ffc2875,0x2d4d2ff4,0xa44eaff8,0x25db2f46,0xaf6e2515,0xaf6ea765,0x2c5d2f80,0xafe6ad96,0x2d72ac87,0x9cb6aeb5,0xaed0ad96,
0x2bb7ab05,0xa8d52ee9,0x2fa02e5e,0x2ff42934,0x2f912e3f,0x2cd82f1a,0xac072b5e,0x2f30a875,0xad962765,0xaeb5ad72,0xac87afff,0xad962cb0,
0xa993afd4,0x2fc92a4e,0x2fe62a4e,0x2aaaae99,0x2ff82cd8,0xaff49fd9,0xa8752d4d,0xa17e2fbc,0x29f12fed,0xa6a12f91,0xafd4ad4d,0x2d962e5e,
0xafe6ad00,0x9cb6aff8,0x2d72a8d5,0xaed0ad00,0x2d27a993,0x28752fe6,0x28752fc9,0x2fa02aaa,0x29342fdd,0xac07af5a,0xafbcad96,0xaffca5db,
0xab5e2cb0,0xaf022aaa,0xa30eaf80,0xab5e2ed0,0xab05b000,0x2e5eac5d,0x2ee92eb5,0x2934af5a,0x2fdd2cd8,0xad962d4d,0xaf5a9fd9,0xa5db2fbc,
0xaddc2875,0x2cb0ae1f,0x2765ae1f,0x1cb6aff4,0xafc9a5db,0xaf80a9f1,0x2f469648,0xafe6a5db,0x2bb7acd8,0x2fa02934,0xa8d52dfe,0x2ff4244e,
0x29342ff8,0xafbca875,0xac07aff4,0xaffca17e,0xaf5aaddc,0x2fd42765,0x2fd42cb0,0x30001cb6,0xa993af6e,0x2765afdd,0xa515afdd,0xaaaa3000,
0x28d52f91,0xaf022e5e,0x230e2fed,0x2fa0ad4d,0xa814afaf,0x2f91a17e,0x9fd9aff8,0xaee9a30e,0x26a12fc9,0xaa4ead72,0x16482fff,0x26a12e7c,
0x2bb7af46,0x2f1aae7c,0x2f1aac32,0xaff42993,0xacd82eb5,0xaf301648,0xaf912a4e,0x2c072c5d,0x2dbaadfe,0x25db2e5e,0x2fdda814,0x2a4eaffc,
0xae7c2d27,0x2d72afaf,0xafff230e,0xafc92d27,0x2fd4a934,0x2f6ea44e,0x2dba2cd8,0xa6a1adfe,0xafff217e,0xa515ae3f,0xac32ae3f,0xaddc2fa0,
0x2faf2515,0xae1f2f80,0x28d52f46,0x2fafa765,0xaee9aa4e,0x2f91a5db,0x9fd9afdd,0xa814adba,0x2e5e2b5e,0x29342d00,0xab052faf,0x2ee9af1a,
0xac5daddc,0x2dbaafc9,0x2dbaae7c,0xae999cb6,0x27652f5a,0xaf8026a1,0xaf462c87,0xa5152f5a,0x230eaffc,0x217e2e5e,0x2ff8a814,0x2fafadfe,
0x1fd92faf,0xac072ff8,0xafed217e,0x2dfe230e,0x29f1afe6,0x2fddaaaa,0x2eb52993,0x29f1afc9,0xaddc2e99,0xa515adba,0xac32adba,0xafff2c5d,
0x2fa0ac07,0xaf022f30,0x230e2f91,0x28d52cd8,0xadba2ee9,0xafdd2dfe,0xa5dbaf30,0xaa4e2fbc,0x2fc9abb7,0x2aaa2b5e,0xa9932ff8,0x2fe6abb7,
0xafa09cb6,0x2e3fafc9,0x2e3fae7c,0xa17eaddc,0x2d4d2c5d,0xae5e1648,0xafed2a4e,0xaf912eb5,0xaff82765,0xae3f1cb6,0x2f02addc,0xaff82cb0,
0x2dfe2a4e,0xac072fdd,0xafed25db,0x1fd92dba,0xa6a1aee9,0x2f6ea934,0x2dba2b05,0x2fd4ae5e,0xaaaa2ff4,0x2765af1a,0xa515af1a,0xa993abb7,
0xacb0ac5d,0x9cb6ad96,0x2ddc29f1,0xa765ac5d,0xa30e2fbc,0xaff82dfe,0xa17eaf30,0xafaf2ee9,0x2dfeaf1a,0x244e2d00,0xacd82faf,0x29342b5e,
0xb0002993,0x2fddae7c,0x2fddac32,0x2f6eaf46,0x2ddcb000,0x2fe6afd4,0x2ed0afd4,0xafff2f5a,0xad279fd9,0x2d00aee9,0xabb7a814,0xae1f2f91,
0xae5e2ff4,0x9fd9a8d5,0xaf302fa0,0xa44e2bb7,0x2c872515,0xadba2aaa,0x2a4e2993,0x2c87a765,0x2ff4ad72,0x2e1fac32,0x2e1fa515,0xa8759cb6,
0x2814ae99,0x2ffcaf6e,0x2dfeb000,0xae5e2c87,0xaf5a2b05,0x2eb5afbc,0xac5da44e,0xb0002f91,0xac322fa0,0x2993ad00,0xaf462faf,0xae7c2fa0,
0x2c871fd9,0x16482814,0xa9f12ee9,0x2e99af91,0x2f80afa0,0x2c32a875,0x2e7ca875,0x2aaaad27,0xa30eac32,0x2f1aaddc,0x2e1fafff,0xa30ea515,
0xafed2d96,0x2ffcafd4,0xab05a6a1,0xacd829f1,0xa8142e1f,0xadfe2f02,0xaffc2e3f,0x2e5ead27,0x2e99a993,0xaa4e2cb0,0xaa4e2ed0,0x2fd4af46,
0x2e7cb000,0x1cb625db,0x2ddca6a1,0x2fc9b000,0xa875a934,0x2b5ea814,0x2f1aafed,0x2e3faf30,0xaf302ff4,0xafed2fa0,0xa814a8d5,0xa9342bb7,
0x16482c32,0xafd42fff,0xafdd2ddc,0x16482515,0x2f46ac5d,0xaed02f6e,0xacb02f6e,0x2993a5db,0x2e1fafed,0xad002dfe,0x2bb71fd9,0x2d27ac07,
0xaf5a2cd8,0xac5d2b05,0x2eb5affc,0xb0002fed,0xae7c2ff4,0xaddc2d27,0x9cb6ab5e,0xafc92ff4,0x217e2aaa,0xaf022e7c,0xaf022c32,0xaf1a2f80,
0x2f30ac87,0xafbc2f6e,0xaee93000,0xadfe2e99,0xa8d5a515,0x2875a993,0x2e3faaaa,0xa8d52765,0xaf912d96,0x244ea6a1,0x2fbcafd4,0xab0529f1,
0xae992fed,0x96489fd9,0x29f1adfe,0xac872c07,0x9cb62bb7,0xa515217e,0xac32217e,0xad722d00,0x2c32ae99,0x2f46af5a,0xa9932d96,0x2e7cae99,
0xa875a44e,0x2f1aaf30,0x2b5e9fd9,0x2e3fae5e,0xaf302d27,0x2ee9af02,0x2fbcae3f,0x2dfeae1f,0xaf6e2fff,0x2eb5aed0,0x2eb5afe6,0x2dbaaddc,
0xaddcadba,0xafe6aeb5,0xaed0aeb5,0x2fff2f6e,0xae1fadfe,0xae3fafbc,0xaf02aee9,0x2d272f30,0xae5eae3f,0x9fd9ab5e,0xaf30af1a,0xa44e2875,
0xae99ae7c,0x2d962993,0xaf5aaf46,0xae99ac32,0xad00ad72,0xa17eac32,0xa17ea515,0xabb79cb6,0xac07ac87,0x2dfe29f1,0x1fd99648,0xafedae99,
0xa9f1ab05,0x2fd42fbc,0x26a1244e,0xad96af91,0xa765a8d5,0x2aaa2e3f,0x29932875,0x2515a8d5,0x2e992dfe,0x30002ee9,0x2f6e2fbc,0xac87af30,
0x2f802f1a,0x2c322f02,0x2e7c2f02,0x2aaaa17e,0x2ff42fc9,0xab5e1cb6,0x2d272ddc,0x2ff42e7c,0x2fed3000,0xaffcaeb5,0x2b052c5d,0x2cd82f5a,
0x2c072d27,0x9fd92bb7,0xadfead00,0x2fed2e1f,0x25db2993,0xaf6eacb0,0xaf6eaed0,0x2c5d2f46,0xa5151648,0xaddcafdd,0xafffafd4,0xac321648,
0xabb7a934,0x28d5a814,0xafa0afed,0xaff4af30,0xaf30ae3f,0xafedaf1a,0xa814ab5e,0xa9342875,0xb000afc9,0xa6a1addc,0x25db9cb6,0xb000ae7c,
0xaf46afd4,0x2ed02a4e,0x2cb02a4e,0xa993ae99,0xad27ae5e,0x2e3f2ffc,0x2f022dfe,0x2e1f2814,0xa9f1acd8,0x26a1ab05,0x2fd42ffc,0xad96afed,
0x2515a30e,0x2fff2e1f,0x2ddc2f1a,0x2c32a30e,0x2d272aaa,0x28752e7c,0x28752c32,0x2fa02f80,0x2f912e99,0xaee9a9f1,0xa8141648,0x9fd92c87,
0x2fa02e7c,0x2faf2f46,0xad00a993,0x2fa02c32,0x2f913000,0xa44e2c5d,0xafbcaeb5,0x2b052f5a,0x2c872e5e,0xb000adfe,0xaf6eaffc,0xae99a814,
0x9cb62875,0xa515ae1f,0xac32ae1f,0xad72aff4,0x27652c87,0xa9932a4e,0xaaaaadba,0xa5152c87,0xabb7a44e,0xafa0af30,0x28d59fd9,0xaff4ae5e,
0xaf91ae1f,0x2814abb7,0x2ee92d00,0x1fd9ad27,0xaf5aafff,0x2fd42ed0,0x2fd42fe6,0x30002ddc,0xaf46af6e,0xac32afdd,0xae7cafdd,0x29933000,
0x2b5ea934,0x2faf2cd8,0x2d00a44e,0xaf1aadfe,0x2ee92faf,0xaf30217e,0x2dfe2ff8,0x2fbc230e,0xac5d2765,0x29f1addc,0xad961cb6,0xac5d2cb0,
0x2bb7a993,0x2f1aa515,0x2f1a2765,0xaff4aaaa,0x2e5e2fd4,0xab052dba,0x29342f6e,0x2ee9a6a1,0xadba1fd9,0xa5dbafed,0xafddac07,0xaa4e2dfe,
0xacb0aff8,0x2ddc2f02,0x9cb6ae3f,0xa765aff8,0x2eb52f91,0x2a4e2fed,0x16482e5e,0x2c5dad4d,0xaddc217e,0xae7cae3f,0xafc9ae3f,0x9cb62fa0,
0xabb7afe6,0x2ff82993,0x2b5eaaaa,0xabb7afc9,0x2fbc2a4e,0xaf3025db,0x2dfe2fdd,0x2ee92dba,0xacd828d5,0xaf91230e,0xaf30af02,0x2c072fa0,
0xac5dafff,0x2dbaac32,0x2dbaa515,0xae99addc,0x2fc929f1,0xa9932eb5,0x2aaa2fdd,0x2fe629f1,0xa30e2dfe,0xa17eafed,0xaff8ac07,0xafaf1fd9,
0xadfeafaf,0xa814aff8,0x2e5ea17e,0xaffca30e,0x2f5a2515,0x2c872f46,0x26a12f80,0x2f5aa765,0x9cb62e99,0xae7cadba,0xafc9adba,0xaddc2c5d,
0xaf1aaee9,0x2faf2b05,0x2d00a934,0x2b5eae5e,0x2dbaa814,0x2fdd9fd9,0x25db2f91,0x2a4eaee9,0x27652faf,0xaf4628d5,0xaf80ae1f,0xa5152faf,
0xafa0addc,0x2e3fac32,0x2e3fa515,0xa17eafff,0x2dfea6a1,0xacd82dba,0x244e2f6e,0x29342fd4,0x2d272fc9,0x230e2fff,0xafafad72,0x2d272e7c,
0xaffcaa4e,0xa814afdd,0x2e5ea5db,0xadfeadba,0x2c5dac07,0x2a4e2f91,0x16482f30,0x2eb52cd8,0x29932ff4,0xac32af1a,0xae7caf1a,0xaf46abb7,
0xae7c26a1,0xafff1648,0x2d72aa4e,0xafc926a1,0x230eaee9,0x2ff89fd9,0x217e2f91,0x2fafa814,0x2d4d2fa0,0xafed230e,0xae5eaf02,0xaf9128d5,
0xb000aaaa,0x2fdda515,0x2fdd2765,0x2f6ea993,0x1cb6b000,0x2cb0afd4,0x2765afd4,0xaddc2f5a,0xa17e2ffc,0xaff42c07,0xa8752fbc,0x2ff8a934,
0x244eaff4,0x2dfe28d5,0x2934afa0,0xacd8abb7,0xa5db2fe6,0x9648af46,0xa9f12f80,0xa5db2fc9,0x2ff41cb6,0x2e1f2765,0x2e1f2cb0,0xa875addc,
0xafbca5db,0x1fd9af5a,0xad4dad96,0xacd82fdd,0x2f5a2934,0xaeb52ee9,0x2c5d2e5e,0x3000ab05,0xaed0ab5e,0x2f80a30e,0xaaaaaf02,0xacb0ab5e,
0xa5db2ffc,0xad962fbc,0xaf5a2c07,0x2fdda934,0x2aaaafa0,0x2fc9a875,0x2fe6a875,0xa993ad27,0xad002ed0,0xa8d5ad72,0xaff81cb6,0xad002fe6,
0x2e5ead96,0xad4d2fd4,0x2f9126a1,0x2feda9f1,0xafbca17e,0xad4da875,0x1fd9aff4,0xacd82ff8,0x2e992aaa,0xaa4e2fe6,0xaa4e2fc9,0x2fd4a993,
0xacb0ad96,0x2fffac87,0x2d72aeb5,0xa765ad96,0x28752f30,0xab5eac07,0xaf1a2cd8,0xae3f2f91,0x2934aff4,0x2e5eafa0,0x2ee928d5,0xab05abb7,
0xad962ed0,0xaeb51cb6,0xac87ad72,0xad962fe6,0x2f80ac5d,0xa7652f6e,0x25152f6e,0x2f46a5db,0xaff8244e,0x2ff4ad4d,0x2875affc,0x217eaee9,
0x2f5a244e,0x2c5d2934,0xaeb52dfe,0x3000acd8,0xacb0ad00,0x2d72aff8,0x2fffa8d5,0xa765ad00,0x217e2f80,0xaf022515,0xaf02a765,0xaf1a2f46,
0x2b05afdd,0xa8142f5a,0x2c072d96,0x2d4d25db,0xab5e2fe6,0xaf022f80,0xa30eaf46,0xab5e2fc9,0x2f30ad96,0x2cd826a1,0xac072fd4,0x2f91a9f1,
0xafdd244e,0x2d96affc,0x2f5aad4d,0x25dbaee9,0x2d722bb7,0xae7c217e,0xafc9217e,0xafff2d00,0xaed0a5db,0xaaaaa9f1,0x2f809648,0xacb0a5db,
0x28752e5e,0xaf1a2f91,0xab5ead4d,0xae3f2fed,0x2b05aff8,0x2c072875,0xa8142ff4,0x2d4d217e,0xaf6e2d72,0x2eb5afc9,0x2eb5ae7c,0x2dbaafff,
0x2f80af5a,0x2fc9ae99,0x2fe6ae99,0xaf462d96,0xa8d5ab05,0x2f02afed,0xa30eacd8,0xafa02ffc,0xafbc2f02,0x2934ad27,0xaffc2e1f,0xac072e3f,
0x26a12c32,0xaa4e1cb6,0x16482d72,0x26a12515,0x28752aaa,0xa8d52cb0,0xa8d52ed0,0x2e3faf80,0x2fedaeb5,0x29349648,0x2f30aa4e,0x2814ac5d,
0x1648ad4d,0x2e99acd8,0x2c87afbc,0xa9f11fd9,0xafe62d27,0x2fffafaf,0xaddc230e,0xaed02d27,0xafd42f30,0xaf6e2e5e,0xadba244e,0x26a11fd9,
0x9cb62d27,0xafe62ff4,0xaed02ff4,0x2d72ab5e,0x2fafacb0,0xae1f2f46,0x28d52993,0x2fafaed0,0x2c07af6e,0xa9342c87,0x2ffcae99,0x2fbcb000,
0xa44eab5e,0x2b05ad00,0x2f91afaf,0xafbc2f1a,0xafd42d72,0x1648a765,0x1648acb0,0xafdd2fff,0xac322f5a,0xaaaa26a1,0xaf802c87,0xae7c2f5a,
0x2d009fd9,0xae1f2cd8,0xad272fbc,0xabb72d4d,0x2ffcaf02,0x2ee9ae1f,0xa44e2d27,0x2d4dae3f,0x29f1ae7c,0x2fddaf80,0x2eb5aaaa,0x29f1ac32,
0xad7225db,0x2fe6b000,0x2ed0b000,0x1cb6a6a1,0xafa02fbc,0x2f02af91,0xa30eab05,0xa8d5244e,0x96482c07,0xac872d4d,0xae992b05,0x29f1a814,
0x2ed0abb7,0xa9932b5e,0xaf462ff8,0x2cb0abb7,0x2f1aafff,0xa30e2765,0xa30e2cb0,0x2e1fad72,0x1fd9ac5d,0x244e9648,0x2e5eaa4e,0x2f30aeb5,
0xaff82ed0,0xae3f2ddc,0x2f02afff,0xaff82fe6,0xad4d2f6e,0xaee92e99,0x244eac87,0xaffc3000,0x26a12814,0xaf6e2f30,0xadba2934,0xafd42fed,
0x2f46ad00,0xafc92fa0,0xafe62fa0,0xaf802faf,0x2515ac5d,0x2d72ad96,0x1cb629f1,0x2c32ac5d,0xad002814,0x2d27ad4d,0x2e1fab05,0x2bb7ac07,
0xaffc2f1a,0x2cd8ad00,0x2fedafaf,0x2b05ab5e,0xadba2f80,0x2c87acb0,0x2c87aed0,0x2a4eaaaa,0xaf80af6e,0xafc9afdd,0xafe6afdd,0x2f463000,
0xafa0af91,0xabb7ae5e,0xaff4afed,0x28d52d4d,0xafbcafaf,0x2934a17e,0xaffcaff8,0xac07a30e,0xafd4afc9,0x2f5a2d72,0xb000afff,0xafd4ae7c,
0x2bb72aaa,0x2f1a2cb0,0x2f1a2ed0,0xaff4af80,0x2cd82c5d,0x2f303000,0x2f912f5a,0xac07aeb5,0x2dba2d4d,0x25db2cd8,0x2fdd2fbc,0x2a4e9fd9,
0x2e7c2e1f,0xad72a875,0x2fff2ff4,0x2fc92e1f,0x26a12934,0xa9f1244e,0xad96acd8,0x2fd42dfe,0x9cb6217e,0xafe6ae3f,0xaed0ae3f,0x2d722fa0,
0xa875a515,0xad27af80,0xafa0af46,0xa8752765,0xac07aa4e,0x2934a5db,0xaffcafdd,0xafbcadba,0xae5eaf1a,0xa934ae3f,0x2b052875,0xaee9ab5e,
0xac5dad72,0x2dba2765,0x2dba2cb0,0xae99afff,0xa765aa4e,0x2f802fd4,0x2f462e99,0x2515aa4e,0x230e9fd9,0x217e2cd8,0x2ff82fbc,0x2faf2d4d,
0x2ffc2faf,0x2ee92ff8,0xa44e217e,0x2d4d230e,0x2f6e2fe6,0xa5db2aaa,0xac5da993,0x2f6e2fc9,0x2d722e99,0xafe6adba,0xaed0adba,0x9cb62c5d,
0x28d52c07,0xabb7af30,0xaff4af91,0xafa0acd8,0xadbaac07,0xafddad4d,0xa5dbab05,0xaa4e2814,0xafc9af02,0xaaaaaf1a,0x2993217e,0xafe6af02,
0xafa0afff,0x2e3f2765,0x2e3f2cb0,0xa17ead72,0xad4daeb5,0x2e5e3000,0x2fed2f5a,0x2f912c5d,0x217ea765,0x2d009cb6,0x2bb72ddc,0x217eacb0,
0x2d4d2a4e,0x2ee92fdd,0xa44e25db,0x2ffc2dba,0x2fd42ee9,0xa9f12934,0xad96ab05,0x26a12e5e,0x2f462ff4,0xafc9af1a,0xafe6af1a,0xaf80abb7,
0x2cb02eb5,0x1cb62dba,0xaddcaf6e,0x27652eb5,0xa30e2814,0xaff8ad4d,0xa17eab05,0xafafac07,0xadfeab5e,0xa44eae3f,0x2cd82875,0xa934af1a,
0xb000af80,0x2fdd2cb0,0x2fdd2ed0,0x2f6e2aaa,0xad72b000,0xa515afd4,0xac32afd4,0x9cb62f5a,0x2e1f1fd9,0x2e3f2ee9,0x2f022814,0xad27af91,
0x2cd82ff4,0xaffca8d5,0x2b052fa0,0x2fed2bb7,0xae99a515,0x2d96aaaa,0xaf5aa993,0xae992765,0x2ff42ddc,0x2e1f2ed0,0x2e1f2fe6,0xa875afff,
0xa8142c87,0xaffca9f1,0xadfe1648,0x2e5e2e99,0xaf5aaf30,0x2eb5a814,0xac5dafed,0xb000a934,0x2c32a8d5,0xa9932e3f,0x2f462875,0x2e7ca8d5,
0xae999fd9,0xb000a814,0xaf6eaee9,0x2c872f91,0xa993afa0,0x2ed0a875,0x2cb0a875,0xaf46ad27,0x2ff42c32,0xab5e2ddc,0x2d272fff,0x2ff42515,
0xa44e2d96,0x9fd9afd4,0xaf30a6a1,0xae5e29f1,0x2814ad27,0x2dfeabb7,0x2ffc2d00,0xae5eae1f,0x2e992f80,0xaa4e2e7c,0xaa4e2c32,0x2fd42aaa,
0xae7c1648,0x9cb6afdd,0xaddcafd4,0xafc91648,0xa875af91,0x2b5e2fbc,0x2f1a244e,0x2e3fab05,0x2b052ff4,0xa44e2fa0,0xafbca8d5,0x2f912bb7,
0xb000ac32,0xa6a1afff,0x25dbaddc,0xb000a515,0x2aaaac5d,0x2c322f6e,0x2e7c2f6e,0x2f80a5db,0x2d272fed,0xae3fadfe,0xaf029fd9,0xae1f2c07,
0xaf5aae5e,0xac5daf30,0x2eb59fd9,0xb000a44e,0x2e7ca30e,0x2ddc2e1f,0x1cb62f1a,0x2fc9a30e,0x217e2f46,0xaf02acb0,0xaf02aed0,0xaf1a2993,
0xaf30ae99,0x2fbc29f1,0x2ee99648,0x2dfeac87,0x2fa02515,0x2faf2993,0xad002aaa,0x2fa0a765,0xa9342d96,0xafeda6a1,0xa814afd4,0xaf3029f1,
0xac87afed,0x30001fd9,0x2f6e2dfe,0x2e99ac07,0x2fff2bb7,0xafe6217e,0xaed0217e,0xaddc2d00,0xac322c87,0xaf462a4e,0x2993adba,0xae7c2c87,
0xa875afed,0x2f1aab05,0x2b5e2ffc,0x2e3facd8,0x2f302e1f,0xaee92bb7,0xafbcad00,0xadfe2d27,0xaf6e9cb6,0x2eb5ac32,0x2eb5a515,0x2dbaad72,
0x2aaaaf5a,0x2ed0ae99,0x2cb0ae99,0xaf802d96,0xab5e2f30,0xafaf244e,0xad002e5e,0x2f1a1fd9,0x2c07af02,0x2b052d27,0x2d4dae1f,0xa814ae3f,
0xac5d2ed0,0x29f1afff,0xad962ddc,0xac5d2fe6,0x28752f80,0xa8d52fe6,0xa8d52fc9,0x2e3faf46,0xa44eafd4,0x2f91adba,0x2b05af6e,0xafbc26a1,
0x96482ffc,0xae99a44e,0xac872ee9,0x29f12d4d,0x2515aff8,0x1cb62f02,0x2d72ae3f,0x2c32aff8,0xaeb5ab05,0xaa4eacd8,0x9648afed,0xac5d2ffc,
0x2d722d27,0xacb02ff4,0xa7652ff4,0x2fffab5e,0xabb7ae7c,0x2ff8aaaa,0x2b5eaf80,0xabb7ac32,0x28142f6e,0xab05ac87,0xad4d2e99,0xac073000,
0x2feda8d5,0x2f30a30e,0x29342f02,0x2814afa0,0xafd49cb6,0x1648aed0,0x1648afe6,0xafdd2d72,0x2ed029f1,0xaf462eb5,0xa9932fdd,0x2cb029f1,
0xad00ad4d,0x2e1f244e,0x2d27aee9,0x2bb7affc,0xad4d2f02,0xafbc2e1f,0xacd8ad27,0x1fd92e3f,0x2f5aacb0,0x2c872993,0x26a12f46,0x2f5aaed0,
0xafff25db,0x2cb0b000,0x2765b000,0xad72a6a1,0x2f1a2814,0xafaf2934,0xad002f30,0xab5e2fed,0x1648afbc,0x2c87affc,0x2e992934,0xa9f1ac07,
0xac322faf,0xaf8028d5,0xaaaaae1f,0xae7c2faf,0x2f1aad72,0xa30e2ed0,0xa30e2fe6,0x2e1f1cb6,0xaffc26a1,0x2fedadba,0x2cd8af6e,0x2b05afd4,
0x2d272c32,0x230e2d72,0xafaf1cb6,0x2d272515,0x9fd9af6e,0x2fbcae99,0x2cd82c87,0x2d4db000,0xac5d2fbc,0xaa4eab05,0x9648af91,0xaeb5244e,
0x2f80ad00,0xaed02fa0,0xacb02fa0,0xaaaa2faf,0xafe626a1,0xaddc1648,0x2fffaa4e,0xaed026a1,0x2d002c07,0xad272ffc,0xae1fa934,0xabb72fbc,
0x1fd9afa0,0x2e5ea30e,0x244e2f02,0x2f30a8d5,0xadba2f46,0x2c87afe6,0x2c87afc9,0x2a4eaf80,0x2fffad96,0x2e7cac5d,0x2fc9ac5d,0xad7229f1,
0x217eadfe,0x2ff4afbc,0x2875aee9,0xaff82f30,0xafed2d00,0x2d4daf1a,0xaf912b5e,0xae5e2faf,0xa5db2e7c,0x9648a993,0xa9f12f46,0xa5db2c32,
0xae3f2fff,0xaff82fc9,0xaff82e7c,0x2f02ad72,0x2c0725db,0xadfe2f5a,0x9fd92d96,0x2fedafdd,0x2f6eaf91,0xa6a12c07,0x2fd4acd8,0x2dbaaf30,
0xa765ab5e,0x2aaaa30e,0x2993af02,0x2515ab5e,0x25dbadfe,0x2d96aee9,0x2f5aafbc,0xafdd2f30,0xaf462b5e,0x2765abb7,0xa515abb7,0xaf802ff8,
0xad002fc9,0xa8d51cb6,0xaff82ddc,0xad002e7c,0x2cd81648,0xadfe2c5d,0xa9342eb5,0xa44e2a4e,0x2c07217e,0x9fd92875,0xadfe2ff4,0x2fedaff8,
0x2fddaf46,0x29f1a515,0x29f12765,0x2eb5af80,0x2515ad96,0x2ddcac87,0x2fffaeb5,0x2c32ad96,0xaf022b05,0x2fa0aee9,0x28d5ae5e,0x230ea934,
0xaf912d00,0xacd82b5e,0x2c07af1a,0xaf302faf,0xad962fc9,0xaeb52ddc,0xac871cb6,0xad962e7c,0x299326a1,0xafc92f5a,0xafe62f5a,0xaaaa2c87,
0x2ff8ae5e,0xaff42ffc,0xa8752dfe,0xa17e2814,0x2f6eafed,0x2fd4af91,0xa6a12d4d,0x2dbaae5e,0x2515ad00,0x2fffaff8,0x2ddca8d5,0x2c32ad00,
0xae1f2993,0x2fafafe6,0x2fafafc9,0x28d5aaaa,0xaf912fdd,0x2ee9af5a,0x2814ad96,0x1fd9a5db,0xab5e2e7c,0xaf022f46,0xa30ea993,0xab5e2c32,
0x2b051648,0xae5e2eb5,0xaee92c5d,0xa9342a4e,0x2fddae5e,0xad962dfe,0xaf5a2ffc,0xa5db2814,0x2ddcafaf,0xacb02d27,0xa7652d27,0x9cb6230e,
0xa765a5db,0x2993a9f1,0x2aaa9648,0x2515a5db,0xaf022cd8,0x28d5a934,0x2fa0adfe,0x230ea44e,0xaf912ff8,0x2814a875,0x2ee9aff4,0x1fd9a17e,
0xaa4e2ddc,0x26a1a765,0x26a1acb0,0x16489cb6,0x9d7f9e49,0xaddcaeb3,0x12480000,0x22ad0000,0x9bdb9cb6,0xac2ead04,0x18b61648,0x290226ad,
0x98b69a49,0xa902aaaf,0x1bdb1a49,0x2c2e2aaf,0x92489648,0xa2ada6ad,0x1d7f1cb6,0x2ddc2d04,0xa420a4b7,0xae8daf7f,0x18b60000,0x23760000,
0xa1e4a312,0xacacad9c,0x1f121cb6,0x29992777,0x9f12a0b6,0xa999ab78,0x21e420b6,0x2cac2b78,0x98b69cb6,0xa376a777,0x24202312,0x2e8d2d9c,
0xa6e0a7db,0xaf3fb025,0x1bdb0000,0x24200000,0xa4e9a5e4,0xad2aae34,0x21e41fdb,0x2a312820,0xa1e4a3db,0xaa31ac21,0x24e923db,0x2d2a2c21,
0x9bdb9fdb,0xa420a820,0x26e025e4,0x2f3f2e34,0xa8d0a980,0xaff2b08c,0x1d7f0000,0x24840000,0xa6e0a820,0xada9aecd,0x2420217f,0x2ac82885,
0xa420a580,0xaac8ac86,0x26e02580,0x2da92c86,0x9d7fa17f,0xa484a885,0x28d02820,0x2ff22ecd,0xaa31ab13,0xb052b0f3,0x1f120000,0x24e90000,
0xa86ba94e,0xae28af65,0x254d2312,0x2b5f28e9,0xa54da712,0xab5faceb,0x286b2712,0x2e282ceb,0x9f12a312,0xa4e9a8e9,0x2a31294e,0x30522f65,
0xab91ac54,0xb0acb15a,0x20520000,0x254d0000,0xa967aa7c,0xaea7affe,0x267b2452,0x2bf6294e,0xa67ba852,0xabf6ad50,0x29672852,0x2ea72d50,
0xa052a452,0xa54da94e,0x2b912a7c,0x30ac2ffe,0xac79ad1e,0xb106b1c1,0x211b0000,0x25b20000,0xaa63abab,0xaf26b04c,0x27a9251b,0x2c4729b3,
0xa7a9a91c,0xac47adb6,0x2a63291c,0x2f262db6,0xa11ba51b,0xa5b2a9b3,0x2c792bab,0x3106304c,0xad2aade8,0xb160b229,0x21e40000,0x26170000,
0xab5fac6d,0xafa5b099,0x286b25e4,0x2c932a17,0xa86ba9e5,0xac93ae1b,0x2b5f29e5,0x2fa52e1b,0xa1e4a5e4,0xa617aa17,0x2d2a2c6d,0x31603099,
0xb1bbb292,0xb44fb4f6,0x267b0000,0x28d00000,0xb012b0e6,0xb216b357,0x2cde2a7c,0x2f3f2cd2,0xacdeae80,0xaf3fb0d9,0x30122e80,0x321630d9,
0xa67baa7c,0xa8d0acd2,0x31bb30e6,0x344f3357,0xb216b2fb,0xb47eb52d,0x26e00000,0x29020000,0xb052b133,0xb257b3a7,0x2d2a2ae1,0x2f8c2d04,
0xad2aaee6,0xaf8cb10c,0x30522ee6,0x3257310c,0xa6e0aae1,0xa902ad04,0x32163133,0x347e33a7,0xb271b364,0xb4aeb565,0x27440000,0x29350000,
0xb092b181,0xb298b3f7,0x2d762b46,0x2fd82d37,0xad76af4c,0xafd8b140,0x30922f4c,0x32983140,0xa744ab46,0xa935ad37,0x32713181,0x34ae33f7,
0xb2cdb3cf,0xb4deb59d,0x27a90000,0x29670000,0xb0d2b1ce,0xb2dab423,0x2dc22bab,0x30122d6a,0xadc2afb2,0xb012b174,0x30d22fb2,0x32da3174,
0xa7a9abab,0xa967ad6a,0x32cd31ce,0x34de3423,0xb329b41d,0xb50eb5d6,0x28070000,0x29990000,0xb113b21c,0xb31cb44c,0x2e0e2c08,0x30392d9c,
0xae0eb00c,0xb039b1a7,0x3113300c,0x331c31a7,0xa807ac08,0xa999ad9c,0x3329321c,0x350e344c,0xb386b453,0xb53fb60f,0x28390000,0x29cc0000,
0xb153b26b,0xb35eb474,0x2e5a2c3a,0x305f2dcf,0xae5ab03f,0xb05fb1db,0x3153303f,0x335e31db,0xa839ac3a,0xa9ccadcf,0x3386326b,0x353f3474,
0xb3e3b489,0xb570b649,0x286b0000,0x29fe0000,0xb194b2b9,0xb3a0b49d,0x2ea72c6d,0x30852e02,0xaea7b072,0xb085b20f,0x31943072,0x33a0320f,
0xa86bac6d,0xa9feae02,0x33e332b9,0x3570349d,0xb420b4bf,0xb5a1b683,0x289e0000,0x2a310000,0xb1d5b308,0xb3e3b4c6,0x2ef32c9f,0x30ac2e34,
0xaef3b0a5,0xb0acb243,0x31d530a5,0x33e33243,0xa89eac9f,0xaa31ae34,0x34203308,0x35a134c6,0xb5d2b6be,0xb76fb857,0x2a630000,0x2bf60000,
0xb413b4ef,0xb523b642,0x30d22e67,0x32092ffe,0xb0d2b278,0xb209b40f,0x34133278,0x3523340f,0xaa63ae67,0xabf6affe,0x35d234ef,0x376f3642,
0xb604b6fa,0xb7a5b878,0x2a950000,0x2c140000,0xb434b519,0xb546b66d,0x30f92e9a,0x32303019,0xb0f9b2ac,0xb230b42a,0x343432ac,0x3546342a,
0xaa95ae9a,0xac14b019,0x36043519,0x37a5366d,0xb637b736,0xb7dbb899,0x2ac80000,0x2c2e0000,0xb456b542,0xb569b699,0x31202ecd,0x32573032,
0xb120b2e1,0xb257b445,0x345632e1,0x35693445,0xaac8aecd,0xac2eb032,0x36373542,0x37db3699,0xb66ab773,0xb809b8bb,0x2afa0000,0x2c470000,
0xb478b56c,0xb58cb6c6,0x31462f00,0x327e304c,0xb146b315,0xb27eb460,0x34783315,0x358c3460,0xaafaaf00,0xac47b04c,0x366a356c,0x380936c6,
0xb69db7b0,0xb825b8dd,0x2b2d0000,0x2c600000,0xb49ab596,0xb5afb6f2,0x316d2f32,0x32a53065,0xb16db34a,0xb2a5b47b,0x349a334a,0x35af347b,
0xab2daf32,0xac60b065,0x369d3596,0x382536f2,0xb6d1b7ee,0xb841b8ff,0x2b5f0000,0x2c790000,0xb4bcb5c1,0xb5d2b71f,0x31942f65,0x32cd307f,
0xb194b37f,0xb2cdb496,0x34bc337f,0x35d23496,0xab5faf65,0xac79b07f,0x36d135c1,0x3841371f,0xb705b817,0xb85db923,0x2b910000,0x2c930000,
0xb4deb5eb,0xb5f6b74d,0x31bb2f98,0x32f43099,0xb1bbb3b4,0xb2f4b4b1,0x34de33b4,0x35f634b1,0xab91af98,0xac93b099,0x370535eb,0x385d374d,
0xb73ab837,0xb87ab946,0x2bc40000,0x2cac0000,0xb500b616,0xb61ab77a,0x31e22fcb,0x331c30b2,0xb1e2b3e9,0xb31cb4cd,0x350033e9,0x361a34cd,
0xabc4afcb,0xacacb0b2,0x373a3616,0x387a377a,0xb897b96b,0xb98dbaa6,0x2cc50000,0x2d900000,0xb63eb7a8,0xb767b895,0x334330cc,0x3442319a,
0xb343b4e8,0xb442b5c8,0x363e34e8,0x376735c8,0xacc5b0cc,0xad90b19a,0x389737a8,0x398d3895,0xb8b4b990,0xb9aebad1,0x2cde0000,0x2da90000,
0xb662b7d7,0xb78db8ae,0x336b30e6,0x345631b4,0xb36bb504,0xb456b5e4,0x36623504,0x378d35e4,0xacdeb0e6,0xada9b1b4,0x38b437d7,0x39ae38ae,
0xb8d2b9b5,0xb9cfbafd,0x2cf80000,0x2dc20000,0xb687b803,0xb7b4b8c7,0x339330ff,0x346a31ce,0xb393b51f,0xb46ab601,0x3687351f,0x37b43601,
0xacf8b0ff,0xadc2b1ce,0x38d23803,0x39cf38c7,0xb8f0b9dc,0xb9f1bb29,0x2d110000,0x2ddc0000,0xb6acb81b,0xb7dbb8e1,0x33bb3119,0x347e31e8,
0xb3bbb53b,0xb47eb61e,0x36ac353b,0x37db361e,0xad11b119,0xaddcb1e8,0x38f0381b,0x39f138e1,0xb90fba02,0xba14bb57,0x2d2a0000,0x2df50000,
0xb6d1b833,0xb801b8fb,0x33e33133,0x34933202,0xb3e3b557,0xb493b63a,0x36d13557,0x3801363a,0xad2ab133,0xadf5b202,0x390f3833,0x3a1438fb,
0xb92eba2a,0xba37bb86,0x2d440000,0x2e0e0000,0xb6f6b84b,0xb815b915,0x3405314d,0x34a7321c,0xb405b573,0xb4a7b657,0x36f63573,0x38153657,
0xad44b14d,0xae0eb21c,0x392e384b,0x3a373915,0xb94dba53,0xba5abbb6,0x2d5d0000,0x2e280000,0xb71bb863,0xb829b930,0x34193167,0x34bc3236,
0xb419b58f,0xb4bcb675,0x371b358f,0x38293675,0xad5db167,0xae28b236,0x394d3863,0x3a5a3930,0xb96dba7c,0xba7ebbe7,0x2d760000,0x2e410000,
0xb741b87c,0xb83db94b,0x342e3181,0x34d03250,0xb42eb5ab,0xb4d0b692,0x374135ab,0x383d3692,0xad76b181,0xae41b250,0x396d387c,0x3a7e394b,
0xa17fa248,0xb1cfb2a1,0x16480000,0x26ad0000,0x9fdba0b6,0xb029b0fd,0x1cb61a48,0x2d002aac,0x9cb69e48,0xad00aeaa,0x1fdb1e48,0x30292eaa,
0x96489a48,0xa6adaaac,0x217f20b6,0x31cf30fd,0xa81fa8b6,0xb27cb365,0x1cb60000,0x27760000,0xa5e4a711,0xb0a6b191,0x231120b6,0x2d972b75,
0xa311a4b6,0xad97af72,0x25e424b6,0x30a62f72,0x9cb6a0b6,0xa776ab75,0x281f2711,0x327c3191,0xaadeabd9,0xb328b414,0x1fdb0000,0x281f0000,
0xa8e8a9e3,0xb122b226,0x25e423db,0x2e2d2c1f,0xa5e4a7da,0xae2db01d,0x28e827da,0x3122301d,0x9fdba3db,0xa81fac1f,0x2ade29e3,0x33283226,
0xaccead7e,0xb3d3b475,0x217f0000,0x28840000,0xaadeac1f,0xb19eb2b9,0x281f257f,0x2ec32c83,0xa81fa97f,0xaec3b080,0x2ade297f,0x319e3080,
0xa17fa57f,0xa884ac83,0x2cce2c1f,0x33d332b9,0xae2daf0e,0xb43eb4d5,0x23110000,0x28e80000,0xac6aad4c,0xb219b34c,0x294d2711,0x2f592ce7,
0xa94dab11,0xaf59b0e4,0x2c6a2b11,0x321930e4,0xa311a711,0xa8e8ace7,0x2e2d2d4c,0x343e334c,0xaf8bb04e,0xb493b534,0x24520000,0x294d0000,
0xad65ae78,0xb294b3df,0x2a7a2852,0x2fef2d4c,0xaa7aac51,0xafefb147,0x2d652c51,0x32943147,0xa452a852,0xa94dad4c,0x2f8b2e78,0x349333df,
0xb074b115,0xb4e7b593,0x251b0000,0x29b10000,0xae5fafa4,0xb30fb438,0x2ba7291b,0x30422db0,0xaba7ad1a,0xb042b1aa,0x2e5f2d1a,0x330f31aa,
0xa51ba91b,0xa9b1adb0,0x30742fa4,0x34e73438,0xb122b1db,0xb53ab5f1,0x25e40000,0x2a160000,0xaf59b067,0xb389b481,0x2c6a29e3,0x308d2e14,
0xac6aade2,0xb08db20d,0x2f592de2,0x3389320d,0xa5e4a9e3,0xaa16ae14,0x31223067,0x353a3481,0xb58db64e,0xb805b887,0x2a7a0000,0x2cce0000,
0xb402b4c9,0xb5dfb6f9,0x30d72e78,0x332830cb,0xb0d7b26f,0xb328b4bd,0x3402326f,0x35df34bd,0xaa7aae78,0xacceb0cb,0x358d34c9,0x380536f9,
0xb5dfb6aa,0xb82ab8b0,0x2ade0000,0x2d000000,0xb43eb511,0xb61ab73d,0x31222edc,0x337130fd,0xb122b2d2,0xb371b4ed,0x343e32d2,0x361a34ed,
0xaadeaedc,0xad00b0fd,0x35df3511,0x382a373d,0xb631b705,0xb850b8d8,0x2b430000,0x2d330000,0xb47bb558,0xb654b780,0x316c2f40,0x33ba312e,
0xb16cb334,0xb3bab51d,0x347b3334,0x3654351d,0xab43af40,0xad33b12e,0x36313558,0x38503780,0xb682b75e,0xb874b900,0x2ba70000,0x2d650000,
0xb4b7b59f,0xb68db7c2,0x31b62fa4,0x34023160,0xb1b6b396,0xb402b54c,0x34b73396,0x368d354c,0xaba7afa4,0xad65b160,0x3682359f,0x387437c2,
0xb6d2b7b7,0xb899b927,0x2c060000,0x2d970000,0xb4f3b5e5,0xb6c6b802,0x32013004,0x34263191,0xb201b3f7,0xb426b57c,0x34f333f7,0x36c6357c,
0xac06b004,0xad97b191,0x36d235e5,0x38993802,0xb721b807,0xb8bcb94d,0x2c380000,0x2dc90000,0xb52fb62b,0xb6ffb822,0x324b3036,0x344b31c3,
0xb24bb42c,0xb44bb5ab,0x352f342c,0x36ff35ab,0xac38b036,0xadc9b1c3,0x3721362b,0x38bc3822,0xb76fb832,0xb8e0b972,0x2c6a0000,0x2dfb0000,
0xb56ab670,0xb737b842,0x32943067,0x346f31f4,0xb294b45d,0xb46fb5da,0x356a345d,0x373735da,0xac6ab067,0xadfbb1f4,0x376f3670,0x38e03842,
0xb7bdb85d,0xb902b996,0x2c9c0000,0x2e2d0000,0xb5a5b6b5,0xb76fb862,0x32de3099,0x34933226,0xb2deb48d,0xb493b608,0x35a5348d,0x376f3608,
0xac9cb099,0xae2db226,0x37bd36b5,0x39023862,0xb924b9ba,0xba1dbab5,0x2e5f0000,0x2fef0000,0xb7a6b881,0xb8a8b96d,0x34b73257,0x35d433df,
0xb4b7b637,0xb5d4b7a1,0x37a63637,0x38a837a1,0xae5fb257,0xafefb3df,0x39243881,0x3a1d396d,0xb946b9dc,0xba39bad0,0x2e910000,0x30100000,
0xb7ddb8a0,0xb8c1b989,0x34db3288,0x35f73408,0xb4dbb665,0xb5f7b7cd,0x37dd3665,0x38c137cd,0xae91b288,0xb010b408,0x394638a0,0x3a393989,
0xb966b9fe,0xba54bae9,0x2ec30000,0x30290000,0xb80ab8bf,0xb8dbb9a4,0x34ff32b9,0x361a3420,0xb4ffb693,0xb61ab7f9,0x380a3693,0x38db37f9,
0xaec3b2b9,0xb029b420,0x396638bf,0x3a5439a4,0xb986ba1f,0xba6fbb02,0x2ef50000,0x30420000,0xb825b8dd,0xb8f3b9be,0x352332ea,0x363c3438,
0xb523b6c1,0xb63cb812,0x382536c1,0x38f33812,0xaef5b2ea,0xb042b438,0x398638dd,0x3a6f39be,0xb9a6ba3f,0xba89bb1a,0x2f270000,0x305b0000,
0xb840b8fb,0xb90cb9d8,0x3546331b,0x365f3451,0xb546b6ee,0xb65fb828,0x384036ee,0x390c3828,0xaf27b31b,0xb05bb451,0x39a638fb,0x3a8939d8,
0xb9c5ba5e,0xbaa2bb30,0x2f590000,0x30740000,0xb85ab918,0xb924b9f2,0x356a334c,0x36823469,0xb56ab71b,0xb682b83d,0x385a371b,0x3924383d,
0xaf59b34c,0xb074b469,0x39c53918,0x3aa239f2,0xb9e3ba7c,0xbababb46,0x2f8b0000,0x308d0000,0xb874b935,0xb93cba0b,0x358d337d,0x36a43481,
0xb58db748,0xb6a4b852,0x38743748,0x393c3852,0xaf8bb37d,0xb08db481,0x39e33935,0x3aba3a0b,0xba00ba99,0xbad1bb5a,0x2fbd0000,0x30a60000,
0xb88eb951,0xb954ba23,0x35b133ae,0x36c63499,0xb5b1b775,0xb6c6b867,0x388e3775,0x39543867,0xafbdb3ae,0xb0a6b499,0x3a003951,0x3ad13a23,
0xbae8bb6e,0xbb7fbbdd,0x30be0000,0x31850000,0xb96bba3b,0xba19bae6,0x36e834b1,0x37f33570,0xb6e8b87c,0xb7f3b91d,0x396b387c,0x3a19391d,
0xb0beb4b1,0xb185b570,0x3ae83a3b,0x3b7f3ae6,0xbafebb80,0xbb8ebbe6,0x30d70000,0x319e0000,0xb982ba52,0xba2dbaf9,0x370a34c9,0x380a3587,
0xb70ab891,0xb80ab930,0x39823891,0x3a2d3930,0xb0d7b4c9,0xb19eb587,0x3afe3a52,0x3b8e3af9,0xbb13bb91,0xbb9cbbed,0x30f00000,0x31b60000,
0xb999ba69,0xba41bb0b,0x372c34e1,0x381a359f,0xb72cb8a6,0xb81ab943,0x399938a6,0x3a413943,0xb0f0b4e1,0xb1b6b59f,0x3b133a69,0x3b9c3b0b,
0xbb27bba0,0xbba9bbf4,0x31090000,0x31cf0000,0xb9afba7f,0xba54bb1d,0x374e34f9,0x382a35b6,0xb74eb8ba,0xb82ab956,0x39af38ba,0x3a543956,
0xb109b4f9,0xb1cfb5b6,0x3b273a7f,0x3ba93b1d,0xbb3abbaf,0xbbb5bbf8,0x31220000,0x31e80000,0xb9c5ba95,0xba67bb2e,0x376f3511,0x383a35ce,
0xb76fb8ce,0xb83ab969,0x39c538ce,0x3a673969,0xb122b511,0xb1e8b5ce,0x3b3a3a95,0x3bb53b2e,0xbb4cbbbc,0xbbc0bbfc,0x313b0000,0x32010000,
0xb9dabaaa,0xba7abb3e,0x37903529,0x384a35e5,0xb790b8e2,0xb84ab97b,0x39da38e2,0x3a7a397b,0xb13bb529,0xb201b5e5,0x3b4c3aaa,0x3bc03b3e,
0xbb5ebbc9,0xbbcbbbff,0x31530000,0x32190000,0xb9f0babf,0xba8cbb4e,0x37b23540,0x385a35fd,0xb7b2b8f6,0xb85ab98d,0x39f038f6,0x3a8c398d,
0xb153b540,0xb219b5fd,0x3b5e3abf,0x3bcb3b4e,0xbb6fbbd4,0xbbd4bc00,0x316c0000,0x32320000,0xba04bad3,0xba9ebb5d,0x37d23558,0x386a3614,
0xb7d2b909,0xb86ab99f,0x3a043909,0x3a9e399f,0xb16cb558,0xb232b614,0x3b6f3ad3,0x3bd43b5d,0x0,0x0,0x0,0x0,
0x2e1f0000,0x336431a8,0x33643400,0x2e1f31a8,0x31a80000,0x31a83400,0xb1a80000,0xb1a8b400,0x33640000,0xae1f31a8,0xae1fb400,0x336431a8,
0x34000000,0xb4000000,0x34000000,0xb4000000,0x33640000,0xae1fb1a8,0xae1f3400,0x3364b1a8,0x31a80000,0x31a8b400,0xb1a80000,0xb1a83400,
0x2e1f0000,0x3364b1a8,0x3364b400,0x2e1fb1a8,0x0,0x0,0x0,0x0,0xae1f0000,0xb36431a8,0xb3643400,0xae1f31a8,
0xb1a80000,0xb1a83400,0x31a80000,0x31a8b400,0xb3640000,0x2e1f31a8,0x2e1fb400,0xb36431a8,0xb4000000,0x34000000,0xb4000000,0x34000000,
0xb3640000,0x2e1fb1a8,0x2e1f3400,0xb364b1a8,0xb1a80000,0xb1a8b400,0x31a80000,0x31a83400,0xae1f0000,0xb364b1a8,0xb364b400,0xae1fb1a8,
0x0,0x0,0x0,0x0,0xae1f0000,0xb364b1a8,0xb364b400,0xae1fb1a8,0x31a80000,0x31a83400,0xb1a80000,0xb1a8b400,
0xb3640000,0x2e1fb1a8,0x2e1f3400,0xb364b1a8,0x34000000,0xb4000000,0x34000000,0xb4000000,0xb3640000,0x2e1f31a8,0x2e1fb400,0xb36431a8,
0x31a80000,0x31a8b400,0xb1a80000,0xb1a83400,0xae1f0000,0xb36431a8,0xb3643400,0xae1f31a8,0x0,0x0,0x0,0x0,
0x2e1f0000,0x3364b1a8,0x3364b400,0x2e1fb1a8,0xb1a80000,0xb1a83400,0x31a80000,0x31a8b400,0x33640000,0xae1fb1a8,0xae1f3400,0x3364b1a8,
0xb4000000,0x34000000,0xb4000000,0x34000000,0x33640000,0xae1f31a8,0xae1fb400,0x336431a8,0xb1a80000,0xb1a8b400,0x31a80000,0x31a83400,
0x2e1f0000,0x336431a8,0x33643400,0x2e1f31a8,0x34003400,0x34003400,0x34003400,0x34003400,0x33643400,0x2e1f31a8,0xae1f0000,0xb364b1a8,
0x31a83400,0xb1a80000,0xb1a8b400,0x31a80000,0x2e1f3400,0xb364b1a8,0x33640000,0xae1f31a8,0x3400,0xb400,0x3400,0xb400,
0xae1f3400,0x3364b1a8,0xb3640000,0x2e1f31a8,0xb1a83400,0x31a80000,0x31a8b400,0xb1a80000,0xb3643400,0xae1f31a8,0x2e1f0000,0x3364b1a8,
0xb4003400,0xb4003400,0xb4003400,0xb4003400,0xb3643400,0xae1f31a8,0x2e1f0000,0x3364b1a8,0xb1a83400,0x31a80000,0x31a8b400,0xb1a80000,
0xae1f3400,0x3364b1a8,0xb3640000,0x2e1f31a8,0x3400,0xb400,0x3400,0xb400,0x2e1f3400,0xb364b1a8,0x33640000,0xae1f31a8,
0x31a83400,0xb1a80000,0xb1a8b400,0x31a80000,0x33643400,0x2e1f31a8,0xae1f0000,0xb364b1a8,0x34003400,0x34003400,0x34003400,0x34003400,
0xb364b400,0xae1fb1a8,0x2e1f0000,0x336431a8,0x31a83400,0xb1a80000,0xb1a8b400,0x31a80000,0xae1fb400,0x336431a8,0xb3640000,0x2e1fb1a8,
0x3400,0xb400,0x3400,0xb400,0x2e1fb400,0xb36431a8,0x33640000,0xae1fb1a8,0xb1a83400,0x31a80000,0x31a8b400,0xb1a80000,
0x3364b400,0x2e1fb1a8,0xae1f0000,0xb36431a8,0xb4003400,0xb4003400,0xb4003400,0xb4003400,0x3364b400,0x2e1fb1a8,0xae1f0000,0xb36431a8,
0xb1a83400,0x31a80000,0x31a8b400,0xb1a80000,0x2e1fb400,0xb36431a8,0x33640000,0xae1fb1a8,0x3400,0xb400,0x3400,0xb400,
0xae1fb400,0x336431a8,0xb3640000,0x2e1fb1a8,0x31a83400,0xb1a80000,0xb1a8b400,0x31a80000,0xb364b400,0xae1fb1a8,0x2e1f0000,0x336431a8,
0x0,0x0,0x0,0x0,0xae1f0000,0xb364b1a8,0xb364b400,0xae1fb1a8,0xb1a80000,0xb1a8b400,0x31a80000,0x31a83400,
0xb3640000,0x2e1fb1a8,0x2e1f3400,0xb364b1a8,0xb4000000,0x34000000,0xb4000000,0x34000000,0xb3640000,0x2e1f31a8,0x2e1fb400,0xb36431a8,
0xb1a80000,0xb1a83400,0x31a80000,0x31a8b400,0xae1f0000,0xb36431a8,0xb3643400,0xae1f31a8,0x0,0x0,0x0,0x0,
0x2e1f0000,0x3364b1a8,0x3364b400,0x2e1fb1a8,0x31a80000,0x31a8b400,0xb1a80000,0xb1a83400,0x33640000,0xae1fb1a8,0xae1f3400,0x3364b1a8,
0x34000000,0xb4000000,0x34000000,0xb4000000,0x33640000,0xae1f31a8,0xae1fb400,0x336431a8,0x31a80000,0x31a83400,0xb1a80000,0xb1a8b400,
0x2e1f0000,0x336431a8,0x33643400,0x2e1f31a8,0x0,0x0,0x0,0x0,0x2e1f0000,0x336431a8,0x33643400,0x2e1f31a8,
0xb1a80000,0xb1a8b400,0x31a80000,0x31a83400,0x33640000,0xae1f31a8,0xae1fb400,0x336431a8,0xb4000000,0x34000000,0xb4000000,0x34000000,
0x33640000,0xae1fb1a8,0xae1f3400,0x3364b1a8,0xb1a80000,0xb1a83400,0x31a80000,0x31a8b400,0x2e1f0000,0x3364b1a8,0x3364b400,0x2e1fb1a8,
0x0,0x0,0x0,0x0,0xae1f0000,0xb36431a8,0xb3643400,0xae1f31a8,0x31a80000,0x31a8b400,0xb1a80000,0xb1a83400,
0xb3640000,0x2e1f31a8,0x2e1fb400,0xb36431a8,0x34000000,0xb4000000,0x34000000,0xb4000000,0xb3640000,0x2e1fb1a8,0x2e1f3400,0xb364b1a8,
0x31a80000,0x31a83400,0xb1a80000,0xb1a8b400,0xae1f0000,0xb364b1a8,0xb364b400,0xae1fb1a8,
};

typedef CUresult (*EncodeFn)(CUtensorMap*, CUtensorMapDataType, cuuint32_t, void*, const cuuint64_t*, const cuuint64_t*,
                             const cuuint32_t*, const cuuint32_t*, CUtensorMapInterleave, CUtensorMapSwizzle,
                             CUtensorMapL2promotion, CUtensorMapFloatOOBfill);

}

extern "C" void kernel_launch(void* const* d_in, const int* in_sizes, int n_in, void* d_out, int out_size) {
    Params p;
    p.x = (const __nv_bfloat16*)d_in[0];
    p.lar = (const __nv_bfloat16*)d_in[1];
    p.aim = (const __nv_bfloat16*)d_in[2];
    p.cr = (const __nv_bfloat16*)d_in[3];
    p.ci = (const __nv_bfloat16*)d_in[4];
    p.logdt = (const __nv_bfloat16*)d_in[5];
    p.dskip = (const __nv_bfloat16*)d_in[6];
    p.wr = (const __nv_bfloat16*)d_in[8];
    p.out = (__nv_bfloat16*)d_out;
    cudaGetSymbolAddress((void**)&p.sc, g_scratch);
    cudaGetSymbolAddress((void**)&p.tab, g_tab);

    void* fn = nullptr;
    cudaDriverEntryPointQueryResult qr;
    cudaGetDriverEntryPoint("cuTensorMapEncodeTiled", &fn, cudaEnableDefault, &qr);
    EncodeFn enc = (EncodeFn)fn;
    CUtensorMap tm_x, tm_g, tm_d;
    const cuuint32_t es[5] = {1, 1, 1, 1, 1};
    {
        const cuuint64_t gd[4] = {1024, 128, 8, 2}, gs[3] = {32768, 4096, 2048};
        const cuuint32_t bx[4] = {16, 64, 4, 1};
        enc(&tm_x, CU_TENSOR_MAP_DATA_TYPE_BFLOAT16, 4, d_in[0], gd, gs, bx, es, CU_TENSOR_MAP_INTERLEAVE_NONE,
            CU_TENSOR_MAP_SWIZZLE_NONE, CU_TENSOR_MAP_L2_PROMOTION_NONE, CU_TENSOR_MAP_FLOAT_OOB_FILL_NONE);
    }
    {
        char *wg = (char*)d_in[9], *wu = (char*)d_in[10];
        p.up_first = wu < wg;
        const cuuint64_t gd[3] = {3584, 1024, 2}, gs[2] = {7168, (cuuint64_t)(p.up_first ? wg - wu : wu - wg)};
        const cuuint32_t bx[3] = {64, 64, 2};
        enc(&tm_g, CU_TENSOR_MAP_DATA_TYPE_BFLOAT16, 3, p.up_first ? wu : wg, gd, gs, bx, es, CU_TENSOR_MAP_INTERLEAVE_NONE,
            CU_TENSOR_MAP_SWIZZLE_128B, (CUtensorMapL2promotion)GPROMO, CU_TENSOR_MAP_FLOAT_OOB_FILL_NONE);
    }
    {
        const cuuint64_t gd[3] = {64, 3584, 16}, gs[2] = {2048, 128};
        const cuuint32_t bx[3] = {64, 64, 2};
        enc(&tm_d, CU_TENSOR_MAP_DATA_TYPE_BFLOAT16, 3, d_in[11], gd, gs, bx, es, CU_TENSOR_MAP_INTERLEAVE_NONE,
            CU_TENSOR_MAP_SWIZZLE_128B, (CUtensorMapL2promotion)DPROMO, CU_TENSOR_MAP_FLOAT_OOB_FILL_NONE);
    }
    cudaFuncSetAttribute(fused_kernel, cudaFuncAttributeMaxDynamicSharedMemorySize, SM_TOTAL + 256);
    fused_kernel<<<128, NTHREADS, SM_TOTAL + 256>>>(p, tm_x, tm_g, tm_d);
}
```

```cpp
#include <cuda_runtime.h>
#include <cuda.h>
#include <cuda_bf16.h>
#include <cuda_fp16.h>
#include <stdint.h>

#define TG(i)
#define TS(i)
#define TSL(i)

#define PT(i)
#define TSW 0
#define SDELAY 1500
#define EDELAY 800
#define FILL 0x53211
#define STSLEEP 100
#define NPRE 8
#define IDEPTH2 3
#define ORDER 0x74365210
#define SDAT 5
#define REFILL 0x773
#define NREP 4
#define GPROMO 0
#define DPROMO 0
#define WPOL "evict_first"
#define FUSE 0
#define PDELAY 900
#define IDEPTH 3

namespace {

constexpr int NTHREADS = 512;
constexpr int SPIN_LIMIT = 1 << 16;

constexpr int SM_SLAB = 0;
constexpr int SM_RING = 32768;
constexpr int SUB     = 1088;
constexpr int SM_K    = SM_RING + 10 * 8192;
constexpr int SM_S    = SM_K + 32 * SUB;
constexpr int SM_U    = SM_S + 32 * SUB;
constexpr int SM_F2   = SM_U + 32 * SUB;
constexpr int SM_XSEL = SM_F2 + 1536;
constexpr int SM_PAIR = SM_XSEL + 4096;
constexpr int SM_H    = SM_PAIR + 2048;
constexpr int SM_KEYS = SM_H + 1024;
constexpr int SM_TOK  = SM_KEYS + 64;
constexpr int SM_XRAW = SM_TOK + 16;
constexpr int SM_SCL  = SM_XRAW + 128;
constexpr int SM_BAR  = SM_SCL + 16;
constexpr int SM_RED  = SM_XSEL;
constexpr int SM_TAB  = SM_RING + 7 * 8192;
constexpr int B_FULL = 0, B_ROW = 24, B_STG = 32, B_SFREE = 34, B_SDONE = 35, B_SLAB = 36, B_TOK = 38, B_UFREE = 39, B_PAIR = 41,
              B_TAB = 42, B_TFREE = 43, B_KFREE = 44, B_U = 46, B_PEER = 48, NBAR = 52;
constexpr int SM_TOTAL = SM_BAR + NBAR * 8;
static_assert(SM_TOTAL + 256 <= 232448, "smem");
__device__ __forceinline__ uint32_t chunk_off(int n) {
    return n < 5 ? SM_RING + n * 16384 : n < 7 ? SM_S + (n - 5) * 16384 : n < 9 ? SM_K + (n - 7) * 16384 : SM_RING + (n - 9) * 16384;
}
constexpr int KP = 272;

struct Scratch {
    uint4 stats[4][1032];
    uint32_t part[128 * 56 * 16];
    uint32_t epoch;
};
__device__ Scratch g_scratch;

struct Params {
    const __nv_bfloat16 *lar, *aim, *cr, *ci, *logdt, *dskip;
    const __nv_bfloat16 *x, *wr;
    __nv_bfloat16* out;
    Scratch* sc;
    const uint4* tab;
    int up_first;
};

__device__ __forceinline__ uint4 ldg128(const void* p) {
    uint4 v; asm volatile("ld.global.nc.v4.u32 {%0,%1,%2,%3}, [%4];" : "=r"(v.x), "=r"(v.y), "=r"(v.z), "=r"(v.w) : "l"(p)); return v;
}
__device__ __forceinline__ uint4 ld_relaxed128(const void* p) {
    uint4 v;
    asm volatile("{ .reg .b128 t; ld.relaxed.gpu.global.b128 t, [%4]; mov.b128 {%0,%1,%2,%3}, t; }"
                 : "=r"(v.x), "=r"(v.y), "=r"(v.z), "=r"(v.w) : "l"(p) : "memory");
    return v;
}
__device__ __forceinline__ void st_relaxed128(void* p, uint4 v) {
    asm volatile("{ .reg .b128 t; mov.b128 t, {%1,%2,%3,%4}; st.relaxed.gpu.global.b128 [%0], t; }"
                 :: "l"(p), "r"(v.x), "r"(v.y), "r"(v.z), "r"(v.w) : "memory");
}
__device__ __forceinline__ void st_relaxed32(void* p, uint32_t v) {
    asm volatile("st.relaxed.gpu.global.u32 [%0], %1;" :: "l"(p), "r"(v) : "memory");
}
__device__ __forceinline__ uint32_t lds32(uint32_t a) { uint32_t v; asm volatile("ld.shared.u32 %0, [%1];" : "=r"(v) : "r"(a)); return v; }
__device__ __forceinline__ uint32_t lds16(uint32_t a) { uint32_t v; asm volatile("ld.shared.u16 %0, [%1];" : "=r"(v) : "r"(a)); return v; }
__device__ __forceinline__ uint2 lds64(uint32_t a) { uint2 v; asm volatile("ld.shared.v2.u32 {%0,%1}, [%2];" : "=r"(v.x), "=r"(v.y) : "r"(a)); return v; }
__device__ __forceinline__ uint4 lds128(uint32_t a) {
    uint4 v; asm volatile("ld.shared.v4.u32 {%0,%1,%2,%3}, [%4];" : "=r"(v.x), "=r"(v.y), "=r"(v.z), "=r"(v.w) : "r"(a)); return v;
}
__device__ __forceinline__ void sts16(uint32_t a, uint32_t v) { asm volatile("st.shared.u16 [%0], %1;" :: "r"(a), "h"((uint16_t)v) : "memory"); }
__device__ __forceinline__ void sts32(uint32_t a, uint32_t v) { asm volatile("st.shared.u32 [%0], %1;" :: "r"(a), "r"(v) : "memory"); }
__device__ __forceinline__ void sts64(uint32_t a, uint32_t x, uint32_t y) { asm volatile("st.shared.v2.u32 [%0], {%1,%2};" :: "r"(a), "r"(x), "r"(y) : "memory"); }
__device__ __forceinline__ void sts128(uint32_t a, uint32_t x, uint32_t y, uint32_t z, uint32_t w) {
    asm volatile("st.shared.v4.u32 [%0], {%1,%2,%3,%4};" :: "r"(a), "r"(x), "r"(y), "r"(z), "r"(w) : "memory");
}
__device__ __forceinline__ void ldsm4(uint32_t a, uint32_t& r0, uint32_t& r1, uint32_t& r2, uint32_t& r3) {
    asm volatile("ldmatrix.sync.aligned.m8n8.x4.shared.b16 {%0,%1,%2,%3}, [%4];" : "=r"(r0), "=r"(r1), "=r"(r2), "=r"(r3) : "r"(a));
}
__device__ __forceinline__ void mma_f16(float (&d)[4], uint32_t a0, uint32_t a1, uint32_t a2, uint32_t a3, uint32_t b0, uint32_t b1) {
    asm("mma.sync.aligned.m16n8k16.row.col.f32.f16.f16.f32 {%0,%1,%2,%3}, {%4,%5,%6,%7}, {%8,%9}, {%0,%1,%2,%3};"
        : "+f"(d[0]), "+f"(d[1]), "+f"(d[2]), "+f"(d[3]) : "r"(a0), "r"(a1), "r"(a2), "r"(a3), "r"(b0), "r"(b1));
}
__device__ __forceinline__ void mma_bf16(float (&d)[4], uint32_t a0, uint32_t a1, uint32_t a2, uint32_t a3, uint32_t b0, uint32_t b1) {
    asm("mma.sync.aligned.m16n8k16.row.col.f32.bf16.bf16.f32 {%0,%1,%2,%3}, {%4,%5,%6,%7}, {%8,%9}, {%0,%1,%2,%3};"
        : "+f"(d[0]), "+f"(d[1]), "+f"(d[2]), "+f"(d[3]) : "r"(a0), "r"(a1), "r"(a2), "r"(a3), "r"(b0), "r"(b1));
}
__device__ __forceinline__ uint32_t prmt(uint32_t a, uint32_t b, uint32_t s) { uint32_t d; asm("prmt.b32 %0, %1, %2, %3;" : "=r"(d) : "r"(a), "r"(b), "r"(s)); return d; }
__device__ __forceinline__ uint32_t pack_h(float lo, float hi) { uint32_t d; asm("cvt.rn.f16x2.f32 %0, %1, %2;" : "=r"(d) : "f"(hi), "f"(lo)); return d; }
__device__ __forceinline__ uint32_t pack_b(float lo, float hi) { uint32_t d; asm("cvt.rn.bf16x2.f32 %0, %1, %2;" : "=r"(d) : "f"(hi), "f"(lo)); return d; }
__device__ __forceinline__ float blo(uint32_t v) { return __uint_as_float(v << 16); }
__device__ __forceinline__ float bhi(uint32_t v) { return __uint_as_float(v & 0xFFFF0000u); }
__device__ __forceinline__ float rb(float v) { return blo(pack_b(v, v)); }
__device__ __forceinline__ uint32_t bsub2(uint32_t a, uint32_t b) { uint32_t d; asm("sub.rn.bf16x2 %0, %1, %2;" : "=r"(d) : "r"(a), "r"(b)); return d; }
__device__ __forceinline__ uint32_t badd2(uint32_t a, uint32_t b) { uint32_t d; asm("add.rn.bf16x2 %0, %1, %2;" : "=r"(d) : "r"(a), "r"(b)); return d; }
__device__ __forceinline__ uint32_t bmul2(uint32_t a, uint32_t b) { uint32_t d; asm("mul.rn.bf16x2 %0, %1, %2;" : "=r"(d) : "r"(a), "r"(b)); return d; }
__device__ __forceinline__ uint32_t bfma2(uint32_t a, uint32_t b, uint32_t c) { uint32_t d; asm("fma.rn.bf16x2 %0, %1, %2, %3;" : "=r"(d) : "r"(a), "r"(b), "r"(c)); return d; }
__device__ __forceinline__ uint32_t dup_lo(uint32_t v) { uint32_t d; asm("{ .reg .b16 l, h; mov.b32 {l, h}, %1; mov.b32 %0, {l, l}; }" : "=r"(d) : "r"(v)); return d; }
__device__ __forceinline__ uint32_t dup_hi(uint32_t v) { uint32_t d; asm("{ .reg .b16 l, h; mov.b32 {l, h}, %1; mov.b32 %0, {h, h}; }" : "=r"(d) : "r"(v)); return d; }
__device__ __forceinline__ uint32_t norm2(uint32_t x, uint32_t m, uint32_t hi, uint32_t lo) {
    uint32_t a = bsub2(x, m);
    return bfma2(a, hi, bmul2(a, lo));
}
__device__ __forceinline__ float ex2(float v) { float d; asm("ex2.approx.ftz.f32 %0, %1;" : "=f"(d) : "f"(v)); return d; }
__device__ __forceinline__ float rcp(float v) { float d; asm("rcp.approx.ftz.f32 %0, %1;" : "=f"(d) : "f"(v)); return d; }
__device__ __forceinline__ float sigmoidf_(float v) { return rcp(1.0f + ex2(-1.4426950408889634f * v)); }
__device__ __forceinline__ float siluf_(float v) { return v * sigmoidf_(v); }

__device__ __forceinline__ void mbar_init(uint32_t a, int n) { asm volatile("mbarrier.init.shared::cta.b64 [%0], %1;" :: "r"(a), "r"(n) : "memory"); }
__device__ __forceinline__ void mbar_expect(uint32_t a, int tx) { asm volatile("mbarrier.arrive.expect_tx.shared::cta.b64 _, [%0], %1;" :: "r"(a), "r"(tx) : "memory"); }
__device__ __forceinline__ void mbar_arrive(uint32_t a) { asm volatile("mbarrier.arrive.shared::cta.b64 _, [%0];" :: "r"(a) : "memory"); }
__device__ __forceinline__ bool mbar_try(uint32_t a) {
    uint32_t d; asm volatile("{ .reg .pred p; mbarrier.try_wait.parity.shared::cta.b64 p, [%1], 0; selp.u32 %0, 1, 0, p; }" : "=r"(d) : "r"(a) : "memory"); return d;
}
__device__ __forceinline__ void mbar_wait(uint32_t a) {
    if (__builtin_expect(!mbar_try(a), 0)) {
        int n = SPIN_LIMIT;
        while (!mbar_try(a) && --n) {}
    }
}
__device__ __forceinline__ void mbar_arrive_peer(uint32_t a) { asm volatile("mbarrier.arrive.relaxed.cluster.shared::cluster.b64 _, [%0];" :: "r"(a) : "memory"); }
__device__ __forceinline__ uint32_t mapa(uint32_t a, uint32_t rank) { uint32_t d; asm("mapa.shared::cluster.u32 %0, %1, %2;" : "=r"(d) : "r"(a), "r"(rank)); return d; }
__device__ __forceinline__ void st_async2(uint32_t a, uint32_t x, uint32_t y, uint32_t bar) {
    asm volatile("st.async.weak.shared::cluster.mbarrier::complete_tx::bytes.v2.b32 [%0], {%1,%2}, [%3];" :: "r"(a), "r"(x), "r"(y), "r"(bar) : "memory");
}
__device__ __forceinline__ void st_async4(uint32_t a, uint32_t x, uint32_t y, uint32_t z, uint32_t w, uint32_t bar) {
    asm volatile("st.async.weak.shared::cluster.mbarrier::complete_tx::bytes.v4.b32 [%0], {%1,%2,%3,%4}, [%5];"
                 :: "r"(a), "r"(x), "r"(y), "r"(z), "r"(w), "r"(bar) : "memory");
}
__device__ __forceinline__ void stsm4(uint32_t a, uint32_t r0, uint32_t r1, uint32_t r2, uint32_t r3) {
    asm volatile("stmatrix.sync.aligned.m8n8.x4.shared.b16 [%0], {%1,%2,%3,%4};" :: "r"(a), "r"(r0), "r"(r1), "r"(r2), "r"(r3) : "memory");
}
__device__ __forceinline__ void proxy_fence() { asm volatile("fence.proxy.async.shared::cta;" ::: "memory"); }
__device__ __forceinline__ void bar_sync(int id, int n) { asm volatile("bar.sync %0, %1;" :: "r"(id), "r"(n) : "memory"); }
__device__ __forceinline__ void bar_arrive(int id, int n) { asm volatile("bar.arrive %0, %1;" :: "r"(id), "r"(n) : "memory"); }
__device__ __forceinline__ void group_sync(int wgi) {
    asm volatile("{ .reg .pred p; setp.ne.s32 p, %0, 0; @p bar.sync 11, 128; @!p bar.sync 10, 128; }" :: "r"(wgi) : "memory");
}
__device__ __forceinline__ void cluster_arrive() { asm volatile("barrier.cluster.arrive.relaxed.aligned;" ::: "memory"); }
__device__ __forceinline__ void cluster_wait() { asm volatile("barrier.cluster.wait.aligned;" ::: "memory"); }
__device__ __forceinline__ void tma3d(uint32_t dst, const CUtensorMap* tm, int c0, int c1, int c2, uint32_t bar, uint64_t pol) {
    asm volatile("cp.async.bulk.tensor.3d.shared::cluster.global.mbarrier::complete_tx::bytes.L2::cache_hint [%0], [%1, {%3, %4, %6}], [%2], %5;"
                 :: "r"(dst), "l"(tm), "r"(bar), "r"(c0), "r"(c1), "l"(pol), "r"(c2) : "memory");
}
__device__ __forceinline__ bool elect() {
    uint32_t p; asm volatile("{ .reg .pred p; elect.sync _|p, 0xFFFFFFFF; selp.u32 %0, 1, 0, p; }" : "=r"(p)); return p;
}

struct cf { float r, i; };
__device__ __forceinline__ cf cmul(cf a, cf b) { return {a.r * b.r - a.i * b.i, a.r * b.i + a.i * b.r}; }
__device__ __forceinline__ cf csq(cf a) { return {a.r * a.r - a.i * a.i, (a.r + a.r) * a.i}; }
__device__ __forceinline__ cf cexp_(float a2, float b) { float m = ex2(a2); return {m * __cosf(b), m * __sinf(b)}; }
struct hc { uint32_t r, i; };
__device__ __forceinline__ hc pk(cf a, cf b) { return {pack_h(a.r, b.r), pack_h(a.i, b.i)}; }
__device__ __forceinline__ hc hmulc(hc a, hc b) {
    const __half2 ar = *reinterpret_cast<__half2*>(&a.r), ai = *reinterpret_cast<__half2*>(&a.i);
    const __half2 br = *reinterpret_cast<__half2*>(&b.r), bi = *reinterpret_cast<__half2*>(&b.i);
    const __half2 r = __hfma2(ar, br, __hneg2(__hmul2_rn(ai, bi))), i = __hfma2(ar, bi, __hmul2_rn(ai, br));
    return {*reinterpret_cast<const uint32_t*>(&r), *reinterpret_cast<const uint32_t*>(&i)};
}
__device__ __forceinline__ void sth(uint32_t a, hc v) { sts32(a, v.r); sts32(a + 128, v.i); }
__device__ __forceinline__ uint32_t cpy(uint32_t v, uint32_t z) { uint32_t d; asm("xor.b32 %0, %1, %2;" : "=r"(d) : "r"(v), "r"(z)); return d; }
__device__ __forceinline__ uint32_t pin(uint32_t v) { return __shfl_sync(0xFFFFFFFFu, v, threadIdx.x & 31); }
__device__ __forceinline__ void sched_fence() { asm volatile("pmevent 0;" ::: "memory"); }
__device__ __forceinline__ float tanh_(float v) { float d; asm("tanh.approx.f32 %0, %1;" : "=f"(d) : "f"(v)); return d; }
__device__ __forceinline__ float silu2(float h) {
    return fmaf(h, tanh_(h), h);
}
__device__ __forceinline__ uint32_t hfma2_(uint32_t a, uint32_t b, uint32_t c) { uint32_t d; asm("fma.rn.f16x2 %0, %1, %2, %3;" : "=r"(d) : "r"(a), "r"(b), "r"(c)); return d; }
__device__ __forceinline__ uint32_t hfms2_(uint32_t a, uint32_t b, uint32_t c) {
    uint32_t d; asm("{ .reg .b32 t; neg.f16x2 t, %1; fma.rn.f16x2 %0, t, %2, %3; }" : "=r"(d) : "r"(a), "r"(b), "r"(c)); return d;
}

__device__ __forceinline__ uint64_t bdesc(uint32_t addr, uint32_t sbo) {
    return (uint64_t)((addr & 0x3FFFFu) >> 4) | ((uint64_t)(128 >> 4) << 16) | ((uint64_t)(sbo >> 4) << 32);
}
__device__ __forceinline__ void wg_h(uint32_t (&d)[16], const uint32_t* a, const uint32_t* b, uint64_t d0, uint64_t d1, uint64_t d2, uint64_t d3) {
    asm volatile(
        "wgmma.mma_async.sync.aligned.m64n64k16.f16.f16.f16 {%0,%1,%2,%3,%4,%5,%6,%7,%8,%9,%10,%11,%12,%13,%14,%15}, {%16,%17,%18,%19}, %32, 0, 1, 1, 1;\n"
        "wgmma.mma_async.sync.aligned.m64n64k16.f16.f16.f16 {%0,%1,%2,%3,%4,%5,%6,%7,%8,%9,%10,%11,%12,%13,%14,%15}, {%20,%21,%22,%23}, %33, 1, 1, 1, 1;\n"
        "wgmma.mma_async.sync.aligned.m64n64k16.f16.f16.f16 {%0,%1,%2,%3,%4,%5,%6,%7,%8,%9,%10,%11,%12,%13,%14,%15}, {%24,%25,%26,%27}, %34, 1, 1, 1, 1;\n"
        "wgmma.mma_async.sync.aligned.m64n64k16.f16.f16.f16 {%0,%1,%2,%3,%4,%5,%6,%7,%8,%9,%10,%11,%12,%13,%14,%15}, {%28,%29,%30,%31}, %35, 1, 1, 1, 1;\n"
        : "=r"(d[0]), "=r"(d[1]), "=r"(d[2]), "=r"(d[3]), "=r"(d[4]), "=r"(d[5]), "=r"(d[6]), "=r"(d[7]), "=r"(d[8]), "=r"(d[9]), "=r"(d[10]), "=r"(d[11]), "=r"(d[12]), "=r"(d[13]), "=r"(d[14]), "=r"(d[15])
        : "r"(a[0]), "r"(a[1]), "r"(a[2]), "r"(a[3]), "r"(a[4]), "r"(a[5]), "r"(a[6]), "r"(a[7]), "r"(b[0]), "r"(b[1]), "r"(b[2]), "r"(b[3]), "r"(b[4]), "r"(b[5]), "r"(b[6]), "r"(b[7]), "l"(d0), "l"(d1), "l"(d2), "l"(d3));
}
__device__ __forceinline__ void wg_f0(float (&d)[32], const uint32_t* a, const uint32_t* b, uint64_t d0, uint64_t d1, uint64_t d2, uint64_t d3) {
    asm volatile(
        "wgmma.mma_async.sync.aligned.m64n64k16.f32.f16.f16 {%0,%1,%2,%3,%4,%5,%6,%7,%8,%9,%10,%11,%12,%13,%14,%15,%16,%17,%18,%19,%20,%21,%22,%23,%24,%25,%26,%27,%28,%29,%30,%31}, {%32,%33,%34,%35}, %48, 0, 1, 1, 1;\n"
        "wgmma.mma_async.sync.aligned.m64n64k16.f32.f16.f16 {%0,%1,%2,%3,%4,%5,%6,%7,%8,%9,%10,%11,%12,%13,%14,%15,%16,%17,%18,%19,%20,%21,%22,%23,%24,%25,%26,%27,%28,%29,%30,%31}, {%36,%37,%38,%39}, %49, 1, 1, 1, 1;\n"
        "wgmma.mma_async.sync.aligned.m64n64k16.f32.f16.f16 {%0,%1,%2,%3,%4,%5,%6,%7,%8,%9,%10,%11,%12,%13,%14,%15,%16,%17,%18,%19,%20,%21,%22,%23,%24,%25,%26,%27,%28,%29,%30,%31}, {%40,%41,%42,%43}, %50, 1, 1, 1, 1;\n"
        "wgmma.mma_async.sync.aligned.m64n64k16.f32.f16.f16 {%0,%1,%2,%3,%4,%5,%6,%7,%8,%9,%10,%11,%12,%13,%14,%15,%16,%17,%18,%19,%20,%21,%22,%23,%24,%25,%26,%27,%28,%29,%30,%31}, {%44,%45,%46,%47}, %51, 1, 1, 1, 1;\n"
        : "=f"(d[0]), "=f"(d[1]), "=f"(d[2]), "=f"(d[3]), "=f"(d[4]), "=f"(d[5]), "=f"(d[6]), "=f"(d[7]), "=f"(d[8]), "=f"(d[9]), "=f"(d[10]), "=f"(d[11]), "=f"(d[12]), "=f"(d[13]), "=f"(d[14]), "=f"(d[15]), "=f"(d[16]), "=f"(d[17]), "=f"(d[18]), "=f"(d[19]), "=f"(d[20]), "=f"(d[21]), "=f"(d[22]), "=f"(d[23]), "=f"(d[24]), "=f"(d[25]), "=f"(d[26]), "=f"(d[27]), "=f"(d[28]), "=f"(d[29]), "=f"(d[30]), "=f"(d[31])
        : "r"(a[0]), "r"(a[1]), "r"(a[2]), "r"(a[3]), "r"(a[4]), "r"(a[5]), "r"(a[6]), "r"(a[7]), "r"(b[0]), "r"(b[1]), "r"(b[2]), "r"(b[3]), "r"(b[4]), "r"(b[5]), "r"(b[6]), "r"(b[7]), "l"(d0), "l"(d1), "l"(d2), "l"(d3));
}
__device__ __forceinline__ void wg_f1(float (&d)[32], const uint32_t* a, const uint32_t* b, uint64_t d0, uint64_t d1, uint64_t d2, uint64_t d3) {
    asm volatile(
        "wgmma.mma_async.sync.aligned.m64n64k16.f32.f16.f16 {%0,%1,%2,%3,%4,%5,%6,%7,%8,%9,%10,%11,%12,%13,%14,%15,%16,%17,%18,%19,%20,%21,%22,%23,%24,%25,%26,%27,%28,%29,%30,%31}, {%32,%33,%34,%35}, %48, 1, 1, 1, 1;\n"
        "wgmma.mma_async.sync.aligned.m64n64k16.f32.f16.f16 {%0,%1,%2,%3,%4,%5,%6,%7,%8,%9,%10,%11,%12,%13,%14,%15,%16,%17,%18,%19,%20,%21,%22,%23,%24,%25,%26,%27,%28,%29,%30,%31}, {%36,%37,%38,%39}, %49, 1, 1, 1, 1;\n"
        "wgmma.mma_async.sync.aligned.m64n64k16.f32.f16.f16 {%0,%1,%2,%3,%4,%5,%6,%7,%8,%9,%10,%11,%12,%13,%14,%15,%16,%17,%18,%19,%20,%21,%22,%23,%24,%25,%26,%27,%28,%29,%30,%31}, {%40,%41,%42,%43}, %50, 1, 1, 1, 1;\n"
        "wgmma.mma_async.sync.aligned.m64n64k16.f32.f16.f16 {%0,%1,%2,%3,%4,%5,%6,%7,%8,%9,%10,%11,%12,%13,%14,%15,%16,%17,%18,%19,%20,%21,%22,%23,%24,%25,%26,%27,%28,%29,%30,%31}, {%44,%45,%46,%47}, %51, 1, 1, 1, 1;\n"
        : "+f"(d[0]), "+f"(d[1]), "+f"(d[2]), "+f"(d[3]), "+f"(d[4]), "+f"(d[5]), "+f"(d[6]), "+f"(d[7]), "+f"(d[8]), "+f"(d[9]), "+f"(d[10]), "+f"(d[11]), "+f"(d[12]), "+f"(d[13]), "+f"(d[14]), "+f"(d[15]), "+f"(d[16]), "+f"(d[17]), "+f"(d[18]), "+f"(d[19]), "+f"(d[20]), "+f"(d[21]), "+f"(d[22]), "+f"(d[23]), "+f"(d[24]), "+f"(d[25]), "+f"(d[26]), "+f"(d[27]), "+f"(d[28]), "+f"(d[29]), "+f"(d[30]), "+f"(d[31])
        : "r"(a[0]), "r"(a[1]), "r"(a[2]), "r"(a[3]), "r"(a[4]), "r"(a[5]), "r"(a[6]), "r"(a[7]), "r"(b[0]), "r"(b[1]), "r"(b[2]), "r"(b[3]), "r"(b[4]), "r"(b[5]), "r"(b[6]), "r"(b[7]), "l"(d0), "l"(d1), "l"(d2), "l"(d3));
}
__device__ __forceinline__ void wg_s(uint32_t* d, const uint32_t* a, const uint32_t* b, uint64_t d0, uint64_t d1) {
    asm volatile(
        "wgmma.mma_async.sync.aligned.m64n32k16.f16.f16.f16 {%0,%1,%2,%3,%4,%5,%6,%7}, {%8,%9,%10,%11}, %16, 0, 1, 1, 1;\n"
        "wgmma.mma_async.sync.aligned.m64n32k16.f16.f16.f16 {%0,%1,%2,%3,%4,%5,%6,%7}, {%12,%13,%14,%15}, %17, 1, 1, 1, 1;\n"
        : "=r"(d[0]), "=r"(d[1]), "=r"(d[2]), "=r"(d[3]), "=r"(d[4]), "=r"(d[5]), "=r"(d[6]), "=r"(d[7])
        : "r"(a[0]), "r"(a[1]), "r"(a[2]), "r"(a[3]), "r"(b[0]), "r"(b[1]), "r"(b[2]), "r"(b[3]), "l"(d0), "l"(d1));
}
template <int ACC> __device__ __forceinline__ void wg_w(float (&d)[4], uint64_t da, uint64_t db) {
    asm volatile("wgmma.mma_async.sync.aligned.m64n8k16.f32.bf16.bf16 {%0,%1,%2,%3}, %4, %5, %6, 1, 1, 1, 0;"
                 : "+f"(d[0]), "+f"(d[1]), "+f"(d[2]), "+f"(d[3]) : "l"(da), "l"(db), "n"(ACC));
}
__device__ __forceinline__ void wg_w0(float (&d)[4], uint64_t da, uint64_t db) {
    asm volatile("wgmma.mma_async.sync.aligned.m64n8k16.f32.bf16.bf16 {%0,%1,%2,%3}, %4, %5, 0, 1, 1, 1, 0;"
                 : "=f"(d[0]), "=f"(d[1]), "=f"(d[2]), "=f"(d[3]) : "l"(da), "l"(db));
}
__device__ __forceinline__ void wg_fence() { asm volatile("wgmma.fence.sync.aligned;" ::: "memory"); }
__device__ __forceinline__ void wg_commit() { asm volatile("wgmma.commit_group.sync.aligned;" ::: "memory"); }
template <int N> __device__ __forceinline__ void wg_wait() { asm volatile("wgmma.wait_group.sync.aligned %0;" :: "n"(N) : "memory"); }
__device__ __forceinline__ void touch(uint32_t& r) { asm volatile("" : "+r"(r) :: "memory"); }
__device__ __forceinline__ void touch(float& r) { asm volatile("" : "+f"(r) :: "memory"); }
template <class T, int N> __device__ __forceinline__ void touch(T (&r)[N]) {
#pragma unroll
    for (int i = 0; i < N; i++) touch(r[i]);
}

__global__ void __cluster_dims__(2, 1, 1) __launch_bounds__(NTHREADS, 1)
fused_kernel(const Params p, const __grid_constant__ CUtensorMap tm_x, const __grid_constant__ CUtensorMap tm_g,
             const __grid_constant__ CUtensorMap tm_d)
{
    extern __shared__ __align__(1024) uint8_t smem_raw[];
    const uint32_t sm = (uint32_t)__cvta_generic_to_shared(smem_raw);
    const uint32_t bars = sm + SM_BAR;
    const int tid = threadIdx.x, lane = tid & 31;
    const int g = lane >> 2, q = lane & 3;
    const int c = blockIdx.x, rank = c & 1, G = c >> 1;

    if (tid < 256) {
        uint2 lar4, aim4, cr4, ci4;
        uint32_t ldt_raw, dsk_raw;
        {
            const uint32_t i = c * 256 + tid;
            asm volatile("ld.global.nc.v2.u32 {%0,%1}, [%10]; ld.global.nc.v2.u32 {%2,%3}, [%11]; ld.global.nc.u16 %8, [%14];\n"
                         "ld.global.nc.v2.u32 {%4,%5}, [%12]; ld.global.nc.v2.u32 {%6,%7}, [%13]; ld.global.nc.u16 %9, [%15];"
                         : "=r"(lar4.x), "=r"(lar4.y), "=r"(aim4.x), "=r"(aim4.y), "=r"(cr4.x), "=r"(cr4.y), "=r"(ci4.x), "=r"(ci4.y), "=r"(ldt_raw), "=r"(dsk_raw)
                         : "l"(p.lar + i * 4), "l"(p.aim + i * 4), "l"(p.cr + i * 4), "l"(p.ci + i * 4), "l"(p.logdt + (i >> 5)), "l"(p.dskip + (i >> 5)));
        }
        cluster_arrive();
        sched_fence();
        const int warp = __shfl_sync(0xFFFFFFFFu, tid >> 5, 0);
        const float logdt = blo(ldt_raw), dsk = blo(dsk_raw);
        asm volatile("setmaxnreg.inc.sync.aligned.u32 160;");
        const int wgi = warp >> 2, w = warp & 3;
        const uint32_t wb = sm + SM_K + (w < 2 ? 16 * w + 8 * wgi : 16 + 16 * wgi + 8 * w) * SUB;
        sth(wb + lane * 4, hc{0x3C003C00u, 0u});
        const uint32_t tb0 = pin(sm + SM_S + (16 * wgi + w) * SUB + lane * 16), tb1 = pin(sm + SM_S + (16 * wgi + w) * SUB + ((lane + 1) & 31) * 16);
        const uint32_t seg = pin(sm + SM_K + (2 * warp + (lane & 1)) * SUB + (lane >> 1) * 16);
        const uint32_t zst = pin(sm + SM_S + (16 * wgi + (lane >> 4)) * SUB + (16 * w + (lane & 15)) * 16);
        sched_fence();

        {
            const uint32_t z = (uint32_t)(uintptr_t)p.lar & 1;
            lar4.x = cpy(lar4.x, z); lar4.y = cpy(lar4.y, z); aim4.x = cpy(aim4.x, z); aim4.y = cpy(aim4.y, z);
            cr4.x = cpy(cr4.x, z); cr4.y = cpy(cr4.y, z); ci4.x = cpy(ci4.x, z); ci4.y = cpy(ci4.y, z);
        }
        const float dt = rb(expf(logdt));
        float outscale, cs, dn;
        {
            uint32_t m0 = __vmaxu2(__vmaxu2(cr4.x & 0x7FFF7FFFu, cr4.y & 0x7FFF7FFFu), __vmaxu2(ci4.x & 0x7FFF7FFFu, ci4.y & 0x7FFF7FFFu));
            uint32_t m1 = max(m0 & 0xFFFFu, m0 >> 16);
            float cmax = blo(__reduce_max_sync(0xFFFFFFFFu, m1));
            const float sc = fminf(fmaxf(fmaxf(2.0f * dt * cmax, fabsf(dsk) * (1.0f / 1024.0f)), 1e-30f), 1e30f);
            outscale = __uint_as_float(__float_as_uint(sc) & 0x7F800000u);
            const float inv = __uint_as_float(0x7F000000u - __float_as_uint(outscale));
            cs = 2.0f * dt * inv * (1.0f / 512.0f);
            dn = dsk * inv * (1.0f / 512.0f);
            if (lane == 0) sts16(sm + SM_SCL + warp * 2, __float_as_uint(32768.0f * outscale) >> 16);
        }
        if (warp == TSW) TSL(39);
        uint32_t fc[16], fs[16], ta[4], tb[4];
        float kacc[2][3][4];
#pragma unroll
        for (int i = 0; i < 2; i++)
#pragma unroll
            for (int j = 0; j < 3; j++) kacc[i][j][0] = kacc[i][j][1] = kacc[i][j][2] = kacc[i][j][3] = 0.f;
        if (lane == 0) kacc[0][0][0] = dn;
        {
            const uint32_t st = wb + lane * 4;
            const uint32_t zk = lds32(wb + 128);
            const uint32_t la = wb + ((lane & 8) ? 29 : (lane & 7)) * KP + (lane >> 4) * 128;
            const uint32_t lo = wb + ((lane >> 3) & 1) * 128 + (lane >> 4) * 16;
            const uint32_t lb = lo + (8 + (lane & 7)) * KP, lb2 = lo + (24 + min(lane & 7, 4)) * KP, lm = lo + 30 * KP;
#pragma unroll 1
            for (int s = 0; s < 2; s++) {
                const uint32_t wl = s ? lar4.y : lar4.x, wa = s ? aim4.y : aim4.x, wr_ = s ? cr4.y : cr4.x, wi = s ? ci4.y : ci4.x;
                const uint32_t ea = pack_b(ex2(blo(wl) * 1.4426950408889634f), ex2(bhi(wl) * 1.4426950408889634f));
                const float a2[2] = {-(blo(ea) * dt) * 1.4426950408889634f, -(bhi(ea) * dt) * 1.4426950408889634f};
                const float b[2] = {blo(wa) * dt, bhi(wa) * dt};
                {
                    cf z8[2], z16[2], z32[2], z64[2], z128[2];
#pragma unroll
                    for (int e = 0; e < 2; e++) {
                        z8[e] = cexp_(a2[e] * 8.f, b[e] * 8.f);
                        z16[e] = csq(z8[e]); z32[e] = csq(z16[e]); z64[e] = csq(z32[e]); z128[e] = csq(z64[e]);
                    }
                    const hc r1 = pk(z8[0], z8[1]), r2 = pk(z16[0], z16[1]), r3 = hmulc(r1, r2), r4 = pk(z32[0], z32[1]);
                    sth(st + 1 * KP, r1); sth(st + 2 * KP, r2); sth(st + 3 * KP, r3); sth(st + 4 * KP, r4);
                    sth(st + 5 * KP, hmulc(r1, r4)); sth(st + 6 * KP, hmulc(r2, r4)); sth(st + 7 * KP, hmulc(r3, r4));
                    sth(st + 29 * KP, pk(z64[0], z64[1])); sth(st + 30 * KP, pk(z128[0], z128[1]));
                }
                {
                    cf C[2], z2[2], z4[2], v2[2], v4[2], c1[2], d1[2];
#pragma unroll
                    for (int e = 0; e < 2; e++) {
                        C[e] = {(e ? bhi(wr_) : blo(wr_)) * cs, (e ? bhi(wi) : blo(wi)) * -cs};
                        const cf z = cexp_(a2[e], -b[e]);
                        const cf v = cexp_(a2[e] * 256.f, b[e] * -256.f);
                        z2[e] = csq(z); z4[e] = csq(z2[e]); v2[e] = csq(v); v4[e] = csq(v2[e]);
                        c1[e] = cmul(C[e], z); d1[e] = cmul(C[e], v);
                    }
                    const hc l0 = pk(C[0], C[1]), l1 = pk(c1[0], c1[1]), e1 = pk(d1[0], d1[1]);
                    const hc h = pk(z2[0], z2[1]), f = pk(z4[0], z4[1]), w = pk(v2[0], v2[1]), y = pk(v4[0], v4[1]);
                    const hc l2 = hmulc(l0, h), l3 = hmulc(l1, h), e2 = hmulc(l0, w), e3 = hmulc(e1, w), e4 = hmulc(l0, y), g2 = hmulc(e1, h);
                    sth(st + 8 * KP, l0); sth(st + 9 * KP, l1); sth(st + 10 * KP, l2); sth(st + 11 * KP, l3);
                    sth(st + 12 * KP, hmulc(l0, f)); sth(st + 13 * KP, hmulc(l1, f)); sth(st + 14 * KP, hmulc(l2, f)); sth(st + 15 * KP, hmulc(l3, f));
                    sth(st + 16 * KP, e1);
                    sth(st + 17 * KP, g2);
                    sth(st + 18 * KP, hmulc(e1, f));
                    sth(st + 19 * KP, hmulc(g2, f));
                    sth(st + 20 * KP, e2);
                    sth(st + 21 * KP, hmulc(e2, f));
                    sth(st + 22 * KP, e3);
                    sth(st + 23 * KP, hmulc(e3, f));
                    sth(st + 24 * KP, e4);
                    sth(st + 25 * KP, hmulc(e1, y));
                    sth(st + 26 * KP, hmulc(e2, y));
                    sth(st + 27 * KP, hmulc(e3, y));
                    sth(st + 28 * KP, hmulc(e4, y));
                }
                __syncwarp();
                if (warp == TSW && s == 0) TSL(27);
                if (s == 1 && lane == 0) mbar_arrive(bars + B_TFREE * 8 + (tb[3] & zk));
#pragma unroll
                for (int kp = 0; kp < 4; kp++) {
                    uint32_t bb[3][4], m2[4];
                    ldsm4(lm + kp * 32, m2[0], m2[1], m2[2], m2[3]);
                    ldsm4(lb + kp * 32, bb[0][0], bb[0][1], bb[0][2], bb[0][3]);
                    ldsm4(lb + 8 * KP + kp * 32, bb[1][0], bb[1][1], bb[1][2], bb[1][3]);
                    ldsm4(lb2 + kp * 32, bb[2][0], bb[2][1], bb[2][2], bb[2][3]);
#pragma unroll
                    for (int k2 = 0; k2 < 2; k2++) {
                        hc v0, m1;
                        ldsm4(la + kp * 32 + k2 * 16, v0.r, m1.r, v0.i, m1.i);
                        const hc mm = {m2[2 * k2], m2[2 * k2 + 1]};
                        const hc v1 = hmulc(v0, m1), v2 = hmulc(v0, mm), v3 = hmulc(v1, mm);
                        v0.r = cpy(v0.r, zk); v0.i = cpy(v0.i, zk);
#pragma unroll
                        for (int nt = 0; nt < 3; nt++) {
                            mma_f16(kacc[0][nt], v0.r, v1.r, v0.i, v1.i, bb[nt][2 * k2], bb[nt][2 * k2 + 1]);
                            mma_f16(kacc[1][nt], v2.r, v3.r, v2.i, v3.i, bb[nt][2 * k2], bb[nt][2 * k2 + 1]);
                        }
                    }
                }
                __syncwarp();
                if (warp == TSW) TSL(s ? 40 : 33);
                if (s == 0) {
                    cluster_wait();
                    mbar_wait(bars + B_TAB * 8);
#pragma unroll
                    for (int i = 0; i < 10; i++) {
                        const uint4 u = lds128(sm + SM_TAB + i * 2048 + (tid & 127) * 16);
                        uint32_t* t = i < 4 ? fc + 4 * i : i < 8 ? fs + 4 * (i - 4) : i == 8 ? ta : tb;
                        t[0] = u.x; t[1] = u.y; t[2] = u.z; t[3] = u.w;
                    }
                }
            }
        }
        TSL(1);
        group_sync(wgi);
        {
            uint32_t v[3][4];
#pragma unroll
            for (int i = 0; i < 12; i++) v[i >> 2][i & 3] = pack_h(kacc[(i >> 1) & 1][i >> 2][2 * (i & 1)], kacc[(i >> 1) & 1][i >> 2][2 * (i & 1) + 1]);
            stsm4(tb0, v[1][0], v[1][1], v[1][2], v[1][3]);
            stsm4(tb0 + 512, v[2][0], v[2][1], v[2][2], v[2][3]);
            stsm4(seg, v[0][0], v[0][1], v[0][2], v[0][3]);
            __syncwarp();
            const uint4 a = lds128(tb0), na = lds128(tb1), nb = lds128(tb1 + 512);
            const uint2 b = lds64(tb0 + 512);
            const bool last = lane == 31;
            const uint32_t n1 = last ? na.z : na.x, n2 = last ? na.w : na.z, n3 = last ? nb.x : na.w;
            const uint32_t sn = last ? 0x5432 : 0x3210, n4 = prmt(nb.x, nb.y, sn), n5 = prmt(nb.y, nb.z, sn);
            sts128(seg + 256, prmt(a.x, 0, 0x1010), prmt(a.x, a.y, 0x5432), prmt(a.y, 0, 0x1010), prmt(a.y, n1, 0x5432));
            sts128(seg + 512, prmt(a.z, 0, 0x1010), a.z, prmt(a.z, 0, 0x3232), prmt(n2, 0, 0x1010));
            sts128(seg + 768, prmt(a.w, 0, 0x1010), a.w, prmt(a.w, 0, 0x3232), prmt(n3, 0, 0x1010));
            const uint32_t s3 = (lane & 1) ? 0x5454 : 0x5410;
#pragma unroll
            for (int i = 0; i < 4; i++) {
                const uint32_t cur = (i & 2) ? b.y : b.x, nx = (i & 2) ? n5 : n4, h = (i & 1) * 0x2222;
                const uint32_t vv = prmt(cur, 0, 0x1010 + h);
                sts128(seg + 16 * SUB + i * 256, vv, vv, prmt(cur, nx, s3 + h), prmt(nx, 0, 0x1010 + h));
            }
        }
        proxy_fence();
        __syncwarp();
        if (lane == 0) mbar_arrive(bars + B_SFREE * 8);
        TSL(2);
        group_sync(wgi);
        const uint64_t dre = bdesc(sm + SM_F2 + 512, 256), dim = bdesc(sm + SM_F2, 256);
        uint32_t k0[32], k1[32];
#pragma unroll
        for (int b = 0; b < 2; b++) {
            const uint64_t d1 = bdesc(sm + SM_K + (16 * b + 8 * wgi) * SUB, SUB);
            uint32_t re[16], im[16];
            if (b == 0 && wgi == 1) bar_sync(5, 256);
            wg_fence();
            wg_h(re, fc, fc + 8, d1, d1 + 16, d1 + 32, d1 + 48);
            wg_h(im, fs, fs + 8, d1, d1 + 16, d1 + 32, d1 + 48);
            wg_commit();
            if (b == 0 && wgi == 0) bar_arrive(5, 256);
            wg_wait<0>();
            touch(re); touch(im);
            if (lane == 0) mbar_arrive(bars + (B_KFREE + b) * 8);
            uint32_t (&kk)[32] = b ? k1 : k0;
#pragma unroll
            for (int hh = 0; hh < 2; hh++) {
#pragma unroll
                for (int i = 8 * hh; i < 8 * hh + 8; i++) {
                    re[i] = hfma2_(ta[i & 3], im[i], re[i]); im[i] = hfms2_(tb[i & 3], re[i], im[i]); re[i] = hfma2_(ta[i & 3], im[i], re[i]);
                }
                wg_fence();
                wg_s(kk + 16 * hh, re + 8 * hh, im + 8 * hh, dre, dim);
                wg_s(kk + 16 * hh + 8, re + 8 * hh + 4, im + 8 * hh + 4, dre, dim);
                wg_commit();
            }
            wg_wait<0>();
            touch(kk);
        }
        if (warp == TSW) TSL(35);
        asm volatile("setmaxnreg.inc.sync.aligned.u32 176;");
        touch(k1);
        {
            const uint32_t sg = (g & 1) ? 0xBC00BC00u : 0x3C003C00u;
#pragma unroll
            for (int i = 0; i < 16; i++) {
                const int r = 8 * (i >> 2) + (i & 3);
                k1[r] = hfms2_(sg, k0[r + 4], k1[r]); k1[r + 4] = hfma2_(sg, k0[r], k1[r + 4]);
            }
            touch(k1);
        }
        const uint32_t peer = mapa(sm, rank ^ 1), so = SM_U + 8 * wgi * SUB + w * 1024 + (8 * q + (g ^ (2 * q))) * 16;
        uint32_t re[16], im[16];
        auto dft128 = [&](int b) {
            const uint64_t d1 = bdesc(sm + SM_U + (16 * b + 8 * wgi) * SUB, SUB);
            wg_fence();
            wg_h(re, fc, fc + 8, d1, d1 + 16, d1 + 32, d1 + 48);
            wg_h(im, fs, fs + 8, d1, d1 + 16, d1 + 32, d1 + 48);
            wg_commit();
        };
        mbar_wait(bars + B_U * 8);
        proxy_fence();
        TSL(3);
        if (wgi == 1) bar_sync(9, 256);
#pragma unroll 1
        for (int b = 0; b < 2; b++) {
            const uint32_t zb = sm + SM_S + 16 * wgi * SUB;
            constexpr int zi = 8 * SUB;
            uint32_t su[2][16], z[2][16], y[2][16];
            auto twiddle = [&](int hh) {
#pragma unroll
                for (int i = 8 * hh; i < 8 * hh + 8; i++) {
                    re[i] = hfma2_(ta[i & 3], im[i], re[i]); im[i] = hfms2_(tb[i & 3], re[i], im[i]); re[i] = hfma2_(ta[i & 3], im[i], re[i]);
                    touch(re[i]); touch(im[i]);
                }
            };
            auto dft16 = [&](int hh) {
                wg_fence();
                wg_s(su[hh], re + 8 * hh, im + 8 * hh, dre, dim); wg_s(su[hh] + 8, re + 8 * hh + 4, im + 8 * hh + 4, dre, dim);
                wg_commit();
                sched_fence();
            };
            auto product = [&](int hh) {
                if (b == 0) {
#pragma unroll
                    for (int i = 0; i < 8; i++) {
                        const int r = 8 * (i >> 2) + (i & 3), kr = 16 * hh + r;
                        const hc u = {su[hh][r], su[hh][r + 4]};
                        const hc t = hmulc(u, hc{k0[kr], k0[kr + 4]}), pp = hmulc(u, hc{k1[kr], k1[kr + 4]});
                        z[hh][r] = t.r; z[hh][r + 4] = t.i; k1[kr] = pp.r; k1[kr + 4] = pp.i;
                        touch(k1[kr]); touch(k1[kr + 4]);
                    }
                } else {
#pragma unroll
                    for (int i = 0; i < 8; i++) {
                        const int r = 8 * (i >> 2) + (i & 3), kr = 16 * hh + r;
                        const hc u = {su[hh][r], su[hh][r + 4]};
                        z[hh][r] = hfms2_(u.i, k0[kr + 4], hfma2_(u.r, k0[kr], k1[kr]));
                        z[hh][r + 4] = hfma2_(u.i, k0[kr], hfma2_(u.r, k0[kr + 4], k1[kr + 4]));
                    }
                }
                touch(z[hh]);
            };
            auto idft16 = [&](int hh) {
                wg_fence();
                wg_s(y[hh], z[hh] + 4, z[hh], dre, dim); wg_s(y[hh] + 8, z[hh] + 12, z[hh] + 8, dre, dim);
                wg_commit();
                sched_fence();
            };
            auto untwiddle = [&](int hh) {
#pragma unroll
                for (int i = 0; i < 2; i++) {
                    uint32_t* const yi = y[hh] + 8 * i, * const yr = yi + 4;
#pragma unroll
                    for (int n = 0; n < 4; n++) {
                        yr[n] = hfms2_(ta[n], yi[n], yr[n]); yi[n] = hfma2_(tb[n], yr[n], yi[n]); yr[n] = hfms2_(ta[n], yi[n], yr[n]);
                    }
                    const uint32_t a = zst + (4 * hh + 2 * i) * SUB;
                    stsm4(a, yr[0], yr[1], yr[2], yr[3]);
                    stsm4(a + zi, yi[0], yi[1], yi[2], yi[3]);
                }
            };
            auto done = [&]() { sched_fence(); wg_wait<0>(); };
            PT(0);
            dft128(b);
            PT(1);
            if (b == 0 && wgi == 0) bar_arrive(9, 256);
            wg_wait<0>();
            touch(re); touch(im);
            PT(2);
            if (lane == 0) mbar_arrive_peer(peer + SM_BAR + (B_PEER + 2 * wgi + b) * 8);
            twiddle(0); twiddle(1); dft16(0); dft16(1);
            PT(3);
            wg_wait<1>(); touch(su[0]);
            product(0); done(); touch(su[1]); PT(4); idft16(0);
            product(1); done(); touch(y[0]); PT(5); idft16(1);
            PT(6);
            mbar_wait(bars + B_SDONE * 8);
            group_sync(wgi);
            untwiddle(0); done(); touch(y[1]);
            untwiddle(1);
            PT(7);
            mbar_wait(bars + (B_U + 1) * 8);
            proxy_fence();
            PT(8);
            if (warp == TSW) TSL(36 + b);
            group_sync(wgi);
            PT(9);
            float acc[32];
            const uint64_t d4 = bdesc(zb, SUB);
            wg_fence();
            wg_f0(acc, fc, fc + 8, d4, d4 + 16, d4 + 32, d4 + 48);
            wg_f1(acc, fs, fs + 8, d4 + zi / 16, d4 + zi / 16 + 16, d4 + zi / 16 + 32, d4 + zi / 16 + 48);
            wg_commit();
            mbar_wait(bars + (B_PEER + 2 * wgi + b) * 8);
            const uint2 sc = lds64(sm + SM_SCL + wgi * 8);
            PT(10);
            wg_wait<0>();
            PT(11);
            touch(acc);
            uint32_t s[2][2][4];
#pragma unroll
            for (int i = 0; i < 8; i++) {
                s[i >> 2][(i >> 1) & 1][2 * (i & 1)] = bmul2(pack_b(acc[i], acc[8 + i]), sc.x);
                s[i >> 2][(i >> 1) & 1][2 * (i & 1) + 1] = bmul2(pack_b(acc[16 + i], acc[24 + i]), sc.y);
            }
            const uint32_t sb = SM_BAR + (B_STG + b) * 8;
#pragma unroll
            for (int j = 0; j < 2; j++)
                if (j == rank) {
#pragma unroll
                    for (int hi = 0; hi < 2; hi++) {
                        const uint32_t (&r)[4] = s[1 - j][hi], (&l)[4] = s[j][hi];
                        st_async4(peer + so + 16 * b * SUB + hi * 512, r[0], r[1], r[2], r[3], peer + sb);
                        sts128(sm + (so ^ 64) + (16 * b + 4) * SUB + hi * 512, l[0], l[1], l[2], l[3]);
                    }
                }
            __syncwarp();
            if (lane == 0) mbar_arrive(sm + sb);
            PT(12);
            if (warp == TSW) TSL(5 + b);
        }
        TSL(7);
    } else {
    const int warp = __shfl_sync(0xFFFFFFFFu, tid >> 5, 0);
    if (warp < 12) {
        const int v = warp - 8;
        cluster_arrive();
        const uint32_t xs = sm + SM_U + v * 8192;
        if (elect()) {
#pragma unroll
            for (int r = 0; r < 2; r++) mbar_init(bars + (B_ROW + 2 * v + r) * 8, 1);
            asm volatile("fence.mbarrier_init.release.cluster;" ::: "memory");
#pragma unroll
            for (int e = 0; e < 2; e++) {
                if (e) { const int t0_ = clock(); while ((int)clock() - t0_ < EDELAY) __nanosleep(40); }
                mbar_expect(bars + (B_ROW + 2 * v + e) * 8, 4096);
#pragma unroll
                for (int r = 0; r < 2; r++)
                    asm volatile("cp.async.bulk.shared::cluster.global.mbarrier::complete_tx::bytes [%0], [%1], 2048, [%2];"
                                 :: "r"(xs + e * 4096 + r * 2048), "l"(p.x + (size_t)(128 * (c & 15) + 32 * v + 16 * r + 2 * (c >> 4) + e) * 1024),
                                    "r"(bars + (B_ROW + 2 * v + e) * 8) : "memory");
            }
        }
        __syncwarp();
        uint4 w4[4];
#pragma unroll
        for (int k = 0; k < 4; k++) w4[k] = ldg128(reinterpret_cast<const uint4*>(p.wr) + 32 * k + lane);
        {
            constexpr uint32_t ONE = 0x3F803F80u;
            const uint32_t zr = p.up_first >> 1;
            uint4 w5[4];
#pragma unroll
            for (int k = 0; k < 4; k++) {
                w5[k].x = w4[k].x + zr; w5[k].y = w4[k].y + zr; w5[k].z = w4[k].z + zr; w5[k].w = w4[k].w + zr;
                w4[k].x = cpy(w4[k].x, zr); w4[k].y = cpy(w4[k].y, zr); w4[k].z = cpy(w4[k].z, zr); w4[k].w = cpy(w4[k].w, zr);
            }
            const bool od = g & 1;
#pragma unroll 1
            for (int r2 = 0; r2 < 2; r2++) {
                mbar_wait(bars + (B_ROW + 2 * v + r2) * 8);
                TSL(43);
                float s1[2][4] = {}, q0[2][4] = {};
#pragma unroll
                for (int k = 0; k < 4; k++)
#pragma unroll
                    for (int r = 0; r < 2; r++) {
                        const uint4 x = lds128(xs + r2 * 4096 + r * 2048 + k * 512 + lane * 16);
                        const uint4& ww = r ? w5[k] : w4[k];
                        mma_bf16(q0[r], cpy(x.x, zr), ww.x, cpy(x.y, zr), ww.y, x.x, x.y);
                        mma_bf16(s1[r], x.x, x.y, x.z, x.w, ONE, ONE);
                        mma_bf16(q0[r], cpy(x.z, zr), ww.z, cpy(x.w, zr), ww.w, x.z, x.w);
                    }
#pragma unroll
                for (int r = 0; r < 2; r++)
                    if (q == (g >> 1))
                        sts128(sm + SM_RED + (4 * v + r2 + 2 * r) * 144 + g * 16, __float_as_uint(od ? q0[r][1] : q0[r][0]),
                               __float_as_uint(od ? q0[r][3] : q0[r][2]), __float_as_uint(s1[r][0]), __float_as_uint(s1[r][2]));
            }
            bar_arrive(7, 160);
        }
        TSL(8);
        bar_sync(6, 160);
        const uint32_t tag = lds32(sm + SM_TOK + 8);
        cluster_wait();
        asm volatile("setmaxnreg.dec.sync.aligned.u32 104;");
        const uint32_t peer = mapa(sm, rank ^ 1);
        if (v == 0 && lane == 0) mbar_arrive_peer(peer + SM_BAR + B_UFREE * 8);
        {
            uint4 st[8];
            const uint4* src = p.sc->stats[G & (NREP - 1)] + rank * 512 + 16 * v + (lane >> 1);
            const uint32_t tb = ((tag & 1) << 15) | ((tag >> 1) << 31);
            const uint32_t xo = pin(sm + SM_SLAB + v * 512 + lane * 16);
            const uint32_t ub = pin(mapa(bars + B_U * 8, lane & 1)), ud = pin(mapa(sm + SM_U + rank * SUB + (16 * v + (lane >> 1)) * 16, lane & 1));
            sched_fence();
            bar_sync(3, 192);
            if (warp == 8) TSL(44);
#pragma unroll
            for (int i = 0; i < 8; i++) st[i] = ld_relaxed128(src + (i >> 2) * 64 + (i & 3) * 128);
            uint4 x0[8];
            mbar_wait(bars + B_UFREE * 8);
            mbar_wait(bars + B_SLAB * 8);
#pragma unroll
            for (int i = 0; i < 8; i++) x0[i] = lds128(xo + (i & 1) * 8192 + (i >> 1) * 2048);
            for (int it = 0; it < SPIN_LIMIT; it++) {
                uint32_t bad = 0;
#pragma unroll
                for (int i = 0; i < 8; i++) bad |= st[i].z ^ tb;
                if (__all_sync(0xFFFFFFFFu, (bad & 0x80008000u) == 0)) break;
#pragma unroll
                for (int i = 0; i < 8; i++)
                    if ((st[i].z ^ tb) & 0x80008000u) st[i] = ld_relaxed128(src + (i >> 2) * 64 + (i & 3) * 128);
            }
            TSL(11); TG(31);
#pragma unroll
            for (int i = 0; i < 8; i++) st[i].z &= 0x7FFF7FFFu;
            uint32_t n[2][8][4];
#pragma unroll
            for (int i = 0; i < 4; i++) { n[0][i][0] = st[4 + i].x; n[0][i][1] = st[4 + i].y; n[0][i][2] = st[4 + i].z; }
#pragma unroll 1
            for (int b = 0; ; b++) {
#pragma unroll
                for (int i = 0; i < 8; i++) {
                    const uint4& t = st[i >> 1];
                    const uint32_t m = (i & 1) ? dup_hi(t.x) : dup_lo(t.x), hi = (i & 1) ? dup_hi(t.z) : dup_lo(t.z), lo = (i & 1) ? dup_hi(t.y) : dup_lo(t.y);
                    uint32_t (&r)[4] = n[1][i];
                    r[0] = norm2(x0[i].x, m, hi, lo); r[1] = norm2(x0[i].y, m, hi, lo); r[2] = norm2(x0[i].z, m, hi, lo); r[3] = norm2(x0[i].w, m, hi, lo);
                }
                sched_fence();
#pragma unroll
                for (int cp = 0; cp < 4; cp++) {
                    float f[8][2];
#pragma unroll
                    for (int i = 0; i < 8; i++) { f[i][0] = blo(n[1][i][cp]); f[i][1] = bhi(n[1][i][cp]); }
#pragma unroll
                    for (int h = 0; h < 2; h++)
                        st_async4(ud + (16 * b + 4 * cp + 2 * h) * SUB, pack_h(f[0][h], f[1][h]), pack_h(f[2][h], f[3][h]),
                                  pack_h(f[4][h], f[5][h]), pack_h(f[6][h], f[7][h]), ub + b * 8);
                    if (cp == 3) TSL(b ? 41 : 12);
                    if (cp >= FUSE) {
#pragma unroll
                        for (int i = 0; i < 8; i++) { n[1][i][cp] = pack_b(silu2(f[i][0]), silu2(f[i][1])); touch(n[1][i][cp]); }
                    }
                    sched_fence();
                }
#pragma unroll
                for (int cp = 0; cp < FUSE; cp++) {
#pragma unroll
                    for (int i = 0; i < 8; i++) {
                        uint32_t& r = n[1][i][cp];
                        r = pack_b(silu2(__uint_as_float(prmt(r, tag >> 2, 0x1044))), silu2(__uint_as_float(prmt(r, tag >> 2, 0x3244))));
                        touch(r);
                    }
                    sched_fence();
                }
                if (b) break;
                mbar_wait(bars + (B_SLAB + 1) * 8);
#pragma unroll
                for (int i = 0; i < 8; i++) {
                    if (i < 4) { st[i].x = n[0][i][0]; st[i].y = n[0][i][1]; st[i].z = n[0][i][2]; }
#pragma unroll
                    for (int k = 0; k < 4; k++) n[0][i][k] = n[1][i][k];
                    x0[i] = lds128(xo + 16384 + (i & 1) * 8192 + (i >> 1) * 2048);
                }
            }
            TSL(0);
            const int ln = (xo - sm) >> 4;
            const bool own = (ln & 1) == rank;
            const uint32_t stg = pin(sm + SM_U + (own ? 4 * SUB : 0) + (ln >> 4) * 512 + (((ln & 14) * 8) ^ (own ? 64 : 0)));
            const int tl = pin(16 * (ln >> 1) + 8 * rank);
            __nv_bfloat16* const op = p.out + (size_t)tl * 1024 + G * 16 + (ln & 1) * 8;
            mbar_wait(bars + B_TOK * 8);
            const uint2 tr = lds64(sm + SM_TOK);
            const int d0 = tr.x - tl, d1 = tr.y - tl;
            uint32_t skip = ((d0 & ~0x407) ? 0u : 1u << ((d0 & 7) + (d0 >> 7))) | ((d1 & ~0x407) ? 0u : 1u << ((d1 & 7) + (d1 >> 7)));
            auto put = [&](int b, int i, const uint4& x, uint32_t s0, uint32_t s1, uint32_t s2, uint32_t s3) {
                const uint32_t (&gt)[4] = n[b][i];
                asm volatile("{ .reg .pred p; setp.eq.u32 p, %5, 0; @p st.global.v4.u32 [%0], {%1,%2,%3,%4}; }"
                             :: "l"(op + (size_t)(1024 * b + i) * 1024), "r"(badd2(x.x, bmul2(s0, gt[0]))), "r"(badd2(x.y, bmul2(s1, gt[1]))),
                                "r"(badd2(x.z, bmul2(s2, gt[2]))), "r"(badd2(x.w, bmul2(s3, gt[3]))), "r"(skip & (1u << (8 * b + i))) : "memory");
            };
            mbar_wait(bars + B_STG * 8);
#pragma unroll
            for (int i = 0; i < 4; i++) {
                const uint32_t a = (stg ^ (32 * i)) + 128 * i;
                const uint4 r0 = lds128(a), r1 = lds128(a + 8 * SUB), xa = lds128(xo + i * 2048), xb = lds128(xo + 8192 + i * 2048);
                put(0, 2 * i, xa, r0.x, r0.y, r1.x, r1.y); put(0, 2 * i + 1, xb, r0.z, r0.w, r1.z, r1.w);
                sched_fence();
                if (i < 3) __nanosleep(STSLEEP);
            }
            TSL(22);
            uint4 x[8], r[2][4];
#pragma unroll
            for (int i = 0; i < 8; i++) x[i] = lds128(xo + 16384 + (i & 1) * 8192 + (i >> 1) * 2048);
            mbar_wait(bars + (B_STG + 1) * 8);
#pragma unroll
            for (int i = 0; i < 4; i++) r[0][i] = lds128((stg ^ (32 * (i >> 1))) + (16 + 8 * (i & 1)) * SUB + 128 * (i >> 1));
#pragma unroll
            for (int h = 0; h < 2; h++) {
#pragma unroll
                for (int i = 0; i < 2; i++) {
                    const uint4 &r0 = r[h][2 * i], &r1 = r[h][2 * i + 1];
                    if (!h) { r[1][2 * i] = lds128((stg ^ (64 + 32 * i)) + 16 * SUB + 256 + 128 * i); r[1][2 * i + 1] = lds128((stg ^ (64 + 32 * i)) + 24 * SUB + 256 + 128 * i); }
                    put(1, 4 * h + 2 * i, x[4 * h + 2 * i], r0.x, r0.y, r1.x, r1.y); put(1, 4 * h + 2 * i + 1, x[4 * h + 2 * i + 1], r0.z, r0.w, r1.z, r1.w);
                }
            }
            TSL(23);
            TSL(17); TG(30);
        }
    } else {
        const int v = warp - 12;
        if (lane == 0) {
            if (v == 1) {
                mbar_init(bars + B_TAB * 8, 1); mbar_init(bars + B_TFREE * 8, 8); mbar_init(bars + B_KFREE * 8, 8); mbar_init(bars + (B_KFREE + 1) * 8, 8);
                mbar_expect(bars + B_TAB * 8, 20480 + 1536);
            } else if (v == 0) {
                mbar_init(bars + B_SLAB * 8, 1); mbar_init(bars + (B_SLAB + 1) * 8, 1); mbar_init(bars + B_TOK * 8, 2); mbar_init(bars + B_UFREE * 8, 1);
                mbar_init(bars + B_SFREE * 8, 8); mbar_init(bars + B_SDONE * 8, 4);
                mbar_expect(bars + B_SLAB * 8, 16384); mbar_expect(bars + (B_SLAB + 1) * 8, 16384);
            } else {
                mbar_init(bars + (B_STG + v - 2) * 8, 9);
                mbar_init(bars + (B_U + v - 2) * 8, 1); mbar_expect(bars + (B_U + v - 2) * 8, 16384);
                mbar_expect(bars + (B_STG + v - 2) * 8, 8192);
                if (v == 2) { mbar_init(bars + B_PAIR * 8, 1); mbar_expect(bars + B_PAIR * 8, 1024); }
            }
            mbar_init(bars + (B_PEER + v) * 8, 4);
#pragma unroll
            for (int i = 0; i < 3; i++) { mbar_init(bars + (B_FULL + 3 * v + i) * 8, 1); mbar_expect(bars + (B_FULL + 3 * v + i) * 8, 16384); }
            asm volatile("fence.mbarrier_init.release.cluster;" ::: "memory");
        }
        __syncwarp();
        cluster_arrive();
        asm volatile("setmaxnreg.dec.sync.aligned.u32 56;");
        uint64_t pol; asm volatile("createpolicy.fractional.L2::" WPOL ".b64 %0, 1.0;" : "=l"(pol));
        auto load_chunk = [&](int n) {
            if (n < 8) tma3d(sm + chunk_off(n), &tm_g, G * 64, rank * 512 + n * 64, 0, bars + (B_FULL + n) * 8, pol);
            else tma3d(sm + chunk_off(n), &tm_d, 0, G * 64, rank * 8 + (n - 8) * 2, bars + (B_FULL + n) * 8, pol);
        };
        uint32_t* const my_part = p.sc->part + ((2 * (32 * rank + v) + (q & 1)) * 56 + G) * 16 + g + 8 * (q >> 1);
        if (G < 56) {
#pragma unroll
            for (int n = 0; n < 8; n++) st_relaxed32(my_part + n * 8 * 56 * 16, 0);
        }
        cluster_wait();
        const bool lead = elect();
        uint32_t key = 0;
        if (v == 0) {
            asm volatile("prefetch.tensormap [%0];" :: "l"(&tm_x) : "memory");
            asm volatile("prefetch.tensormap [%0];" :: "l"(&tm_g) : "memory");
            { const int t0_ = clock(); while ((int)clock() - t0_ < SDELAY) __nanosleep(40); }
            if (lead) {
                int n = 0;
#pragma unroll 1
                for (int i = 0; i < 5; i++) {
                    if (G < 56) {
#pragma unroll 1
                        for (; n < ((FILL >> (4 * i)) & 15); n++) {
                            if (n >= IDEPTH) mbar_wait(bars + (B_FULL + n - IDEPTH) * 8);
                            if (n == 3) mbar_wait(bars + B_TFREE * 8);
                            load_chunk(n);
                        }
                    }
                    if (i < 4)
                        asm volatile("cp.async.bulk.tensor.4d.shared::cluster.global.mbarrier::complete_tx::bytes [%0], [%1, {%3, %4, %5, %6}], [%2];"
                                     :: "r"(sm + SM_SLAB + (i & 1) * 16384 + (i >> 1) * 8192), "l"(&tm_x), "r"(bars + (B_SLAB + (i & 1)) * 8),
                                        "r"(G * 16), "r"(64 * (i & 1)), "r"(4 * rank), "r"(i >> 1) : "memory");
                }
                TS(20);
                if (G < 56) {
#pragma unroll 1
                    for (; n < NPRE; n++) {
                        mbar_wait(bars + (B_FULL + n - IDEPTH2) * 8);
                        mbar_wait(bars + (n < 7 ? B_SFREE : B_KFREE) * 8);
                        load_chunk(n);
                    }
                }
                TS(21);
            }
            __syncwarp();
        } else if (v == 1) {
            if (lead) {
                asm volatile("cp.async.bulk.shared::cluster.global.mbarrier::complete_tx::bytes [%0], [%1], 20480, [%2];"
                             :: "r"(sm + SM_TAB), "l"(p.tab), "r"(bars + B_TAB * 8) : "memory");
                asm volatile("cp.async.bulk.shared::cluster.global.mbarrier::complete_tx::bytes [%0], [%1], 1536, [%2];"
                             :: "r"(sm + SM_F2), "l"(p.tab + 1280), "r"(bars + B_TAB * 8) : "memory");
                asm volatile("prefetch.tensormap [%0];" :: "l"(&tm_d) : "memory");
            }
        } else {
            const int sw = v - 2;
            if (sw == 0) {
                uint32_t tag;
                uint4* const my_stats = p.sc->stats[q] + c * 8 + g;
                asm volatile("ld.relaxed.gpu.global.u32 %0, [%1];" : "=r"(tag) : "l"(&p.sc->epoch) : "memory");
                float ws = 0.f;
#pragma unroll
                for (int k = 0; k < 4; k++) {
                    const uint4 w = ldg128(reinterpret_cast<const uint4*>(p.wr) + 32 * k + lane);
                    ws += (blo(w.x) + bhi(w.x)) + (blo(w.y) + bhi(w.y)) + (blo(w.z) + bhi(w.z)) + (blo(w.w) + bhi(w.w));
                }
                if (q < NREP) st_relaxed128(my_stats, make_uint4(0, 0, 0, 0));
                tag = tag % 3 + 1;
                sts32(sm + SM_TOK + 8, tag);
                bar_arrive(6, 160);
#pragma unroll
                for (int o = 1; o < 32; o <<= 1) ws += __shfl_xor_sync(0xFFFFFFFFu, ws, o);
                const uint32_t tb = ((tag & 1) << 15) | ((tag >> 1) << 31);
                const uint32_t ra = sm + SM_RED + (lane >> 1) * 144 + (lane & 1) * 64;
                const uint32_t kidx = 0xFFFF - (128 * (c & 15) + 16 * (lane >> 2) + 2 * (c >> 4) + ((lane >> 1) & 1));
                touch(ws);
                bar_sync(7, 160);
                const uint4 a0 = lds128(ra), a1 = lds128(ra + 16), a2 = lds128(ra + 32), a3 = lds128(ra + 48);
#define F(v) __uint_as_float(v)
                float ss = (F(a0.x) + F(a1.x)) + (F(a2.x) + F(a3.x)), dw = (F(a0.y) + F(a1.y)) + (F(a2.y) + F(a3.y));
                float sx = ((F(a0.z) + F(a1.z)) + (F(a2.z) + F(a3.z))) + ((F(a0.w) + F(a1.w)) + (F(a2.w) + F(a3.w)));
#undef F
                ss += __shfl_xor_sync(0xFFFFFFFFu, ss, 1); dw += __shfl_xor_sync(0xFFFFFFFFu, dw, 1); sx += __shfl_xor_sync(0xFFFFFFFFu, sx, 1);
                const float mean = sx * (1.0f / 1024.0f);
                const float var = fmaxf(ss * (1.0f / 1024.0f) - mean * mean, 0.f);
                const float m = rb(mean);
                float sd; asm("sqrt.approx.ftz.f32 %0, %1;" : "=f"(sd) : "f"(rb(rb(var) + 1e-5f)));
                const float rs = rcp(rb(sd));
                const float hi = rb(rs);
                const uint32_t p0 = pack_b(m, 0.5f * hi), p1 = pack_b(0.5f * (rs - hi), rs * (dw - m * ws));
                const uint32_t o0 = __shfl_xor_sync(0xFFFFFFFFu, p0, 2), o1 = __shfl_xor_sync(0xFFFFFFFFu, p1, 2);
                const uint32_t kr = ((p1 ^ (p1 >> 31 ? 0xFFFF0000u : 0x80000000u)) & 0xFFFF0000u) | kidx;
                const uint32_t k1 = __reduce_max_sync(0xFFFFFFFFu, kr), k2 = __reduce_max_sync(0xFFFFFFFFu, kr == k1 ? 0u : kr);
                const uint32_t sl = (q & 2) ? 0x1054 : 0x5410;
                if (q < NREP) st_relaxed128(my_stats, make_uint4(prmt(p0, o0, sl), prmt(p1, o1, sl), (prmt(p0, o0, sl + 0x2222) & 0x7FFF7FFFu) | tb, g == 0 ? k1 : k2));
                TSL(9);
                { const int t0_ = clock(); while ((int)clock() - t0_ < PDELAY) __nanosleep(20); }
            }
            bar_sync(3, 192);
            const uint32_t tg = lds32(sm + SM_TOK + 8), tb = ((tg & 1) << 15) | ((tg >> 1) << 31);
            {
                const uint32_t* src = &p.sc->stats[G & (NREP - 1)][(sw * 64 + (lane >> 1)) * 8 + (lane & 1)].z;
                uint2 kz[4];
#pragma unroll
                for (int i = 0; i < 4; i++) kz[i] = make_uint2(~tb, 0);
                int it = 0;
                bool ok;
                do {
#pragma unroll
                    for (int i = 0; i < 4; i++)
                        asm volatile("{ .reg .pred p; .reg .b64 t; setp.ne.u32 p, %3, 0; mov.b64 t, {%0,%1};\n"
                                     "@p ld.relaxed.gpu.global.b64 t, [%2]; mov.b64 {%0,%1}, t; }"
                                     : "+r"(kz[i].x), "+r"(kz[i].y) : "l"(src + i * 512), "r"((kz[i].x ^ tb) & 0x80008000u) : "memory");
                    ok = __all_sync(0xFFFFFFFFu, (((kz[0].x ^ tb) | (kz[1].x ^ tb) | (kz[2].x ^ tb) | (kz[3].x ^ tb)) & 0x80008000u) == 0);
                } while (!ok && ++it < SPIN_LIMIT);
                const uint32_t a1 = max(kz[0].y, kz[1].y), b1 = max(kz[2].y, kz[3].y);
                const uint32_t h1 = max(a1, b1), h2 = __vimax3_u32(min(a1, b1), min(kz[0].y, kz[1].y), min(kz[2].y, kz[3].y));
                const uint32_t w1 = __reduce_max_sync(0xFFFFFFFFu, h1), w2 = __reduce_max_sync(0xFFFFFFFFu, h1 == w1 ? h2 : h1);
                sts64(sm + SM_KEYS + sw * 8, w1, w2);
                bar_sync(8, 64);
                const uint2 o = lds64(sm + SM_KEYS + 8 - sw * 8);
                key = sw ? __vimax3_u32(min(w1, o.x), w2, o.y) : max(w1, o.x);
                TSL(19);
            }
            const int t = (0xFFFF - (key & 0xFFFF)) & 2047;
            {
                const uint4* row = reinterpret_cast<const uint4*>(p.x + (size_t)t * 1024);
                uint4 xr[3];
                xr[0] = ldg128(row + 64 * rank + lane); xr[1] = ldg128(row + 64 * rank + 32 + lane); xr[2] = ldg128(row + 2 * G + (lane & 1));
                uint4 stk;
                int it = 0;
                do stk = ld_relaxed128(p.sc->stats[G & (NREP - 1)] + ((t >> 1) & 7) * 128 + (t >> 4)); while (((stk.z ^ tb) & 0x80008000u) && ++it < SPIN_LIMIT);
                if (lane == 0) {
                    sts32(sm + SM_TOK + 4 * sw, t);
                    if (c == 0 && sw == 0) st_relaxed32(&p.sc->epoch, tg);
                }
                const uint32_t se = (t & 1) ? 0x3232 : 0x1010;
                const uint32_t m = prmt(stk.x, 0, se), hi = bmul2(prmt(stk.z, 0, se) & 0x7FFF7FFFu, 0x40004000u), lo = bmul2(prmt(stk.y, 0, se), 0x40004000u);
                const uint32_t a = sm + SM_XSEL + lane * 32 + sw * 16;
#pragma unroll
                for (int i = 0; i < 2; i++)
                    sts128(a + i * 1024, norm2(xr[i].x, m, hi, lo), norm2(xr[i].y, m, hi, lo), norm2(xr[i].z, m, hi, lo), norm2(xr[i].w, m, hi, lo));
                proxy_fence();
                __syncwarp();
                if (lane == 0) mbar_arrive(bars + B_TOK * 8);
                if (lane < 2) {
                    sts128(sm + SM_XRAW + sw * 64 + lane * 16, xr[2].x, xr[2].y, xr[2].z, xr[2].w);
                    sts128(sm + SM_XRAW + sw * 64 + 32 + lane * 16, norm2(xr[2].x, m, hi, lo), norm2(xr[2].y, m, hi, lo), norm2(xr[2].z, m, hi, lo), norm2(xr[2].w, m, hi, lo));
                }
                __syncwarp();
                TSL(42);
            }
        }
        const uint32_t po = pin(sm + SM_PAIR + v * 256 + lane * 4), pd = pin(mapa(po, rank ^ 1)), pb = pin(mapa(bars + B_PAIR * 8, rank ^ 1));
        const uint32_t hd = pin(sm + SM_H + (2 * v + (q >> 1)) * 128 + (q & 1) * 32 + g * 2);
        const bool upf = pin(p.up_first);
        mbar_wait(bars + B_TOK * 8);
        const uint32_t tag = lds32(sm + SM_TOK + 8);
        {
            if (G < 56) {
                const uint32_t SMB = sm & 0x3FFFFu;
                const uint64_t dw = (uint64_t)(SMB >> 4) | (1ull << 16) | (64ull << 32) | (1ull << 62);
                const uint64_t dx = (uint64_t)((SMB + SM_XSEL) >> 4) | (2ull << 16) | (8ull << 32);
                const uint64_t dh = (uint64_t)((SMB + SM_H) >> 4) | (8ull << 16) | (8ull << 32);
                const uint64_t dw2 = dw + (tag >> 2);
                float ag[4], au[4];
                TSL(13);
#pragma unroll
                for (int st = 0; st < 8; st++) {
                    const int n = (ORDER >> (4 * st)) & 15;
                    const uint64_t a = dw + (chunk_off(n) >> 4), b = dx + n * 16;
                    mbar_wait(bars + (B_FULL + n) * 8);
                    wg_fence();
                    if (st == 0) { wg_w0(ag, a, b); wg_w0(au, a + 512, b); } else { wg_w<1>(ag, a, b); wg_w<1>(au, a + 512, b); }
#pragma unroll
                    for (int k = 1; k < 4; k++) { wg_w<1>(ag, a + 128 * k, b + 4 * k); wg_w<1>(au, a + 512 + 128 * k, b + 4 * k); }
                    wg_commit();
                    if (st == 0 && v == 0) {
                        mbar_wait(bars + (B_KFREE + 1) * 8);
                        if (lead) {
#pragma unroll
                            for (int i = NPRE; i < 9; i++) load_chunk(i);
                        }
                        __syncwarp();
                    }
                    bool any = false;
#pragma unroll
                    for (int i = 0; i < 3; i++) any |= ((REFILL >> (4 * i)) & 15) == st;
                    if (any) {
                        wg_wait<1>(); bar_sync(4, 128);
                        if (v == (st & 3)) {
#pragma unroll
                            for (int i = 0; i < 3; i++) if (((REFILL >> (4 * i)) & 15) == st && lead) load_chunk(9 + i);
                            __syncwarp();
                        }
                    }
                    if (st == SDAT) { wg_wait<1>(); if (lane == 0) mbar_arrive(bars + B_SDONE * 8); }
                    if (st == SDAT) TSL(4);
                }
                wg_wait<0>();
                touch(ag); touch(au);
                TSL(14);
                if (q == 0) {
                    st_async4(pd, __float_as_uint(ag[0]), __float_as_uint(ag[1]), __float_as_uint(ag[2]), __float_as_uint(ag[3]), pb);
                    st_async4(pd + 128, __float_as_uint(au[0]), __float_as_uint(au[1]), __float_as_uint(au[2]), __float_as_uint(au[3]), pb);
                    sts128(po + 1024, __float_as_uint(ag[0]), __float_as_uint(ag[1]), __float_as_uint(ag[2]), __float_as_uint(ag[3]));
                    sts128(po + 1152, __float_as_uint(au[0]), __float_as_uint(au[1]), __float_as_uint(au[2]), __float_as_uint(au[3]));
                }
                __syncwarp();
                {
                    const float a0 = __uint_as_float(lds32(po + 1024)), a1 = __uint_as_float(lds32(po + 1152));
                    mbar_wait(bars + B_PAIR * 8);
                    const uint32_t gu = pack_b(a0 + __uint_as_float(lds32(po)), a1 + __uint_as_float(lds32(po + 128)));
                    const float gs = upf ? bhi(gu) : blo(gu), us = upf ? blo(gu) : bhi(gu);
                    const float hv = rb(siluf_(gs)) * us;
                    const uint32_t hb = pack_b(hv, hv);
                    sts16(hd, hb); sts16(hd + 64, hb);
                }
                proxy_fence();
                bar_sync(4, 128);
                TSL(15);
                float d[2][2][4];
#pragma unroll
                for (int n = 0; n < 5; n++) {
                    if (n < 4) {
                        const uint64_t a = dw2 + (chunk_off(8 + n) >> 4);
                        mbar_wait(bars + (B_FULL + 8 + n) * 8);
                        if (n == 3) TSL(24);
                        wg_fence();
                        wg_w0(d[n & 1][0], a, dh); wg_w0(d[n & 1][1], a + 512, dh);
#pragma unroll
                        for (int k = 1; k < 4; k++) { wg_w<1>(d[n & 1][0], a + 128 * k, dh + 16 * k); wg_w<1>(d[n & 1][1], a + 512 + 128 * k, dh + 16 * k); }
                        wg_commit();
                    }
                    if (n > 0) {
                        if (n < 4) wg_wait<1>(); else wg_wait<0>();
#pragma unroll
                        for (int i = 0; i < 2; i++) {
                            float (&r)[4] = d[(n - 1) & 1][i];
                            touch(r);
                            st_relaxed32(my_part + (2 * n - 2 + i) * 8 * 56 * 16, (__float_as_uint((q & 2) ? r[2] : r[0]) & ~3u) | tag);
                        }
                    }
                }
                TSL(16);
            } else {
                if (lane == 0) mbar_arrive(bars + B_SDONE * 8);
                mbar_wait(bars + B_STG * 8);
            }
            const int k = v & 1, t = lds32(sm + SM_TOK + 4 * k);
            if (((t >> 3) & 1) == rank) {
                const uint2* src = reinterpret_cast<const uint2*>(p.sc->part) + (2 * G + k) * 448 + (v >> 1) * 224 + lane;
                const int col = lane & 15, tq = (t >> 1) & 3;
                float sg = rb(sigmoidf_(__uint_as_float((key & 0x80000000u) ? (key & 0x7FFF0000u) : (~key & 0xFFFF0000u))));
                float xn = blo(lds16(sm + SM_XRAW + k * 64 + 32 + col * 2)), xv = blo(lds16(sm + SM_XRAW + k * 64 + col * 2));
                const bool own = (col >> 3) == rank;
                const uint32_t sa = pin(sm + SM_U + (16 * (t >> 10) + 8 * ((col >> 2) & 1) + (own ? 4 : 0)) * SUB + ((t >> 7) & 7) * 512 + 128 * tq
                                        + ((t & 0x70) ^ (32 * tq) ^ (own ? 64 : 0)) + (t & 1) * 8 + (col & 3) * 2);
                const uint32_t ra = pin(sm + SM_XSEL + k * 512 + lane * 4), wa = pin(sm + SM_XSEL + k * 512 + (v >> 1) * 256 + lane * 8);
                __nv_bfloat16* const op = p.out + pin(t * 1024 + G * 16 + col);
                touch(sg); touch(xn); touch(xv);
                sched_fence();
                uint2 pv[7] = {};
                for (int it = 0; it < SPIN_LIMIT; it++) {
#pragma unroll
                    for (int i = 0; i < 7; i++)
                        if (((pv[i].x ^ tag) | (pv[i].y ^ tag)) & 3)
                            asm volatile("ld.relaxed.gpu.global.v2.u32 {%0,%1}, [%2];" : "=r"(pv[i].x), "=r"(pv[i].y) : "l"(src + 32 * i) : "memory");
                    uint32_t bd[7];
#pragma unroll
                    for (int i = 0; i < 7; i++) { bd[i] = (pv[i].x ^ tag) | (pv[i].y ^ tag); touch(bd[i]); }
                    const uint32_t bad = (bd[0] | bd[1] | bd[2]) | (bd[3] | bd[4] | bd[5]) | bd[6];
                    if (__all_sync(0xFFFFFFFFu, (bad & 3) == 0)) break;
                }
#define F(v) __uint_as_float(v)
                sts64(wa, __float_as_uint(((F(pv[0].x) + F(pv[1].x)) + (F(pv[2].x) + F(pv[3].x))) + ((F(pv[4].x) + F(pv[5].x)) + F(pv[6].x))),
                      __float_as_uint(((F(pv[0].y) + F(pv[1].y)) + (F(pv[2].y) + F(pv[3].y))) + ((F(pv[4].y) + F(pv[5].y)) + F(pv[6].y))));
                if (v < 2) {
                    if (k) bar_arrive(13, 64); else bar_arrive(12, 64);
                } else {
                    mbar_wait(bars + (B_STG + (t >> 10)) * 8);
                    const float s = blo(lds16(sa));
                    if (k) bar_sync(13, 64); else bar_sync(12, 64);
                    TSL(25);
                    float y = (F(lds32(ra)) + F(lds32(ra + 128))) + (F(lds32(ra + 256)) + F(lds32(ra + 384)));
#undef F
                    y += __shfl_xor_sync(0xFFFFFFFFu, y, 16);
                    const float z = rb(xn + rb(rb(y) * sg));
                    if (lane < 16) *op = __float2bfloat16(xv + rb(s * rb(siluf_(z))));
                }
                TSL(26); TG(29);
            }
        }
    }
    }
}

__device__ __align__(128) const uint32_t g_tab[5504] = {
0x2fff3000,0x2e7c2fd4,0x2fc92fd4,0xad72af5a,0x2ff82ffc,0x230e2c07,0x2faf2fbc,0x217ea934,0x2fed2ff4,0xad4da8d5,0x2f912fa0,0x2e5e2bb7,
0x2fdd2fe6,0xb000af46,0x2f6e2f80,0x2fdd2fc9,0x2ff42fff,0x2e1f2fc9,0x2e1f2e7c,0xa875ad72,0x2fbc2fdd,0x9fd92a4e,0x2d4d2dba,0x2cd825db,
0x2f5a2f91,0xaeb5ac07,0x2c5d2cd8,0x30002f30,0x2ed02f1a,0xaf80aff4,0x2aaa2bb7,0x2cb02f1a,0x2fdd2ffc,0x2dba2fbc,0x2a4e2c07,0x25dba934,
0x2f462fa0,0xa7652875,0x25152875,0x2f802d27,0x2e3f2ed0,0xafa0ad72,0xa17e1cb6,0x2e3f2fe6,0x2cd82d96,0xadfeafd4,0xa934a6a1,0xa44e29f1,
0x2fbc2ff8,0x2d4d2faf,0x9fd9230e,0x2cd8217e,0x2e992f46,0xaa4e2515,0xaa4ea765,0x2fd42f80,0x2cb02dba,0xafffae99,0xad72ac5d,0x27652dba,
0x28752b05,0xab5eaee9,0xaf1aae5e,0xae3fa934,0x2f912ff4,0x2cd82fa0,0xac07a8d5,0x2f302bb7,0x2dba2ed0,0xac5d1cb6,0xae99ad72,0x2dba2fe6,
0x29932c5d,0xafc9af6e,0xafe6af6e,0xaaaa25db,0xa17e244e,0xa30ead4d,0xafafaffc,0xaff8aee9,0x2f5a2fed,0x2c5d2f91,0xaeb5ad4d,0x30002e5e,
0x2cb02e3f,0xad72a17e,0xafffafa0,0x27652e3f,0x217e2993,0xaf02afe6,0xaf02afc9,0xaf1aaaaa,0xab05a5db,0x2814aa4e,0xac07adba,0xad4dafdd,
0x2f1a2fe6,0x2bb72f80,0xaff4af46,0x2f1a2fc9,0x2b052d96,0xae5ea6a1,0xaee9afd4,0xa93429f1,0xa5db244e,0xadbaaffc,0xaa4ead4d,0xafddaee9,
0xaddcabb7,0x2cb0a17e,0x2765a17e,0x1cb6ad00,0x2ed02fdd,0x2aaa2f6e,0xaf80b000,0x2cb02fdd,0x28752cd8,0xaf1aa934,0xab5eadfe,0xae3fa44e,
0xab05a17e,0xac07afaf,0x2814a30e,0xad4daff8,0xaf6eaddc,0x2eb52765,0x2eb52cb0,0x2dba1cb6,0x29932f5a,0xa7652e99,0x25152e99,0x2aaaad96,
0xafa0ab05,0xabb7afed,0xaff4acd8,0x28d52ffc,0xa814af02,0x2f912d27,0x9fd9ae1f,0xaee9ae3f,0x2fd42c32,0xaf5a1cb6,0x30002d72,0x2fd42515,
0x28752f46,0xa8d52e7c,0xa8d52c32,0x2e3fa993,0xafedac5d,0xa934b000,0xaf30af5a,0xa8142eb5,0x1648adfe,0x2e992e5e,0x2c87a814,0xa9f1affc,
0x2fe62e1f,0xafffa875,0x2ddc2ff4,0x2ed02e1f,0x26a12f30,0xa9f12e5e,0xad96244e,0x2fd41fd9,0xafffad27,0xa515aff4,0xac32aff4,0xaddc2b5e,
0x2875acb0,0x2d272f46,0x2fa02993,0x2875aed0,0x2ee92f6e,0xaf91ac87,0x1fd92e99,0x28143000,0x244e2f1a,0xab052e3f,0xaf91a875,0x2fbc2b5e,
0xafd4addc,0x1648afc9,0x1648ae7c,0xafdd9cb6,0x2c32aa4e,0x2aaa2fd4,0x2f802e99,0x2e7caa4e,0x2d002ffc,0xae1fae5e,0xad272814,0xabb72dfe,
0x1fd92f02,0xac072e1f,0xafedad27,0x2dfe2e3f,0xaf6eae7c,0x25dbaf80,0x2c5daaaa,0xaf6eac32,0x2ddca5db,0x25153000,0x2c323000,0x2fff26a1,
0x28d52fbc,0xabb7af91,0xaff4ab05,0xafa0244e,0x96482ee9,0xac872dfe,0xae99af30,0x29f12fbc,0xaed0af02,0x2993af1a,0x2f46217e,0xacb0af02,
0x2f1a1cb6,0xa30e2fc9,0xa30e2e7c,0x2e1f2ddc,0x9fd92eb5,0xa44eb000,0xae5eaf5a,0xaf30ac5d,0xa17e2ed0,0xad002ddc,0xabb7afff,0xa17e2fe6,
0xadfeaf6e,0x2c07ae99,0x2fed2c87,0x9fd9b000,0x2fd42814,0xa9f12f30,0xad962934,0x26a12fed,0xaaaa2d00,0x2765afa0,0xa515afa0,0xa993afaf,
0xa5152eb5,0xad722dba,0x9cb6af6e,0xac322eb5,0xad00afbc,0x2d27adfe,0x2e1f2f30,0x2bb7aee9,0x2ffc2b5e,0xacd82e3f,0xafeda875,0xab052f1a,
0xadba2993,0x2c87ae7c,0x2c87ac32,0x2a4eaf46,0xaddc2d96,0xafe62c5d,0xaed02c5d,0x2fffa9f1,0x2e1fad4d,0x2e3f2814,0x2f02ac07,0xad27ab05,
0xae5e2d00,0x9fd9af1a,0xaf302b5e,0xa44e2faf,0x2e99acb0,0xad962f80,0x2f5aaaaa,0x2e99aed0,0xae3f2d72,0xaff82c32,0xaff82515,0x2f021cb6,
0x2ee9ac87,0x2d4d29f1,0x2ffc9648,0xa44eae99,0xaf6e2b05,0x26a1afbc,0xafd4a44e,0xadba2f91,0x2fc9a8d5,0xaf462e3f,0x2f802875,0x2fe6a8d5,
0xae992d4d,0xb0002c07,0xaf6ea814,0x2c872b05,0x2f80ab5e,0x2c322bb7,0x2e7c2bb7,0x2aaaaff8,0xaff42765,0x2b5eafff,0xad27ad72,0xaff42cb0,
0x2fed1648,0xaffc2c5d,0x2b052eb5,0x2cd82a4e,0xaee92d27,0xaffc2bb7,0xad4dad00,0x244e2e1f,0x2fdda993,0x29f12cb0,0x29f12ed0,0x2eb5af46,
0xafe61648,0x2d72afdd,0x9cb6afd4,0xaed01648,0x2f022934,0xafa02814,0xa8d52fed,0xa30e2f30,0xaf302d00,0xafed2b5e,0xa814af1a,0xa9342faf,
0x3000a765,0x26a12d72,0xa5db2fff,0x3000acb0,0xaf46a6a1,0x2ed0af5a,0x2cb0af5a,0xa993ac87,0x2d272cd8,0xae3f9fd9,0xaf022d4d,0xae1f2fbc,
0xaf6e2cd8,0xafd42b05,0x26a1affc,0xadba2fed,0x2fe6a30e,0x1cb62e1f,0xad722f1a,0x2ed0a30e,0xae1faaaa,0x2fafae7c,0x2fafac32,0x28d5af80,
0x29342e99,0xac07a9f1,0xafbc1648,0xaffc2c87,0xafa02cb0,0xafaf2aaa,0x2d00af80,0xafa02ed0,0x2f911648,0xa44e2eb5,0xafbc2c5d,0x2b052a4e,
0xac87acd8,0x3000ad4d,0x2f6e1fd9,0x2e99afbc,0x9cb62faf,0xa515ad27,0xac32ad27,0xad72a30e,0xafc92c87,0xaf802a4e,0x2f46adba,0xafe62c87,
0x2f02244e,0xa8d52f30,0xafa01fd9,0xa30e2e5e,0xa934ae1f,0x2fbcabb7,0x2c072d00,0x2ffcad27,0xaa4e2fff,0x26a1aed0,0x26a1afe6,0x1648addc,
0xaf4629f1,0xac3225db,0xae7c25db,0x29931648,0xab5e2f91,0xafaf2e5e,0xad002fed,0x2f1aad4d,0x2ee9a875,0xaf302ff8,0x2dfea17e,0x2fbcaff4,
0x2c5dafc9,0xa9f12d72,0x2d96afff,0x2c5dae7c,0xaf022993,0xab5e2515,0xab5ea765,0xa30e2aaa,0xacd82fd4,0xaf302dba,0xaf912f6e,0x2c07a6a1,
0x2d969fd9,0xafdd2fed,0x25db2c07,0x2f5aadfe,0x2e7caff8,0xad722f02,0x2fffae3f,0x2fc9aff8,0xaeb52934,0xaa4e244e,0x9648acd8,0xac5d2dfe,
0xaddc2ff8,0xae7c2d00,0xafc92d00,0x9cb628d5,0x2bb72515,0xaff82f80,0xab5e2f46,0x2bb7a765,0x2fbcaf5a,0xaf302fdd,0x2dfea5db,0x2ee9ad96,
0xae5e28d5,0xa934230e,0x2b05af02,0xaee92fa0,0xaeb52fff,0xad962c32,0xad962515,0xac872ddc,0x276529f1,0xaf802eb5,0xaf462fdd,0xa51529f1,
0x2ff4adfe,0xaff82fed,0x217e2c07,0x28759fd9,0xadfe2875,0xa814217e,0x2e5eaff8,0xaffc2ff4,0xaf5a2fe6,0xac872aaa,0xa6a1a993,0xaf5a2fc9,
0x9cb62c87,0xae7c2d96,0xafc92d96,0xaddc2eb5,0x2f1aac07,0xafaf2f30,0xad002f91,0xab5e2cd8,0xad962814,0xa5db1fd9,0x2fddaf91,0xaf5a2ee9,
0xafc92faf,0xaaaa28d5,0x2993ae1f,0xafe62faf,0xa8d52ddc,0xad002c32,0xad002515,0xaff82fff,0x2d4da6a1,0xae5e2dba,0xafed2f6e,0xaf912fd4,
0xad272765,0xa30e1cb6,0x2fafaddc,0xad272cb0,0xaffc2f5a,0xa81425db,0x2e5eafdd,0xadfe2d96,0xac5d2ee9,0xaa4e2934,0x9648ab05,0xaeb52e5e,
0x2993230e,0xac322b5e,0xae7c2b5e,0xaf462f02,0xacb026a1,0x9cb61648,0x2ddcaa4e,0xa76526a1,0xaff42ee9,0xa17e1fd9,0x2ff8af91,0xa8752814,
0xadfe2fa0,0xa44e230e,0x2cd8af02,0xa93428d5,0x96482aaa,0xa5db2515,0xa5dba765,0xa9f12993,0x2f462f5a,0x2c322e99,0x2e7c2e99,0xa993ad96,
0x2f1a2f30,0xa875244e,0x2e3f2e5e,0x2b5e1fd9,0x2ee92f02,0xaf30ad27,0x2dfe2e1f,0x2fbc2e3f,0x2eb52ed0,0xaf6eafff,0x2dba2ddc,0x2eb52fe6,
0x28752993,0xa8d52515,0xa8d5a765,0x2e3f2aaa,0x244e26a1,0xaf91ad96,0xab05a9f1,0x2fbc2fd4,0x96481fd9,0xae99afed,0xac87ac07,0x29f12dfe,
0xa515a17e,0x9cb6abb7,0xad72ad00,0xac32a17e,0xac5dab05,0xaf5aacd8,0xb000afed,0x2eb52ffc,0xaddcad27,0xae7caff4,0xafc9aff4,0x9cb62b5e,
0xaf02ae7c,0x217eaaaa,0xaf1aaf80,0xaf02ac32,0xafbcaf6e,0x2f302c87,0xadfeae99,0xaee9b000,0xafedafa0,0xaf30aff4,0xa934abb7,0xa81428d5,
0xafd4afff,0x1648ac32,0x1648a515,0xafddaddc,0xaed0af6e,0x2f462c5d,0x299325db,0xacb0af6e,0xad00adfe,0x2e1f2fed,0x2d272c07,0x2bb79fd9,
0xadfeaf02,0xa814ae1f,0x2e5e2d27,0xaffcae3f,0xaa4eacb0,0x2e992993,0x2fd42f46,0xaa4eaed0,0x1cb6a5db,0x2e7c3000,0x2fc93000,0x2ddc26a1,
0x2b5e2814,0xa8752934,0x2e3f2f30,0x2f1a2fed,0x1648a814,0x2c879fd9,0x2e992f91,0xa9f1aee9,0x2c322875,0x2f802fa0,0x2aaa2d27,0x2e7c2875,
0x2f1a2ddc,0xa30e2c32,0xa30e2515,0x2e1f2fff,0x2ffc2fd4,0xafedad96,0xacd8a9f1,0xab0526a1,0x2e1f2c32,0x2ff42d72,0xa8751cb6,0x2e1f2515,
0x2ffc2f6e,0x28142e99,0xae5eac87,0x2dfe3000,0x2eb52fbc,0xaf5aab05,0xb000af91,0xac5d244e,0x29932d00,0xac32afa0,0xae7cafa0,0xaf46afaf,
0x2fe62fd4,0x2ddc3000,0xafffaf5a,0x2ed02fd4,0x2d002ee9,0xad271fd9,0xae1faf91,0xabb72814,0x9fd928d5,0xae5eaff4,0xa44eabb7,0xaf30afa0,
0xadbaaaaa,0x2c87a515,0x2c872765,0x2a4ea993,0x9cb62d96,0xacb02c5d,0xa7652c5d,0x2ddca9f1,0xaff8adfe,0xa30eafbc,0xafafaee9,0xa17e2f30,
0x244ead00,0x2dfe2f1a,0x2934ab5e,0xacd8afaf,0x2fdd2e7c,0xb000a993,0x2f6e2f46,0x2fdd2c32,0xae3f9cb6,0xaff8a765,0xaff8acb0,0x2f022ddc,
0xac07afdd,0x2dfeaa4e,0x1fd9adba,0xafeda5db,0x2f6e2934,0xa6a12ee9,0x2fd42e5e,0x2dbaab05,0x27652f1a,0xaaaaaff4,0xa9932bb7,0xa5152f1a,
0xafddadfe,0xadbaaee9,0xaa4eafbc,0xa5db2f30,0x2aaaab5e,0x2fc92bb7,0x2fe62bb7,0xa993aff8,0x2e3f2fc9,0xafa01cb6,0xa17e2ddc,0x2e3f2e7c,
0xae5e9648,0x2d4dac5d,0xaf91aeb5,0xafedaa4e,0xac07aff8,0x1fd9afaf,0x2dfea30e,0xafeda17e,0x2fdd2aaa,0x29f12fe6,0x29f12fc9,0x2eb5a993,
0xa5152dba,0xaddcae99,0xafffac5d,0xac322dba,0xaf02af30,0x2fa02c07,0x28d5acd8,0x230eaf91,0x2934ad00,0x2e5eab5e,0x2ee92f1a,0xab05afaf,
0x2dba2fc9,0xac5d2ddc,0xae991cb6,0x2dba2e7c,0xaf80a6a1,0x2765af5a,0xa515af5a,0xaf46ac87,0x217eae5e,0x230e2ffc,0x2faf2dfe,0x2ff82814,
0x2f6e244e,0x2fd42934,0xa6a12dfe,0x2dbaacd8,0xa5152e3f,0xafffa17e,0xaddcafa0,0xac322e3f,0xae1faf80,0x2fafa515,0x2faf2765,0x28d5af46,
0x2f9125db,0xaee92a4e,0xa8142dba,0x9fd92fdd,0x2f1a2e7c,0x2bb72f46,0xaff4a993,0x2f1a2c32,0xaf309648,0xacd8aeb5,0x2c07ac5d,0xaf91aa4e,
0x25dbae5e,0x2dba2dfe,0x2a4e2ffc,0x2fdd2814,0x2d722faf,0xae7cad27,0xafc9ad27,0xafffa30e,0x27652fdd,0xa9932f6e,0xaaaab000,0xa5152fdd,
0xaf02ae5e,0x28d5af91,0x2fa02d4d,0x230eafed,0x2f91217e,0xa8142faf,0xaee9230e,0x9fd92ff8,0xaa4e2d72,0x26a1afc9,0x26a1ae7c,0x1648afff,
0xaf8029f1,0xafc925db,0xafe625db,0x2f461648,0x2fa0a934,0x2bb72cd8,0x2ff4a44e,0xa8d5adfe,0xafbc2875,0x2934aff8,0xaffc217e,0xac072ff4,
0x2fd4a765,0xaf5a2ddc,0x30009cb6,0x2fd4acb0,0xaf02aaaa,0xab5eacb0,0xab5eaed0,0xa30e2f80,0x2e5e2c5d,0xab053000,0x29342f5a,0x2ee9aeb5,
0xad96ad4d,0x2fddacd8,0xa5dbafbc,0xaf5a1fd9,0x2cb02e1f,0xaddca875,0x1cb62ff4,0x27652e1f,0xa6a1af91,0x29f1afed,0x2d96ae5e,0xafd42d4d,
0x9cb62ff8,0xafe62d00,0xaed02d00,0x2d7228d5,0x2875afe6,0x2d272993,0x2fa0aaaa,0x2875afc9,0xac072f5a,0x2934afdd,0xaffc25db,0xafbc2d96,
0x2cd8af1a,0x2f91ae3f,0x2f302875,0xac07ab5e,0xaeb52d72,0xad96a765,0xad96acb0,0xac872fff,0x2fc9aa4e,0xa9932fd4,0x2aaa2e99,0x2fe6aa4e,
0xaff41fd9,0x2ff8acd8,0xa17eafbc,0xa875ad4d,0x2ffca875,0x2ee9a17e,0xa44e2ff8,0x2d4daff4,0xaf6ea515,0x25dbaf46,0x2c5daf80,0xaf6e2765,
0x2d722c87,0xafe62d96,0xaed02d96,0x9cb62eb5,0xa8d5aee9,0x2bb72b05,0x2ff4a934,0x2fa0ae5e,0x2d962c07,0x25db2d4d,0xafdd2b05,0x2f5aa814,
0xa765af02,0x2f46af1a,0x2f80217e,0x2515af02,0xa8d52fff,0xad00a765,0xad00acb0,0xaff82d72,0x2dfeaeb5,0xacd83000,0x244e2f5a,0x29342c5d,
0xa17e2fc9,0xad002fff,0xabb7ad72,0xa17e2e7c,0x2d4daf5a,0x2ee9a5db,0xa44e2fdd,0x2ffcad96,0xafd42c07,0x29f1af91,0x2d96af30,0xa6a1acd8,
0x2f46230e,0xafc92b5e,0xafe62b5e,0xaf802f02,0xae7c2eb5,0xafff2dba,0x2d72af6e,0xafc92eb5,0x2ff4a814,0x217e2d4d,0xaff82b05,0x28752c07,
0xad4dab5e,0x2fedae3f,0x2e5e2875,0x2f91af1a,0x96482f80,0xa5dbacb0,0xa5dbaed0,0xa9f1aaaa,0xad729648,0xa515a6a1,0xac32a6a1,0x9cb62a4e,
0xae1f2ffc,0xae3f2c07,0xaf022fbc,0x2d27a934,0x2cd8230e,0xaffc2fa0,0x2b0528d5,0x2fedaf02,0x2e99afe6,0xad962f46,0x2f5aaf80,0x2e99afc9,
0x230eaddc,0x2d27aed0,0x2d27afe6,0xafaf2fff,0xafbc2c87,0x1fd9a9f1,0xad4d1648,0xacd82e99,0xaa4e2f30,0xac5d2814,0xaeb52fed,0x96482934,
0x2ed0a8d5,0xaf802e3f,0x2aaa2875,0x2cb0a8d5,0x2e99affc,0x3000afbc,0x2f6eac07,0xac872934,0xa993a8d5,0x2ed0afaf,0x2cb0afaf,0xaf462e1f,
0xaff42ed0,0x2b5ead72,0xad271cb6,0xaff42fe6,0xa44e2dba,0x9fd9a6a1,0xaf302fd4,0xae5e2f6e,0x2fbcad27,0x2d4dabb7,0x9fd92d00,0x2cd8ae1f,
0x2c87af80,0x2f5aae7c,0x2f5aac32,0x26a1aaaa,0xacb01648,0x2fffafdd,0x2d72afd4,0xa7651648,0xafaf2f91,0x2f1aafbc,0xab5ea44e,0xad002b05,
0x2b05230e,0xa44e28d5,0xafbc2fa0,0x2f91af02,0x3000aed0,0x26a19cb6,0xa5db2d72,0x3000afe6,0x2aaaaeb5,0x2c32a9f1,0x2e7ca9f1,0x2f80afdd,
0xad27244e,0x2e3fad4d,0x2f02affc,0x2e1faee9,0xaa4e2e5e,0xaeb52f30,0xac5d1fd9,0x9648244e,0x2cb0a30e,0xad722e1f,0xafff2f1a,0x2765a30e,
0x2ff8af46,0xabb72cb0,0xabb72ed0,0x2b5ea993,0x2b05ae99,0xa81429f1,0x2c079648,0x2d4dac87,0xafa02fe6,0xafaf2f80,0x2d00af46,0xafa02fc9,
0xa9342dba,0xafed2fd4,0xa814a6a1,0xaf302f6e,0x2c87a44e,0xb0002ffc,0xaf6e2d4d,0xae992ee9,0x2fffaf02,0xafe62ff8,0xaed02ff8,0xaddc2e3f,
0xaed02c87,0xaaaa2a4e,0x2f80adba,0xacb02c87,0xafaf2fed,0xab5e2b05,0x2f1aaffc,0xad002cd8,0xab052e1f,0xac072bb7,0x2814ad00,0xad4d2d27,
0x29f11cb6,0xac5d2c32,0xac5d2515,0xad962d72,0x2d722d96,0x25152c5d,0x2c322c5d,0x1cb6a9f1,0x2d272d4d,0xad00a814,0x2bb72c07,0x2e1f2b05,
0x2cd82d00,0xaffcaf1a,0x2b052b5e,0x2fed2faf,0x2c872cb0,0xadbaaf80,0x2a4e2aaa,0x2c872ed0,0xae3faddc,0xaff8aed0,0xaff8afe6,0x2f022fff,
0xaee9ae99,0xad4daf6e,0xaffcb000,0x244e2c87,0xaf6eaf30,0x26a1a814,0xafd4afed,0xadbaa934,0xafc9afa0,0x2f462d00,0xaf80afaf,0xafe6afa0,
0xac87ad4d,0x9648ac07,0x29f12814,0xae99ab05,0xa993ab5e,0x2ed02bb7,0x2cb02bb7,0xaf46aff8,0xa30ea765,0x2f1a2fff,0x2e1f2d72,0xa30eacb0,
0x244e1648,0x1fd92c5d,0x2f302eb5,0x2e5e2a4e,0x2ee92e1f,0x2ffc2f02,0x2d4d2e3f,0xa44ead27,0x2fdd2f80,0x29f12e7c,0x29f12c32,0x2eb52aaa,
0x2fe63000,0xad72a5db,0x1cb626a1,0x2ed03000,0x2f022f91,0xafa0afbc,0xa8d5a44e,0xa30e2b05,0x2b052d00,0xa44e2b5e,0xafbcaf1a,0x2f912faf,
0x16482765,0xafd4ad72,0xafddafff,0x16482cb0,0xaaaaa6a1,0xac32af5a,0xae7caf5a,0xaf80ac87,0xae1facd8,0x2d001fd9,0xabb7ad4d,0xad27afbc,
0xaf6eae5e,0xafd4af30,0x26a19fd9,0xadbaa44e,0xafe6aff4,0x9cb6ad27,0x2d722b5e,0xaed0aff4,0xae1faf46,0x2faf2cb0,0x2faf2ed0,0x28d5a993,
0xa934ac87,0x2c072f6e,0x2fbc3000,0x2ffc2e99,0xa8d5acb0,0x2875aaaa,0x2e3f2f80,0xa8d5aed0,0x29341648,0x2fed2eb5,0x28142c5d,0x2f302a4e,
0x2e992cd8,0x16482d4d,0xa9f19fd9,0x2c872fbc,0x2fff2faf,0xafe6ad27,0xaed0ad27,0xaddca30e,0x2fc92e99,0x2f802f5a,0xaf46ad96,0x2fe62e99,
0x2f022fed,0xa8d52b05,0xafa0affc,0xa30e2cd8,0x29342d27,0xafbcaf02,0xac07ae3f,0xaffcae1f,0xaa4e9cb6,0x26a1ac32,0x26a1a515,0x1648ad72,
0xaaaa29f1,0xaed025db,0xacb025db,0x2f801648,0xaf1aaf91,0x2875ae5e,0xae3fafed,0xab5e2d4d,0x2c07a875,0x2b052ff8,0x2d4da17e,0xa814aff4,
0x2eb52fc9,0xaf6ead72,0x2dba2fff,0x2eb52e7c,0xaf02af80,0xab5eafe6,0xab5eafc9,0xa30e2f46,0x2cd8a6a1,0x2f302d96,0x2f9129f1,0xac07afd4,
0x2d962ffc,0xafdda44e,0x25db2ee9,0x2f5a2d4d,0xae7ca17e,0x2d72abb7,0xafffad00,0xafc9a17e,0x2c5da934,0x2f5aa44e,0x30002cd8,0xaeb5adfe,
0x2d722ff8,0xacb02d00,0xa7652d00,0x2fff28d5,0xaf02a515,0x217eaf80,0xaf1aaf46,0xaf022765,0xa814af5a,0x2b052fdd,0x2d4da5db,0x2c07ad96,
0x2e5e2fa0,0x29342ff4,0xab052bb7,0x2ee9a8d5,0xaeb59cb6,0xad96aed0,0xad96afe6,0xac872d72,0xa765af6e,0x2f802c5d,0x2f4625db,0x2515af6e,
0x2ff42d4d,0xaff8a44e,0x217e2ee9,0x28752ffc,0xad4d2875,0xafbc217e,0xacd8aff8,0x1fd92ff4,0xaa4eafe6,0x2e99aaaa,0x2fd42993,0xaa4eafc9,
0x2fff2c87,0xacb02d96,0xa7652d96,0x2d722eb5,0xab5e2c07,0x2875af30,0xae3faf91,0xaf1aacd8,0xad96afbc,0xa5dbaffc,0x2fdd2934,0xaf5aac07,
0x2fc92875,0x2aaa2fa0,0xa9932d27,0x2fe62875,0xa8d52d72,0xad00aed0,0xad00afe6,0xaff89cb6,0xad4dafd4,0x2e5e2d96,0x2fed29f1,0x2f91a6a1,
0x2e1fa765,0x2ff49cb6,0xa8752ddc,0x2e1facb0,0x1fd92f5a,0xafbc25db,0xacd8afdd,0xad4d2d96,0xaeb5aee9,0x2f5aa934,0x30002b05,0x2c5dae5e,
0x2f80230e,0xaed02b5e,0xacb02b5e,0xaaaa2f02,0x2cb02fd4,0x1cb63000,0xaddcaf5a,0x27652fd4,0xaff4ac07,0xa17eaffc,0x2ff82934,0xa875afbc,
0x2dfea8d5,0x244e2ff4,0xacd82bb7,0x29342fa0,0x96482f46,0xa5dbafe6,0xa5dbafc9,0xa9f1af80,0xafff9648,0xae7ca6a1,0xafc9a6a1,0x2d722a4e,
0x2ff81fd9,0x230e2ee9,0x2faf2814,0x217eaf91,0xafeda30e,0x2d4dafa0,0xaf91a8d5,0xae5e2f02,0x2fdd2515,0xb0002aaa,0x2f6e2993,0x2fdda765,
0x230eafff,0x2d27afc9,0x2d27ae7c,0xafaf2d72,0xa8142fdd,0xaffc2a4e,0xadfe2dba,0x2e5e25db,0x2a4eaf91,0x2c5d2c07,0x2eb5acd8,0x1648af30,
0xac322f1a,0x2993aff4,0xaf462bb7,0xae7c2f1a,0x2fdd1fd9,0x2dba2814,0x2a4e2ee9,0x25dbaf91,0xaf46a8d5,0x2765afaf,0xa515afaf,0xaf802e1f,
0x2e3f2c32,0xafa02ddc,0xa17e2fff,0x2e3f2515,0xacd8adba,0x2dfe26a1,0x2934afd4,0x244eaf6e,0xa8142ff8,0xadfe2faf,0xaffc230e,0x2e5e217e,
0x2c87af46,0x2f5aa515,0x2f5a2765,0x26a1af80,0xae7c2dba,0x9cb6ae99,0xaddcac5d,0xafc92dba,0x2fafab05,0xaf1a2ee9,0x2b5e2e5e,0x2d002934,
0xaf91a30e,0xacd8a8d5,0x2c07afa0,0xaf302f02,0x2dba2c32,0xac5d2fff,0xae992ddc,0x2dba2515,0xa993aeb5,0x2fc9a9f1,0x2fe6a9f1,0x2aaaafdd,
0xa17e2fed,0xa30eadfe,0xafaf9fd9,0xaff82c07,0x2a4eafed,0x2eb5af91,0x2c5d2d4d,0x1648ae5e,0xae7c2e3f,0xaddca17e,0x9cb6afa0,0xafc92e3f,
0x2ff8a993,0xabb72fe6,0xabb72fc9,0x2b5e2aaa,0xaf30a5db,0x2fbcaa4e,0x2ee9adba,0x2dfeafdd,0x2f1a2515,0x2bb72993,0xaff42aaa,0x2f1aa765,
0xab05adba,0x2e5eafd4,0x2ee926a1,0x2934af6e,0xa5db2fed,0xadba9fd9,0xaa4eadfe,0xafdd2c07,0x2ddcaf02,0xacb02ff8,0xa7652ff8,0x9cb62e3f,
0xac322fdd,0xaf462f6e,0x2993b000,0xae7c2fdd,0x2fafacd8,0x2b5e2934,0xaf1a2dfe,0x2d00244e,0xaf30a17e,0x2ee9afaf,0x2fbca30e,0x2dfeaff8,
0x29f12ddc,0xac5da765,0xac5dacb0,0xad969cb6,0xa993aa4e,0x2765ac87,0xa515ac87,0xaaaa2dba,0xafa02f30,0xabb7244e,0xaff42e5e,0x28d51fd9,
0x28142bb7,0xaf912e1f,0x1fd92d27,0x2ee9ad00,0x2fd4aed0,0xaf5a2fff,0x3000addc,0x2fd4afe6,0x2fafaf46,0x2fa0ae7c,0x2fa0ac32,0xad002993,
0xa44eac5d,0x2f91b000,0x2b05af5a,0xafbc2eb5,0xb0002dfe,0x2c87ae5e,0xae992814,0xaf6e2ffc,0xa5152e1f,0x9cb6a875,0xad722ff4,0xac322e1f,
0x26a12b05,0xa9f12cd8,0xad962fed,0x2fd4affc,0x2fffae1f,0x2515230e,0x2c32230e,0x2ddcaf1a,0x2875ae7c,0x2d27aaaa,0x2fa0af80,0x2875ac32,
0xaee929f1,0x2f91ae99,0x9fd9ac87,0xa8149648,0xafed2f1a,0xaf302e3f,0xa934a875,0xa8142b5e,0xa6a12ddc,0xb0002fc9,0xb0002e7c,0x25db1cb6,
0x2ed0aa4e,0xaf462fd4,0xa9932e99,0x2cb0aa4e,0x2e3faffc,0xad272e5e,0x2e1fa814,0x2f02adfe,0x9fd9abb7,0x2c07ad27,0x2fedae1f,0xadfe2d00,
0xaf6e2cb0,0x25dba993,0x2c5daf46,0xaf6e2ed0,0xaddc2fdd,0xa5159648,0xac329648,0xafff2fd4,0x28d52814,0xabb72934,0xaff42f30,0xafa02fed,
0x3000aee9,0x2e99adfe,0xac872f30,0x2f6eafbc,0x2c32af02,0x2f80af1a,0x2aaa217e,0x2e7caf02,0xab5e9cb6,0x2ff4afc9,0x2ff4ae7c,0x2d27addc,
0xaffc2eb5,0x2fedb000,0x2cd8af5a,0x2b05ac5d,0xa17e2c32,0xad002d72,0xabb71cb6,0xa17e2515,0x2dfea9f1,0xac072c87,0xafed2e99,0x1fd91648,
0x2fd4afbc,0xa9f12b05,0xad962f91,0x26a1a44e,0x2aaaae3f,0xa76528d5,0x251528d5,0x2993a875,0xafe62eb5,0xaddc2dba,0x2fffaf6e,0xaed02eb5,
0xae3f2fbc,0xae1f2dfe,0x2d27af30,0xaf022ee9,0x9fd92b5e,0xae5e2e3f,0xa44ea875,0xaf302f1a,0x2d96a993,0xae992e7c,0xae992c32,0xaf5a2f46,
0x299329f1,0xa76525db,0x251525db,0x2aaa1648,0x28d52934,0xaf02acd8,0x230e244e,0x2fa02dfe,0x28142875,0xaf91aff8,0x1fd9217e,0x2ee92ff4,
0x26a12765,0xaa4eaddc,0x16481cb6,0x26a12cb0,0xaf02af46,0xab5eae7c,0xab5eac32,0xa30e2993,0xae5eaeb5,0x2b059648,0xa934aa4e,0xaee9ac5d,
0xad96adfe,0x2fdd2e5e,0xa5dba814,0xaf5aaffc,0xacb0ad27,0x2ddc2faf,0x9cb6a30e,0xa765ad27,0x2fd42f91,0x2f6e2fed,0x2dba2e5e,0xa6a1ad4d,
0x2fff2ff8,0x25152d00,0x2c322d00,0x2ddc28d5,0x2faf2fe6,0xae1fa993,0x28d52aaa,0x2faf2fc9,0x2ee92f5a,0xaf91afdd,0x1fd925db,0x28142d96,
0xacd8ab5e,0xaf91ad00,0xaf30afaf,0x2c072f1a,0xaeb5addc,0xad96afc9,0xad96ae7c,0xac879cb6,0xafc9af5a,0x2993a6a1,0xaaaaac87,0xafe6af5a,
0xaff4affc,0x2ff82e5e,0xa17ea814,0xa875adfe,0x9fd9a875,0x2c07a17e,0x2fed2ff8,0xadfeaff4,0x29f12515,0x2fdd2f46,0x2eb52f80,0x29f1a765,
0x2ddc2c87,0x25152d96,0x2c322d96,0x2fff2eb5,0x2fa02ee9,0xaf02ab05,0x230e2934,0x28d52e5e,0x2d962ee9,0x25db2dfe,0xafddaf30,0x2f5a2fbc,
0x27652bb7,0xaf46ab5e,0xaf80aff8,0xa5152bb7,0xa8d59cb6,0xad00afc9,0xad00ae7c,0xaff8addc,0xadfeac5d,0x2cd89648,0xa44eaa4e,0xa934aeb5,
0xaff8afc9,0xae3fafff,0x2f022d72,0xaff8ae7c,0xadfeaf5a,0x2c07a5db,0x2fed2fdd,0x9fd9ad96,0xa6a1ac07,0x2f6e2f91,0x2dba2f30,0x2fd42cd8,
0x2aaa230e,0xa7652b5e,0x25152b5e,0x29932f02,0x2e7c2c5d,0x2fff2d96,0xad72a9f1,0x2fc92c5d,0x2ff42fbc,0x217e2dfe,0xaff8af30,0x28752ee9,
0x2d4d2f1a,0xafedad00,0xae5eafaf,0xaf91ab5e,0x96482993,0xa5dbae7c,0xa5dbac32,0xa9f1af46,0xaddc9648,0xafe6a6a1,0xaed0a6a1,0x2fff2a4e,
0xad27affc,0x2d00ac07,0xabb7afbc,0xae1f2934,0x2e5e230e,0x1fd92fa0,0x2f3028d5,0x244eaf02,0x2c872fe6,0xadbaaf46,0x2a4e2f80,0x2c872fc9,
0x230ead72,0x2d27ac32,0x2d27a515,0xafaf9cb6,0x2fbc2e99,0x9fd92f6e,0x2d4d3000,0x2cd8ac87,0xaa4e2b05,0xac5dafbc,0xaeb5a44e,0x96482f91,
0xaed0afa0,0x2f802d00,0xaaaaafaf,0xacb0afa0,0x2c872ffc,0x16482fbc,0xa9f12c07,0x2e99a934,0xaf80a8d5,0xac32afaf,0xae7cafaf,0xaaaa2e1f,
0xa30eaed0,0x2f1a2d72,0x2e1f9cb6,0xa30eafe6,0x2fed2dba,0xaffca6a1,0x2b052fd4,0x2cd82f6e,0xafbcae1f,0xad4daf02,0x1fd9ae3f,0xacd82d27,
0x2c87a993,0x2f5a2cb0,0x2f5a2ed0,0x26a1af46,0x2cb03000,0xafffa5db,0xad7226a1,0x27653000,0xafafa934,0x2f1aa814,0xab5eafed,0xad00af30,
0x2f30230e,0x2fed28d5,0x28142fa0,0x2934af02,0x16482ed0,0xafd41cb6,0xafddad72,0x16482fe6,0xaf46aeb5,0x2ed0a9f1,0x2cb0a9f1,0xa993afdd,
0x2e1fa44e,0xad002d4d,0x2bb72ffc,0x2d272ee9,0xaa4e2cd8,0xaeb52b05,0xac5daffc,0x96482fed,0xacb0aff4,0x2d72ad27,0x2fff2b5e,0xa765aff4,
0x2ff82aaa,0xabb72e7c,0xabb72c32,0x2b5e2f80,0xab052c87,0x2814af6e,0xac07b000,0xad4dae99,0xa8d5afe6,0x2875af80,0x2e3f2f46,0xa8d5afc9,
0x2f912dba,0xa44e2fd4,0xafbca6a1,0x2b052f6e,0xae99244e,0x9648affc,0x29f1ad4d,0xac87aee9,0x1cb6af02,0x25152ff8,0x2c322ff8,0x2d722e3f,
0x2ed02e99,0x2aaa2f5a,0xaf80ad96,0x2cb02e99,0xafafa44e,0xab5eaf30,0x2f1a9fd9,0xad00ae5e,0x2b05ad27,0x2c072f02,0xa8142e3f,0x2d4d2e1f,
0x29f12fff,0xac5daed0,0xac5dafe6,0xad96addc,0xaf46aa4e,0xac32ac87,0xae7cac87,0x29932dba,0x2f1a2b05,0xa8752fed,0x2e3f2cd8,0x2b5eaffc,
0xaee9abb7,0x2f30ae1f,0xadfead27,0xafbc2d00,0x2eb52c32,0xaf6e1cb6,0x2dba2d72,0x2eb52515,0x2fafa993,0x2fa0a515,0x2fa02765,0xad00aaaa,
0xafed26a1,0xa934ad96,0xaf30a9f1,0xa8142fd4,0x30009fd9,0xac872fed,0x2e992c07,0x2f6eadfe,0xafe6a17e,0x2fffabb7,0xaddcad00,0xaed0a17e,
0xac5d2f30,0xaf5a2e5e,0xb000244e,0x2eb51fd9,0x2ddcae1f,0x2e7c230e,0x2fc9230e,0x1cb6af1a,0xaf022cb0,0x217eaf46,0xaf1aa993,0xaf022ed0,
0x2fbca9f1,0xaf302e99,0x2dfe2c87,0x2ee91648,0xa44eafa0,0x2b05aff4,0x2f91abb7,0xafbc28d5,0xa6a12fff,0xb0002c32,0xb0002515,0x25db2ddc,
0x2c32af6e,0x2aaa2c5d,0x2f8025db,0x2e7caf6e,0xae3f2dfe,0x2d27afed,0xae1fac07,0xaf021fd9,0x2dfe2bb7,0x28142d27,0xae5e2e1f,0x2ffcad00,
0xaa4eae7c,0x2e99af80,0x2fd4aaaa,0xaa4eac32,0x9cb62fdd,0xae7c9648,0xafc99648,0xaddc2fd4,0x2b5eafbc,0xa8752f91,0x2e3f2b05,0x2f1aa44e,
0xb0002814,0xae991fd9,0x2c87af91,0xaf6e2ee9,0x2ed02875,0xa9932fa0,0xaf462d27,0x2cb02875,0xab5eaddc,0x2ff4ac32,0x2ff4a515,0x2d27afff,
0x9fd92fd4,0xa44ead96,0xae5ea9f1,0xaf3026a1,0x2e1faed0,0x2ff4addc,0xa8752fff,0x2e1fafe6,0xaffc29f1,0xa814ac87,0x2e5eae99,0xadfe9648,
0x2eb52814,0xaf5a2f30,0xb0002934,0xac5d2fed,0xa993ae3f,0x2c3228d5,0x2e7c28d5,0x2f46a875,0xa5152fd4,0xad723000,0x9cb6af5a,0xac322fd4,
0x2e3faee9,0x2e1f9fd9,0xad272f91,0x2f02a814,0xaffc28d5,0x2cd8aff4,0x2fedabb7,0x2b05afa0,0x2d962aaa,0xae992515,0xae99a765,0xaf5a2993,
0x1cb6adba,0x2cb0aeb5,0x2765aeb5,0xaddc2f6e,0xaff82d4d,0xa30ea814,0xafaf2c07,0xa17e2b05,0xa44e2e3f,0xadfe2b5e,0xa9342f1a,0x2cd8a875,
0x2fddacb0,0xb0002f80,0x2f6eaaaa,0x2fddaed0,0x2d001cb6,0x217e2765,0x217e2cb0,0x2bb7addc,0x2ee9afdd,0x2d4daa4e,0x2ffcadba,0xa44ea5db,
0xa9f1a934,0x2fd4aee9,0x26a1ae5e,0xad962b05,0xafc92f1a,0x2f46aff4,0xaf802bb7,0xafe62f1a,0xafdd2d4d,0xadba2c07,0xaa4ea814,0xa5db2b05,
0xaaaa2f1a,0xafc92f02,0xafe62f02,0x2993a17e,0x2e3fa765,0xafa02fff,0xa17e2d72,0x2e3facb0,0x2e5eb000,0xad4d2eb5,0x2f91ac5d,0x2fedaf5a,
0x2ee9aff8,0x2ffcafaf,0x2d4da30e,0xa44ea17e,0xa5dbaaaa,0x2f6eafe6,0x2f6eafc9,0xac5d2993,0xafe62dba,0x2d72ae99,0x9cb6ac5d,0xaed02dba,
0xabb72f30,0x28d5ac07,0xafa02cd8,0xaff42f91,0xa9342e3f,0xae5e2f1a,0xaee92b5e,0x2b05a875,0x2dbaa765,0xac5d2d72,0xae992fff,0x2dbaacb0,
0x2f80afd4,0xa7652a4e,0x25152a4e,0x2f46ae99,0x217eacd8,0x230e1fd9,0x2fafad4d,0x2ff8afbc,0xa9f1a44e,0x26a1a934,0x2fd4adfe,0xad962cd8,
0xafe62e3f,0x9cb6a17e,0x2d72afa0,0xaed02e3f,0xad272f80,0xa8752515,0xa875a765,0xafa02f46,0x293425db,0xac072a4e,0xafbc2dba,0xaffc2fdd,
0x2f1aacb0,0x2bb7aaaa,0xaff42f80,0x2f1aaed0,0x2f30b000,0x2cd8ac5d,0xac072eb5,0x2f91af5a,0x25dbacd8,0x2dbaad4d,0x2a4e1fd9,0x2fddafbc,
0xad722875,0x2e7cae1f,0x2fc9ae1f,0x2fffaff4,0xafc92fdd,0xaf802f6e,0x2f46b000,0xafe62fdd,0xabb72e5e,0xafa02f91,0x28d5ad4d,0xaff42fed,
0x2934217e,0xafbc2faf,0xac07230e,0xaffc2ff8,0x2f5aad72,0xafd42fc9,0xafd42e7c,0xb0002fff,0x9cb69648,0xacb0a6a1,0xa765a6a1,0x2ddc2a4e,
0xa17e9fd9,0xaff4aee9,0xa875a814,0x2ff82f91,0xa44ea30e,0xadfeafa0,0xa934a8d5,0x2cd82f02,0xa5dba515,0x9648aaaa,0xa9f1a993,0xa5db2765,
0xa30e9cb6,0xad27a765,0xad27acb0,0x2faf2ddc,0xa814a5db,0xaffcaf5a,0xadfead96,0x2e5e2fdd,0xaa4ea934,0xac5daee9,0xaeb5ae5e,0x96482b05,
0xac32ab5e,0x2993a30e,0xaf46af02,0xae7cab5e,0xa5db9fd9,0xad96a814,0xaf5aaee9,0x2fdd2f91,0xaaaaa8d5,0xafc9afaf,0xafe6afaf,0x29932e1f,
0xad00ac32,0xa8d5addc,0xaff8afff,0xad00a515,0xae5eadba,0x2d4d26a1,0xaf91afd4,0xafedaf6e,0xa814a17e,0xadfea875,0xaffcaff4,0x2e5e2ff8,
0xac87aaaa,0xaf5aafe6,0xaf5aafc9,0xa6a12993,0xae7cad96,0x9cb6ac87,0xaddcaeb5,0xafc9ad96,0xafafaf30,0x2f1a2c07,0xab5eacd8,0xad00af91,
0xa934a30e,0xae5ea8d5,0xaee9afa0,0x2b052f02,0xad96ac32,0xaeb5afff,0xac87addc,0xad96a515,0xaf80aeb5,0x2765a9f1,0xa515a9f1,0xaf46afdd,
0xaff8afed,0x2ff42dfe,0x28751fd9,0x217eac07,0xaa4ea44e,0xaeb5a934,0xac5dadfe,0x96482cd8,0xae7cad00,0xaddcaff8,0x9cb6a8d5,0xafc9ad00,
0xaff8af80,0x2bb7a515,0x2bb72765,0xab5eaf46,0xaf30afdd,0x2fbc2f5a,0x2ee92d96,0x2dfe25db,0xab5ea515,0xaf02a993,0xa30eaaaa,0xab5e2765,
0xaf30adba,0xacd8afd4,0x2c0726a1,0xaf91af6e,0xafddafed,0x2d961fd9,0x2f5a2dfe,0x25dbac07,0xad72af02,0x2e7c2ff8,0x2fc92ff8,0x2fff2e3f,
0xac32a5db,0xaf46a9f1,0x29939648,0xae7ca5db,0xafafae5e,0xab5eaf91,0x2f1a2d4d,0xad00afed,0xaf30aff8,0x2ee92875,0x2fbc2ff4,0x2dfe217e,
0xa9f1ad72,0x2c5d2fc9,0x2c5d2e7c,0x2d962fff,0xaf80aa4e,0xafc9ac87,0xafe6ac87,0x2f462dba,0xa8d5af30,0x2f02a44e,0xa30eae5e,0xafa09fd9,
0x2fbc2bb7,0xa9342e1f,0x2ffc2d27,0x2c07ad00,0x26a12ed0,0xaa4eafff,0x16482ddc,0x26a12fe6,0xafafaaaa,0xafa0acb0,0xafa0aed0,0x2d002f80,
0xa44eaeb5,0x2f919648,0x2b05aa4e,0xafbcac5d,0x30002d4d,0xac872cd8,0x2e992fbc,0x2f6e9fd9,0xa5152d27,0x9cb6afaf,0xad72230e,0xac322d27,
0xafd4ab05,0xaf6eacd8,0xadbaafed,0x26a12ffc,0x1cb6ae1f,0x2fe6230e,0x2ed0230e,0xad72af1a,0x2faf2e7c,0xae1f2aaa,0x28d52f80,0x2faf2c32,
0xac0729f1,0x2934ae99,0xaffcac87,0xafbc9648,0xafedab5e,0xaf30ad00,0xa934afaf,0xa8142f1a,0x26a1ad72,0x30002765,0x30002cb0,0xa5dbafff,
0x2ed02f5a,0xaf4626a1,0xa9932c87,0x2cb02f5a,0xae3f1fd9,0x2d27acd8,0xae1fafbc,0xaf02ad4d,0xaffcabb7,0xaee9ad27,0x244eae1f,0xad4d2d00,
0x29f1acb0,0x2fdd2993,0x2eb52f46,0x29f1aed0,0x2d722fdd,0xafe69648,0xaed09648,0x9cb62fd4,0xafa0a814,0x2f02a934,0xa30eaf30,0xa8d5afed,
0xb000ac07,0xae99ad4d,0x2c87ab05,0xaf6e2814,0x2c32abb7,0x2f802b5e,0x2aaa2ff8,0x2e7cabb7,0x2b5e2fff,0xaff4a765,0xaff4acb0,0xad272d72,
0xaffcac5d,0x2fed9648,0x2cd8aa4e,0x2b05aeb5,0xaff8ac32,0xae3fad72,0x2f029cb6,0xaff8a515,0x2d4da9f1,0x2ee92c87,0xa44e2e99,0x2ffc1648,
0x26a12fbc,0xaf6eab05,0xadbaaf91,0xafd4244e,0xaf46ae3f,0x2fc928d5,0x2fe628d5,0x2f80a875,0xafe6ac5d,0xaddcad96,0x2fff29f1,0xaed0ac5d,
0x2e3fa814,0x2e1f2d4d,0xad272b05,0x2f022c07,0x9fd92f1a,0xae5ead00,0xa44eafaf,0xaf30ab5e,0xad96af80,0x2e992cb0,0x2e992ed0,0x2f5a2aaa,
0xad72adba,0xa515aeb5,0xac32aeb5,0x9cb62f6e,0x2d272dfe,0xad002fbc,0x2bb72ee9,0x2e1faf30,0xacd8ae3f,0x2ffcab5e,0xab05af1a,0xafed2875,
0x2c872e7c,0xadbaa993,0x2a4e2f46,0x2c872c32,0xad00addc,0xa17eaed0,0xa17eafe6,0xabb72fff,0x2c072e99,0xadfe2f6e,0x9fd93000,0x2fedac87,
0xa9f1af30,0x2fd4a814,0x26a1afed,0xad96a934,0x27652fa0,0xaaaaad00,0xa9932faf,0xa5152fa0,0xac87adfe,0x9648aee9,0x29f1afbc,0xae992f30,
0x29932f1a,0xaed02f02,0xacb02f02,0x2f46a17e,0xa30eafc9,0x2f1a9cb6,0x2e1faddc,0xa30eae7c,0xa44e3000,0x9fd9aeb5,0xaf302c5d,0xae5e2f5a,
0xac07ae1f,0x1fd9af02,0x2dfeae3f,0xafed2d27,0x25db2f80,0xaf6e2e7c,0xaf6e2c32,0x2c5d2aaa,0x2515b000,0x2ddc25db,0x2fffa6a1,0x2c32b000,
0xabb72f91,0x28d5afbc,0xafa0a44e,0xaff42b05,0xab05ae3f,0x244eaf1a,0x2fbcab5e,0xaf912875,0x16482fc9,0xafd42ddc,0xafdd1cb6,0x16482e7c,
0x2aaaafd4,0x2c322a4e,0x2e7c2a4e,0x2f80ae99,0xae1f2e5e,0x2d00affc,0xabb7adfe,0xad27a814,0xa9f1ae5e,0x26a1af30,0x2fd49fd9,0xad96a44e,
0xa5152ff4,0xafff2d27,0xaddcab5e,0xac322ff4,0x2d27af46,0x28752cb0,0x28752ed0,0x2fa0a993,0xaf912c87,0x2ee9af6e,0x2814b000,0x1fd9ae99,
0xa8d5ae7c,0x2875af46,0x2e3f2993,0xa8d5ac32,0xa9343000,0xafed2c5d,0xa814aeb5,0xaf302f5a,0x2e99ae5e,0x16482dfe,0xa9f12ffc,0x2c872814,
0xafff2875,0x2fe6ae1f,0x2ed0ae1f,0x2ddcaff4,0xa765ae99,0x2993af5a,0x2aaa2d96,0x2515ae99,0xabb72fed,0xafa02b05,0x28d5affc,0xaff42cd8,
0x2f91ad27,0xa8142f02,0xaee92e3f,0x9fd92e1f,0xaf5a9cb6,0x2fd4ac32,0x2fd4a515,0x3000ad72,0x2aaaaf6e,0x2ed0afdd,0x2cb0afdd,0xaf803000,
0xaf1a2934,0x2875acd8,0xae3f244e,0xab5e2dfe,0xac072faf,0xab05217e,0xad4d2ff8,0x2814230e,0x2eb5a765,0xaf6e2ddc,0x2dba9cb6,0x2eb5acb0,
0x2bb7af80,0x2f1aafe6,0x2f1aafc9,0xaff42f46,0xae5e26a1,0x2b05ad96,0xa934a9f1,0xaee92fd4,0xadba2ffc,0xa5dba44e,0xafdd2ee9,0xaa4e2d4d,
0x2cb0217e,0xaddc2bb7,0x1cb62d00,0x2765217e,0x2c5daf91,0x2f5aafed,0x3000ae5e,0xaeb52d4d,0xad72217e,0x2cb0ae3f,0x2765ae3f,0xafff2fa0,
0xaf022fe6,0x217ea993,0xaf1a2aaa,0xaf022fc9,0x28142a4e,0xab0525db,0xad4d2fdd,0xac072dba,0x2cd8afa0,0x2f91aff4,0x2f30abb7,0xac0728d5,
0xac5d9cb6,0x2dbaaed0,0x2dbaafe6,0xae992d72,0xafc92f6e,0x2993ac5d,0xaaaaa5db,0xafe62f6e,0xa30e2d4d,0xa17ea44e,0xaff82ee9,0xafaf2ffc,
0x2d4dafaf,0x2fbcaff8,0x2cd8a17e,0x9fd9a30e,0xaa4ea515,0x2e99af46,0x2fd4af80,0xaa4e2765,0xafff2e99,0x2cb0adba,0x2765adba,0xad722c5d,
0xab5e2ee9,0x2875ab05,0xae3f2934,0xaf1a2e5e,0x2dbaafbc,0x2fddaffc,0x25db2934,0x2a4eac07,0xa765a875,0x2f46afa0,0x2f80ad27,0x2515a875,
0xafa02d72,0x2e3faed0,0x2e3fafe6,0xa17e9cb6,0xadfe2fd4,0x2cd8ad96,0xa44ea9f1,0xa93426a1,0x2e1fafc9,0x2ff4afff,0xa8752d72,0x2e1fae7c,
0x9fd9aa4e,0x2fbcafdd,0x2cd8a5db,0x2d4dadba,0xaeb52c07,0x2f5aaf91,0x3000af30,0x2c5dacd8,0xaf802ff4,0x2ed0af1a,0x2cb0af1a,0x2aaaabb7,
0x2e7cafd4,0x2fffb000,0xad722f5a,0x2fc9afd4,0x230eac07,0x2ff8affc,0x217e2934,0x2fafafbc,0xad4d28d5,0x2fedaff4,0x2e5eabb7,0x2f91afa0,
0xb0002f46,0x2fddafe6,0x2fddafc9,0x2f6eaf80,0xaaaaaa4e,0xaed0ac87,0xacb0ac87,0x2f802dba,0xab5eab05,0xafafafed,0xad00acd8,0x2f1a2ffc,
0xac07abb7,0xab05ae1f,0xad4dad27,0x28142d00,0xac5dac32,0x29f19cb6,0xad96ad72,0xac5da515,0xafafaf80,0xafa0afe6,0xafa0afc9,0x2d002f46,
0xafedafd4,0xa934adba,0xaf30af6e,0xa81426a1,0xb000affc,0x2c87244e,0xae99aee9,0xaf6ead4d,0xafe6aff8,0x2fff2f02,0xaddcae3f,0xaed0aff8,
0xaeb5af30,0xaa4eae5e,0x9648a44e,0xac5d9fd9,0xad72ae1f,0x2cb0230e,0x2765230e,0xafffaf1a,0xabb7acb0,0x2ff82f46,0x2b5e2993,0xabb7aed0,
0xa814a9f1,0x2b052e99,0x2d4d2c87,0x2c071648,0xa44ea8d5,0x2b05a30e,0x2f912f02,0xafbcafa0,0x26a11cb6,0x30002ed0,0x30002fe6,0xa5dbad72,
0x2c3229f1,0x2aaa2eb5,0x2f802fdd,0x2e7c29f1,0x2e3f2d4d,0xad27a44e,0x2e1f2ee9,0x2f022ffc,0x2d4d2bb7,0x2fbc2d27,0x2cd82e1f,0x9fd9ad00,
0x2f5a2e7c,0x2c872f80,0x26a12aaa,0x2f5a2c32,0x2fff2fdd,0xacb09648,0xa7659648,0x2d722fd4,0x2f1a2fbc,0xafafaf91,0xad00ab05,0xab5e244e,
0x30002fbc,0x2e992ffc,0xac87a934,0x2f6e2c07,0x2ed02faf,0xa99328d5,0xaf46ae1f,0x2cb02faf,0x2b5e2d72,0xaff4aed0,0xaff4afe6,0xad279cb6,
0x9fd926a1,0xa44eadba,0xae5eaf6e,0xaf30afd4,0x2d272ed0,0x230e2ddc,0xafafafff,0x2d272fe6,0x1fd929f1,0xafbcac87,0xacd8ae99,0xad4d9648,
0xac5da814,0xaa4eaf30,0x9648a934,0xaeb5afed,0xaf80ae3f,0x2ed028d5,0x2cb028d5,0x2aaaa875,0xa51526a1,0xad721648,0x9cb6aa4e,0xac3226a1,
0xae3fac07,0xae1faffc,0x2d272934,0xaf02afbc,0xaffcafa0,0x2cd8a30e,0x2fed2f02,0x2b05a8d5,0xad96af46,0x2e992fe6,0x2e992fc9,0x2f5a2f80,
0xafffadba,0xae7caeb5,0xafc9aeb5,0x2d722f6e,0x217ead4d,0x2ff42814,0x2875ac07,0xaff8ab05,0x2fed2e3f,0xad4d2b5e,0x2f912f1a,0x2e5ea875,
0xa5db2cb0,0x9648af80,0xa9f12aaa,0xa5db2ed0,0xad00afff,0xa17eafc9,0xa17eae7c,0xabb72d72,0x2ee925db,0x2d4d2f5a,0x2ffc2d96,0xa44eafdd,
0x29f12f91,0xafd4ac07,0xa6a12cd8,0x2d962f30,0xafc9ab5e,0x2f46a30e,0xaf80af02,0xafe6ab5e,0x25dbad4d,0x2d96ac07,0x2f5a2814,0xafddab05,
0x2f462f1a,0xa7652f02,0x25152f02,0x2f80a17e,0xad002765,0xa8d5afff,0xaff8ad72,0xad002cb0,0xacd8b000,0x2dfe2eb5,0x2934ac5d,0x244eaf5a,
0x2ee9217e,0x2ffc2875,0x2d4d2ff4,0xa44eaff8,0x25db2f46,0xaf6e2515,0xaf6ea765,0x2c5d2f80,0xafe6ad96,0x2d72ac87,0x9cb6aeb5,0xaed0ad96,
0x2bb7ab05,0xa8d52ee9,0x2fa02e5e,0x2ff42934,0x2f912e3f,0x2cd82f1a,0xac072b5e,0x2f30a875,0xad962765,0xaeb5ad72,0xac87afff,0xad962cb0,
0xa993afd4,0x2fc92a4e,0x2fe62a4e,0x2aaaae99,0x2ff82cd8,0xaff49fd9,0xa8752d4d,0xa17e2fbc,0x29f12fed,0xa6a12f91,0xafd4ad4d,0x2d962e5e,
0xafe6ad00,0x9cb6aff8,0x2d72a8d5,0xaed0ad00,0x2d27a993,0x28752fe6,0x28752fc9,0x2fa02aaa,0x29342fdd,0xac07af5a,0xafbcad96,0xaffca5db,
0xab5e2cb0,0xaf022aaa,0xa30eaf80,0xab5e2ed0,0xab05b000,0x2e5eac5d,0x2ee92eb5,0x2934af5a,0x2fdd2cd8,0xad962d4d,0xaf5a9fd9,0xa5db2fbc,
0xaddc2875,0x2cb0ae1f,0x2765ae1f,0x1cb6aff4,0xafc9a5db,0xaf80a9f1,0x2f469648,0xafe6a5db,0x2bb7acd8,0x2fa02934,0xa8d52dfe,0x2ff4244e,
0x29342ff8,0xafbca875,0xac07aff4,0xaffca17e,0xaf5aaddc,0x2fd42765,0x2fd42cb0,0x30001cb6,0xa993af6e,0x2765afdd,0xa515afdd,0xaaaa3000,
0x28d52f91,0xaf022e5e,0x230e2fed,0x2fa0ad4d,0xa814afaf,0x2f91a17e,0x9fd9aff8,0xaee9a30e,0x26a12fc9,0xaa4ead72,0x16482fff,0x26a12e7c,
0x2bb7af46,0x2f1aae7c,0x2f1aac32,0xaff42993,0xacd82eb5,0xaf301648,0xaf912a4e,0x2c072c5d,0x2dbaadfe,0x25db2e5e,0x2fdda814,0x2a4eaffc,
0xae7c2d27,0x2d72afaf,0xafff230e,0xafc92d27,0x2fd4a934,0x2f6ea44e,0x2dba2cd8,0xa6a1adfe,0xafff217e,0xa515ae3f,0xac32ae3f,0xaddc2fa0,
0x2faf2515,0xae1f2f80,0x28d52f46,0x2fafa765,0xaee9aa4e,0x2f91a5db,0x9fd9afdd,0xa814adba,0x2e5e2b5e,0x29342d00,0xab052faf,0x2ee9af1a,
0xac5daddc,0x2dbaafc9,0x2dbaae7c,0xae999cb6,0x27652f5a,0xaf8026a1,0xaf462c87,0xa5152f5a,0x230eaffc,0x217e2e5e,0x2ff8a814,0x2fafadfe,
0x1fd92faf,0xac072ff8,0xafed217e,0x2dfe230e,0x29f1afe6,0x2fddaaaa,0x2eb52993,0x29f1afc9,0xaddc2e99,0xa515adba,0xac32adba,0xafff2c5d,
0x2fa0ac07,0xaf022f30,0x230e2f91,0x28d52cd8,0xadba2ee9,0xafdd2dfe,0xa5dbaf30,0xaa4e2fbc,0x2fc9abb7,0x2aaa2b5e,0xa9932ff8,0x2fe6abb7,
0xafa09cb6,0x2e3fafc9,0x2e3fae7c,0xa17eaddc,0x2d4d2c5d,0xae5e1648,0xafed2a4e,0xaf912eb5,0xaff82765,0xae3f1cb6,0x2f02addc,0xaff82cb0,
0x2dfe2a4e,0xac072fdd,0xafed25db,0x1fd92dba,0xa6a1aee9,0x2f6ea934,0x2dba2b05,0x2fd4ae5e,0xaaaa2ff4,0x2765af1a,0xa515af1a,0xa993abb7,
0xacb0ac5d,0x9cb6ad96,0x2ddc29f1,0xa765ac5d,0xa30e2fbc,0xaff82dfe,0xa17eaf30,0xafaf2ee9,0x2dfeaf1a,0x244e2d00,0xacd82faf,0x29342b5e,
0xb0002993,0x2fddae7c,0x2fddac32,0x2f6eaf46,0x2ddcb000,0x2fe6afd4,0x2ed0afd4,0xafff2f5a,0xad279fd9,0x2d00aee9,0xabb7a814,0xae1f2f91,
0xae5e2ff4,0x9fd9a8d5,0xaf302fa0,0xa44e2bb7,0x2c872515,0xadba2aaa,0x2a4e2993,0x2c87a765,0x2ff4ad72,0x2e1fac32,0x2e1fa515,0xa8759cb6,
0x2814ae99,0x2ffcaf6e,0x2dfeb000,0xae5e2c87,0xaf5a2b05,0x2eb5afbc,0xac5da44e,0xb0002f91,0xac322fa0,0x2993ad00,0xaf462faf,0xae7c2fa0,
0x2c871fd9,0x16482814,0xa9f12ee9,0x2e99af91,0x2f80afa0,0x2c32a875,0x2e7ca875,0x2aaaad27,0xa30eac32,0x2f1aaddc,0x2e1fafff,0xa30ea515,
0xafed2d96,0x2ffcafd4,0xab05a6a1,0xacd829f1,0xa8142e1f,0xadfe2f02,0xaffc2e3f,0x2e5ead27,0x2e99a993,0xaa4e2cb0,0xaa4e2ed0,0x2fd4af46,
0x2e7cb000,0x1cb625db,0x2ddca6a1,0x2fc9b000,0xa875a934,0x2b5ea814,0x2f1aafed,0x2e3faf30,0xaf302ff4,0xafed2fa0,0xa814a8d5,0xa9342bb7,
0x16482c32,0xafd42fff,0xafdd2ddc,0x16482515,0x2f46ac5d,0xaed02f6e,0xacb02f6e,0x2993a5db,0x2e1fafed,0xad002dfe,0x2bb71fd9,0x2d27ac07,
0xaf5a2cd8,0xac5d2b05,0x2eb5affc,0xb0002fed,0xae7c2ff4,0xaddc2d27,0x9cb6ab5e,0xafc92ff4,0x217e2aaa,0xaf022e7c,0xaf022c32,0xaf1a2f80,
0x2f30ac87,0xafbc2f6e,0xaee93000,0xadfe2e99,0xa8d5a515,0x2875a993,0x2e3faaaa,0xa8d52765,0xaf912d96,0x244ea6a1,0x2fbcafd4,0xab0529f1,
0xae992fed,0x96489fd9,0x29f1adfe,0xac872c07,0x9cb62bb7,0xa515217e,0xac32217e,0xad722d00,0x2c32ae99,0x2f46af5a,0xa9932d96,0x2e7cae99,
0xa875a44e,0x2f1aaf30,0x2b5e9fd9,0x2e3fae5e,0xaf302d27,0x2ee9af02,0x2fbcae3f,0x2dfeae1f,0xaf6e2fff,0x2eb5aed0,0x2eb5afe6,0x2dbaaddc,
0xaddcadba,0xafe6aeb5,0xaed0aeb5,0x2fff2f6e,0xae1fadfe,0xae3fafbc,0xaf02aee9,0x2d272f30,0xae5eae3f,0x9fd9ab5e,0xaf30af1a,0xa44e2875,
0xae99ae7c,0x2d962993,0xaf5aaf46,0xae99ac32,0xad00ad72,0xa17eac32,0xa17ea515,0xabb79cb6,0xac07ac87,0x2dfe29f1,0x1fd99648,0xafedae99,
0xa9f1ab05,0x2fd42fbc,0x26a1244e,0xad96af91,0xa765a8d5,0x2aaa2e3f,0x29932875,0x2515a8d5,0x2e992dfe,0x30002ee9,0x2f6e2fbc,0xac87af30,
0x2f802f1a,0x2c322f02,0x2e7c2f02,0x2aaaa17e,0x2ff42fc9,0xab5e1cb6,0x2d272ddc,0x2ff42e7c,0x2fed3000,0xaffcaeb5,0x2b052c5d,0x2cd82f5a,
0x2c072d27,0x9fd92bb7,0xadfead00,0x2fed2e1f,0x25db2993,0xaf6eacb0,0xaf6eaed0,0x2c5d2f46,0xa5151648,0xaddcafdd,0xafffafd4,0xac321648,
0xabb7a934,0x28d5a814,0xafa0afed,0xaff4af30,0xaf30ae3f,0xafedaf1a,0xa814ab5e,0xa9342875,0xb000afc9,0xa6a1addc,0x25db9cb6,0xb000ae7c,
0xaf46afd4,0x2ed02a4e,0x2cb02a4e,0xa993ae99,0xad27ae5e,0x2e3f2ffc,0x2f022dfe,0x2e1f2814,0xa9f1acd8,0x26a1ab05,0x2fd42ffc,0xad96afed,
0x2515a30e,0x2fff2e1f,0x2ddc2f1a,0x2c32a30e,0x2d272aaa,0x28752e7c,0x28752c32,0x2fa02f80,0x2f912e99,0xaee9a9f1,0xa8141648,0x9fd92c87,
0x2fa02e7c,0x2faf2f46,0xad00a993,0x2fa02c32,0x2f913000,0xa44e2c5d,0xafbcaeb5,0x2b052f5a,0x2c872e5e,0xb000adfe,0xaf6eaffc,0xae99a814,
0x9cb62875,0xa515ae1f,0xac32ae1f,0xad72aff4,0x27652c87,0xa9932a4e,0xaaaaadba,0xa5152c87,0xabb7a44e,0xafa0af30,0x28d59fd9,0xaff4ae5e,
0xaf91ae1f,0x2814abb7,0x2ee92d00,0x1fd9ad27,0xaf5aafff,0x2fd42ed0,0x2fd42fe6,0x30002ddc,0xaf46af6e,0xac32afdd,0xae7cafdd,0x29933000,
0x2b5ea934,0x2faf2cd8,0x2d00a44e,0xaf1aadfe,0x2ee92faf,0xaf30217e,0x2dfe2ff8,0x2fbc230e,0xac5d2765,0x29f1addc,0xad961cb6,0xac5d2cb0,
0x2bb7a993,0x2f1aa515,0x2f1a2765,0xaff4aaaa,0x2e5e2fd4,0xab052dba,0x29342f6e,0x2ee9a6a1,0xadba1fd9,0xa5dbafed,0xafddac07,0xaa4e2dfe,
0xacb0aff8,0x2ddc2f02,0x9cb6ae3f,0xa765aff8,0x2eb52f91,0x2a4e2fed,0x16482e5e,0x2c5dad4d,0xaddc217e,0xae7cae3f,0xafc9ae3f,0x9cb62fa0,
0xabb7afe6,0x2ff82993,0x2b5eaaaa,0xabb7afc9,0x2fbc2a4e,0xaf3025db,0x2dfe2fdd,0x2ee92dba,0xacd828d5,0xaf91230e,0xaf30af02,0x2c072fa0,
0xac5dafff,0x2dbaac32,0x2dbaa515,0xae99addc,0x2fc929f1,0xa9932eb5,0x2aaa2fdd,0x2fe629f1,0xa30e2dfe,0xa17eafed,0xaff8ac07,0xafaf1fd9,
0xadfeafaf,0xa814aff8,0x2e5ea17e,0xaffca30e,0x2f5a2515,0x2c872f46,0x26a12f80,0x2f5aa765,0x9cb62e99,0xae7cadba,0xafc9adba,0xaddc2c5d,
0xaf1aaee9,0x2faf2b05,0x2d00a934,0x2b5eae5e,0x2dbaa814,0x2fdd9fd9,0x25db2f91,0x2a4eaee9,0x27652faf,0xaf4628d5,0xaf80ae1f,0xa5152faf,
0xafa0addc,0x2e3fac32,0x2e3fa515,0xa17eafff,0x2dfea6a1,0xacd82dba,0x244e2f6e,0x29342fd4,0x2d272fc9,0x230e2fff,0xafafad72,0x2d272e7c,
0xaffcaa4e,0xa814afdd,0x2e5ea5db,0xadfeadba,0x2c5dac07,0x2a4e2f91,0x16482f30,0x2eb52cd8,0x29932ff4,0xac32af1a,0xae7caf1a,0xaf46abb7,
0xae7c26a1,0xafff1648,0x2d72aa4e,0xafc926a1,0x230eaee9,0x2ff89fd9,0x217e2f91,0x2fafa814,0x2d4d2fa0,0xafed230e,0xae5eaf02,0xaf9128d5,
0xb000aaaa,0x2fdda515,0x2fdd2765,0x2f6ea993,0x1cb6b000,0x2cb0afd4,0x2765afd4,0xaddc2f5a,0xa17e2ffc,0xaff42c07,0xa8752fbc,0x2ff8a934,
0x244eaff4,0x2dfe28d5,0x2934afa0,0xacd8abb7,0xa5db2fe6,0x9648af46,0xa9f12f80,0xa5db2fc9,0x2ff41cb6,0x2e1f2765,0x2e1f2cb0,0xa875addc,
0xafbca5db,0x1fd9af5a,0xad4dad96,0xacd82fdd,0x2f5a2934,0xaeb52ee9,0x2c5d2e5e,0x3000ab05,0xaed0ab5e,0x2f80a30e,0xaaaaaf02,0xacb0ab5e,
0xa5db2ffc,0xad962fbc,0xaf5a2c07,0x2fdda934,0x2aaaafa0,0x2fc9a875,0x2fe6a875,0xa993ad27,0xad002ed0,0xa8d5ad72,0xaff81cb6,0xad002fe6,
0x2e5ead96,0xad4d2fd4,0x2f9126a1,0x2feda9f1,0xafbca17e,0xad4da875,0x1fd9aff4,0xacd82ff8,0x2e992aaa,0xaa4e2fe6,0xaa4e2fc9,0x2fd4a993,
0xacb0ad96,0x2fffac87,0x2d72aeb5,0xa765ad96,0x28752f30,0xab5eac07,0xaf1a2cd8,0xae3f2f91,0x2934aff4,0x2e5eafa0,0x2ee928d5,0xab05abb7,
0xad962ed0,0xaeb51cb6,0xac87ad72,0xad962fe6,0x2f80ac5d,0xa7652f6e,0x25152f6e,0x2f46a5db,0xaff8244e,0x2ff4ad4d,0x2875affc,0x217eaee9,
0x2f5a244e,0x2c5d2934,0xaeb52dfe,0x3000acd8,0xacb0ad00,0x2d72aff8,0x2fffa8d5,0xa765ad00,0x217e2f80,0xaf022515,0xaf02a765,0xaf1a2f46,
0x2b05afdd,0xa8142f5a,0x2c072d96,0x2d4d25db,0xab5e2fe6,0xaf022f80,0xa30eaf46,0xab5e2fc9,0x2f30ad96,0x2cd826a1,0xac072fd4,0x2f91a9f1,
0xafdd244e,0x2d96affc,0x2f5aad4d,0x25dbaee9,0x2d722bb7,0xae7c217e,0xafc9217e,0xafff2d00,0xaed0a5db,0xaaaaa9f1,0x2f809648,0xacb0a5db,
0x28752e5e,0xaf1a2f91,0xab5ead4d,0xae3f2fed,0x2b05aff8,0x2c072875,0xa8142ff4,0x2d4d217e,0xaf6e2d72,0x2eb5afc9,0x2eb5ae7c,0x2dbaafff,
0x2f80af5a,0x2fc9ae99,0x2fe6ae99,0xaf462d96,0xa8d5ab05,0x2f02afed,0xa30eacd8,0xafa02ffc,0xafbc2f02,0x2934ad27,0xaffc2e1f,0xac072e3f,
0x26a12c32,0xaa4e1cb6,0x16482d72,0x26a12515,0x28752aaa,0xa8d52cb0,0xa8d52ed0,0x2e3faf80,0x2fedaeb5,0x29349648,0x2f30aa4e,0x2814ac5d,
0x1648ad4d,0x2e99acd8,0x2c87afbc,0xa9f11fd9,0xafe62d27,0x2fffafaf,0xaddc230e,0xaed02d27,0xafd42f30,0xaf6e2e5e,0xadba244e,0x26a11fd9,
0x9cb62d27,0xafe62ff4,0xaed02ff4,0x2d72ab5e,0x2fafacb0,0xae1f2f46,0x28d52993,0x2fafaed0,0x2c07af6e,0xa9342c87,0x2ffcae99,0x2fbcb000,
0xa44eab5e,0x2b05ad00,0x2f91afaf,0xafbc2f1a,0xafd42d72,0x1648a765,0x1648acb0,0xafdd2fff,0xac322f5a,0xaaaa26a1,0xaf802c87,0xae7c2f5a,
0x2d009fd9,0xae1f2cd8,0xad272fbc,0xabb72d4d,0x2ffcaf02,0x2ee9ae1f,0xa44e2d27,0x2d4dae3f,0x29f1ae7c,0x2fddaf80,0x2eb5aaaa,0x29f1ac32,
0xad7225db,0x2fe6b000,0x2ed0b000,0x1cb6a6a1,0xafa02fbc,0x2f02af91,0xa30eab05,0xa8d5244e,0x96482c07,0xac872d4d,0xae992b05,0x29f1a814,
0x2ed0abb7,0xa9932b5e,0xaf462ff8,0x2cb0abb7,0x2f1aafff,0xa30e2765,0xa30e2cb0,0x2e1fad72,0x1fd9ac5d,0x244e9648,0x2e5eaa4e,0x2f30aeb5,
0xaff82ed0,0xae3f2ddc,0x2f02afff,0xaff82fe6,0xad4d2f6e,0xaee92e99,0x244eac87,0xaffc3000,0x26a12814,0xaf6e2f30,0xadba2934,0xafd42fed,
0x2f46ad00,0xafc92fa0,0xafe62fa0,0xaf802faf,0x2515ac5d,0x2d72ad96,0x1cb629f1,0x2c32ac5d,0xad002814,0x2d27ad4d,0x2e1fab05,0x2bb7ac07,
0xaffc2f1a,0x2cd8ad00,0x2fedafaf,0x2b05ab5e,0xadba2f80,0x2c87acb0,0x2c87aed0,0x2a4eaaaa,0xaf80af6e,0xafc9afdd,0xafe6afdd,0x2f463000,
0xafa0af91,0xabb7ae5e,0xaff4afed,0x28d52d4d,0xafbcafaf,0x2934a17e,0xaffcaff8,0xac07a30e,0xafd4afc9,0x2f5a2d72,0xb000afff,0xafd4ae7c,
0x2bb72aaa,0x2f1a2cb0,0x2f1a2ed0,0xaff4af80,0x2cd82c5d,0x2f303000,0x2f912f5a,0xac07aeb5,0x2dba2d4d,0x25db2cd8,0x2fdd2fbc,0x2a4e9fd9,
0x2e7c2e1f,0xad72a875,0x2fff2ff4,0x2fc92e1f,0x26a12934,0xa9f1244e,0xad96acd8,0x2fd42dfe,0x9cb6217e,0xafe6ae3f,0xaed0ae3f,0x2d722fa0,
0xa875a515,0xad27af80,0xafa0af46,0xa8752765,0xac07aa4e,0x2934a5db,0xaffcafdd,0xafbcadba,0xae5eaf1a,0xa934ae3f,0x2b052875,0xaee9ab5e,
0xac5dad72,0x2dba2765,0x2dba2cb0,0xae99afff,0xa765aa4e,0x2f802fd4,0x2f462e99,0x2515aa4e,0x230e9fd9,0x217e2cd8,0x2ff82fbc,0x2faf2d4d,
0x2ffc2faf,0x2ee92ff8,0xa44e217e,0x2d4d230e,0x2f6e2fe6,0xa5db2aaa,0xac5da993,0x2f6e2fc9,0x2d722e99,0xafe6adba,0xaed0adba,0x9cb62c5d,
0x28d52c07,0xabb7af30,0xaff4af91,0xafa0acd8,0xadbaac07,0xafddad4d,0xa5dbab05,0xaa4e2814,0xafc9af02,0xaaaaaf1a,0x2993217e,0xafe6af02,
0xafa0afff,0x2e3f2765,0x2e3f2cb0,0xa17ead72,0xad4daeb5,0x2e5e3000,0x2fed2f5a,0x2f912c5d,0x217ea765,0x2d009cb6,0x2bb72ddc,0x217eacb0,
0x2d4d2a4e,0x2ee92fdd,0xa44e25db,0x2ffc2dba,0x2fd42ee9,0xa9f12934,0xad96ab05,0x26a12e5e,0x2f462ff4,0xafc9af1a,0xafe6af1a,0xaf80abb7,
0x2cb02eb5,0x1cb62dba,0xaddcaf6e,0x27652eb5,0xa30e2814,0xaff8ad4d,0xa17eab05,0xafafac07,0xadfeab5e,0xa44eae3f,0x2cd82875,0xa934af1a,
0xb000af80,0x2fdd2cb0,0x2fdd2ed0,0x2f6e2aaa,0xad72b000,0xa515afd4,0xac32afd4,0x9cb62f5a,0x2e1f1fd9,0x2e3f2ee9,0x2f022814,0xad27af91,
0x2cd82ff4,0xaffca8d5,0x2b052fa0,0x2fed2bb7,0xae99a515,0x2d96aaaa,0xaf5aa993,0xae992765,0x2ff42ddc,0x2e1f2ed0,0x2e1f2fe6,0xa875afff,
0xa8142c87,0xaffca9f1,0xadfe1648,0x2e5e2e99,0xaf5aaf30,0x2eb5a814,0xac5dafed,0xb000a934,0x2c32a8d5,0xa9932e3f,0x2f462875,0x2e7ca8d5,
0xae999fd9,0xb000a814,0xaf6eaee9,0x2c872f91,0xa993afa0,0x2ed0a875,0x2cb0a875,0xaf46ad27,0x2ff42c32,0xab5e2ddc,0x2d272fff,0x2ff42515,
0xa44e2d96,0x9fd9afd4,0xaf30a6a1,0xae5e29f1,0x2814ad27,0x2dfeabb7,0x2ffc2d00,0xae5eae1f,0x2e992f80,0xaa4e2e7c,0xaa4e2c32,0x2fd42aaa,
0xae7c1648,0x9cb6afdd,0xaddcafd4,0xafc91648,0xa875af91,0x2b5e2fbc,0x2f1a244e,0x2e3fab05,0x2b052ff4,0xa44e2fa0,0xafbca8d5,0x2f912bb7,
0xb000ac32,0xa6a1afff,0x25dbaddc,0xb000a515,0x2aaaac5d,0x2c322f6e,0x2e7c2f6e,0x2f80a5db,0x2d272fed,0xae3fadfe,0xaf029fd9,0xae1f2c07,
0xaf5aae5e,0xac5daf30,0x2eb59fd9,0xb000a44e,0x2e7ca30e,0x2ddc2e1f,0x1cb62f1a,0x2fc9a30e,0x217e2f46,0xaf02acb0,0xaf02aed0,0xaf1a2993,
0xaf30ae99,0x2fbc29f1,0x2ee99648,0x2dfeac87,0x2fa02515,0x2faf2993,0xad002aaa,0x2fa0a765,0xa9342d96,0xafeda6a1,0xa814afd4,0xaf3029f1,
0xac87afed,0x30001fd9,0x2f6e2dfe,0x2e99ac07,0x2fff2bb7,0xafe6217e,0xaed0217e,0xaddc2d00,0xac322c87,0xaf462a4e,0x2993adba,0xae7c2c87,
0xa875afed,0x2f1aab05,0x2b5e2ffc,0x2e3facd8,0x2f302e1f,0xaee92bb7,0xafbcad00,0xadfe2d27,0xaf6e9cb6,0x2eb5ac32,0x2eb5a515,0x2dbaad72,
0x2aaaaf5a,0x2ed0ae99,0x2cb0ae99,0xaf802d96,0xab5e2f30,0xafaf244e,0xad002e5e,0x2f1a1fd9,0x2c07af02,0x2b052d27,0x2d4dae1f,0xa814ae3f,
0xac5d2ed0,0x29f1afff,0xad962ddc,0xac5d2fe6,0x28752f80,0xa8d52fe6,0xa8d52fc9,0x2e3faf46,0xa44eafd4,0x2f91adba,0x2b05af6e,0xafbc26a1,
0x96482ffc,0xae99a44e,0xac872ee9,0x29f12d4d,0x2515aff8,0x1cb62f02,0x2d72ae3f,0x2c32aff8,0xaeb5ab05,0xaa4eacd8,0x9648afed,0xac5d2ffc,
0x2d722d27,0xacb02ff4,0xa7652ff4,0x2fffab5e,0xabb7ae7c,0x2ff8aaaa,0x2b5eaf80,0xabb7ac32,0x28142f6e,0xab05ac87,0xad4d2e99,0xac073000,
0x2feda8d5,0x2f30a30e,0x29342f02,0x2814afa0,0xafd49cb6,0x1648aed0,0x1648afe6,0xafdd2d72,0x2ed029f1,0xaf462eb5,0xa9932fdd,0x2cb029f1,
0xad00ad4d,0x2e1f244e,0x2d27aee9,0x2bb7affc,0xad4d2f02,0xafbc2e1f,0xacd8ad27,0x1fd92e3f,0x2f5aacb0,0x2c872993,0x26a12f46,0x2f5aaed0,
0xafff25db,0x2cb0b000,0x2765b000,0xad72a6a1,0x2f1a2814,0xafaf2934,0xad002f30,0xab5e2fed,0x1648afbc,0x2c87affc,0x2e992934,0xa9f1ac07,
0xac322faf,0xaf8028d5,0xaaaaae1f,0xae7c2faf,0x2f1aad72,0xa30e2ed0,0xa30e2fe6,0x2e1f1cb6,0xaffc26a1,0x2fedadba,0x2cd8af6e,0x2b05afd4,
0x2d272c32,0x230e2d72,0xafaf1cb6,0x2d272515,0x9fd9af6e,0x2fbcae99,0x2cd82c87,0x2d4db000,0xac5d2fbc,0xaa4eab05,0x9648af91,0xaeb5244e,
0x2f80ad00,0xaed02fa0,0xacb02fa0,0xaaaa2faf,0xafe626a1,0xaddc1648,0x2fffaa4e,0xaed026a1,0x2d002c07,0xad272ffc,0xae1fa934,0xabb72fbc,
0x1fd9afa0,0x2e5ea30e,0x244e2f02,0x2f30a8d5,0xadba2f46,0x2c87afe6,0x2c87afc9,0x2a4eaf80,0x2fffad96,0x2e7cac5d,0x2fc9ac5d,0xad7229f1,
0x217eadfe,0x2ff4afbc,0x2875aee9,0xaff82f30,0xafed2d00,0x2d4daf1a,0xaf912b5e,0xae5e2faf,0xa5db2e7c,0x9648a993,0xa9f12f46,0xa5db2c32,
0xae3f2fff,0xaff82fc9,0xaff82e7c,0x2f02ad72,0x2c0725db,0xadfe2f5a,0x9fd92d96,0x2fedafdd,0x2f6eaf91,0xa6a12c07,0x2fd4acd8,0x2dbaaf30,
0xa765ab5e,0x2aaaa30e,0x2993af02,0x2515ab5e,0x25dbadfe,0x2d96aee9,0x2f5aafbc,0xafdd2f30,0xaf462b5e,0x2765abb7,0xa515abb7,0xaf802ff8,
0xad002fc9,0xa8d51cb6,0xaff82ddc,0xad002e7c,0x2cd81648,0xadfe2c5d,0xa9342eb5,0xa44e2a4e,0x2c07217e,0x9fd92875,0xadfe2ff4,0x2fedaff8,
0x2fddaf46,0x29f1a515,0x29f12765,0x2eb5af80,0x2515ad96,0x2ddcac87,0x2fffaeb5,0x2c32ad96,0xaf022b05,0x2fa0aee9,0x28d5ae5e,0x230ea934,
0xaf912d00,0xacd82b5e,0x2c07af1a,0xaf302faf,0xad962fc9,0xaeb52ddc,0xac871cb6,0xad962e7c,0x299326a1,0xafc92f5a,0xafe62f5a,0xaaaa2c87,
0x2ff8ae5e,0xaff42ffc,0xa8752dfe,0xa17e2814,0x2f6eafed,0x2fd4af91,0xa6a12d4d,0x2dbaae5e,0x2515ad00,0x2fffaff8,0x2ddca8d5,0x2c32ad00,
0xae1f2993,0x2fafafe6,0x2fafafc9,0x28d5aaaa,0xaf912fdd,0x2ee9af5a,0x2814ad96,0x1fd9a5db,0xab5e2e7c,0xaf022f46,0xa30ea993,0xab5e2c32,
0x2b051648,0xae5e2eb5,0xaee92c5d,0xa9342a4e,0x2fddae5e,0xad962dfe,0xaf5a2ffc,0xa5db2814,0x2ddcafaf,0xacb02d27,0xa7652d27,0x9cb6230e,
0xa765a5db,0x2993a9f1,0x2aaa9648,0x2515a5db,0xaf022cd8,0x28d5a934,0x2fa0adfe,0x230ea44e,0xaf912ff8,0x2814a875,0x2ee9aff4,0x1fd9a17e,
0xaa4e2ddc,0x26a1a765,0x26a1acb0,0x16489cb6,0x9d7f9e49,0xaddcaeb3,0x12480000,0x22ad0000,0x9bdb9cb6,0xac2ead04,0x18b61648,0x290226ad,
0x98b69a49,0xa902aaaf,0x1bdb1a49,0x2c2e2aaf,0x92489648,0xa2ada6ad,0x1d7f1cb6,0x2ddc2d04,0xa420a4b7,0xae8daf7f,0x18b60000,0x23760000,
0xa1e4a312,0xacacad9c,0x1f121cb6,0x29992777,0x9f12a0b6,0xa999ab78,0x21e420b6,0x2cac2b78,0x98b69cb6,0xa376a777,0x24202312,0x2e8d2d9c,
0xa6e0a7db,0xaf3fb025,0x1bdb0000,0x24200000,0xa4e9a5e4,0xad2aae34,0x21e41fdb,0x2a312820,0xa1e4a3db,0xaa31ac21,0x24e923db,0x2d2a2c21,
0x9bdb9fdb,0xa420a820,0x26e025e4,0x2f3f2e34,0xa8d0a980,0xaff2b08c,0x1d7f0000,0x24840000,0xa6e0a820,0xada9aecd,0x2420217f,0x2ac82885,
0xa420a580,0xaac8ac86,0x26e02580,0x2da92c86,0x9d7fa17f,0xa484a885,0x28d02820,0x2ff22ecd,0xaa31ab13,0xb052b0f3,0x1f120000,0x24e90000,
0xa86ba94e,0xae28af65,0x254d2312,0x2b5f28e9,0xa54da712,0xab5faceb,0x286b2712,0x2e282ceb,0x9f12a312,0xa4e9a8e9,0x2a31294e,0x30522f65,
0xab91ac54,0xb0acb15a,0x20520000,0x254d0000,0xa967aa7c,0xaea7affe,0x267b2452,0x2bf6294e,0xa67ba852,0xabf6ad50,0x29672852,0x2ea72d50,
0xa052a452,0xa54da94e,0x2b912a7c,0x30ac2ffe,0xac79ad1e,0xb106b1c1,0x211b0000,0x25b20000,0xaa63abab,0xaf26b04c,0x27a9251b,0x2c4729b3,
0xa7a9a91c,0xac47adb6,0x2a63291c,0x2f262db6,0xa11ba51b,0xa5b2a9b3,0x2c792bab,0x3106304c,0xad2aade8,0xb160b229,0x21e40000,0x26170000,
0xab5fac6d,0xafa5b099,0x286b25e4,0x2c932a17,0xa86ba9e5,0xac93ae1b,0x2b5f29e5,0x2fa52e1b,0xa1e4a5e4,0xa617aa17,0x2d2a2c6d,0x31603099,
0xb1bbb292,0xb44fb4f6,0x267b0000,0x28d00000,0xb012b0e6,0xb216b357,0x2cde2a7c,0x2f3f2cd2,0xacdeae80,0xaf3fb0d9,0x30122e80,0x321630d9,
0xa67baa7c,0xa8d0acd2,0x31bb30e6,0x344f3357,0xb216b2fb,0xb47eb52d,0x26e00000,0x29020000,0xb052b133,0xb257b3a7,0x2d2a2ae1,0x2f8c2d04,
0xad2aaee6,0xaf8cb10c,0x30522ee6,0x3257310c,0xa6e0aae1,0xa902ad04,0x32163133,0x347e33a7,0xb271b364,0xb4aeb565,0x27440000,0x29350000,
0xb092b181,0xb298b3f7,0x2d762b46,0x2fd82d37,0xad76af4c,0xafd8b140,0x30922f4c,0x32983140,0xa744ab46,0xa935ad37,0x32713181,0x34ae33f7,
0xb2cdb3cf,0xb4deb59d,0x27a90000,0x29670000,0xb0d2b1ce,0xb2dab423,0x2dc22bab,0x30122d6a,0xadc2afb2,0xb012b174,0x30d22fb2,0x32da3174,
0xa7a9abab,0xa967ad6a,0x32cd31ce,0x34de3423,0xb329b41d,0xb50eb5d6,0x28070000,0x29990000,0xb113b21c,0xb31cb44c,0x2e0e2c08,0x30392d9c,
0xae0eb00c,0xb039b1a7,0x3113300c,0x331c31a7,0xa807ac08,0xa999ad9c,0x3329321c,0x350e344c,0xb386b453,0xb53fb60f,0x28390000,0x29cc0000,
0xb153b26b,0xb35eb474,0x2e5a2c3a,0x305f2dcf,0xae5ab03f,0xb05fb1db,0x3153303f,0x335e31db,0xa839ac3a,0xa9ccadcf,0x3386326b,0x353f3474,
0xb3e3b489,0xb570b649,0x286b0000,0x29fe0000,0xb194b2b9,0xb3a0b49d,0x2ea72c6d,0x30852e02,0xaea7b072,0xb085b20f,0x31943072,0x33a0320f,
0xa86bac6d,0xa9feae02,0x33e332b9,0x3570349d,0xb420b4bf,0xb5a1b683,0x289e0000,0x2a310000,0xb1d5b308,0xb3e3b4c6,0x2ef32c9f,0x30ac2e34,
0xaef3b0a5,0xb0acb243,0x31d530a5,0x33e33243,0xa89eac9f,0xaa31ae34,0x34203308,0x35a134c6,0xb5d2b6be,0xb76fb857,0x2a630000,0x2bf60000,
0xb413b4ef,0xb523b642,0x30d22e67,0x32092ffe,0xb0d2b278,0xb209b40f,0x34133278,0x3523340f,0xaa63ae67,0xabf6affe,0x35d234ef,0x376f3642,
0xb604b6fa,0xb7a5b878,0x2a950000,0x2c140000,0xb434b519,0xb546b66d,0x30f92e9a,0x32303019,0xb0f9b2ac,0xb230b42a,0x343432ac,0x3546342a,
0xaa95ae9a,0xac14b019,0x36043519,0x37a5366d,0xb637b736,0xb7dbb899,0x2ac80000,0x2c2e0000,0xb456b542,0xb569b699,0x31202ecd,0x32573032,
0xb120b2e1,0xb257b445,0x345632e1,0x35693445,0xaac8aecd,0xac2eb032,0x36373542,0x37db3699,0xb66ab773,0xb809b8bb,0x2afa0000,0x2c470000,
0xb478b56c,0xb58cb6c6,0x31462f00,0x327e304c,0xb146b315,0xb27eb460,0x34783315,0x358c3460,0xaafaaf00,0xac47b04c,0x366a356c,0x380936c6,
0xb69db7b0,0xb825b8dd,0x2b2d0000,0x2c600000,0xb49ab596,0xb5afb6f2,0x316d2f32,0x32a53065,0xb16db34a,0xb2a5b47b,0x349a334a,0x35af347b,
0xab2daf32,0xac60b065,0x369d3596,0x382536f2,0xb6d1b7ee,0xb841b8ff,0x2b5f0000,0x2c790000,0xb4bcb5c1,0xb5d2b71f,0x31942f65,0x32cd307f,
0xb194b37f,0xb2cdb496,0x34bc337f,0x35d23496,0xab5faf65,0xac79b07f,0x36d135c1,0x3841371f,0xb705b817,0xb85db923,0x2b910000,0x2c930000,
0xb4deb5eb,0xb5f6b74d,0x31bb2f98,0x32f43099,0xb1bbb3b4,0xb2f4b4b1,0x34de33b4,0x35f634b1,0xab91af98,0xac93b099,0x370535eb,0x385d374d,
0xb73ab837,0xb87ab946,0x2bc40000,0x2cac0000,0xb500b616,0xb61ab77a,0x31e22fcb,0x331c30b2,0xb1e2b3e9,0xb31cb4cd,0x350033e9,0x361a34cd,
0xabc4afcb,0xacacb0b2,0x373a3616,0x387a377a,0xb897b96b,0xb98dbaa6,0x2cc50000,0x2d900000,0xb63eb7a8,0xb767b895,0x334330cc,0x3442319a,
0xb343b4e8,0xb442b5c8,0x363e34e8,0x376735c8,0xacc5b0cc,0xad90b19a,0x389737a8,0x398d3895,0xb8b4b990,0xb9aebad1,0x2cde0000,0x2da90000,
0xb662b7d7,0xb78db8ae,0x336b30e6,0x345631b4,0xb36bb504,0xb456b5e4,0x36623504,0x378d35e4,0xacdeb0e6,0xada9b1b4,0x38b437d7,0x39ae38ae,
0xb8d2b9b5,0xb9cfbafd,0x2cf80000,0x2dc20000,0xb687b803,0xb7b4b8c7,0x339330ff,0x346a31ce,0xb393b51f,0xb46ab601,0x3687351f,0x37b43601,
0xacf8b0ff,0xadc2b1ce,0x38d23803,0x39cf38c7,0xb8f0b9dc,0xb9f1bb29,0x2d110000,0x2ddc0000,0xb6acb81b,0xb7dbb8e1,0x33bb3119,0x347e31e8,
0xb3bbb53b,0xb47eb61e,0x36ac353b,0x37db361e,0xad11b119,0xaddcb1e8,0x38f0381b,0x39f138e1,0xb90fba02,0xba14bb57,0x2d2a0000,0x2df50000,
0xb6d1b833,0xb801b8fb,0x33e33133,0x34933202,0xb3e3b557,0xb493b63a,0x36d13557,0x3801363a,0xad2ab133,0xadf5b202,0x390f3833,0x3a1438fb,
0xb92eba2a,0xba37bb86,0x2d440000,0x2e0e0000,0xb6f6b84b,0xb815b915,0x3405314d,0x34a7321c,0xb405b573,0xb4a7b657,0x36f63573,0x38153657,
0xad44b14d,0xae0eb21c,0x392e384b,0x3a373915,0xb94dba53,0xba5abbb6,0x2d5d0000,0x2e280000,0xb71bb863,0xb829b930,0x34193167,0x34bc3236,
0xb419b58f,0xb4bcb675,0x371b358f,0x38293675,0xad5db167,0xae28b236,0x394d3863,0x3a5a3930,0xb96dba7c,0xba7ebbe7,0x2d760000,0x2e410000,
0xb741b87c,0xb83db94b,0x342e3181,0x34d03250,0xb42eb5ab,0xb4d0b692,0x374135ab,0x383d3692,0xad76b181,0xae41b250,0x396d387c,0x3a7e394b,
0xa17fa248,0xb1cfb2a1,0x16480000,0x26ad0000,0x9fdba0b6,0xb029b0fd,0x1cb61a48,0x2d002aac,0x9cb69e48,0xad00aeaa,0x1fdb1e48,0x30292eaa,
0x96489a48,0xa6adaaac,0x217f20b6,0x31cf30fd,0xa81fa8b6,0xb27cb365,0x1cb60000,0x27760000,0xa5e4a711,0xb0a6b191,0x231120b6,0x2d972b75,
0xa311a4b6,0xad97af72,0x25e424b6,0x30a62f72,0x9cb6a0b6,0xa776ab75,0x281f2711,0x327c3191,0xaadeabd9,0xb328b414,0x1fdb0000,0x281f0000,
0xa8e8a9e3,0xb122b226,0x25e423db,0x2e2d2c1f,0xa5e4a7da,0xae2db01d,0x28e827da,0x3122301d,0x9fdba3db,0xa81fac1f,0x2ade29e3,0x33283226,
0xaccead7e,0xb3d3b475,0x217f0000,0x28840000,0xaadeac1f,0xb19eb2b9,0x281f257f,0x2ec32c83,0xa81fa97f,0xaec3b080,0x2ade297f,0x319e3080,
0xa17fa57f,0xa884ac83,0x2cce2c1f,0x33d332b9,0xae2daf0e,0xb43eb4d5,0x23110000,0x28e80000,0xac6aad4c,0xb219b34c,0x294d2711,0x2f592ce7,
0xa94dab11,0xaf59b0e4,0x2c6a2b11,0x321930e4,0xa311a711,0xa8e8ace7,0x2e2d2d4c,0x343e334c,0xaf8bb04e,0xb493b534,0x24520000,0x294d0000,
0xad65ae78,0xb294b3df,0x2a7a2852,0x2fef2d4c,0xaa7aac51,0xafefb147,0x2d652c51,0x32943147,0xa452a852,0xa94dad4c,0x2f8b2e78,0x349333df,
0xb074b115,0xb4e7b593,0x251b0000,0x29b10000,0xae5fafa4,0xb30fb438,0x2ba7291b,0x30422db0,0xaba7ad1a,0xb042b1aa,0x2e5f2d1a,0x330f31aa,
0xa51ba91b,0xa9b1adb0,0x30742fa4,0x34e73438,0xb122b1db,0xb53ab5f1,0x25e40000,0x2a160000,0xaf59b067,0xb389b481,0x2c6a29e3,0x308d2e14,
0xac6aade2,0xb08db20d,0x2f592de2,0x3389320d,0xa5e4a9e3,0xaa16ae14,0x31223067,0x353a3481,0xb58db64e,0xb805b887,0x2a7a0000,0x2cce0000,
0xb402b4c9,0xb5dfb6f9,0x30d72e78,0x332830cb,0xb0d7b26f,0xb328b4bd,0x3402326f,0x35df34bd,0xaa7aae78,0xacceb0cb,0x358d34c9,0x380536f9,
0xb5dfb6aa,0xb82ab8b0,0x2ade0000,0x2d000000,0xb43eb511,0xb61ab73d,0x31222edc,0x337130fd,0xb122b2d2,0xb371b4ed,0x343e32d2,0x361a34ed,
0xaadeaedc,0xad00b0fd,0x35df3511,0x382a373d,0xb631b705,0xb850b8d8,0x2b430000,0x2d330000,0xb47bb558,0xb654b780,0x316c2f40,0x33ba312e,
0xb16cb334,0xb3bab51d,0x347b3334,0x3654351d,0xab43af40,0xad33b12e,0x36313558,0x38503780,0xb682b75e,0xb874b900,0x2ba70000,0x2d650000,
0xb4b7b59f,0xb68db7c2,0x31b62fa4,0x34023160,0xb1b6b396,0xb402b54c,0x34b73396,0x368d354c,0xaba7afa4,0xad65b160,0x3682359f,0x387437c2,
0xb6d2b7b7,0xb899b927,0x2c060000,0x2d970000,0xb4f3b5e5,0xb6c6b802,0x32013004,0x34263191,0xb201b3f7,0xb426b57c,0x34f333f7,0x36c6357c,
0xac06b004,0xad97b191,0x36d235e5,0x38993802,0xb721b807,0xb8bcb94d,0x2c380000,0x2dc90000,0xb52fb62b,0xb6ffb822,0x324b3036,0x344b31c3,
0xb24bb42c,0xb44bb5ab,0x352f342c,0x36ff35ab,0xac38b036,0xadc9b1c3,0x3721362b,0x38bc3822,0xb76fb832,0xb8e0b972,0x2c6a0000,0x2dfb0000,
0xb56ab670,0xb737b842,0x32943067,0x346f31f4,0xb294b45d,0xb46fb5da,0x356a345d,0x373735da,0xac6ab067,0xadfbb1f4,0x376f3670,0x38e03842,
0xb7bdb85d,0xb902b996,0x2c9c0000,0x2e2d0000,0xb5a5b6b5,0xb76fb862,0x32de3099,0x34933226,0xb2deb48d,0xb493b608,0x35a5348d,0x376f3608,
0xac9cb099,0xae2db226,0x37bd36b5,0x39023862,0xb924b9ba,0xba1dbab5,0x2e5f0000,0x2fef0000,0xb7a6b881,0xb8a8b96d,0x34b73257,0x35d433df,
0xb4b7b637,0xb5d4b7a1,0x37a63637,0x38a837a1,0xae5fb257,0xafefb3df,0x39243881,0x3a1d396d,0xb946b9dc,0xba39bad0,0x2e910000,0x30100000,
0xb7ddb8a0,0xb8c1b989,0x34db3288,0x35f73408,0xb4dbb665,0xb5f7b7cd,0x37dd3665,0x38c137cd,0xae91b288,0xb010b408,0x394638a0,0x3a393989,
0xb966b9fe,0xba54bae9,0x2ec30000,0x30290000,0xb80ab8bf,0xb8dbb9a4,0x34ff32b9,0x361a3420,0xb4ffb693,0xb61ab7f9,0x380a3693,0x38db37f9,
0xaec3b2b9,0xb029b420,0x396638bf,0x3a5439a4,0xb986ba1f,0xba6fbb02,0x2ef50000,0x30420000,0xb825b8dd,0xb8f3b9be,0x352332ea,0x363c3438,
0xb523b6c1,0xb63cb812,0x382536c1,0x38f33812,0xaef5b2ea,0xb042b438,0x398638dd,0x3a6f39be,0xb9a6ba3f,0xba89bb1a,0x2f270000,0x305b0000,
0xb840b8fb,0xb90cb9d8,0x3546331b,0x365f3451,0xb546b6ee,0xb65fb828,0x384036ee,0x390c3828,0xaf27b31b,0xb05bb451,0x39a638fb,0x3a8939d8,
0xb9c5ba5e,0xbaa2bb30,0x2f590000,0x30740000,0xb85ab918,0xb924b9f2,0x356a334c,0x36823469,0xb56ab71b,0xb682b83d,0x385a371b,0x3924383d,
0xaf59b34c,0xb074b469,0x39c53918,0x3aa239f2,0xb9e3ba7c,0xbababb46,0x2f8b0000,0x308d0000,0xb874b935,0xb93cba0b,0x358d337d,0x36a43481,
0xb58db748,0xb6a4b852,0x38743748,0x393c3852,0xaf8bb37d,0xb08db481,0x39e33935,0x3aba3a0b,0xba00ba99,0xbad1bb5a,0x2fbd0000,0x30a60000,
0xb88eb951,0xb954ba23,0x35b133ae,0x36c63499,0xb5b1b775,0xb6c6b867,0x388e3775,0x39543867,0xafbdb3ae,0xb0a6b499,0x3a003951,0x3ad13a23,
0xbae8bb6e,0xbb7fbbdd,0x30be0000,0x31850000,0xb96bba3b,0xba19bae6,0x36e834b1,0x37f33570,0xb6e8b87c,0xb7f3b91d,0x396b387c,0x3a19391d,
0xb0beb4b1,0xb185b570,0x3ae83a3b,0x3b7f3ae6,0xbafebb80,0xbb8ebbe6,0x30d70000,0x319e0000,0xb982ba52,0xba2dbaf9,0x370a34c9,0x380a3587,
0xb70ab891,0xb80ab930,0x39823891,0x3a2d3930,0xb0d7b4c9,0xb19eb587,0x3afe3a52,0x3b8e3af9,0xbb13bb91,0xbb9cbbed,0x30f00000,0x31b60000,
0xb999ba69,0xba41bb0b,0x372c34e1,0x381a359f,0xb72cb8a6,0xb81ab943,0x399938a6,0x3a413943,0xb0f0b4e1,0xb1b6b59f,0x3b133a69,0x3b9c3b0b,
0xbb27bba0,0xbba9bbf4,0x31090000,0x31cf0000,0xb9afba7f,0xba54bb1d,0x374e34f9,0x382a35b6,0xb74eb8ba,0xb82ab956,0x39af38ba,0x3a543956,
0xb109b4f9,0xb1cfb5b6,0x3b273a7f,0x3ba93b1d,0xbb3abbaf,0xbbb5bbf8,0x31220000,0x31e80000,0xb9c5ba95,0xba67bb2e,0x376f3511,0x383a35ce,
0xb76fb8ce,0xb83ab969,0x39c538ce,0x3a673969,0xb122b511,0xb1e8b5ce,0x3b3a3a95,0x3bb53b2e,0xbb4cbbbc,0xbbc0bbfc,0x313b0000,0x32010000,
0xb9dabaaa,0xba7abb3e,0x37903529,0x384a35e5,0xb790b8e2,0xb84ab97b,0x39da38e2,0x3a7a397b,0xb13bb529,0xb201b5e5,0x3b4c3aaa,0x3bc03b3e,
0xbb5ebbc9,0xbbcbbbff,0x31530000,0x32190000,0xb9f0babf,0xba8cbb4e,0x37b23540,0x385a35fd,0xb7b2b8f6,0xb85ab98d,0x39f038f6,0x3a8c398d,
0xb153b540,0xb219b5fd,0x3b5e3abf,0x3bcb3b4e,0xbb6fbbd4,0xbbd4bc00,0x316c0000,0x32320000,0xba04bad3,0xba9ebb5d,0x37d23558,0x386a3614,
0xb7d2b909,0xb86ab99f,0x3a043909,0x3a9e399f,0xb16cb558,0xb232b614,0x3b6f3ad3,0x3bd43b5d,0x0,0x0,0x0,0x0,
0x2e1f0000,0x336431a8,0x33643400,0x2e1f31a8,0x31a80000,0x31a83400,0xb1a80000,0xb1a8b400,0x33640000,0xae1f31a8,0xae1fb400,0x336431a8,
0x34000000,0xb4000000,0x34000000,0xb4000000,0x33640000,0xae1fb1a8,0xae1f3400,0x3364b1a8,0x31a80000,0x31a8b400,0xb1a80000,0xb1a83400,
0x2e1f0000,0x3364b1a8,0x3364b400,0x2e1fb1a8,0x0,0x0,0x0,0x0,0xae1f0000,0xb36431a8,0xb3643400,0xae1f31a8,
0xb1a80000,0xb1a83400,0x31a80000,0x31a8b400,0xb3640000,0x2e1f31a8,0x2e1fb400,0xb36431a8,0xb4000000,0x34000000,0xb4000000,0x34000000,
0xb3640000,0x2e1fb1a8,0x2e1f3400,0xb364b1a8,0xb1a80000,0xb1a8b400,0x31a80000,0x31a83400,0xae1f0000,0xb364b1a8,0xb364b400,0xae1fb1a8,
0x0,0x0,0x0,0x0,0xae1f0000,0xb364b1a8,0xb364b400,0xae1fb1a8,0x31a80000,0x31a83400,0xb1a80000,0xb1a8b400,
0xb3640000,0x2e1fb1a8,0x2e1f3400,0xb364b1a8,0x34000000,0xb4000000,0x34000000,0xb4000000,0xb3640000,0x2e1f31a8,0x2e1fb400,0xb36431a8,
0x31a80000,0x31a8b400,0xb1a80000,0xb1a83400,0xae1f0000,0xb36431a8,0xb3643400,0xae1f31a8,0x0,0x0,0x0,0x0,
0x2e1f0000,0x3364b1a8,0x3364b400,0x2e1fb1a8,0xb1a80000,0xb1a83400,0x31a80000,0x31a8b400,0x33640000,0xae1fb1a8,0xae1f3400,0x3364b1a8,
0xb4000000,0x34000000,0xb4000000,0x34000000,0x33640000,0xae1f31a8,0xae1fb400,0x336431a8,0xb1a80000,0xb1a8b400,0x31a80000,0x31a83400,
0x2e1f0000,0x336431a8,0x33643400,0x2e1f31a8,0x34003400,0x34003400,0x34003400,0x34003400,0x33643400,0x2e1f31a8,0xae1f0000,0xb364b1a8,
0x31a83400,0xb1a80000,0xb1a8b400,0x31a80000,0x2e1f3400,0xb364b1a8,0x33640000,0xae1f31a8,0x3400,0xb400,0x3400,0xb400,
0xae1f3400,0x3364b1a8,0xb3640000,0x2e1f31a8,0xb1a83400,0x31a80000,0x31a8b400,0xb1a80000,0xb3643400,0xae1f31a8,0x2e1f0000,0x3364b1a8,
0xb4003400,0xb4003400,0xb4003400,0xb4003400,0xb3643400,0xae1f31a8,0x2e1f0000,0x3364b1a8,0xb1a83400,0x31a80000,0x31a8b400,0xb1a80000,
0xae1f3400,0x3364b1a8,0xb3640000,0x2e1f31a8,0x3400,0xb400,0x3400,0xb400,0x2e1f3400,0xb364b1a8,0x33640000,0xae1f31a8,
0x31a83400,0xb1a80000,0xb1a8b400,0x31a80000,0x33643400,0x2e1f31a8,0xae1f0000,0xb364b1a8,0x34003400,0x34003400,0x34003400,0x34003400,
0xb364b400,0xae1fb1a8,0x2e1f0000,0x336431a8,0x31a83400,0xb1a80000,0xb1a8b400,0x31a80000,0xae1fb400,0x336431a8,0xb3640000,0x2e1fb1a8,
0x3400,0xb400,0x3400,0xb400,0x2e1fb400,0xb36431a8,0x33640000,0xae1fb1a8,0xb1a83400,0x31a80000,0x31a8b400,0xb1a80000,
0x3364b400,0x2e1fb1a8,0xae1f0000,0xb36431a8,0xb4003400,0xb4003400,0xb4003400,0xb4003400,0x3364b400,0x2e1fb1a8,0xae1f0000,0xb36431a8,
0xb1a83400,0x31a80000,0x31a8b400,0xb1a80000,0x2e1fb400,0xb36431a8,0x33640000,0xae1fb1a8,0x3400,0xb400,0x3400,0xb400,
0xae1fb400,0x336431a8,0xb3640000,0x2e1fb1a8,0x31a83400,0xb1a80000,0xb1a8b400,0x31a80000,0xb364b400,0xae1fb1a8,0x2e1f0000,0x336431a8,
0x0,0x0,0x0,0x0,0xae1f0000,0xb364b1a8,0xb364b400,0xae1fb1a8,0xb1a80000,0xb1a8b400,0x31a80000,0x31a83400,
0xb3640000,0x2e1fb1a8,0x2e1f3400,0xb364b1a8,0xb4000000,0x34000000,0xb4000000,0x34000000,0xb3640000,0x2e1f31a8,0x2e1fb400,0xb36431a8,
0xb1a80000,0xb1a83400,0x31a80000,0x31a8b400,0xae1f0000,0xb36431a8,0xb3643400,0xae1f31a8,0x0,0x0,0x0,0x0,
0x2e1f0000,0x3364b1a8,0x3364b400,0x2e1fb1a8,0x31a80000,0x31a8b400,0xb1a80000,0xb1a83400,0x33640000,0xae1fb1a8,0xae1f3400,0x3364b1a8,
0x34000000,0xb4000000,0x34000000,0xb4000000,0x33640000,0xae1f31a8,0xae1fb400,0x336431a8,0x31a80000,0x31a83400,0xb1a80000,0xb1a8b400,
0x2e1f0000,0x336431a8,0x33643400,0x2e1f31a8,0x0,0x0,0x0,0x0,0x2e1f0000,0x336431a8,0x33643400,0x2e1f31a8,
0xb1a80000,0xb1a8b400,0x31a80000,0x31a83400,0x33640000,0xae1f31a8,0xae1fb400,0x336431a8,0xb4000000,0x34000000,0xb4000000,0x34000000,
0x33640000,0xae1fb1a8,0xae1f3400,0x3364b1a8,0xb1a80000,0xb1a83400,0x31a80000,0x31a8b400,0x2e1f0000,0x3364b1a8,0x3364b400,0x2e1fb1a8,
0x0,0x0,0x0,0x0,0xae1f0000,0xb36431a8,0xb3643400,0xae1f31a8,0x31a80000,0x31a8b400,0xb1a80000,0xb1a83400,
0xb3640000,0x2e1f31a8,0x2e1fb400,0xb36431a8,0x34000000,0xb4000000,0x34000000,0xb4000000,0xb3640000,0x2e1fb1a8,0x2e1f3400,0xb364b1a8,
0x31a80000,0x31a83400,0xb1a80000,0xb1a8b400,0xae1f0000,0xb364b1a8,0xb364b400,0xae1fb1a8,
};

typedef CUresult (*EncodeFn)(CUtensorMap*, CUtensorMapDataType, cuuint32_t, void*, const cuuint64_t*, const cuuint64_t*,
                             const cuuint32_t*, const cuuint32_t*, CUtensorMapInterleave, CUtensorMapSwizzle,
                             CUtensorMapL2promotion, CUtensorMapFloatOOBfill);

}

extern "C" void kernel_launch(void* const* d_in, const int* in_sizes, int n_in, void* d_out, int out_size) {
    Params p;
    p.x = (const __nv_bfloat16*)d_in[0];
    p.lar = (const __nv_bfloat16*)d_in[1];
    p.aim = (const __nv_bfloat16*)d_in[2];
    p.cr = (const __nv_bfloat16*)d_in[3];
    p.ci = (const __nv_bfloat16*)d_in[4];
    p.logdt = (const __nv_bfloat16*)d_in[5];
    p.dskip = (const __nv_bfloat16*)d_in[6];
    p.wr = (const __nv_bfloat16*)d_in[8];
    p.out = (__nv_bfloat16*)d_out;
    cudaGetSymbolAddress((void**)&p.sc, g_scratch);
    cudaGetSymbolAddress((void**)&p.tab, g_tab);

    void* fn = nullptr;
    cudaDriverEntryPointQueryResult qr;
    cudaGetDriverEntryPoint("cuTensorMapEncodeTiled", &fn, cudaEnableDefault, &qr);
    EncodeFn enc = (EncodeFn)fn;
    CUtensorMap tm_x, tm_g, tm_d;
    const cuuint32_t es[5] = {1, 1, 1, 1, 1};
    {
        const cuuint64_t gd[4] = {1024, 128, 8, 2}, gs[3] = {32768, 4096, 2048};
        const cuuint32_t bx[4] = {16, 64, 4, 1};
        enc(&tm_x, CU_TENSOR_MAP_DATA_TYPE_BFLOAT16, 4, d_in[0], gd, gs, bx, es, CU_TENSOR_MAP_INTERLEAVE_NONE,
            CU_TENSOR_MAP_SWIZZLE_NONE, CU_TENSOR_MAP_L2_PROMOTION_NONE, CU_TENSOR_MAP_FLOAT_OOB_FILL_NONE);
    }
    {
        char *wg = (char*)d_in[9], *wu = (char*)d_in[10];
        p.up_first = wu < wg;
        const cuuint64_t gd[3] = {3584, 1024, 2}, gs[2] = {7168, (cuuint64_t)(p.up_first ? wg - wu : wu - wg)};
        const cuuint32_t bx[3] = {64, 64, 2};
        enc(&tm_g, CU_TENSOR_MAP_DATA_TYPE_BFLOAT16, 3, p.up_first ? wu : wg, gd, gs, bx, es, CU_TENSOR_MAP_INTERLEAVE_NONE,
            CU_TENSOR_MAP_SWIZZLE_128B, (CUtensorMapL2promotion)GPROMO, CU_TENSOR_MAP_FLOAT_OOB_FILL_NONE);
    }
    {
        const cuuint64_t gd[3] = {64, 3584, 16}, gs[2] = {2048, 128};
        const cuuint32_t bx[3] = {64, 64, 2};
        enc(&tm_d, CU_TENSOR_MAP_DATA_TYPE_BFLOAT16, 3, d_in[11], gd, gs, bx, es, CU_TENSOR_MAP_INTERLEAVE_NONE,
            CU_TENSOR_MAP_SWIZZLE_128B, (CUtensorMapL2promotion)DPROMO, CU_TENSOR_MAP_FLOAT_OOB_FILL_NONE);
    }
    cudaFuncSetAttribute(fused_kernel, cudaFuncAttributeMaxDynamicSharedMemorySize, SM_TOTAL + 256);
    fused_kernel<<<128, NTHREADS, SM_TOTAL + 256>>>(p, tm_x, tm_g, tm_d);
}
```
